```python
import torch

def _softmax(x, axis=-1):
    return torch.softmax(x, dim=axis)
def _gelu(x):
    return torch.nn.functional.gelu(x, approximate="tanh")
def _silu(x):
    return torch.nn.functional.silu(x)
def _sigmoid(x):
    return torch.sigmoid(x)
def _layernorm(x, axis=-1, eps=1e-5):
    m = x.mean(dim=axis, keepdim=True)
    v = x.var(dim=axis, keepdim=True, unbiased=False)
    return (x - m) / torch.sqrt(v + eps)
def _scatter_add(tgt, idx, src, axis=0):
    return tgt.clone().index_add_(axis, idx, src)
def _segment_sum(src, seg, n):
    out = torch.zeros((n,) + src.shape[1:], dtype=src.dtype)
    return out.index_add_(0, seg, src)
def _pad(x, pw):
    flat = tuple(v for pair in reversed(pw) for v in pair)
    return torch.nn.functional.pad(x, flat)

kernel_name = 'gated_mix__ssm_conv_s5__dense_activation_gelu__prompt'

def setup_inputs():

    _w = (lambda a: (lambda t: t.to(torch.bfloat16) if t.is_floating_point() else t)(torch.as_tensor(a)))
    def _A_setup():
        B, S, D = 1, 2048, 512
        P = D
        Lambda_re = -0.5 * (lambda _x: torch.exp(torch.as_tensor(_x)))((lambda *s: torch.randn(*s, dtype=torch.bfloat16) * 0.2)(P))
        Lambda_im = (lambda *s: torch.randn(*s, dtype=torch.bfloat16) * 0.8)(P) * 1.0
        B_re = (lambda *s: torch.randn(*s, dtype=torch.bfloat16) * 0.2)(P, D) * (D ** -0.5)
        B_im = (lambda *s: torch.randn(*s, dtype=torch.bfloat16) * 0.2)(P, D) * (D ** -0.5)
        C_re = (lambda *s: torch.randn(*s, dtype=torch.bfloat16) * 0.2)(D, P) * (P ** -0.5)
        C_im = (lambda *s: torch.randn(*s, dtype=torch.bfloat16) * 0.2)(D, P) * (P ** -0.5)
        log_dt = (lambda *s: torch.randn(*s, dtype=torch.bfloat16) * 0.2)(P) * 0.3 - 2.0
        Dskip = (lambda *s: torch.randn(*s, dtype=torch.bfloat16) * 0.05)(D)
        return {
            "x": _w((lambda *s: torch.randn(*s, dtype=torch.bfloat16) * 0.05)(B, S, D)),
            "Lambda_re": _w(Lambda_re),
            "Lambda_im": _w(Lambda_im),
            "B_re": _w(B_re),
            "B_im": _w(B_im),
            "C_re": _w(C_re),
            "C_im": _w(C_im),
            "log_dt": _w(log_dt),
            "Dskip": _w(Dskip),
        }
    _A_in = _A_setup()

    def _B_setup():
        B, S, D, F = 1, 2048, 512, 1792
        return {
            "x": _w((lambda *s: torch.randn(*s, dtype=torch.bfloat16) * 0.05)(B, S, D)),
            "w1": _w((lambda *s: torch.randn(*s, dtype=torch.bfloat16) * 3.2)(D, F) * (D ** -0.5)),
            "b1": _w((lambda *s: torch.randn(*s, dtype=torch.bfloat16) * 3.2)(F) * 0.01),
            "w2": _w((lambda *s: torch.randn(*s, dtype=torch.bfloat16) * 0.1)(F, D) * (F ** -0.5)),
            "b2": _w((lambda *s: torch.randn(*s, dtype=torch.bfloat16) * 0.2)(D) * 0.01),
        }
    _B_in = _B_setup()

    return {
        "A_x": _A_in["x"],
        "A_Lambda_re": _A_in["Lambda_re"],
        "A_Lambda_im": _A_in["Lambda_im"],
        "A_B_re": _A_in["B_re"],
        "A_B_im": _A_in["B_im"],
        "A_C_re": _A_in["C_re"],
        "A_C_im": _A_in["C_im"],
        "A_log_dt": _A_in["log_dt"],
        "A_Dskip": _A_in["Dskip"],
        "B_x": _B_in["x"],
        "B_w1": _B_in["w1"],
        "B_b1": _B_in["b1"],
        "B_w2": _B_in["w2"],
        "B_b2": _B_in["b2"],
        "gate_w": _w((lambda *s: torch.randn(*s, dtype=torch.bfloat16) * 0.05)(512) * 16.0),
    }

def reference(A_x, A_Lambda_re, A_Lambda_im, A_B_re, A_B_im, A_C_re, A_C_im, A_log_dt, A_Dskip, B_x, B_w1, B_b1, B_w2, B_b2, gate_w):
    def _A_ref(x, Lambda_re, Lambda_im, B_re, B_im, C_re, C_im, log_dt, Dskip):
        Bsz, L, H = x.shape
        Lam = Lambda_re + 1j * Lambda_im
        Bmat = B_re + 1j * B_im
        Cmat = C_re + 1j * C_im
        dt = torch.exp(log_dt)
        Lam_bar = torch.exp(dt * Lam)
        B_bar = ((Lam_bar - 1.0) / Lam)[:, None] * Bmat
        Bu = torch.einsum("bld,pd->blp", x + 0j, B_bar)
        h = torch.zeros_like(Bu[:, 0, :])
        hs = []
        for t in range(L):
            h = Lam_bar[None, :] * h + Bu[:, t, :]
            hs.append(h)
        hseq = torch.stack(hs, 1)
        y = 2.0 * torch.einsum("blp,dp->bld", hseq, Cmat).real + x * Dskip[None, None, :]
        return y

    def _B_ref(x, w1, b1, w2, b2):
        h = torch.einsum("bsd,df->bsf", x, w1) + b1
        h = _gelu(h)
        return torch.einsum("bsf,fd->bsd", h, w2) + b2

    x = A_x
    g = _sigmoid((x * gate_w).sum(-1, keepdims=True))
    a = _A_ref(x, A_Lambda_re, A_Lambda_im, A_B_re, A_B_im, A_C_re, A_C_im, A_log_dt, A_Dskip)
    b = _B_ref(x, B_w1, B_b1, B_w2, B_b2)
    return g * a + (1 - g) * b
```

```cpp
#include <cuda_runtime.h>
#include <cuda_bf16.h>
#include <cuda.h>
#include <stdint.h>

namespace {

constexpr int SEQ = 2048, DM = 512, FF = 1792;
constexpr int NSLOT = 6;
constexpr uint32_t OFF_X = 0, OFF_RING = 131072, OFF_MISC = 229376;
constexpr uint32_t OFF_XFULL = OFF_MISC, OFF_FULL = OFF_XFULL + 64, OFF_EMPTY = OFF_FULL + 48, OFF_GBAR = OFF_EMPTY + 48,
                   OFF_CBAR = OFF_GBAR + 8, OFF_BBAR = OFF_CBAR + 8;
constexpr uint32_t OFF_GS = OFF_MISC + 256;
constexpr uint32_t OFF_CARRY = OFF_GS + 512;
constexpr uint32_t OFF_B1 = OFF_CARRY + 1024;
constexpr uint32_t SMEM_BYTES = OFF_B1 + 896;
static_assert(SMEM_BYTES <= 232448, "smem");

struct Maps { CUtensorMap x, bre, bim, w1a, w1b, w2, cre, cim; };

__device__ uint4 g_part[16 * 8 * 7 * 4 * 256];
__device__ float2 g_end[8 * 32 * 64];
__device__ unsigned g_epoch[128];
#define TS(role, i) do {} while (0)

__device__ __forceinline__ void mbar_init(uint32_t bar, uint32_t cnt) { asm volatile("mbarrier.init.shared::cta.b64 [%0], %1;" ::"r"(bar), "r"(cnt)); }
__device__ __forceinline__ void mbar_expect_tx(uint32_t bar, uint32_t bytes) { asm volatile("mbarrier.arrive.expect_tx.shared::cta.b64 _, [%0], %1;" ::"r"(bar), "r"(bytes) : "memory"); }
__device__ __forceinline__ void mbar_arrive(uint32_t bar) { asm volatile("mbarrier.arrive.shared::cta.b64 _, [%0];" ::"r"(bar) : "memory"); }
__device__ __forceinline__ void mbar_arrive_cl(uint32_t cbar) { asm volatile("mbarrier.arrive.shared::cluster.b64 _, [%0];" ::"r"(cbar) : "memory"); }
__device__ __forceinline__ void mbar_wait(uint32_t bar, uint32_t parity) {
  asm volatile(
      "{\n.reg .pred p;\n.reg .u32 c;\nmov.u32 c, 0;\n"
      "LAB_WAIT:\n"
      "mbarrier.try_wait.parity.shared::cta.b64 p, [%0], %1;\n"
      "@p bra LAB_DONE;\n"
      "add.u32 c, c, 1;\nsetp.lt.u32 p, c, 200000;\n@p bra LAB_WAIT;\n"
      "LAB_DONE:\n}" ::"r"(bar), "r"(parity) : "memory");
}
__device__ __forceinline__ void tma2d_mc(uint32_t dst, const CUtensorMap* m, int c0, int c1, uint32_t bar) {
  asm volatile("cp.async.bulk.tensor.2d.shared::cluster.global.mbarrier::complete_tx::bytes.multicast::cluster [%0], [%1, {%3,%4}], [%2], %5;"
               ::"r"(dst), "l"(m), "r"(bar), "r"(c0), "r"(c1), "h"((uint16_t)3) : "memory");
}
__device__ __forceinline__ void tma3d_mc(uint32_t dst, const CUtensorMap* m, int c0, int c1, int c2, uint32_t bar) {
  asm volatile("cp.async.bulk.tensor.3d.shared::cluster.global.mbarrier::complete_tx::bytes.multicast::cluster [%0], [%1, {%3,%4,%5}], [%2], %6;"
               ::"r"(dst), "l"(m), "r"(bar), "r"(c0), "r"(c1), "r"(c2), "h"((uint16_t)3) : "memory");
}
__device__ __forceinline__ void tma5d(uint32_t dst, const CUtensorMap* m, int c0, int c4, uint32_t bar) {
  asm volatile("cp.async.bulk.tensor.5d.shared::cluster.global.mbarrier::complete_tx::bytes [%0], [%1, {%3,%5,%5,%5,%4}], [%2];"
               ::"r"(dst), "l"(m), "r"(bar), "r"(c0), "r"(c4), "r"(0) : "memory");
}
__device__ __forceinline__ void l2_prefetch(const void* p, uint32_t bytes) { asm volatile("cp.async.bulk.prefetch.L2.global [%0], %1;" ::"l"(p), "r"(bytes) : "memory"); }
__device__ __forceinline__ void wg_fence() { asm volatile("wgmma.fence.sync.aligned;" ::: "memory"); }
__device__ __forceinline__ void wg_commit() { asm volatile("wgmma.commit_group.sync.aligned;" ::: "memory"); }
template <int N> __device__ __forceinline__ void wg_wait() { asm volatile("wgmma.wait_group.sync.aligned %0;" ::"n"(N) : "memory"); }
template <int N> __device__ __forceinline__ void reg_fence(float (&d)[N]) {
#pragma unroll
  for (int i = 0; i < N; i++) asm volatile("" : "+f"(d[i])::"memory");
}
__device__ __forceinline__ void bar_sync(int id, int n) { asm volatile("bar.sync %0, %1;" ::"r"(id), "r"(n) : "memory"); }
__device__ __forceinline__ void bar_arrive(int id, int n) { asm volatile("bar.arrive %0, %1;" ::"r"(id), "r"(n) : "memory"); }
constexpr uint32_t DH128 = (1024 >> 4) | (1u << 30), DH64 = (512 >> 4) | (2u << 30);
__host__ __device__ constexpr uint32_t lbo(uint32_t bytes) { return (bytes >> 4) << 20; }
__device__ __forceinline__ uint32_t pack_bf16(float lo, float hi) { uint32_t r; asm("cvt.rn.bf16x2.f32 %0, %1, %2;" : "=r"(r) : "f"(hi), "f"(lo)); return r; }
__device__ __forceinline__ float bf_lo(uint32_t v) { return __uint_as_float(v << 16); }
__device__ __forceinline__ float bf_hi(uint32_t v) { return __uint_as_float(v & 0xffff0000u); }
__device__ __forceinline__ float bf_ld(const __nv_bfloat16* p) { return __bfloat162float(__ldg(p)); }
__device__ __forceinline__ float2 lds_f2(uint32_t a) { float2 v; asm volatile("ld.shared.v2.f32 {%0,%1}, [%2];" : "=f"(v.x), "=f"(v.y) : "r"(a)); return v; }
__device__ __forceinline__ float lds_f(uint32_t a) { float v; asm volatile("ld.shared.f32 %0, [%1];" : "=f"(v) : "r"(a)); return v; }
__device__ __forceinline__ uint32_t lds_u(uint32_t a) { uint32_t v; asm volatile("ld.shared.u32 %0, [%1];" : "=r"(v) : "r"(a)); return v; }
__device__ __forceinline__ uint4 lds_u4(uint32_t a) { uint4 v; asm volatile("ld.shared.v4.u32 {%0,%1,%2,%3}, [%4];" : "=r"(v.x), "=r"(v.y), "=r"(v.z), "=r"(v.w) : "r"(a)); return v; }
__device__ __forceinline__ void st_b128(uint4* p, uint32_t a, uint32_t b, uint32_t c, uint32_t d) {
  asm volatile("{.reg .b64 l, h; .reg .b128 v; mov.b64 l, {%1,%2}; mov.b64 h, {%3,%4}; mov.b128 v, {l,h}; st.relaxed.gpu.global.b128 [%0], v;}"
               ::"l"(p), "r"(a), "r"(b), "r"(c), "r"(d) : "memory");
}
__device__ __forceinline__ void ld_b128(const uint4* p, uint32_t& a, uint32_t& b, uint32_t& c, uint32_t& d) {
  asm volatile("{.reg .b64 l, h; .reg .b128 v; ld.relaxed.gpu.global.b128 v, [%4]; mov.b128 {l,h}, v; mov.b64 {%0,%1}, l; mov.b64 {%2,%3}, h;}"
               : "=r"(a), "=r"(b), "=r"(c), "=r"(d) : "l"(p) : "memory");
}
__device__ __forceinline__ float tanh_fast(float x) { float y; asm("tanh.approx.f32 %0, %1;" : "=f"(y) : "f"(x)); return y; }
__device__ __forceinline__ float gelu_s(float v, float sh) {
  float p = fmaf(v * v, 0.0356774081363f, 0.7978845608029f);
  float t = tanh_fast(v * p);
  float hs = v * sh;
  return fmaf(hs, t, hs);
}
struct cplx { float re, im; };
__device__ __forceinline__ cplx cmul(cplx a, cplx b) { return {fmaf(a.re, b.re, -a.im * b.im), fmaf(a.re, b.im, a.im * b.re)}; }
__device__ __forceinline__ cplx cfma(cplx a, cplx b, cplx c) {
  return {fmaf(a.re, b.re, fmaf(-a.im, b.im, c.re)), fmaf(a.re, b.im, fmaf(a.im, b.re, c.im))};
}
__device__ __forceinline__ cplx make_lam(float lre, float lim, float ldt) {
  float dt = __bfloat162float(__float2bfloat16_rn(expf(ldt)));
  float mag = expf(dt * lre), sn, cs;
  sincospif(dt * lim * 0.31830988618379067f, &sn, &cs);
  return {mag * cs, mag * sn};
}

template<int TA,int TB,uint32_t AH,uint32_t BH> __device__ __forceinline__ void wgmma_n64_ss(float (&d)[32], uint32_t al, uint32_t ao, uint32_t bl, uint32_t bo, int scale_d){
  asm volatile("{.reg .pred p; .reg .b32 t, v; .reg .b64 da, db; setp.ne.b32 p, %36, 0; add.u32 t, %32, %33; mov.b64 da, {t, %39}; add.u32 v, %34, %35; mov.b64 db, {v, %40};\n"
   "wgmma.mma_async.sync.aligned.m64n64k16.f32.bf16.bf16 {%0,%1,%2,%3,%4,%5,%6,%7,%8,%9,%10,%11,%12,%13,%14,%15,%16,%17,%18,%19,%20,%21,%22,%23,%24,%25,%26,%27,%28,%29,%30,%31}, da, db, p, 1, 1, %37, %38;}"
   : "+f"(d[0]),"+f"(d[1]),"+f"(d[2]),"+f"(d[3]),"+f"(d[4]),"+f"(d[5]),"+f"(d[6]),"+f"(d[7]),"+f"(d[8]),"+f"(d[9]),"+f"(d[10]),"+f"(d[11]),"+f"(d[12]),"+f"(d[13]),"+f"(d[14]),"+f"(d[15]),"+f"(d[16]),"+f"(d[17]),"+f"(d[18]),"+f"(d[19]),"+f"(d[20]),"+f"(d[21]),"+f"(d[22]),"+f"(d[23]),"+f"(d[24]),"+f"(d[25]),"+f"(d[26]),"+f"(d[27]),"+f"(d[28]),"+f"(d[29]),"+f"(d[30]),"+f"(d[31])
   : "r"(al),"r"(ao >> 4),"r"(bl),"r"(bo >> 4),"r"(scale_d),"n"(TA),"n"(TB),"n"(AH),"n"(BH));
}
template<int TB,uint32_t BH> __device__ __forceinline__ void wgmma_n64_rs(float (&d)[32], uint32_t a0,uint32_t a1,uint32_t a2,uint32_t a3, uint32_t bl, uint32_t bo, int scale_d){
  asm volatile("{.reg .pred p; .reg .b32 t; .reg .b64 db; setp.ne.b32 p, %38, 0; add.u32 t, %36, %37; mov.b64 db, {t, %40};\n"
   "wgmma.mma_async.sync.aligned.m64n64k16.f32.bf16.bf16 {%0,%1,%2,%3,%4,%5,%6,%7,%8,%9,%10,%11,%12,%13,%14,%15,%16,%17,%18,%19,%20,%21,%22,%23,%24,%25,%26,%27,%28,%29,%30,%31}, {%32,%33,%34,%35}, db, p, 1, 1, %39;}"
   : "+f"(d[0]),"+f"(d[1]),"+f"(d[2]),"+f"(d[3]),"+f"(d[4]),"+f"(d[5]),"+f"(d[6]),"+f"(d[7]),"+f"(d[8]),"+f"(d[9]),"+f"(d[10]),"+f"(d[11]),"+f"(d[12]),"+f"(d[13]),"+f"(d[14]),"+f"(d[15]),"+f"(d[16]),"+f"(d[17]),"+f"(d[18]),"+f"(d[19]),"+f"(d[20]),"+f"(d[21]),"+f"(d[22]),"+f"(d[23]),"+f"(d[24]),"+f"(d[25]),"+f"(d[26]),"+f"(d[27]),"+f"(d[28]),"+f"(d[29]),"+f"(d[30]),"+f"(d[31])
   : "r"(a0),"r"(a1),"r"(a2),"r"(a3),"r"(bl),"r"(bo >> 4),"r"(scale_d),"n"(TB),"n"(BH));
}
template<int TA,int TB,uint32_t AH,uint32_t BH> __device__ __forceinline__ void wgmma_n96_ss(float (&d)[48], uint32_t al, uint32_t ao, uint32_t bl, uint32_t bo, int scale_d){
  asm volatile("{.reg .pred p; .reg .b32 t, v; .reg .b64 da, db; setp.ne.b32 p, %52, 0; add.u32 t, %48, %49; mov.b64 da, {t, %55}; add.u32 v, %50, %51; mov.b64 db, {v, %56};\n"
   "wgmma.mma_async.sync.aligned.m64n96k16.f32.bf16.bf16 {%0,%1,%2,%3,%4,%5,%6,%7,%8,%9,%10,%11,%12,%13,%14,%15,%16,%17,%18,%19,%20,%21,%22,%23,%24,%25,%26,%27,%28,%29,%30,%31,%32,%33,%34,%35,%36,%37,%38,%39,%40,%41,%42,%43,%44,%45,%46,%47}, da, db, p, 1, 1, %53, %54;}"
   : "+f"(d[0]),"+f"(d[1]),"+f"(d[2]),"+f"(d[3]),"+f"(d[4]),"+f"(d[5]),"+f"(d[6]),"+f"(d[7]),"+f"(d[8]),"+f"(d[9]),"+f"(d[10]),"+f"(d[11]),"+f"(d[12]),"+f"(d[13]),"+f"(d[14]),"+f"(d[15]),"+f"(d[16]),"+f"(d[17]),"+f"(d[18]),"+f"(d[19]),"+f"(d[20]),"+f"(d[21]),"+f"(d[22]),"+f"(d[23]),"+f"(d[24]),"+f"(d[25]),"+f"(d[26]),"+f"(d[27]),"+f"(d[28]),"+f"(d[29]),"+f"(d[30]),"+f"(d[31]),"+f"(d[32]),"+f"(d[33]),"+f"(d[34]),"+f"(d[35]),"+f"(d[36]),"+f"(d[37]),"+f"(d[38]),"+f"(d[39]),"+f"(d[40]),"+f"(d[41]),"+f"(d[42]),"+f"(d[43]),"+f"(d[44]),"+f"(d[45]),"+f"(d[46]),"+f"(d[47])
   : "r"(al),"r"(ao >> 4),"r"(bl),"r"(bo >> 4),"r"(scale_d),"n"(TA),"n"(TB),"n"(AH),"n"(BH));
}
template<int TA,int TB,uint32_t AH,uint32_t BH> __device__ __forceinline__ void wgmma_n128_ss(float (&d)[64], uint32_t al, uint32_t ao, uint32_t bl, uint32_t bo, int scale_d){
  asm volatile("{.reg .pred p; .reg .b32 t, v; .reg .b64 da, db; setp.ne.b32 p, %68, 0; add.u32 t, %64, %65; mov.b64 da, {t, %71}; add.u32 v, %66, %67; mov.b64 db, {v, %72};\n"
   "wgmma.mma_async.sync.aligned.m64n128k16.f32.bf16.bf16 {%0,%1,%2,%3,%4,%5,%6,%7,%8,%9,%10,%11,%12,%13,%14,%15,%16,%17,%18,%19,%20,%21,%22,%23,%24,%25,%26,%27,%28,%29,%30,%31,%32,%33,%34,%35,%36,%37,%38,%39,%40,%41,%42,%43,%44,%45,%46,%47,%48,%49,%50,%51,%52,%53,%54,%55,%56,%57,%58,%59,%60,%61,%62,%63}, da, db, p, 1, 1, %69, %70;}"
   : "+f"(d[0]),"+f"(d[1]),"+f"(d[2]),"+f"(d[3]),"+f"(d[4]),"+f"(d[5]),"+f"(d[6]),"+f"(d[7]),"+f"(d[8]),"+f"(d[9]),"+f"(d[10]),"+f"(d[11]),"+f"(d[12]),"+f"(d[13]),"+f"(d[14]),"+f"(d[15]),"+f"(d[16]),"+f"(d[17]),"+f"(d[18]),"+f"(d[19]),"+f"(d[20]),"+f"(d[21]),"+f"(d[22]),"+f"(d[23]),"+f"(d[24]),"+f"(d[25]),"+f"(d[26]),"+f"(d[27]),"+f"(d[28]),"+f"(d[29]),"+f"(d[30]),"+f"(d[31]),"+f"(d[32]),"+f"(d[33]),"+f"(d[34]),"+f"(d[35]),"+f"(d[36]),"+f"(d[37]),"+f"(d[38]),"+f"(d[39]),"+f"(d[40]),"+f"(d[41]),"+f"(d[42]),"+f"(d[43]),"+f"(d[44]),"+f"(d[45]),"+f"(d[46]),"+f"(d[47]),"+f"(d[48]),"+f"(d[49]),"+f"(d[50]),"+f"(d[51]),"+f"(d[52]),"+f"(d[53]),"+f"(d[54]),"+f"(d[55]),"+f"(d[56]),"+f"(d[57]),"+f"(d[58]),"+f"(d[59]),"+f"(d[60]),"+f"(d[61]),"+f"(d[62]),"+f"(d[63])
   : "r"(al),"r"(ao >> 4),"r"(bl),"r"(bo >> 4),"r"(scale_d),"n"(TA),"n"(TB),"n"(AH),"n"(BH));
}

__global__ void __cluster_dims__(2, 1, 1) __launch_bounds__(384, 1)
fused_kernel(const __grid_constant__ Maps maps, const __nv_bfloat16* __restrict__ x, const __nv_bfloat16* __restrict__ lam_re,
             const __nv_bfloat16* __restrict__ lam_im, const __nv_bfloat16* __restrict__ log_dt, const __nv_bfloat16* __restrict__ dskip,
             const __nv_bfloat16* __restrict__ b1, const __nv_bfloat16* __restrict__ b2, const __nv_bfloat16* __restrict__ gate_w,
             const __nv_bfloat16* __restrict__ pf_bre, const __nv_bfloat16* __restrict__ pf_bim, const __nv_bfloat16* __restrict__ pf_w1,
             const __nv_bfloat16* __restrict__ pf_w2, const __nv_bfloat16* __restrict__ pf_cre, const __nv_bfloat16* __restrict__ pf_cim,
             float* __restrict__ out) {
  extern __shared__ __align__(1024) unsigned char smem_raw[];
  const uint32_t sb = (uint32_t)__cvta_generic_to_shared(smem_raw);
  const int b = blockIdx.x;
  const int rank = b & 1, s = (b >> 1) & 7, m = ((b >> 4) << 1) | rank;
  const int warp = __shfl_sync(0xffffffffu, (int)(threadIdx.x >> 5), 0);
  const int lane = threadIdx.x & 31;
  const int kb0 = (s < 2) ? 2 : 0;

  if (threadIdx.x == 256) {
    TS(2, 0);
    for (int i = 0; i < 8; i++) mbar_init(sb + OFF_XFULL + 8 * i, 1);
    for (int i = 0; i < NSLOT; i++) { mbar_init(sb + OFF_FULL + 8 * i, 1); mbar_init(sb + OFF_EMPTY + 8 * i, 16); }
    mbar_init(sb + OFF_GBAR, 64); mbar_init(sb + OFF_CBAR, 64); mbar_init(sb + OFF_BBAR, 32);
    asm volatile("fence.mbarrier_init.release.cluster;" ::: "memory");
    asm volatile("fence.proxy.async.shared::cta;" ::: "memory");
    mbar_expect_tx(sb + OFF_XFULL, 16384);
    tma5d(sb + OFF_X, &maps.x, 0, 2 * m, sb + OFF_XFULL);
  } else if (threadIdx.x == 352) {
    l2_prefetch(pf_bre + b * 2048, 4096);
    l2_prefetch(pf_bim + b * 2048, 4096);
    l2_prefetch(x + b * 8192, 16384);
  }
  __syncwarp();
  asm volatile("barrier.cluster.arrive.relaxed.aligned;" ::: "memory");
  asm volatile("barrier.cluster.wait.aligned;" ::: "memory");

  if (warp >= 8) {
    asm volatile("setmaxnreg.dec.sync.aligned.u32 56;");
    if (warp == 8) {
      if (lane == 0) {
        TS(2, 1);
        const CUtensorMap* mb = rank ? &maps.bim : &maps.bre;
        const CUtensorMap* mc = rank ? &maps.cim : &maps.cre;
        int slot = 0; uint32_t ph = 1;
#pragma unroll 1
        for (int u = 0; u < 24; u++) {
          const uint32_t fb = sb + OFF_FULL + 8 * slot, dst = sb + OFF_RING + slot * 16384;
          if (u >= NSLOT) mbar_wait(sb + OFF_EMPTY + 8 * slot, ph);
          if (u < 8) {
            mbar_expect_tx(fb, 16384);
            tma2d_mc(dst + rank * 8192, mb, u * 64, s * 64, fb);
            if (u < 6) {
              mbar_expect_tx(sb + OFF_XFULL + 8 * (u + 1), 16384);
              tma5d(sb + OFF_X + (u + 1) * 16384, &maps.x, (u + 1) * 64, 2 * m, sb + OFF_XFULL + 8 * (u + 1));
              if (u == 5) {
                mbar_expect_tx(sb + OFF_XFULL + 56, 16384);
                tma5d(sb + OFF_X + 7 * 16384, &maps.x, 7 * 64, 2 * m, sb + OFF_XFULL + 56);
              }
            }
          } else if (u < 16) {
            mbar_expect_tx(fb, 16384);
            tma2d_mc(dst + rank * 8192, &maps.w1a, s * 224 + rank * 64, (u - 8) * 64, fb);
          } else {
            mbar_expect_tx(fb, 12288);
            tma3d_mc(dst + rank * 6144, &maps.w1b, 0, ((u - 16 + kb0) & 7) * 64 + rank * 32, s * 7 + 4, fb);
          }
          if (++slot == NSLOT) { slot = 0; ph ^= 1; }
        }
#pragma unroll 1
        for (int p = 0; p < 8; p++) {
          const int piece = (s + 1 + p) & 7;
#pragma unroll
          for (int j = 0; j < 3; j++) {
            const uint32_t fb = sb + OFF_FULL + 8 * slot, dst = sb + OFF_RING + slot * 16384;
            mbar_wait(sb + OFF_EMPTY + 8 * slot, ph);
            if (j == 0) {
              mbar_expect_tx(fb, 16384);
              tma2d_mc(dst + rank * 8192, mc, s * 64, piece * 64, fb);
            } else {
              mbar_expect_tx(fb, 14336);
              tma2d_mc(dst + rank * 7168, &maps.w2, piece * 64, s * 224 + (j - 1) * 112 + rank * 56, fb);
            }
            if (++slot == NSLOT) { slot = 0; ph ^= 1; }
          }
        }
        TS(2, 2);
      }
    } else if (warp == 11) {
      if (lane == 0) {
        l2_prefetch(pf_w1 + b * 7168, 14336);
        l2_prefetch(pf_cre + b * 2048, 4096);
        l2_prefetch(pf_cim + b * 2048, 4096);
        l2_prefetch(pf_w2 + b * 7168, 14336);
      }
      for (int i = lane; i < 112; i += 32) {
        uint32_t v = __ldg(reinterpret_cast<const uint32_t*>(b1 + s * 224) + i);
        asm volatile("st.shared.v2.f32 [%0], {%1,%2};" ::"r"(sb + OFF_B1 + i * 8), "f"(bf_lo(v)), "f"(bf_hi(v)) : "memory");
      }
      mbar_arrive(sb + OFF_BBAR);
    } else {
      const int t = threadIdx.x - 288;
      {
        uint4 w = __ldg(reinterpret_cast<const uint4*>(gate_w) + t);
        asm volatile("st.shared.v4.u32 [%0], {%1,%2,%3,%4};" ::"r"(sb + OFF_CARRY + t * 16), "r"(w.x), "r"(w.y), "r"(w.z), "r"(w.w) : "memory");
      }
      unsigned par;
      asm volatile("ld.relaxed.gpu.global.u32 %0, [%1];" : "=r"(par) : "l"(g_epoch + b) : "memory");
      par = (par + 1) & 1;
      cplx l64 = make_lam(bf_ld(lam_re + s * 64 + t), bf_ld(lam_im + s * 64 + t), bf_ld(log_dt + s * 64 + t));
#pragma unroll
      for (int i = 0; i < 6; i++) l64 = cmul(l64, l64);
      bar_sync(5, 64);
      float z0 = 0.f, z1 = 0.f, y0 = 0.f, y1 = 0.f;
#pragma unroll 1
      for (int kb = 0; kb < 8; kb++) {
        mbar_wait(sb + OFF_XFULL + 8 * kb, 0);
        const uint32_t xr = sb + OFF_X + kb * 16384 + t * 128;
#pragma unroll 2
        for (int c = 0; c < 8; c++) {
          uint4 w = lds_u4(sb + OFF_CARRY + kb * 128 + c * 16);
          uint4 a = lds_u4(xr + ((c ^ (t & 7)) << 4));
          uint4 d = lds_u4(xr + 8192 + ((c ^ (t & 7)) << 4));
          float wl, wh;
          wl = bf_lo(w.x); wh = bf_hi(w.x); z0 = fmaf(bf_lo(a.x), wl, z0); y0 = fmaf(bf_hi(a.x), wh, y0); z1 = fmaf(bf_lo(d.x), wl, z1); y1 = fmaf(bf_hi(d.x), wh, y1);
          wl = bf_lo(w.y); wh = bf_hi(w.y); z0 = fmaf(bf_lo(a.y), wl, z0); y0 = fmaf(bf_hi(a.y), wh, y0); z1 = fmaf(bf_lo(d.y), wl, z1); y1 = fmaf(bf_hi(d.y), wh, y1);
          wl = bf_lo(w.z); wh = bf_hi(w.z); z0 = fmaf(bf_lo(a.z), wl, z0); y0 = fmaf(bf_hi(a.z), wh, y0); z1 = fmaf(bf_lo(d.z), wl, z1); y1 = fmaf(bf_hi(d.z), wh, y1);
          wl = bf_lo(w.w); wh = bf_hi(w.w); z0 = fmaf(bf_lo(a.w), wl, z0); y0 = fmaf(bf_hi(a.w), wh, y0); z1 = fmaf(bf_lo(d.w), wl, z1); y1 = fmaf(bf_hi(d.w), wh, y1);
        }
      }
      {
        float g0 = __fdividef(1.f, 1.f + expf(-(z0 + y0))), g1 = __fdividef(1.f, 1.f + expf(-(z1 + y1)));
        asm volatile("st.shared.f32 [%0], %1;" ::"r"(sb + OFF_GS + t * 4), "f"(g0) : "memory");
        asm volatile("st.shared.f32 [%0], %1;" ::"r"(sb + OFF_GS + 256 + t * 4), "f"(g1) : "memory");
      }
      mbar_arrive(sb + OFF_GBAR);
      if (t == 0) TS(3, 0);
      bar_sync(5, 64);
      const float2* eb = g_end + s * 2048 + t;
      const int n = 2 * m + 1;
      cplx S = {0.f, 0.f}, S0 = {0.f, 0.f};
#pragma unroll 1
      for (int c0 = 0; c0 < n; c0 += 8) {
        uint32_t er[8], ei[8];
        int tries = 0;
        while (true) {
          uint32_t bad = 0;
#pragma unroll
          for (int i = 0; i < 8; i++) {
            int c = min(c0 + i, n - 1);
            unsigned long long v;
            asm volatile("ld.relaxed.gpu.global.b64 %0, [%1];" : "=l"(v) : "l"(eb + c * 64) : "memory");
            er[i] = (uint32_t)v; ei[i] = (uint32_t)(v >> 32);
          }
#pragma unroll
          for (int i = 0; i < 8; i++) bad |= er[i] ^ par;
          if (!(bad & 1)) break;
          if (++tries > 200000) break;
        }
#pragma unroll
        for (int i = 0; i < 8; i++) {
          if (c0 + i < n) {
            S0 = S;
            S = cfma(l64, S, cplx{__uint_as_float(er[i]), __uint_as_float(ei[i])});
          }
        }
      }
      asm volatile("st.shared.v2.f32 [%0], {%1,%2};" ::"r"(sb + OFF_CARRY + t * 8), "f"(S0.re), "f"(S0.im) : "memory");
      asm volatile("st.shared.v2.f32 [%0], {%1,%2};" ::"r"(sb + OFF_CARRY + 512 + t * 8), "f"(S.re), "f"(S.im) : "memory");
      mbar_arrive(sb + OFF_CBAR);
      if (t == 0) TS(3, 1);
    }
  } else {
    asm volatile("setmaxnreg.inc.sync.aligned.u32 224;");
    const int wg = warp >> 2, w = warp & 3, q = lane & 3, gr = lane >> 2;
    TS(wg, 0);
    unsigned epoch;
    asm volatile("ld.relaxed.gpu.global.u32 %0, [%1];" : "=r"(epoch) : "l"(g_epoch + b) : "memory");
    const int c0 = s * 64 + w * 16 + gr;
    float pr[2], pi[2], pd[2];
#pragma unroll
    for (int h = 0; h < 2; h++) { pr[h] = bf_ld(lam_re + c0 + 8 * h); pi[h] = bf_ld(lam_im + c0 + 8 * h); pd[h] = bf_ld(log_dt + c0 + 8 * h); }
    uint32_t ebar;
    asm volatile("mapa.shared::cluster.u32 %0, %1, %2;" : "=r"(ebar) : "r"(sb + OFF_EMPTY), "r"(lane & 1));
    auto release = [&](int slot) { if (lane < 2) mbar_arrive_cl(ebar + 8 * slot); };
    const uint32_t xw = sb + OFF_X + wg * 8192, fullb = sb + OFF_FULL;
    const uint32_t dxw = (xw & 0x3FFFF) >> 4, dring = ((sb + OFF_RING) & 0x3FFFF) >> 4;

    float ure[32], uim[32], aa[64], ab[48];
    cplx lam[2], coef[2], l16[2], l32[2], lq[2], pre[2];

#pragma unroll
    for (int kb = 0; kb < 8; kb++) {
      const int slot = kb % NSLOT;
      mbar_wait(sb + OFF_XFULL + 8 * kb, 0);
      mbar_wait(fullb + 8 * slot, (kb / NSLOT) & 1);
      if (kb == 0) TS(wg, 1);
      wg_fence();
#pragma unroll
      for (int kk = 0; kk < 4; kk++) {
        wgmma_n64_ss<0, 0, DH128, DH128>(ure, dring, slot * 16384 + kk * 32, dxw, kb * 16384 + kk * 32, (kb | kk) != 0);
        wgmma_n64_ss<0, 0, DH128, DH128>(uim, dring, slot * 16384 + 8192 + kk * 32, dxw, kb * 16384 + kk * 32, (kb | kk) != 0);
      }
      wg_commit();
      if (kb > 0) { wg_wait<1>(); release((kb - 1) % NSLOT); }
      if (kb == 1 || kb == 2) {
        const int h = kb - 1;
        lam[h] = make_lam(pr[h], pi[h], pd[h]);
        const float inv = __fdividef(1.f, fmaf(pr[h], pr[h], pi[h] * pi[h]));
        coef[h] = cmul(cplx{lam[h].re - 1.f, lam[h].im}, cplx{pr[h] * inv, -pi[h] * inv});
        cplx t = cmul(lam[h], lam[h]); t = cmul(t, t); t = cmul(t, t);
        l16[h] = cmul(t, t); l32[h] = cmul(l16[h], l16[h]);
        cplx a = (q & 1) ? l16[h] : cplx{1.f, 0.f}, c = (q & 2) ? l32[h] : cplx{1.f, 0.f};
        lq[h] = cmul(cmul(a, c), coef[h]);
      }
      if (kb == 6) {
        mbar_wait(sb + OFF_BBAR, 0);
#pragma unroll
        for (int j = 0; j < 16; j++) {
          float2 v = lds_f2(sb + OFF_B1 + j * 32 + q * 8);
          aa[4 * j] = v.x; aa[4 * j + 1] = v.y; aa[4 * j + 2] = v.x; aa[4 * j + 3] = v.y;
        }
      }
    }
    const uint32_t par = (epoch + 1) & 1;
    TS(wg, 2);
#pragma unroll
    for (int kb = 0; kb < 8; kb++) {
      const int u = 8 + kb, slot = u % NSLOT;
      mbar_wait(fullb + 8 * slot, (u / NSLOT) & 1);
      wg_fence();
#pragma unroll
      for (int kk = 0; kk < 4; kk++)
        wgmma_n128_ss<0, 1, DH128, DH128>(aa, dxw, kb * 16384 + kk * 32, dring, slot * 16384 + kk * 2048 + lbo(8192), 1);
      wg_commit();
      wg_wait<1>();
      release((u - 1) % NSLOT);
      if (kb == 0) {
        reg_fence(ure); reg_fence(uim);
        cplx e[2];
#pragma unroll
        for (int h = 0; h < 2; h++) e[h] = cplx{ure[2 * h], uim[2 * h]};
#pragma unroll
        for (int t = 1; t < 16; t++)
#pragma unroll
          for (int h = 0; h < 2; h++) { const int i = 4 * (t >> 1) + 2 * h + (t & 1); e[h] = cfma(lam[h], e[h], cplx{ure[i], uim[i]}); }
#pragma unroll
        for (int h = 0; h < 2; h++) {
          cplx y = {__shfl_up_sync(0xffffffffu, e[h].re, 1, 4), __shfl_up_sync(0xffffffffu, e[h].im, 1, 4)};
          if (q >= 1) e[h] = cfma(l16[h], y, e[h]);
          y = cplx{__shfl_up_sync(0xffffffffu, e[h].re, 2, 4), __shfl_up_sync(0xffffffffu, e[h].im, 2, 4)};
          if (q >= 2) e[h] = cfma(l32[h], y, e[h]);
          if (q == 3) {
            unsigned long long v = ((unsigned long long)__float_as_uint(e[h].im) << 32) | ((__float_as_uint(e[h].re) & ~1u) | par);
            asm volatile("st.relaxed.gpu.global.b64 [%0], %1;" ::"l"(g_end + s * 2048 + (2 * m + wg) * 64 + w * 16 + gr + 8 * h), "l"(v) : "memory");
          }
          y = cplx{__shfl_up_sync(0xffffffffu, e[h].re, 1, 4), __shfl_up_sync(0xffffffffu, e[h].im, 1, 4)};
          pre[h] = (q >= 1) ? cmul(coef[h], y) : cplx{0.f, 0.f};
        }
        TS(wg, 3);
      }
      if (kb == 1 || kb == 2) {
#pragma unroll
        for (int i = (kb - 1) * 16; i < kb * 16; i++) {
          cplx v = cmul(coef[(i >> 1) & 1], cplx{ure[i], uim[i]});
          ure[i] = v.re; uim[i] = v.im;
        }
        reg_fence(ure); reg_fence(uim);
      }
      if (kb == 6) {
#pragma unroll
        for (int j = 0; j < 12; j++) {
          float2 v = lds_f2(sb + OFF_B1 + 512 + j * 32 + q * 8);
          ab[4 * j] = v.x; ab[4 * j + 1] = v.y; ab[4 * j + 2] = v.x; ab[4 * j + 3] = v.y;
        }
      }
    }
    TS(wg, 4);
    uint32_t H[56];
    float gv[2], sh[2];
    cplx hst[2];
    const uint32_t hbase = xw + kb0 * 16384, dh = dxw + kb0 * 1024;
#pragma unroll
    for (int kb = 0; kb < 8; kb++) {
      const int u = 16 + kb, slot = u % NSLOT;
      mbar_wait(fullb + 8 * slot, (u / NSLOT) & 1);
      wg_fence();
      const uint32_t dxa = dxw + ((kb + kb0) & 7) * 1024;
#pragma unroll
      for (int kk = 0; kk < 4; kk++)
        wgmma_n96_ss<0, 1, DH128, DH64>(ab, dxa, kk * 32, dring, slot * 16384 + (kk >> 1) * 6144 + (kk & 1) * 1024 + lbo(2048), 1);
      wg_commit();
      wg_wait<1>();
      release((u - 1) % NSLOT);
      if (kb == 0) {
        reg_fence(aa);
        mbar_wait(sb + OFF_GBAR, 0);
#pragma unroll
        for (int h = 0; h < 2; h++) { gv[h] = lds_f(sb + OFF_GS + (wg * 64 + w * 16 + gr + 8 * h) * 4); sh[h] = 0.5f - 0.5f * gv[h]; }
      }
      if (kb < 3 || kb == 7) {
        const int ch = kb < 3 ? kb : 3;
#pragma unroll
        for (int i = ch * 8; i < ch * 8 + 8; i++) {
          H[i] = pack_bf16(gelu_s(aa[2 * i], sh[i & 1]), gelu_s(aa[2 * i + 1], sh[i & 1]));
          asm volatile("" : "+r"(H[i])::"memory");
        }
      } else {
        if (kb == 3) {
          TS(wg, 5);
          mbar_wait(sb + OFF_CBAR, 0);
          TS(wg, 6);
#pragma unroll
          for (int h = 0; h < 2; h++) {
            float2 c = lds_f2(sb + OFF_CARRY + wg * 512 + (w * 16 + gr + 8 * h) * 8);
            hst[h] = cfma(lq[h], cplx{c.x, c.y}, pre[h]);
          }
        }
        const int j0 = (kb - 3) * 2;
        uint32_t rr[4], ri[4];
#pragma unroll
        for (int jj = 0; jj < 2; jj++) {
          const int j = j0 + jj;
          float2 g2 = lds_f2(sb + OFF_GS + (wg * 64 + j * 8 + q * 2) * 4);
          g2.x += g2.x; g2.y += g2.y;
#pragma unroll
          for (int h = 0; h < 2; h++) {
            const int i = 4 * j + 2 * h;
            cplx h0 = cfma(lam[h], hst[h], cplx{ure[i], uim[i]});
            hst[h] = cfma(lam[h], h0, cplx{ure[i + 1], uim[i + 1]});
            rr[jj * 2 + h] = pack_bf16(h0.re * g2.x, hst[h].re * g2.y);
            ri[jj * 2 + h] = pack_bf16(-h0.im * g2.x, -hst[h].im * g2.y);
          }
        }
        const uint32_t a = hbase + (w * 16 + (lane & 15)) * 128 + (((j0 + (lane >> 4)) ^ (lane & 7)) << 4);
        asm volatile("stmatrix.sync.aligned.m8n8.x4.shared.b16 [%0], {%1,%2,%3,%4};" ::"r"(a), "r"(rr[0]), "r"(rr[1]), "r"(rr[2]), "r"(rr[3]) : "memory");
        asm volatile("stmatrix.sync.aligned.m8n8.x4.shared.b16 [%0], {%1,%2,%3,%4};" ::"r"(a + 16384), "r"(ri[0]), "r"(ri[1]), "r"(ri[2]), "r"(ri[3]) : "memory");
        if (kb == 6) asm volatile("fence.proxy.async.shared::cta;" ::: "memory");
      }
    }
    bar_sync(1 + wg, 128);
    TS(wg, 7);
    float o[32], sum[32];
    auto gelu_b = [&](int ch) {
#pragma unroll
      for (int i = ch * 6; i < ch * 6 + 6; i++) {
        H[32 + i] = pack_bf16(gelu_s(ab[2 * i], sh[i & 1]), gelu_s(ab[2 * i + 1], sh[i & 1]));
        asm volatile("" : "+r"(H[32 + i])::"memory");
      }
    };
    auto mma_h = [&](uint32_t sl, int part) {
      wg_fence();
#pragma unroll
      for (int kk = 0; kk < 4; kk++)
        wgmma_n64_ss<1, 0, DH128, DH128>(o, dh, part * 16384 + kk * 2048, sl, part * 8192 + kk * 32, (part | kk) != 0);
    };
    auto mma_w = [&](uint32_t sl, int k0, int k1) {
      wg_fence();
#pragma unroll
      for (int kk = k0; kk < k1; kk++)
        wgmma_n64_rs<1, DH128>(o, H[4 * kk], H[4 * kk + 1], H[4 * kk + 2], H[4 * kk + 3], sl, 16384 + (kk / 7) * 16384 + (kk % 7) * 2048, 1);
    };
    uint4* const psend = g_part + (size_t)m * (8 * 7 * 1024) + threadIdx.x;
    const uint4* const precv = g_part + (size_t)(m * 8 + s) * (7 * 1024) + threadIdx.x;
    auto send = [&](int p) {
      uint4* dst = psend + (((s + 1 + p) & 7) * 7 + p) * 1024;
#pragma unroll
      for (int i = 0; i < 4; i++)
        st_b128(dst + i * 256, (pack_bf16(o[8 * i], o[8 * i + 1]) & ~1u) | par, pack_bf16(o[8 * i + 2], o[8 * i + 3]),
                pack_bf16(o[8 * i + 4], o[8 * i + 5]), pack_bf16(o[8 * i + 6], o[8 * i + 7]));
    };
    auto recv_issue = [&](uint32_t (&r)[16], int p) {
#pragma unroll
      for (int i = 0; i < 4; i++) ld_b128(precv + p * 1024 + i * 256, r[4 * i], r[4 * i + 1], r[4 * i + 2], r[4 * i + 3]);
    };
    auto recv_add = [&](uint32_t (&r)[16], int p, float (&acc)[32]) {
      int tries = 0;
      while (((r[0] ^ par) | (r[4] ^ par) | (r[8] ^ par) | (r[12] ^ par)) & 1) {
        recv_issue(r, p);
        if (++tries > 200000) break;
      }
#pragma unroll
      for (int i = 0; i < 16; i++) { acc[2 * i] += bf_lo(r[i]); acc[2 * i + 1] += bf_hi(r[i]); }
    };
    {
      mbar_wait(fullb + 0, 0);
      mma_h(dring, 0); wg_commit();
      wg_wait<1>(); release(23 % NSLOT);
      reg_fence(ab);
      gelu_b(0);
      mma_h(dring, 1); wg_commit();
      gelu_b(1);
      mbar_wait(fullb + 8, 0);
      mma_w(dring, 0, 4); wg_commit();
      wg_wait<1>(); release(0);
      gelu_b(2);
      mbar_wait(fullb + 16, 0);
      mma_w(dring, 4, 8); wg_commit();
      gelu_b(3);
      if (wg == 1) bar_sync(4, 256);
      mma_w(dring, 8, 14); wg_commit();
      bar_arrive(4 - wg, 256);
      wg_wait<1>(); release(1);
      wg_wait<0>(); release(2);
      reg_fence(o);
      send(0);
    }
    TS(wg, 8);
    uint32_t r0[16];
#pragma unroll 1
    for (int p = 1; p < 7; p++) {
      const int sl0 = 3 * (p & 1);
      const uint32_t ph = (p >> 1) & 1, sa = dring + sl0 * 1024;
      if (p >= 2) recv_issue(r0, p - 2);
      mbar_wait(fullb + 8 * sl0, ph);
      bar_sync(3 + wg, 256);
      mma_h(sa, 0); mma_h(sa, 1); wg_commit();
      mbar_wait(fullb + 8 * sl0 + 8, ph);
      mma_w(sa, 0, 7); wg_commit();
      mbar_wait(fullb + 8 * sl0 + 16, ph);
      mma_w(sa, 7, 14); wg_commit();
      bar_arrive(4 - wg, 256);
      wg_wait<1>();
      if (p < 6) { release(sl0); release(sl0 + 1); }
      wg_wait<0>();
      if (p < 6) release(sl0 + 2);
      reg_fence(o);
      send(p);
      if (p == 1) {
#pragma unroll
        for (int j = 0; j < 8; j++) {
          const uint32_t dk = __ldg(reinterpret_cast<const uint32_t*>(dskip + s * 64 + j * 8) + q);
          const uint32_t bb = __ldg(reinterpret_cast<const uint32_t*>(b2 + s * 64 + j * 8) + q);
#pragma unroll
          for (int h = 0; h < 2; h++) {
            const uint32_t xv = lds_u(xw + s * 16384 + (w * 16 + gr + 8 * h) * 128 + ((j ^ gr) << 4) + q * 4);
            const float og = 2.f * sh[h];
            sum[4 * j + 2 * h] = fmaf(gv[h] * bf_lo(xv), bf_lo(dk), og * bf_lo(bb));
            sum[4 * j + 2 * h + 1] = fmaf(gv[h] * bf_hi(xv), bf_hi(dk), og * bf_hi(bb));
          }
        }
      } else {
        recv_add(r0, p - 2, sum);
      }
      TS(wg, 8 + p);
    }
    {
      const uint32_t sa = dring + 3 * 1024;
      uint32_t r1[16];
      recv_issue(r0, 5);
      mbar_wait(fullb + 24, 1);
      bar_sync(3 + wg, 256);
      mma_h(sa, 0); mma_h(sa, 1);
      mbar_wait(fullb + 32, 1);
      mma_w(sa, 0, 7);
      mbar_wait(fullb + 40, 1);
      mma_w(sa, 7, 14); wg_commit();
      if (wg == 0) bar_arrive(4, 256);
      recv_issue(r1, 6);
      recv_add(r0, 5, sum);
      TS(wg, 15);
      recv_add(r1, 6, sum);
      TS(wg, 16);
      wg_wait<0>();
      reg_fence(o);
      float* op = out + (size_t)(m * 128 + wg * 64 + (gr >> 1) * 16 + w * 4 + (gr & 1)) * DM + s * 64 + q * 2;
#pragma unroll
      for (int j = 0; j < 8; j++)
#pragma unroll
        for (int h = 0; h < 2; h++)
          *reinterpret_cast<float2*>(op + h * 2 * DM + j * 8) = make_float2(o[4 * j + 2 * h] + sum[4 * j + 2 * h], o[4 * j + 2 * h + 1] + sum[4 * j + 2 * h + 1]);
      if (threadIdx.x == 128) g_epoch[b] = epoch + 1;
      TS(wg, 17);
    }
  }
}

typedef CUresult (*EncFn)(CUtensorMap*, CUtensorMapDataType, cuuint32_t, void*, const cuuint64_t*, const cuuint64_t*, const cuuint32_t*,
                          const cuuint32_t*, CUtensorMapInterleave, CUtensorMapSwizzle, CUtensorMapL2promotion, CUtensorMapFloatOOBfill);

void encode(EncFn f, CUtensorMap* mp, const void* p, int rank, const cuuint64_t* dims, const cuuint64_t* strides, const cuuint32_t* box, CUtensorMapSwizzle sw) {
  cuuint32_t es[5] = {1, 1, 1, 1, 1};
  f(mp, CU_TENSOR_MAP_DATA_TYPE_BFLOAT16, rank, const_cast<void*>(p), dims, strides, box, es, CU_TENSOR_MAP_INTERLEAVE_NONE, sw,
    CU_TENSOR_MAP_L2_PROMOTION_L2_128B, CU_TENSOR_MAP_FLOAT_OOB_FILL_NONE);
}

}

extern "C" void kernel_launch(void* const* d_in, const int* in_sizes, int n_in, void* d_out, int out_size) {
  typedef const __nv_bfloat16* bp;
  bp x = (bp)d_in[0], lre = (bp)d_in[1], lim = (bp)d_in[2], bre = (bp)d_in[3], bim = (bp)d_in[4], cre = (bp)d_in[5], cim = (bp)d_in[6],
     ldt = (bp)d_in[7], dsk = (bp)d_in[8], w1 = (bp)d_in[10], b1 = (bp)d_in[11], w2 = (bp)d_in[12], b2 = (bp)d_in[13], gw = (bp)d_in[14];
  static EncFn enc = nullptr;
  if (!enc) {
    void* f = nullptr;
    cudaDriverEntryPointQueryResult qr;
    cudaGetDriverEntryPoint("cuTensorMapEncodeTiled", &f, cudaEnableDefault, &qr);
    enc = (EncFn)f;
    cudaFuncSetAttribute(fused_kernel, cudaFuncAttributeMaxDynamicSharedMemorySize, SMEM_BYTES);
  }
  Maps maps;
  {
    cuuint64_t d[5] = {DM, 2, 4, 8, SEQ / 64}, st[4] = {DM * 2, 16 * DM * 2, 2 * DM * 2, 64 * DM * 2};
    cuuint32_t bx[5] = {64, 2, 4, 8, 2};
    encode(enc, &maps.x, x, 5, d, st, bx, CU_TENSOR_MAP_SWIZZLE_128B);
  }
  {
    cuuint64_t d[2] = {DM, DM}, st[1] = {DM * 2};
    cuuint32_t bx[2] = {64, 64};
    encode(enc, &maps.bre, bre, 2, d, st, bx, CU_TENSOR_MAP_SWIZZLE_128B);
    encode(enc, &maps.bim, bim, 2, d, st, bx, CU_TENSOR_MAP_SWIZZLE_128B);
    encode(enc, &maps.cre, cre, 2, d, st, bx, CU_TENSOR_MAP_SWIZZLE_128B);
    encode(enc, &maps.cim, cim, 2, d, st, bx, CU_TENSOR_MAP_SWIZZLE_128B);
  }
  {
    cuuint64_t d[2] = {FF, DM}, st[1] = {FF * 2};
    cuuint32_t bx[2] = {64, 64};
    encode(enc, &maps.w1a, w1, 2, d, st, bx, CU_TENSOR_MAP_SWIZZLE_128B);
    cuuint64_t d3[3] = {32, DM, FF / 32}, st3[2] = {FF * 2, 64};
    cuuint32_t bx3[3] = {32, 32, 3};
    encode(enc, &maps.w1b, w1, 3, d3, st3, bx3, CU_TENSOR_MAP_SWIZZLE_64B);
  }
  {
    cuuint64_t d[2] = {DM, FF}, st[1] = {DM * 2};
    cuuint32_t bx[2] = {64, 56};
    encode(enc, &maps.w2, w2, 2, d, st, bx, CU_TENSOR_MAP_SWIZZLE_128B);
  }
  fused_kernel<<<128, 384, SMEM_BYTES>>>(maps, x, lre, lim, ldt, dsk, b1, b2, gw, bre, bim, w1, w2, cre, cim, (float*)d_out);
}
```

```cpp
#include <cuda_runtime.h>
#include <cuda_bf16.h>
#include <cuda.h>
#include <stdint.h>

#define PF 2
#define PFK 2
namespace {

constexpr int SEQ = 2048, DM = 512, FF = 1792;
constexpr int NSLOT = 6;
constexpr uint32_t OFF_X = 0, OFF_RING = 131072, OFF_MISC = 229376;
constexpr uint32_t OFF_XFULL = OFF_MISC, OFF_FULL = OFF_XFULL + 64, OFF_EMPTY = OFF_FULL + 48, OFF_GBAR = OFF_EMPTY + 48,
                   OFF_CBAR = OFF_GBAR + 8, OFF_BBAR = OFF_CBAR + 8;
constexpr uint32_t OFF_GS = OFF_MISC + 256;
constexpr uint32_t OFF_CARRY = OFF_GS + 512;
constexpr uint32_t OFF_B1 = OFF_CARRY + 1024;
constexpr uint32_t SMEM_BYTES = OFF_B1 + 896;
static_assert(SMEM_BYTES <= 232448, "smem");

struct Maps { CUtensorMap x, bre, bim, w1a, w1b, w2, cre, cim; };

__device__ uint4 g_part[16 * 8 * 7 * 4 * 256];
__device__ float2 g_end[8 * 16 * 64];
__device__ unsigned g_gate[SEQ];
__device__ unsigned g_epoch[128];
#define TG(role) do {} while (0)
#define TS2(role, i) do {} while (0)
#define TS(role, i) do {} while (0)

__device__ __forceinline__ void mbar_init(uint32_t bar, uint32_t cnt) { asm volatile("mbarrier.init.shared::cta.b64 [%0], %1;" ::"r"(bar), "r"(cnt)); }
__device__ __forceinline__ void mbar_expect_tx(uint32_t bar, uint32_t bytes) { asm volatile("mbarrier.arrive.expect_tx.shared::cta.b64 _, [%0], %1;" ::"r"(bar), "r"(bytes) : "memory"); }
__device__ __forceinline__ void mbar_arrive(uint32_t bar) { asm volatile("mbarrier.arrive.shared::cta.b64 _, [%0];" ::"r"(bar) : "memory"); }
__device__ __forceinline__ void mbar_arrive_cl(uint32_t cbar) { asm volatile("mbarrier.arrive.shared::cluster.b64 _, [%0];" ::"r"(cbar) : "memory"); }
__device__ __forceinline__ void mbar_wait(uint32_t bar, uint32_t parity) {
  asm volatile(
      "{\n.reg .pred p;\n.reg .u32 c;\n"
      "mbarrier.try_wait.parity.shared::cta.b64 p, [%0], %1;\n"
      "@p bra.uni LAB_DONE;\n"
      "mov.u32 c, 0;\n"
      "LAB_WAIT:\n"
      "mbarrier.try_wait.parity.shared::cta.b64 p, [%0], %1;\n"
      "@p bra.uni LAB_DONE;\n"
      "add.u32 c, c, 1;\nsetp.lt.u32 p, c, 200000;\n@p bra.uni LAB_WAIT;\n"
      "LAB_DONE:\n}" ::"r"(bar), "r"(parity) : "memory");
}
__device__ __forceinline__ void tma2d(uint32_t dst, const CUtensorMap* m, int c0, int c1, uint32_t bar) {
  asm volatile("cp.async.bulk.tensor.2d.shared::cluster.global.mbarrier::complete_tx::bytes [%0], [%1, {%3,%4}], [%2];"
               ::"r"(dst), "l"(m), "r"(bar), "r"(c0), "r"(c1) : "memory");
}
__device__ __forceinline__ void tma2d_mc(uint32_t dst, const CUtensorMap* m, int c0, int c1, uint32_t bar) {
  asm volatile("cp.async.bulk.tensor.2d.shared::cluster.global.mbarrier::complete_tx::bytes.multicast::cluster [%0], [%1, {%3,%4}], [%2], %5;"
               ::"r"(dst), "l"(m), "r"(bar), "r"(c0), "r"(c1), "h"((uint16_t)3) : "memory");
}
__device__ __forceinline__ void tma3d_mc(uint32_t dst, const CUtensorMap* m, int c0, int c1, int c2, uint32_t bar) {
  asm volatile("cp.async.bulk.tensor.3d.shared::cluster.global.mbarrier::complete_tx::bytes.multicast::cluster [%0], [%1, {%3,%4,%5}], [%2], %6;"
               ::"r"(dst), "l"(m), "r"(bar), "r"(c0), "r"(c1), "r"(c2), "h"((uint16_t)3) : "memory");
}
__device__ __forceinline__ void tma5d(uint32_t dst, const CUtensorMap* m, int c0, int c4, uint32_t bar) {
  asm volatile("cp.async.bulk.tensor.5d.shared::cluster.global.mbarrier::complete_tx::bytes [%0], [%1, {%3,%5,%5,%5,%4}], [%2];"
               ::"r"(dst), "l"(m), "r"(bar), "r"(c0), "r"(c4), "r"(0) : "memory");
}
__device__ __forceinline__ void l2_prefetch(const void* p, uint32_t bytes) { asm volatile("cp.async.bulk.prefetch.L2.global [%0], %1;" ::"l"(p), "r"(bytes) : "memory"); }
__device__ __forceinline__ void wg_fence() { asm volatile("wgmma.fence.sync.aligned;" ::: "memory"); }
__device__ __forceinline__ void wg_commit() { asm volatile("wgmma.commit_group.sync.aligned;" ::: "memory"); }
template <int N> __device__ __forceinline__ void wg_wait() { asm volatile("wgmma.wait_group.sync.aligned %0;" ::"n"(N) : "memory"); }
template <int N> __device__ __forceinline__ void reg_fence(float (&d)[N]) {
#pragma unroll
  for (int i = 0; i < N; i++) asm volatile("" : "+f"(d[i])::"memory");
}
__device__ __forceinline__ void bar_sync(int id, int n) { asm volatile("bar.sync %0, %1;" ::"r"(id), "r"(n) : "memory"); }
__device__ __forceinline__ void bar_arrive(int id, int n) { asm volatile("bar.arrive %0, %1;" ::"r"(id), "r"(n) : "memory"); }
constexpr uint32_t DH128 = (1024 >> 4) | (1u << 30), DH64 = (512 >> 4) | (2u << 30);
__host__ __device__ constexpr uint32_t lbo(uint32_t bytes) { return (bytes >> 4) << 20; }
__device__ __forceinline__ uint32_t pack_bf16(float lo, float hi) { uint32_t r; asm("cvt.rn.bf16x2.f32 %0, %1, %2;" : "=r"(r) : "f"(hi), "f"(lo)); return r; }
__device__ __forceinline__ float bf_lo(uint32_t v) { return __uint_as_float(v << 16); }
__device__ __forceinline__ float bf_hi(uint32_t v) { return __uint_as_float(v & 0xffff0000u); }
__device__ __forceinline__ float bf_ld(const __nv_bfloat16* p) { return __bfloat162float(__ldg(p)); }
__device__ __forceinline__ float2 lds_f2(uint32_t a) { float2 v; asm volatile("ld.shared.v2.f32 {%0,%1}, [%2];" : "=f"(v.x), "=f"(v.y) : "r"(a)); return v; }
__device__ __forceinline__ float lds_f(uint32_t a) { float v; asm volatile("ld.shared.f32 %0, [%1];" : "=f"(v) : "r"(a)); return v; }
__device__ __forceinline__ uint32_t lds_u(uint32_t a) { uint32_t v; asm volatile("ld.shared.u32 %0, [%1];" : "=r"(v) : "r"(a)); return v; }
__device__ __forceinline__ uint4 lds_u4(uint32_t a) { uint4 v; asm volatile("ld.shared.v4.u32 {%0,%1,%2,%3}, [%4];" : "=r"(v.x), "=r"(v.y), "=r"(v.z), "=r"(v.w) : "r"(a)); return v; }
__device__ __forceinline__ void st_b128(uint4* p, uint32_t a, uint32_t b, uint32_t c, uint32_t d) {
  asm volatile("{.reg .b64 l, h; .reg .b128 v; mov.b64 l, {%1,%2}; mov.b64 h, {%3,%4}; mov.b128 v, {l,h}; st.relaxed.gpu.global.b128 [%0], v;}"
               ::"l"(p), "r"(a), "r"(b), "r"(c), "r"(d) : "memory");
}
__device__ __forceinline__ void ld_b128(const uint4* p, uint32_t& a, uint32_t& b, uint32_t& c, uint32_t& d) {
  asm volatile("{.reg .b64 l, h; .reg .b128 v; ld.relaxed.gpu.global.b128 v, [%4]; mov.b128 {l,h}, v; mov.b64 {%0,%1}, l; mov.b64 {%2,%3}, h;}"
               : "=r"(a), "=r"(b), "=r"(c), "=r"(d) : "l"(p) : "memory");
}
__device__ __forceinline__ float tanh_fast(float x) { float y; asm("tanh.approx.f32 %0, %1;" : "=f"(y) : "f"(x)); return y; }
__device__ __forceinline__ float gelu2(float v) {
  float p = fmaf(v * v, 0.0356774081363f, 0.7978845608029f);
  return fmaf(v, tanh_fast(v * p), v);
}
__device__ __forceinline__ uint32_t bf2_mul(uint32_t a, uint32_t b) { uint32_t r; asm("mul.rn.bf16x2 %0, %1, %2;" : "=r"(r) : "r"(a), "r"(b)); return r; }
__device__ __forceinline__ uint32_t bf2_add(uint32_t a, uint32_t b) { uint32_t r; asm("add.rn.bf16x2 %0, %1, %2;" : "=r"(r) : "r"(a), "r"(b)); return r; }
__device__ __forceinline__ void pin(float& a) { asm volatile("" : "+f"(a)::"memory"); }
__device__ __forceinline__ void pin(uint32_t& a) { asm volatile("" : "+r"(a)::"memory"); }
struct cplx { float re, im; };
__device__ __forceinline__ cplx cmul(cplx a, cplx b) { return {fmaf(a.re, b.re, -a.im * b.im), fmaf(a.re, b.im, a.im * b.re)}; }
__device__ __forceinline__ cplx cfma(cplx a, cplx b, cplx c) {
  return {fmaf(a.re, b.re, fmaf(-a.im, b.im, c.re)), fmaf(a.re, b.im, fmaf(a.im, b.re, c.im))};
}
__device__ __forceinline__ cplx make_lam(float lre, float lim, float ldt) {
  float dt = __bfloat162float(__float2bfloat16_rn(expf(ldt)));
  float mag = expf(dt * lre), sn, cs;
  sincospif(dt * lim * 0.31830988618379067f, &sn, &cs);
  return {mag * cs, mag * sn};
}

template<int TA,int TB,uint32_t AH,uint32_t BH> __device__ __forceinline__ void wgmma_n64_ss(float (&d)[32], uint32_t al, uint32_t ao, uint32_t bl, uint32_t bo, int scale_d){
  asm volatile("{.reg .pred p; .reg .b32 t, v; .reg .b64 da, db; setp.ne.b32 p, %36, 0; add.u32 t, %32, %33; mov.b64 da, {t, %39}; add.u32 v, %34, %35; mov.b64 db, {v, %40};\n"
   "wgmma.mma_async.sync.aligned.m64n64k16.f32.bf16.bf16 {%0,%1,%2,%3,%4,%5,%6,%7,%8,%9,%10,%11,%12,%13,%14,%15,%16,%17,%18,%19,%20,%21,%22,%23,%24,%25,%26,%27,%28,%29,%30,%31}, da, db, p, 1, 1, %37, %38;}"
   : "+f"(d[0]),"+f"(d[1]),"+f"(d[2]),"+f"(d[3]),"+f"(d[4]),"+f"(d[5]),"+f"(d[6]),"+f"(d[7]),"+f"(d[8]),"+f"(d[9]),"+f"(d[10]),"+f"(d[11]),"+f"(d[12]),"+f"(d[13]),"+f"(d[14]),"+f"(d[15]),"+f"(d[16]),"+f"(d[17]),"+f"(d[18]),"+f"(d[19]),"+f"(d[20]),"+f"(d[21]),"+f"(d[22]),"+f"(d[23]),"+f"(d[24]),"+f"(d[25]),"+f"(d[26]),"+f"(d[27]),"+f"(d[28]),"+f"(d[29]),"+f"(d[30]),"+f"(d[31])
   : "r"(al),"r"(ao >> 4),"r"(bl),"r"(bo >> 4),"r"(scale_d),"n"(TA),"n"(TB),"n"(AH),"n"(BH));
}
template<int TB,uint32_t BH> __device__ __forceinline__ void wgmma_n64_rs(float (&d)[32], uint32_t a0,uint32_t a1,uint32_t a2,uint32_t a3, uint32_t bl, uint32_t bo, int scale_d){
  asm volatile("{.reg .pred p; .reg .b32 t; .reg .b64 db; setp.ne.b32 p, %38, 0; add.u32 t, %36, %37; mov.b64 db, {t, %40};\n"
   "wgmma.mma_async.sync.aligned.m64n64k16.f32.bf16.bf16 {%0,%1,%2,%3,%4,%5,%6,%7,%8,%9,%10,%11,%12,%13,%14,%15,%16,%17,%18,%19,%20,%21,%22,%23,%24,%25,%26,%27,%28,%29,%30,%31}, {%32,%33,%34,%35}, db, p, 1, 1, %39;}"
   : "+f"(d[0]),"+f"(d[1]),"+f"(d[2]),"+f"(d[3]),"+f"(d[4]),"+f"(d[5]),"+f"(d[6]),"+f"(d[7]),"+f"(d[8]),"+f"(d[9]),"+f"(d[10]),"+f"(d[11]),"+f"(d[12]),"+f"(d[13]),"+f"(d[14]),"+f"(d[15]),"+f"(d[16]),"+f"(d[17]),"+f"(d[18]),"+f"(d[19]),"+f"(d[20]),"+f"(d[21]),"+f"(d[22]),"+f"(d[23]),"+f"(d[24]),"+f"(d[25]),"+f"(d[26]),"+f"(d[27]),"+f"(d[28]),"+f"(d[29]),"+f"(d[30]),"+f"(d[31])
   : "r"(a0),"r"(a1),"r"(a2),"r"(a3),"r"(bl),"r"(bo >> 4),"r"(scale_d),"n"(TB),"n"(BH));
}
template<int TA,int TB,uint32_t AH,uint32_t BH> __device__ __forceinline__ void wgmma_n96_ss(float (&d)[48], uint32_t al, uint32_t ao, uint32_t bl, uint32_t bo, int scale_d){
  asm volatile("{.reg .pred p; .reg .b32 t, v; .reg .b64 da, db; setp.ne.b32 p, %52, 0; add.u32 t, %48, %49; mov.b64 da, {t, %55}; add.u32 v, %50, %51; mov.b64 db, {v, %56};\n"
   "wgmma.mma_async.sync.aligned.m64n96k16.f32.bf16.bf16 {%0,%1,%2,%3,%4,%5,%6,%7,%8,%9,%10,%11,%12,%13,%14,%15,%16,%17,%18,%19,%20,%21,%22,%23,%24,%25,%26,%27,%28,%29,%30,%31,%32,%33,%34,%35,%36,%37,%38,%39,%40,%41,%42,%43,%44,%45,%46,%47}, da, db, p, 1, 1, %53, %54;}"
   : "+f"(d[0]),"+f"(d[1]),"+f"(d[2]),"+f"(d[3]),"+f"(d[4]),"+f"(d[5]),"+f"(d[6]),"+f"(d[7]),"+f"(d[8]),"+f"(d[9]),"+f"(d[10]),"+f"(d[11]),"+f"(d[12]),"+f"(d[13]),"+f"(d[14]),"+f"(d[15]),"+f"(d[16]),"+f"(d[17]),"+f"(d[18]),"+f"(d[19]),"+f"(d[20]),"+f"(d[21]),"+f"(d[22]),"+f"(d[23]),"+f"(d[24]),"+f"(d[25]),"+f"(d[26]),"+f"(d[27]),"+f"(d[28]),"+f"(d[29]),"+f"(d[30]),"+f"(d[31]),"+f"(d[32]),"+f"(d[33]),"+f"(d[34]),"+f"(d[35]),"+f"(d[36]),"+f"(d[37]),"+f"(d[38]),"+f"(d[39]),"+f"(d[40]),"+f"(d[41]),"+f"(d[42]),"+f"(d[43]),"+f"(d[44]),"+f"(d[45]),"+f"(d[46]),"+f"(d[47])
   : "r"(al),"r"(ao >> 4),"r"(bl),"r"(bo >> 4),"r"(scale_d),"n"(TA),"n"(TB),"n"(AH),"n"(BH));
}
template<int TA,int TB,uint32_t AH,uint32_t BH> __device__ __forceinline__ void wgmma_n128_ss(float (&d)[64], uint32_t al, uint32_t ao, uint32_t bl, uint32_t bo, int scale_d){
  asm volatile("{.reg .pred p; .reg .b32 t, v; .reg .b64 da, db; setp.ne.b32 p, %68, 0; add.u32 t, %64, %65; mov.b64 da, {t, %71}; add.u32 v, %66, %67; mov.b64 db, {v, %72};\n"
   "wgmma.mma_async.sync.aligned.m64n128k16.f32.bf16.bf16 {%0,%1,%2,%3,%4,%5,%6,%7,%8,%9,%10,%11,%12,%13,%14,%15,%16,%17,%18,%19,%20,%21,%22,%23,%24,%25,%26,%27,%28,%29,%30,%31,%32,%33,%34,%35,%36,%37,%38,%39,%40,%41,%42,%43,%44,%45,%46,%47,%48,%49,%50,%51,%52,%53,%54,%55,%56,%57,%58,%59,%60,%61,%62,%63}, da, db, p, 1, 1, %69, %70;}"
   : "+f"(d[0]),"+f"(d[1]),"+f"(d[2]),"+f"(d[3]),"+f"(d[4]),"+f"(d[5]),"+f"(d[6]),"+f"(d[7]),"+f"(d[8]),"+f"(d[9]),"+f"(d[10]),"+f"(d[11]),"+f"(d[12]),"+f"(d[13]),"+f"(d[14]),"+f"(d[15]),"+f"(d[16]),"+f"(d[17]),"+f"(d[18]),"+f"(d[19]),"+f"(d[20]),"+f"(d[21]),"+f"(d[22]),"+f"(d[23]),"+f"(d[24]),"+f"(d[25]),"+f"(d[26]),"+f"(d[27]),"+f"(d[28]),"+f"(d[29]),"+f"(d[30]),"+f"(d[31]),"+f"(d[32]),"+f"(d[33]),"+f"(d[34]),"+f"(d[35]),"+f"(d[36]),"+f"(d[37]),"+f"(d[38]),"+f"(d[39]),"+f"(d[40]),"+f"(d[41]),"+f"(d[42]),"+f"(d[43]),"+f"(d[44]),"+f"(d[45]),"+f"(d[46]),"+f"(d[47]),"+f"(d[48]),"+f"(d[49]),"+f"(d[50]),"+f"(d[51]),"+f"(d[52]),"+f"(d[53]),"+f"(d[54]),"+f"(d[55]),"+f"(d[56]),"+f"(d[57]),"+f"(d[58]),"+f"(d[59]),"+f"(d[60]),"+f"(d[61]),"+f"(d[62]),"+f"(d[63])
   : "r"(al),"r"(ao >> 4),"r"(bl),"r"(bo >> 4),"r"(scale_d),"n"(TA),"n"(TB),"n"(AH),"n"(BH));
}
template<int TB,uint32_t BH> __device__ __forceinline__ void wgmma_n128_rs(float (&d)[64], uint32_t a0,uint32_t a1,uint32_t a2,uint32_t a3, uint32_t bl, uint32_t bo, int scale_d){
  asm volatile("{.reg .pred p; .reg .b32 t; .reg .b64 db; setp.ne.b32 p, %70, 0; add.u32 t, %68, %69; mov.b64 db, {t, %72};\n"
   "wgmma.mma_async.sync.aligned.m64n128k16.f32.bf16.bf16 {%0,%1,%2,%3,%4,%5,%6,%7,%8,%9,%10,%11,%12,%13,%14,%15,%16,%17,%18,%19,%20,%21,%22,%23,%24,%25,%26,%27,%28,%29,%30,%31,%32,%33,%34,%35,%36,%37,%38,%39,%40,%41,%42,%43,%44,%45,%46,%47,%48,%49,%50,%51,%52,%53,%54,%55,%56,%57,%58,%59,%60,%61,%62,%63}, {%64,%65,%66,%67}, db, p, 1, 1, %71;}"
   : "+f"(d[0]),"+f"(d[1]),"+f"(d[2]),"+f"(d[3]),"+f"(d[4]),"+f"(d[5]),"+f"(d[6]),"+f"(d[7]),"+f"(d[8]),"+f"(d[9]),"+f"(d[10]),"+f"(d[11]),"+f"(d[12]),"+f"(d[13]),"+f"(d[14]),"+f"(d[15]),"+f"(d[16]),"+f"(d[17]),"+f"(d[18]),"+f"(d[19]),"+f"(d[20]),"+f"(d[21]),"+f"(d[22]),"+f"(d[23]),"+f"(d[24]),"+f"(d[25]),"+f"(d[26]),"+f"(d[27]),"+f"(d[28]),"+f"(d[29]),"+f"(d[30]),"+f"(d[31]),"+f"(d[32]),"+f"(d[33]),"+f"(d[34]),"+f"(d[35]),"+f"(d[36]),"+f"(d[37]),"+f"(d[38]),"+f"(d[39]),"+f"(d[40]),"+f"(d[41]),"+f"(d[42]),"+f"(d[43]),"+f"(d[44]),"+f"(d[45]),"+f"(d[46]),"+f"(d[47]),"+f"(d[48]),"+f"(d[49]),"+f"(d[50]),"+f"(d[51]),"+f"(d[52]),"+f"(d[53]),"+f"(d[54]),"+f"(d[55]),"+f"(d[56]),"+f"(d[57]),"+f"(d[58]),"+f"(d[59]),"+f"(d[60]),"+f"(d[61]),"+f"(d[62]),"+f"(d[63])
   : "r"(a0),"r"(a1),"r"(a2),"r"(a3),"r"(bl),"r"(bo >> 4),"r"(scale_d),"n"(TB),"n"(BH));
}

__global__ void __cluster_dims__(2, 1, 1) __launch_bounds__(384, 1)
fused_kernel(const __grid_constant__ Maps maps, const __nv_bfloat16* __restrict__ lam_re,
             const __nv_bfloat16* __restrict__ lam_im, const __nv_bfloat16* __restrict__ log_dt, const __nv_bfloat16* __restrict__ dskip,
             const __nv_bfloat16* __restrict__ b1, const __nv_bfloat16* __restrict__ b2, const __nv_bfloat16* __restrict__ gate_w,
             const __nv_bfloat16* __restrict__ pf_w1, const __nv_bfloat16* __restrict__ pf_w2, const __nv_bfloat16* __restrict__ pf_cre,
             const __nv_bfloat16* __restrict__ pf_cim, float* __restrict__ out) {
  extern __shared__ __align__(1024) unsigned char smem_raw[];
  const uint32_t sb = (uint32_t)__cvta_generic_to_shared(smem_raw);
  const int b = blockIdx.x;
  const int rank = b & 1, s = (b >> 1) & 7, m = ((b >> 4) << 1) | rank;
  const int warp = __shfl_sync(0xffffffffu, (int)(threadIdx.x >> 5), 0);
  const int lane = threadIdx.x & 31;
  const int kb0 = (s < 2) ? 2 : 0;

  if (warp == 8) {
    if (lane == 0) { TS(2, 0); TG(2); }
    if (lane < 23) mbar_init(sb + OFF_XFULL + 8 * lane, lane < 14 ? 1 : lane < 20 ? 16 : lane < 22 ? 64 : 32);
    asm volatile("fence.mbarrier_init.release.cluster;" ::: "memory");
    asm volatile("fence.proxy.async.shared::cta;" ::: "memory");
    __syncwarp();
    asm volatile("barrier.cluster.arrive.relaxed.aligned;" ::: "memory");
    if (lane == 0) {
      mbar_expect_tx(sb + OFF_XFULL, 16384);
      tma5d(sb + OFF_X, &maps.x, 0, 2 * m, sb + OFF_XFULL);
      mbar_expect_tx(sb + OFF_FULL, 16384);
      tma2d(sb + OFF_RING, &maps.bre, 0, s * 64, sb + OFF_FULL);
      tma2d(sb + OFF_RING + 8192, &maps.bim, 0, s * 64, sb + OFF_FULL);
      mbar_expect_tx(sb + OFF_XFULL + 8, 16384);
      tma5d(sb + OFF_X + 16384, &maps.x, 64, 2 * m, sb + OFF_XFULL + 8);
    }
    __syncwarp();
  } else {
    asm volatile("barrier.cluster.arrive.relaxed.aligned;" ::: "memory");
  }

  if (warp >= 8) {
    asm volatile("setmaxnreg.dec.sync.aligned.u32 56;");
    if (warp == 8) {
      asm volatile("barrier.cluster.wait.aligned;" ::: "memory");
      if (lane == 0) {
        TS(2, 1);
        const CUtensorMap* mb = rank ? &maps.bim : &maps.bre;
        const CUtensorMap* mc = rank ? &maps.cim : &maps.cre;
        int slot = 1; uint32_t ph = 1;
#pragma unroll 1
        for (int u = 1; u < 30; u++) {
          const uint32_t fb = sb + OFF_FULL + 8 * slot, dst = sb + OFF_RING + slot * 16384;
          if (u >= NSLOT) mbar_wait(sb + OFF_EMPTY + 8 * slot, ph);
          TS2(0, u);
          if (u < 8) {
            mbar_expect_tx(fb, 16384);
            tma2d_mc(dst + rank * 8192, mb, u * 64, s * 64, fb);
            if (u < 6) {
              mbar_expect_tx(sb + OFF_XFULL + 8 * (u + 1), 16384);
              tma5d(sb + OFF_X + (u + 1) * 16384, &maps.x, (u + 1) * 64, 2 * m, sb + OFF_XFULL + 8 * (u + 1));
              if (u == 5) {
                mbar_expect_tx(sb + OFF_XFULL + 56, 16384);
                tma5d(sb + OFF_X + 7 * 16384, &maps.x, 7 * 64, 2 * m, sb + OFF_XFULL + 56);
              }
            }
          } else if (u < 16) {
            mbar_expect_tx(fb, 12288);
            tma3d_mc(dst + rank * 6144, &maps.w1b, 0, (u - 8) * 64 + rank * 32, s * 7, fb);
          } else if (u < 24) {
            mbar_expect_tx(fb, 16384);
            tma2d_mc(dst + rank * 8192, &maps.w1a, s * 224 + 96 + rank * 64, ((u - 16 + kb0) & 7) * 64, fb);
          } else if (u < 26) {
            mbar_expect_tx(fb, 16384);
            tma2d_mc(dst + rank * 8192, u == 24 ? &maps.cre : &maps.cim, s * 64, ((s + 1 + rank) & 7) * 64, fb);
          } else {
            mbar_expect_tx(fb, 14336);
            tma2d_mc(dst + rank * 7168, &maps.w2, ((s + 1 + (u & 1)) & 7) * 64, s * 224 + ((u - 26) >> 1) * 112 + rank * 56, fb);
          }
          if (++slot == NSLOT) { slot = 0; ph ^= 1; }
        }
#pragma unroll 1
        for (int p = 2; p < 8; p++) {
          const int piece = (s + 1 + p) & 7;
#pragma unroll
          for (int j = 0; j < 3; j++) {
            const uint32_t fb = sb + OFF_FULL + 8 * slot, dst = sb + OFF_RING + slot * 16384;
            mbar_wait(sb + OFF_EMPTY + 8 * slot, ph);
            TS2(0, 24 + 3 * p + j);
            if (j == 0) {
              mbar_expect_tx(fb, 16384);
              tma2d_mc(dst + rank * 8192, mc, s * 64, piece * 64, fb);
            } else {
              mbar_expect_tx(fb, 14336);
              tma2d_mc(dst + rank * 7168, &maps.w2, piece * 64, s * 224 + (j - 1) * 112 + rank * 56, fb);
            }
            if (++slot == NSLOT) { slot = 0; ph ^= 1; }
          }
        }
        TS(2, 2);
      }
    } else if (warp == 11) {
      uint32_t v[4];
#pragma unroll
      for (int i = 0; i < 4; i++) v[i] = (i * 32 + lane < 112) ? __ldg(reinterpret_cast<const uint32_t*>(b1 + s * 224) + i * 32 + lane) : 0u;
#pragma unroll
      for (int i = 0; i < 4; i++)
        if (i * 32 + lane < 112) asm volatile("st.shared.v2.f32 [%0], {%1,%2};" ::"r"(sb + OFF_B1 + (i * 32 + lane) * 8), "f"(bf_lo(v[i])), "f"(bf_hi(v[i])) : "memory");
      asm volatile("barrier.cluster.wait.aligned;" ::: "memory");
      mbar_arrive(sb + OFF_BBAR);
      if ((PF & 2) && lane == 0) {
        mbar_wait(sb + OFF_XFULL + 8 * PFK, 0);
        l2_prefetch(pf_w1 + b * 7168, 14336);
        l2_prefetch(pf_cre + b * 2048, 4096);
        l2_prefetch(pf_cim + b * 2048, 4096);
        l2_prefetch(pf_w2 + b * 7168, 14336);
      }
    } else {
      const int t = threadIdx.x - 288;
      unsigned par;
      asm volatile("ld.relaxed.gpu.global.u32 %0, [%1];" : "=r"(par) : "l"(g_epoch + b) : "memory");
      const float pr = bf_ld(lam_re + s * 64 + t), pi = bf_ld(lam_im + s * 64 + t), pd = bf_ld(log_dt + s * 64 + t);
      const uint4* gwp = reinterpret_cast<const uint4*>(gate_w) + (lane & 7);
      uint4 wn = __ldg(gwp);
      asm volatile("barrier.cluster.wait.aligned;" ::: "memory");
      par = (par + 1) & 1;
      cplx l64 = make_lam(pr, pi, pd);
#pragma unroll
      for (int i = 0; i < 6; i++) l64 = cmul(l64, l64);
      const int row = s * 16 + (t >> 5) * 8 + (lane >> 3);
      const uint32_t xr0 = sb + OFF_X + row * 128 + (((lane & 7) ^ (row & 7)) << 4), xr1 = (xr0 + 512) ^ 64;
      float z0 = 0.f, z1 = 0.f;
#pragma unroll 1
      for (int kb = 0; kb < 8; kb++) {
        const uint4 w = wn;
        wn = __ldg(gwp + ((kb + 1) & 7) * 8);
        mbar_wait(sb + OFF_XFULL + 8 * kb, 0);
        const uint4 a = lds_u4(xr0 + kb * 16384), d = lds_u4(xr1 + kb * 16384);
        const uint32_t wv[4] = {w.x, w.y, w.z, w.w}, av[4] = {a.x, a.y, a.z, a.w}, dv[4] = {d.x, d.y, d.z, d.w};
#pragma unroll
        for (int c = 0; c < 4; c++) {
          const float wl = bf_lo(wv[c]), wh = bf_hi(wv[c]);
          z0 = fmaf(bf_hi(av[c]), wh, fmaf(bf_lo(av[c]), wl, z0));
          z1 = fmaf(bf_hi(dv[c]), wh, fmaf(bf_lo(dv[c]), wl, z1));
        }
      }
      {
        float zz = (lane & 4) ? z1 : z0;
        zz += __shfl_xor_sync(0xffffffffu, (lane & 4) ? z0 : z1, 4);
        zz += __shfl_xor_sync(0xffffffffu, zz, 2);
        zz += __shfl_xor_sync(0xffffffffu, zz, 1);
        const float rho = 4.f * expf(zz > 40.f ? 40.f : zz);
        if ((lane & 3) == 0)
          asm volatile("st.relaxed.gpu.global.u32 [%0], %1;" ::"l"(g_gate + m * 128 + row + (lane & 4)), "r"((__float_as_uint(rho) & ~1u) | par) : "memory");
      }
      if (t == 0) TS(3, 0);
      mbar_wait(sb + OFF_GBAR, 0);
      const float2 e0 = lds_f2(sb + OFF_CARRY + t * 8), e1 = lds_f2(sb + OFF_CARRY + 512 + t * 8);
      float2* eb = g_end + s * 1024 + t;
      {
        const cplx e = cfma(l64, cplx{e0.x, e0.y}, cplx{e1.x, e1.y});
        const unsigned long long v = ((unsigned long long)__float_as_uint(e.im) << 32) | ((__float_as_uint(e.re) & ~1u) | par);
        asm volatile("st.relaxed.gpu.global.b64 [%0], %1;" ::"l"(eb + m * 64), "l"(v) : "memory");
      }
      if (t == 0) TS(3, 1);
      {
        const unsigned* gp = g_gate + m * 128 + t;
        unsigned g0, g1;
        int tries = 0;
#pragma unroll 1
        do {
          asm volatile("ld.relaxed.gpu.global.u32 %0, [%1];" : "=r"(g0) : "l"(gp) : "memory");
          asm volatile("ld.relaxed.gpu.global.u32 %0, [%1];" : "=r"(g1) : "l"(gp + 64) : "memory");
        } while ((((g0 ^ par) | (g1 ^ par)) & 1) && ++tries < 200000);
        asm volatile("st.shared.u32 [%0], %1;" ::"r"(sb + OFF_GS + t * 4), "r"(g0) : "memory");
        asm volatile("st.shared.u32 [%0], %1;" ::"r"(sb + OFF_GS + 256 + t * 4), "r"(g1) : "memory");
      }
      if (t == 0) TS(3, 2);
      cplx S = {0.f, 0.f};
      {
        uint32_t er[15], ei[15], bad;
        int tries = 0;
#pragma unroll 1
        do {
          bad = 0;
#pragma unroll
          for (int i = 0; i < 15; i++) {
            er[i] = par; ei[i] = 0;
            asm volatile("{.reg .pred p; .reg .b64 v; setp.lt.s32 p, %3, %4; @p ld.relaxed.gpu.global.b64 v, [%2]; @p mov.b64 {%0,%1}, v;}"
                         : "+r"(er[i]), "+r"(ei[i]) : "l"(eb + i * 64), "r"(i), "r"(m) : "memory");
          }
#pragma unroll
          for (int i = 0; i < 15; i++) bad |= er[i] ^ par;
        } while ((bad & 1) && ++tries < 200000);
        const cplx l128 = cmul(l64, l64);
#pragma unroll
        for (int i = 0; i < 15; i++)
          if (i < m) S = cfma(l128, S, cplx{__uint_as_float(er[i]), __uint_as_float(ei[i])});
      }
      const cplx S1 = cfma(l64, S, cplx{e0.x, e0.y});
      asm volatile("st.shared.v2.f32 [%0], {%1,%2};" ::"r"(sb + OFF_CARRY + t * 8), "f"(S.re), "f"(S.im) : "memory");
      asm volatile("st.shared.v2.f32 [%0], {%1,%2};" ::"r"(sb + OFF_CARRY + 512 + t * 8), "f"(S1.re), "f"(S1.im) : "memory");
      mbar_arrive(sb + OFF_CBAR);
      if (t == 0) TS(3, 3);
    }
  } else {
    const int wg = warp >> 2, w = warp & 3, q = lane & 3, gr = lane >> 2;
    unsigned epoch;
    asm volatile("ld.relaxed.gpu.global.u32 %0, [%1];" : "=r"(epoch) : "l"(g_epoch + b) : "memory");
    const int c0 = s * 64 + w * 16 + gr;
    float pr[2], pi[2], pd[2];
#pragma unroll
    for (int h = 0; h < 2; h++) { pr[h] = bf_ld(lam_re + c0 + 8 * h); pi[h] = bf_ld(lam_im + c0 + 8 * h); pd[h] = bf_ld(log_dt + c0 + 8 * h); }
    asm volatile("setmaxnreg.inc.sync.aligned.u32 224;");
    asm volatile("barrier.cluster.wait.aligned;" ::: "memory");
    TS(wg, 0);
    uint32_t ebar;
    asm volatile("mapa.shared::cluster.u32 %0, %1, %2;" : "=r"(ebar) : "r"(sb + OFF_EMPTY), "r"(lane & 1));
    auto release = [&](int slot) { if (lane < 2) mbar_arrive_cl(ebar + 8 * slot); };
    const uint32_t xw = sb + OFF_X + wg * 8192, fullb = sb + OFF_FULL;
    const uint32_t dxw = (xw & 0x3FFFF) >> 4, dring = ((sb + OFF_RING) & 0x3FFFF) >> 4;

    float ure[32], uim[32], aa[48], ab[64];
    cplx lam[2], coef[2], l16[2], l32[2], lq[2], pre[2], e[2];
#pragma unroll
    for (int h = 0; h < 2; h++) {
      lam[h] = make_lam(pr[h], pi[h], pd[h]);
      const float inv = __fdividef(1.f, fmaf(pr[h], pr[h], pi[h] * pi[h]));
      coef[h] = cmul(cplx{lam[h].re - 1.f, lam[h].im}, cplx{pr[h] * inv, -pi[h] * inv});
      cplx t = cmul(lam[h], lam[h]); t = cmul(t, t); t = cmul(t, t);
      l16[h] = cmul(t, t); l32[h] = cmul(l16[h], l16[h]);
      cplx a = (q & 1) ? l16[h] : cplx{1.f, 0.f}, c = (q & 2) ? l32[h] : cplx{1.f, 0.f};
      lq[h] = cmul(cmul(a, c), coef[h]);
      pin(lq[h].re); pin(lq[h].im);
    }
    const uint32_t par = (epoch + 1) & 1;
    TS(wg, 24);

#pragma unroll
    for (int kb = 0; kb < 8; kb++) {
      const int slot = kb % NSLOT;
      TS2(1, kb);
      mbar_wait(sb + OFF_XFULL + 8 * kb, 0);
      if (kb == 0) TS(wg, 18);
      mbar_wait(fullb + 8 * slot, (kb / NSLOT) & 1);
      TS2(2, kb);
      if (kb == 0) TS(wg, 1);
      wg_fence();
#pragma unroll
      for (int kk = 0; kk < 4; kk++) {
        wgmma_n64_ss<0, 0, DH128, DH128>(ure, dring, slot * 16384 + kk * 32, dxw, kb * 16384 + kk * 32, (kb | kk) != 0);
        wgmma_n64_ss<0, 0, DH128, DH128>(uim, dring, slot * 16384 + 8192 + kk * 32, dxw, kb * 16384 + kk * 32, (kb | kk) != 0);
      }
      wg_commit();
      if (kb > 0) { wg_wait<1>(); release((kb - 1) % NSLOT); }
      if (kb == 3) mbar_wait(sb + OFF_BBAR, 0);
      if (kb >= 3 && kb < 7) {
#pragma unroll
        for (int j = (kb - 3) * 3; j < (kb - 2) * 3; j++) {
          const float2 v = lds_f2(sb + OFF_B1 + j * 32 + q * 8), v2 = lds_f2(sb + OFF_B1 + j * 32 + q * 8);
          aa[4 * j] = v.x; aa[4 * j + 1] = v.y; aa[4 * j + 2] = v2.x; aa[4 * j + 3] = v2.y;
        }
      }
    }
    TS(wg, 2);
#pragma unroll
    for (int kb = 0; kb < 8; kb++) {
      const int u = 8 + kb, slot = u % NSLOT;
      TS2(1, u);
      mbar_wait(fullb + 8 * slot, (u / NSLOT) & 1);
      TS2(2, u);
      wg_fence();
#pragma unroll
      for (int kk = 0; kk < 4; kk++)
        wgmma_n96_ss<0, 1, DH128, DH64>(aa, dxw, kb * 16384 + kk * 32, dring, slot * 16384 + (kk >> 1) * 6144 + (kk & 1) * 1024 + lbo(2048), 1);
      wg_commit();
      wg_wait<1>();
      release((u - 1) % NSLOT);
      if (kb == 0) {
        reg_fence(ure); reg_fence(uim);
#pragma unroll
        for (int h = 0; h < 2; h++) e[h] = cplx{ure[2 * h], uim[2 * h]};
      }
      if (kb < 3) {
#pragma unroll
        for (int t = 1 + 5 * kb; t < 6 + 5 * kb; t++)
#pragma unroll
          for (int h = 0; h < 2; h++) { const int i = 4 * (t >> 1) + 2 * h + (t & 1); e[h] = cfma(lam[h], e[h], cplx{ure[i], uim[i]}); }
#pragma unroll
        for (int h = 0; h < 2; h++) { pin(e[h].re); pin(e[h].im); }
      } else if (kb == 3) {
#pragma unroll
        for (int h = 0; h < 2; h++) {
          cplx y = {__shfl_up_sync(0xffffffffu, e[h].re, 1, 4), __shfl_up_sync(0xffffffffu, e[h].im, 1, 4)};
          if (q >= 1) e[h] = cfma(l16[h], y, e[h]);
          y = cplx{__shfl_up_sync(0xffffffffu, e[h].re, 2, 4), __shfl_up_sync(0xffffffffu, e[h].im, 2, 4)};
          if (q >= 2) e[h] = cfma(l32[h], y, e[h]);
        }
        if (q == 3) {
#pragma unroll
          for (int h = 0; h < 2; h++)
            asm volatile("st.shared.v2.f32 [%0], {%1,%2};" ::"r"(sb + OFF_CARRY + wg * 512 + (w * 16 + gr + 8 * h) * 8), "f"(e[h].re), "f"(e[h].im) : "memory");
          mbar_arrive(sb + OFF_GBAR);
        }
#pragma unroll
        for (int h = 0; h < 2; h++) {
          const cplx y = {__shfl_up_sync(0xffffffffu, e[h].re, 1, 4), __shfl_up_sync(0xffffffffu, e[h].im, 1, 4)};
          pre[h] = (q >= 1) ? cmul(coef[h], y) : cplx{0.f, 0.f};
          pin(pre[h].re); pin(pre[h].im);
        }
        TS(wg, 3);
      } else {
#pragma unroll
        for (int i = (kb - 4) * 8; i < (kb - 3) * 8; i++) {
          pin(ure[i]); pin(uim[i]);
          const cplx v = cmul(coef[(i >> 1) & 1], cplx{ure[i], uim[i]});
          ure[i] = v.re; uim[i] = v.im;
          pin(ure[i]); pin(uim[i]);
        }
#pragma unroll
        for (int j = (kb - 4) * 4; j < (kb - 3) * 4; j++) {
          const float2 v = lds_f2(sb + OFF_B1 + 384 + j * 32 + q * 8), v2 = lds_f2(sb + OFF_B1 + 384 + j * 32 + q * 8);
          ab[4 * j] = v.x; ab[4 * j + 1] = v.y; ab[4 * j + 2] = v2.x; ab[4 * j + 3] = v2.y;
        }
      }
    }
    TS(wg, 4);
    uint32_t H[56];
    cplx hst[2];
    const uint32_t hbase = xw + kb0 * 16384, dh = dxw + kb0 * 1024;
    const uint32_t hst_addr = hbase + (w * 16 + (lane & 15)) * 128 + (((lane >> 4) ^ (lane & 7)) << 4);
#pragma unroll
    for (int kb = 0; kb < 8; kb++) {
      const int u = 16 + kb, slot = u % NSLOT;
      TS2(1, u);
      mbar_wait(fullb + 8 * slot, (u / NSLOT) & 1);
      TS2(2, u);
      wg_fence();
      const uint32_t dxa = dxw + ((kb + kb0) & 7) * 1024;
#pragma unroll
      for (int kk = 0; kk < 4; kk++)
        wgmma_n128_ss<0, 1, DH128, DH128>(ab, dxa, kk * 32, dring, slot * 16384 + kk * 2048 + lbo(8192), 1);
      wg_commit();
      wg_wait<1>();
      release((u - 1) % NSLOT);
      if (kb < 3 || kb == 7) {
        const int ch = kb < 3 ? kb : 3;
#pragma unroll
        for (int i = ch * 6; i < ch * 6 + 6; i++) {
          pin(aa[2 * i]); pin(aa[2 * i + 1]);
          H[i] = pack_bf16(gelu2(aa[2 * i]), gelu2(aa[2 * i + 1]));
          pin(H[i]);
        }
      } else {
        if (kb == 3) {
          TS(wg, 5);
          mbar_wait(sb + OFF_CBAR, 0);
          TS(wg, 6);
#pragma unroll
          for (int h = 0; h < 2; h++) {
            const float2 c = lds_f2(sb + OFF_CARRY + wg * 512 + (w * 16 + gr + 8 * h) * 8);
            hst[h] = cfma(lq[h], cplx{c.x, c.y}, pre[h]);
          }
        }
        const int j0 = (kb - 3) * 2;
        uint32_t rr[4], ri[4];
#pragma unroll
        for (int jj = 0; jj < 2; jj++) {
          const int j = j0 + jj;
          const float2 g2 = lds_f2(sb + OFF_GS + (wg * 64 + j * 8 + q * 2) * 4);
#pragma unroll
          for (int h = 0; h < 2; h++) {
            const int i = 4 * j + 2 * h;
            const cplx h0 = cfma(lam[h], hst[h], cplx{ure[i], uim[i]});
            hst[h] = cfma(lam[h], h0, cplx{ure[i + 1], uim[i + 1]});
            rr[jj * 2 + h] = pack_bf16(h0.re * g2.x, hst[h].re * g2.y);
            ri[jj * 2 + h] = pack_bf16(-h0.im * g2.x, -hst[h].im * g2.y);
          }
        }
        const uint32_t a = hst_addr ^ (j0 << 4);
        asm volatile("stmatrix.sync.aligned.m8n8.x4.shared.b16 [%0], {%1,%2,%3,%4};" ::"r"(a), "r"(rr[0]), "r"(rr[1]), "r"(rr[2]), "r"(rr[3]) : "memory");
        asm volatile("stmatrix.sync.aligned.m8n8.x4.shared.b16 [%0], {%1,%2,%3,%4};" ::"r"(a + 16384), "r"(ri[0]), "r"(ri[1]), "r"(ri[2]), "r"(ri[3]) : "memory");
        if (kb == 6) asm volatile("fence.proxy.async.shared::cta;" ::: "memory");
      }
    }
    bar_sync(1 + wg, 128);
    TS(wg, 7);

    uint4* const psend = g_part + (size_t)m * (8 * 7 * 1024) + threadIdx.x;
    const uint4* const precv = g_part + (size_t)(m * 8 + s) * (7 * 1024) + threadIdx.x;
    auto send = [&](const float* o, int p) {
      uint4* dst = psend + (((s + 1 + p) & 7) * 7 + p) * 1024;
#pragma unroll
      for (int i = 0; i < 4; i++) {
        uint32_t t0;
        asm("lop3.b32 %0, %1, 0xfffffffe, %2, 0xea;" : "=r"(t0) : "r"(pack_bf16(o[8 * i], o[8 * i + 1])), "r"(par));
        st_b128(dst + i * 256, t0, pack_bf16(o[8 * i + 2], o[8 * i + 3]), pack_bf16(o[8 * i + 4], o[8 * i + 5]), pack_bf16(o[8 * i + 6], o[8 * i + 7]));
      }
    };
    auto recv_issue = [&](uint32_t (&r)[16], int p) {
#pragma unroll
      for (int i = 0; i < 4; i++) ld_b128(precv + p * 1024 + i * 256, r[4 * i], r[4 * i + 1], r[4 * i + 2], r[4 * i + 3]);
    };
    auto recv_check = [&](uint32_t (&r)[16], int p) {
      if (__builtin_expect(__any_sync(0xffffffffu, ((r[0] ^ par) | (r[4] ^ par) | (r[8] ^ par) | (r[12] ^ par)) & 1), 0)) {
        int tries = 0;
#pragma unroll 1
        do { recv_issue(r, p); } while (__any_sync(0xffffffffu, ((r[0] ^ par) | (r[4] ^ par) | (r[8] ^ par) | (r[12] ^ par)) & 1) && ++tries < 200000);
      }
    };
    float sum[32];
    auto recv_add = [&](uint32_t (&r)[16], int p) {
      recv_check(r, p);
#pragma unroll
      for (int i = 0; i < 16; i++) { sum[2 * i] += bf_lo(r[i]); sum[2 * i + 1] += bf_hi(r[i]); }
      reg_fence(sum);
    };
    {
      float o2[64];
      auto gelu_b = [&](int i0, int i1) {
#pragma unroll
        for (int i = i0; i < i1; i++) {
          pin(ab[2 * i]); pin(ab[2 * i + 1]);
          H[24 + i] = pack_bf16(gelu2(ab[2 * i]), gelu2(ab[2 * i + 1]));
          pin(H[24 + i]);
        }
      };
      auto mma_h2 = [&](int part) {
        wg_fence();
#pragma unroll
        for (int kk = 0; kk < 4; kk++)
          wgmma_n128_ss<1, 0, DH128, DH128>(o2, dh, part * 16384 + kk * 2048, dring, part * 16384 + kk * 32, (part | kk) != 0);
        wg_commit();
      };
      auto mma_w2 = [&](int k0, int k1) {
        wg_fence();
#pragma unroll
        for (int kk = k0; kk < k1; kk++)
          wgmma_n128_rs<1, DH128>(o2, H[4 * kk], H[4 * kk + 1], H[4 * kk + 2], H[4 * kk + 3], dring, 32768 + (kk / 7) * 32768 + (kk % 7) * 2048 + lbo(16384), 1);
        wg_commit();
      };
      mbar_wait(fullb + 0, 0);
      mma_h2(0);
      wg_wait<1>(); release(5);
      gelu_b(0, 6);
      mbar_wait(fullb + 8, 0);
      mma_h2(1);
      wg_wait<1>(); release(0);
      gelu_b(6, 12);
      mbar_wait(fullb + 16, 0); mbar_wait(fullb + 24, 0);
      mma_w2(0, 4);
      wg_wait<1>(); release(1);
      gelu_b(12, 18);
      mma_w2(4, 7);
      gelu_b(18, 23);
      mbar_wait(fullb + 32, 0); mbar_wait(fullb + 40, 0);
      mma_w2(7, 10);
      wg_wait<1>(); release(2); release(3);
      gelu_b(23, 28);
      mma_w2(10, 12);
      gelu_b(28, 32);
      if (wg == 1) bar_sync(4, 256);
      mma_w2(12, 14);
      bar_arrive(4 - wg, 256);
      wg_wait<0>(); release(4); release(5);
      reg_fence(o2);
      TS(wg, 8);
      send(o2, 0); send(o2 + 32, 1);
      TS(wg, 9);
    }
    float o[32], rho[2];
    uint32_t r0[16], r1[16];
#pragma unroll
    for (int p = 2; p < 8; p++) {
      const int sl0 = 3 * (p & 1);
      const uint32_t ph = (p >> 1) & 1;
      if (p == 2) {
#pragma unroll
        for (int j = 0; j < 8; j++) {
          r0[j] = __ldg(reinterpret_cast<const uint32_t*>(dskip + s * 64 + j * 8) + q);
          r0[8 + j] = __ldg(reinterpret_cast<const uint32_t*>(b2 + s * 64 + j * 8) + q);
        }
      }
      if (p == 4 || p == 5) { recv_issue(r0, 2 * p - 8); recv_issue(r1, 2 * p - 7); }
      if (p >= 6) recv_issue(r0, p - 2);
      mbar_wait(fullb + 8 * sl0, ph);
      bar_sync(3 + wg, 256);
      if (p == 6) TS(wg, 20);
      wg_fence();
#pragma unroll
      for (int kk = 0; kk < 8; kk++)
        wgmma_n64_ss<1, 0, DH128, DH128>(o, dh, (kk >> 2) * 16384 + (kk & 3) * 2048, dring, sl0 * 16384 + (kk >> 2) * 8192 + (kk & 3) * 32, kk != 0);
#pragma unroll
      for (int hf = 0; hf < 2; hf++) {
        mbar_wait(fullb + 8 * (sl0 + 1 + hf), ph);
        wg_fence();
#pragma unroll
        for (int kk = 7 * hf; kk < 7 * hf + 7; kk++)
          wgmma_n64_rs<1, DH128>(o, H[4 * kk], H[4 * kk + 1], H[4 * kk + 2], H[4 * kk + 3], dring, (sl0 + 1 + hf) * 16384 + (kk % 7) * 2048, 1);
        wg_commit();
      }
      if (p < 7 || wg == 0) bar_arrive(4 - wg, 256);
      if (p == 6) TS(wg, 21);
      if (p == 7) recv_issue(r1, 6);
      if (p < 6) { wg_wait<1>(); release(sl0); release(sl0 + 1); }
      if (p == 2 || p == 3) {
        if (p == 2) {
#pragma unroll
          for (int h = 0; h < 2; h++) rho[h] = lds_f(sb + OFF_GS + (wg * 64 + w * 16 + gr + 8 * h) * 4);
        }
#pragma unroll
        for (int j = (p - 2) * 4; j < (p - 1) * 4; j++) {
          const uint32_t bb = bf2_add(r0[8 + j], r0[8 + j]);
#pragma unroll
          for (int h = 0; h < 2; h++) {
            const uint32_t xd = bf2_mul(lds_u(xw + s * 16384 + (w * 16 + gr + 8 * h) * 128 + ((j ^ gr) << 4) + q * 4), r0[j]);
            sum[4 * j + 2 * h] = fmaf(0.5f * rho[h], bf_lo(xd), bf_lo(bb));
            sum[4 * j + 2 * h + 1] = fmaf(0.5f * rho[h], bf_hi(xd), bf_hi(bb));
            pin(sum[4 * j + 2 * h]); pin(sum[4 * j + 2 * h + 1]);
          }
        }
      } else {
        recv_add(r0, p < 6 ? 2 * p - 8 : p - 2);
      }
      if (p == 6) TS(wg, 22);
      wg_wait<0>();
      if (p < 6) release(sl0 + 2);
      reg_fence(o);
      if (p == 6) TS(wg, 23);
      if (p < 7) send(o, p);
      if (p == 4 || p == 5) recv_add(r1, 2 * p - 7);
      TS(wg, 8 + p);
    }
    {
      float fs[2];
#pragma unroll
      for (int h = 0; h < 2; h++) fs[h] = __fdividef(2.f, 4.f + rho[h]);
#pragma unroll
      for (int i = 0; i < 32; i++) sum[i] = (sum[i] + o[i]) * fs[(i >> 1) & 1];
      reg_fence(sum);
      recv_check(r1, 6);
      TS(wg, 16);
      float* op = out + (size_t)(m * 128 + wg * 64 + (gr >> 1) * 16 + w * 4 + (gr & 1)) * DM + s * 64 + q * 2;
#pragma unroll
      for (int i = 0; i < 16; i++)
        *reinterpret_cast<float2*>(op + (i & 1) * 2 * DM + (i >> 1) * 8) =
            make_float2(fmaf(bf_lo(r1[i]), fs[i & 1], sum[2 * i]), fmaf(bf_hi(r1[i]), fs[i & 1], sum[2 * i + 1]));
      if (threadIdx.x == 128) g_epoch[b] = epoch + 1;
      TS(wg, 17); TG(wg);
    }
  }
}

typedef CUresult (*EncFn)(CUtensorMap*, CUtensorMapDataType, cuuint32_t, void*, const cuuint64_t*, const cuuint64_t*, const cuuint32_t*,
                          const cuuint32_t*, CUtensorMapInterleave, CUtensorMapSwizzle, CUtensorMapL2promotion, CUtensorMapFloatOOBfill);

void encode(EncFn f, CUtensorMap* mp, const void* p, int rank, const cuuint64_t* dims, const cuuint64_t* strides, const cuuint32_t* box, CUtensorMapSwizzle sw) {
  cuuint32_t es[5] = {1, 1, 1, 1, 1};
  f(mp, CU_TENSOR_MAP_DATA_TYPE_BFLOAT16, rank, const_cast<void*>(p), dims, strides, box, es, CU_TENSOR_MAP_INTERLEAVE_NONE, sw,
    CU_TENSOR_MAP_L2_PROMOTION_L2_128B, CU_TENSOR_MAP_FLOAT_OOB_FILL_NONE);
}

}

extern "C" void kernel_launch(void* const* d_in, const int* in_sizes, int n_in, void* d_out, int out_size) {
  typedef const __nv_bfloat16* bp;
  bp x = (bp)d_in[0], lre = (bp)d_in[1], lim = (bp)d_in[2], bre = (bp)d_in[3], bim = (bp)d_in[4], cre = (bp)d_in[5], cim = (bp)d_in[6],
     ldt = (bp)d_in[7], dsk = (bp)d_in[8], w1 = (bp)d_in[10], b1 = (bp)d_in[11], w2 = (bp)d_in[12], b2 = (bp)d_in[13], gw = (bp)d_in[14];
  static EncFn enc = nullptr;
  if (!enc) {
    void* f = nullptr;
    cudaDriverEntryPointQueryResult qr;
    cudaGetDriverEntryPoint("cuTensorMapEncodeTiled", &f, cudaEnableDefault, &qr);
    enc = (EncFn)f;
    cudaFuncSetAttribute(fused_kernel, cudaFuncAttributeMaxDynamicSharedMemorySize, SMEM_BYTES);
  }
  Maps maps;
  {
    cuuint64_t d[5] = {DM, 2, 4, 8, SEQ / 64}, st[4] = {DM * 2, 16 * DM * 2, 2 * DM * 2, 64 * DM * 2};
    cuuint32_t bx[5] = {64, 2, 4, 8, 2};
    encode(enc, &maps.x, x, 5, d, st, bx, CU_TENSOR_MAP_SWIZZLE_128B);
  }
  {
    cuuint64_t d[2] = {DM, DM}, st[1] = {DM * 2};
    cuuint32_t bx[2] = {64, 64};
    encode(enc, &maps.bre, bre, 2, d, st, bx, CU_TENSOR_MAP_SWIZZLE_128B);
    encode(enc, &maps.bim, bim, 2, d, st, bx, CU_TENSOR_MAP_SWIZZLE_128B);
    encode(enc, &maps.cre, cre, 2, d, st, bx, CU_TENSOR_MAP_SWIZZLE_128B);
    encode(enc, &maps.cim, cim, 2, d, st, bx, CU_TENSOR_MAP_SWIZZLE_128B);
  }
  {
    cuuint64_t d[2] = {FF, DM}, st[1] = {FF * 2};
    cuuint32_t bx[2] = {64, 64};
    encode(enc, &maps.w1a, w1, 2, d, st, bx, CU_TENSOR_MAP_SWIZZLE_128B);
    cuuint64_t d3[3] = {32, DM, FF / 32}, st3[2] = {FF * 2, 64};
    cuuint32_t bx3[3] = {32, 32, 3};
    encode(enc, &maps.w1b, w1, 3, d3, st3, bx3, CU_TENSOR_MAP_SWIZZLE_64B);
  }
  {
    cuuint64_t d[2] = {DM, FF}, st[1] = {DM * 2};
    cuuint32_t bx[2] = {64, 56};
    encode(enc, &maps.w2, w2, 2, d, st, bx, CU_TENSOR_MAP_SWIZZLE_128B);
  }
  fused_kernel<<<128, 384, SMEM_BYTES>>>(maps, lre, lim, ldt, dsk, b1, b2, gw, w1, w2, cre, cim, (float*)d_out);
}
```

```cpp
#include <cuda_runtime.h>
#include <cuda_bf16.h>
#include <cuda.h>
#include <stdint.h>

#define PF 2
#define PFK 2
namespace {

constexpr int SEQ = 2048, DM = 512, FF = 1792;
constexpr int NSLOT = 6;
constexpr uint32_t OFF_X = 0, OFF_RING = 131072, OFF_MISC = 229376;
constexpr uint32_t OFF_XFULL = OFF_MISC, OFF_FULL = OFF_XFULL + 64, OFF_EMPTY = OFF_FULL + 48, OFF_GBAR = OFF_EMPTY + 48,
                   OFF_CBAR = OFF_GBAR + 8;
constexpr uint32_t OFF_GS = OFF_MISC + 256;
constexpr uint32_t OFF_CARRY = OFF_GS + 512;
constexpr uint32_t SMEM_BYTES = OFF_CARRY + 1024;
static_assert(SMEM_BYTES <= 232448, "smem");

struct Maps { CUtensorMap x, bre, bim, w1a, w1b, w2, cre, cim; };

__device__ uint4 g_part[16 * 8 * 7 * 1024];
__device__ float2 g_end[8 * 16 * 64];
__device__ unsigned g_gate[SEQ];
__device__ unsigned g_epoch[128];
#define TG(role) do {} while (0)
#define TS2(role, i) do {} while (0)
#define TS(role, i) do {} while (0)

__device__ __forceinline__ void mbar_init(uint32_t bar, uint32_t cnt) { asm volatile("mbarrier.init.shared::cta.b64 [%0], %1;" ::"r"(bar), "r"(cnt)); }
__device__ __forceinline__ void mbar_expect_tx(uint32_t bar, uint32_t bytes) { asm volatile("mbarrier.arrive.expect_tx.shared::cta.b64 _, [%0], %1;" ::"r"(bar), "r"(bytes) : "memory"); }
__device__ __forceinline__ void mbar_arrive(uint32_t bar) { asm volatile("mbarrier.arrive.shared::cta.b64 _, [%0];" ::"r"(bar) : "memory"); }
__device__ __forceinline__ void mbar_arrive_cl(uint32_t cbar) { asm volatile("mbarrier.arrive.shared::cluster.b64 _, [%0];" ::"r"(cbar) : "memory"); }
__device__ __forceinline__ void mbar_wait(uint32_t bar, uint32_t parity) {
  asm volatile(
      "{\n.reg .pred p;\n.reg .u32 c;\n"
      "mbarrier.try_wait.parity.shared::cta.b64 p, [%0], %1;\n"
      "@p bra.uni LAB_DONE;\n"
      "mov.u32 c, 0;\n"
      "LAB_WAIT:\n"
      "mbarrier.try_wait.parity.shared::cta.b64 p, [%0], %1;\n"
      "@p bra.uni LAB_DONE;\n"
      "add.u32 c, c, 1;\nsetp.lt.u32 p, c, 200000;\n@p bra.uni LAB_WAIT;\n"
      "LAB_DONE:\n}" ::"r"(bar), "r"(parity) : "memory");
}
__device__ __forceinline__ void tma2d(uint32_t dst, const CUtensorMap* m, int c0, int c1, uint32_t bar) {
  asm volatile("cp.async.bulk.tensor.2d.shared::cluster.global.mbarrier::complete_tx::bytes [%0], [%1, {%3,%4}], [%2];"
               ::"r"(dst), "l"(m), "r"(bar), "r"(c0), "r"(c1) : "memory");
}
__device__ __forceinline__ void tma2d_mc(uint32_t dst, const CUtensorMap* m, int c0, int c1, uint32_t bar) {
  asm volatile("cp.async.bulk.tensor.2d.shared::cluster.global.mbarrier::complete_tx::bytes.multicast::cluster [%0], [%1, {%3,%4}], [%2], %5;"
               ::"r"(dst), "l"(m), "r"(bar), "r"(c0), "r"(c1), "h"((uint16_t)3) : "memory");
}
__device__ __forceinline__ void tma3d_mc(uint32_t dst, const CUtensorMap* m, int c0, int c1, int c2, uint32_t bar) {
  asm volatile("cp.async.bulk.tensor.3d.shared::cluster.global.mbarrier::complete_tx::bytes.multicast::cluster [%0], [%1, {%3,%4,%5}], [%2], %6;"
               ::"r"(dst), "l"(m), "r"(bar), "r"(c0), "r"(c1), "r"(c2), "h"((uint16_t)3) : "memory");
}
__device__ __forceinline__ void tma5d(uint32_t dst, const CUtensorMap* m, int c0, int c4, uint32_t bar) {
  asm volatile("cp.async.bulk.tensor.5d.shared::cluster.global.mbarrier::complete_tx::bytes [%0], [%1, {%3,%5,%5,%5,%4}], [%2];"
               ::"r"(dst), "l"(m), "r"(bar), "r"(c0), "r"(c4), "r"(0) : "memory");
}
__device__ __forceinline__ void l2_prefetch(const void* p, uint32_t bytes) { asm volatile("cp.async.bulk.prefetch.L2.global [%0], %1;" ::"l"(p), "r"(bytes) : "memory"); }
__device__ __forceinline__ bool elect_one() {
  uint32_t pred;
  asm volatile("{.reg .pred P; elect.sync _|P, 0xffffffff; selp.u32 %0, 1, 0, P;}" : "=r"(pred));
  return pred != 0;
}
__device__ __forceinline__ void wg_fence() { asm volatile("wgmma.fence.sync.aligned;" ::: "memory"); }
__device__ __forceinline__ void wg_commit() { asm volatile("wgmma.commit_group.sync.aligned;" ::: "memory"); }
template <int N> __device__ __forceinline__ void wg_wait() { asm volatile("wgmma.wait_group.sync.aligned %0;" ::"n"(N) : "memory"); }
template <int N> __device__ __forceinline__ void reg_fence(float (&d)[N]) {
#pragma unroll
  for (int i = 0; i < N; i++) asm volatile("" : "+f"(d[i])::"memory");
}
__device__ __forceinline__ void bar_sync(int id, int n) { asm volatile("bar.sync %0, %1;" ::"r"(id), "r"(n) : "memory"); }
__device__ __forceinline__ void bar_arrive(int id, int n) { asm volatile("bar.arrive %0, %1;" ::"r"(id), "r"(n) : "memory"); }
constexpr uint32_t DH128 = (1024 >> 4) | (1u << 30), DH64 = (512 >> 4) | (2u << 30);
__host__ __device__ constexpr uint32_t lbo(uint32_t bytes) { return (bytes >> 4) << 20; }
__device__ __forceinline__ uint32_t pack_bf16(float lo, float hi) { uint32_t r; asm("cvt.rn.bf16x2.f32 %0, %1, %2;" : "=r"(r) : "f"(hi), "f"(lo)); return r; }
__device__ __forceinline__ float bf_lo(uint32_t v) { return __uint_as_float(v << 16); }
__device__ __forceinline__ float bf_hi(uint32_t v) { return __uint_as_float(v & 0xffff0000u); }
__device__ __forceinline__ float bf_ld(const __nv_bfloat16* p) { return __bfloat162float(__ldg(p)); }
__device__ __forceinline__ float2 lds_f2(uint32_t a) { float2 v; asm volatile("ld.shared.v2.f32 {%0,%1}, [%2];" : "=f"(v.x), "=f"(v.y) : "r"(a)); return v; }
__device__ __forceinline__ float lds_f(uint32_t a) { float v; asm volatile("ld.shared.f32 %0, [%1];" : "=f"(v) : "r"(a)); return v; }
__device__ __forceinline__ uint32_t lds_u(uint32_t a) { uint32_t v; asm volatile("ld.shared.u32 %0, [%1];" : "=r"(v) : "r"(a)); return v; }
__device__ __forceinline__ uint4 lds_u4(uint32_t a) { uint4 v; asm volatile("ld.shared.v4.u32 {%0,%1,%2,%3}, [%4];" : "=r"(v.x), "=r"(v.y), "=r"(v.z), "=r"(v.w) : "r"(a)); return v; }
__device__ __forceinline__ void st_b128(uint4* p, uint32_t a, uint32_t b, uint32_t c, uint32_t d) {
  asm volatile("{.reg .b64 l, h; .reg .b128 v; mov.b64 l, {%1,%2}; mov.b64 h, {%3,%4}; mov.b128 v, {l,h}; st.relaxed.gpu.global.b128 [%0], v;}"
               ::"l"(p), "r"(a), "r"(b), "r"(c), "r"(d) : "memory");
}
__device__ __forceinline__ void ld_b128(const uint4* p, uint32_t& a, uint32_t& b, uint32_t& c, uint32_t& d) {
  asm volatile("{.reg .b64 l, h; .reg .b128 v; ld.relaxed.gpu.global.b128 v, [%4]; mov.b128 {l,h}, v; mov.b64 {%0,%1}, l; mov.b64 {%2,%3}, h;}"
               : "=r"(a), "=r"(b), "=r"(c), "=r"(d) : "l"(p) : "memory");
}
__device__ __forceinline__ float tanh_fast(float x) { float y; asm("tanh.approx.f32 %0, %1;" : "=f"(y) : "f"(x)); return y; }
__device__ __forceinline__ float gelu2(float v) {
  float p = fmaf(v * v, 0.0356774081363f, 0.7978845608029f);
  return fmaf(v, tanh_fast(v * p), v);
}
__device__ __forceinline__ uint32_t bf2_mul(uint32_t a, uint32_t b) { uint32_t r; asm("mul.rn.bf16x2 %0, %1, %2;" : "=r"(r) : "r"(a), "r"(b)); return r; }
__device__ __forceinline__ uint32_t bf2_add(uint32_t a, uint32_t b) { uint32_t r; asm("add.rn.bf16x2 %0, %1, %2;" : "=r"(r) : "r"(a), "r"(b)); return r; }
__device__ __forceinline__ void pin(float& a) { asm volatile("" : "+f"(a)::"memory"); }
__device__ __forceinline__ void pin(uint32_t& a) { asm volatile("" : "+r"(a)::"memory"); }
struct cplx { float re, im; };
__device__ __forceinline__ cplx cmul(cplx a, cplx b) { return {fmaf(a.re, b.re, -a.im * b.im), fmaf(a.re, b.im, a.im * b.re)}; }
__device__ __forceinline__ cplx cfma(cplx a, cplx b, cplx c) {
  return {fmaf(a.re, b.re, fmaf(-a.im, b.im, c.re)), fmaf(a.re, b.im, fmaf(a.im, b.re, c.im))};
}
__device__ __forceinline__ cplx make_lam(float lre, float lim, float ldt) {
  float dt = __bfloat162float(__float2bfloat16_rn(expf(ldt)));
  float mag = expf(dt * lre), sn, cs;
  sincospif(dt * lim * 0.31830988618379067f, &sn, &cs);
  return {mag * cs, mag * sn};
}

template<int TA,int TB,uint32_t AH,uint32_t BH> __device__ __forceinline__ void wgmma_n64_ss(float (&d)[32], uint32_t al, uint32_t ao, uint32_t bl, uint32_t bo, int scale_d){
  asm volatile("{.reg .pred p; .reg .b32 t, v; .reg .b64 da, db; setp.ne.b32 p, %36, 0; add.u32 t, %32, %33; mov.b64 da, {t, %39}; add.u32 v, %34, %35; mov.b64 db, {v, %40};\n"
   "wgmma.mma_async.sync.aligned.m64n64k16.f32.bf16.bf16 {%0,%1,%2,%3,%4,%5,%6,%7,%8,%9,%10,%11,%12,%13,%14,%15,%16,%17,%18,%19,%20,%21,%22,%23,%24,%25,%26,%27,%28,%29,%30,%31}, da, db, p, 1, 1, %37, %38;}"
   : "+f"(d[0]),"+f"(d[1]),"+f"(d[2]),"+f"(d[3]),"+f"(d[4]),"+f"(d[5]),"+f"(d[6]),"+f"(d[7]),"+f"(d[8]),"+f"(d[9]),"+f"(d[10]),"+f"(d[11]),"+f"(d[12]),"+f"(d[13]),"+f"(d[14]),"+f"(d[15]),"+f"(d[16]),"+f"(d[17]),"+f"(d[18]),"+f"(d[19]),"+f"(d[20]),"+f"(d[21]),"+f"(d[22]),"+f"(d[23]),"+f"(d[24]),"+f"(d[25]),"+f"(d[26]),"+f"(d[27]),"+f"(d[28]),"+f"(d[29]),"+f"(d[30]),"+f"(d[31])
   : "r"(al),"r"(ao >> 4),"r"(bl),"r"(bo >> 4),"r"(scale_d),"n"(TA),"n"(TB),"n"(AH),"n"(BH));
}
template<int TB,uint32_t BH> __device__ __forceinline__ void wgmma_n64_rs(float (&d)[32], uint32_t a0,uint32_t a1,uint32_t a2,uint32_t a3, uint32_t bl, uint32_t bo, int scale_d){
  asm volatile("{.reg .pred p; .reg .b32 t; .reg .b64 db; setp.ne.b32 p, %38, 0; add.u32 t, %36, %37; mov.b64 db, {t, %40};\n"
   "wgmma.mma_async.sync.aligned.m64n64k16.f32.bf16.bf16 {%0,%1,%2,%3,%4,%5,%6,%7,%8,%9,%10,%11,%12,%13,%14,%15,%16,%17,%18,%19,%20,%21,%22,%23,%24,%25,%26,%27,%28,%29,%30,%31}, {%32,%33,%34,%35}, db, p, 1, 1, %39;}"
   : "+f"(d[0]),"+f"(d[1]),"+f"(d[2]),"+f"(d[3]),"+f"(d[4]),"+f"(d[5]),"+f"(d[6]),"+f"(d[7]),"+f"(d[8]),"+f"(d[9]),"+f"(d[10]),"+f"(d[11]),"+f"(d[12]),"+f"(d[13]),"+f"(d[14]),"+f"(d[15]),"+f"(d[16]),"+f"(d[17]),"+f"(d[18]),"+f"(d[19]),"+f"(d[20]),"+f"(d[21]),"+f"(d[22]),"+f"(d[23]),"+f"(d[24]),"+f"(d[25]),"+f"(d[26]),"+f"(d[27]),"+f"(d[28]),"+f"(d[29]),"+f"(d[30]),"+f"(d[31])
   : "r"(a0),"r"(a1),"r"(a2),"r"(a3),"r"(bl),"r"(bo >> 4),"r"(scale_d),"n"(TB),"n"(BH));
}
template<int TA,int TB,uint32_t AH,uint32_t BH> __device__ __forceinline__ void wgmma_n96_ss(float (&d)[48], uint32_t al, uint32_t ao, uint32_t bl, uint32_t bo, int scale_d){
  asm volatile("{.reg .pred p; .reg .b32 t, v; .reg .b64 da, db; setp.ne.b32 p, %52, 0; add.u32 t, %48, %49; mov.b64 da, {t, %55}; add.u32 v, %50, %51; mov.b64 db, {v, %56};\n"
   "wgmma.mma_async.sync.aligned.m64n96k16.f32.bf16.bf16 {%0,%1,%2,%3,%4,%5,%6,%7,%8,%9,%10,%11,%12,%13,%14,%15,%16,%17,%18,%19,%20,%21,%22,%23,%24,%25,%26,%27,%28,%29,%30,%31,%32,%33,%34,%35,%36,%37,%38,%39,%40,%41,%42,%43,%44,%45,%46,%47}, da, db, p, 1, 1, %53, %54;}"
   : "+f"(d[0]),"+f"(d[1]),"+f"(d[2]),"+f"(d[3]),"+f"(d[4]),"+f"(d[5]),"+f"(d[6]),"+f"(d[7]),"+f"(d[8]),"+f"(d[9]),"+f"(d[10]),"+f"(d[11]),"+f"(d[12]),"+f"(d[13]),"+f"(d[14]),"+f"(d[15]),"+f"(d[16]),"+f"(d[17]),"+f"(d[18]),"+f"(d[19]),"+f"(d[20]),"+f"(d[21]),"+f"(d[22]),"+f"(d[23]),"+f"(d[24]),"+f"(d[25]),"+f"(d[26]),"+f"(d[27]),"+f"(d[28]),"+f"(d[29]),"+f"(d[30]),"+f"(d[31]),"+f"(d[32]),"+f"(d[33]),"+f"(d[34]),"+f"(d[35]),"+f"(d[36]),"+f"(d[37]),"+f"(d[38]),"+f"(d[39]),"+f"(d[40]),"+f"(d[41]),"+f"(d[42]),"+f"(d[43]),"+f"(d[44]),"+f"(d[45]),"+f"(d[46]),"+f"(d[47])
   : "r"(al),"r"(ao >> 4),"r"(bl),"r"(bo >> 4),"r"(scale_d),"n"(TA),"n"(TB),"n"(AH),"n"(BH));
}
template<int TA,int TB,uint32_t AH,uint32_t BH> __device__ __forceinline__ void wgmma_n128_ss(float (&d)[64], uint32_t al, uint32_t ao, uint32_t bl, uint32_t bo, int scale_d){
  asm volatile("{.reg .pred p; .reg .b32 t, v; .reg .b64 da, db; setp.ne.b32 p, %68, 0; add.u32 t, %64, %65; mov.b64 da, {t, %71}; add.u32 v, %66, %67; mov.b64 db, {v, %72};\n"
   "wgmma.mma_async.sync.aligned.m64n128k16.f32.bf16.bf16 {%0,%1,%2,%3,%4,%5,%6,%7,%8,%9,%10,%11,%12,%13,%14,%15,%16,%17,%18,%19,%20,%21,%22,%23,%24,%25,%26,%27,%28,%29,%30,%31,%32,%33,%34,%35,%36,%37,%38,%39,%40,%41,%42,%43,%44,%45,%46,%47,%48,%49,%50,%51,%52,%53,%54,%55,%56,%57,%58,%59,%60,%61,%62,%63}, da, db, p, 1, 1, %69, %70;}"
   : "+f"(d[0]),"+f"(d[1]),"+f"(d[2]),"+f"(d[3]),"+f"(d[4]),"+f"(d[5]),"+f"(d[6]),"+f"(d[7]),"+f"(d[8]),"+f"(d[9]),"+f"(d[10]),"+f"(d[11]),"+f"(d[12]),"+f"(d[13]),"+f"(d[14]),"+f"(d[15]),"+f"(d[16]),"+f"(d[17]),"+f"(d[18]),"+f"(d[19]),"+f"(d[20]),"+f"(d[21]),"+f"(d[22]),"+f"(d[23]),"+f"(d[24]),"+f"(d[25]),"+f"(d[26]),"+f"(d[27]),"+f"(d[28]),"+f"(d[29]),"+f"(d[30]),"+f"(d[31]),"+f"(d[32]),"+f"(d[33]),"+f"(d[34]),"+f"(d[35]),"+f"(d[36]),"+f"(d[37]),"+f"(d[38]),"+f"(d[39]),"+f"(d[40]),"+f"(d[41]),"+f"(d[42]),"+f"(d[43]),"+f"(d[44]),"+f"(d[45]),"+f"(d[46]),"+f"(d[47]),"+f"(d[48]),"+f"(d[49]),"+f"(d[50]),"+f"(d[51]),"+f"(d[52]),"+f"(d[53]),"+f"(d[54]),"+f"(d[55]),"+f"(d[56]),"+f"(d[57]),"+f"(d[58]),"+f"(d[59]),"+f"(d[60]),"+f"(d[61]),"+f"(d[62]),"+f"(d[63])
   : "r"(al),"r"(ao >> 4),"r"(bl),"r"(bo >> 4),"r"(scale_d),"n"(TA),"n"(TB),"n"(AH),"n"(BH));
}
template<int TB,uint32_t BH> __device__ __forceinline__ void wgmma_n128_rs(float (&d)[64], uint32_t a0,uint32_t a1,uint32_t a2,uint32_t a3, uint32_t bl, uint32_t bo, int scale_d){
  asm volatile("{.reg .pred p; .reg .b32 t; .reg .b64 db; setp.ne.b32 p, %70, 0; add.u32 t, %68, %69; mov.b64 db, {t, %72};\n"
   "wgmma.mma_async.sync.aligned.m64n128k16.f32.bf16.bf16 {%0,%1,%2,%3,%4,%5,%6,%7,%8,%9,%10,%11,%12,%13,%14,%15,%16,%17,%18,%19,%20,%21,%22,%23,%24,%25,%26,%27,%28,%29,%30,%31,%32,%33,%34,%35,%36,%37,%38,%39,%40,%41,%42,%43,%44,%45,%46,%47,%48,%49,%50,%51,%52,%53,%54,%55,%56,%57,%58,%59,%60,%61,%62,%63}, {%64,%65,%66,%67}, db, p, 1, 1, %71;}"
   : "+f"(d[0]),"+f"(d[1]),"+f"(d[2]),"+f"(d[3]),"+f"(d[4]),"+f"(d[5]),"+f"(d[6]),"+f"(d[7]),"+f"(d[8]),"+f"(d[9]),"+f"(d[10]),"+f"(d[11]),"+f"(d[12]),"+f"(d[13]),"+f"(d[14]),"+f"(d[15]),"+f"(d[16]),"+f"(d[17]),"+f"(d[18]),"+f"(d[19]),"+f"(d[20]),"+f"(d[21]),"+f"(d[22]),"+f"(d[23]),"+f"(d[24]),"+f"(d[25]),"+f"(d[26]),"+f"(d[27]),"+f"(d[28]),"+f"(d[29]),"+f"(d[30]),"+f"(d[31]),"+f"(d[32]),"+f"(d[33]),"+f"(d[34]),"+f"(d[35]),"+f"(d[36]),"+f"(d[37]),"+f"(d[38]),"+f"(d[39]),"+f"(d[40]),"+f"(d[41]),"+f"(d[42]),"+f"(d[43]),"+f"(d[44]),"+f"(d[45]),"+f"(d[46]),"+f"(d[47]),"+f"(d[48]),"+f"(d[49]),"+f"(d[50]),"+f"(d[51]),"+f"(d[52]),"+f"(d[53]),"+f"(d[54]),"+f"(d[55]),"+f"(d[56]),"+f"(d[57]),"+f"(d[58]),"+f"(d[59]),"+f"(d[60]),"+f"(d[61]),"+f"(d[62]),"+f"(d[63])
   : "r"(a0),"r"(a1),"r"(a2),"r"(a3),"r"(bl),"r"(bo >> 4),"r"(scale_d),"n"(TB),"n"(BH));
}

__global__ void __cluster_dims__(2, 1, 1) __launch_bounds__(384, 1)
fused_kernel(const __grid_constant__ Maps maps, const __nv_bfloat16* __restrict__ lam_re,
             const __nv_bfloat16* __restrict__ lam_im, const __nv_bfloat16* __restrict__ log_dt, const __nv_bfloat16* __restrict__ dskip,
             const __nv_bfloat16* __restrict__ b1, const __nv_bfloat16* __restrict__ b2, const __nv_bfloat16* __restrict__ gate_w,
             const __nv_bfloat16* __restrict__ pf_w1, const __nv_bfloat16* __restrict__ pf_w2, const __nv_bfloat16* __restrict__ pf_cre,
             const __nv_bfloat16* __restrict__ pf_cim, float* __restrict__ out) {
  extern __shared__ __align__(1024) unsigned char smem_raw[];
  const uint32_t sb = (uint32_t)__cvta_generic_to_shared(smem_raw);
  const int b = blockIdx.x;
  const int rank = b & 1, s = (b >> 1) & 7, m = ((b >> 4) << 1) | rank;
  const int warp = __shfl_sync(0xffffffffu, (int)(threadIdx.x >> 5), 0);
  const int lane = threadIdx.x & 31;
  const int xrot = 7 - s;

  if (warp == 8) {
    if (elect_one()) {
      TS(2, 0); TG(2);
      mbar_init(sb + OFF_XFULL, 1); mbar_init(sb + OFF_FULL, 1); mbar_init(sb + OFF_XFULL + 8, 1);
      asm volatile("fence.mbarrier_init.release.cluster;" ::: "memory");
      asm volatile("fence.proxy.async.shared::cta;" ::: "memory");
      mbar_expect_tx(sb + OFF_XFULL, 16384);
      tma5d(sb + OFF_X + xrot * 16384, &maps.x, 0, 2 * m, sb + OFF_XFULL);
      mbar_expect_tx(sb + OFF_FULL, 16384);
      tma2d(sb + OFF_RING, &maps.bre, 0, s * 64, sb + OFF_FULL);
      tma2d(sb + OFF_RING + 8192, &maps.bim, 0, s * 64, sb + OFF_FULL);
      mbar_expect_tx(sb + OFF_XFULL + 8, 16384);
      tma5d(sb + OFF_X + ((xrot + 1) & 7) * 16384, &maps.x, 64, 2 * m, sb + OFF_XFULL + 8);
    }
  } else if (warp < 6) {
    if (elect_one()) {
      mbar_init(sb + OFF_XFULL + 16 + 8 * warp, 1); mbar_init(sb + OFF_EMPTY + 8 * warp, 16);
      if (warp) mbar_init(sb + OFF_FULL + 8 * warp, 1);
      asm volatile("fence.mbarrier_init.release.cluster;" ::: "memory");
    }
  } else if (warp < 8) {
    if (elect_one()) {
      mbar_init(sb + OFF_GBAR + 8 * (warp - 6), 64);
      asm volatile("fence.mbarrier_init.release.cluster;" ::: "memory");
    }
  }
  __syncwarp();
  asm volatile("barrier.cluster.arrive.relaxed.aligned;" ::: "memory");

  if (warp >= 8) {
    asm volatile("setmaxnreg.dec.sync.aligned.u32 56;");
    if (warp == 8) {
      asm volatile("barrier.cluster.wait.aligned;" ::: "memory");
      if (elect_one()) {
        TS(2, 1);
        const CUtensorMap* mb = rank ? &maps.bim : &maps.bre;
        const CUtensorMap* mc = rank ? &maps.cim : &maps.cre;
        int slot = 1; uint32_t ph = 1;
#pragma unroll 1
        for (int u = 1; u < 30; u++) {
          const uint32_t fb = sb + OFF_FULL + 8 * slot, dst = sb + OFF_RING + slot * 16384;
          if (u >= NSLOT) mbar_wait(sb + OFF_EMPTY + 8 * slot, ph);
          TS2(0, u);
          if (u < 8) {
            mbar_expect_tx(fb, 16384);
            tma2d_mc(dst + rank * 8192, mb, u * 64, s * 64, fb);
            if (u < 6) {
              mbar_expect_tx(sb + OFF_XFULL + 8 * (u + 1), 16384);
              tma5d(sb + OFF_X + ((u + 1 + xrot) & 7) * 16384, &maps.x, (u + 1) * 64, 2 * m, sb + OFF_XFULL + 8 * (u + 1));
              if (u == 5) {
                mbar_expect_tx(sb + OFF_XFULL + 56, 16384);
                tma5d(sb + OFF_X + ((7 + xrot) & 7) * 16384, &maps.x, 7 * 64, 2 * m, sb + OFF_XFULL + 56);
              }
            }
          } else if (u < 16) {
            mbar_expect_tx(fb, 12288);
            tma3d_mc(dst + rank * 6144, &maps.w1b, 0, (u - 8) * 64 + rank * 32, s * 7, fb);
          } else if (u < 24) {
            mbar_expect_tx(fb, 16384);
            tma2d_mc(dst + rank * 8192, &maps.w1a, s * 224 + 96 + rank * 64, ((u - 15 + s) & 7) * 64, fb);
          } else if (u < 26) {
            mbar_expect_tx(fb, 16384);
            tma2d_mc(dst + rank * 8192, u == 24 ? &maps.cre : &maps.cim, s * 64, ((s + 1 + rank) & 7) * 64, fb);
          } else {
            mbar_expect_tx(fb, 14336);
            tma2d_mc(dst + rank * 7168, &maps.w2, ((s + 1 + (u & 1)) & 7) * 64, s * 224 + ((u - 26) >> 1) * 112 + rank * 56, fb);
          }
          if (++slot == NSLOT) { slot = 0; ph ^= 1; }
        }
#pragma unroll 1
        for (int p = 2; p < 8; p++) {
          const int piece = (s + 1 + p) & 7, grp = p >= 5 ? p - 5 : p - 2;
          const uint32_t fb = sb + OFF_XFULL + 8 * (p - 2), dst = grp == 0 ? sb + OFF_X + 2 * 16384 : sb + OFF_RING + (grp - 1) * 49152;
          if (p >= 5) mbar_wait(sb + OFF_EMPTY + 8 * grp, 1);
          else if (p >= 3) { for (int j = 0; j < 3; j++) mbar_wait(sb + OFF_EMPTY + 8 * ((grp - 1) * 3 + j), 0); }
          TS2(0, 28 + p);
          mbar_expect_tx(fb, 45056);
          tma2d_mc(dst + rank * 8192, mc, s * 64, piece * 64, fb);
          tma2d_mc(dst + 16384 + rank * 7168, &maps.w2, piece * 64, s * 224 + rank * 56, fb);
          tma2d_mc(dst + 32768 + rank * 7168, &maps.w2, piece * 64, s * 224 + 112 + rank * 56, fb);
        }
        TS(2, 2);
      }
    } else if (warp == 11) {
      asm volatile("barrier.cluster.wait.aligned;" ::: "memory");
      if ((PF & 2) && elect_one()) {
        mbar_wait(sb + OFF_XFULL + 8 * PFK, 0);
        l2_prefetch(pf_w1 + b * 7168, 14336);
        l2_prefetch(pf_cre + b * 2048, 4096);
        l2_prefetch(pf_cim + b * 2048, 4096);
        l2_prefetch(pf_w2 + b * 7168, 14336);
      }
    } else {
      const int t = threadIdx.x - 288;
      unsigned par;
      asm volatile("ld.relaxed.gpu.global.u32 %0, [%1];" : "=r"(par) : "l"(g_epoch + b) : "memory");
      const float pr = bf_ld(lam_re + s * 64 + t), pi = bf_ld(lam_im + s * 64 + t), pd = bf_ld(log_dt + s * 64 + t);
      const uint4* gwp = reinterpret_cast<const uint4*>(gate_w) + (lane & 7);
      uint4 wn = __ldg(gwp);
      asm volatile("barrier.cluster.wait.aligned;" ::: "memory");
      par = (par + 1) & 1;
      cplx l64 = make_lam(pr, pi, pd);
#pragma unroll
      for (int i = 0; i < 6; i++) l64 = cmul(l64, l64);
      const int row = s * 16 + (t >> 5) * 8 + (lane >> 3);
      const uint32_t xr0 = sb + OFF_X + row * 128 + (((lane & 7) ^ (row & 7)) << 4), xr1 = (xr0 + 512) ^ 64;
      float z0 = 0.f, z1 = 0.f;
#pragma unroll 1
      for (int kb = 0; kb < 8; kb++) {
        const uint4 w = wn;
        wn = __ldg(gwp + ((kb + 1) & 7) * 8);
        mbar_wait(sb + OFF_XFULL + 8 * kb, 0);
        const uint32_t xo = ((kb + xrot) & 7) * 16384;
        const uint4 a = lds_u4(xr0 + xo), d = lds_u4(xr1 + xo);
        const uint32_t wv[4] = {w.x, w.y, w.z, w.w}, av[4] = {a.x, a.y, a.z, a.w}, dv[4] = {d.x, d.y, d.z, d.w};
#pragma unroll
        for (int c = 0; c < 4; c++) {
          const float wl = bf_lo(wv[c]), wh = bf_hi(wv[c]);
          z0 = fmaf(bf_hi(av[c]), wh, fmaf(bf_lo(av[c]), wl, z0));
          z1 = fmaf(bf_hi(dv[c]), wh, fmaf(bf_lo(dv[c]), wl, z1));
        }
      }
      {
        float zz = (lane & 4) ? z1 : z0;
        zz += __shfl_xor_sync(0xffffffffu, (lane & 4) ? z0 : z1, 4);
        zz += __shfl_xor_sync(0xffffffffu, zz, 2);
        zz += __shfl_xor_sync(0xffffffffu, zz, 1);
        const float rho = 4.f * expf(zz > 40.f ? 40.f : zz);
        if ((lane & 3) == 0)
          asm volatile("st.relaxed.gpu.global.u32 [%0], %1;" ::"l"(g_gate + m * 128 + row + (lane & 4)), "r"((__float_as_uint(rho) & ~1u) | par) : "memory");
      }
      if (t == 0) TS(3, 0);
      mbar_wait(sb + OFF_GBAR, 0);
      const float2 e0 = lds_f2(sb + OFF_CARRY + t * 8), e1 = lds_f2(sb + OFF_CARRY + 512 + t * 8);
      float2* eb = g_end + s * 1024 + t;
      {
        const cplx e = cfma(l64, cplx{e0.x, e0.y}, cplx{e1.x, e1.y});
        const unsigned long long v = ((unsigned long long)__float_as_uint(e.im) << 32) | ((__float_as_uint(e.re) & ~1u) | par);
        asm volatile("st.relaxed.gpu.global.b64 [%0], %1;" ::"l"(eb + m * 64), "l"(v) : "memory");
      }
      if (t == 0) TS(3, 1);
      {
        const unsigned* gp = g_gate + m * 128 + t;
        unsigned g0, g1;
        int tries = 0;
#pragma unroll 1
        do {
          asm volatile("ld.relaxed.gpu.global.u32 %0, [%1];" : "=r"(g0) : "l"(gp) : "memory");
          asm volatile("ld.relaxed.gpu.global.u32 %0, [%1];" : "=r"(g1) : "l"(gp + 64) : "memory");
        } while ((((g0 ^ par) | (g1 ^ par)) & 1) && ++tries < 200000);
        asm volatile("st.shared.u32 [%0], %1;" ::"r"(sb + OFF_GS + t * 4), "r"(g0) : "memory");
        asm volatile("st.shared.u32 [%0], %1;" ::"r"(sb + OFF_GS + 256 + t * 4), "r"(g1) : "memory");
      }
      if (t == 0) TS(3, 2);
      cplx S = {0.f, 0.f};
      {
        unsigned long long v[15];
        uint32_t bad;
        int tries = 0;
        const float2* e15 = eb + (m - 15) * 64;
#pragma unroll 1
        do {
          bad = 0;
#pragma unroll
          for (int i = 0; i < 15; i++) {
            v[i] = par;
            asm volatile("{.reg .pred p; setp.ge.s32 p, %2, %3; @p ld.relaxed.gpu.global.b64 %0, [%1];}" : "+l"(v[i]) : "l"(e15 + i * 64), "r"(m), "r"(15 - i) : "memory");
          }
#pragma unroll
          for (int i = 0; i < 15; i++) bad |= (uint32_t)v[i] ^ par;
        } while ((bad & 1) && ++tries < 200000);
        const cplx l128 = cmul(l64, l64);
#pragma unroll
        for (int i = 0; i < 15; i++) S = cfma(l128, S, cplx{__uint_as_float((uint32_t)v[i] & ~1u), __uint_as_float((uint32_t)(v[i] >> 32))});
      }
      const cplx S1 = cfma(l64, S, cplx{e0.x, e0.y});
      asm volatile("st.shared.v2.f32 [%0], {%1,%2};" ::"r"(sb + OFF_CARRY + t * 8), "f"(S.re), "f"(S.im) : "memory");
      asm volatile("st.shared.v2.f32 [%0], {%1,%2};" ::"r"(sb + OFF_CARRY + 512 + t * 8), "f"(S1.re), "f"(S1.im) : "memory");
      mbar_arrive(sb + OFF_CBAR);
      if (t == 0) TS(3, 3);
    }
  } else {
    const int wg = warp >> 2, w = warp & 3, q = lane & 3, gr = lane >> 2;
    unsigned epoch;
    asm volatile("ld.relaxed.gpu.global.u32 %0, [%1];" : "=r"(epoch) : "l"(g_epoch + b) : "memory");
    const int c0 = s * 64 + w * 16 + gr;
    float pr[2], pi[2], pd[2];
#pragma unroll
    for (int h = 0; h < 2; h++) { pr[h] = bf_ld(lam_re + c0 + 8 * h); pi[h] = bf_ld(lam_im + c0 + 8 * h); pd[h] = bf_ld(log_dt + c0 + 8 * h); }
    uint32_t bv[28];
#pragma unroll
    for (int j = 0; j < 28; j++) bv[j] = __ldg(reinterpret_cast<const uint32_t*>(b1 + s * 224 + j * 8) + q);
    asm volatile("setmaxnreg.inc.sync.aligned.u32 224;");
    asm volatile("barrier.cluster.wait.aligned;" ::: "memory");
    TS(wg, 0);
    uint32_t ebar;
    asm volatile("mapa.shared::cluster.u32 %0, %1, %2;" : "=r"(ebar) : "r"(sb + OFF_EMPTY), "r"(lane & 1));
    auto release = [&](int slot) { if (lane < 2) mbar_arrive_cl(ebar + 8 * slot); };
    const uint32_t xw = sb + OFF_X + wg * 8192, fullb = sb + OFF_FULL;
    const uint32_t dxw = (xw & 0x3FFFF) >> 4, dring = ((sb + OFF_RING) & 0x3FFFF) >> 4;

    float ure[32], uim[32], aa[48], ab[64];
    cplx lam[2], coef[2], l16[2], l32[2], lq[2], pre[2], e[2];
#pragma unroll
    for (int h = 0; h < 2; h++) {
      lam[h] = make_lam(pr[h], pi[h], pd[h]);
      const float inv = __fdividef(1.f, fmaf(pr[h], pr[h], pi[h] * pi[h]));
      coef[h] = cmul(cplx{lam[h].re - 1.f, lam[h].im}, cplx{pr[h] * inv, -pi[h] * inv});
      cplx t = cmul(lam[h], lam[h]); t = cmul(t, t); t = cmul(t, t);
      l16[h] = cmul(t, t); l32[h] = cmul(l16[h], l16[h]);
      cplx a = (q & 1) ? l16[h] : cplx{1.f, 0.f}, c = (q & 2) ? l32[h] : cplx{1.f, 0.f};
      lq[h] = cmul(cmul(a, c), coef[h]);
      pin(lq[h].re); pin(lq[h].im);
    }
#pragma unroll
    for (int j = 0; j < 12; j++) { aa[4 * j] = aa[4 * j + 2] = bf_lo(bv[j]); aa[4 * j + 1] = aa[4 * j + 3] = bf_hi(bv[j]); }
#pragma unroll
    for (int j = 0; j < 16; j++) { ab[4 * j] = ab[4 * j + 2] = bf_lo(bv[12 + j]); ab[4 * j + 1] = ab[4 * j + 3] = bf_hi(bv[12 + j]); }
    reg_fence(aa); reg_fence(ab);
    const uint32_t par = (epoch + 1) & 1;
    TS(wg, 24);

#pragma unroll
    for (int kb = 0; kb < 8; kb++) {
      const int slot = kb % NSLOT;
      TS2(1, kb);
      mbar_wait(sb + OFF_XFULL + 8 * kb, 0);
      if (kb == 0) TS(wg, 18);
      mbar_wait(fullb + 8 * slot, (kb / NSLOT) & 1);
      TS2(2, kb);
      if (kb == 0) TS(wg, 1);
      wg_fence();
      const uint32_t dxa = dxw + ((kb + xrot) & 7) * 1024;
#pragma unroll
      for (int kk = 0; kk < 4; kk++) {
        wgmma_n64_ss<0, 0, DH128, DH128>(ure, dring, slot * 16384 + kk * 32, dxa, kk * 32, (kb | kk) != 0);
        wgmma_n64_ss<0, 0, DH128, DH128>(uim, dring, slot * 16384 + 8192 + kk * 32, dxa, kk * 32, (kb | kk) != 0);
      }
      wg_commit();
      if (kb > 0) { wg_wait<1>(); release((kb - 1) % NSLOT); }
    }
    TS(wg, 2);
#pragma unroll
    for (int kb = 0; kb < 8; kb++) {
      const int u = 8 + kb, slot = u % NSLOT;
      TS2(1, u);
      mbar_wait(fullb + 8 * slot, (u / NSLOT) & 1);
      TS2(2, u);
      wg_fence();
      const uint32_t dxa = dxw + ((kb + xrot) & 7) * 1024;
#pragma unroll
      for (int kk = 0; kk < 4; kk++)
        wgmma_n96_ss<0, 1, DH128, DH64>(aa, dxa, kk * 32, dring, slot * 16384 + (kk >> 1) * 6144 + (kk & 1) * 1024 + lbo(2048), 1);
      wg_commit();
      wg_wait<1>();
      release((u - 1) % NSLOT);
      if (kb == 0) {
        reg_fence(ure); reg_fence(uim);
#pragma unroll
        for (int h = 0; h < 2; h++) e[h] = cplx{ure[2 * h], uim[2 * h]};
      }
      if (kb < 3) {
#pragma unroll
        for (int t = 1 + 5 * kb; t < 6 + 5 * kb; t++)
#pragma unroll
          for (int h = 0; h < 2; h++) { const int i = 4 * (t >> 1) + 2 * h + (t & 1); e[h] = cfma(lam[h], e[h], cplx{ure[i], uim[i]}); }
#pragma unroll
        for (int h = 0; h < 2; h++) { pin(e[h].re); pin(e[h].im); }
      } else if (kb == 3) {
#pragma unroll
        for (int h = 0; h < 2; h++) {
          cplx y = {__shfl_up_sync(0xffffffffu, e[h].re, 1, 4), __shfl_up_sync(0xffffffffu, e[h].im, 1, 4)};
          if (q >= 1) e[h] = cfma(l16[h], y, e[h]);
          y = cplx{__shfl_up_sync(0xffffffffu, e[h].re, 2, 4), __shfl_up_sync(0xffffffffu, e[h].im, 2, 4)};
          if (q >= 2) e[h] = cfma(l32[h], y, e[h]);
        }
        if (q == 3) {
#pragma unroll
          for (int h = 0; h < 2; h++)
            asm volatile("st.shared.v2.f32 [%0], {%1,%2};" ::"r"(sb + OFF_CARRY + wg * 512 + (w * 16 + gr + 8 * h) * 8), "f"(e[h].re), "f"(e[h].im) : "memory");
          mbar_arrive(sb + OFF_GBAR);
        }
#pragma unroll
        for (int h = 0; h < 2; h++) {
          const cplx y = {__shfl_up_sync(0xffffffffu, e[h].re, 1, 4), __shfl_up_sync(0xffffffffu, e[h].im, 1, 4)};
          pre[h] = (q >= 1) ? cmul(coef[h], y) : cplx{0.f, 0.f};
          pin(pre[h].re); pin(pre[h].im);
        }
        TS(wg, 3);
      } else {
#pragma unroll
        for (int i = (kb - 4) * 8; i < (kb - 3) * 8; i++) {
          pin(ure[i]); pin(uim[i]);
          const cplx v = cmul(coef[(i >> 1) & 1], cplx{ure[i], uim[i]});
          ure[i] = v.re; uim[i] = v.im;
          pin(ure[i]); pin(uim[i]);
        }
      }
    }
    TS(wg, 4);
    uint32_t H[56];
    cplx hst[2];
    const uint32_t dh = dxw;
    const uint32_t hst_addr = xw + (w * 16 + (lane & 15)) * 128 + (((lane >> 4) ^ (lane & 7)) << 4);
#pragma unroll
    for (int kb = 0; kb < 8; kb++) {
      const int u = 16 + kb, slot = u % NSLOT;
      TS2(1, u);
      mbar_wait(fullb + 8 * slot, (u / NSLOT) & 1);
      TS2(2, u);
      wg_fence();
#pragma unroll
      for (int kk = 0; kk < 4; kk++)
        wgmma_n128_ss<0, 1, DH128, DH128>(ab, dxw, kb * 16384 + kk * 32, dring, slot * 16384 + kk * 2048 + lbo(8192), 1);
      wg_commit();
      wg_wait<1>();
      release((u - 1) % NSLOT);
      if (kb < 3 || kb == 7) {
        const int ch = kb < 3 ? kb : 3;
#pragma unroll
        for (int i = ch * 6; i < ch * 6 + 6; i++) {
          pin(aa[2 * i]); pin(aa[2 * i + 1]);
          H[i] = pack_bf16(gelu2(aa[2 * i]), gelu2(aa[2 * i + 1]));
          pin(H[i]);
        }
      } else {
        if (kb == 3) {
          TS(wg, 5);
          mbar_wait(sb + OFF_CBAR, 0);
          TS(wg, 6);
#pragma unroll
          for (int h = 0; h < 2; h++) {
            const float2 c = lds_f2(sb + OFF_CARRY + wg * 512 + (w * 16 + gr + 8 * h) * 8);
            hst[h] = cfma(lq[h], cplx{c.x, c.y}, pre[h]);
          }
        }
        const int j0 = (kb - 3) * 2;
        uint32_t rr[4], ri[4];
#pragma unroll
        for (int jj = 0; jj < 2; jj++) {
          const int j = j0 + jj;
          const float2 g2 = lds_f2(sb + OFF_GS + (wg * 64 + j * 8 + q * 2) * 4);
#pragma unroll
          for (int h = 0; h < 2; h++) {
            const int i = 4 * j + 2 * h;
            const cplx h0 = cfma(lam[h], hst[h], cplx{ure[i], uim[i]});
            hst[h] = cfma(lam[h], h0, cplx{ure[i + 1], uim[i + 1]});
            rr[jj * 2 + h] = pack_bf16(h0.re * g2.x, hst[h].re * g2.y);
            ri[jj * 2 + h] = pack_bf16(-h0.im * g2.x, -hst[h].im * g2.y);
          }
        }
        const uint32_t a = hst_addr ^ (j0 << 4);
        asm volatile("stmatrix.sync.aligned.m8n8.x4.shared.b16 [%0], {%1,%2,%3,%4};" ::"r"(a), "r"(rr[0]), "r"(rr[1]), "r"(rr[2]), "r"(rr[3]) : "memory");
        asm volatile("stmatrix.sync.aligned.m8n8.x4.shared.b16 [%0], {%1,%2,%3,%4};" ::"r"(a + 16384), "r"(ri[0]), "r"(ri[1]), "r"(ri[2]), "r"(ri[3]) : "memory");
        if (kb == 6) asm volatile("fence.proxy.async.shared::cta;" ::: "memory");
      }
    }
    bar_sync(1 + wg, 128);
    TS(wg, 7);

    uint4* const psend = g_part + (size_t)m * (8 * 7 * 1024) + warp * 128;
    const uint4* const precv = g_part + (size_t)(m * 8 + s) * (7 * 1024) + warp * 128 + lane;
    const uint32_t stg = sb + OFF_X + 5 * 16384 + warp * 2048;
    auto stage = [&](const float* o, int p) {
#pragma unroll
      for (int i = 0; i < 4; i++) {
        uint32_t t0;
        asm("lop3.b32 %0, %1, 0xfffffffe, %2, 0xea;" : "=r"(t0) : "r"(pack_bf16(o[8 * i], o[8 * i + 1])), "r"(par));
        asm volatile("st.shared.v4.u32 [%0], {%1,%2,%3,%4};" ::"r"(stg + lane * 16 + (p & 1) * 16384 + i * 512), "r"(t0), "r"(pack_bf16(o[8 * i + 2], o[8 * i + 3])),
                     "r"(pack_bf16(o[8 * i + 4], o[8 * i + 5])), "r"(pack_bf16(o[8 * i + 6], o[8 * i + 7])) : "memory");
      }
    };
    auto push = [&](int p) {
      asm volatile("cp.async.bulk.global.shared::cta.bulk_group [%0], [%1], 2048;" ::"l"(psend + (((s + 1 + p) & 7) * 7 + p) * 1024), "r"(stg + (p & 1) * 16384) : "memory");
      asm volatile("cp.async.bulk.commit_group;" ::: "memory");
    };
    auto recv_issue = [&](uint32_t (&r)[16], int p) {
#pragma unroll
      for (int i = 0; i < 4; i++) ld_b128(precv + p * 1024 + i * 32, r[4 * i], r[4 * i + 1], r[4 * i + 2], r[4 * i + 3]);
    };
    auto recv_check = [&](uint32_t (&r)[16], int p) {
      if (__builtin_expect(__any_sync(0xffffffffu, ((r[0] ^ par) | (r[4] ^ par) | (r[8] ^ par) | (r[12] ^ par)) & 1), 0)) {
        int tries = 0;
#pragma unroll 1
        do { recv_issue(r, p); } while (__any_sync(0xffffffffu, ((r[0] ^ par) | (r[4] ^ par) | (r[8] ^ par) | (r[12] ^ par)) & 1) && ++tries < 200000);
      }
    };
    float sum[32];
    auto recv_add = [&](uint32_t (&r)[16], int p) {
      recv_check(r, p);
#pragma unroll
      for (int i = 0; i < 16; i++) { sum[2 * i] += bf_lo(r[i]); sum[2 * i + 1] += bf_hi(r[i]); }
      reg_fence(sum);
    };
    {
      float o2[64];
      auto gelu_b = [&](int i0, int i1) {
#pragma unroll
        for (int i = i0; i < i1; i++) {
          pin(ab[2 * i]); pin(ab[2 * i + 1]);
          H[24 + i] = pack_bf16(gelu2(ab[2 * i]), gelu2(ab[2 * i + 1]));
          pin(H[24 + i]);
        }
      };
      auto mma_h2 = [&](int part) {
        wg_fence();
#pragma unroll
        for (int kk = 0; kk < 4; kk++)
          wgmma_n128_ss<1, 0, DH128, DH128>(o2, dh, part * 16384 + kk * 2048, dring, part * 16384 + kk * 32, (part | kk) != 0);
        wg_commit();
      };
      auto mma_w2 = [&](int k0, int k1) {
        wg_fence();
#pragma unroll
        for (int kk = k0; kk < k1; kk++)
          wgmma_n128_rs<1, DH128>(o2, H[4 * kk], H[4 * kk + 1], H[4 * kk + 2], H[4 * kk + 3], dring, 32768 + (kk / 7) * 32768 + (kk % 7) * 2048 + lbo(16384), 1);
        wg_commit();
      };
      mbar_wait(fullb + 0, 0);
      mma_h2(0);
      wg_wait<1>(); release(5);
      gelu_b(0, 6);
      mbar_wait(fullb + 8, 0);
      mma_h2(1);
      wg_wait<1>(); release(0);
      gelu_b(6, 12);
      mbar_wait(fullb + 16, 0); mbar_wait(fullb + 24, 0);
      mma_w2(0, 4);
      wg_wait<1>(); release(1);
      gelu_b(12, 18);
      mma_w2(4, 7);
      gelu_b(18, 23);
      mbar_wait(fullb + 32, 0); mbar_wait(fullb + 40, 0);
      mma_w2(7, 10);
      wg_wait<1>(); release(2); release(3);
      gelu_b(23, 28);
      mma_w2(10, 12);
      gelu_b(28, 32);
      if (wg == 1) bar_sync(4, 256);
      mma_w2(12, 14);
      bar_arrive(4 - wg, 256);
      wg_wait<0>(); release(4); release(5);
      reg_fence(o2);
      TS(wg, 8);
      stage(o2, 0); stage(o2 + 32, 1);
      asm volatile("fence.proxy.async.shared::cta;" ::: "memory");
      __syncwarp();
      if (elect_one()) { push(0); push(1); }
      TS(wg, 9);
    }
    const uint32_t dx0 = ((sb + OFF_X) & 0x3FFFF) >> 4;
    float o[32], rho[2];
    uint32_t r0[16], r1[16];
#pragma unroll
    for (int p = 2; p < 8; p++) {
      const int grp = p >= 5 ? p - 5 : p - 2;
      const uint32_t wo = grp == 0 ? 2 * 16384 : OFF_RING + (grp - 1) * 49152;
      if (p == 2) {
#pragma unroll
        for (int j = 0; j < 8; j++) {
          r0[j] = __ldg(reinterpret_cast<const uint32_t*>(dskip + s * 64 + j * 8) + q);
          r0[8 + j] = __ldg(reinterpret_cast<const uint32_t*>(b2 + s * 64 + j * 8) + q);
        }
      }
      if (p == 4 || p == 5) { recv_issue(r0, 2 * p - 8); recv_issue(r1, 2 * p - 7); }
      if (p >= 6) recv_issue(r0, p - 2);
      mbar_wait(sb + OFF_XFULL + 8 * (p - 2), 1);
      if (p == 6) TS(wg, 19);
      bar_sync(3 + wg, 256);
      if (p == 6) TS(wg, 20);
      wg_fence();
#pragma unroll
      for (int kk = 0; kk < 8; kk++)
        wgmma_n64_ss<1, 0, DH128, DH128>(o, dh, (kk >> 2) * 16384 + (kk & 3) * 2048, dx0, wo + (kk >> 2) * 8192 + (kk & 3) * 32, kk != 0);
#pragma unroll
      for (int kk = 0; kk < 14; kk++)
        wgmma_n64_rs<1, DH128>(o, H[4 * kk], H[4 * kk + 1], H[4 * kk + 2], H[4 * kk + 3], dx0, wo + 16384 + (kk / 7) * 16384 + (kk % 7) * 2048, 1);
      wg_commit();
      if (p < 7 || wg == 0) bar_arrive(4 - wg, 256);
      if (p == 6) TS(wg, 21);
      if (p == 7) recv_issue(r1, 6);
      if (p < 7 && elect_one()) asm volatile("cp.async.bulk.wait_group.read 1;" ::: "memory");
      if (p == 2 || p == 3) {
        if (p == 2) {
#pragma unroll
          for (int h = 0; h < 2; h++) rho[h] = lds_f(sb + OFF_GS + (wg * 64 + w * 16 + gr + 8 * h) * 4);
        }
#pragma unroll
        for (int j = (p - 2) * 4; j < (p - 1) * 4; j++) {
          const uint32_t bb = bf2_add(r0[8 + j], r0[8 + j]);
#pragma unroll
          for (int h = 0; h < 2; h++) {
            const uint32_t xd = bf2_mul(lds_u(xw + 7 * 16384 + (w * 16 + gr + 8 * h) * 128 + ((j ^ gr) << 4) + q * 4), r0[j]);
            sum[4 * j + 2 * h] = fmaf(0.5f * rho[h], bf_lo(xd), bf_lo(bb));
            sum[4 * j + 2 * h + 1] = fmaf(0.5f * rho[h], bf_hi(xd), bf_hi(bb));
            pin(sum[4 * j + 2 * h]); pin(sum[4 * j + 2 * h + 1]);
          }
        }
      } else {
        recv_add(r0, p < 6 ? 2 * p - 8 : p - 2);
      }
      if (p == 6) TS(wg, 22);
      wg_wait<0>();
      if (p < 5) release(grp);
      reg_fence(o);
      if (p == 6) TS(wg, 23);
      if (p < 7) {
        stage(o, p);
        asm volatile("fence.proxy.async.shared::cta;" ::: "memory");
        __syncwarp();
        if (elect_one()) push(p);
      }
      if (p == 4 || p == 5) recv_add(r1, 2 * p - 7);
      TS(wg, 8 + p);
    }
    {
      float fs[2];
#pragma unroll
      for (int h = 0; h < 2; h++) fs[h] = __fdividef(2.f, 4.f + rho[h]);
#pragma unroll
      for (int i = 0; i < 32; i++) sum[i] = (sum[i] + o[i]) * fs[(i >> 1) & 1];
      reg_fence(sum);
      recv_check(r1, 6);
      TS(wg, 16);
      float* op = out + (size_t)(m * 128 + wg * 64 + (gr >> 1) * 16 + w * 4 + (gr & 1)) * DM + s * 64 + q * 2;
#pragma unroll
      for (int i = 0; i < 16; i++)
        *reinterpret_cast<float2*>(op + (i & 1) * 2 * DM + (i >> 1) * 8) =
            make_float2(fmaf(bf_lo(r1[i]), fs[i & 1], sum[2 * i]), fmaf(bf_hi(r1[i]), fs[i & 1], sum[2 * i + 1]));
      if (threadIdx.x == 128) g_epoch[b] = epoch + 1;
      if (elect_one()) asm volatile("cp.async.bulk.wait_group.read 0;" ::: "memory");
      TS(wg, 17); TG(wg);
    }
  }
}

typedef CUresult (*EncFn)(CUtensorMap*, CUtensorMapDataType, cuuint32_t, void*, const cuuint64_t*, const cuuint64_t*, const cuuint32_t*,
                          const cuuint32_t*, CUtensorMapInterleave, CUtensorMapSwizzle, CUtensorMapL2promotion, CUtensorMapFloatOOBfill);

void encode(EncFn f, CUtensorMap* mp, const void* p, int rank, const cuuint64_t* dims, const cuuint64_t* strides, const cuuint32_t* box, CUtensorMapSwizzle sw) {
  cuuint32_t es[5] = {1, 1, 1, 1, 1};
  f(mp, CU_TENSOR_MAP_DATA_TYPE_BFLOAT16, rank, const_cast<void*>(p), dims, strides, box, es, CU_TENSOR_MAP_INTERLEAVE_NONE, sw,
    CU_TENSOR_MAP_L2_PROMOTION_L2_128B, CU_TENSOR_MAP_FLOAT_OOB_FILL_NONE);
}

}

extern "C" void kernel_launch(void* const* d_in, const int* in_sizes, int n_in, void* d_out, int out_size) {
  typedef const __nv_bfloat16* bp;
  bp x = (bp)d_in[0], lre = (bp)d_in[1], lim = (bp)d_in[2], bre = (bp)d_in[3], bim = (bp)d_in[4], cre = (bp)d_in[5], cim = (bp)d_in[6],
     ldt = (bp)d_in[7], dsk = (bp)d_in[8], w1 = (bp)d_in[10], b1 = (bp)d_in[11], w2 = (bp)d_in[12], b2 = (bp)d_in[13], gw = (bp)d_in[14];
  static EncFn enc = nullptr;
  if (!enc) {
    void* f = nullptr;
    cudaDriverEntryPointQueryResult qr;
    cudaGetDriverEntryPoint("cuTensorMapEncodeTiled", &f, cudaEnableDefault, &qr);
    enc = (EncFn)f;
    cudaFuncSetAttribute(fused_kernel, cudaFuncAttributeMaxDynamicSharedMemorySize, SMEM_BYTES);
  }
  Maps maps;
  {
    cuuint64_t d[5] = {DM, 2, 4, 8, SEQ / 64}, st[4] = {DM * 2, 16 * DM * 2, 2 * DM * 2, 64 * DM * 2};
    cuuint32_t bx[5] = {64, 2, 4, 8, 2};
    encode(enc, &maps.x, x, 5, d, st, bx, CU_TENSOR_MAP_SWIZZLE_128B);
  }
  {
    cuuint64_t d[2] = {DM, DM}, st[1] = {DM * 2};
    cuuint32_t bx[2] = {64, 64};
    encode(enc, &maps.bre, bre, 2, d, st, bx, CU_TENSOR_MAP_SWIZZLE_128B);
    encode(enc, &maps.bim, bim, 2, d, st, bx, CU_TENSOR_MAP_SWIZZLE_128B);
    encode(enc, &maps.cre, cre, 2, d, st, bx, CU_TENSOR_MAP_SWIZZLE_128B);
    encode(enc, &maps.cim, cim, 2, d, st, bx, CU_TENSOR_MAP_SWIZZLE_128B);
  }
  {
    cuuint64_t d[2] = {FF, DM}, st[1] = {FF * 2};
    cuuint32_t bx[2] = {64, 64};
    encode(enc, &maps.w1a, w1, 2, d, st, bx, CU_TENSOR_MAP_SWIZZLE_128B);
    cuuint64_t d3[3] = {32, DM, FF / 32}, st3[2] = {FF * 2, 64};
    cuuint32_t bx3[3] = {32, 32, 3};
    encode(enc, &maps.w1b, w1, 3, d3, st3, bx3, CU_TENSOR_MAP_SWIZZLE_64B);
  }
  {
    cuuint64_t d[2] = {DM, FF}, st[1] = {DM * 2};
    cuuint32_t bx[2] = {64, 56};
    encode(enc, &maps.w2, w2, 2, d, st, bx, CU_TENSOR_MAP_SWIZZLE_128B);
  }
  fused_kernel<<<128, 384, SMEM_BYTES>>>(maps, lre, lim, ldt, dsk, b1, b2, gw, w1, w2, cre, cim, (float*)d_out);
}
```

```cpp
#include <cuda_runtime.h>
#include <cuda_bf16.h>
#include <cuda.h>
#include <stdint.h>

#define PF 2
#define SEND_TMA 1
#define PFK 2
namespace {

constexpr int SEQ = 2048, DM = 512, FF = 1792;
constexpr int NSLOT = 6;
constexpr uint32_t OFF_X = 0, OFF_RING = 131072, OFF_MISC = 229376;
constexpr uint32_t OFF_XFULL = OFF_MISC, OFF_FULL = OFF_XFULL + 64, OFF_EMPTY = OFF_FULL + 48, OFF_GBAR = OFF_EMPTY + 48,
                   OFF_CBAR = OFF_GBAR + 8, OFF_EPOCH = OFF_CBAR + 8;
constexpr uint32_t OFF_GS = OFF_MISC + 256;
constexpr uint32_t OFF_CARRY = OFF_GS + 512;
constexpr uint32_t OFF_DBG = OFF_CARRY + 1024;
constexpr uint32_t SMEM_BYTES = OFF_DBG + 768;
static_assert(SMEM_BYTES <= 232448, "smem");

struct Maps { CUtensorMap x, bre, bim, w1a, w1b, w2, cre, cim; };

__device__ uint4 g_part[16 * 8 * 7 * 1024];
__device__ float2 g_end[8 * 16 * 64];
__device__ unsigned g_gate[SEQ];
__device__ unsigned g_epoch[128];
#define TG(role) do {} while (0)
#define TS2(role, i) do {} while (0)
#define TS(role, i) do {} while (0)
#define TDUMP() do {} while (0)

__device__ __forceinline__ void mbar_init(uint32_t bar, uint32_t cnt) { asm volatile("mbarrier.init.shared::cta.b64 [%0], %1;" ::"r"(bar), "r"(cnt)); }
__device__ __forceinline__ void mbar_expect_tx(uint32_t bar, uint32_t bytes) { asm volatile("mbarrier.arrive.expect_tx.shared::cta.b64 _, [%0], %1;" ::"r"(bar), "r"(bytes) : "memory"); }
__device__ __forceinline__ void mbar_arrive(uint32_t bar) { asm volatile("mbarrier.arrive.shared::cta.b64 _, [%0];" ::"r"(bar) : "memory"); }
__device__ __forceinline__ void mbar_arrive_cl(uint32_t cbar) { asm volatile("mbarrier.arrive.shared::cluster.b64 _, [%0];" ::"r"(cbar) : "memory"); }
__device__ __forceinline__ void mbar_wait(uint32_t bar, uint32_t parity) {
  asm volatile(
      "{\n.reg .pred p;\n.reg .u32 c;\n"
      "mbarrier.try_wait.parity.shared::cta.b64 p, [%0], %1;\n"
      "@p bra.uni LAB_DONE;\n"
      "mov.u32 c, 0;\n"
      "LAB_WAIT:\n"
      "mbarrier.try_wait.parity.shared::cta.b64 p, [%0], %1;\n"
      "@p bra.uni LAB_DONE;\n"
      "add.u32 c, c, 1;\nsetp.lt.u32 p, c, 200000;\n@p bra.uni LAB_WAIT;\n"
      "LAB_DONE:\n}" ::"r"(bar), "r"(parity) : "memory");
}
__device__ __forceinline__ void tma2d(uint32_t dst, const CUtensorMap* m, int c0, int c1, uint32_t bar) {
  asm volatile("cp.async.bulk.tensor.2d.shared::cluster.global.mbarrier::complete_tx::bytes [%0], [%1, {%3,%4}], [%2];"
               ::"r"(dst), "l"(m), "r"(bar), "r"(c0), "r"(c1) : "memory");
}
__device__ __forceinline__ void tma2d_mc(uint32_t dst, const CUtensorMap* m, int c0, int c1, uint32_t bar) {
  asm volatile("cp.async.bulk.tensor.2d.shared::cluster.global.mbarrier::complete_tx::bytes.multicast::cluster [%0], [%1, {%3,%4}], [%2], %5;"
               ::"r"(dst), "l"(m), "r"(bar), "r"(c0), "r"(c1), "h"((uint16_t)3) : "memory");
}
__device__ __forceinline__ void tma3d_mc(uint32_t dst, const CUtensorMap* m, int c0, int c1, int c2, uint32_t bar) {
  asm volatile("cp.async.bulk.tensor.3d.shared::cluster.global.mbarrier::complete_tx::bytes.multicast::cluster [%0], [%1, {%3,%4,%5}], [%2], %6;"
               ::"r"(dst), "l"(m), "r"(bar), "r"(c0), "r"(c1), "r"(c2), "h"((uint16_t)3) : "memory");
}
__device__ __forceinline__ void tma5d(uint32_t dst, const CUtensorMap* m, int c0, int c4, uint32_t bar) {
  asm volatile("cp.async.bulk.tensor.5d.shared::cluster.global.mbarrier::complete_tx::bytes [%0], [%1, {%3,%5,%5,%5,%4}], [%2];"
               ::"r"(dst), "l"(m), "r"(bar), "r"(c0), "r"(c4), "r"(0) : "memory");
}
__device__ __forceinline__ void l2_prefetch(const void* p, uint32_t bytes) { asm volatile("cp.async.bulk.prefetch.L2.global [%0], %1;" ::"l"(p), "r"(bytes) : "memory"); }
__device__ __forceinline__ bool elect_one() {
  uint32_t pred;
  asm volatile("{.reg .pred P; elect.sync _|P, 0xffffffff; selp.u32 %0, 1, 0, P;}" : "=r"(pred));
  return pred != 0;
}
__device__ __forceinline__ void wg_fence() { asm volatile("wgmma.fence.sync.aligned;" ::: "memory"); }
__device__ __forceinline__ void wg_commit() { asm volatile("wgmma.commit_group.sync.aligned;" ::: "memory"); }
template <int N> __device__ __forceinline__ void wg_wait() { asm volatile("wgmma.wait_group.sync.aligned %0;" ::"n"(N) : "memory"); }
template <int N> __device__ __forceinline__ void reg_fence(float (&d)[N]) {
#pragma unroll
  for (int i = 0; i < N; i++) asm volatile("" : "+f"(d[i])::"memory");
}
__device__ __forceinline__ void bar_sync(int id, int n) { asm volatile("bar.sync %0, %1;" ::"r"(id), "r"(n) : "memory"); }
__device__ __forceinline__ void bar_arrive(int id, int n) { asm volatile("bar.arrive %0, %1;" ::"r"(id), "r"(n) : "memory"); }
constexpr uint32_t DH128 = (1024 >> 4) | (1u << 30), DH64 = (512 >> 4) | (2u << 30);
__host__ __device__ constexpr uint32_t lbo(uint32_t bytes) { return (bytes >> 4) << 20; }
__device__ __forceinline__ uint32_t pack_bf16(float lo, float hi) { uint32_t r; asm("cvt.rn.bf16x2.f32 %0, %1, %2;" : "=r"(r) : "f"(hi), "f"(lo)); return r; }
__device__ __forceinline__ float bf_lo(uint32_t v) { return __uint_as_float(v << 16); }
__device__ __forceinline__ float bf_hi(uint32_t v) { return __uint_as_float(v & 0xffff0000u); }
__device__ __forceinline__ float bf_ld(const __nv_bfloat16* p) { return __bfloat162float(__ldg(p)); }
__device__ __forceinline__ float2 lds_f2(uint32_t a) { float2 v; asm volatile("ld.shared.v2.f32 {%0,%1}, [%2];" : "=f"(v.x), "=f"(v.y) : "r"(a)); return v; }
__device__ __forceinline__ float lds_f(uint32_t a) { float v; asm volatile("ld.shared.f32 %0, [%1];" : "=f"(v) : "r"(a)); return v; }
__device__ __forceinline__ uint32_t lds_u(uint32_t a) { uint32_t v; asm volatile("ld.shared.u32 %0, [%1];" : "=r"(v) : "r"(a)); return v; }
__device__ __forceinline__ uint4 lds_u4(uint32_t a) { uint4 v; asm volatile("ld.shared.v4.u32 {%0,%1,%2,%3}, [%4];" : "=r"(v.x), "=r"(v.y), "=r"(v.z), "=r"(v.w) : "r"(a)); return v; }
__device__ __forceinline__ void st_b128(uint4* p, uint32_t a, uint32_t b, uint32_t c, uint32_t d) {
  asm volatile("{.reg .b64 l, h; .reg .b128 v; mov.b64 l, {%1,%2}; mov.b64 h, {%3,%4}; mov.b128 v, {l,h}; st.relaxed.gpu.global.b128 [%0], v;}"
               ::"l"(p), "r"(a), "r"(b), "r"(c), "r"(d) : "memory");
}
__device__ __forceinline__ void ld_b128(const uint4* p, uint32_t& a, uint32_t& b, uint32_t& c, uint32_t& d) {
  asm volatile("{.reg .b64 l, h; .reg .b128 v; ld.relaxed.gpu.global.b128 v, [%4]; mov.b128 {l,h}, v; mov.b64 {%0,%1}, l; mov.b64 {%2,%3}, h;}"
               : "=r"(a), "=r"(b), "=r"(c), "=r"(d) : "l"(p) : "memory");
}
__device__ __forceinline__ float tanh_fast(float x) { float y; asm("tanh.approx.f32 %0, %1;" : "=f"(y) : "f"(x)); return y; }
__device__ __forceinline__ float gelu2(float v) {
  float p = fmaf(v * v, 0.0356774081363f, 0.7978845608029f);
  return fmaf(v, tanh_fast(v * p), v);
}
__device__ __forceinline__ uint32_t bf2_mul(uint32_t a, uint32_t b) { uint32_t r; asm("mul.rn.bf16x2 %0, %1, %2;" : "=r"(r) : "r"(a), "r"(b)); return r; }
__device__ __forceinline__ uint32_t bf2_add(uint32_t a, uint32_t b) { uint32_t r; asm("add.rn.bf16x2 %0, %1, %2;" : "=r"(r) : "r"(a), "r"(b)); return r; }
__device__ __forceinline__ uint32_t bf2_fma(uint32_t a, uint32_t b, uint32_t c) { uint32_t r; asm("fma.rn.bf16x2 %0, %1, %2, %3;" : "=r"(r) : "r"(a), "r"(b), "r"(c)); return r; }
__device__ __forceinline__ void pin(float& a) { asm volatile("" : "+f"(a)::"memory"); }
__device__ __forceinline__ void pin(uint32_t& a) { asm volatile("" : "+r"(a)::"memory"); }
struct cplx { float re, im; };
__device__ __forceinline__ cplx cmul(cplx a, cplx b) { return {fmaf(a.re, b.re, -a.im * b.im), fmaf(a.re, b.im, a.im * b.re)}; }
__device__ __forceinline__ cplx cfma(cplx a, cplx b, cplx c) {
  return {fmaf(a.re, b.re, fmaf(-a.im, b.im, c.re)), fmaf(a.re, b.im, fmaf(a.im, b.re, c.im))};
}
__device__ __forceinline__ cplx make_lam(float lre, float lim, float ldt) {
  float dt = __bfloat162float(__float2bfloat16_rn(expf(ldt)));
  float mag = expf(dt * lre), sn, cs;
  sincospif(dt * lim * 0.31830988618379067f, &sn, &cs);
  return {mag * cs, mag * sn};
}

template<int TA,int TB,uint32_t AH,uint32_t BH> __device__ __forceinline__ void wgmma_n64_ss(float (&d)[32], uint32_t al, uint32_t ao, uint32_t bl, uint32_t bo, int scale_d){
  asm volatile("{.reg .pred p; .reg .b32 t, v; .reg .b64 da, db; setp.ne.b32 p, %36, 0; add.u32 t, %32, %33; mov.b64 da, {t, %39}; add.u32 v, %34, %35; mov.b64 db, {v, %40};\n"
   "wgmma.mma_async.sync.aligned.m64n64k16.f32.bf16.bf16 {%0,%1,%2,%3,%4,%5,%6,%7,%8,%9,%10,%11,%12,%13,%14,%15,%16,%17,%18,%19,%20,%21,%22,%23,%24,%25,%26,%27,%28,%29,%30,%31}, da, db, p, 1, 1, %37, %38;}"
   : "+f"(d[0]),"+f"(d[1]),"+f"(d[2]),"+f"(d[3]),"+f"(d[4]),"+f"(d[5]),"+f"(d[6]),"+f"(d[7]),"+f"(d[8]),"+f"(d[9]),"+f"(d[10]),"+f"(d[11]),"+f"(d[12]),"+f"(d[13]),"+f"(d[14]),"+f"(d[15]),"+f"(d[16]),"+f"(d[17]),"+f"(d[18]),"+f"(d[19]),"+f"(d[20]),"+f"(d[21]),"+f"(d[22]),"+f"(d[23]),"+f"(d[24]),"+f"(d[25]),"+f"(d[26]),"+f"(d[27]),"+f"(d[28]),"+f"(d[29]),"+f"(d[30]),"+f"(d[31])
   : "r"(al),"r"(ao >> 4),"r"(bl),"r"(bo >> 4),"r"(scale_d),"n"(TA),"n"(TB),"n"(AH),"n"(BH));
}
template<int TB,uint32_t BH> __device__ __forceinline__ void wgmma_n64_rs(float (&d)[32], uint32_t a0,uint32_t a1,uint32_t a2,uint32_t a3, uint32_t bl, uint32_t bo, int scale_d){
  asm volatile("{.reg .pred p; .reg .b32 t; .reg .b64 db; setp.ne.b32 p, %38, 0; add.u32 t, %36, %37; mov.b64 db, {t, %40};\n"
   "wgmma.mma_async.sync.aligned.m64n64k16.f32.bf16.bf16 {%0,%1,%2,%3,%4,%5,%6,%7,%8,%9,%10,%11,%12,%13,%14,%15,%16,%17,%18,%19,%20,%21,%22,%23,%24,%25,%26,%27,%28,%29,%30,%31}, {%32,%33,%34,%35}, db, p, 1, 1, %39;}"
   : "+f"(d[0]),"+f"(d[1]),"+f"(d[2]),"+f"(d[3]),"+f"(d[4]),"+f"(d[5]),"+f"(d[6]),"+f"(d[7]),"+f"(d[8]),"+f"(d[9]),"+f"(d[10]),"+f"(d[11]),"+f"(d[12]),"+f"(d[13]),"+f"(d[14]),"+f"(d[15]),"+f"(d[16]),"+f"(d[17]),"+f"(d[18]),"+f"(d[19]),"+f"(d[20]),"+f"(d[21]),"+f"(d[22]),"+f"(d[23]),"+f"(d[24]),"+f"(d[25]),"+f"(d[26]),"+f"(d[27]),"+f"(d[28]),"+f"(d[29]),"+f"(d[30]),"+f"(d[31])
   : "r"(a0),"r"(a1),"r"(a2),"r"(a3),"r"(bl),"r"(bo >> 4),"r"(scale_d),"n"(TB),"n"(BH));
}
template<int TA,int TB,uint32_t AH,uint32_t BH> __device__ __forceinline__ void wgmma_n96_ss(float (&d)[48], uint32_t al, uint32_t ao, uint32_t bl, uint32_t bo, int scale_d){
  asm volatile("{.reg .pred p; .reg .b32 t, v; .reg .b64 da, db; setp.ne.b32 p, %52, 0; add.u32 t, %48, %49; mov.b64 da, {t, %55}; add.u32 v, %50, %51; mov.b64 db, {v, %56};\n"
   "wgmma.mma_async.sync.aligned.m64n96k16.f32.bf16.bf16 {%0,%1,%2,%3,%4,%5,%6,%7,%8,%9,%10,%11,%12,%13,%14,%15,%16,%17,%18,%19,%20,%21,%22,%23,%24,%25,%26,%27,%28,%29,%30,%31,%32,%33,%34,%35,%36,%37,%38,%39,%40,%41,%42,%43,%44,%45,%46,%47}, da, db, p, 1, 1, %53, %54;}"
   : "+f"(d[0]),"+f"(d[1]),"+f"(d[2]),"+f"(d[3]),"+f"(d[4]),"+f"(d[5]),"+f"(d[6]),"+f"(d[7]),"+f"(d[8]),"+f"(d[9]),"+f"(d[10]),"+f"(d[11]),"+f"(d[12]),"+f"(d[13]),"+f"(d[14]),"+f"(d[15]),"+f"(d[16]),"+f"(d[17]),"+f"(d[18]),"+f"(d[19]),"+f"(d[20]),"+f"(d[21]),"+f"(d[22]),"+f"(d[23]),"+f"(d[24]),"+f"(d[25]),"+f"(d[26]),"+f"(d[27]),"+f"(d[28]),"+f"(d[29]),"+f"(d[30]),"+f"(d[31]),"+f"(d[32]),"+f"(d[33]),"+f"(d[34]),"+f"(d[35]),"+f"(d[36]),"+f"(d[37]),"+f"(d[38]),"+f"(d[39]),"+f"(d[40]),"+f"(d[41]),"+f"(d[42]),"+f"(d[43]),"+f"(d[44]),"+f"(d[45]),"+f"(d[46]),"+f"(d[47])
   : "r"(al),"r"(ao >> 4),"r"(bl),"r"(bo >> 4),"r"(scale_d),"n"(TA),"n"(TB),"n"(AH),"n"(BH));
}
template<int TA,int TB,uint32_t AH,uint32_t BH> __device__ __forceinline__ void wgmma_n128_ss(float (&d)[64], uint32_t al, uint32_t ao, uint32_t bl, uint32_t bo, int scale_d){
  asm volatile("{.reg .pred p; .reg .b32 t, v; .reg .b64 da, db; setp.ne.b32 p, %68, 0; add.u32 t, %64, %65; mov.b64 da, {t, %71}; add.u32 v, %66, %67; mov.b64 db, {v, %72};\n"
   "wgmma.mma_async.sync.aligned.m64n128k16.f32.bf16.bf16 {%0,%1,%2,%3,%4,%5,%6,%7,%8,%9,%10,%11,%12,%13,%14,%15,%16,%17,%18,%19,%20,%21,%22,%23,%24,%25,%26,%27,%28,%29,%30,%31,%32,%33,%34,%35,%36,%37,%38,%39,%40,%41,%42,%43,%44,%45,%46,%47,%48,%49,%50,%51,%52,%53,%54,%55,%56,%57,%58,%59,%60,%61,%62,%63}, da, db, p, 1, 1, %69, %70;}"
   : "+f"(d[0]),"+f"(d[1]),"+f"(d[2]),"+f"(d[3]),"+f"(d[4]),"+f"(d[5]),"+f"(d[6]),"+f"(d[7]),"+f"(d[8]),"+f"(d[9]),"+f"(d[10]),"+f"(d[11]),"+f"(d[12]),"+f"(d[13]),"+f"(d[14]),"+f"(d[15]),"+f"(d[16]),"+f"(d[17]),"+f"(d[18]),"+f"(d[19]),"+f"(d[20]),"+f"(d[21]),"+f"(d[22]),"+f"(d[23]),"+f"(d[24]),"+f"(d[25]),"+f"(d[26]),"+f"(d[27]),"+f"(d[28]),"+f"(d[29]),"+f"(d[30]),"+f"(d[31]),"+f"(d[32]),"+f"(d[33]),"+f"(d[34]),"+f"(d[35]),"+f"(d[36]),"+f"(d[37]),"+f"(d[38]),"+f"(d[39]),"+f"(d[40]),"+f"(d[41]),"+f"(d[42]),"+f"(d[43]),"+f"(d[44]),"+f"(d[45]),"+f"(d[46]),"+f"(d[47]),"+f"(d[48]),"+f"(d[49]),"+f"(d[50]),"+f"(d[51]),"+f"(d[52]),"+f"(d[53]),"+f"(d[54]),"+f"(d[55]),"+f"(d[56]),"+f"(d[57]),"+f"(d[58]),"+f"(d[59]),"+f"(d[60]),"+f"(d[61]),"+f"(d[62]),"+f"(d[63])
   : "r"(al),"r"(ao >> 4),"r"(bl),"r"(bo >> 4),"r"(scale_d),"n"(TA),"n"(TB),"n"(AH),"n"(BH));
}

__global__ void __cluster_dims__(2, 1, 1) __launch_bounds__(384, 1)
fused_kernel(const __grid_constant__ Maps maps, const __nv_bfloat16* __restrict__ lam_re,
             const __nv_bfloat16* __restrict__ lam_im, const __nv_bfloat16* __restrict__ log_dt, const __nv_bfloat16* __restrict__ dskip,
             const __nv_bfloat16* __restrict__ b1, const __nv_bfloat16* __restrict__ b2, const __nv_bfloat16* __restrict__ gate_w,
             const __nv_bfloat16* __restrict__ pf_w1, const __nv_bfloat16* __restrict__ pf_w2, const __nv_bfloat16* __restrict__ pf_cre,
             const __nv_bfloat16* __restrict__ pf_cim, float* __restrict__ out) {
  extern __shared__ __align__(1024) unsigned char smem_raw[];
  const uint32_t sb = (uint32_t)__cvta_generic_to_shared(smem_raw);
  const int b = blockIdx.x;
  const int rank = b & 1, s = (b >> 1) & 7, m = ((b >> 4) << 1) | rank;
  const int warp = __shfl_sync(0xffffffffu, (int)(threadIdx.x >> 5), 0);
  const int lane = threadIdx.x & 31;
  const int xrot = 7 - s;

  if (warp == 8) {
    if (elect_one()) {
      TS(2, 0);
      mbar_init(sb + OFF_XFULL, 1); mbar_init(sb + OFF_FULL, 1); mbar_init(sb + OFF_XFULL + 8, 1);
      asm volatile("fence.mbarrier_init.release.cluster;" ::: "memory");
      asm volatile("fence.proxy.async.shared::cta;" ::: "memory");
      mbar_expect_tx(sb + OFF_XFULL, 16384);
      tma5d(sb + OFF_X + xrot * 16384, &maps.x, 0, 2 * m, sb + OFF_XFULL);
      mbar_expect_tx(sb + OFF_FULL, 16384);
      tma2d(sb + OFF_RING, &maps.bre, 0, s * 64, sb + OFF_FULL);
      tma2d(sb + OFF_RING + 8192, &maps.bim, 0, s * 64, sb + OFF_FULL);
      mbar_expect_tx(sb + OFF_XFULL + 8, 16384);
      tma5d(sb + OFF_X + ((xrot + 1) & 7) * 16384, &maps.x, 64, 2 * m, sb + OFF_XFULL + 8);
    }
  } else if (warp < 6) {
    if (elect_one()) {
      mbar_init(sb + OFF_XFULL + 16 + 8 * warp, 1); mbar_init(sb + OFF_EMPTY + 8 * warp, 16);
      if (warp) mbar_init(sb + OFF_FULL + 8 * warp, 1);
      asm volatile("fence.mbarrier_init.release.cluster;" ::: "memory");
    }
  } else if (warp < 8) {
    if (elect_one()) {
      mbar_init(sb + OFF_GBAR + 8 * (warp - 6), 64);
      asm volatile("fence.mbarrier_init.release.cluster;" ::: "memory");
    }
  }
  __syncwarp();
  asm volatile("barrier.cluster.arrive.relaxed.aligned;" ::: "memory");

  if (warp >= 8) {
    asm volatile("setmaxnreg.dec.sync.aligned.u32 56;");
    if (warp == 8) {
      asm volatile("barrier.cluster.wait.aligned;" ::: "memory");
      if (elect_one()) {
        TS(2, 1); TG(2);
        const CUtensorMap* mb = rank ? &maps.bim : &maps.bre;
        const CUtensorMap* mc = rank ? &maps.cim : &maps.cre;
        int slot = 1; uint32_t ph = 1;
#pragma unroll 1
        for (int u = 1; u < 24; u++) {
          const uint32_t fb = sb + OFF_FULL + 8 * slot, dst = sb + OFF_RING + slot * 16384;
          if (u >= NSLOT) mbar_wait(sb + OFF_EMPTY + 8 * slot, ph);
          TS2(0, u);
          if (u < 8) {
            mbar_expect_tx(fb, 16384);
            tma2d_mc(dst + rank * 8192, mb, u * 64, s * 64, fb);
            if (u < 6) {
              mbar_expect_tx(sb + OFF_XFULL + 8 * (u + 1), 16384);
              tma5d(sb + OFF_X + ((u + 1 + xrot) & 7) * 16384, &maps.x, (u + 1) * 64, 2 * m, sb + OFF_XFULL + 8 * (u + 1));
              if (u == 5) {
                mbar_expect_tx(sb + OFF_XFULL + 56, 16384);
                tma5d(sb + OFF_X + ((7 + xrot) & 7) * 16384, &maps.x, 7 * 64, 2 * m, sb + OFF_XFULL + 56);
              }
            }
          } else if (u < 16) {
            mbar_expect_tx(fb, 12288);
            tma3d_mc(dst + rank * 6144, &maps.w1b, 0, (u - 8) * 64 + rank * 32, s * 7, fb);
          } else {
            mbar_expect_tx(fb, 16384);
            tma2d_mc(dst + rank * 8192, &maps.w1a, s * 224 + 96 + rank * 64, ((u - 15 + s) & 7) * 64, fb);
          }
          if (++slot == NSLOT) { slot = 0; ph ^= 1; }
        }
#pragma unroll 1
        for (int p = 0; p < 8; p++) {
          const int piece = (s + 1 + p) & 7, grp = p % 3;
          const uint32_t fb = sb + OFF_XFULL + 8 * p, dst = grp == 1 ? sb + OFF_X + 2 * 16384 : sb + OFF_RING + grp * 24576;
          if (p >= 3) mbar_wait(sb + OFF_EMPTY + 8 * (p - 3), 0);
          else if (p != 1) mbar_wait(sb + OFF_EMPTY + 16 + 12 * p, 1);
          TS2(0, 24 + p);
          mbar_expect_tx(fb, 45056);
          tma2d_mc(dst + rank * 8192, mc, s * 64, piece * 64, fb);
          tma2d_mc(dst + 16384 + rank * 7168, &maps.w2, piece * 64, s * 224 + rank * 56, fb);
          tma2d_mc(dst + 32768 + rank * 7168, &maps.w2, piece * 64, s * 224 + 112 + rank * 56, fb);
        }
        TS(2, 2);
      }
    } else if (warp == 11) {
      asm volatile("barrier.cluster.wait.aligned;" ::: "memory");
      if ((PF & 2) && elect_one()) {
        mbar_wait(sb + OFF_XFULL + 8 * PFK, 0);
        l2_prefetch(pf_w1 + b * 7168, 14336);
        l2_prefetch(pf_cre + b * 2048, 4096);
        l2_prefetch(pf_cim + b * 2048, 4096);
        l2_prefetch(pf_w2 + b * 7168, 14336);
      }
    } else {
      const int t = threadIdx.x - 288;
      unsigned par;
      asm volatile("ld.relaxed.gpu.global.u32 %0, [%1];" : "=r"(par) : "l"(g_epoch + b) : "memory");
      const float pr = bf_ld(lam_re + s * 64 + t), pi = bf_ld(lam_im + s * 64 + t), pd = bf_ld(log_dt + s * 64 + t);
      const uint4* gwp = reinterpret_cast<const uint4*>(gate_w) + (lane & 7);
      uint4 gw[8];
#pragma unroll
      for (int kb = 0; kb < 8; kb++) gw[kb] = __ldg(gwp + kb * 8);
      asm volatile("barrier.cluster.wait.aligned;" ::: "memory");
      if (t == 0) asm volatile("st.shared.u32 [%0], %1;" ::"r"(sb + OFF_EPOCH), "r"(par + 1) : "memory");
      par = (par + 1) & 1;
      cplx l64 = make_lam(pr, pi, pd);
#pragma unroll
      for (int i = 0; i < 6; i++) l64 = cmul(l64, l64);
      const int row = s * 16 + (t >> 5) * 8 + (lane >> 3);
      const uint32_t xr0 = sb + OFF_X + row * 128 + (((lane & 7) ^ (row & 7)) << 4), xr1 = (xr0 + 512) ^ 64;
      float z0 = 0.f, z1 = 0.f;
#pragma unroll
      for (int kb = 0; kb < 8; kb++) {
        const uint4 w = gw[kb];
        mbar_wait(sb + OFF_XFULL + 8 * kb, 0);
        const uint32_t xo = ((kb + xrot) & 7) * 16384;
        const uint4 a = lds_u4(xr0 + xo), d = lds_u4(xr1 + xo);
        const uint32_t wv[4] = {w.x, w.y, w.z, w.w}, av[4] = {a.x, a.y, a.z, a.w}, dv[4] = {d.x, d.y, d.z, d.w};
#pragma unroll
        for (int c = 0; c < 4; c++) {
          const float wl = bf_lo(wv[c]), wh = bf_hi(wv[c]);
          z0 = fmaf(bf_hi(av[c]), wh, fmaf(bf_lo(av[c]), wl, z0));
          z1 = fmaf(bf_hi(dv[c]), wh, fmaf(bf_lo(dv[c]), wl, z1));
        }
      }
      {
        float zz = (lane & 4) ? z1 : z0;
        zz += __shfl_xor_sync(0xffffffffu, (lane & 4) ? z0 : z1, 4);
        zz += __shfl_xor_sync(0xffffffffu, zz, 2);
        zz += __shfl_xor_sync(0xffffffffu, zz, 1);
        const float rho = 4.f * expf(zz > 40.f ? 40.f : zz);
        if ((lane & 3) == 0)
          asm volatile("st.relaxed.gpu.global.u32 [%0], %1;" ::"l"(g_gate + m * 128 + row + (lane & 4)), "r"((__float_as_uint(rho) & ~1u) | par) : "memory");
      }
      if (t == 0) TS(3, 0);
      mbar_wait(sb + OFF_GBAR, 0);
      const float2 e0 = lds_f2(sb + OFF_CARRY + t * 8), e1 = lds_f2(sb + OFF_CARRY + 512 + t * 8);
      float2* eb = g_end + s * 1024 + t;
      {
        const cplx e = cfma(l64, cplx{e0.x, e0.y}, cplx{e1.x, e1.y});
        const unsigned long long v = ((unsigned long long)__float_as_uint(e.im) << 32) | ((__float_as_uint(e.re) & ~1u) | par);
        asm volatile("st.relaxed.gpu.global.b64 [%0], %1;" ::"l"(eb + m * 64), "l"(v) : "memory");
      }
      if (t == 0) TS(3, 1);
      {
        const unsigned* gp = g_gate + m * 128 + t;
        unsigned g0, g1;
        int tries = 0;
#pragma unroll 1
        do {
          asm volatile("ld.relaxed.gpu.global.u32 %0, [%1];" : "=r"(g0) : "l"(gp) : "memory");
          asm volatile("ld.relaxed.gpu.global.u32 %0, [%1];" : "=r"(g1) : "l"(gp + 64) : "memory");
        } while ((((g0 ^ par) | (g1 ^ par)) & 1) && ++tries < 200000);
        asm volatile("st.shared.u32 [%0], %1;" ::"r"(sb + OFF_GS + t * 4), "r"(g0) : "memory");
        asm volatile("st.shared.u32 [%0], %1;" ::"r"(sb + OFF_GS + 256 + t * 4), "r"(g1) : "memory");
      }
      if (t == 0) TS(3, 2);
      cplx S = {0.f, 0.f};
      {
        unsigned long long v[15];
        uint32_t bad;
        int tries = 0;
        const float2* e15 = eb + (m - 15) * 64;
#pragma unroll 1
        do {
          bad = 0;
#pragma unroll
          for (int i = 0; i < 15; i++) {
            v[i] = par;
            asm volatile("{.reg .pred p; setp.ge.s32 p, %2, %3; @p ld.relaxed.gpu.global.b64 %0, [%1];}" : "+l"(v[i]) : "l"(e15 + i * 64), "r"(m), "r"(15 - i) : "memory");
          }
#pragma unroll
          for (int i = 0; i < 15; i++) bad |= (uint32_t)v[i] ^ par;
        } while ((bad & 1) && ++tries < 200000);
        const cplx l128 = cmul(l64, l64);
#pragma unroll
        for (int i = 0; i < 15; i++) S = cfma(l128, S, cplx{__uint_as_float((uint32_t)v[i] & ~1u), __uint_as_float((uint32_t)(v[i] >> 32))});
      }
      const cplx S1 = cfma(l64, S, cplx{e0.x, e0.y});
      asm volatile("st.shared.v2.f32 [%0], {%1,%2};" ::"r"(sb + OFF_CARRY + t * 8), "f"(S.re), "f"(S.im) : "memory");
      asm volatile("st.shared.v2.f32 [%0], {%1,%2};" ::"r"(sb + OFF_CARRY + 512 + t * 8), "f"(S1.re), "f"(S1.im) : "memory");
      mbar_arrive(sb + OFF_CBAR);
      if (t == 0) TS(3, 3);
    }
  } else {
    const int wg = warp >> 2, w = warp & 3, q = lane & 3, gr = lane >> 2;
    const int c0 = s * 64 + w * 16 + gr + (q & 2) * 4;
    const float pr = bf_ld(lam_re + c0), pi = bf_ld(lam_im + c0), pd = bf_ld(log_dt + c0);
    uint32_t bv[28];
#pragma unroll
    for (int j = 0; j < 28; j++) bv[j] = __ldg(reinterpret_cast<const uint32_t*>(b1 + s * 224 + j * 8) + q);
    asm volatile("setmaxnreg.inc.sync.aligned.u32 224;");
    asm volatile("barrier.cluster.wait.aligned;" ::: "memory");
    TS(wg, 0);
    uint32_t ebar;
    asm volatile("mapa.shared::cluster.u32 %0, %1, %2;" : "=r"(ebar) : "r"(sb + OFF_EMPTY), "r"(lane & 1));
    auto release = [&](int slot) { if (lane < 2) mbar_arrive_cl(ebar + 8 * slot); };
    const uint32_t xw = sb + OFF_X + wg * 8192, fullb = sb + OFF_FULL;
    const uint32_t dxw = (xw & 0x3FFFF) >> 4, dring = ((sb + OFF_RING) & 0x3FFFF) >> 4;

    float ure[32], uim[32], aa[48], ab[64];
    cplx lam[2], coef[2], l16[2], l32[2], lq[2], pre[2], e[2];
    {
      const cplx l1 = make_lam(pr, pi, pd);
      const float inv = __fdividef(1.f, fmaf(pr, pr, pi * pi));
      const cplx cf = cmul(cplx{l1.re - 1.f, l1.im}, cplx{pr * inv, -pi * inv});
      cplx t = cmul(l1, l1); t = cmul(t, t); t = cmul(t, t); t = cmul(t, t);
#pragma unroll
      for (int h = 0; h < 2; h++) {
        lam[h] = cplx{__shfl_sync(0xffffffffu, l1.re, 2 * h, 4), __shfl_sync(0xffffffffu, l1.im, 2 * h, 4)};
        coef[h] = cplx{__shfl_sync(0xffffffffu, cf.re, 2 * h, 4), __shfl_sync(0xffffffffu, cf.im, 2 * h, 4)};
        l16[h] = cplx{__shfl_sync(0xffffffffu, t.re, 2 * h, 4), __shfl_sync(0xffffffffu, t.im, 2 * h, 4)};
      }
    }
    TS(wg, 24);

#pragma unroll
    for (int kb = 0; kb < 8; kb++) {
      const int slot = kb % NSLOT;
      TS2(1, kb);
      mbar_wait(sb + OFF_XFULL + 8 * kb, 0);
      if (kb == 0) TS(wg, 18);
      mbar_wait(fullb + 8 * slot, (kb / NSLOT) & 1);
      TS2(2, kb);
      if (kb == 0) TS(wg, 1);
      wg_fence();
      const uint32_t dxa = dxw + ((kb + xrot) & 7) * 1024;
#pragma unroll
      for (int kk = 0; kk < 4; kk++) {
        wgmma_n64_ss<0, 0, DH128, DH128>(ure, dring, slot * 16384 + kk * 32, dxa, kk * 32, (kb | kk) != 0);
        wgmma_n64_ss<0, 0, DH128, DH128>(uim, dring, slot * 16384 + 8192 + kk * 32, dxa, kk * 32, (kb | kk) != 0);
      }
      wg_commit();
      if (kb > 0) { wg_wait<1>(); release((kb - 1) % NSLOT); }
      if (kb == 0) {
#pragma unroll
        for (int h = 0; h < 2; h++) {
          pin(l16[h].re); pin(l16[h].im);
          l32[h] = cmul(l16[h], l16[h]);
          const cplx a = (q & 1) ? l16[h] : cplx{1.f, 0.f}, c = (q & 2) ? l32[h] : cplx{1.f, 0.f};
          lq[h] = cmul(cmul(a, c), coef[h]);
          pin(lq[h].re); pin(lq[h].im);
        }
      } else {
#pragma unroll
        for (int j = (kb - 1) * 4; j < kb * 4; j++) {
          pin(bv[j]);
          float* d = j < 12 ? aa + 4 * j : ab + 4 * (j - 12);
          d[0] = d[2] = bf_lo(bv[j]); d[1] = d[3] = bf_hi(bv[j]);
          pin(d[0]); pin(d[1]); pin(d[2]); pin(d[3]);
        }
      }
    }
    TS(wg, 2);
#pragma unroll
    for (int kb = 0; kb < 8; kb++) {
      const int u = 8 + kb, slot = u % NSLOT;
      TS2(1, u);
      mbar_wait(fullb + 8 * slot, (u / NSLOT) & 1);
      TS2(2, u);
      wg_fence();
      const uint32_t dxa = dxw + ((kb + xrot) & 7) * 1024;
#pragma unroll
      for (int kk = 0; kk < 4; kk++)
        wgmma_n96_ss<0, 1, DH128, DH64>(aa, dxa, kk * 32, dring, slot * 16384 + (kk >> 1) * 6144 + (kk & 1) * 1024 + lbo(2048), 1);
      wg_commit();
      wg_wait<1>();
      release((u - 1) % NSLOT);
      if (kb == 0) {
        reg_fence(ure); reg_fence(uim);
#pragma unroll
        for (int h = 0; h < 2; h++) e[h] = cplx{ure[2 * h], uim[2 * h]};
      }
      if (kb < 3) {
#pragma unroll
        for (int t = 1 + 5 * kb; t < 6 + 5 * kb; t++)
#pragma unroll
          for (int h = 0; h < 2; h++) { const int i = 4 * (t >> 1) + 2 * h + (t & 1); e[h] = cfma(lam[h], e[h], cplx{ure[i], uim[i]}); }
#pragma unroll
        for (int h = 0; h < 2; h++) { pin(e[h].re); pin(e[h].im); }
      } else if (kb == 3) {
#pragma unroll
        for (int h = 0; h < 2; h++) {
          cplx y = {__shfl_up_sync(0xffffffffu, e[h].re, 1, 4), __shfl_up_sync(0xffffffffu, e[h].im, 1, 4)};
          if (q >= 1) e[h] = cfma(l16[h], y, e[h]);
          y = cplx{__shfl_up_sync(0xffffffffu, e[h].re, 2, 4), __shfl_up_sync(0xffffffffu, e[h].im, 2, 4)};
          if (q >= 2) e[h] = cfma(l32[h], y, e[h]);
        }
        if (q == 3) {
#pragma unroll
          for (int h = 0; h < 2; h++)
            asm volatile("st.shared.v2.f32 [%0], {%1,%2};" ::"r"(sb + OFF_CARRY + wg * 512 + (w * 16 + gr + 8 * h) * 8), "f"(e[h].re), "f"(e[h].im) : "memory");
          mbar_arrive(sb + OFF_GBAR);
        }
#pragma unroll
        for (int h = 0; h < 2; h++) {
          const cplx y = {__shfl_up_sync(0xffffffffu, e[h].re, 1, 4), __shfl_up_sync(0xffffffffu, e[h].im, 1, 4)};
          pre[h] = (q >= 1) ? cmul(coef[h], y) : cplx{0.f, 0.f};
          pin(pre[h].re); pin(pre[h].im);
        }
        TS(wg, 3);
      } else {
#pragma unroll
        for (int i = (kb - 4) * 8; i < (kb - 3) * 8; i++) {
          pin(ure[i]); pin(uim[i]);
          const cplx v = cmul(coef[(i >> 1) & 1], cplx{ure[i], uim[i]});
          ure[i] = v.re; uim[i] = v.im;
          pin(ure[i]); pin(uim[i]);
        }
      }
    }
    TS(wg, 4);
    uint32_t H[56];
    cplx hst[2];
    const uint32_t dh = dxw;
    const uint32_t hst_addr = xw + (w * 16 + (lane & 15)) * 128 + (((lane >> 4) ^ (lane & 7)) << 4);
#pragma unroll
    for (int kb = 0; kb < 8; kb++) {
      const int u = 16 + kb, slot = u % NSLOT;
      TS2(1, u);
      mbar_wait(fullb + 8 * slot, (u / NSLOT) & 1);
      TS2(2, u);
      wg_fence();
#pragma unroll
      for (int kk = 0; kk < 4; kk++)
        wgmma_n128_ss<0, 1, DH128, DH128>(ab, dxw, kb * 16384 + kk * 32, dring, slot * 16384 + kk * 2048 + lbo(8192), 1);
      wg_commit();
      wg_wait<1>();
      release((u - 1) % NSLOT);
      if (kb < 3 || kb == 7) {
        const int ch = kb < 3 ? kb : 3;
#pragma unroll
        for (int i = ch * 6; i < ch * 6 + 6; i++) {
          pin(aa[2 * i]); pin(aa[2 * i + 1]);
          H[i] = pack_bf16(gelu2(aa[2 * i]), gelu2(aa[2 * i + 1]));
          pin(H[i]);
        }
      } else {
        if (kb == 3) {
          TS(wg, 5);
          mbar_wait(sb + OFF_CBAR, 0);
          TS(wg, 6);
#pragma unroll
          for (int h = 0; h < 2; h++) {
            const float2 c = lds_f2(sb + OFF_CARRY + wg * 512 + (w * 16 + gr + 8 * h) * 8);
            hst[h] = cfma(lq[h], cplx{c.x, c.y}, pre[h]);
          }
        }
        const int j0 = (kb - 3) * 2;
        uint32_t rr[4], ri[4];
#pragma unroll
        for (int jj = 0; jj < 2; jj++) {
          const int j = j0 + jj;
          const float2 g2 = lds_f2(sb + OFF_GS + (wg * 64 + j * 8 + q * 2) * 4);
#pragma unroll
          for (int h = 0; h < 2; h++) {
            const int i = 4 * j + 2 * h;
            const cplx h0 = cfma(lam[h], hst[h], cplx{ure[i], uim[i]});
            hst[h] = cfma(lam[h], h0, cplx{ure[i + 1], uim[i + 1]});
            rr[jj * 2 + h] = pack_bf16(h0.re * g2.x, hst[h].re * g2.y);
            ri[jj * 2 + h] = pack_bf16(-h0.im * g2.x, -hst[h].im * g2.y);
          }
        }
        const uint32_t a = hst_addr ^ (j0 << 4);
        asm volatile("stmatrix.sync.aligned.m8n8.x4.shared.b16 [%0], {%1,%2,%3,%4};" ::"r"(a), "r"(rr[0]), "r"(rr[1]), "r"(rr[2]), "r"(rr[3]) : "memory");
        asm volatile("stmatrix.sync.aligned.m8n8.x4.shared.b16 [%0], {%1,%2,%3,%4};" ::"r"(a + 16384), "r"(ri[0]), "r"(ri[1]), "r"(ri[2]), "r"(ri[3]) : "memory");
        if (kb == 6) asm volatile("fence.proxy.async.shared::cta;" ::: "memory");
      }
    }
    bar_sync(1 + wg, 128);
    TS(wg, 7);

    uint4* const psend = g_part + (size_t)m * (8 * 7 * 1024) + warp * 128;
    const uint4* const precv = g_part + (size_t)(m * 8 + s) * (7 * 1024) + warp * 128 + lane;
    const uint32_t stg = sb + OFF_X + 5 * 16384 + warp * 2048;
    const uint32_t dx0 = ((sb + OFF_X) & 0x3FFFF) >> 4;
    float o[32], rho[2];
    uint32_t r0[16], r1[16], sum[16], tag;
    auto send = [&](int p) {
#pragma unroll
      for (int i = 0; i < 4; i++) {
        uint32_t t0;
        asm("lop3.b32 %0, %1, 1, %2, 0xb8;" : "=r"(t0) : "r"(pack_bf16(o[8 * i], o[8 * i + 1])), "r"(tag));
        asm volatile("st.shared.v4.u32 [%0], {%1,%2,%3,%4};" ::"r"(stg + lane * 16 + (p & 1) * 16384 + i * 512), "r"(t0), "r"(pack_bf16(o[8 * i + 2], o[8 * i + 3])),
                     "r"(pack_bf16(o[8 * i + 4], o[8 * i + 5])), "r"(pack_bf16(o[8 * i + 6], o[8 * i + 7])) : "memory");
      }
      asm volatile("fence.proxy.async.shared::cta;" ::: "memory");
      __syncwarp();
      if (elect_one()) {
        asm volatile("cp.async.bulk.global.shared::cta.bulk_group [%0], [%1], 2048;" ::"l"(psend + (((s + 1 + p) & 7) * 7 + p) * 1024), "r"(stg + (p & 1) * 16384) : "memory");
        asm volatile("cp.async.bulk.commit_group;" ::: "memory");
        asm volatile("cp.async.bulk.wait_group.read 1;" ::: "memory");
      }
    };
    auto recv_issue = [&](uint32_t (&r)[16], int p) {
#pragma unroll
      for (int i = 0; i < 4; i++) ld_b128(precv + p * 1024 + i * 32, r[4 * i], r[4 * i + 1], r[4 * i + 2], r[4 * i + 3]);
    };
    auto stale = [&](uint32_t (&r)[16]) {
      uint32_t t0, t1;
      asm("lop3.b32 %0, %1, %2, %3, 0x7e;" : "=r"(t0) : "r"(r[0]), "r"(r[4]), "r"(tag));
      asm("lop3.b32 %0, %1, %2, %3, 0x7e;" : "=r"(t1) : "r"(r[8]), "r"(r[12]), "r"(tag));
      return __any_sync(0xffffffffu, (t0 | t1) & 1);
    };
    auto recv_check = [&](uint32_t (&r)[16], int p) {
      if (__builtin_expect(stale(r), 0)) {
        int tries = 0;
#pragma unroll 1
        do { recv_issue(r, p); } while (stale(r) && ++tries < 200000);
      }
    };
    auto gelu_b = [&](int i0, int i1) {
#pragma unroll
      for (int i = i0; i < i1; i++) {
        pin(ab[2 * i]); pin(ab[2 * i + 1]);
        H[24 + i] = pack_bf16(gelu2(ab[2 * i]), gelu2(ab[2 * i + 1]));
        pin(H[24 + i]);
      }
    };
    auto mma = [&](uint32_t wo, int k0, int k1) {
      wg_fence();
#pragma unroll
      for (int k = k0; k < k1; k++) {
        if (k < 8) wgmma_n64_ss<1, 0, DH128, DH128>(o, dh, (k >> 2) * 16384 + (k & 3) * 2048, dx0, wo + (k >> 2) * 8192 + (k & 3) * 32, k != 0);
        else { const int kk = k - 8; wgmma_n64_rs<1, DH128>(o, H[4 * kk], H[4 * kk + 1], H[4 * kk + 2], H[4 * kk + 3], dx0, wo + 16384 + (kk / 7) * 16384 + (kk % 7) * 2048, 1); }
      }
      wg_commit();
    };
#pragma unroll
    for (int p = 0; p < 8; p++) {
      const uint32_t wo = (p % 3) == 1 ? 2 * 16384 : OFF_RING + (p % 3) * 24576;
      mbar_wait(sb + OFF_XFULL + 8 * p, 1);
      if (p == 0) {
        mma(wo, 0, 4);
        wg_wait<1>(); release(5);
        gelu_b(0, 6);
        mma(wo, 4, 8);
        gelu_b(6, 12);
        mma(wo, 8, 12);
        gelu_b(12, 18);
        mma(wo, 12, 15);
        gelu_b(18, 24);
        mma(wo, 15, 18);
        gelu_b(24, 32);
        if (wg == 1) bar_sync(4, 256);
        mma(wo, 18, 22);
      } else {
        if (p == 5) TS(wg, 19);
        bar_sync(3 + wg, 256);
        if (p == 5) TS(wg, 20);
        mma(wo, 0, 22);
      }
      if (p < 7 || wg == 0) bar_arrive(4 - wg, 256);
      if (p == 5) TS(wg, 21);
      if (p == 7) recv_issue(r1, 6);
      tag = lds_u(sb + OFF_EPOCH);
      if (p == 1) {
#pragma unroll
        for (int h = 0; h < 2; h++) {
          rho[h] = lds_f(sb + OFF_GS + (wg * 64 + w * 16 + gr + 8 * h) * 4);
          const uint32_t rh = pack_bf16(0.25f * rho[h], 0.25f * rho[h]);
#pragma unroll
          for (int j = 0; j < 8; j++) {
            const uint32_t xd = bf2_mul(lds_u(xw + 7 * 16384 + (w * 16 + gr + 8 * h) * 128 + ((j ^ gr) << 4) + q * 4), r0[j]);
            const uint32_t t = bf2_fma(xd, rh, r0[8 + j]);
            sum[2 * j + h] = bf2_add(t, t);
          }
        }
      } else if (p >= 2) {
        recv_check(r0, p - 2);
#pragma unroll
        for (int i = 0; i < 16; i++) sum[i] = bf2_add(sum[i], r0[i]);
      }
      if (p == 5) TS(wg, 22);
      wg_wait<0>();
      if (p < 5) release(p);
      reg_fence(o);
      if (p == 5) TS(wg, 23);
      if (p < 7) send(p);
      if (p == 0) {
#pragma unroll
        for (int j = 0; j < 8; j++) {
          r0[j] = __ldg(reinterpret_cast<const uint32_t*>(dskip + s * 64 + j * 8) + q);
          r0[8 + j] = __ldg(reinterpret_cast<const uint32_t*>(b2 + s * 64 + j * 8) + q);
        }
      } else if (p < 7) {
        recv_issue(r0, p - 1);
      }
      TS(wg, 8 + p);
    }
    {
      float fs[2];
#pragma unroll
      for (int h = 0; h < 2; h++) fs[h] = __fdividef(2.f, 4.f + rho[h]);
#pragma unroll
      for (int i = 0; i < 16; i++) { o[2 * i] = (o[2 * i] + bf_lo(sum[i])) * fs[i & 1]; o[2 * i + 1] = (o[2 * i + 1] + bf_hi(sum[i])) * fs[i & 1]; }
      reg_fence(o);
      tag = lds_u(sb + OFF_EPOCH);
      recv_check(r1, 6);
      TS(wg, 16);
      float* op = out + (size_t)(m * 128 + wg * 64 + (gr >> 1) * 16 + w * 4 + (gr & 1)) * DM + s * 64 + q * 2;
#pragma unroll
      for (int i = 0; i < 16; i++)
        *reinterpret_cast<float2*>(op + (i & 1) * 2 * DM + (i >> 1) * 8) =
            make_float2(fmaf(bf_lo(r1[i]), fs[i & 1], o[2 * i]), fmaf(bf_hi(r1[i]), fs[i & 1], o[2 * i + 1]));
      if (threadIdx.x == 128) g_epoch[b] = tag;
      if (elect_one()) asm volatile("cp.async.bulk.wait_group.read 0;" ::: "memory");
      TS(wg, 17); TG(wg); TDUMP();
    }
  }
}

typedef CUresult (*EncFn)(CUtensorMap*, CUtensorMapDataType, cuuint32_t, void*, const cuuint64_t*, const cuuint64_t*, const cuuint32_t*,
                          const cuuint32_t*, CUtensorMapInterleave, CUtensorMapSwizzle, CUtensorMapL2promotion, CUtensorMapFloatOOBfill);

void encode(EncFn f, CUtensorMap* mp, const void* p, int rank, const cuuint64_t* dims, const cuuint64_t* strides, const cuuint32_t* box, CUtensorMapSwizzle sw) {
  cuuint32_t es[5] = {1, 1, 1, 1, 1};
  f(mp, CU_TENSOR_MAP_DATA_TYPE_BFLOAT16, rank, const_cast<void*>(p), dims, strides, box, es, CU_TENSOR_MAP_INTERLEAVE_NONE, sw,
    CU_TENSOR_MAP_L2_PROMOTION_L2_128B, CU_TENSOR_MAP_FLOAT_OOB_FILL_NONE);
}

}

extern "C" void kernel_launch(void* const* d_in, const int* in_sizes, int n_in, void* d_out, int out_size) {
  typedef const __nv_bfloat16* bp;
  bp x = (bp)d_in[0], lre = (bp)d_in[1], lim = (bp)d_in[2], bre = (bp)d_in[3], bim = (bp)d_in[4], cre = (bp)d_in[5], cim = (bp)d_in[6],
     ldt = (bp)d_in[7], dsk = (bp)d_in[8], w1 = (bp)d_in[10], b1 = (bp)d_in[11], w2 = (bp)d_in[12], b2 = (bp)d_in[13], gw = (bp)d_in[14];
  static EncFn enc = nullptr;
  if (!enc) {
    void* f = nullptr;
    cudaDriverEntryPointQueryResult qr;
    cudaGetDriverEntryPoint("cuTensorMapEncodeTiled", &f, cudaEnableDefault, &qr);
    enc = (EncFn)f;
    cudaFuncSetAttribute(fused_kernel, cudaFuncAttributeMaxDynamicSharedMemorySize, SMEM_BYTES);
  }
  Maps maps;
  {
    cuuint64_t d[5] = {DM, 2, 4, 8, SEQ / 64}, st[4] = {DM * 2, 16 * DM * 2, 2 * DM * 2, 64 * DM * 2};
    cuuint32_t bx[5] = {64, 2, 4, 8, 2};
    encode(enc, &maps.x, x, 5, d, st, bx, CU_TENSOR_MAP_SWIZZLE_128B);
  }
  {
    cuuint64_t d[2] = {DM, DM}, st[1] = {DM * 2};
    cuuint32_t bx[2] = {64, 64};
    encode(enc, &maps.bre, bre, 2, d, st, bx, CU_TENSOR_MAP_SWIZZLE_128B);
    encode(enc, &maps.bim, bim, 2, d, st, bx, CU_TENSOR_MAP_SWIZZLE_128B);
    encode(enc, &maps.cre, cre, 2, d, st, bx, CU_TENSOR_MAP_SWIZZLE_128B);
    encode(enc, &maps.cim, cim, 2, d, st, bx, CU_TENSOR_MAP_SWIZZLE_128B);
  }
  {
    cuuint64_t d[2] = {FF, DM}, st[1] = {FF * 2};
    cuuint32_t bx[2] = {64, 64};
    encode(enc, &maps.w1a, w1, 2, d, st, bx, CU_TENSOR_MAP_SWIZZLE_128B);
    cuuint64_t d3[3] = {32, DM, FF / 32}, st3[2] = {FF * 2, 64};
    cuuint32_t bx3[3] = {32, 32, 3};
    encode(enc, &maps.w1b, w1, 3, d3, st3, bx3, CU_TENSOR_MAP_SWIZZLE_64B);
  }
  {
    cuuint64_t d[2] = {DM, FF}, st[1] = {DM * 2};
    cuuint32_t bx[2] = {64, 56};
    encode(enc, &maps.w2, w2, 2, d, st, bx, CU_TENSOR_MAP_SWIZZLE_128B);
  }
  fused_kernel<<<128, 384, SMEM_BYTES>>>(maps, lre, lim, ldt, dsk, b1, b2, gw, w1, w2, cre, cim, (float*)d_out);
}
```

```cpp
#include <cuda_runtime.h>
#include <cuda_bf16.h>
#include <cuda.h>
#include <stdint.h>

#define PF 2
#define SEND_TMA 1
#define PFK 2
namespace {

constexpr int SEQ = 2048, DM = 512, FF = 1792;
constexpr int NSLOT = 6;
constexpr uint32_t OFF_X = 0, OFF_RING = 131072, OFF_MISC = 229376;
constexpr uint32_t OFF_XFULL = OFF_MISC, OFF_FULL = OFF_XFULL + 64, OFF_EMPTY = OFF_FULL + 48, OFF_GBAR = OFF_EMPTY + 48,
                   OFF_CBAR = OFF_GBAR + 8, OFF_EPOCH = OFF_CBAR + 8;
constexpr uint32_t OFF_GS = OFF_MISC + 256;
constexpr uint32_t OFF_CARRY = OFF_GS + 512;
constexpr uint32_t OFF_DB = OFF_CARRY + 1024;
constexpr uint32_t OFF_DBG = OFF_DB + 256;
constexpr uint32_t SMEM_BYTES = OFF_DBG + 768;
static_assert(SMEM_BYTES <= 232448, "smem");

struct Maps { CUtensorMap x, bre, bim, w1a, w1b, w2, cre, cim; };

__device__ uint4 g_part[16 * 8 * 7 * 1024];
__device__ float2 g_end[8 * 16 * 64];
__device__ unsigned g_gate[SEQ];
__device__ unsigned g_epoch[128];
#define TG(role) do {} while (0)
#define TS2(role, i) do {} while (0)
#define TS(role, i) do {} while (0)
#define TDUMP() do {} while (0)

__device__ __forceinline__ void mbar_init(uint32_t bar, uint32_t cnt) { asm volatile("mbarrier.init.shared::cta.b64 [%0], %1;" ::"r"(bar), "r"(cnt)); }
__device__ __forceinline__ void mbar_expect_tx(uint32_t bar, uint32_t bytes) { asm volatile("mbarrier.arrive.expect_tx.shared::cta.b64 _, [%0], %1;" ::"r"(bar), "r"(bytes) : "memory"); }
__device__ __forceinline__ void mbar_arrive(uint32_t bar) { asm volatile("mbarrier.arrive.shared::cta.b64 _, [%0];" ::"r"(bar) : "memory"); }
__device__ __forceinline__ void mbar_arrive_cl(uint32_t cbar) { asm volatile("mbarrier.arrive.shared::cluster.b64 _, [%0];" ::"r"(cbar) : "memory"); }
__device__ __forceinline__ void mbar_wait(uint32_t bar, uint32_t parity) {
  asm volatile(
      "{\n.reg .pred p;\n.reg .u32 c;\n"
      "mbarrier.try_wait.parity.shared::cta.b64 p, [%0], %1;\n"
      "@p bra.uni LAB_DONE;\n"
      "mov.u32 c, 0;\n"
      "LAB_WAIT:\n"
      "mbarrier.try_wait.parity.shared::cta.b64 p, [%0], %1;\n"
      "@p bra.uni LAB_DONE;\n"
      "add.u32 c, c, 1;\nsetp.lt.u32 p, c, 200000;\n@p bra.uni LAB_WAIT;\n"
      "LAB_DONE:\n}" ::"r"(bar), "r"(parity) : "memory");
}
__device__ __forceinline__ void tma2d(uint32_t dst, const CUtensorMap* m, int c0, int c1, uint32_t bar) {
  asm volatile("cp.async.bulk.tensor.2d.shared::cluster.global.mbarrier::complete_tx::bytes [%0], [%1, {%3,%4}], [%2];"
               ::"r"(dst), "l"(m), "r"(bar), "r"(c0), "r"(c1) : "memory");
}
__device__ __forceinline__ void tma2d_mc(uint32_t dst, const CUtensorMap* m, int c0, int c1, uint32_t bar) {
  asm volatile("cp.async.bulk.tensor.2d.shared::cluster.global.mbarrier::complete_tx::bytes.multicast::cluster [%0], [%1, {%3,%4}], [%2], %5;"
               ::"r"(dst), "l"(m), "r"(bar), "r"(c0), "r"(c1), "h"((uint16_t)3) : "memory");
}
__device__ __forceinline__ void tma3d_mc(uint32_t dst, const CUtensorMap* m, int c0, int c1, int c2, uint32_t bar) {
  asm volatile("cp.async.bulk.tensor.3d.shared::cluster.global.mbarrier::complete_tx::bytes.multicast::cluster [%0], [%1, {%3,%4,%5}], [%2], %6;"
               ::"r"(dst), "l"(m), "r"(bar), "r"(c0), "r"(c1), "r"(c2), "h"((uint16_t)3) : "memory");
}
__device__ __forceinline__ void tma5d(uint32_t dst, const CUtensorMap* m, int c0, int c4, uint32_t bar) {
  asm volatile("cp.async.bulk.tensor.5d.shared::cluster.global.mbarrier::complete_tx::bytes [%0], [%1, {%3,%5,%5,%5,%4}], [%2];"
               ::"r"(dst), "l"(m), "r"(bar), "r"(c0), "r"(c4), "r"(0) : "memory");
}
__device__ __forceinline__ void l2_prefetch(const void* p, uint32_t bytes) { asm volatile("cp.async.bulk.prefetch.L2.global [%0], %1;" ::"l"(p), "r"(bytes) : "memory"); }
__device__ __forceinline__ bool elect_one() {
  uint32_t pred;
  asm volatile("{.reg .pred P; elect.sync _|P, 0xffffffff; selp.u32 %0, 1, 0, P;}" : "=r"(pred));
  return pred != 0;
}
__device__ __forceinline__ void wg_fence() { asm volatile("wgmma.fence.sync.aligned;" ::: "memory"); }
__device__ __forceinline__ void wg_commit() { asm volatile("wgmma.commit_group.sync.aligned;" ::: "memory"); }
template <int N> __device__ __forceinline__ void wg_wait() { asm volatile("wgmma.wait_group.sync.aligned %0;" ::"n"(N) : "memory"); }
template <int N> __device__ __forceinline__ void reg_fence(float (&d)[N]) {
#pragma unroll
  for (int i = 0; i < N; i++) asm volatile("" : "+f"(d[i])::"memory");
}
__device__ __forceinline__ void bar_sync(int id, int n) { asm volatile("bar.sync %0, %1;" ::"r"(id), "r"(n) : "memory"); }
__device__ __forceinline__ void bar_arrive(int id, int n) { asm volatile("bar.arrive %0, %1;" ::"r"(id), "r"(n) : "memory"); }
constexpr uint32_t DH128 = (1024 >> 4) | (1u << 30), DH64 = (512 >> 4) | (2u << 30);
__host__ __device__ constexpr uint32_t lbo(uint32_t bytes) { return (bytes >> 4) << 20; }
__device__ __forceinline__ uint32_t pack_bf16(float lo, float hi) { uint32_t r; asm("cvt.rn.bf16x2.f32 %0, %1, %2;" : "=r"(r) : "f"(hi), "f"(lo)); return r; }
__device__ __forceinline__ float bf_lo(uint32_t v) { return __uint_as_float(v << 16); }
__device__ __forceinline__ float bf_hi(uint32_t v) { return __uint_as_float(v & 0xffff0000u); }
__device__ __forceinline__ float bf_ld(const __nv_bfloat16* p) { return __bfloat162float(__ldg(p)); }
__device__ __forceinline__ float2 lds_f2(uint32_t a) { float2 v; asm volatile("ld.shared.v2.f32 {%0,%1}, [%2];" : "=f"(v.x), "=f"(v.y) : "r"(a)); return v; }
__device__ __forceinline__ float lds_f(uint32_t a) { float v; asm volatile("ld.shared.f32 %0, [%1];" : "=f"(v) : "r"(a)); return v; }
__device__ __forceinline__ uint32_t lds_u(uint32_t a) { uint32_t v; asm volatile("ld.shared.u32 %0, [%1];" : "=r"(v) : "r"(a)); return v; }
__device__ __forceinline__ uint4 lds_u4(uint32_t a) { uint4 v; asm volatile("ld.shared.v4.u32 {%0,%1,%2,%3}, [%4];" : "=r"(v.x), "=r"(v.y), "=r"(v.z), "=r"(v.w) : "r"(a)); return v; }
__device__ __forceinline__ void st_b128(uint4* p, uint32_t a, uint32_t b, uint32_t c, uint32_t d) {
  asm volatile("{.reg .b64 l, h; .reg .b128 v; mov.b64 l, {%1,%2}; mov.b64 h, {%3,%4}; mov.b128 v, {l,h}; st.relaxed.gpu.global.b128 [%0], v;}"
               ::"l"(p), "r"(a), "r"(b), "r"(c), "r"(d) : "memory");
}
__device__ __forceinline__ void ld_b128(const uint4* p, uint32_t& a, uint32_t& b, uint32_t& c, uint32_t& d) {
  asm volatile("{.reg .b64 l, h; .reg .b128 v; ld.relaxed.gpu.global.b128 v, [%4]; mov.b128 {l,h}, v; mov.b64 {%0,%1}, l; mov.b64 {%2,%3}, h;}"
               : "=r"(a), "=r"(b), "=r"(c), "=r"(d) : "l"(p) : "memory");
}
__device__ __forceinline__ float tanh_fast(float x) { float y; asm("tanh.approx.f32 %0, %1;" : "=f"(y) : "f"(x)); return y; }
__device__ __forceinline__ float gelu2(float v) {
  float p = fmaf(v * v, 0.0356774081363f, 0.7978845608029f);
  return fmaf(v, tanh_fast(v * p), v);
}
__device__ __forceinline__ uint32_t bf2_mul(uint32_t a, uint32_t b) { uint32_t r; asm("mul.rn.bf16x2 %0, %1, %2;" : "=r"(r) : "r"(a), "r"(b)); return r; }
__device__ __forceinline__ uint32_t bf2_add(uint32_t a, uint32_t b) { uint32_t r; asm("add.rn.bf16x2 %0, %1, %2;" : "=r"(r) : "r"(a), "r"(b)); return r; }
__device__ __forceinline__ uint32_t bf2_fma(uint32_t a, uint32_t b, uint32_t c) { uint32_t r; asm("fma.rn.bf16x2 %0, %1, %2, %3;" : "=r"(r) : "r"(a), "r"(b), "r"(c)); return r; }
__device__ __forceinline__ void pin(float& a) { asm volatile("" : "+f"(a)::"memory"); }
__device__ __forceinline__ void pin(uint32_t& a) { asm volatile("" : "+r"(a)::"memory"); }
struct cplx { float re, im; };
__device__ __forceinline__ cplx cmul(cplx a, cplx b) { return {fmaf(a.re, b.re, -a.im * b.im), fmaf(a.re, b.im, a.im * b.re)}; }
__device__ __forceinline__ cplx cfma(cplx a, cplx b, cplx c) {
  return {fmaf(a.re, b.re, fmaf(-a.im, b.im, c.re)), fmaf(a.re, b.im, fmaf(a.im, b.re, c.im))};
}
__device__ __forceinline__ cplx make_lam(float lre, float lim, float ldt) {
  float dt = __bfloat162float(__float2bfloat16_rn(expf(ldt)));
  float mag = expf(dt * lre), sn, cs;
  sincospif(dt * lim * 0.31830988618379067f, &sn, &cs);
  return {mag * cs, mag * sn};
}

template<int TA,int TB,uint32_t AH,uint32_t BH> __device__ __forceinline__ void wgmma_n64_ss(float (&d)[32], uint32_t al, uint32_t ao, uint32_t bl, uint32_t bo, int scale_d){
  asm volatile("{.reg .pred p; .reg .b32 t, v; .reg .b64 da, db; setp.ne.b32 p, %36, 0; add.u32 t, %32, %33; mov.b64 da, {t, %39}; add.u32 v, %34, %35; mov.b64 db, {v, %40};\n"
   "wgmma.mma_async.sync.aligned.m64n64k16.f32.bf16.bf16 {%0,%1,%2,%3,%4,%5,%6,%7,%8,%9,%10,%11,%12,%13,%14,%15,%16,%17,%18,%19,%20,%21,%22,%23,%24,%25,%26,%27,%28,%29,%30,%31}, da, db, p, 1, 1, %37, %38;}"
   : "+f"(d[0]),"+f"(d[1]),"+f"(d[2]),"+f"(d[3]),"+f"(d[4]),"+f"(d[5]),"+f"(d[6]),"+f"(d[7]),"+f"(d[8]),"+f"(d[9]),"+f"(d[10]),"+f"(d[11]),"+f"(d[12]),"+f"(d[13]),"+f"(d[14]),"+f"(d[15]),"+f"(d[16]),"+f"(d[17]),"+f"(d[18]),"+f"(d[19]),"+f"(d[20]),"+f"(d[21]),"+f"(d[22]),"+f"(d[23]),"+f"(d[24]),"+f"(d[25]),"+f"(d[26]),"+f"(d[27]),"+f"(d[28]),"+f"(d[29]),"+f"(d[30]),"+f"(d[31])
   : "r"(al),"r"(ao >> 4),"r"(bl),"r"(bo >> 4),"r"(scale_d),"n"(TA),"n"(TB),"n"(AH),"n"(BH));
}
template<int TB,uint32_t BH> __device__ __forceinline__ void wgmma_n64_rs(float (&d)[32], uint32_t a0,uint32_t a1,uint32_t a2,uint32_t a3, uint32_t bl, uint32_t bo, int scale_d){
  asm volatile("{.reg .pred p; .reg .b32 t; .reg .b64 db; setp.ne.b32 p, %38, 0; add.u32 t, %36, %37; mov.b64 db, {t, %40};\n"
   "wgmma.mma_async.sync.aligned.m64n64k16.f32.bf16.bf16 {%0,%1,%2,%3,%4,%5,%6,%7,%8,%9,%10,%11,%12,%13,%14,%15,%16,%17,%18,%19,%20,%21,%22,%23,%24,%25,%26,%27,%28,%29,%30,%31}, {%32,%33,%34,%35}, db, p, 1, 1, %39;}"
   : "+f"(d[0]),"+f"(d[1]),"+f"(d[2]),"+f"(d[3]),"+f"(d[4]),"+f"(d[5]),"+f"(d[6]),"+f"(d[7]),"+f"(d[8]),"+f"(d[9]),"+f"(d[10]),"+f"(d[11]),"+f"(d[12]),"+f"(d[13]),"+f"(d[14]),"+f"(d[15]),"+f"(d[16]),"+f"(d[17]),"+f"(d[18]),"+f"(d[19]),"+f"(d[20]),"+f"(d[21]),"+f"(d[22]),"+f"(d[23]),"+f"(d[24]),"+f"(d[25]),"+f"(d[26]),"+f"(d[27]),"+f"(d[28]),"+f"(d[29]),"+f"(d[30]),"+f"(d[31])
   : "r"(a0),"r"(a1),"r"(a2),"r"(a3),"r"(bl),"r"(bo >> 4),"r"(scale_d),"n"(TB),"n"(BH));
}
template<int TA,int TB,uint32_t AH,uint32_t BH> __device__ __forceinline__ void wgmma_n96_ss(float (&d)[48], uint32_t al, uint32_t ao, uint32_t bl, uint32_t bo, int scale_d){
  asm volatile("{.reg .pred p; .reg .b32 t, v; .reg .b64 da, db; setp.ne.b32 p, %52, 0; add.u32 t, %48, %49; mov.b64 da, {t, %55}; add.u32 v, %50, %51; mov.b64 db, {v, %56};\n"
   "wgmma.mma_async.sync.aligned.m64n96k16.f32.bf16.bf16 {%0,%1,%2,%3,%4,%5,%6,%7,%8,%9,%10,%11,%12,%13,%14,%15,%16,%17,%18,%19,%20,%21,%22,%23,%24,%25,%26,%27,%28,%29,%30,%31,%32,%33,%34,%35,%36,%37,%38,%39,%40,%41,%42,%43,%44,%45,%46,%47}, da, db, p, 1, 1, %53, %54;}"
   : "+f"(d[0]),"+f"(d[1]),"+f"(d[2]),"+f"(d[3]),"+f"(d[4]),"+f"(d[5]),"+f"(d[6]),"+f"(d[7]),"+f"(d[8]),"+f"(d[9]),"+f"(d[10]),"+f"(d[11]),"+f"(d[12]),"+f"(d[13]),"+f"(d[14]),"+f"(d[15]),"+f"(d[16]),"+f"(d[17]),"+f"(d[18]),"+f"(d[19]),"+f"(d[20]),"+f"(d[21]),"+f"(d[22]),"+f"(d[23]),"+f"(d[24]),"+f"(d[25]),"+f"(d[26]),"+f"(d[27]),"+f"(d[28]),"+f"(d[29]),"+f"(d[30]),"+f"(d[31]),"+f"(d[32]),"+f"(d[33]),"+f"(d[34]),"+f"(d[35]),"+f"(d[36]),"+f"(d[37]),"+f"(d[38]),"+f"(d[39]),"+f"(d[40]),"+f"(d[41]),"+f"(d[42]),"+f"(d[43]),"+f"(d[44]),"+f"(d[45]),"+f"(d[46]),"+f"(d[47])
   : "r"(al),"r"(ao >> 4),"r"(bl),"r"(bo >> 4),"r"(scale_d),"n"(TA),"n"(TB),"n"(AH),"n"(BH));
}
template<int TA,int TB,uint32_t AH,uint32_t BH> __device__ __forceinline__ void wgmma_n128_ss(float (&d)[64], uint32_t al, uint32_t ao, uint32_t bl, uint32_t bo, int scale_d){
  asm volatile("{.reg .pred p; .reg .b32 t, v; .reg .b64 da, db; setp.ne.b32 p, %68, 0; add.u32 t, %64, %65; mov.b64 da, {t, %71}; add.u32 v, %66, %67; mov.b64 db, {v, %72};\n"
   "wgmma.mma_async.sync.aligned.m64n128k16.f32.bf16.bf16 {%0,%1,%2,%3,%4,%5,%6,%7,%8,%9,%10,%11,%12,%13,%14,%15,%16,%17,%18,%19,%20,%21,%22,%23,%24,%25,%26,%27,%28,%29,%30,%31,%32,%33,%34,%35,%36,%37,%38,%39,%40,%41,%42,%43,%44,%45,%46,%47,%48,%49,%50,%51,%52,%53,%54,%55,%56,%57,%58,%59,%60,%61,%62,%63}, da, db, p, 1, 1, %69, %70;}"
   : "+f"(d[0]),"+f"(d[1]),"+f"(d[2]),"+f"(d[3]),"+f"(d[4]),"+f"(d[5]),"+f"(d[6]),"+f"(d[7]),"+f"(d[8]),"+f"(d[9]),"+f"(d[10]),"+f"(d[11]),"+f"(d[12]),"+f"(d[13]),"+f"(d[14]),"+f"(d[15]),"+f"(d[16]),"+f"(d[17]),"+f"(d[18]),"+f"(d[19]),"+f"(d[20]),"+f"(d[21]),"+f"(d[22]),"+f"(d[23]),"+f"(d[24]),"+f"(d[25]),"+f"(d[26]),"+f"(d[27]),"+f"(d[28]),"+f"(d[29]),"+f"(d[30]),"+f"(d[31]),"+f"(d[32]),"+f"(d[33]),"+f"(d[34]),"+f"(d[35]),"+f"(d[36]),"+f"(d[37]),"+f"(d[38]),"+f"(d[39]),"+f"(d[40]),"+f"(d[41]),"+f"(d[42]),"+f"(d[43]),"+f"(d[44]),"+f"(d[45]),"+f"(d[46]),"+f"(d[47]),"+f"(d[48]),"+f"(d[49]),"+f"(d[50]),"+f"(d[51]),"+f"(d[52]),"+f"(d[53]),"+f"(d[54]),"+f"(d[55]),"+f"(d[56]),"+f"(d[57]),"+f"(d[58]),"+f"(d[59]),"+f"(d[60]),"+f"(d[61]),"+f"(d[62]),"+f"(d[63])
   : "r"(al),"r"(ao >> 4),"r"(bl),"r"(bo >> 4),"r"(scale_d),"n"(TA),"n"(TB),"n"(AH),"n"(BH));
}

__global__ void __cluster_dims__(2, 1, 1) __launch_bounds__(384, 1)
fused_kernel(const __grid_constant__ Maps maps, const __nv_bfloat16* __restrict__ lam_re,
             const __nv_bfloat16* __restrict__ lam_im, const __nv_bfloat16* __restrict__ log_dt, const __nv_bfloat16* __restrict__ dskip,
             const __nv_bfloat16* __restrict__ b1, const __nv_bfloat16* __restrict__ b2, const __nv_bfloat16* __restrict__ gate_w,
             const __nv_bfloat16* __restrict__ pf_w1, const __nv_bfloat16* __restrict__ pf_w2, const __nv_bfloat16* __restrict__ pf_cre,
             const __nv_bfloat16* __restrict__ pf_cim, float* __restrict__ out) {
  extern __shared__ __align__(1024) unsigned char smem_raw[];
  const uint32_t sb = (uint32_t)__cvta_generic_to_shared(smem_raw);
  const int b = blockIdx.x;
  const int rank = b & 1, s = (b >> 1) & 7, m = ((b >> 4) << 1) | rank;
  const int warp = __shfl_sync(0xffffffffu, (int)(threadIdx.x >> 5), 0);
  const int lane = threadIdx.x & 31;
  const int xrot = 7 - s;

  if (warp == 8) {
    if (elect_one()) {
      TS(2, 0);
      mbar_init(sb + OFF_XFULL, 1); mbar_init(sb + OFF_FULL, 1); mbar_init(sb + OFF_XFULL + 8, 1);
      asm volatile("fence.mbarrier_init.release.cluster;" ::: "memory");
      asm volatile("fence.proxy.async.shared::cta;" ::: "memory");
      mbar_expect_tx(sb + OFF_XFULL, 16384);
      tma5d(sb + OFF_X + xrot * 16384, &maps.x, 0, 2 * m, sb + OFF_XFULL);
      TS(2, 3);
      mbar_expect_tx(sb + OFF_FULL, 16384);
      tma2d(sb + OFF_RING, &maps.bre, 0, s * 64, sb + OFF_FULL);
      tma2d(sb + OFF_RING + 8192, &maps.bim, 0, s * 64, sb + OFF_FULL);
      mbar_expect_tx(sb + OFF_XFULL + 8, 16384);
      tma5d(sb + OFF_X + ((xrot + 1) & 7) * 16384, &maps.x, 64, 2 * m, sb + OFF_XFULL + 8);
      TS(2, 4);
    }
  } else if (warp < 6) {
    if (elect_one()) {
      mbar_init(sb + OFF_XFULL + 16 + 8 * warp, 1); mbar_init(sb + OFF_EMPTY + 8 * warp, 16);
      if (warp) mbar_init(sb + OFF_FULL + 8 * warp, 1);
      asm volatile("fence.mbarrier_init.release.cluster;" ::: "memory");
    }
  } else if (warp < 8) {
    if (elect_one()) {
      mbar_init(sb + OFF_GBAR + 8 * (warp - 6), warp == 6 ? 64 : 96);
      asm volatile("fence.mbarrier_init.release.cluster;" ::: "memory");
    }
  }
  __syncwarp();
  asm volatile("barrier.cluster.arrive.relaxed.aligned;" ::: "memory");

  if (warp >= 8) {
    asm volatile("setmaxnreg.dec.sync.aligned.u32 56;");
    if (warp == 8) {
      asm volatile("barrier.cluster.wait.aligned;" ::: "memory");
      if (elect_one()) {
        TS(2, 1);
        const CUtensorMap* mb = rank ? &maps.bim : &maps.bre;
        const CUtensorMap* mc = rank ? &maps.cim : &maps.cre;
        int slot = 1; uint32_t ph = 1;
#pragma unroll 1
        for (int u = 1; u < 27; u++) {
          const uint32_t fb = sb + OFF_FULL + 8 * slot, dst = sb + OFF_RING + slot * 16384;
          if (u >= NSLOT) mbar_wait(sb + OFF_EMPTY + 8 * slot, ph);
          TS2(0, u);
          if (u < 8) {
            mbar_expect_tx(fb, 16384);
            tma2d_mc(dst + rank * 8192, mb, u * 64, s * 64, fb);
            if (u < 6) {
              mbar_expect_tx(sb + OFF_XFULL + 8 * (u + 1), 16384);
              tma5d(sb + OFF_X + ((u + 1 + xrot) & 7) * 16384, &maps.x, (u + 1) * 64, 2 * m, sb + OFF_XFULL + 8 * (u + 1));
              if (u == 5) {
                mbar_expect_tx(sb + OFF_XFULL + 56, 16384);
                tma5d(sb + OFF_X + ((7 + xrot) & 7) * 16384, &maps.x, 7 * 64, 2 * m, sb + OFF_XFULL + 56);
              }
            }
          } else if (u < 16) {
            mbar_expect_tx(fb, 12288);
            tma3d_mc(dst + rank * 6144, &maps.w1b, 0, (u - 8) * 64 + rank * 32, s * 7, fb);
          } else if (u < 24) {
            mbar_expect_tx(fb, 16384);
            tma2d_mc(dst + rank * 8192, &maps.w1a, s * 224 + 96 + rank * 64, ((u - 15 + s) & 7) * 64, fb);
          } else if (u == 24) {
            mbar_expect_tx(fb, 16384);
            tma2d_mc(dst + rank * 8192, mc, s * 64, ((s + 1) & 7) * 64, fb);
          } else {
            mbar_expect_tx(fb, 14336);
            tma2d_mc(dst + rank * 7168, &maps.w2, ((s + 1) & 7) * 64, s * 224 + (u - 25) * 112 + rank * 56, fb);
          }
          if (++slot == NSLOT) { slot = 0; ph ^= 1; }
        }
#pragma unroll 1
        for (int p = 1; p < 8; p++) {
          const int piece = (s + 1 + p) & 7, grp = p % 3;
          const uint32_t fb = sb + OFF_XFULL + 8 * p, dst = grp == 1 ? sb + OFF_X + 2 * 16384 : sb + OFF_RING + grp * 24576;
          if (p >= 3) mbar_wait(sb + OFF_EMPTY + 8 * (p - 3), 0);
          else if (p == 2) mbar_wait(sb + OFF_EMPTY + 40, 1);
          TS2(0, 32 + p);
          mbar_expect_tx(fb, 45056);
          tma2d_mc(dst + rank * 8192, mc, s * 64, piece * 64, fb);
          tma2d_mc(dst + 16384 + rank * 7168, &maps.w2, piece * 64, s * 224 + rank * 56, fb);
          tma2d_mc(dst + 32768 + rank * 7168, &maps.w2, piece * 64, s * 224 + 112 + rank * 56, fb);
        }
        TS(2, 2);
      }
    } else if (warp == 11) {
      if (lane == 0) TG(2);
      const uint32_t dk = __ldg(reinterpret_cast<const uint32_t*>(dskip + s * 64) + lane), bb = __ldg(reinterpret_cast<const uint32_t*>(b2 + s * 64) + lane);
      asm volatile("st.shared.v2.u32 [%0], {%1,%2};" ::"r"(sb + OFF_DB + lane * 8), "r"(dk), "r"(bb) : "memory");
      asm volatile("barrier.cluster.wait.aligned;" ::: "memory");
      mbar_arrive(sb + OFF_CBAR);
      if ((PF & 2) && elect_one()) {
        mbar_wait(sb + OFF_XFULL + 8 * PFK, 0);
        l2_prefetch(pf_w1 + b * 7168, 14336);
        l2_prefetch(pf_cre + b * 2048, 4096);
        l2_prefetch(pf_cim + b * 2048, 4096);
        l2_prefetch(pf_w2 + b * 7168, 14336);
      }
    } else {
      const int t = threadIdx.x - 288;
      unsigned par;
      asm volatile("ld.relaxed.gpu.global.u32 %0, [%1];" : "=r"(par) : "l"(g_epoch + b) : "memory");
      const float pr = bf_ld(lam_re + s * 64 + t), pi = bf_ld(lam_im + s * 64 + t), pd = bf_ld(log_dt + s * 64 + t);
      const uint4* gwp = reinterpret_cast<const uint4*>(gate_w) + (lane & 7);
      uint4 gw[8];
#pragma unroll
      for (int kb = 0; kb < 8; kb++) gw[kb] = __ldg(gwp + kb * 8);
      asm volatile("barrier.cluster.wait.aligned;" ::: "memory");
      if (t == 0) asm volatile("st.shared.u32 [%0], %1;" ::"r"(sb + OFF_EPOCH), "r"(par + 1) : "memory");
      par = (par + 1) & 1;
      cplx l64 = make_lam(pr, pi, pd);
#pragma unroll
      for (int i = 0; i < 6; i++) l64 = cmul(l64, l64);
      const int row = s * 16 + (t >> 5) * 8 + (lane >> 3);
      const uint32_t xr0 = sb + OFF_X + row * 128 + (((lane & 7) ^ (row & 7)) << 4), xr1 = (xr0 + 512) ^ 64;
      float z0 = 0.f, z1 = 0.f;
#pragma unroll
      for (int kb = 0; kb < 8; kb++) {
        const uint4 w = gw[kb];
        mbar_wait(sb + OFF_XFULL + 8 * kb, 0);
        const uint32_t xo = ((kb + xrot) & 7) * 16384;
        const uint4 a = lds_u4(xr0 + xo), d = lds_u4(xr1 + xo);
        const uint32_t wv[4] = {w.x, w.y, w.z, w.w}, av[4] = {a.x, a.y, a.z, a.w}, dv[4] = {d.x, d.y, d.z, d.w};
#pragma unroll
        for (int c = 0; c < 4; c++) {
          const float wl = bf_lo(wv[c]), wh = bf_hi(wv[c]);
          z0 = fmaf(bf_hi(av[c]), wh, fmaf(bf_lo(av[c]), wl, z0));
          z1 = fmaf(bf_hi(dv[c]), wh, fmaf(bf_lo(dv[c]), wl, z1));
        }
      }
      {
        float zz = (lane & 4) ? z1 : z0;
        zz += __shfl_xor_sync(0xffffffffu, (lane & 4) ? z0 : z1, 4);
        zz += __shfl_xor_sync(0xffffffffu, zz, 2);
        zz += __shfl_xor_sync(0xffffffffu, zz, 1);
        const float rho = 4.f * expf(zz > 40.f ? 40.f : zz);
        if ((lane & 3) == 0)
          asm volatile("st.relaxed.gpu.global.u32 [%0], %1;" ::"l"(g_gate + m * 128 + row + (lane & 4)), "r"((__float_as_uint(rho) & ~1u) | par) : "memory");
      }
      if (t == 0) TS(3, 0);
      mbar_wait(sb + OFF_GBAR, 0);
      const float2 e0 = lds_f2(sb + OFF_CARRY + t * 8), e1 = lds_f2(sb + OFF_CARRY + 512 + t * 8);
      float2* eb = g_end + s * 1024 + t;
      {
        const cplx e = cfma(l64, cplx{e0.x, e0.y}, cplx{e1.x, e1.y});
        const unsigned long long v = ((unsigned long long)__float_as_uint(e.im) << 32) | ((__float_as_uint(e.re) & ~1u) | par);
        asm volatile("st.relaxed.gpu.global.b64 [%0], %1;" ::"l"(eb + m * 64), "l"(v) : "memory");
      }
      if (t == 0) TS(3, 1);
      {
        const unsigned* gp = g_gate + m * 128 + t;
        unsigned g0, g1;
        int tries = 0;
#pragma unroll 1
        do {
          asm volatile("ld.relaxed.gpu.global.u32 %0, [%1];" : "=r"(g0) : "l"(gp) : "memory");
          asm volatile("ld.relaxed.gpu.global.u32 %0, [%1];" : "=r"(g1) : "l"(gp + 64) : "memory");
        } while ((((g0 ^ par) | (g1 ^ par)) & 1) && ++tries < 200000);
        asm volatile("st.shared.u32 [%0], %1;" ::"r"(sb + OFF_GS + t * 4), "r"(g0) : "memory");
        asm volatile("st.shared.u32 [%0], %1;" ::"r"(sb + OFF_GS + 256 + t * 4), "r"(g1) : "memory");
      }
      if (t == 0) TS(3, 2);
      cplx S = {0.f, 0.f};
      {
        unsigned long long v[15];
        uint32_t bad;
        int tries = 0;
        const float2* e15 = eb + (m - 15) * 64;
#pragma unroll 1
        do {
          bad = 0;
#pragma unroll
          for (int i = 0; i < 15; i++) {
            v[i] = par;
            asm volatile("{.reg .pred p; setp.ge.s32 p, %2, %3; @p ld.relaxed.gpu.global.b64 %0, [%1];}" : "+l"(v[i]) : "l"(e15 + i * 64), "r"(m), "r"(15 - i) : "memory");
          }
#pragma unroll
          for (int i = 0; i < 15; i++) bad |= (uint32_t)v[i] ^ par;
        } while ((bad & 1) && ++tries < 200000);
        const cplx l128 = cmul(l64, l64);
#pragma unroll
        for (int i = 0; i < 15; i++) S = cfma(l128, S, cplx{__uint_as_float((uint32_t)v[i] & ~1u), __uint_as_float((uint32_t)(v[i] >> 32))});
      }
      const cplx S1 = cfma(l64, S, cplx{e0.x, e0.y});
      asm volatile("st.shared.v2.f32 [%0], {%1,%2};" ::"r"(sb + OFF_CARRY + t * 8), "f"(S.re), "f"(S.im) : "memory");
      asm volatile("st.shared.v2.f32 [%0], {%1,%2};" ::"r"(sb + OFF_CARRY + 512 + t * 8), "f"(S1.re), "f"(S1.im) : "memory");
      mbar_arrive(sb + OFF_CBAR);
      if (t == 0) TS(3, 3);
    }
  } else {
    const int wg = warp >> 2, w = warp & 3, q = lane & 3, gr = lane >> 2;
    const int c0 = s * 64 + w * 16 + gr + (q & 2) * 4;
    const float pr = bf_ld(lam_re + c0), pi = bf_ld(lam_im + c0), pd = bf_ld(log_dt + c0);
    uint32_t bv[28];
#pragma unroll
    for (int j = 0; j < 28; j++) bv[j] = __ldg(reinterpret_cast<const uint32_t*>(b1 + s * 224 + j * 8) + q);
    asm volatile("setmaxnreg.inc.sync.aligned.u32 224;");
    asm volatile("barrier.cluster.wait.aligned;" ::: "memory");
    TS(wg, 0);
    uint32_t ebar;
    asm volatile("mapa.shared::cluster.u32 %0, %1, %2;" : "=r"(ebar) : "r"(sb + OFF_EMPTY), "r"(lane & 1));
    auto release = [&](int slot) { if (lane < 2) mbar_arrive_cl(ebar + 8 * slot); };
    const uint32_t xw = sb + OFF_X + wg * 8192, fullb = sb + OFF_FULL;
    const uint32_t dxw = (xw & 0x3FFFF) >> 4, dring = ((sb + OFF_RING) & 0x3FFFF) >> 4;

    float ure[32], uim[32], aa[48], ab[64];
    cplx lam[2], coef[2], l16[2], l32[2], lq[2], pre[2], e[2];
    {
      const cplx l1 = make_lam(pr, pi, pd);
      const float inv = __fdividef(1.f, fmaf(pr, pr, pi * pi));
      const cplx cf = cmul(cplx{l1.re - 1.f, l1.im}, cplx{pr * inv, -pi * inv});
      cplx t = cmul(l1, l1); t = cmul(t, t); t = cmul(t, t); t = cmul(t, t);
#pragma unroll
      for (int h = 0; h < 2; h++) {
        lam[h] = cplx{__shfl_sync(0xffffffffu, l1.re, 2 * h, 4), __shfl_sync(0xffffffffu, l1.im, 2 * h, 4)};
        coef[h] = cplx{__shfl_sync(0xffffffffu, cf.re, 2 * h, 4), __shfl_sync(0xffffffffu, cf.im, 2 * h, 4)};
        l16[h] = cplx{__shfl_sync(0xffffffffu, t.re, 2 * h, 4), __shfl_sync(0xffffffffu, t.im, 2 * h, 4)};
      }
    }
    TS(wg, 24);

#pragma unroll
    for (int kb = 0; kb < 8; kb++) {
      const int slot = kb % NSLOT;
      TS2(1, kb);
      mbar_wait(sb + OFF_XFULL + 8 * kb, 0);
      if (kb == 0) TS(wg, 18);
      mbar_wait(fullb + 8 * slot, (kb / NSLOT) & 1);
      TS2(2, kb);
      if (kb == 0) TS(wg, 1);
      wg_fence();
      const uint32_t dxa = dxw + ((kb + xrot) & 7) * 1024;
#pragma unroll
      for (int kk = 0; kk < 4; kk++) {
        wgmma_n64_ss<0, 0, DH128, DH128>(ure, dring, slot * 16384 + kk * 32, dxa, kk * 32, (kb | kk) != 0);
        wgmma_n64_ss<0, 0, DH128, DH128>(uim, dring, slot * 16384 + 8192 + kk * 32, dxa, kk * 32, (kb | kk) != 0);
      }
      wg_commit();
      if (kb > 0) { wg_wait<1>(); release((kb - 1) % NSLOT); }
      if (kb == 0) {
#pragma unroll
        for (int h = 0; h < 2; h++) {
          pin(l16[h].re); pin(l16[h].im);
          l32[h] = cmul(l16[h], l16[h]);
          const cplx a = (q & 1) ? l16[h] : cplx{1.f, 0.f}, c = (q & 2) ? l32[h] : cplx{1.f, 0.f};
          lq[h] = cmul(cmul(a, c), coef[h]);
          pin(lq[h].re); pin(lq[h].im);
        }
      } else {
#pragma unroll
        for (int j = (kb - 1) * 4; j < kb * 4; j++) {
          pin(bv[j]);
          float* d = j < 12 ? aa + 4 * j : ab + 4 * (j - 12);
          d[0] = d[2] = bf_lo(bv[j]); d[1] = d[3] = bf_hi(bv[j]);
          pin(d[0]); pin(d[1]); pin(d[2]); pin(d[3]);
        }
      }
    }
    TS(wg, 2);
#pragma unroll
    for (int kb = 0; kb < 8; kb++) {
      const int u = 8 + kb, slot = u % NSLOT;
      TS2(1, u);
      mbar_wait(fullb + 8 * slot, (u / NSLOT) & 1);
      TS2(2, u);
      wg_fence();
      const uint32_t dxa = dxw + ((kb + xrot) & 7) * 1024;
#pragma unroll
      for (int kk = 0; kk < 4; kk++)
        wgmma_n96_ss<0, 1, DH128, DH64>(aa, dxa, kk * 32, dring, slot * 16384 + (kk >> 1) * 6144 + (kk & 1) * 1024 + lbo(2048), 1);
      wg_commit();
      wg_wait<1>();
      release((u - 1) % NSLOT);
      if (kb == 0) {
        reg_fence(ure); reg_fence(uim);
#pragma unroll
        for (int h = 0; h < 2; h++) e[h] = cplx{ure[2 * h], uim[2 * h]};
      }
      if (kb < 3) {
#pragma unroll
        for (int t = 1 + 5 * kb; t < 6 + 5 * kb; t++)
#pragma unroll
          for (int h = 0; h < 2; h++) { const int i = 4 * (t >> 1) + 2 * h + (t & 1); e[h] = cfma(lam[h], e[h], cplx{ure[i], uim[i]}); }
#pragma unroll
        for (int h = 0; h < 2; h++) { pin(e[h].re); pin(e[h].im); }
      } else if (kb == 3) {
#pragma unroll
        for (int h = 0; h < 2; h++) {
          cplx y = {__shfl_up_sync(0xffffffffu, e[h].re, 1, 4), __shfl_up_sync(0xffffffffu, e[h].im, 1, 4)};
          if (q >= 1) e[h] = cfma(l16[h], y, e[h]);
          y = cplx{__shfl_up_sync(0xffffffffu, e[h].re, 2, 4), __shfl_up_sync(0xffffffffu, e[h].im, 2, 4)};
          if (q >= 2) e[h] = cfma(l32[h], y, e[h]);
        }
        if (q == 3) {
#pragma unroll
          for (int h = 0; h < 2; h++)
            asm volatile("st.shared.v2.f32 [%0], {%1,%2};" ::"r"(sb + OFF_CARRY + wg * 512 + (w * 16 + gr + 8 * h) * 8), "f"(e[h].re), "f"(e[h].im) : "memory");
          mbar_arrive(sb + OFF_GBAR);
        }
#pragma unroll
        for (int h = 0; h < 2; h++) {
          const cplx y = {__shfl_up_sync(0xffffffffu, e[h].re, 1, 4), __shfl_up_sync(0xffffffffu, e[h].im, 1, 4)};
          pre[h] = (q >= 1) ? cmul(coef[h], y) : cplx{0.f, 0.f};
          pin(pre[h].re); pin(pre[h].im);
        }
        TS(wg, 3);
      } else {
#pragma unroll
        for (int i = (kb - 4) * 8; i < (kb - 3) * 8; i++) {
          pin(ure[i]); pin(uim[i]);
          const cplx v = cmul(coef[(i >> 1) & 1], cplx{ure[i], uim[i]});
          ure[i] = v.re; uim[i] = v.im;
          pin(ure[i]); pin(uim[i]);
        }
      }
    }
    TS(wg, 4);
    uint32_t H[56];
    cplx hst[2];
    const uint32_t dh = dxw;
    const uint32_t hst_addr = xw + (w * 16 + (lane & 15)) * 128 + (((lane >> 4) ^ (lane & 7)) << 4);
#pragma unroll
    for (int kb = 0; kb < 8; kb++) {
      const int u = 16 + kb, slot = u % NSLOT;
      TS2(1, u);
      mbar_wait(fullb + 8 * slot, (u / NSLOT) & 1);
      TS2(2, u);
      wg_fence();
#pragma unroll
      for (int kk = 0; kk < 4; kk++)
        wgmma_n128_ss<0, 1, DH128, DH128>(ab, dxw, kb * 16384 + kk * 32, dring, slot * 16384 + kk * 2048 + lbo(8192), 1);
      wg_commit();
      wg_wait<1>();
      release((u - 1) % NSLOT);
      if (kb < 3 || kb == 7) {
        const int ch = kb < 3 ? kb : 3;
#pragma unroll
        for (int i = ch * 6; i < ch * 6 + 6; i++) {
          pin(aa[2 * i]); pin(aa[2 * i + 1]);
          H[i] = pack_bf16(gelu2(aa[2 * i]), gelu2(aa[2 * i + 1]));
          pin(H[i]);
        }
      } else {
        if (kb == 3) {
          TS(wg, 5);
          mbar_wait(sb + OFF_CBAR, 0);
          TS(wg, 6);
#pragma unroll
          for (int h = 0; h < 2; h++) {
            const float2 c = lds_f2(sb + OFF_CARRY + wg * 512 + (w * 16 + gr + 8 * h) * 8);
            hst[h] = cfma(lq[h], cplx{c.x, c.y}, pre[h]);
          }
        }
        const int j0 = (kb - 3) * 2;
        uint32_t rr[4], ri[4];
#pragma unroll
        for (int jj = 0; jj < 2; jj++) {
          const int j = j0 + jj;
          const float2 g2 = lds_f2(sb + OFF_GS + (wg * 64 + j * 8 + q * 2) * 4);
#pragma unroll
          for (int h = 0; h < 2; h++) {
            const int i = 4 * j + 2 * h;
            const cplx h0 = cfma(lam[h], hst[h], cplx{ure[i], uim[i]});
            hst[h] = cfma(lam[h], h0, cplx{ure[i + 1], uim[i + 1]});
            rr[jj * 2 + h] = pack_bf16(h0.re * g2.x, hst[h].re * g2.y);
            ri[jj * 2 + h] = pack_bf16(-h0.im * g2.x, -hst[h].im * g2.y);
          }
        }
        const uint32_t a = hst_addr ^ (j0 << 4);
        asm volatile("stmatrix.sync.aligned.m8n8.x4.shared.b16 [%0], {%1,%2,%3,%4};" ::"r"(a), "r"(rr[0]), "r"(rr[1]), "r"(rr[2]), "r"(rr[3]) : "memory");
        asm volatile("stmatrix.sync.aligned.m8n8.x4.shared.b16 [%0], {%1,%2,%3,%4};" ::"r"(a + 16384), "r"(ri[0]), "r"(ri[1]), "r"(ri[2]), "r"(ri[3]) : "memory");
        if (kb == 6) asm volatile("fence.proxy.async.shared::cta;" ::: "memory");
      }
    }
    bar_sync(1 + wg, 128);
    TS(wg, 7);

    uint4* const psend = g_part + (size_t)m * (8 * 7 * 1024) + warp * 128;
    const uint4* const precv = g_part + (size_t)(m * 8 + s) * (7 * 1024) + warp * 128 + lane;
    const uint32_t stg = sb + OFF_X + 5 * 16384 + warp * 2048;
    const uint32_t dx0 = ((sb + OFF_X) & 0x3FFFF) >> 4;
    float o[32], rho[2];
    uint32_t r0[16], r1[16], r2[16], sum[16], tag;
    auto send = [&](int p) {
#pragma unroll
      for (int i = 0; i < 4; i++) {
        uint32_t t0;
        asm("lop3.b32 %0, %1, 1, %2, 0xb8;" : "=r"(t0) : "r"(pack_bf16(o[8 * i], o[8 * i + 1])), "r"(tag));
        asm volatile("st.shared.v4.u32 [%0], {%1,%2,%3,%4};" ::"r"(stg + lane * 16 + (p & 1) * 16384 + i * 512), "r"(t0), "r"(pack_bf16(o[8 * i + 2], o[8 * i + 3])),
                     "r"(pack_bf16(o[8 * i + 4], o[8 * i + 5])), "r"(pack_bf16(o[8 * i + 6], o[8 * i + 7])) : "memory");
      }
      asm volatile("fence.proxy.async.shared::cta;" ::: "memory");
      __syncwarp();
      if (elect_one()) {
        asm volatile("cp.async.bulk.global.shared::cta.bulk_group [%0], [%1], 2048;" ::"l"(psend + (((s + 1 + p) & 7) * 7 + p) * 1024), "r"(stg + (p & 1) * 16384) : "memory");
        asm volatile("cp.async.bulk.commit_group;" ::: "memory");
        asm volatile("cp.async.bulk.wait_group.read 1;" ::: "memory");
      }
    };
    auto recv_issue = [&](uint32_t (&r)[16], int p) {
#pragma unroll
      for (int i = 0; i < 4; i++) ld_b128(precv + p * 1024 + i * 32, r[4 * i], r[4 * i + 1], r[4 * i + 2], r[4 * i + 3]);
    };
    auto stale = [&](uint32_t (&r)[16]) {
      uint32_t t0, t1;
      asm("lop3.b32 %0, %1, %2, %3, 0x7e;" : "=r"(t0) : "r"(r[0]), "r"(r[4]), "r"(tag));
      asm("lop3.b32 %0, %1, %2, %3, 0x7e;" : "=r"(t1) : "r"(r[8]), "r"(r[12]), "r"(tag));
      return __any_sync(0xffffffffu, (t0 | t1) & 1);
    };
    auto recv_check = [&](uint32_t (&r)[16], int p) {
      if (__builtin_expect(stale(r), 0)) {
        int tries = 0;
#pragma unroll 1
        do { recv_issue(r, p); } while (stale(r) && ++tries < 200000);
      }
    };
    auto gelu_b = [&](int i0, int i1) {
#pragma unroll
      for (int i = i0; i < i1; i++) {
        pin(ab[2 * i]); pin(ab[2 * i + 1]);
        H[24 + i] = pack_bf16(gelu2(ab[2 * i]), gelu2(ab[2 * i + 1]));
        pin(H[24 + i]);
      }
    };
    auto mma = [&](uint32_t wo, int k0, int k1) {
      wg_fence();
#pragma unroll
      for (int k = k0; k < k1; k++) {
        if (k < 8) wgmma_n64_ss<1, 0, DH128, DH128>(o, dh, (k >> 2) * 16384 + (k & 3) * 2048, dx0, wo + (k >> 2) * 8192 + (k & 3) * 32, k != 0);
        else { const int kk = k - 8; wgmma_n64_rs<1, DH128>(o, H[4 * kk], H[4 * kk + 1], H[4 * kk + 2], H[4 * kk + 3], dx0, wo + 16384 + (kk / 7) * 16384 + (kk % 7) * 2048, 1); }
      }
      wg_commit();
    };
#pragma unroll
    for (int p = 0; p < 8; p++) {
      const uint32_t wo = (p % 3) == 1 ? 2 * 16384 : OFF_RING + (p % 3) * 24576;
      if (p == 0) {
        mbar_wait(fullb, 0);
        mma(wo, 0, 4);
        wg_wait<1>(); release(5);
        gelu_b(0, 6);
        mma(wo, 4, 8);
        gelu_b(6, 12);
        mbar_wait(fullb + 8, 0);
        mma(wo, 8, 12);
        gelu_b(12, 18);
        mma(wo, 12, 15);
        gelu_b(18, 24);
        mbar_wait(fullb + 16, 0);
        mma(wo, 15, 18);
        gelu_b(24, 32);
        if (wg == 1) bar_sync(4, 256);
        mma(wo, 18, 22);
      } else {
        mbar_wait(sb + OFF_XFULL + 8 * p, 1);
        if (p == 3) TS(wg, 19);
        bar_sync(3 + wg, 256);
        mma(wo, 0, 22);
      }
      if (p < 7 || wg == 0) bar_arrive(4 - wg, 256);
      if (p == 3) TS(wg, 21);
      if (p == 7) recv_issue(r2, 6);
      if (p == 0 || p >= 5) tag = lds_u(sb + OFF_EPOCH);
      if (p == 2) {
        uint32_t rh[2];
#pragma unroll
        for (int h = 0; h < 2; h++) {
          rho[h] = lds_f(sb + OFF_GS + (wg * 64 + w * 16 + gr + 8 * h) * 4);
          rh[h] = pack_bf16(0.25f * rho[h], 0.25f * rho[h]);
        }
#pragma unroll
        for (int j = 0; j < 8; j++) {
          const float2 db = lds_f2(sb + OFF_DB + j * 32 + q * 8);
#pragma unroll
          for (int h = 0; h < 2; h++) {
            const uint32_t xd = bf2_mul(lds_u(xw + 7 * 16384 + (w * 16 + gr + 8 * h) * 128 + ((j ^ gr) << 4) + q * 4), __float_as_uint(db.x));
            const uint32_t t = bf2_fma(xd, rh[h], __float_as_uint(db.y));
            sum[2 * j + h] = bf2_add(t, t);
          }
        }
      } else if (p >= 5) {
        recv_check(r0, 2 * p - 10); recv_check(r1, 2 * p - 9);
#pragma unroll
        for (int i = 0; i < 16; i++) sum[i] = bf2_add(sum[i], bf2_add(r0[i], r1[i]));
      }
      if (p == 3) TS(wg, 22);
      wg_wait<0>();
      if (p < 5) release(p);
      reg_fence(o);
      if (p == 3) TS(wg, 23);
      if (p < 7) send(p);
      if (p >= 4 && p < 7) { recv_issue(r0, 2 * p - 8); recv_issue(r1, 2 * p - 7); }
      TS(wg, 8 + p);
    }
    {
      float fs[2];
#pragma unroll
      for (int h = 0; h < 2; h++) fs[h] = __fdividef(2.f, 4.f + rho[h]);
#pragma unroll
      for (int i = 0; i < 16; i++) { o[2 * i] = (o[2 * i] + bf_lo(sum[i])) * fs[i & 1]; o[2 * i + 1] = (o[2 * i + 1] + bf_hi(sum[i])) * fs[i & 1]; }
      reg_fence(o);
      tag = lds_u(sb + OFF_EPOCH);
      recv_check(r2, 6);
      TS(wg, 16);
      float* op = out + (size_t)(m * 128 + wg * 64 + (gr >> 1) * 16 + w * 4 + (gr & 1)) * DM + s * 64 + q * 2;
#pragma unroll
      for (int i = 0; i < 16; i++)
        *reinterpret_cast<float2*>(op + (i & 1) * 2 * DM + (i >> 1) * 8) =
            make_float2(fmaf(bf_lo(r2[i]), fs[i & 1], o[2 * i]), fmaf(bf_hi(r2[i]), fs[i & 1], o[2 * i + 1]));
      if (threadIdx.x == 128) g_epoch[b] = tag;
      if (elect_one()) asm volatile("cp.async.bulk.wait_group.read 0;" ::: "memory");
      TS(wg, 17); TG(wg); TDUMP();
    }
  }
}

typedef CUresult (*EncFn)(CUtensorMap*, CUtensorMapDataType, cuuint32_t, void*, const cuuint64_t*, const cuuint64_t*, const cuuint32_t*,
                          const cuuint32_t*, CUtensorMapInterleave, CUtensorMapSwizzle, CUtensorMapL2promotion, CUtensorMapFloatOOBfill);

void encode(EncFn f, CUtensorMap* mp, const void* p, int rank, const cuuint64_t* dims, const cuuint64_t* strides, const cuuint32_t* box, CUtensorMapSwizzle sw) {
  cuuint32_t es[5] = {1, 1, 1, 1, 1};
  f(mp, CU_TENSOR_MAP_DATA_TYPE_BFLOAT16, rank, const_cast<void*>(p), dims, strides, box, es, CU_TENSOR_MAP_INTERLEAVE_NONE, sw,
    CU_TENSOR_MAP_L2_PROMOTION_L2_128B, CU_TENSOR_MAP_FLOAT_OOB_FILL_NONE);
}

}

extern "C" void kernel_launch(void* const* d_in, const int* in_sizes, int n_in, void* d_out, int out_size) {
  typedef const __nv_bfloat16* bp;
  bp x = (bp)d_in[0], lre = (bp)d_in[1], lim = (bp)d_in[2], bre = (bp)d_in[3], bim = (bp)d_in[4], cre = (bp)d_in[5], cim = (bp)d_in[6],
     ldt = (bp)d_in[7], dsk = (bp)d_in[8], w1 = (bp)d_in[10], b1 = (bp)d_in[11], w2 = (bp)d_in[12], b2 = (bp)d_in[13], gw = (bp)d_in[14];
  static EncFn enc = nullptr;
  if (!enc) {
    void* f = nullptr;
    cudaDriverEntryPointQueryResult qr;
    cudaGetDriverEntryPoint("cuTensorMapEncodeTiled", &f, cudaEnableDefault, &qr);
    enc = (EncFn)f;
    cudaFuncSetAttribute(fused_kernel, cudaFuncAttributeMaxDynamicSharedMemorySize, SMEM_BYTES);
  }
  Maps maps;
  {
    cuuint64_t d[5] = {DM, 2, 4, 8, SEQ / 64}, st[4] = {DM * 2, 16 * DM * 2, 2 * DM * 2, 64 * DM * 2};
    cuuint32_t bx[5] = {64, 2, 4, 8, 2};
    encode(enc, &maps.x, x, 5, d, st, bx, CU_TENSOR_MAP_SWIZZLE_128B);
  }
  {
    cuuint64_t d[2] = {DM, DM}, st[1] = {DM * 2};
    cuuint32_t bx[2] = {64, 64};
    encode(enc, &maps.bre, bre, 2, d, st, bx, CU_TENSOR_MAP_SWIZZLE_128B);
    encode(enc, &maps.bim, bim, 2, d, st, bx, CU_TENSOR_MAP_SWIZZLE_128B);
    encode(enc, &maps.cre, cre, 2, d, st, bx, CU_TENSOR_MAP_SWIZZLE_128B);
    encode(enc, &maps.cim, cim, 2, d, st, bx, CU_TENSOR_MAP_SWIZZLE_128B);
  }
  {
    cuuint64_t d[2] = {FF, DM}, st[1] = {FF * 2};
    cuuint32_t bx[2] = {64, 64};
    encode(enc, &maps.w1a, w1, 2, d, st, bx, CU_TENSOR_MAP_SWIZZLE_128B);
    cuuint64_t d3[3] = {32, DM, FF / 32}, st3[2] = {FF * 2, 64};
    cuuint32_t bx3[3] = {32, 32, 3};
    encode(enc, &maps.w1b, w1, 3, d3, st3, bx3, CU_TENSOR_MAP_SWIZZLE_64B);
  }
  {
    cuuint64_t d[2] = {DM, FF}, st[1] = {DM * 2};
    cuuint32_t bx[2] = {64, 56};
    encode(enc, &maps.w2, w2, 2, d, st, bx, CU_TENSOR_MAP_SWIZZLE_128B);
  }
  fused_kernel<<<128, 384, SMEM_BYTES>>>(maps, lre, lim, ldt, dsk, b1, b2, gw, w1, w2, cre, cim, (float*)d_out);
}
```

```cpp
#include <cuda_runtime.h>
#include <cuda_bf16.h>
#include <cuda.h>
#include <stdint.h>

#define PF 2
#define SEND_TMA 0
#define PFK 2
namespace {

constexpr int SEQ = 2048, DM = 512, FF = 1792;
constexpr int NSLOT = 6;
constexpr uint32_t OFF_X = 0, OFF_RING = 131072, OFF_MISC = 229376;
constexpr uint32_t OFF_XFULL = OFF_MISC, OFF_FULL = OFF_XFULL + 64, OFF_EMPTY = OFF_FULL + 48, OFF_GBAR = OFF_EMPTY + 48,
                   OFF_CBAR = OFF_GBAR + 8, OFF_EPOCH = OFF_CBAR + 8;
constexpr uint32_t OFF_GS = OFF_MISC + 256;
constexpr uint32_t OFF_CARRY = OFF_GS + 512;
constexpr uint32_t OFF_DB = OFF_CARRY + 1024;
constexpr uint32_t OFF_DBG = OFF_DB + 256;
constexpr uint32_t SMEM_BYTES = OFF_DBG + 768;
static_assert(SMEM_BYTES <= 232448, "smem");

struct Maps { CUtensorMap x, bre, bim, w1a, w1b, w2, cre, cim; };

__device__ uint4 g_part[16 * 8 * 7 * 1024];
__device__ float2 g_end[8 * 16 * 64];
__device__ unsigned g_gate[SEQ];
__device__ unsigned g_epoch[128];
#define TG(role) do {} while (0)
#define TS2(role, i) do {} while (0)
#define TS(role, i) do {} while (0)
#define TDUMP() do {} while (0)

__device__ __forceinline__ void mbar_init(uint32_t bar, uint32_t cnt) { asm volatile("mbarrier.init.shared::cta.b64 [%0], %1;" ::"r"(bar), "r"(cnt)); }
__device__ __forceinline__ void mbar_expect_tx(uint32_t bar, uint32_t bytes) { asm volatile("mbarrier.arrive.expect_tx.shared::cta.b64 _, [%0], %1;" ::"r"(bar), "r"(bytes) : "memory"); }
__device__ __forceinline__ void mbar_arrive(uint32_t bar) { asm volatile("mbarrier.arrive.shared::cta.b64 _, [%0];" ::"r"(bar) : "memory"); }
__device__ __forceinline__ void mbar_arrive_cl(uint32_t cbar) { asm volatile("mbarrier.arrive.shared::cluster.b64 _, [%0];" ::"r"(cbar) : "memory"); }
__device__ __forceinline__ void mbar_wait(uint32_t bar, uint32_t parity) {
  asm volatile(
      "{\n.reg .pred p;\n.reg .u32 c;\n"
      "mbarrier.try_wait.parity.shared::cta.b64 p, [%0], %1;\n"
      "@p bra.uni LAB_DONE;\n"
      "mov.u32 c, 0;\n"
      "LAB_WAIT:\n"
      "mbarrier.try_wait.parity.shared::cta.b64 p, [%0], %1;\n"
      "@p bra.uni LAB_DONE;\n"
      "add.u32 c, c, 1;\nsetp.lt.u32 p, c, 200000;\n@p bra.uni LAB_WAIT;\n"
      "LAB_DONE:\n}" ::"r"(bar), "r"(parity) : "memory");
}
__device__ __forceinline__ void tma2d(uint32_t dst, const CUtensorMap* m, int c0, int c1, uint32_t bar) {
  asm volatile("cp.async.bulk.tensor.2d.shared::cluster.global.mbarrier::complete_tx::bytes [%0], [%1, {%3,%4}], [%2];"
               ::"r"(dst), "l"(m), "r"(bar), "r"(c0), "r"(c1) : "memory");
}
__device__ __forceinline__ void tma2d_mc(uint32_t dst, const CUtensorMap* m, int c0, int c1, uint32_t bar) {
  asm volatile("cp.async.bulk.tensor.2d.shared::cluster.global.mbarrier::complete_tx::bytes.multicast::cluster [%0], [%1, {%3,%4}], [%2], %5;"
               ::"r"(dst), "l"(m), "r"(bar), "r"(c0), "r"(c1), "h"((uint16_t)3) : "memory");
}
__device__ __forceinline__ void tma3d_mc(uint32_t dst, const CUtensorMap* m, int c0, int c1, int c2, uint32_t bar) {
  asm volatile("cp.async.bulk.tensor.3d.shared::cluster.global.mbarrier::complete_tx::bytes.multicast::cluster [%0], [%1, {%3,%4,%5}], [%2], %6;"
               ::"r"(dst), "l"(m), "r"(bar), "r"(c0), "r"(c1), "r"(c2), "h"((uint16_t)3) : "memory");
}
__device__ __forceinline__ void tma5d(uint32_t dst, const CUtensorMap* m, int c0, int c4, uint32_t bar) {
  asm volatile("cp.async.bulk.tensor.5d.shared::cluster.global.mbarrier::complete_tx::bytes [%0], [%1, {%3,%5,%5,%5,%4}], [%2];"
               ::"r"(dst), "l"(m), "r"(bar), "r"(c0), "r"(c4), "r"(0) : "memory");
}
__device__ __forceinline__ void l2_prefetch(const void* p, uint32_t bytes) { asm volatile("cp.async.bulk.prefetch.L2.global [%0], %1;" ::"l"(p), "r"(bytes) : "memory"); }
__device__ __forceinline__ bool elect_one() {
  uint32_t pred;
  asm volatile("{.reg .pred P; elect.sync _|P, 0xffffffff; selp.u32 %0, 1, 0, P;}" : "=r"(pred));
  return pred != 0;
}
__device__ __forceinline__ void wg_fence() { asm volatile("wgmma.fence.sync.aligned;" ::: "memory"); }
__device__ __forceinline__ void wg_commit() { asm volatile("wgmma.commit_group.sync.aligned;" ::: "memory"); }
template <int N> __device__ __forceinline__ void wg_wait() { asm volatile("wgmma.wait_group.sync.aligned %0;" ::"n"(N) : "memory"); }
template <int N> __device__ __forceinline__ void reg_fence(float (&d)[N]) {
#pragma unroll
  for (int i = 0; i < N; i++) asm volatile("" : "+f"(d[i])::"memory");
}
__device__ __forceinline__ void bar_sync(int id, int n) { asm volatile("bar.sync %0, %1;" ::"r"(id), "r"(n) : "memory"); }
__device__ __forceinline__ void bar_arrive(int id, int n) { asm volatile("bar.arrive %0, %1;" ::"r"(id), "r"(n) : "memory"); }
constexpr uint32_t DH128 = (1024 >> 4) | (1u << 30), DH64 = (512 >> 4) | (2u << 30);
__host__ __device__ constexpr uint32_t lbo(uint32_t bytes) { return (bytes >> 4) << 20; }
__device__ __forceinline__ uint32_t pack_bf16(float lo, float hi) { uint32_t r; asm("cvt.rn.bf16x2.f32 %0, %1, %2;" : "=r"(r) : "f"(hi), "f"(lo)); return r; }
__device__ __forceinline__ float bf_lo(uint32_t v) { return __uint_as_float(v << 16); }
__device__ __forceinline__ float bf_hi(uint32_t v) { return __uint_as_float(v & 0xffff0000u); }
__device__ __forceinline__ float bf_ld(const __nv_bfloat16* p) { return __bfloat162float(__ldg(p)); }
__device__ __forceinline__ float2 lds_f2(uint32_t a) { float2 v; asm volatile("ld.shared.v2.f32 {%0,%1}, [%2];" : "=f"(v.x), "=f"(v.y) : "r"(a)); return v; }
__device__ __forceinline__ float lds_f(uint32_t a) { float v; asm volatile("ld.shared.f32 %0, [%1];" : "=f"(v) : "r"(a)); return v; }
__device__ __forceinline__ uint32_t lds_u(uint32_t a) { uint32_t v; asm volatile("ld.shared.u32 %0, [%1];" : "=r"(v) : "r"(a)); return v; }
__device__ __forceinline__ uint4 lds_u4(uint32_t a) { uint4 v; asm volatile("ld.shared.v4.u32 {%0,%1,%2,%3}, [%4];" : "=r"(v.x), "=r"(v.y), "=r"(v.z), "=r"(v.w) : "r"(a)); return v; }
__device__ __forceinline__ void st_b128(uint4* p, uint32_t a, uint32_t b, uint32_t c, uint32_t d) {
  asm volatile("{.reg .b64 l, h; .reg .b128 v; mov.b64 l, {%1,%2}; mov.b64 h, {%3,%4}; mov.b128 v, {l,h}; st.relaxed.gpu.global.b128 [%0], v;}"
               ::"l"(p), "r"(a), "r"(b), "r"(c), "r"(d) : "memory");
}
__device__ __forceinline__ void ld_b128(const uint4* p, uint32_t& a, uint32_t& b, uint32_t& c, uint32_t& d) {
  asm volatile("{.reg .b64 l, h; .reg .b128 v; ld.relaxed.gpu.global.b128 v, [%4]; mov.b128 {l,h}, v; mov.b64 {%0,%1}, l; mov.b64 {%2,%3}, h;}"
               : "=r"(a), "=r"(b), "=r"(c), "=r"(d) : "l"(p) : "memory");
}
__device__ __forceinline__ float tanh_fast(float x) { float y; asm("tanh.approx.f32 %0, %1;" : "=f"(y) : "f"(x)); return y; }
__device__ __forceinline__ float gelu2(float v) {
  float p = fmaf(v * v, 0.0356774081363f, 0.7978845608029f);
  return fmaf(v, tanh_fast(v * p), v);
}
__device__ __forceinline__ uint32_t bf2_mul(uint32_t a, uint32_t b) { uint32_t r; asm("mul.rn.bf16x2 %0, %1, %2;" : "=r"(r) : "r"(a), "r"(b)); return r; }
__device__ __forceinline__ uint32_t bf2_add(uint32_t a, uint32_t b) { uint32_t r; asm("add.rn.bf16x2 %0, %1, %2;" : "=r"(r) : "r"(a), "r"(b)); return r; }
__device__ __forceinline__ uint32_t bf2_fma(uint32_t a, uint32_t b, uint32_t c) { uint32_t r; asm("fma.rn.bf16x2 %0, %1, %2, %3;" : "=r"(r) : "r"(a), "r"(b), "r"(c)); return r; }
__device__ __forceinline__ void pin(float& a) { asm volatile("" : "+f"(a)::"memory"); }
__device__ __forceinline__ void pin(uint32_t& a) { asm volatile("" : "+r"(a)::"memory"); }
struct cplx { float re, im; };
__device__ __forceinline__ cplx cmul(cplx a, cplx b) { return {fmaf(a.re, b.re, -a.im * b.im), fmaf(a.re, b.im, a.im * b.re)}; }
__device__ __forceinline__ cplx cfma(cplx a, cplx b, cplx c) {
  return {fmaf(a.re, b.re, fmaf(-a.im, b.im, c.re)), fmaf(a.re, b.im, fmaf(a.im, b.re, c.im))};
}
__device__ __forceinline__ cplx make_lam(float lre, float lim, float ldt) {
  float dt = __bfloat162float(__float2bfloat16_rn(expf(ldt)));
  float mag = expf(dt * lre), sn, cs;
  sincospif(dt * lim * 0.31830988618379067f, &sn, &cs);
  return {mag * cs, mag * sn};
}

template<int TA,int TB,uint32_t AH,uint32_t BH> __device__ __forceinline__ void wgmma_n64_ss(float (&d)[32], uint32_t al, uint32_t ao, uint32_t bl, uint32_t bo, int scale_d){
  asm volatile("{.reg .pred p; .reg .b32 t, v; .reg .b64 da, db; setp.ne.b32 p, %36, 0; add.u32 t, %32, %33; mov.b64 da, {t, %39}; add.u32 v, %34, %35; mov.b64 db, {v, %40};\n"
   "wgmma.mma_async.sync.aligned.m64n64k16.f32.bf16.bf16 {%0,%1,%2,%3,%4,%5,%6,%7,%8,%9,%10,%11,%12,%13,%14,%15,%16,%17,%18,%19,%20,%21,%22,%23,%24,%25,%26,%27,%28,%29,%30,%31}, da, db, p, 1, 1, %37, %38;}"
   : "+f"(d[0]),"+f"(d[1]),"+f"(d[2]),"+f"(d[3]),"+f"(d[4]),"+f"(d[5]),"+f"(d[6]),"+f"(d[7]),"+f"(d[8]),"+f"(d[9]),"+f"(d[10]),"+f"(d[11]),"+f"(d[12]),"+f"(d[13]),"+f"(d[14]),"+f"(d[15]),"+f"(d[16]),"+f"(d[17]),"+f"(d[18]),"+f"(d[19]),"+f"(d[20]),"+f"(d[21]),"+f"(d[22]),"+f"(d[23]),"+f"(d[24]),"+f"(d[25]),"+f"(d[26]),"+f"(d[27]),"+f"(d[28]),"+f"(d[29]),"+f"(d[30]),"+f"(d[31])
   : "r"(al),"r"(ao >> 4),"r"(bl),"r"(bo >> 4),"r"(scale_d),"n"(TA),"n"(TB),"n"(AH),"n"(BH));
}
template<int TB,uint32_t BH> __device__ __forceinline__ void wgmma_n64_rs(float (&d)[32], uint32_t a0,uint32_t a1,uint32_t a2,uint32_t a3, uint32_t bl, uint32_t bo, int scale_d){
  asm volatile("{.reg .pred p; .reg .b32 t; .reg .b64 db; setp.ne.b32 p, %38, 0; add.u32 t, %36, %37; mov.b64 db, {t, %40};\n"
   "wgmma.mma_async.sync.aligned.m64n64k16.f32.bf16.bf16 {%0,%1,%2,%3,%4,%5,%6,%7,%8,%9,%10,%11,%12,%13,%14,%15,%16,%17,%18,%19,%20,%21,%22,%23,%24,%25,%26,%27,%28,%29,%30,%31}, {%32,%33,%34,%35}, db, p, 1, 1, %39;}"
   : "+f"(d[0]),"+f"(d[1]),"+f"(d[2]),"+f"(d[3]),"+f"(d[4]),"+f"(d[5]),"+f"(d[6]),"+f"(d[7]),"+f"(d[8]),"+f"(d[9]),"+f"(d[10]),"+f"(d[11]),"+f"(d[12]),"+f"(d[13]),"+f"(d[14]),"+f"(d[15]),"+f"(d[16]),"+f"(d[17]),"+f"(d[18]),"+f"(d[19]),"+f"(d[20]),"+f"(d[21]),"+f"(d[22]),"+f"(d[23]),"+f"(d[24]),"+f"(d[25]),"+f"(d[26]),"+f"(d[27]),"+f"(d[28]),"+f"(d[29]),"+f"(d[30]),"+f"(d[31])
   : "r"(a0),"r"(a1),"r"(a2),"r"(a3),"r"(bl),"r"(bo >> 4),"r"(scale_d),"n"(TB),"n"(BH));
}
template<int TA,int TB,uint32_t AH,uint32_t BH> __device__ __forceinline__ void wgmma_n96_ss(float (&d)[48], uint32_t al, uint32_t ao, uint32_t bl, uint32_t bo, int scale_d){
  asm volatile("{.reg .pred p; .reg .b32 t, v; .reg .b64 da, db; setp.ne.b32 p, %52, 0; add.u32 t, %48, %49; mov.b64 da, {t, %55}; add.u32 v, %50, %51; mov.b64 db, {v, %56};\n"
   "wgmma.mma_async.sync.aligned.m64n96k16.f32.bf16.bf16 {%0,%1,%2,%3,%4,%5,%6,%7,%8,%9,%10,%11,%12,%13,%14,%15,%16,%17,%18,%19,%20,%21,%22,%23,%24,%25,%26,%27,%28,%29,%30,%31,%32,%33,%34,%35,%36,%37,%38,%39,%40,%41,%42,%43,%44,%45,%46,%47}, da, db, p, 1, 1, %53, %54;}"
   : "+f"(d[0]),"+f"(d[1]),"+f"(d[2]),"+f"(d[3]),"+f"(d[4]),"+f"(d[5]),"+f"(d[6]),"+f"(d[7]),"+f"(d[8]),"+f"(d[9]),"+f"(d[10]),"+f"(d[11]),"+f"(d[12]),"+f"(d[13]),"+f"(d[14]),"+f"(d[15]),"+f"(d[16]),"+f"(d[17]),"+f"(d[18]),"+f"(d[19]),"+f"(d[20]),"+f"(d[21]),"+f"(d[22]),"+f"(d[23]),"+f"(d[24]),"+f"(d[25]),"+f"(d[26]),"+f"(d[27]),"+f"(d[28]),"+f"(d[29]),"+f"(d[30]),"+f"(d[31]),"+f"(d[32]),"+f"(d[33]),"+f"(d[34]),"+f"(d[35]),"+f"(d[36]),"+f"(d[37]),"+f"(d[38]),"+f"(d[39]),"+f"(d[40]),"+f"(d[41]),"+f"(d[42]),"+f"(d[43]),"+f"(d[44]),"+f"(d[45]),"+f"(d[46]),"+f"(d[47])
   : "r"(al),"r"(ao >> 4),"r"(bl),"r"(bo >> 4),"r"(scale_d),"n"(TA),"n"(TB),"n"(AH),"n"(BH));
}
template<int TA,int TB,uint32_t AH,uint32_t BH> __device__ __forceinline__ void wgmma_n128_ss(float (&d)[64], uint32_t al, uint32_t ao, uint32_t bl, uint32_t bo, int scale_d){
  asm volatile("{.reg .pred p; .reg .b32 t, v; .reg .b64 da, db; setp.ne.b32 p, %68, 0; add.u32 t, %64, %65; mov.b64 da, {t, %71}; add.u32 v, %66, %67; mov.b64 db, {v, %72};\n"
   "wgmma.mma_async.sync.aligned.m64n128k16.f32.bf16.bf16 {%0,%1,%2,%3,%4,%5,%6,%7,%8,%9,%10,%11,%12,%13,%14,%15,%16,%17,%18,%19,%20,%21,%22,%23,%24,%25,%26,%27,%28,%29,%30,%31,%32,%33,%34,%35,%36,%37,%38,%39,%40,%41,%42,%43,%44,%45,%46,%47,%48,%49,%50,%51,%52,%53,%54,%55,%56,%57,%58,%59,%60,%61,%62,%63}, da, db, p, 1, 1, %69, %70;}"
   : "+f"(d[0]),"+f"(d[1]),"+f"(d[2]),"+f"(d[3]),"+f"(d[4]),"+f"(d[5]),"+f"(d[6]),"+f"(d[7]),"+f"(d[8]),"+f"(d[9]),"+f"(d[10]),"+f"(d[11]),"+f"(d[12]),"+f"(d[13]),"+f"(d[14]),"+f"(d[15]),"+f"(d[16]),"+f"(d[17]),"+f"(d[18]),"+f"(d[19]),"+f"(d[20]),"+f"(d[21]),"+f"(d[22]),"+f"(d[23]),"+f"(d[24]),"+f"(d[25]),"+f"(d[26]),"+f"(d[27]),"+f"(d[28]),"+f"(d[29]),"+f"(d[30]),"+f"(d[31]),"+f"(d[32]),"+f"(d[33]),"+f"(d[34]),"+f"(d[35]),"+f"(d[36]),"+f"(d[37]),"+f"(d[38]),"+f"(d[39]),"+f"(d[40]),"+f"(d[41]),"+f"(d[42]),"+f"(d[43]),"+f"(d[44]),"+f"(d[45]),"+f"(d[46]),"+f"(d[47]),"+f"(d[48]),"+f"(d[49]),"+f"(d[50]),"+f"(d[51]),"+f"(d[52]),"+f"(d[53]),"+f"(d[54]),"+f"(d[55]),"+f"(d[56]),"+f"(d[57]),"+f"(d[58]),"+f"(d[59]),"+f"(d[60]),"+f"(d[61]),"+f"(d[62]),"+f"(d[63])
   : "r"(al),"r"(ao >> 4),"r"(bl),"r"(bo >> 4),"r"(scale_d),"n"(TA),"n"(TB),"n"(AH),"n"(BH));
}

__global__ void __cluster_dims__(2, 1, 1) __launch_bounds__(384, 1)
fused_kernel(const __grid_constant__ Maps maps, const __nv_bfloat16* __restrict__ lam_re,
             const __nv_bfloat16* __restrict__ lam_im, const __nv_bfloat16* __restrict__ log_dt, const __nv_bfloat16* __restrict__ dskip,
             const __nv_bfloat16* __restrict__ b1, const __nv_bfloat16* __restrict__ b2, const __nv_bfloat16* __restrict__ gate_w,
             const __nv_bfloat16* __restrict__ pf_w1, const __nv_bfloat16* __restrict__ pf_w2, const __nv_bfloat16* __restrict__ pf_cre,
             const __nv_bfloat16* __restrict__ pf_cim, const __nv_bfloat16* __restrict__ pf_x,
             const __nv_bfloat16* __restrict__ pf_bre, const __nv_bfloat16* __restrict__ pf_bim, float* __restrict__ out) {
  extern __shared__ __align__(1024) unsigned char smem_raw[];
  const uint32_t sb = (uint32_t)__cvta_generic_to_shared(smem_raw);
  const int b = blockIdx.x;
  const int rank = b & 1, s = (b >> 1) & 7, m = ((b >> 4) << 1) | rank;
  const int warp = __shfl_sync(0xffffffffu, (int)(threadIdx.x >> 5), 0);
  const int lane = threadIdx.x & 31;
  const int xrot = 7 - s;

  if (warp == 8) {
    if (elect_one()) {
      TS(2, 0);
      mbar_init(sb + OFF_XFULL, 1); mbar_init(sb + OFF_FULL, 1); mbar_init(sb + OFF_XFULL + 8, 1);
      asm volatile("fence.mbarrier_init.release.cluster;" ::: "memory");
      asm volatile("fence.proxy.async.shared::cta;" ::: "memory");
      mbar_expect_tx(sb + OFF_XFULL, 16384);
      tma5d(sb + OFF_X + xrot * 16384, &maps.x, 0, 2 * m, sb + OFF_XFULL);
      TS(2, 3);
      mbar_expect_tx(sb + OFF_FULL, 16384);
      tma2d(sb + OFF_RING, &maps.bre, 0, s * 64, sb + OFF_FULL);
      tma2d(sb + OFF_RING + 8192, &maps.bim, 0, s * 64, sb + OFF_FULL);
      mbar_expect_tx(sb + OFF_XFULL + 8, 16384);
      tma5d(sb + OFF_X + ((xrot + 1) & 7) * 16384, &maps.x, 64, 2 * m, sb + OFF_XFULL + 8);
      TS(2, 4);
    }
  } else if (warp < 6) {
    if (elect_one()) {
      mbar_init(sb + OFF_XFULL + 16 + 8 * warp, 1); mbar_init(sb + OFF_EMPTY + 8 * warp, 16);
      if (warp) mbar_init(sb + OFF_FULL + 8 * warp, 1);
      asm volatile("fence.mbarrier_init.release.cluster;" ::: "memory");
    }
  } else if (warp < 8) {
    if (elect_one()) {
      mbar_init(sb + OFF_GBAR + 8 * (warp - 6), warp == 6 ? 64 : 96);
      asm volatile("fence.mbarrier_init.release.cluster;" ::: "memory");
    }
  }
  __syncwarp();
  asm volatile("barrier.cluster.arrive.relaxed.aligned;" ::: "memory");
  if (warp == 8) {
    asm volatile("barrier.cluster.wait.aligned;" ::: "memory");
    if (elect_one()) {
      TS(2, 1);
#pragma unroll 1
      for (int u = 1; u < 7; u++) {
        if (u < 6) {
          mbar_expect_tx(sb + OFF_FULL + 8 * u, 16384);
          tma2d_mc(sb + OFF_RING + u * 16384 + rank * 8192, rank ? &maps.bim : &maps.bre, u * 64, s * 64, sb + OFF_FULL + 8 * u);
        }
        mbar_expect_tx(sb + OFF_XFULL + 8 * (u + 1), 16384);
        tma5d(sb + OFF_X + ((u + 1 + xrot) & 7) * 16384, &maps.x, (u + 1) * 64, 2 * m, sb + OFF_XFULL + 8 * (u + 1));
      }
      TS(2, 5);
    }
    __syncwarp();
  }

  if (warp >= 8) {
    asm volatile("setmaxnreg.dec.sync.aligned.u32 56;");
    if (warp == 8) {
      if (elect_one()) {
        const CUtensorMap* mb = rank ? &maps.bim : &maps.bre;
        const CUtensorMap* mc = rank ? &maps.cim : &maps.cre;
        int slot = 0; uint32_t ph = 0;
#pragma unroll 1
        for (int u = 6; u < 27; u++) {
          const uint32_t fb = sb + OFF_FULL + 8 * slot, dst = sb + OFF_RING + slot * 16384;
          mbar_wait(sb + OFF_EMPTY + 8 * slot, ph);
          TS2(0, u);
          if (u < 8) {
            mbar_expect_tx(fb, 16384);
            tma2d_mc(dst + rank * 8192, mb, u * 64, s * 64, fb);
          } else if (u < 16) {
            mbar_expect_tx(fb, 12288);
            tma3d_mc(dst + rank * 6144, &maps.w1b, 0, (u - 8) * 64 + rank * 32, s * 7, fb);
          } else if (u < 24) {
            mbar_expect_tx(fb, 16384);
            tma2d_mc(dst + rank * 8192, &maps.w1a, s * 224 + 96 + rank * 64, ((u - 15 + s) & 7) * 64, fb);
          } else if (u == 25) {
            mbar_expect_tx(fb, 16384);
            tma2d_mc(dst + rank * 8192, mc, s * 64, ((s + 1) & 7) * 64, fb);
          } else {
            mbar_expect_tx(fb, 14336);
            tma2d_mc(dst + rank * 7168, &maps.w2, ((s + 1) & 7) * 64, s * 224 + (u - 24) * 56 + rank * 56, fb);
          }
          if (++slot == NSLOT) { slot = 0; ph ^= 1; }
        }
#pragma unroll 1
        for (int p = 1; p < 8; p++) {
          const int piece = (s + 1 + p) & 7, grp = p % 3;
          const uint32_t fb = sb + OFF_XFULL + 8 * p, dst = grp == 1 ? sb + OFF_X + 2 * 16384 : sb + OFF_RING + grp * 24576;
          if (p >= 3) mbar_wait(sb + OFF_EMPTY + 8 * (p - 3), 0);
          else if (p == 2) mbar_wait(sb + OFF_EMPTY + 40, 1);
          TS2(0, 32 + p);
          mbar_expect_tx(fb, 45056);
          tma2d_mc(dst + rank * 7168, &maps.w2, piece * 64, s * 224 + rank * 56, fb);
          tma2d_mc(dst + 16384 + rank * 8192, mc, s * 64, piece * 64, fb);
          tma2d_mc(dst + 32768 + rank * 7168, &maps.w2, piece * 64, s * 224 + 112 + rank * 56, fb);
        }
        TS(2, 2);
      }
    } else if (warp == 11) {
      if (lane == 0) TG(2);
      const uint32_t dk = __ldg(reinterpret_cast<const uint32_t*>(dskip + s * 64) + lane), bb = __ldg(reinterpret_cast<const uint32_t*>(b2 + s * 64) + lane);
      asm volatile("st.shared.v2.u32 [%0], {%1,%2};" ::"r"(sb + OFF_DB + lane * 8), "r"(dk), "r"(bb) : "memory");
      asm volatile("barrier.cluster.wait.aligned;" ::: "memory");
      mbar_arrive(sb + OFF_CBAR);
      if ((PF & 2) && elect_one()) {
        mbar_wait(sb + OFF_XFULL + 8 * PFK, 0);
        l2_prefetch(pf_w1 + b * 7168, 14336);
        l2_prefetch(pf_cre + b * 2048, 4096);
        l2_prefetch(pf_cim + b * 2048, 4096);
        l2_prefetch(pf_w2 + b * 7168, 14336);
      }
    } else {
      const int t = threadIdx.x - 288;
      unsigned par;
      asm volatile("ld.relaxed.gpu.global.u32 %0, [%1];" : "=r"(par) : "l"(g_epoch + b) : "memory");
      const float pr = bf_ld(lam_re + s * 64 + t), pi = bf_ld(lam_im + s * 64 + t), pd = bf_ld(log_dt + s * 64 + t);
      const uint4* gwp = reinterpret_cast<const uint4*>(gate_w) + (lane & 7);
      uint4 gw[8];
#pragma unroll
      for (int kb = 0; kb < 8; kb++) gw[kb] = __ldg(gwp + kb * 8);
      asm volatile("barrier.cluster.wait.aligned;" ::: "memory");
      if (t == 0) asm volatile("st.shared.u32 [%0], %1;" ::"r"(sb + OFF_EPOCH), "r"(par + 1) : "memory");
      par = (par + 1) & 1;
      cplx l64 = make_lam(pr, pi, pd);
#pragma unroll
      for (int i = 0; i < 6; i++) l64 = cmul(l64, l64);
      const int row = s * 16 + (t >> 5) * 8 + (lane >> 3);
      const uint32_t xr0 = sb + OFF_X + row * 128 + (((lane & 7) ^ (row & 7)) << 4), xr1 = (xr0 + 512) ^ 64;
      float z0 = 0.f, z1 = 0.f;
#pragma unroll
      for (int kb = 0; kb < 8; kb++) {
        const uint4 w = gw[kb];
        mbar_wait(sb + OFF_XFULL + 8 * kb, 0);
        const uint32_t xo = ((kb + xrot) & 7) * 16384;
        const uint4 a = lds_u4(xr0 + xo), d = lds_u4(xr1 + xo);
        const uint32_t wv[4] = {w.x, w.y, w.z, w.w}, av[4] = {a.x, a.y, a.z, a.w}, dv[4] = {d.x, d.y, d.z, d.w};
#pragma unroll
        for (int c = 0; c < 4; c++) {
          const float wl = bf_lo(wv[c]), wh = bf_hi(wv[c]);
          z0 = fmaf(bf_hi(av[c]), wh, fmaf(bf_lo(av[c]), wl, z0));
          z1 = fmaf(bf_hi(dv[c]), wh, fmaf(bf_lo(dv[c]), wl, z1));
        }
      }
      {
        float zz = (lane & 4) ? z1 : z0;
        zz += __shfl_xor_sync(0xffffffffu, (lane & 4) ? z0 : z1, 4);
        zz += __shfl_xor_sync(0xffffffffu, zz, 2);
        zz += __shfl_xor_sync(0xffffffffu, zz, 1);
        const float rho = 4.f * expf(zz > 40.f ? 40.f : zz);
        if ((lane & 3) == 0)
          asm volatile("st.relaxed.gpu.global.u32 [%0], %1;" ::"l"(g_gate + m * 128 + row + (lane & 4)), "r"((__float_as_uint(rho) & ~1u) | par) : "memory");
      }
      if (t == 0) TS(3, 0);
      mbar_wait(sb + OFF_GBAR, 0);
      const float2 e0 = lds_f2(sb + OFF_CARRY + t * 8), e1 = lds_f2(sb + OFF_CARRY + 512 + t * 8);
      float2* eb = g_end + s * 1024 + t;
      {
        const cplx e = cfma(l64, cplx{e0.x, e0.y}, cplx{e1.x, e1.y});
        const unsigned long long v = ((unsigned long long)__float_as_uint(e.im) << 32) | ((__float_as_uint(e.re) & ~1u) | par);
        asm volatile("st.relaxed.gpu.global.b64 [%0], %1;" ::"l"(eb + m * 64), "l"(v) : "memory");
      }
      if (t == 0) TS(3, 1);
      cplx S = {0.f, 0.f};
      {
        unsigned long long v[15];
        uint32_t bad, g0, g1;
        int tries = 0;
        const unsigned* gp = g_gate + m * 128 + t;
        const float2* e15 = eb + (m - 15) * 64;
#pragma unroll 1
        do {
          asm volatile("ld.relaxed.gpu.global.u32 %0, [%1];" : "=r"(g0) : "l"(gp) : "memory");
          asm volatile("ld.relaxed.gpu.global.u32 %0, [%1];" : "=r"(g1) : "l"(gp + 64) : "memory");
#pragma unroll
          for (int i = 0; i < 15; i++) {
            v[i] = par;
            asm volatile("{.reg .pred p; setp.ge.s32 p, %2, %3; @p ld.relaxed.gpu.global.b64 %0, [%1];}" : "+l"(v[i]) : "l"(e15 + i * 64), "r"(m), "r"(15 - i) : "memory");
          }
          bad = (g0 ^ par) | (g1 ^ par);
#pragma unroll
          for (int i = 0; i < 15; i++) bad |= (uint32_t)v[i] ^ par;
        } while ((bad & 1) && ++tries < 200000);
        if (t == 0) TS(3, 2);
        asm volatile("st.shared.u32 [%0], %1;" ::"r"(sb + OFF_GS + t * 4), "r"(g0) : "memory");
        asm volatile("st.shared.u32 [%0], %1;" ::"r"(sb + OFF_GS + 256 + t * 4), "r"(g1) : "memory");
        const cplx l128 = cmul(l64, l64);
#pragma unroll
        for (int i = 0; i < 15; i++) S = cfma(l128, S, cplx{__uint_as_float((uint32_t)v[i] & ~1u), __uint_as_float((uint32_t)(v[i] >> 32))});
      }
      const cplx S1 = cfma(l64, S, cplx{e0.x, e0.y});
      asm volatile("st.shared.v2.f32 [%0], {%1,%2};" ::"r"(sb + OFF_CARRY + t * 8), "f"(S.re), "f"(S.im) : "memory");
      asm volatile("st.shared.v2.f32 [%0], {%1,%2};" ::"r"(sb + OFF_CARRY + 512 + t * 8), "f"(S1.re), "f"(S1.im) : "memory");
      mbar_arrive(sb + OFF_CBAR);
      if (t == 0) TS(3, 3);
    }
  } else {
    const int wg = warp >> 2, w = warp & 3, q = lane & 3, gr = lane >> 2;
    const int c0 = s * 64 + w * 16 + gr + (q & 2) * 4;
    const float pr = bf_ld(lam_re + c0), pi = bf_ld(lam_im + c0), pd = bf_ld(log_dt + c0);
    uint32_t bv[28];
#pragma unroll
    for (int j = 0; j < 28; j++) bv[j] = __ldg(reinterpret_cast<const uint32_t*>(b1 + s * 224 + j * 8) + q);
    asm volatile("setmaxnreg.inc.sync.aligned.u32 224;");
    asm volatile("barrier.cluster.wait.aligned;" ::: "memory");
    TS(wg, 0);
    uint32_t ebar;
    asm volatile("mapa.shared::cluster.u32 %0, %1, %2;" : "=r"(ebar) : "r"(sb + OFF_EMPTY), "r"(lane & 1));
    auto release = [&](int slot) { if (lane < 2) mbar_arrive_cl(ebar + 8 * slot); };
    const uint32_t xw = sb + OFF_X + wg * 8192, fullb = sb + OFF_FULL;
    const uint32_t dxw = (xw & 0x3FFFF) >> 4, dring = ((sb + OFF_RING) & 0x3FFFF) >> 4;

    float ure[32], uim[32], aa[48], ab[64];
    cplx lam[2], coef[2], l16[2], l32[2], lq[2], pre[2], e[2];
    {
      const cplx l1 = make_lam(pr, pi, pd);
      const float inv = __fdividef(1.f, fmaf(pr, pr, pi * pi));
      const cplx cf = cmul(cplx{l1.re - 1.f, l1.im}, cplx{pr * inv, -pi * inv});
      cplx t = cmul(l1, l1); t = cmul(t, t); t = cmul(t, t); t = cmul(t, t);
#pragma unroll
      for (int h = 0; h < 2; h++) {
        lam[h] = cplx{__shfl_sync(0xffffffffu, l1.re, 2 * h, 4), __shfl_sync(0xffffffffu, l1.im, 2 * h, 4)};
        coef[h] = cplx{__shfl_sync(0xffffffffu, cf.re, 2 * h, 4), __shfl_sync(0xffffffffu, cf.im, 2 * h, 4)};
        l16[h] = cplx{__shfl_sync(0xffffffffu, t.re, 2 * h, 4), __shfl_sync(0xffffffffu, t.im, 2 * h, 4)};
      }
    }
    TS(wg, 24);

#pragma unroll
    for (int kb = 0; kb < 8; kb++) {
      const int slot = kb % NSLOT;
      TS2(1, kb);
      mbar_wait(sb + OFF_XFULL + 8 * kb, 0);
      if (kb == 0) TS(wg, 18);
      mbar_wait(fullb + 8 * slot, (kb / NSLOT) & 1);
      TS2(2, kb);
      if (kb == 0) TS(wg, 1);
      wg_fence();
      const uint32_t dxa = dxw + ((kb + xrot) & 7) * 1024;
#pragma unroll
      for (int kk = 0; kk < 4; kk++) {
        wgmma_n64_ss<0, 0, DH128, DH128>(ure, dring, slot * 16384 + kk * 32, dxa, kk * 32, (kb | kk) != 0);
        wgmma_n64_ss<0, 0, DH128, DH128>(uim, dring, slot * 16384 + 8192 + kk * 32, dxa, kk * 32, (kb | kk) != 0);
      }
      wg_commit();
      if (kb > 0) { wg_wait<1>(); release((kb - 1) % NSLOT); }
      if (kb == 0) {
#pragma unroll
        for (int h = 0; h < 2; h++) {
          pin(l16[h].re); pin(l16[h].im);
          l32[h] = cmul(l16[h], l16[h]);
          const cplx a = (q & 1) ? l16[h] : cplx{1.f, 0.f}, c = (q & 2) ? l32[h] : cplx{1.f, 0.f};
          lq[h] = cmul(cmul(a, c), coef[h]);
          pin(lq[h].re); pin(lq[h].im);
        }
      } else {
#pragma unroll
        for (int j = (kb - 1) * 4; j < kb * 4; j++) {
          pin(bv[j]);
          float* d = j < 12 ? aa + 4 * j : ab + 4 * (j - 12);
          d[0] = d[2] = bf_lo(bv[j]); d[1] = d[3] = bf_hi(bv[j]);
          pin(d[0]); pin(d[1]); pin(d[2]); pin(d[3]);
        }
      }
    }
    TS(wg, 2);
#pragma unroll
    for (int kb = 0; kb < 8; kb++) {
      const int u = 8 + kb, slot = u % NSLOT;
      TS2(1, u);
      mbar_wait(fullb + 8 * slot, (u / NSLOT) & 1);
      TS2(2, u);
      wg_fence();
      const uint32_t dxa = dxw + ((kb + xrot) & 7) * 1024;
#pragma unroll
      for (int kk = 0; kk < 4; kk++)
        wgmma_n96_ss<0, 1, DH128, DH64>(aa, dxa, kk * 32, dring, slot * 16384 + (kk >> 1) * 6144 + (kk & 1) * 1024 + lbo(2048), 1);
      wg_commit();
      wg_wait<1>();
      release((u - 1) % NSLOT);
      if (kb == 0) {
        reg_fence(ure); reg_fence(uim);
#pragma unroll
        for (int h = 0; h < 2; h++) e[h] = cplx{ure[2 * h], uim[2 * h]};
      }
      if (kb < 3) {
#pragma unroll
        for (int t = 1 + 5 * kb; t < 6 + 5 * kb; t++)
#pragma unroll
          for (int h = 0; h < 2; h++) { const int i = 4 * (t >> 1) + 2 * h + (t & 1); e[h] = cfma(lam[h], e[h], cplx{ure[i], uim[i]}); }
#pragma unroll
        for (int h = 0; h < 2; h++) { pin(e[h].re); pin(e[h].im); }
      } else if (kb == 3) {
#pragma unroll
        for (int h = 0; h < 2; h++) {
          cplx y = {__shfl_up_sync(0xffffffffu, e[h].re, 1, 4), __shfl_up_sync(0xffffffffu, e[h].im, 1, 4)};
          if (q >= 1) e[h] = cfma(l16[h], y, e[h]);
          y = cplx{__shfl_up_sync(0xffffffffu, e[h].re, 2, 4), __shfl_up_sync(0xffffffffu, e[h].im, 2, 4)};
          if (q >= 2) e[h] = cfma(l32[h], y, e[h]);
        }
        if (q == 3) {
#pragma unroll
          for (int h = 0; h < 2; h++)
            asm volatile("st.shared.v2.f32 [%0], {%1,%2};" ::"r"(sb + OFF_CARRY + wg * 512 + (w * 16 + gr + 8 * h) * 8), "f"(e[h].re), "f"(e[h].im) : "memory");
          mbar_arrive(sb + OFF_GBAR);
        }
#pragma unroll
        for (int h = 0; h < 2; h++) {
          const cplx y = {__shfl_up_sync(0xffffffffu, e[h].re, 1, 4), __shfl_up_sync(0xffffffffu, e[h].im, 1, 4)};
          pre[h] = (q >= 1) ? cmul(coef[h], y) : cplx{0.f, 0.f};
          pin(pre[h].re); pin(pre[h].im);
        }
        TS(wg, 3);
      } else {
#pragma unroll
        for (int i = (kb - 4) * 8; i < (kb - 3) * 8; i++) {
          pin(ure[i]); pin(uim[i]);
          const cplx v = cmul(coef[(i >> 1) & 1], cplx{ure[i], uim[i]});
          ure[i] = v.re; uim[i] = v.im;
          pin(ure[i]); pin(uim[i]);
        }
      }
    }
    TS(wg, 4);
    uint32_t H[56];
    cplx hst[2];
    const uint32_t dh = dxw;
    const uint32_t hst_addr = xw + (w * 16 + (lane & 15)) * 128 + (((lane >> 4) ^ (lane & 7)) << 4);
#pragma unroll
    for (int kb = 0; kb < 8; kb++) {
      const int u = 16 + kb, slot = u % NSLOT;
      TS2(1, u);
      mbar_wait(fullb + 8 * slot, (u / NSLOT) & 1);
      TS2(2, u);
      wg_fence();
#pragma unroll
      for (int kk = 0; kk < 4; kk++)
        wgmma_n128_ss<0, 1, DH128, DH128>(ab, dxw, kb * 16384 + kk * 32, dring, slot * 16384 + kk * 2048 + lbo(8192), 1);
      wg_commit();
      wg_wait<1>();
      release((u - 1) % NSLOT);
      if (kb < 4) {
        const int ch = kb;
#pragma unroll
        for (int i = ch * 6; i < ch * 6 + 6; i++) {
          pin(aa[2 * i]); pin(aa[2 * i + 1]);
          H[i] = pack_bf16(gelu2(aa[2 * i]), gelu2(aa[2 * i + 1]));
          pin(H[i]);
        }
      } else {
        if (kb == 4) {
          TS(wg, 5);
          mbar_wait(sb + OFF_CBAR, 0);
          TS(wg, 6);
#pragma unroll
          for (int h = 0; h < 2; h++) {
            const float2 c = lds_f2(sb + OFF_CARRY + wg * 512 + (w * 16 + gr + 8 * h) * 8);
            hst[h] = cfma(lq[h], cplx{c.x, c.y}, pre[h]);
          }
        }
        const int j0 = (kb - 4) * 2;
        uint32_t rr[4], ri[4];
#pragma unroll
        for (int jj = 0; jj < 2; jj++) {
          const int j = j0 + jj;
          const float2 g2 = lds_f2(sb + OFF_GS + (wg * 64 + j * 8 + q * 2) * 4);
#pragma unroll
          for (int h = 0; h < 2; h++) {
            const int i = 4 * j + 2 * h;
            const cplx h0 = cfma(lam[h], hst[h], cplx{ure[i], uim[i]});
            hst[h] = cfma(lam[h], h0, cplx{ure[i + 1], uim[i + 1]});
            rr[jj * 2 + h] = pack_bf16(h0.re * g2.x, hst[h].re * g2.y);
            ri[jj * 2 + h] = pack_bf16(-h0.im * g2.x, -hst[h].im * g2.y);
          }
        }
        const uint32_t a = hst_addr ^ (j0 << 4);
        asm volatile("stmatrix.sync.aligned.m8n8.x4.shared.b16 [%0], {%1,%2,%3,%4};" ::"r"(a), "r"(rr[0]), "r"(rr[1]), "r"(rr[2]), "r"(rr[3]) : "memory");
        asm volatile("stmatrix.sync.aligned.m8n8.x4.shared.b16 [%0], {%1,%2,%3,%4};" ::"r"(a + 16384), "r"(ri[0]), "r"(ri[1]), "r"(ri[2]), "r"(ri[3]) : "memory");
      }
    }
    TS(wg, 7);

    uint4* const psend = g_part + (size_t)m * (8 * 7 * 1024) + warp * 128;
    const uint4* const precv = g_part + (size_t)(m * 8 + s) * (7 * 1024) + warp * 128 + lane;
    const uint32_t stg = sb + OFF_X + 5 * 16384 + warp * 2048;
    const uint32_t dx0 = ((sb + OFF_X) & 0x3FFFF) >> 4;
    float o[32], rho[2];
    uint32_t r0[16], r1[16], r2[16], sum[16], tag;
    auto send = [&](int p) {
#pragma unroll
      for (int i = 0; i < 4; i++) {
        uint32_t t0;
        asm("lop3.b32 %0, %1, 1, %2, 0xb8;" : "=r"(t0) : "r"(pack_bf16(o[8 * i], o[8 * i + 1])), "r"(tag));
        st_b128(psend + (((s + 1 + p) & 7) * 7 + p) * 1024 + i * 32 + lane, t0, pack_bf16(o[8 * i + 2], o[8 * i + 3]), pack_bf16(o[8 * i + 4], o[8 * i + 5]),
                pack_bf16(o[8 * i + 6], o[8 * i + 7]));
      }
    };
    auto recv_issue = [&](uint32_t (&r)[16], int p) {
#pragma unroll
      for (int i = 0; i < 4; i++) ld_b128(precv + p * 1024 + i * 32, r[4 * i], r[4 * i + 1], r[4 * i + 2], r[4 * i + 3]);
    };
    auto stale = [&](uint32_t (&r)[16]) {
      uint32_t t0, t1;
      asm("lop3.b32 %0, %1, %2, %3, 0x7e;" : "=r"(t0) : "r"(r[0]), "r"(r[4]), "r"(tag));
      asm("lop3.b32 %0, %1, %2, %3, 0x7e;" : "=r"(t1) : "r"(r[8]), "r"(r[12]), "r"(tag));
      return __any_sync(0xffffffffu, (t0 | t1) & 1);
    };
    auto recv_check = [&](uint32_t (&r)[16], int p) {
      if (__builtin_expect(stale(r), 0)) {
        int tries = 0;
#pragma unroll 1
        do { recv_issue(r, p); } while (stale(r) && ++tries < 200000);
      }
    };
    auto gelu_b = [&](int i0, int i1) {
#pragma unroll
      for (int i = i0; i < i1; i++) {
        pin(ab[2 * i]); pin(ab[2 * i + 1]);
        H[24 + i] = pack_bf16(gelu2(ab[2 * i]), gelu2(ab[2 * i + 1]));
        pin(H[24 + i]);
      }
    };
    auto mma = [&](uint32_t wo, int k0, int k1) {
      wg_fence();
#pragma unroll
      for (int k = k0; k < k1; k++) {
        if (k >= 6 && k < 14) {
          const int kk = k - 6;
          wgmma_n64_ss<1, 0, DH128, DH128>(o, dh, (kk >> 2) * 16384 + (kk & 3) * 2048, dx0, wo + 16384 + (kk >> 2) * 8192 + (kk & 3) * 32, 1);
        } else {
          const int kk = k < 6 ? k : k - 8;
          wgmma_n64_rs<1, DH128>(o, H[4 * kk], H[4 * kk + 1], H[4 * kk + 2], H[4 * kk + 3], dx0, wo + (kk / 7) * 32768 + (kk % 7) * 2048, k != 0);
        }
      }
      wg_commit();
    };
    uint32_t rh[2];
#pragma unroll
    for (int p = 0; p < 8; p++) {
      const uint32_t wo = (p % 3) == 1 ? 2 * 16384 : OFF_RING + (p % 3) * 24576;
      if (p == 0) {
        mbar_wait(fullb, 0);
        mma(wo, 0, 3);
        asm volatile("fence.proxy.async.shared::cta;" ::: "memory");
        wg_wait<1>(); release(5);
        gelu_b(0, 4);
        mma(wo, 3, 6);
        gelu_b(4, 10);
        bar_sync(1 + wg, 128);
        mbar_wait(fullb + 8, 0);
        mma(wo, 6, 10);
        gelu_b(10, 16);
        mma(wo, 10, 15);
        gelu_b(16, 24);
        mbar_wait(fullb + 16, 0);
        mma(wo, 15, 18);
        gelu_b(24, 32);
        if (wg == 1) bar_sync(4, 256);
        mma(wo, 18, 22);
      } else {
        mbar_wait(sb + OFF_XFULL + 8 * p, 1);
        if (p == 6) TS(wg, 19);
        bar_sync(3 + wg, 256);
        mma(wo, 0, 22);
      }
      if (p < 7 || wg == 0) bar_arrive(4 - wg, 256);
      if (p == 6) TS(wg, 21);
      if (p == 7) recv_issue(r2, 6);
      if (p == 0 || p >= 3) tag = lds_u(sb + OFF_EPOCH);
      if (p == 1 || p == 2) {
        if (p == 1) {
#pragma unroll
          for (int h = 0; h < 2; h++) {
            rho[h] = lds_f(sb + OFF_GS + (wg * 64 + w * 16 + gr + 8 * h) * 4);
            rh[h] = pack_bf16(0.25f * rho[h], 0.25f * rho[h]);
          }
        }
#pragma unroll
        for (int j = (p - 1) * 4; j < p * 4; j++) {
          const float2 db = lds_f2(sb + OFF_DB + j * 32 + q * 8);
#pragma unroll
          for (int h = 0; h < 2; h++) {
            const uint32_t xd = bf2_mul(lds_u(xw + 7 * 16384 + (w * 16 + gr + 8 * h) * 128 + ((j ^ gr) << 4) + q * 4), __float_as_uint(db.x));
            const uint32_t t = bf2_fma(xd, rh[h], __float_as_uint(db.y));
            sum[2 * j + h] = bf2_add(t, t);
          }
        }
      }
      if (p == 7) {
        recv_check(r0, 4); recv_check(r1, 5);
#pragma unroll
        for (int i = 0; i < 16; i++) sum[i] = bf2_add(sum[i], bf2_add(r0[i], r1[i]));
        TS(wg, 20);
      }
      wg_wait<0>();
      if (p < 5) release(p);
      reg_fence(o);
      if (p == 6) TS(wg, 22);
      if (p < 7) send(p);
      if (p == 6) TS(wg, 23);
      if (p >= 3 && p < 7) {
        recv_check(r0, p - 3);
#pragma unroll
        for (int i = 0; i < 16; i++) sum[i] = bf2_add(sum[i], r0[i]);
      }
      if (p >= 2 && p < 7) recv_issue(r0, p - 2);
      if (p == 6) recv_issue(r1, 5);
      TS(wg, 8 + p);
    }
    {
      float fs[2];
#pragma unroll
      for (int h = 0; h < 2; h++) fs[h] = __fdividef(2.f, 4.f + rho[h]);
#pragma unroll
      for (int i = 0; i < 16; i++) { o[2 * i] = (o[2 * i] + bf_lo(sum[i])) * fs[i & 1]; o[2 * i + 1] = (o[2 * i + 1] + bf_hi(sum[i])) * fs[i & 1]; }
      reg_fence(o);
      tag = lds_u(sb + OFF_EPOCH);
      recv_check(r2, 6);
      TS(wg, 16);
      float* op = out + (size_t)(m * 128 + wg * 64 + (gr >> 1) * 16 + w * 4 + (gr & 1)) * DM + s * 64 + q * 2;
#pragma unroll
      for (int i = 0; i < 16; i++)
        *reinterpret_cast<float2*>(op + (i & 1) * 2 * DM + (i >> 1) * 8) =
            make_float2(fmaf(bf_lo(r2[i]), fs[i & 1], o[2 * i]), fmaf(bf_hi(r2[i]), fs[i & 1], o[2 * i + 1]));
      if (threadIdx.x == 128) g_epoch[b] = tag;
      TS(wg, 17); TG(wg); TDUMP();
    }
  }
}

typedef CUresult (*EncFn)(CUtensorMap*, CUtensorMapDataType, cuuint32_t, void*, const cuuint64_t*, const cuuint64_t*, const cuuint32_t*,
                          const cuuint32_t*, CUtensorMapInterleave, CUtensorMapSwizzle, CUtensorMapL2promotion, CUtensorMapFloatOOBfill);

void encode(EncFn f, CUtensorMap* mp, const void* p, int rank, const cuuint64_t* dims, const cuuint64_t* strides, const cuuint32_t* box, CUtensorMapSwizzle sw) {
  cuuint32_t es[5] = {1, 1, 1, 1, 1};
  f(mp, CU_TENSOR_MAP_DATA_TYPE_BFLOAT16, rank, const_cast<void*>(p), dims, strides, box, es, CU_TENSOR_MAP_INTERLEAVE_NONE, sw,
    CU_TENSOR_MAP_L2_PROMOTION_L2_128B, CU_TENSOR_MAP_FLOAT_OOB_FILL_NONE);
}

}

extern "C" void kernel_launch(void* const* d_in, const int* in_sizes, int n_in, void* d_out, int out_size) {
  typedef const __nv_bfloat16* bp;
  bp x = (bp)d_in[0], lre = (bp)d_in[1], lim = (bp)d_in[2], bre = (bp)d_in[3], bim = (bp)d_in[4], cre = (bp)d_in[5], cim = (bp)d_in[6],
     ldt = (bp)d_in[7], dsk = (bp)d_in[8], w1 = (bp)d_in[10], b1 = (bp)d_in[11], w2 = (bp)d_in[12], b2 = (bp)d_in[13], gw = (bp)d_in[14];
  static EncFn enc = nullptr;
  if (!enc) {
    void* f = nullptr;
    cudaDriverEntryPointQueryResult qr;
    cudaGetDriverEntryPoint("cuTensorMapEncodeTiled", &f, cudaEnableDefault, &qr);
    enc = (EncFn)f;
    cudaFuncSetAttribute(fused_kernel, cudaFuncAttributeMaxDynamicSharedMemorySize, SMEM_BYTES);
  }
  Maps maps;
  {
    cuuint64_t d[5] = {DM, 2, 4, 8, SEQ / 64}, st[4] = {DM * 2, 16 * DM * 2, 2 * DM * 2, 64 * DM * 2};
    cuuint32_t bx[5] = {64, 2, 4, 8, 2};
    encode(enc, &maps.x, x, 5, d, st, bx, CU_TENSOR_MAP_SWIZZLE_128B);
  }
  {
    cuuint64_t d[2] = {DM, DM}, st[1] = {DM * 2};
    cuuint32_t bx[2] = {64, 64};
    encode(enc, &maps.bre, bre, 2, d, st, bx, CU_TENSOR_MAP_SWIZZLE_128B);
    encode(enc, &maps.bim, bim, 2, d, st, bx, CU_TENSOR_MAP_SWIZZLE_128B);
    encode(enc, &maps.cre, cre, 2, d, st, bx, CU_TENSOR_MAP_SWIZZLE_128B);
    encode(enc, &maps.cim, cim, 2, d, st, bx, CU_TENSOR_MAP_SWIZZLE_128B);
  }
  {
    cuuint64_t d[2] = {FF, DM}, st[1] = {FF * 2};
    cuuint32_t bx[2] = {64, 64};
    encode(enc, &maps.w1a, w1, 2, d, st, bx, CU_TENSOR_MAP_SWIZZLE_128B);
    cuuint64_t d3[3] = {32, DM, FF / 32}, st3[2] = {FF * 2, 64};
    cuuint32_t bx3[3] = {32, 32, 3};
    encode(enc, &maps.w1b, w1, 3, d3, st3, bx3, CU_TENSOR_MAP_SWIZZLE_64B);
  }
  {
    cuuint64_t d[2] = {DM, FF}, st[1] = {DM * 2};
    cuuint32_t bx[2] = {64, 56};
    encode(enc, &maps.w2, w2, 2, d, st, bx, CU_TENSOR_MAP_SWIZZLE_128B);
  }
  fused_kernel<<<128, 384, SMEM_BYTES>>>(maps, lre, lim, ldt, dsk, b1, b2, gw, w1, w2, cre, cim, x, bre, bim, (float*)d_out);
}
```

```cpp
#include <cuda_runtime.h>
#include <cuda_bf16.h>
#include <cuda.h>
#include <stdint.h>

#define PF 2
#define SEND_TMA 0
#define PFK 5
namespace {

constexpr int SEQ = 2048, DM = 512, FF = 1792;
constexpr int NSLOT = 6;
constexpr uint32_t OFF_X = 0, OFF_RING = 131072, OFF_MISC = 229376;
constexpr uint32_t OFF_XFULL = OFF_MISC, OFF_FULL = OFF_XFULL + 64, OFF_EMPTY = OFF_FULL + 48, OFF_GBAR = OFF_EMPTY + 48,
                   OFF_CBAR = OFF_GBAR + 8, OFF_EPOCH = OFF_CBAR + 8;
constexpr uint32_t OFF_GS = OFF_MISC + 256;
constexpr uint32_t OFF_CARRY = OFF_GS + 512;
constexpr uint32_t OFF_DB = OFF_CARRY + 1024;
constexpr uint32_t OFF_DBG = OFF_DB + 256;
constexpr uint32_t SMEM_BYTES = OFF_DBG + 768;
static_assert(SMEM_BYTES <= 232448, "smem");

struct Maps { CUtensorMap x, bre, bim, w1a, w1b, w2, cre, cim; };

__device__ uint4 g_part[16 * 8 * 7 * 1024];
__device__ float2 g_end[8 * 16 * 64];
__device__ unsigned g_gate[SEQ];
__device__ unsigned g_epoch[128];
#define TG(role) do {} while (0)
#define TS2(role, i) do {} while (0)
#define TS(role, i) do {} while (0)
#define TDUMP() do {} while (0)

__device__ __forceinline__ void mbar_init(uint32_t bar, uint32_t cnt) { asm volatile("mbarrier.init.shared::cta.b64 [%0], %1;" ::"r"(bar), "r"(cnt)); }
__device__ __forceinline__ void mbar_expect_tx(uint32_t bar, uint32_t bytes) { asm volatile("mbarrier.arrive.expect_tx.shared::cta.b64 _, [%0], %1;" ::"r"(bar), "r"(bytes) : "memory"); }
__device__ __forceinline__ void mbar_arrive(uint32_t bar) { asm volatile("mbarrier.arrive.shared::cta.b64 _, [%0];" ::"r"(bar) : "memory"); }
__device__ __forceinline__ void mbar_arrive_cl(uint32_t cbar) { asm volatile("mbarrier.arrive.shared::cluster.b64 _, [%0];" ::"r"(cbar) : "memory"); }
__device__ __forceinline__ void mbar_wait(uint32_t bar, uint32_t parity) {
  asm volatile(
      "{\n.reg .pred p;\n.reg .u32 c;\n"
      "mbarrier.try_wait.parity.shared::cta.b64 p, [%0], %1;\n"
      "@p bra.uni LAB_DONE;\n"
      "mov.u32 c, 0;\n"
      "LAB_WAIT:\n"
      "mbarrier.try_wait.parity.shared::cta.b64 p, [%0], %1;\n"
      "@p bra.uni LAB_DONE;\n"
      "add.u32 c, c, 1;\nsetp.lt.u32 p, c, 200000;\n@p bra.uni LAB_WAIT;\n"
      "LAB_DONE:\n}" ::"r"(bar), "r"(parity) : "memory");
}
__device__ __forceinline__ void tma2d(uint32_t dst, const CUtensorMap* m, int c0, int c1, uint32_t bar) {
  asm volatile("cp.async.bulk.tensor.2d.shared::cluster.global.mbarrier::complete_tx::bytes [%0], [%1, {%3,%4}], [%2];"
               ::"r"(dst), "l"(m), "r"(bar), "r"(c0), "r"(c1) : "memory");
}
__device__ __forceinline__ void tma2d_mc(uint32_t dst, const CUtensorMap* m, int c0, int c1, uint32_t bar) {
  asm volatile("cp.async.bulk.tensor.2d.shared::cluster.global.mbarrier::complete_tx::bytes.multicast::cluster [%0], [%1, {%3,%4}], [%2], %5;"
               ::"r"(dst), "l"(m), "r"(bar), "r"(c0), "r"(c1), "h"((uint16_t)3) : "memory");
}
__device__ __forceinline__ void tma3d_mc(uint32_t dst, const CUtensorMap* m, int c0, int c1, int c2, uint32_t bar) {
  asm volatile("cp.async.bulk.tensor.3d.shared::cluster.global.mbarrier::complete_tx::bytes.multicast::cluster [%0], [%1, {%3,%4,%5}], [%2], %6;"
               ::"r"(dst), "l"(m), "r"(bar), "r"(c0), "r"(c1), "r"(c2), "h"((uint16_t)3) : "memory");
}
__device__ __forceinline__ void tma5d(uint32_t dst, const CUtensorMap* m, int c0, int c4, uint32_t bar) {
  asm volatile("cp.async.bulk.tensor.5d.shared::cluster.global.mbarrier::complete_tx::bytes [%0], [%1, {%3,%5,%5,%5,%4}], [%2];"
               ::"r"(dst), "l"(m), "r"(bar), "r"(c0), "r"(c4), "r"(0) : "memory");
}
__device__ __forceinline__ void l2_prefetch(const void* p, uint32_t bytes) { asm volatile("cp.async.bulk.prefetch.L2.global [%0], %1;" ::"l"(p), "r"(bytes) : "memory"); }
__device__ __forceinline__ bool elect_one() {
  uint32_t pred;
  asm volatile("{.reg .pred P; elect.sync _|P, 0xffffffff; selp.u32 %0, 1, 0, P;}" : "=r"(pred));
  return pred != 0;
}
__device__ __forceinline__ void wg_fence() { asm volatile("wgmma.fence.sync.aligned;" ::: "memory"); }
__device__ __forceinline__ void wg_commit() { asm volatile("wgmma.commit_group.sync.aligned;" ::: "memory"); }
template <int N> __device__ __forceinline__ void wg_wait() { asm volatile("wgmma.wait_group.sync.aligned %0;" ::"n"(N) : "memory"); }
template <int N> __device__ __forceinline__ void reg_fence(float (&d)[N]) {
#pragma unroll
  for (int i = 0; i < N; i++) asm volatile("" : "+f"(d[i])::"memory");
}
__device__ __forceinline__ void bar_sync(int id, int n) { asm volatile("bar.sync %0, %1;" ::"r"(id), "r"(n) : "memory"); }
__device__ __forceinline__ void bar_arrive(int id, int n) { asm volatile("bar.arrive %0, %1;" ::"r"(id), "r"(n) : "memory"); }
constexpr uint32_t DH128 = (1024 >> 4) | (1u << 30), DH64 = (512 >> 4) | (2u << 30);
__host__ __device__ constexpr uint32_t lbo(uint32_t bytes) { return (bytes >> 4) << 20; }
__device__ __forceinline__ uint32_t pack_bf16(float lo, float hi) { uint32_t r; asm("cvt.rn.bf16x2.f32 %0, %1, %2;" : "=r"(r) : "f"(hi), "f"(lo)); return r; }
__device__ __forceinline__ float bf_lo(uint32_t v) { return __uint_as_float(v << 16); }
__device__ __forceinline__ float bf_hi(uint32_t v) { return __uint_as_float(v & 0xffff0000u); }
__device__ __forceinline__ float bf_ld(const __nv_bfloat16* p) { return __bfloat162float(__ldg(p)); }
__device__ __forceinline__ uint32_t raw_ld(const __nv_bfloat16* p) { return __ldg(reinterpret_cast<const unsigned short*>(p)); }
__device__ __forceinline__ uint32_t late16(uint32_t bar) {
  uint32_t r;
  asm volatile("{.reg .pred p; mbarrier.test_wait.parity.shared::cta.b64 p, [%1], 0; selp.u32 %0, 16, 0, p;}" : "=r"(r) : "r"(bar) : "memory");
  return r;
}
__device__ __forceinline__ float2 lds_f2(uint32_t a) { float2 v; asm volatile("ld.shared.v2.f32 {%0,%1}, [%2];" : "=f"(v.x), "=f"(v.y) : "r"(a)); return v; }
__device__ __forceinline__ float lds_f(uint32_t a) { float v; asm volatile("ld.shared.f32 %0, [%1];" : "=f"(v) : "r"(a)); return v; }
__device__ __forceinline__ uint32_t lds_u(uint32_t a) { uint32_t v; asm volatile("ld.shared.u32 %0, [%1];" : "=r"(v) : "r"(a)); return v; }
__device__ __forceinline__ uint4 lds_u4(uint32_t a) { uint4 v; asm volatile("ld.shared.v4.u32 {%0,%1,%2,%3}, [%4];" : "=r"(v.x), "=r"(v.y), "=r"(v.z), "=r"(v.w) : "r"(a)); return v; }
__device__ __forceinline__ void st_b128(uint4* p, uint32_t a, uint32_t b, uint32_t c, uint32_t d) {
  asm volatile("{.reg .b64 l, h; .reg .b128 v; mov.b64 l, {%1,%2}; mov.b64 h, {%3,%4}; mov.b128 v, {l,h}; st.relaxed.gpu.global.b128 [%0], v;}"
               ::"l"(p), "r"(a), "r"(b), "r"(c), "r"(d) : "memory");
}
__device__ __forceinline__ void ld_b128(const uint4* p, uint32_t& a, uint32_t& b, uint32_t& c, uint32_t& d) {
  asm volatile("{.reg .b64 l, h; .reg .b128 v; ld.relaxed.gpu.global.b128 v, [%4]; mov.b128 {l,h}, v; mov.b64 {%0,%1}, l; mov.b64 {%2,%3}, h;}"
               : "=r"(a), "=r"(b), "=r"(c), "=r"(d) : "l"(p) : "memory");
}
__device__ __forceinline__ float tanh_fast(float x) { float y; asm("tanh.approx.f32 %0, %1;" : "=f"(y) : "f"(x)); return y; }
__device__ __forceinline__ float gelu2(float v) {
  float p = fmaf(v * v, 0.0356774081363f, 0.7978845608029f);
  return fmaf(v, tanh_fast(v * p), v);
}
__device__ __forceinline__ uint32_t bf2_mul(uint32_t a, uint32_t b) { uint32_t r; asm("mul.rn.bf16x2 %0, %1, %2;" : "=r"(r) : "r"(a), "r"(b)); return r; }
__device__ __forceinline__ uint32_t bf2_add(uint32_t a, uint32_t b) { uint32_t r; asm("add.rn.bf16x2 %0, %1, %2;" : "=r"(r) : "r"(a), "r"(b)); return r; }
__device__ __forceinline__ uint32_t bf2_fma(uint32_t a, uint32_t b, uint32_t c) { uint32_t r; asm("fma.rn.bf16x2 %0, %1, %2, %3;" : "=r"(r) : "r"(a), "r"(b), "r"(c)); return r; }
__device__ __forceinline__ void pin(float& a) { asm volatile("" : "+f"(a)::"memory"); }
__device__ __forceinline__ void pin(uint32_t& a) { asm volatile("" : "+r"(a)::"memory"); }
struct cplx { float re, im; };
__device__ __forceinline__ cplx cmul(cplx a, cplx b) { return {fmaf(a.re, b.re, -a.im * b.im), fmaf(a.re, b.im, a.im * b.re)}; }
__device__ __forceinline__ cplx cfma(cplx a, cplx b, cplx c) {
  return {fmaf(a.re, b.re, fmaf(-a.im, b.im, c.re)), fmaf(a.re, b.im, fmaf(a.im, b.re, c.im))};
}
__device__ __forceinline__ cplx make_lam(float lre, float lim, float ldt) {
  float dt = __bfloat162float(__float2bfloat16_rn(expf(ldt)));
  float mag = expf(dt * lre), sn, cs;
  sincospif(dt * lim * 0.31830988618379067f, &sn, &cs);
  return {mag * cs, mag * sn};
}

template<int TA,int TB,uint32_t AH,uint32_t BH> __device__ __forceinline__ void wgmma_n64_ss(float (&d)[32], uint32_t al, uint32_t ao, uint32_t bl, uint32_t bo, int scale_d){
  asm volatile("{.reg .pred p; .reg .b32 t, v; .reg .b64 da, db; setp.ne.b32 p, %36, 0; add.u32 t, %32, %33; mov.b64 da, {t, %39}; add.u32 v, %34, %35; mov.b64 db, {v, %40};\n"
   "wgmma.mma_async.sync.aligned.m64n64k16.f32.bf16.bf16 {%0,%1,%2,%3,%4,%5,%6,%7,%8,%9,%10,%11,%12,%13,%14,%15,%16,%17,%18,%19,%20,%21,%22,%23,%24,%25,%26,%27,%28,%29,%30,%31}, da, db, p, 1, 1, %37, %38;}"
   : "+f"(d[0]),"+f"(d[1]),"+f"(d[2]),"+f"(d[3]),"+f"(d[4]),"+f"(d[5]),"+f"(d[6]),"+f"(d[7]),"+f"(d[8]),"+f"(d[9]),"+f"(d[10]),"+f"(d[11]),"+f"(d[12]),"+f"(d[13]),"+f"(d[14]),"+f"(d[15]),"+f"(d[16]),"+f"(d[17]),"+f"(d[18]),"+f"(d[19]),"+f"(d[20]),"+f"(d[21]),"+f"(d[22]),"+f"(d[23]),"+f"(d[24]),"+f"(d[25]),"+f"(d[26]),"+f"(d[27]),"+f"(d[28]),"+f"(d[29]),"+f"(d[30]),"+f"(d[31])
   : "r"(al),"r"(ao >> 4),"r"(bl),"r"(bo >> 4),"r"(scale_d),"n"(TA),"n"(TB),"n"(AH),"n"(BH));
}
template<int TB,uint32_t BH> __device__ __forceinline__ void wgmma_n64_rs(float (&d)[32], uint32_t a0,uint32_t a1,uint32_t a2,uint32_t a3, uint32_t bl, uint32_t bo, int scale_d){
  asm volatile("{.reg .pred p; .reg .b32 t; .reg .b64 db; setp.ne.b32 p, %38, 0; add.u32 t, %36, %37; mov.b64 db, {t, %40};\n"
   "wgmma.mma_async.sync.aligned.m64n64k16.f32.bf16.bf16 {%0,%1,%2,%3,%4,%5,%6,%7,%8,%9,%10,%11,%12,%13,%14,%15,%16,%17,%18,%19,%20,%21,%22,%23,%24,%25,%26,%27,%28,%29,%30,%31}, {%32,%33,%34,%35}, db, p, 1, 1, %39;}"
   : "+f"(d[0]),"+f"(d[1]),"+f"(d[2]),"+f"(d[3]),"+f"(d[4]),"+f"(d[5]),"+f"(d[6]),"+f"(d[7]),"+f"(d[8]),"+f"(d[9]),"+f"(d[10]),"+f"(d[11]),"+f"(d[12]),"+f"(d[13]),"+f"(d[14]),"+f"(d[15]),"+f"(d[16]),"+f"(d[17]),"+f"(d[18]),"+f"(d[19]),"+f"(d[20]),"+f"(d[21]),"+f"(d[22]),"+f"(d[23]),"+f"(d[24]),"+f"(d[25]),"+f"(d[26]),"+f"(d[27]),"+f"(d[28]),"+f"(d[29]),"+f"(d[30]),"+f"(d[31])
   : "r"(a0),"r"(a1),"r"(a2),"r"(a3),"r"(bl),"r"(bo >> 4),"r"(scale_d),"n"(TB),"n"(BH));
}
template<int TA,int TB,uint32_t AH,uint32_t BH> __device__ __forceinline__ void wgmma_n96_ss(float (&d)[48], uint32_t al, uint32_t ao, uint32_t bl, uint32_t bo, int scale_d){
  asm volatile("{.reg .pred p; .reg .b32 t, v; .reg .b64 da, db; setp.ne.b32 p, %52, 0; add.u32 t, %48, %49; mov.b64 da, {t, %55}; add.u32 v, %50, %51; mov.b64 db, {v, %56};\n"
   "wgmma.mma_async.sync.aligned.m64n96k16.f32.bf16.bf16 {%0,%1,%2,%3,%4,%5,%6,%7,%8,%9,%10,%11,%12,%13,%14,%15,%16,%17,%18,%19,%20,%21,%22,%23,%24,%25,%26,%27,%28,%29,%30,%31,%32,%33,%34,%35,%36,%37,%38,%39,%40,%41,%42,%43,%44,%45,%46,%47}, da, db, p, 1, 1, %53, %54;}"
   : "+f"(d[0]),"+f"(d[1]),"+f"(d[2]),"+f"(d[3]),"+f"(d[4]),"+f"(d[5]),"+f"(d[6]),"+f"(d[7]),"+f"(d[8]),"+f"(d[9]),"+f"(d[10]),"+f"(d[11]),"+f"(d[12]),"+f"(d[13]),"+f"(d[14]),"+f"(d[15]),"+f"(d[16]),"+f"(d[17]),"+f"(d[18]),"+f"(d[19]),"+f"(d[20]),"+f"(d[21]),"+f"(d[22]),"+f"(d[23]),"+f"(d[24]),"+f"(d[25]),"+f"(d[26]),"+f"(d[27]),"+f"(d[28]),"+f"(d[29]),"+f"(d[30]),"+f"(d[31]),"+f"(d[32]),"+f"(d[33]),"+f"(d[34]),"+f"(d[35]),"+f"(d[36]),"+f"(d[37]),"+f"(d[38]),"+f"(d[39]),"+f"(d[40]),"+f"(d[41]),"+f"(d[42]),"+f"(d[43]),"+f"(d[44]),"+f"(d[45]),"+f"(d[46]),"+f"(d[47])
   : "r"(al),"r"(ao >> 4),"r"(bl),"r"(bo >> 4),"r"(scale_d),"n"(TA),"n"(TB),"n"(AH),"n"(BH));
}
template<int TA,int TB,uint32_t AH,uint32_t BH> __device__ __forceinline__ void wgmma_n128_ss(float (&d)[64], uint32_t al, uint32_t ao, uint32_t bl, uint32_t bo, int scale_d){
  asm volatile("{.reg .pred p; .reg .b32 t, v; .reg .b64 da, db; setp.ne.b32 p, %68, 0; add.u32 t, %64, %65; mov.b64 da, {t, %71}; add.u32 v, %66, %67; mov.b64 db, {v, %72};\n"
   "wgmma.mma_async.sync.aligned.m64n128k16.f32.bf16.bf16 {%0,%1,%2,%3,%4,%5,%6,%7,%8,%9,%10,%11,%12,%13,%14,%15,%16,%17,%18,%19,%20,%21,%22,%23,%24,%25,%26,%27,%28,%29,%30,%31,%32,%33,%34,%35,%36,%37,%38,%39,%40,%41,%42,%43,%44,%45,%46,%47,%48,%49,%50,%51,%52,%53,%54,%55,%56,%57,%58,%59,%60,%61,%62,%63}, da, db, p, 1, 1, %69, %70;}"
   : "+f"(d[0]),"+f"(d[1]),"+f"(d[2]),"+f"(d[3]),"+f"(d[4]),"+f"(d[5]),"+f"(d[6]),"+f"(d[7]),"+f"(d[8]),"+f"(d[9]),"+f"(d[10]),"+f"(d[11]),"+f"(d[12]),"+f"(d[13]),"+f"(d[14]),"+f"(d[15]),"+f"(d[16]),"+f"(d[17]),"+f"(d[18]),"+f"(d[19]),"+f"(d[20]),"+f"(d[21]),"+f"(d[22]),"+f"(d[23]),"+f"(d[24]),"+f"(d[25]),"+f"(d[26]),"+f"(d[27]),"+f"(d[28]),"+f"(d[29]),"+f"(d[30]),"+f"(d[31]),"+f"(d[32]),"+f"(d[33]),"+f"(d[34]),"+f"(d[35]),"+f"(d[36]),"+f"(d[37]),"+f"(d[38]),"+f"(d[39]),"+f"(d[40]),"+f"(d[41]),"+f"(d[42]),"+f"(d[43]),"+f"(d[44]),"+f"(d[45]),"+f"(d[46]),"+f"(d[47]),"+f"(d[48]),"+f"(d[49]),"+f"(d[50]),"+f"(d[51]),"+f"(d[52]),"+f"(d[53]),"+f"(d[54]),"+f"(d[55]),"+f"(d[56]),"+f"(d[57]),"+f"(d[58]),"+f"(d[59]),"+f"(d[60]),"+f"(d[61]),"+f"(d[62]),"+f"(d[63])
   : "r"(al),"r"(ao >> 4),"r"(bl),"r"(bo >> 4),"r"(scale_d),"n"(TA),"n"(TB),"n"(AH),"n"(BH));
}

__global__ void __cluster_dims__(2, 1, 1) __launch_bounds__(384, 1)
fused_kernel(const __grid_constant__ Maps maps, const __nv_bfloat16* __restrict__ lam_re,
             const __nv_bfloat16* __restrict__ lam_im, const __nv_bfloat16* __restrict__ log_dt, const __nv_bfloat16* __restrict__ dskip,
             const __nv_bfloat16* __restrict__ b1, const __nv_bfloat16* __restrict__ b2, const __nv_bfloat16* __restrict__ gate_w,
             const __nv_bfloat16* __restrict__ pf_w1, const __nv_bfloat16* __restrict__ pf_w2, const __nv_bfloat16* __restrict__ pf_cre,
             const __nv_bfloat16* __restrict__ pf_cim, const __nv_bfloat16* __restrict__ pf_x,
             const __nv_bfloat16* __restrict__ pf_bre, const __nv_bfloat16* __restrict__ pf_bim, float* __restrict__ out) {
  extern __shared__ __align__(1024) unsigned char smem_raw[];
  const uint32_t sb = (uint32_t)__cvta_generic_to_shared(smem_raw);
  const int b = blockIdx.x;
  const int rank = b & 1, s = (b >> 1) & 7, m = ((b >> 4) << 1) | rank;
  const int warp = __shfl_sync(0xffffffffu, (int)(threadIdx.x >> 5), 0);
  const int lane = threadIdx.x & 31;
  const int xrot = 7 - s;

  if (warp == 8) {
    if (elect_one()) {
      TS(2, 0);
      mbar_init(sb + OFF_XFULL, 1); mbar_init(sb + OFF_FULL, 1); mbar_init(sb + OFF_XFULL + 8, 1);
      asm volatile("fence.mbarrier_init.release.cluster;" ::: "memory");
      asm volatile("fence.proxy.async.shared::cta;" ::: "memory");
      mbar_expect_tx(sb + OFF_XFULL, 16384);
      tma5d(sb + OFF_X + xrot * 16384, &maps.x, 0, 2 * m, sb + OFF_XFULL);
      TS(2, 3);
      mbar_expect_tx(sb + OFF_FULL, 16384);
      tma2d(sb + OFF_RING, &maps.bre, 0, s * 64, sb + OFF_FULL);
      tma2d(sb + OFF_RING + 8192, &maps.bim, 0, s * 64, sb + OFF_FULL);
      mbar_expect_tx(sb + OFF_XFULL + 8, 16384);
      tma5d(sb + OFF_X + ((xrot + 1) & 7) * 16384, &maps.x, 64, 2 * m, sb + OFF_XFULL + 8);
      TS(2, 4);
    }
  } else if (warp < 6) {
    if (elect_one()) {
      mbar_init(sb + OFF_XFULL + 16 + 8 * warp, 1); mbar_init(sb + OFF_EMPTY + 8 * warp, 16);
      if (warp) mbar_init(sb + OFF_FULL + 8 * warp, 1);
      asm volatile("fence.mbarrier_init.release.cluster;" ::: "memory");
    }
  } else if (warp < 8) {
    if (elect_one()) {
      mbar_init(sb + OFF_GBAR + 8 * (warp - 6), warp == 6 ? 64 : 96);
      asm volatile("fence.mbarrier_init.release.cluster;" ::: "memory");
    }
  }
  __syncwarp();
  asm volatile("barrier.cluster.arrive.relaxed.aligned;" ::: "memory");
  if (warp == 8) {
    asm volatile("barrier.cluster.wait.aligned;" ::: "memory");
    if (elect_one()) {
      TS(2, 1);
#pragma unroll 1
      for (int u = 1; u < 7; u++) {
        if (u < 6) {
          mbar_expect_tx(sb + OFF_FULL + 8 * u, 16384);
          tma2d_mc(sb + OFF_RING + u * 16384 + rank * 8192, rank ? &maps.bim : &maps.bre, u * 64, s * 64, sb + OFF_FULL + 8 * u);
        }
        mbar_expect_tx(sb + OFF_XFULL + 8 * (u + 1), 16384);
        tma5d(sb + OFF_X + ((u + 1 + xrot) & 7) * 16384, &maps.x, (u + 1) * 64, 2 * m, sb + OFF_XFULL + 8 * (u + 1));
      }
      TS(2, 5);
    }
    __syncwarp();
  }

  if (warp >= 8) {
    asm volatile("setmaxnreg.dec.sync.aligned.u32 56;");
    if (warp == 8) {
      if (elect_one()) {
        const CUtensorMap* mb = rank ? &maps.bim : &maps.bre;
        const CUtensorMap* mc = rank ? &maps.cim : &maps.cre;
        int slot = 0; uint32_t ph = 0;
#pragma unroll 1
        for (int u = 6; u < 27; u++) {
          const uint32_t fb = sb + OFF_FULL + 8 * slot, dst = sb + OFF_RING + slot * 16384;
          mbar_wait(sb + OFF_EMPTY + 8 * slot, ph);
          TS2(0, u);
          if (u < 8) {
            mbar_expect_tx(fb, 16384);
            tma2d_mc(dst + rank * 8192, mb, u * 64, s * 64, fb);
          } else if (u < 16) {
            mbar_expect_tx(fb, 12288);
            tma3d_mc(dst + rank * 6144, &maps.w1b, 0, (u - 8) * 64 + rank * 32, s * 7, fb);
          } else if (u < 24) {
            mbar_expect_tx(fb, 16384);
            tma2d_mc(dst + rank * 8192, &maps.w1a, s * 224 + 96 + rank * 64, ((u - 15 + s) & 7) * 64, fb);
          } else if (u == 25) {
            mbar_expect_tx(fb, 16384);
            tma2d_mc(dst + rank * 8192, mc, s * 64, ((s + 1) & 7) * 64, fb);
          } else {
            mbar_expect_tx(fb, 14336);
            tma2d_mc(dst + rank * 7168, &maps.w2, ((s + 1) & 7) * 64, s * 224 + (u - 24) * 56 + rank * 56, fb);
          }
          if (++slot == NSLOT) { slot = 0; ph ^= 1; }
        }
#pragma unroll 1
        for (int p = 1; p < 8; p++) {
          const int piece = (s + 1 + p) & 7, grp = p % 3;
          const uint32_t fb = sb + OFF_XFULL + 8 * p, dst = grp == 1 ? sb + OFF_X + 2 * 16384 : sb + OFF_RING + grp * 24576;
          if (p >= 3) mbar_wait(sb + OFF_EMPTY + 8 * (p - 3), 0);
          else if (p == 2) mbar_wait(sb + OFF_EMPTY + 40, 1);
          TS2(0, 32 + p);
          mbar_expect_tx(fb, 45056);
          tma2d_mc(dst + rank * 7168, &maps.w2, piece * 64, s * 224 + rank * 56, fb);
          tma2d_mc(dst + 16384 + rank * 8192, mc, s * 64, piece * 64, fb);
          tma2d_mc(dst + 32768 + rank * 7168, &maps.w2, piece * 64, s * 224 + 112 + rank * 56, fb);
        }
        TS(2, 2);
      }
    } else if (warp == 11) {
      if (lane == 0) TG(2);
      const uint4* gwp = reinterpret_cast<const uint4*>(gate_w) + (lane & 7);
      uint4 gw[4];
#pragma unroll
      for (int i = 0; i < 4; i++) gw[i] = __ldg(gwp + i * 8);
      unsigned par;
      asm volatile("ld.relaxed.gpu.global.u32 %0, [%1];" : "=r"(par) : "l"(g_epoch + b) : "memory");
      const uint32_t dk = __ldg(reinterpret_cast<const uint32_t*>(dskip + s * 64) + lane), bb = __ldg(reinterpret_cast<const uint32_t*>(b2 + s * 64) + lane);
      asm volatile("barrier.cluster.wait.aligned;" ::: "memory");
      const int row = s * 16 + (lane >> 3);
      const uint32_t xr0 = sb + OFF_X + row * 128 + (((lane & 7) ^ (row & 7)) << 4), xr1 = (xr0 + 512) ^ 64;
      float z[4] = {0.f, 0.f, 0.f, 0.f};
#pragma unroll
      for (int kb = 0; kb < 8; kb++) {
        const uint32_t wv[4] = {gw[kb & 3].x, gw[kb & 3].y, gw[kb & 3].z, gw[kb & 3].w};
        if (kb < 4) gw[kb] = __ldg(gwp + (kb + 4) * 8);
        mbar_wait(sb + OFF_XFULL + 8 * kb, 0);
        if ((PF & 2) && kb == PFK && elect_one()) {
          l2_prefetch(pf_w1 + b * 7168, 14336);
          l2_prefetch(pf_cre + b * 2048, 4096);
          l2_prefetch(pf_cim + b * 2048, 4096);
          l2_prefetch(pf_w2 + b * 7168, 14336);
        }
        const uint32_t xo = ((kb + xrot) & 7) * 16384;
#pragma unroll
        for (int r = 0; r < 4; r++) {
          const uint4 a = lds_u4(((r & 1) ? xr1 : xr0) + xo + (r >> 1) * 1024);
          const uint32_t p0 = bf2_mul(a.x, wv[0]), p1 = bf2_mul(a.y, wv[1]), p2 = bf2_mul(a.z, wv[2]), p3 = bf2_mul(a.w, wv[3]);
          z[r] += ((bf_lo(p0) + bf_hi(p0)) + (bf_lo(p1) + bf_hi(p1))) + ((bf_lo(p2) + bf_hi(p2)) + (bf_lo(p3) + bf_hi(p3)));
        }
      }
      asm volatile("st.shared.v2.u32 [%0], {%1,%2};" ::"r"(sb + OFF_DB + lane * 8), "r"(dk), "r"(bb) : "memory");
      if (lane == 0) asm volatile("st.shared.u32 [%0], %1;" ::"r"(sb + OFF_EPOCH), "r"(par + 1) : "memory");
      par = (par + 1) & 1;
      {
        float y0 = (lane & 4) ? z[1] : z[0], y1 = (lane & 4) ? z[3] : z[2];
        y0 += __shfl_xor_sync(0xffffffffu, (lane & 4) ? z[0] : z[1], 4);
        y1 += __shfl_xor_sync(0xffffffffu, (lane & 4) ? z[2] : z[3], 4);
        float zz = (lane & 2) ? y1 : y0;
        zz += __shfl_xor_sync(0xffffffffu, (lane & 2) ? y0 : y1, 2);
        zz += __shfl_xor_sync(0xffffffffu, zz, 1);
        const float rho = 4.f * expf(zz > 40.f ? 40.f : zz);
        if ((lane & 1) == 0)
          asm volatile("st.relaxed.gpu.global.u32 [%0], %1;" ::"l"(g_gate + m * 128 + row + (lane & 4) + (lane & 2) * 4), "r"((__float_as_uint(rho) & ~1u) | par) : "memory");
      }
      if (lane == 0) TS(3, 0);
      mbar_wait(sb + OFF_GBAR, 0);
      uint32_t g0, g1, g2, g3;
      int tries = 0;
#pragma unroll 1
      do {
        asm volatile("ld.relaxed.gpu.global.v4.u32 {%0,%1,%2,%3}, [%4];" : "=r"(g0), "=r"(g1), "=r"(g2), "=r"(g3) : "l"(g_gate + m * 128 + lane * 4) : "memory");
      } while ((((g0 ^ par) | (g1 ^ par) | (g2 ^ par) | (g3 ^ par)) & 1) && ++tries < 200000);
      asm volatile("st.shared.v4.u32 [%0], {%1,%2,%3,%4};" ::"r"(sb + OFF_GS + lane * 16), "r"(g0), "r"(g1), "r"(g2), "r"(g3) : "memory");
      mbar_arrive(sb + OFF_CBAR);
      if (lane == 0) TS(3, 4);
    } else {
      const int t = threadIdx.x - 288;
      unsigned par;
      asm volatile("ld.relaxed.gpu.global.u32 %0, [%1];" : "=r"(par) : "l"(g_epoch + b) : "memory");
      const float pr = bf_ld(lam_re + s * 64 + t), pi = bf_ld(lam_im + s * 64 + t), pd = bf_ld(log_dt + s * 64 + t);
      asm volatile("barrier.cluster.wait.aligned;" ::: "memory");
      par = (par + 1) & 1;
      cplx l64 = make_lam(pr, pi, pd);
#pragma unroll
      for (int i = 0; i < 6; i++) l64 = cmul(l64, l64);
      cplx l128 = cmul(l64, l64);
      pin(l128.re); pin(l128.im);
      mbar_wait(sb + OFF_GBAR, 0);
      const float2 e0 = lds_f2(sb + OFF_CARRY + t * 8), e1 = lds_f2(sb + OFF_CARRY + 512 + t * 8);
      float2* eb = g_end + s * 1024 + t;
      {
        const cplx e = cfma(l64, cplx{e0.x, e0.y}, cplx{e1.x, e1.y});
        const unsigned long long v = ((unsigned long long)__float_as_uint(e.im) << 32) | ((__float_as_uint(e.re) & ~1u) | par);
        asm volatile("st.relaxed.gpu.global.b64 [%0], %1;" ::"l"(eb + m * 64), "l"(v) : "memory");
      }
      if (t == 0) TS(3, 1);
      cplx S = {0.f, 0.f};
      {
        unsigned long long v[15];
        uint32_t bad;
        int tries = 0;
        const float2* e15 = eb + (m - 15) * 64;
#pragma unroll 1
        do {
#pragma unroll
          for (int i = 0; i < 15; i++) {
            v[i] = par;
            asm volatile("{.reg .pred p; setp.ge.s32 p, %2, %3; @p ld.relaxed.gpu.global.b64 %0, [%1];}" : "+l"(v[i]) : "l"(e15 + i * 64), "r"(m), "r"(15 - i) : "memory");
          }
          bad = 0;
#pragma unroll
          for (int i = 0; i < 15; i++) bad |= (uint32_t)v[i] ^ par;
        } while ((bad & 1) && ++tries < 200000);
        if (t == 0) TS(3, 2);
#pragma unroll
        for (int i = 0; i < 15; i++) S = cfma(l128, S, cplx{__uint_as_float((uint32_t)v[i] & ~1u), __uint_as_float((uint32_t)(v[i] >> 32))});
      }
      const cplx S1 = cfma(l64, S, cplx{e0.x, e0.y});
      asm volatile("st.shared.v2.f32 [%0], {%1,%2};" ::"r"(sb + OFF_CARRY + t * 8), "f"(S.re), "f"(S.im) : "memory");
      asm volatile("st.shared.v2.f32 [%0], {%1,%2};" ::"r"(sb + OFF_CARRY + 512 + t * 8), "f"(S1.re), "f"(S1.im) : "memory");
      mbar_arrive(sb + OFF_CBAR);
      if (t == 0) TS(3, 3);
    }
  } else {
    const int wg = warp >> 2, w = warp & 3, q = lane & 3, gr = lane >> 2;
    const int c0 = s * 64 + w * 16 + gr + (q & 2) * 4;
    const uint32_t prr = raw_ld(lam_re + c0), pir = raw_ld(lam_im + c0), pdr = raw_ld(log_dt + c0);
    uint32_t bv[28];
#pragma unroll
    for (int j = 0; j < 28; j++) bv[j] = __ldg(reinterpret_cast<const uint32_t*>(b1 + s * 224 + j * 8) + q);
    asm volatile("setmaxnreg.inc.sync.aligned.u32 224;");
    asm volatile("barrier.cluster.wait.aligned;" ::: "memory");
    TS(wg, 0);
    uint32_t ebar;
    asm volatile("mapa.shared::cluster.u32 %0, %1, %2;" : "=r"(ebar) : "r"(sb + OFF_EMPTY), "r"(lane & 1));
    auto release = [&](int slot) { if (lane < 2) mbar_arrive_cl(ebar + 8 * slot); };
    const uint32_t xw = sb + OFF_X + wg * 8192, fullb = sb + OFF_FULL;
    const uint32_t dxw = (xw & 0x3FFFF) >> 4, dring = ((sb + OFF_RING) & 0x3FFFF) >> 4;

    float ure[32], uim[32], aa[48], ab[64];
    cplx lam[2], coef[2], l16[2], l32[2], lq[2], pre[2], e[2];
    cplx l1, cf;
    uint32_t sh16, mhi;
    TS(wg, 24);

#pragma unroll
    for (int kb = 0; kb < 8; kb++) {
      const int slot = kb % NSLOT;
      TS2(1, kb);
      mbar_wait(sb + OFF_XFULL + 8 * kb, 0);
      if (kb == 0) TS(wg, 18);
      mbar_wait(fullb + 8 * slot, (kb / NSLOT) & 1);
      TS2(2, kb);
      if (kb == 0) TS(wg, 1);
      wg_fence();
      const uint32_t dxa = dxw + ((kb + xrot) & 7) * 1024;
#pragma unroll
      for (int kk = 0; kk < 4; kk++) {
        wgmma_n64_ss<0, 0, DH128, DH128>(ure, dring, slot * 16384 + kk * 32, dxa, kk * 32, (kb | kk) != 0);
        wgmma_n64_ss<0, 0, DH128, DH128>(uim, dring, slot * 16384 + 8192 + kk * 32, dxa, kk * 32, (kb | kk) != 0);
      }
      wg_commit();
      if (kb > 0) { wg_wait<1>(); release((kb - 1) % NSLOT); }
      if (kb == 2) {
        sh16 = late16(sb + OFF_XFULL); mhi = 0xffffffffu << sh16;
        l1 = make_lam(__uint_as_float(prr << sh16), __uint_as_float(pir << sh16), __uint_as_float(pdr << sh16));
        pin(l1.re); pin(l1.im);
      }
      if (kb == 3) {
        const float pr = __uint_as_float(prr << sh16), pi = __uint_as_float(pir << sh16);
        const float inv = __fdividef(1.f, fmaf(pr, pr, pi * pi));
        cf = cmul(cplx{l1.re - 1.f, l1.im}, cplx{pr * inv, -pi * inv});
        cplx t = cmul(l1, l1); t = cmul(t, t); t = cmul(t, t); t = cmul(t, t);
#pragma unroll
        for (int h = 0; h < 2; h++) {
          lam[h] = cplx{__shfl_sync(0xffffffffu, l1.re, 2 * h, 4), __shfl_sync(0xffffffffu, l1.im, 2 * h, 4)};
          coef[h] = cplx{__shfl_sync(0xffffffffu, cf.re, 2 * h, 4), __shfl_sync(0xffffffffu, cf.im, 2 * h, 4)};
          l16[h] = cplx{__shfl_sync(0xffffffffu, t.re, 2 * h, 4), __shfl_sync(0xffffffffu, t.im, 2 * h, 4)};
        }
      }
      if (kb == 4) {
#pragma unroll
        for (int h = 0; h < 2; h++) {
          pin(l16[h].re); pin(l16[h].im);
          l32[h] = cmul(l16[h], l16[h]);
          const cplx a = (q & 1) ? l16[h] : cplx{1.f, 0.f}, c = (q & 2) ? l32[h] : cplx{1.f, 0.f};
          lq[h] = cmul(cmul(a, c), coef[h]);
          pin(lq[h].re); pin(lq[h].im);
        }
      }
      if (kb >= 4) {
#pragma unroll
        for (int j = (kb - 4) * 7; j < (kb - 3) * 7; j++) {
          pin(bv[j]);
          float* d = j < 12 ? aa + 4 * j : ab + 4 * (j - 12);
          d[0] = d[2] = __uint_as_float(bv[j] << sh16); d[1] = d[3] = __uint_as_float(bv[j] & mhi);
          pin(d[0]); pin(d[1]); pin(d[2]); pin(d[3]);
        }
      }
    }
    TS(wg, 2);
#pragma unroll
    for (int kb = 0; kb < 8; kb++) {
      const int u = 8 + kb, slot = u % NSLOT;
      TS2(1, u);
      mbar_wait(fullb + 8 * slot, (u / NSLOT) & 1);
      TS2(2, u);
      wg_fence();
      const uint32_t dxa = dxw + ((kb + xrot) & 7) * 1024;
#pragma unroll
      for (int kk = 0; kk < 4; kk++)
        wgmma_n96_ss<0, 1, DH128, DH64>(aa, dxa, kk * 32, dring, slot * 16384 + (kk >> 1) * 6144 + (kk & 1) * 1024 + lbo(2048), 1);
      wg_commit();
      wg_wait<1>();
      release((u - 1) % NSLOT);
      if (kb == 0) {
        reg_fence(ure); reg_fence(uim);
#pragma unroll
        for (int h = 0; h < 2; h++) e[h] = cplx{ure[2 * h], uim[2 * h]};
      }
      if (kb < 3) {
#pragma unroll
        for (int t = 1 + 5 * kb; t < 6 + 5 * kb; t++)
#pragma unroll
          for (int h = 0; h < 2; h++) { const int i = 4 * (t >> 1) + 2 * h + (t & 1); e[h] = cfma(lam[h], e[h], cplx{ure[i], uim[i]}); }
#pragma unroll
        for (int h = 0; h < 2; h++) { pin(e[h].re); pin(e[h].im); }
      } else if (kb == 3) {
#pragma unroll
        for (int h = 0; h < 2; h++) {
          cplx y = {__shfl_up_sync(0xffffffffu, e[h].re, 1, 4), __shfl_up_sync(0xffffffffu, e[h].im, 1, 4)};
          if (q >= 1) e[h] = cfma(l16[h], y, e[h]);
          y = cplx{__shfl_up_sync(0xffffffffu, e[h].re, 2, 4), __shfl_up_sync(0xffffffffu, e[h].im, 2, 4)};
          if (q >= 2) e[h] = cfma(l32[h], y, e[h]);
        }
        if (q == 3) {
#pragma unroll
          for (int h = 0; h < 2; h++)
            asm volatile("st.shared.v2.f32 [%0], {%1,%2};" ::"r"(sb + OFF_CARRY + wg * 512 + (w * 16 + gr + 8 * h) * 8), "f"(e[h].re), "f"(e[h].im) : "memory");
          mbar_arrive(sb + OFF_GBAR);
        }
#pragma unroll
        for (int h = 0; h < 2; h++) {
          const cplx y = {__shfl_up_sync(0xffffffffu, e[h].re, 1, 4), __shfl_up_sync(0xffffffffu, e[h].im, 1, 4)};
          pre[h] = (q >= 1) ? cmul(coef[h], y) : cplx{0.f, 0.f};
          pin(pre[h].re); pin(pre[h].im);
        }
        TS(wg, 3);
      } else {
#pragma unroll
        for (int i = (kb - 4) * 8; i < (kb - 3) * 8; i++) {
          pin(ure[i]); pin(uim[i]);
          const cplx v = cmul(coef[(i >> 1) & 1], cplx{ure[i], uim[i]});
          ure[i] = v.re; uim[i] = v.im;
          pin(ure[i]); pin(uim[i]);
        }
      }
    }
    TS(wg, 4);
    uint32_t H[56];
    cplx hst[2];
    const uint32_t dh = dxw;
    const uint32_t hst_addr = xw + (w * 16 + (lane & 15)) * 128 + (((lane >> 4) ^ (lane & 7)) << 4);
#pragma unroll
    for (int kb = 0; kb < 8; kb++) {
      const int u = 16 + kb, slot = u % NSLOT;
      TS2(1, u);
      mbar_wait(fullb + 8 * slot, (u / NSLOT) & 1);
      TS2(2, u);
      wg_fence();
#pragma unroll
      for (int kk = 0; kk < 4; kk++)
        wgmma_n128_ss<0, 1, DH128, DH128>(ab, dxw, kb * 16384 + kk * 32, dring, slot * 16384 + kk * 2048 + lbo(8192), 1);
      wg_commit();
      wg_wait<1>();
      release((u - 1) % NSLOT);
      if (kb < 4) {
        const int ch = kb;
#pragma unroll
        for (int i = ch * 6; i < ch * 6 + 6; i++) {
          pin(aa[2 * i]); pin(aa[2 * i + 1]);
          H[i] = pack_bf16(gelu2(aa[2 * i]), gelu2(aa[2 * i + 1]));
          pin(H[i]);
        }
      } else {
        if (kb == 4) {
          TS(wg, 5);
          mbar_wait(sb + OFF_CBAR, 0);
          TS(wg, 6);
#pragma unroll
          for (int h = 0; h < 2; h++) {
            const float2 c = lds_f2(sb + OFF_CARRY + wg * 512 + (w * 16 + gr + 8 * h) * 8);
            hst[h] = cfma(lq[h], cplx{c.x, c.y}, pre[h]);
          }
        }
        const int j0 = (kb - 4) * 2;
        uint32_t rr[4], ri[4];
#pragma unroll
        for (int jj = 0; jj < 2; jj++) {
          const int j = j0 + jj;
          const float2 g2 = lds_f2(sb + OFF_GS + (wg * 64 + j * 8 + q * 2) * 4);
#pragma unroll
          for (int h = 0; h < 2; h++) {
            const int i = 4 * j + 2 * h;
            const cplx h0 = cfma(lam[h], hst[h], cplx{ure[i], uim[i]});
            hst[h] = cfma(lam[h], h0, cplx{ure[i + 1], uim[i + 1]});
            rr[jj * 2 + h] = pack_bf16(h0.re * g2.x, hst[h].re * g2.y);
            ri[jj * 2 + h] = pack_bf16(-h0.im * g2.x, -hst[h].im * g2.y);
          }
        }
        const uint32_t a = hst_addr ^ (j0 << 4);
        asm volatile("stmatrix.sync.aligned.m8n8.x4.shared.b16 [%0], {%1,%2,%3,%4};" ::"r"(a), "r"(rr[0]), "r"(rr[1]), "r"(rr[2]), "r"(rr[3]) : "memory");
        asm volatile("stmatrix.sync.aligned.m8n8.x4.shared.b16 [%0], {%1,%2,%3,%4};" ::"r"(a + 16384), "r"(ri[0]), "r"(ri[1]), "r"(ri[2]), "r"(ri[3]) : "memory");
      }
    }
    TS(wg, 7);

    uint4* const psend = g_part + (size_t)m * (8 * 7 * 1024) + warp * 128;
    const uint4* const precv = g_part + (size_t)(m * 8 + s) * (7 * 1024) + warp * 128 + lane;
    const uint32_t stg = sb + OFF_X + 5 * 16384 + warp * 2048;
    const uint32_t dx0 = ((sb + OFF_X) & 0x3FFFF) >> 4;
    float o[32], rho[2];
    uint32_t r0[16], r1[16], r2[16], sum[16], tag;
    auto send = [&](int p) {
#pragma unroll
      for (int i = 0; i < 4; i++) {
        uint32_t t0;
        asm("lop3.b32 %0, %1, 1, %2, 0xb8;" : "=r"(t0) : "r"(pack_bf16(o[8 * i], o[8 * i + 1])), "r"(tag));
        st_b128(psend + (((s + 1 + p) & 7) * 7 + p) * 1024 + i * 32 + lane, t0, pack_bf16(o[8 * i + 2], o[8 * i + 3]), pack_bf16(o[8 * i + 4], o[8 * i + 5]),
                pack_bf16(o[8 * i + 6], o[8 * i + 7]));
      }
    };
    auto recv_issue = [&](uint32_t (&r)[16], int p) {
#pragma unroll
      for (int i = 0; i < 4; i++) ld_b128(precv + p * 1024 + i * 32, r[4 * i], r[4 * i + 1], r[4 * i + 2], r[4 * i + 3]);
    };
    auto stale = [&](uint32_t (&r)[16]) {
      uint32_t t0, t1;
      asm("lop3.b32 %0, %1, %2, %3, 0x7e;" : "=r"(t0) : "r"(r[0]), "r"(r[4]), "r"(tag));
      asm("lop3.b32 %0, %1, %2, %3, 0x7e;" : "=r"(t1) : "r"(r[8]), "r"(r[12]), "r"(tag));
      return __any_sync(0xffffffffu, (t0 | t1) & 1);
    };
    auto recv_check = [&](uint32_t (&r)[16], int p) {
      if (__builtin_expect(stale(r), 0)) {
        int tries = 0;
#pragma unroll 1
        do { recv_issue(r, p); } while (stale(r) && ++tries < 200000);
      }
    };
    auto gelu_b = [&](int i0, int i1) {
#pragma unroll
      for (int i = i0; i < i1; i++) {
        pin(ab[2 * i]); pin(ab[2 * i + 1]);
        H[24 + i] = pack_bf16(gelu2(ab[2 * i]), gelu2(ab[2 * i + 1]));
        pin(H[24 + i]);
      }
    };
    auto mma = [&](uint32_t wo, int k0, int k1) {
      wg_fence();
#pragma unroll
      for (int k = k0; k < k1; k++) {
        if (k >= 6 && k < 14) {
          const int kk = k - 6;
          wgmma_n64_ss<1, 0, DH128, DH128>(o, dh, (kk >> 2) * 16384 + (kk & 3) * 2048, dx0, wo + 16384 + (kk >> 2) * 8192 + (kk & 3) * 32, 1);
        } else {
          const int kk = k < 6 ? k : k - 8;
          wgmma_n64_rs<1, DH128>(o, H[4 * kk], H[4 * kk + 1], H[4 * kk + 2], H[4 * kk + 3], dx0, wo + (kk / 7) * 32768 + (kk % 7) * 2048, k != 0);
        }
      }
      wg_commit();
    };
    uint32_t rh[2];
#pragma unroll
    for (int p = 0; p < 8; p++) {
      const uint32_t wo = (p % 3) == 1 ? 2 * 16384 : OFF_RING + (p % 3) * 24576;
      if (p == 0) {
        mbar_wait(fullb, 0);
        mma(wo, 0, 3);
        asm volatile("fence.proxy.async.shared::cta;" ::: "memory");
        wg_wait<1>(); release(5);
        gelu_b(0, 4);
        mma(wo, 3, 6);
        gelu_b(4, 10);
        bar_sync(1 + wg, 128);
        mbar_wait(fullb + 8, 0);
        mma(wo, 6, 10);
        gelu_b(10, 16);
        mma(wo, 10, 15);
        gelu_b(16, 24);
        mbar_wait(fullb + 16, 0);
        mma(wo, 15, 18);
        gelu_b(24, 32);
        if (wg == 1) bar_sync(4, 256);
        mma(wo, 18, 22);
      } else {
        mbar_wait(sb + OFF_XFULL + 8 * p, 1);
        if (p == 6) TS(wg, 19);
        bar_sync(3 + wg, 256);
        mma(wo, 0, 22);
      }
      if (p < 7 || wg == 0) bar_arrive(4 - wg, 256);
      if (p == 6) TS(wg, 21);
      if (p == 7) recv_issue(r2, 6);
      if (p == 0 || p >= 3) tag = lds_u(sb + OFF_EPOCH);
      if (p == 1 || p == 2) {
        if (p == 1) {
#pragma unroll
          for (int h = 0; h < 2; h++) {
            rho[h] = lds_f(sb + OFF_GS + (wg * 64 + w * 16 + gr + 8 * h) * 4);
            rh[h] = pack_bf16(0.25f * rho[h], 0.25f * rho[h]);
          }
        }
#pragma unroll
        for (int j = (p - 1) * 4; j < p * 4; j++) {
          const float2 db = lds_f2(sb + OFF_DB + j * 32 + q * 8);
#pragma unroll
          for (int h = 0; h < 2; h++) {
            const uint32_t xd = bf2_mul(lds_u(xw + 7 * 16384 + (w * 16 + gr + 8 * h) * 128 + ((j ^ gr) << 4) + q * 4), __float_as_uint(db.x));
            const uint32_t t = bf2_fma(xd, rh[h], __float_as_uint(db.y));
            sum[2 * j + h] = bf2_add(t, t);
          }
        }
      }
      if (p >= 3) {
        recv_check(r0, p - 3);
        if (p == 7) recv_check(r1, 5);
#pragma unroll
        for (int i = 0; i < 16; i++) sum[i] = bf2_add(sum[i], p == 7 ? bf2_add(r0[i], r1[i]) : r0[i]);
        if (p == 7) TS(wg, 20);
      }
      if (p >= 2 && p < 7) recv_issue(r0, p - 2);
      wg_wait<0>();
      if (p < 5) release(p);
      reg_fence(o);
      if (p == 6) TS(wg, 22);
      if (p < 7) send(p);
      if (p == 6) TS(wg, 23);
      if (p == 6) recv_issue(r1, 5);
      TS(wg, 8 + p);
    }
    {
      float fs[2];
#pragma unroll
      for (int h = 0; h < 2; h++) fs[h] = __fdividef(2.f, 4.f + rho[h]);
#pragma unroll
      for (int i = 0; i < 16; i++) { o[2 * i] = (o[2 * i] + bf_lo(sum[i])) * fs[i & 1]; o[2 * i + 1] = (o[2 * i + 1] + bf_hi(sum[i])) * fs[i & 1]; }
      reg_fence(o);
      tag = lds_u(sb + OFF_EPOCH);
      recv_check(r2, 6);
      TS(wg, 16);
      float* op = out + (size_t)(m * 128 + wg * 64 + (gr >> 1) * 16 + w * 4 + (gr & 1)) * DM + s * 64 + q * 2;
#pragma unroll
      for (int i = 0; i < 16; i++)
        *reinterpret_cast<float2*>(op + (i & 1) * 2 * DM + (i >> 1) * 8) =
            make_float2(fmaf(bf_lo(r2[i]), fs[i & 1], o[2 * i]), fmaf(bf_hi(r2[i]), fs[i & 1], o[2 * i + 1]));
      if (threadIdx.x == 128) g_epoch[b] = tag;
      TS(wg, 17); TG(wg); TDUMP();
    }
  }
}

typedef CUresult (*EncFn)(CUtensorMap*, CUtensorMapDataType, cuuint32_t, void*, const cuuint64_t*, const cuuint64_t*, const cuuint32_t*,
                          const cuuint32_t*, CUtensorMapInterleave, CUtensorMapSwizzle, CUtensorMapL2promotion, CUtensorMapFloatOOBfill);

void encode(EncFn f, CUtensorMap* mp, const void* p, int rank, const cuuint64_t* dims, const cuuint64_t* strides, const cuuint32_t* box, CUtensorMapSwizzle sw) {
  cuuint32_t es[5] = {1, 1, 1, 1, 1};
  f(mp, CU_TENSOR_MAP_DATA_TYPE_BFLOAT16, rank, const_cast<void*>(p), dims, strides, box, es, CU_TENSOR_MAP_INTERLEAVE_NONE, sw,
    CU_TENSOR_MAP_L2_PROMOTION_L2_128B, CU_TENSOR_MAP_FLOAT_OOB_FILL_NONE);
}

}

extern "C" void kernel_launch(void* const* d_in, const int* in_sizes, int n_in, void* d_out, int out_size) {
  typedef const __nv_bfloat16* bp;
  bp x = (bp)d_in[0], lre = (bp)d_in[1], lim = (bp)d_in[2], bre = (bp)d_in[3], bim = (bp)d_in[4], cre = (bp)d_in[5], cim = (bp)d_in[6],
     ldt = (bp)d_in[7], dsk = (bp)d_in[8], w1 = (bp)d_in[10], b1 = (bp)d_in[11], w2 = (bp)d_in[12], b2 = (bp)d_in[13], gw = (bp)d_in[14];
  static EncFn enc = nullptr;
  if (!enc) {
    void* f = nullptr;
    cudaDriverEntryPointQueryResult qr;
    cudaGetDriverEntryPoint("cuTensorMapEncodeTiled", &f, cudaEnableDefault, &qr);
    enc = (EncFn)f;
    cudaFuncSetAttribute(fused_kernel, cudaFuncAttributeMaxDynamicSharedMemorySize, SMEM_BYTES);
  }
  Maps maps;
  {
    cuuint64_t d[5] = {DM, 2, 4, 8, SEQ / 64}, st[4] = {DM * 2, 16 * DM * 2, 2 * DM * 2, 64 * DM * 2};
    cuuint32_t bx[5] = {64, 2, 4, 8, 2};
    encode(enc, &maps.x, x, 5, d, st, bx, CU_TENSOR_MAP_SWIZZLE_128B);
  }
  {
    cuuint64_t d[2] = {DM, DM}, st[1] = {DM * 2};
    cuuint32_t bx[2] = {64, 64};
    encode(enc, &maps.bre, bre, 2, d, st, bx, CU_TENSOR_MAP_SWIZZLE_128B);
    encode(enc, &maps.bim, bim, 2, d, st, bx, CU_TENSOR_MAP_SWIZZLE_128B);
    encode(enc, &maps.cre, cre, 2, d, st, bx, CU_TENSOR_MAP_SWIZZLE_128B);
    encode(enc, &maps.cim, cim, 2, d, st, bx, CU_TENSOR_MAP_SWIZZLE_128B);
  }
  {
    cuuint64_t d[2] = {FF, DM}, st[1] = {FF * 2};
    cuuint32_t bx[2] = {64, 64};
    encode(enc, &maps.w1a, w1, 2, d, st, bx, CU_TENSOR_MAP_SWIZZLE_128B);
    cuuint64_t d3[3] = {32, DM, FF / 32}, st3[2] = {FF * 2, 64};
    cuuint32_t bx3[3] = {32, 32, 3};
    encode(enc, &maps.w1b, w1, 3, d3, st3, bx3, CU_TENSOR_MAP_SWIZZLE_64B);
  }
  {
    cuuint64_t d[2] = {DM, FF}, st[1] = {DM * 2};
    cuuint32_t bx[2] = {64, 56};
    encode(enc, &maps.w2, w2, 2, d, st, bx, CU_TENSOR_MAP_SWIZZLE_128B);
  }
  fused_kernel<<<128, 384, SMEM_BYTES>>>(maps, lre, lim, ldt, dsk, b1, b2, gw, w1, w2, cre, cim, x, bre, bim, (float*)d_out);
}
```

```cpp
#include <cuda_runtime.h>
#include <cuda_bf16.h>
#include <cuda.h>
#include <stdint.h>

#define PF 2
#define SEND_TMA 0
#define PFK 5
namespace {

constexpr int SEQ = 2048, DM = 512, FF = 1792;
constexpr int NSLOT = 6;
constexpr uint32_t OFF_X = 0, OFF_RING = 131072, OFF_MISC = 229376;
constexpr uint32_t OFF_XFULL = OFF_MISC, OFF_FULL = OFF_XFULL + 64, OFF_EMPTY = OFF_FULL + 48, OFF_GBAR = OFF_EMPTY + 48,
                   OFF_CBAR = OFF_GBAR + 8, OFF_EPOCH = OFF_CBAR + 8;
constexpr uint32_t OFF_GS = OFF_MISC + 256;
constexpr uint32_t OFF_CARRY = OFF_GS + 512;
constexpr uint32_t OFF_DB = OFF_CARRY + 1024;
constexpr uint32_t OFF_DBG = OFF_DB + 256;
constexpr uint32_t SMEM_BYTES = OFF_DBG + 768;
static_assert(SMEM_BYTES <= 232448, "smem");

struct Maps { CUtensorMap x, bre, bim, w1a, w1b, w2, cre, cim; };

__device__ uint4 g_part[16 * 8 * 7 * 1024];
__device__ float2 g_end[8 * 16 * 64];
__device__ unsigned g_gate[SEQ];
__device__ unsigned g_epoch[128];
#define TG(role) do {} while (0)
#define TS2(role, i) do {} while (0)
#define TS(role, i) do {} while (0)
#define TDUMP() do {} while (0)

__device__ __forceinline__ void mbar_init(uint32_t bar, uint32_t cnt) { asm volatile("mbarrier.init.shared::cta.b64 [%0], %1;" ::"r"(bar), "r"(cnt)); }
__device__ __forceinline__ void mbar_expect_tx(uint32_t bar, uint32_t bytes) { asm volatile("mbarrier.arrive.expect_tx.shared::cta.b64 _, [%0], %1;" ::"r"(bar), "r"(bytes) : "memory"); }
__device__ __forceinline__ void mbar_arrive(uint32_t bar) { asm volatile("mbarrier.arrive.shared::cta.b64 _, [%0];" ::"r"(bar) : "memory"); }
__device__ __forceinline__ void mbar_arrive_cl(uint32_t cbar) { asm volatile("mbarrier.arrive.shared::cluster.b64 _, [%0];" ::"r"(cbar) : "memory"); }
__device__ __forceinline__ void mbar_wait(uint32_t bar, uint32_t parity) {
  asm volatile(
      "{\n.reg .pred p;\n.reg .u32 c;\n"
      "mbarrier.try_wait.parity.shared::cta.b64 p, [%0], %1;\n"
      "@p bra.uni LAB_DONE;\n"
      "mov.u32 c, 0;\n"
      "LAB_WAIT:\n"
      "mbarrier.try_wait.parity.shared::cta.b64 p, [%0], %1;\n"
      "@p bra.uni LAB_DONE;\n"
      "add.u32 c, c, 1;\nsetp.lt.u32 p, c, 200000;\n@p bra.uni LAB_WAIT;\n"
      "LAB_DONE:\n}" ::"r"(bar), "r"(parity) : "memory");
}
__device__ __forceinline__ void tma2d(uint32_t dst, const CUtensorMap* m, int c0, int c1, uint32_t bar) {
  asm volatile("cp.async.bulk.tensor.2d.shared::cluster.global.mbarrier::complete_tx::bytes [%0], [%1, {%3,%4}], [%2];"
               ::"r"(dst), "l"(m), "r"(bar), "r"(c0), "r"(c1) : "memory");
}
__device__ __forceinline__ void tma2d_mc(uint32_t dst, const CUtensorMap* m, int c0, int c1, uint32_t bar) {
  asm volatile("cp.async.bulk.tensor.2d.shared::cluster.global.mbarrier::complete_tx::bytes.multicast::cluster [%0], [%1, {%3,%4}], [%2], %5;"
               ::"r"(dst), "l"(m), "r"(bar), "r"(c0), "r"(c1), "h"((uint16_t)3) : "memory");
}
__device__ __forceinline__ void tma3d_mc(uint32_t dst, const CUtensorMap* m, int c0, int c1, int c2, uint32_t bar) {
  asm volatile("cp.async.bulk.tensor.3d.shared::cluster.global.mbarrier::complete_tx::bytes.multicast::cluster [%0], [%1, {%3,%4,%5}], [%2], %6;"
               ::"r"(dst), "l"(m), "r"(bar), "r"(c0), "r"(c1), "r"(c2), "h"((uint16_t)3) : "memory");
}
__device__ __forceinline__ void tma5d(uint32_t dst, const CUtensorMap* m, int c0, int c4, uint32_t bar) {
  asm volatile("cp.async.bulk.tensor.5d.shared::cluster.global.mbarrier::complete_tx::bytes [%0], [%1, {%3,%5,%5,%5,%4}], [%2];"
               ::"r"(dst), "l"(m), "r"(bar), "r"(c0), "r"(c4), "r"(0) : "memory");
}
__device__ __forceinline__ void l2_prefetch(const void* p, uint32_t bytes) { asm volatile("cp.async.bulk.prefetch.L2.global [%0], %1;" ::"l"(p), "r"(bytes) : "memory"); }
__device__ __forceinline__ bool elect_one() {
  uint32_t pred;
  asm volatile("{.reg .pred P; elect.sync _|P, 0xffffffff; selp.u32 %0, 1, 0, P;}" : "=r"(pred));
  return pred != 0;
}
__device__ __forceinline__ void wg_fence() { asm volatile("wgmma.fence.sync.aligned;" ::: "memory"); }
__device__ __forceinline__ void wg_commit() { asm volatile("wgmma.commit_group.sync.aligned;" ::: "memory"); }
template <int N> __device__ __forceinline__ void wg_wait() { asm volatile("wgmma.wait_group.sync.aligned %0;" ::"n"(N) : "memory"); }
template <int N> __device__ __forceinline__ void reg_fence(float (&d)[N]) {
#pragma unroll
  for (int i = 0; i < N; i++) asm volatile("" : "+f"(d[i])::"memory");
}
__device__ __forceinline__ void bar_sync(int id, int n) { asm volatile("bar.sync %0, %1;" ::"r"(id), "r"(n) : "memory"); }
__device__ __forceinline__ void bar_arrive(int id, int n) { asm volatile("bar.arrive %0, %1;" ::"r"(id), "r"(n) : "memory"); }
constexpr uint32_t DH128 = (1024 >> 4) | (1u << 30), DH64 = (512 >> 4) | (2u << 30);
__host__ __device__ constexpr uint32_t lbo(uint32_t bytes) { return (bytes >> 4) << 20; }
__device__ __forceinline__ uint32_t pack_bf16(float lo, float hi) { uint32_t r; asm("cvt.rn.bf16x2.f32 %0, %1, %2;" : "=r"(r) : "f"(hi), "f"(lo)); return r; }
__device__ __forceinline__ float bf_lo(uint32_t v) { return __uint_as_float(v << 16); }
__device__ __forceinline__ float bf_hi(uint32_t v) { return __uint_as_float(v & 0xffff0000u); }
__device__ __forceinline__ float bf_ld(const __nv_bfloat16* p) { return __bfloat162float(__ldg(p)); }
__device__ __forceinline__ uint32_t raw_ld(const __nv_bfloat16* p) { return __ldg(reinterpret_cast<const unsigned short*>(p)); }
__device__ __forceinline__ uint32_t late16(uint32_t bar) {
  uint32_t r;
  asm volatile("{.reg .pred p; mbarrier.test_wait.parity.shared::cta.b64 p, [%1], 0; selp.u32 %0, 16, 0, p;}" : "=r"(r) : "r"(bar) : "memory");
  return r;
}
__device__ __forceinline__ float2 lds_f2(uint32_t a) { float2 v; asm volatile("ld.shared.v2.f32 {%0,%1}, [%2];" : "=f"(v.x), "=f"(v.y) : "r"(a)); return v; }
__device__ __forceinline__ float lds_f(uint32_t a) { float v; asm volatile("ld.shared.f32 %0, [%1];" : "=f"(v) : "r"(a)); return v; }
__device__ __forceinline__ uint32_t lds_u(uint32_t a) { uint32_t v; asm volatile("ld.shared.u32 %0, [%1];" : "=r"(v) : "r"(a)); return v; }
__device__ __forceinline__ uint4 lds_u4(uint32_t a) { uint4 v; asm volatile("ld.shared.v4.u32 {%0,%1,%2,%3}, [%4];" : "=r"(v.x), "=r"(v.y), "=r"(v.z), "=r"(v.w) : "r"(a)); return v; }
__device__ __forceinline__ void st_b128(uint4* p, uint32_t a, uint32_t b, uint32_t c, uint32_t d) {
  asm volatile("{.reg .b64 l, h; .reg .b128 v; mov.b64 l, {%1,%2}; mov.b64 h, {%3,%4}; mov.b128 v, {l,h}; st.relaxed.gpu.global.b128 [%0], v;}"
               ::"l"(p), "r"(a), "r"(b), "r"(c), "r"(d) : "memory");
}
__device__ __forceinline__ void ld_b128(const uint4* p, uint32_t& a, uint32_t& b, uint32_t& c, uint32_t& d) {
  asm volatile("{.reg .b64 l, h; .reg .b128 v; ld.relaxed.gpu.global.b128 v, [%4]; mov.b128 {l,h}, v; mov.b64 {%0,%1}, l; mov.b64 {%2,%3}, h;}"
               : "=r"(a), "=r"(b), "=r"(c), "=r"(d) : "l"(p) : "memory");
}
__device__ __forceinline__ float tanh_fast(float x) { float y; asm("tanh.approx.f32 %0, %1;" : "=f"(y) : "f"(x)); return y; }
__device__ __forceinline__ float gelu2(float v) {
  float p = fmaf(v * v, 0.0356774081363f, 0.7978845608029f);
  return fmaf(v, tanh_fast(v * p), v);
}
__device__ __forceinline__ uint32_t bf2_mul(uint32_t a, uint32_t b) { uint32_t r; asm("mul.rn.bf16x2 %0, %1, %2;" : "=r"(r) : "r"(a), "r"(b)); return r; }
__device__ __forceinline__ uint32_t bf2_add(uint32_t a, uint32_t b) { uint32_t r; asm("add.rn.bf16x2 %0, %1, %2;" : "=r"(r) : "r"(a), "r"(b)); return r; }
__device__ __forceinline__ uint32_t bf2_fma(uint32_t a, uint32_t b, uint32_t c) { uint32_t r; asm("fma.rn.bf16x2 %0, %1, %2, %3;" : "=r"(r) : "r"(a), "r"(b), "r"(c)); return r; }
__device__ __forceinline__ void pin(float& a) { asm volatile("" : "+f"(a)::"memory"); }
__device__ __forceinline__ void pin(uint32_t& a) { asm volatile("" : "+r"(a)::"memory"); }
struct cplx { float re, im; };
__device__ __forceinline__ cplx cmul(cplx a, cplx b) { return {fmaf(a.re, b.re, -a.im * b.im), fmaf(a.re, b.im, a.im * b.re)}; }
__device__ __forceinline__ cplx cfma(cplx a, cplx b, cplx c) {
  return {fmaf(a.re, b.re, fmaf(-a.im, b.im, c.re)), fmaf(a.re, b.im, fmaf(a.im, b.re, c.im))};
}
__device__ __forceinline__ cplx make_lam(float lre, float lim, float ldt) {
  float dt = __bfloat162float(__float2bfloat16_rn(expf(ldt)));
  float mag = expf(dt * lre), sn, cs;
  sincospif(dt * lim * 0.31830988618379067f, &sn, &cs);
  return {mag * cs, mag * sn};
}

template<int TA,int TB,uint32_t AH,uint32_t BH> __device__ __forceinline__ void wgmma_n64_ss(float (&d)[32], uint32_t al, uint32_t ao, uint32_t bl, uint32_t bo, int scale_d){
  asm volatile("{.reg .pred p; .reg .b32 t, v; .reg .b64 da, db; setp.ne.b32 p, %36, 0; add.u32 t, %32, %33; mov.b64 da, {t, %39}; add.u32 v, %34, %35; mov.b64 db, {v, %40};\n"
   "wgmma.mma_async.sync.aligned.m64n64k16.f32.bf16.bf16 {%0,%1,%2,%3,%4,%5,%6,%7,%8,%9,%10,%11,%12,%13,%14,%15,%16,%17,%18,%19,%20,%21,%22,%23,%24,%25,%26,%27,%28,%29,%30,%31}, da, db, p, 1, 1, %37, %38;}"
   : "+f"(d[0]),"+f"(d[1]),"+f"(d[2]),"+f"(d[3]),"+f"(d[4]),"+f"(d[5]),"+f"(d[6]),"+f"(d[7]),"+f"(d[8]),"+f"(d[9]),"+f"(d[10]),"+f"(d[11]),"+f"(d[12]),"+f"(d[13]),"+f"(d[14]),"+f"(d[15]),"+f"(d[16]),"+f"(d[17]),"+f"(d[18]),"+f"(d[19]),"+f"(d[20]),"+f"(d[21]),"+f"(d[22]),"+f"(d[23]),"+f"(d[24]),"+f"(d[25]),"+f"(d[26]),"+f"(d[27]),"+f"(d[28]),"+f"(d[29]),"+f"(d[30]),"+f"(d[31])
   : "r"(al),"r"(ao >> 4),"r"(bl),"r"(bo >> 4),"r"(scale_d),"n"(TA),"n"(TB),"n"(AH),"n"(BH));
}
template<int TB,uint32_t BH> __device__ __forceinline__ void wgmma_n64_rs(float (&d)[32], uint32_t a0,uint32_t a1,uint32_t a2,uint32_t a3, uint32_t bl, uint32_t bo, int scale_d){
  asm volatile("{.reg .pred p; .reg .b32 t; .reg .b64 db; setp.ne.b32 p, %38, 0; add.u32 t, %36, %37; mov.b64 db, {t, %40};\n"
   "wgmma.mma_async.sync.aligned.m64n64k16.f32.bf16.bf16 {%0,%1,%2,%3,%4,%5,%6,%7,%8,%9,%10,%11,%12,%13,%14,%15,%16,%17,%18,%19,%20,%21,%22,%23,%24,%25,%26,%27,%28,%29,%30,%31}, {%32,%33,%34,%35}, db, p, 1, 1, %39;}"
   : "+f"(d[0]),"+f"(d[1]),"+f"(d[2]),"+f"(d[3]),"+f"(d[4]),"+f"(d[5]),"+f"(d[6]),"+f"(d[7]),"+f"(d[8]),"+f"(d[9]),"+f"(d[10]),"+f"(d[11]),"+f"(d[12]),"+f"(d[13]),"+f"(d[14]),"+f"(d[15]),"+f"(d[16]),"+f"(d[17]),"+f"(d[18]),"+f"(d[19]),"+f"(d[20]),"+f"(d[21]),"+f"(d[22]),"+f"(d[23]),"+f"(d[24]),"+f"(d[25]),"+f"(d[26]),"+f"(d[27]),"+f"(d[28]),"+f"(d[29]),"+f"(d[30]),"+f"(d[31])
   : "r"(a0),"r"(a1),"r"(a2),"r"(a3),"r"(bl),"r"(bo >> 4),"r"(scale_d),"n"(TB),"n"(BH));
}
template<int TA,int TB,uint32_t AH,uint32_t BH> __device__ __forceinline__ void wgmma_n96_ss(float (&d)[48], uint32_t al, uint32_t ao, uint32_t bl, uint32_t bo, int scale_d){
  asm volatile("{.reg .pred p; .reg .b32 t, v; .reg .b64 da, db; setp.ne.b32 p, %52, 0; add.u32 t, %48, %49; mov.b64 da, {t, %55}; add.u32 v, %50, %51; mov.b64 db, {v, %56};\n"
   "wgmma.mma_async.sync.aligned.m64n96k16.f32.bf16.bf16 {%0,%1,%2,%3,%4,%5,%6,%7,%8,%9,%10,%11,%12,%13,%14,%15,%16,%17,%18,%19,%20,%21,%22,%23,%24,%25,%26,%27,%28,%29,%30,%31,%32,%33,%34,%35,%36,%37,%38,%39,%40,%41,%42,%43,%44,%45,%46,%47}, da, db, p, 1, 1, %53, %54;}"
   : "+f"(d[0]),"+f"(d[1]),"+f"(d[2]),"+f"(d[3]),"+f"(d[4]),"+f"(d[5]),"+f"(d[6]),"+f"(d[7]),"+f"(d[8]),"+f"(d[9]),"+f"(d[10]),"+f"(d[11]),"+f"(d[12]),"+f"(d[13]),"+f"(d[14]),"+f"(d[15]),"+f"(d[16]),"+f"(d[17]),"+f"(d[18]),"+f"(d[19]),"+f"(d[20]),"+f"(d[21]),"+f"(d[22]),"+f"(d[23]),"+f"(d[24]),"+f"(d[25]),"+f"(d[26]),"+f"(d[27]),"+f"(d[28]),"+f"(d[29]),"+f"(d[30]),"+f"(d[31]),"+f"(d[32]),"+f"(d[33]),"+f"(d[34]),"+f"(d[35]),"+f"(d[36]),"+f"(d[37]),"+f"(d[38]),"+f"(d[39]),"+f"(d[40]),"+f"(d[41]),"+f"(d[42]),"+f"(d[43]),"+f"(d[44]),"+f"(d[45]),"+f"(d[46]),"+f"(d[47])
   : "r"(al),"r"(ao >> 4),"r"(bl),"r"(bo >> 4),"r"(scale_d),"n"(TA),"n"(TB),"n"(AH),"n"(BH));
}
template<int TA,int TB,uint32_t AH,uint32_t BH> __device__ __forceinline__ void wgmma_n128_ss(float (&d)[64], uint32_t al, uint32_t ao, uint32_t bl, uint32_t bo, int scale_d){
  asm volatile("{.reg .pred p; .reg .b32 t, v; .reg .b64 da, db; setp.ne.b32 p, %68, 0; add.u32 t, %64, %65; mov.b64 da, {t, %71}; add.u32 v, %66, %67; mov.b64 db, {v, %72};\n"
   "wgmma.mma_async.sync.aligned.m64n128k16.f32.bf16.bf16 {%0,%1,%2,%3,%4,%5,%6,%7,%8,%9,%10,%11,%12,%13,%14,%15,%16,%17,%18,%19,%20,%21,%22,%23,%24,%25,%26,%27,%28,%29,%30,%31,%32,%33,%34,%35,%36,%37,%38,%39,%40,%41,%42,%43,%44,%45,%46,%47,%48,%49,%50,%51,%52,%53,%54,%55,%56,%57,%58,%59,%60,%61,%62,%63}, da, db, p, 1, 1, %69, %70;}"
   : "+f"(d[0]),"+f"(d[1]),"+f"(d[2]),"+f"(d[3]),"+f"(d[4]),"+f"(d[5]),"+f"(d[6]),"+f"(d[7]),"+f"(d[8]),"+f"(d[9]),"+f"(d[10]),"+f"(d[11]),"+f"(d[12]),"+f"(d[13]),"+f"(d[14]),"+f"(d[15]),"+f"(d[16]),"+f"(d[17]),"+f"(d[18]),"+f"(d[19]),"+f"(d[20]),"+f"(d[21]),"+f"(d[22]),"+f"(d[23]),"+f"(d[24]),"+f"(d[25]),"+f"(d[26]),"+f"(d[27]),"+f"(d[28]),"+f"(d[29]),"+f"(d[30]),"+f"(d[31]),"+f"(d[32]),"+f"(d[33]),"+f"(d[34]),"+f"(d[35]),"+f"(d[36]),"+f"(d[37]),"+f"(d[38]),"+f"(d[39]),"+f"(d[40]),"+f"(d[41]),"+f"(d[42]),"+f"(d[43]),"+f"(d[44]),"+f"(d[45]),"+f"(d[46]),"+f"(d[47]),"+f"(d[48]),"+f"(d[49]),"+f"(d[50]),"+f"(d[51]),"+f"(d[52]),"+f"(d[53]),"+f"(d[54]),"+f"(d[55]),"+f"(d[56]),"+f"(d[57]),"+f"(d[58]),"+f"(d[59]),"+f"(d[60]),"+f"(d[61]),"+f"(d[62]),"+f"(d[63])
   : "r"(al),"r"(ao >> 4),"r"(bl),"r"(bo >> 4),"r"(scale_d),"n"(TA),"n"(TB),"n"(AH),"n"(BH));
}

__global__ void __cluster_dims__(2, 1, 1) __launch_bounds__(384, 1)
fused_kernel(const __grid_constant__ Maps maps, const __nv_bfloat16* __restrict__ lam_re,
             const __nv_bfloat16* __restrict__ lam_im, const __nv_bfloat16* __restrict__ log_dt, const __nv_bfloat16* __restrict__ dskip,
             const __nv_bfloat16* __restrict__ b1, const __nv_bfloat16* __restrict__ b2, const __nv_bfloat16* __restrict__ gate_w,
             const __nv_bfloat16* __restrict__ pf_w1, const __nv_bfloat16* __restrict__ pf_w2, const __nv_bfloat16* __restrict__ pf_cre,
             const __nv_bfloat16* __restrict__ pf_cim, const __nv_bfloat16* __restrict__ pf_x,
             const __nv_bfloat16* __restrict__ pf_bre, const __nv_bfloat16* __restrict__ pf_bim, float* __restrict__ out) {
  extern __shared__ __align__(1024) unsigned char smem_raw[];
  const uint32_t sb = (uint32_t)__cvta_generic_to_shared(smem_raw);
  const int b = blockIdx.x;
  const int rank = b & 1, s = (b >> 1) & 7, m = ((b >> 4) << 1) | rank;
  const int warp = __shfl_sync(0xffffffffu, (int)(threadIdx.x >> 5), 0);
  const int lane = threadIdx.x & 31;
  const int xrot = 7 - s;

  if (warp != 8) asm volatile("barrier.cluster.arrive.relaxed.aligned;" ::: "memory");
  if (warp < 8) {
    const int wg = warp >> 2, w = warp & 3, q = lane & 3, gr = lane >> 2;
    const int c0 = s * 64 + w * 16 + gr + (q & 2) * 4;
    const uint32_t prr = raw_ld(lam_re + c0), pir = raw_ld(lam_im + c0), pdr = raw_ld(log_dt + c0);
    uint32_t bv[28];
#pragma unroll
    for (int j = 0; j < 28; j++) bv[j] = __ldg(reinterpret_cast<const uint32_t*>(b1 + s * 224 + j * 8) + q);
    asm volatile("setmaxnreg.inc.sync.aligned.u32 224;");
    asm volatile("barrier.cluster.wait.aligned;" ::: "memory");
    TS(wg, 0);
    uint32_t ebar;
    asm volatile("mapa.shared::cluster.u32 %0, %1, %2;" : "=r"(ebar) : "r"(sb + OFF_EMPTY), "r"(lane & 1));
    auto release = [&](int slot) { if (lane < 2) mbar_arrive_cl(ebar + 8 * slot); };
    const uint32_t xw = sb + OFF_X + wg * 8192, fullb = sb + OFF_FULL;
    const uint32_t dxw = (xw & 0x3FFFF) >> 4, dring = ((sb + OFF_RING) & 0x3FFFF) >> 4;

    float ure[32], uim[32], aa[48], ab[64];
    cplx lam[2], coef[2], l16[2], l32[2], lq[2], pre[2], e[2];
    cplx l1, cf;
    uint32_t sh16, mhi;
    TS(wg, 24);

#pragma unroll
    for (int kb = 0; kb < 8; kb++) {
      const int slot = kb % NSLOT;
      TS2(1, kb);
      mbar_wait(sb + OFF_XFULL + 8 * kb, 0);
      if (kb == 0) TS(wg, 18);
      mbar_wait(fullb + 8 * slot, (kb / NSLOT) & 1);
      TS2(2, kb);
      if (kb == 0) TS(wg, 1);
      wg_fence();
      const uint32_t dxa = dxw + ((kb + xrot) & 7) * 1024;
#pragma unroll
      for (int kk = 0; kk < 4; kk++) {
        wgmma_n64_ss<0, 0, DH128, DH128>(ure, dring, slot * 16384 + kk * 32, dxa, kk * 32, (kb | kk) != 0);
        wgmma_n64_ss<0, 0, DH128, DH128>(uim, dring, slot * 16384 + 8192 + kk * 32, dxa, kk * 32, (kb | kk) != 0);
      }
      wg_commit();
      if (kb > 0) { wg_wait<1>(); release((kb - 1) % NSLOT); }
      if (kb == 2) {
        sh16 = late16(sb + OFF_XFULL); mhi = 0xffffffffu << sh16;
        l1 = make_lam(__uint_as_float(prr << sh16), __uint_as_float(pir << sh16), __uint_as_float(pdr << sh16));
        pin(l1.re); pin(l1.im);
      }
      if (kb == 3) {
        const float pr = __uint_as_float(prr << sh16), pi = __uint_as_float(pir << sh16);
        const float inv = __fdividef(1.f, fmaf(pr, pr, pi * pi));
        cf = cmul(cplx{l1.re - 1.f, l1.im}, cplx{pr * inv, -pi * inv});
        cplx t = cmul(l1, l1); t = cmul(t, t); t = cmul(t, t); t = cmul(t, t);
#pragma unroll
        for (int h = 0; h < 2; h++) {
          lam[h] = cplx{__shfl_sync(0xffffffffu, l1.re, 2 * h, 4), __shfl_sync(0xffffffffu, l1.im, 2 * h, 4)};
          coef[h] = cplx{__shfl_sync(0xffffffffu, cf.re, 2 * h, 4), __shfl_sync(0xffffffffu, cf.im, 2 * h, 4)};
          l16[h] = cplx{__shfl_sync(0xffffffffu, t.re, 2 * h, 4), __shfl_sync(0xffffffffu, t.im, 2 * h, 4)};
        }
      }
      if (kb == 4) {
#pragma unroll
        for (int h = 0; h < 2; h++) {
          pin(l16[h].re); pin(l16[h].im);
          l32[h] = cmul(l16[h], l16[h]);
          const cplx a = (q & 1) ? l16[h] : cplx{1.f, 0.f}, c = (q & 2) ? l32[h] : cplx{1.f, 0.f};
          lq[h] = cmul(cmul(a, c), coef[h]);
          pin(lq[h].re); pin(lq[h].im);
        }
      }
      if (kb >= 4) {
#pragma unroll
        for (int j = (kb - 4) * 7; j < (kb - 3) * 7; j++) {
          pin(bv[j]);
          float* d = j < 12 ? aa + 4 * j : ab + 4 * (j - 12);
          d[0] = d[2] = __uint_as_float(bv[j] << sh16); d[1] = d[3] = __uint_as_float(bv[j] & mhi);
          pin(d[0]); pin(d[1]); pin(d[2]); pin(d[3]);
        }
      }
    }
    TS(wg, 2);
#pragma unroll
    for (int kb = 0; kb < 8; kb++) {
      const int u = 8 + kb, slot = u % NSLOT;
      TS2(1, u);
      mbar_wait(fullb + 8 * slot, (u / NSLOT) & 1);
      TS2(2, u);
      wg_fence();
      const uint32_t dxa = dxw + ((kb + xrot) & 7) * 1024;
#pragma unroll
      for (int kk = 0; kk < 4; kk++)
        wgmma_n96_ss<0, 1, DH128, DH64>(aa, dxa, kk * 32, dring, slot * 16384 + (kk >> 1) * 6144 + (kk & 1) * 1024 + lbo(2048), 1);
      wg_commit();
      wg_wait<1>();
      release((u - 1) % NSLOT);
      if (kb == 0) {
        reg_fence(ure); reg_fence(uim);
#pragma unroll
        for (int h = 0; h < 2; h++) e[h] = cplx{ure[2 * h], uim[2 * h]};
      }
      if (kb < 3) {
#pragma unroll
        for (int t = 1 + 5 * kb; t < 6 + 5 * kb; t++)
#pragma unroll
          for (int h = 0; h < 2; h++) { const int i = 4 * (t >> 1) + 2 * h + (t & 1); e[h] = cfma(lam[h], e[h], cplx{ure[i], uim[i]}); }
#pragma unroll
        for (int h = 0; h < 2; h++) { pin(e[h].re); pin(e[h].im); }
      } else if (kb == 3) {
#pragma unroll
        for (int h = 0; h < 2; h++) {
          cplx y = {__shfl_up_sync(0xffffffffu, e[h].re, 1, 4), __shfl_up_sync(0xffffffffu, e[h].im, 1, 4)};
          if (q >= 1) e[h] = cfma(l16[h], y, e[h]);
          y = cplx{__shfl_up_sync(0xffffffffu, e[h].re, 2, 4), __shfl_up_sync(0xffffffffu, e[h].im, 2, 4)};
          if (q >= 2) e[h] = cfma(l32[h], y, e[h]);
        }
        if (q == 3) {
#pragma unroll
          for (int h = 0; h < 2; h++)
            asm volatile("st.shared.v2.f32 [%0], {%1,%2};" ::"r"(sb + OFF_CARRY + wg * 512 + (w * 16 + gr + 8 * h) * 8), "f"(e[h].re), "f"(e[h].im) : "memory");
          mbar_arrive(sb + OFF_GBAR);
        }
#pragma unroll
        for (int h = 0; h < 2; h++) {
          const cplx y = {__shfl_up_sync(0xffffffffu, e[h].re, 1, 4), __shfl_up_sync(0xffffffffu, e[h].im, 1, 4)};
          pre[h] = (q >= 1) ? cmul(coef[h], y) : cplx{0.f, 0.f};
          pin(pre[h].re); pin(pre[h].im);
        }
        TS(wg, 3);
      } else {
#pragma unroll
        for (int i = (kb - 4) * 8; i < (kb - 3) * 8; i++) {
          pin(ure[i]); pin(uim[i]);
          const cplx v = cmul(coef[(i >> 1) & 1], cplx{ure[i], uim[i]});
          ure[i] = v.re; uim[i] = v.im;
          pin(ure[i]); pin(uim[i]);
        }
      }
    }
    TS(wg, 4);
    uint32_t H[56];
    cplx hst[2];
    const uint32_t dh = dxw;
    const uint32_t hst_addr = xw + (w * 16 + (lane & 15)) * 128 + (((lane >> 4) ^ (lane & 7)) << 4);
#pragma unroll
    for (int kb = 0; kb < 8; kb++) {
      const int u = 16 + kb, slot = u % NSLOT;
      TS2(1, u);
      mbar_wait(fullb + 8 * slot, (u / NSLOT) & 1);
      TS2(2, u);
      wg_fence();
#pragma unroll
      for (int kk = 0; kk < 4; kk++)
        wgmma_n128_ss<0, 1, DH128, DH128>(ab, dxw, kb * 16384 + kk * 32, dring, slot * 16384 + kk * 2048 + lbo(8192), 1);
      wg_commit();
      wg_wait<1>();
      release((u - 1) % NSLOT);
      if (kb < 4) {
        const int ch = kb;
#pragma unroll
        for (int i = ch * 6; i < ch * 6 + 6; i++) {
          pin(aa[2 * i]); pin(aa[2 * i + 1]);
          H[i] = pack_bf16(gelu2(aa[2 * i]), gelu2(aa[2 * i + 1]));
          pin(H[i]);
        }
      } else {
        if (kb == 4) {
          TS(wg, 5);
          mbar_wait(sb + OFF_CBAR, 0);
          TS(wg, 6);
#pragma unroll
          for (int h = 0; h < 2; h++) {
            const float2 c = lds_f2(sb + OFF_CARRY + wg * 512 + (w * 16 + gr + 8 * h) * 8);
            hst[h] = cfma(lq[h], cplx{c.x, c.y}, pre[h]);
          }
        }
        const int j0 = (kb - 4) * 2;
        uint32_t rr[4], ri[4];
#pragma unroll
        for (int jj = 0; jj < 2; jj++) {
          const int j = j0 + jj;
          const float2 g2 = lds_f2(sb + OFF_GS + (wg * 64 + j * 8 + q * 2) * 4);
#pragma unroll
          for (int h = 0; h < 2; h++) {
            const int i = 4 * j + 2 * h;
            const cplx h0 = cfma(lam[h], hst[h], cplx{ure[i], uim[i]});
            hst[h] = cfma(lam[h], h0, cplx{ure[i + 1], uim[i + 1]});
            rr[jj * 2 + h] = pack_bf16(h0.re * g2.x, hst[h].re * g2.y);
            ri[jj * 2 + h] = pack_bf16(-h0.im * g2.x, -hst[h].im * g2.y);
          }
        }
        const uint32_t a = hst_addr ^ (j0 << 4);
        asm volatile("stmatrix.sync.aligned.m8n8.x4.shared.b16 [%0], {%1,%2,%3,%4};" ::"r"(a), "r"(rr[0]), "r"(rr[1]), "r"(rr[2]), "r"(rr[3]) : "memory");
        asm volatile("stmatrix.sync.aligned.m8n8.x4.shared.b16 [%0], {%1,%2,%3,%4};" ::"r"(a + 16384), "r"(ri[0]), "r"(ri[1]), "r"(ri[2]), "r"(ri[3]) : "memory");
      }
    }
    TS(wg, 7);

    uint4* const psend = g_part + (size_t)m * (8 * 7 * 1024) + warp * 128;
    const uint4* const precv = g_part + (size_t)(m * 8 + s) * (7 * 1024) + warp * 128 + lane;
    const uint32_t stg = sb + OFF_X + 5 * 16384 + warp * 2048;
    const uint32_t dx0 = ((sb + OFF_X) & 0x3FFFF) >> 4;
    float o[32], fin[32], rho[2];
    uint32_t r0[16], r1[16], r2[16], sum[16], tag;
    auto send = [&](int p) {
#pragma unroll
      for (int i = 0; i < 4; i++) {
        uint32_t t0;
        asm("lop3.b32 %0, %1, 1, %2, 0xb8;" : "=r"(t0) : "r"(pack_bf16(o[8 * i], o[8 * i + 1])), "r"(tag));
        st_b128(psend + (((s + 1 + p) & 7) * 7 + p) * 1024 + i * 32 + lane, t0, pack_bf16(o[8 * i + 2], o[8 * i + 3]), pack_bf16(o[8 * i + 4], o[8 * i + 5]),
                pack_bf16(o[8 * i + 6], o[8 * i + 7]));
      }
    };
    auto recv_issue = [&](uint32_t (&r)[16], int p) {
#pragma unroll
      for (int i = 0; i < 4; i++) ld_b128(precv + p * 1024 + i * 32, r[4 * i], r[4 * i + 1], r[4 * i + 2], r[4 * i + 3]);
    };
    auto stale = [&](uint32_t (&r)[16]) {
      uint32_t t0, t1;
      asm("lop3.b32 %0, %1, %2, %3, 0x7e;" : "=r"(t0) : "r"(r[0]), "r"(r[4]), "r"(tag));
      asm("lop3.b32 %0, %1, %2, %3, 0x7e;" : "=r"(t1) : "r"(r[8]), "r"(r[12]), "r"(tag));
      return __any_sync(0xffffffffu, (t0 | t1) & 1);
    };
    auto recv_check = [&](uint32_t (&r)[16], int p) {
      if (__builtin_expect(stale(r), 0)) {
        int tries = 0;
#pragma unroll 1
        do { recv_issue(r, p); } while (stale(r) && ++tries < 200000);
      }
    };
    auto gelu_b = [&](int i0, int i1) {
#pragma unroll
      for (int i = i0; i < i1; i++) {
        pin(ab[2 * i]); pin(ab[2 * i + 1]);
        H[24 + i] = pack_bf16(gelu2(ab[2 * i]), gelu2(ab[2 * i + 1]));
        pin(H[24 + i]);
      }
    };
    auto mma = [&](float (&o)[32], uint32_t wo, int k0, int k1, int acc) {
      wg_fence();
#pragma unroll
      for (int k = k0; k < k1; k++) {
        if (k >= 6 && k < 14) {
          const int kk = k - 6;
          wgmma_n64_ss<1, 0, DH128, DH128>(o, dh, (kk >> 2) * 16384 + (kk & 3) * 2048, dx0, wo + 16384 + (kk >> 2) * 8192 + (kk & 3) * 32, 1);
        } else {
          const int kk = k < 6 ? k : k - 8;
          wgmma_n64_rs<1, DH128>(o, H[4 * kk], H[4 * kk + 1], H[4 * kk + 2], H[4 * kk + 3], dx0, wo + (kk / 7) * 32768 + (kk % 7) * 2048, k != 0 || acc);
        }
      }
      wg_commit();
    };
#pragma unroll
    for (int p = 0; p < 8; p++) {
      const uint32_t wo = (p % 3) == 1 ? 2 * 16384 : OFF_RING + (p % 3) * 24576;
      if (p == 0) {
        mbar_wait(fullb, 0);
        mma(o, wo, 0, 3, 0);
        asm volatile("fence.proxy.async.shared::cta;" ::: "memory");
        wg_wait<1>(); release(5);
        gelu_b(0, 4);
        mma(o, wo, 3, 6, 0);
        gelu_b(4, 10);
        bar_sync(1 + wg, 128);
        mbar_wait(fullb + 8, 0);
        mma(o, wo, 6, 10, 0);
        gelu_b(10, 16);
        mma(o, wo, 10, 15, 0);
        gelu_b(16, 24);
        mbar_wait(fullb + 16, 0);
        mma(o, wo, 15, 18, 0);
        gelu_b(24, 32);
        if (wg == 1) bar_sync(4, 256);
        mma(o, wo, 18, 22, 0);
      } else {
        mbar_wait(sb + OFF_XFULL + 8 * p, 1);
        if (p == 6) TS(wg, 19);
        bar_sync(3 + wg, 256);
        if (p < 7) mma(o, wo, 0, 22, 0); else mma(fin, wo, 0, 22, 1);
      }
      if (p < 7 || wg == 0) bar_arrive(4 - wg, 256);
      if (p == 6) TS(wg, 21);
      if (p == 7) recv_issue(r2, 6);
      if (p == 0 || p >= 3) tag = lds_u(sb + OFF_EPOCH);
      if (p == 1 || p == 2) {
        if (p == 1) {
#pragma unroll
          for (int h = 0; h < 2; h++) rho[h] = 0.5f * lds_f(sb + OFF_GS + (wg * 64 + w * 16 + gr + 8 * h) * 4);
        }
#pragma unroll
        for (int j = (p - 1) * 4; j < p * 4; j++) {
          const float2 db = lds_f2(sb + OFF_DB + j * 32 + q * 8);
#pragma unroll
          for (int h = 0; h < 2; h++) {
            const uint32_t xd = bf2_mul(lds_u(xw + 7 * 16384 + (w * 16 + gr + 8 * h) * 128 + ((j ^ gr) << 4) + q * 4), __float_as_uint(db.x));
            fin[4 * j + 2 * h] = fmaf(bf_lo(xd), rho[h], bf_lo(__float_as_uint(db.y)));
            fin[4 * j + 2 * h + 1] = fmaf(bf_hi(xd), rho[h], bf_hi(__float_as_uint(db.y)));
            pin(fin[4 * j + 2 * h]); pin(fin[4 * j + 2 * h + 1]);
          }
        }
      }
      if (p >= 3) {
        if (p == 7) TS(wg, 25);
        recv_check(r0, p - 3);
        if (p == 7) TS(wg, 26);
        if (p == 7) recv_check(r1, 5);
#pragma unroll
        for (int i = 0; i < 16; i++) sum[i] = p == 3 ? r0[i] : bf2_add(sum[i], p == 7 ? bf2_add(r0[i], r1[i]) : r0[i]);
        if (p == 7) TS(wg, 20);
      }
      if (p >= 2 && p < 7) recv_issue(r0, p - 2);
      wg_wait<0>();
      if (p < 5) release(p);
      if (p < 7) reg_fence(o); else reg_fence(fin);
      if (p == 6) TS(wg, 22);
      if (p < 7) send(p);
      if (p == 6) TS(wg, 23);
      if (p == 6) recv_issue(r1, 5);
      TS(wg, 8 + p);
    }
    {
      float fs[2];
#pragma unroll
      for (int h = 0; h < 2; h++) fs[h] = __fdividef(1.f, 2.f + rho[h]);
#pragma unroll
      for (int i = 0; i < 16; i++) { o[2 * i] = (fin[2 * i] + bf_lo(sum[i])) * fs[i & 1]; o[2 * i + 1] = (fin[2 * i + 1] + bf_hi(sum[i])) * fs[i & 1]; }
      reg_fence(o);
      tag = lds_u(sb + OFF_EPOCH);
      recv_check(r2, 6);
      TS(wg, 16);
      float* op = out + (size_t)(m * 128 + wg * 64 + (gr >> 1) * 16 + w * 4 + (gr & 1)) * DM + s * 64 + q * 2;
#pragma unroll
      for (int i = 0; i < 16; i++)
        *reinterpret_cast<float2*>(op + (i & 1) * 2 * DM + (i >> 1) * 8) =
            make_float2(fmaf(bf_lo(r2[i]), fs[i & 1], o[2 * i]), fmaf(bf_hi(r2[i]), fs[i & 1], o[2 * i + 1]));
      if (threadIdx.x == 128) g_epoch[b] = tag;
      TS(wg, 17); TG(wg); TDUMP();
    }
  } else {
    asm volatile("setmaxnreg.dec.sync.aligned.u32 56;");
    int wsel = warp;
    asm("" : "+r"(wsel));
    if (wsel > 8) {
     if (warp != 11) {
      const int t = threadIdx.x - 288;
      unsigned par;
      asm volatile("ld.relaxed.gpu.global.u32 %0, [%1];" : "=r"(par) : "l"(g_epoch + b) : "memory");
      const float pr = bf_ld(lam_re + s * 64 + t), pi = bf_ld(lam_im + s * 64 + t), pd = bf_ld(log_dt + s * 64 + t);
      asm volatile("barrier.cluster.wait.aligned;" ::: "memory");
      par = (par + 1) & 1;
      cplx l64 = make_lam(pr, pi, pd);
#pragma unroll
      for (int i = 0; i < 6; i++) l64 = cmul(l64, l64);
      cplx l128 = cmul(l64, l64);
      pin(l128.re); pin(l128.im);
      mbar_wait(sb + OFF_GBAR, 0);
      const float2 e0 = lds_f2(sb + OFF_CARRY + t * 8), e1 = lds_f2(sb + OFF_CARRY + 512 + t * 8);
      float2* eb = g_end + s * 1024 + t;
      {
        const cplx e = cfma(l64, cplx{e0.x, e0.y}, cplx{e1.x, e1.y});
        const unsigned long long v = ((unsigned long long)__float_as_uint(e.im) << 32) | ((__float_as_uint(e.re) & ~1u) | par);
        asm volatile("st.relaxed.gpu.global.b64 [%0], %1;" ::"l"(eb + m * 64), "l"(v) : "memory");
      }
      if (t == 0) TS(3, 1);
      cplx S = {0.f, 0.f};
      {
        unsigned long long v[15];
        uint32_t bad;
        int tries = 0;
        const float2* e15 = eb + (m - 15) * 64;
#pragma unroll 1
        do {
#pragma unroll
          for (int i = 0; i < 15; i++) {
            v[i] = par;
            asm volatile("{.reg .pred p; setp.ge.s32 p, %2, %3; @p ld.relaxed.gpu.global.b64 %0, [%1];}" : "+l"(v[i]) : "l"(e15 + i * 64), "r"(m), "r"(15 - i) : "memory");
          }
          bad = 0;
#pragma unroll
          for (int i = 0; i < 15; i++) bad |= (uint32_t)v[i] ^ par;
        } while ((bad & 1) && ++tries < 200000);
        if (t == 0) TS(3, 2);
#pragma unroll
        for (int i = 0; i < 15; i++) S = cfma(l128, S, cplx{__uint_as_float((uint32_t)v[i] & ~1u), __uint_as_float((uint32_t)(v[i] >> 32))});
      }
      const cplx S1 = cfma(l64, S, cplx{e0.x, e0.y});
      asm volatile("st.shared.v2.f32 [%0], {%1,%2};" ::"r"(sb + OFF_CARRY + t * 8), "f"(S.re), "f"(S.im) : "memory");
      asm volatile("st.shared.v2.f32 [%0], {%1,%2};" ::"r"(sb + OFF_CARRY + 512 + t * 8), "f"(S1.re), "f"(S1.im) : "memory");
      mbar_arrive(sb + OFF_CBAR);
      if (t == 0) TS(3, 3);
     } else {
      if (lane == 0) TG(2);
      const uint4* gwp = reinterpret_cast<const uint4*>(gate_w) + (lane & 7);
      uint4 gw[4];
#pragma unroll
      for (int i = 0; i < 4; i++) gw[i] = __ldg(gwp + i * 8);
      unsigned par;
      asm volatile("ld.relaxed.gpu.global.u32 %0, [%1];" : "=r"(par) : "l"(g_epoch + b) : "memory");
      const uint32_t dk = __ldg(reinterpret_cast<const uint32_t*>(dskip + s * 64) + lane), bb = __ldg(reinterpret_cast<const uint32_t*>(b2 + s * 64) + lane);
      asm volatile("barrier.cluster.wait.aligned;" ::: "memory");
      const int row = s * 16 + (lane >> 3);
      const uint32_t xr0 = sb + OFF_X + row * 128 + (((lane & 7) ^ (row & 7)) << 4), xr1 = (xr0 + 512) ^ 64;
      float z[4] = {0.f, 0.f, 0.f, 0.f};
#pragma unroll
      for (int kb = 0; kb < 8; kb++) {
        const uint32_t wv[4] = {gw[kb & 3].x, gw[kb & 3].y, gw[kb & 3].z, gw[kb & 3].w};
        if (kb < 4) gw[kb] = __ldg(gwp + (kb + 4) * 8);
        mbar_wait(sb + OFF_XFULL + 8 * kb, 0);
        if ((PF & 2) && kb == PFK && elect_one()) {
          l2_prefetch(pf_w1 + b * 7168, 14336);
          l2_prefetch(pf_cre + b * 2048, 4096);
          l2_prefetch(pf_cim + b * 2048, 4096);
          l2_prefetch(pf_w2 + b * 7168, 14336);
        }
        const uint32_t xo = ((kb + xrot) & 7) * 16384;
#pragma unroll
        for (int r = 0; r < 4; r++) {
          const uint4 a = lds_u4(((r & 1) ? xr1 : xr0) + xo + (r >> 1) * 1024);
          const uint32_t p = bf2_fma(a.w, wv[3], bf2_fma(a.z, wv[2], bf2_fma(a.y, wv[1], bf2_mul(a.x, wv[0]))));
          z[r] += bf_lo(p); z[r] += bf_hi(p);
        }
      }
      asm volatile("st.shared.v2.u32 [%0], {%1,%2};" ::"r"(sb + OFF_DB + lane * 8), "r"(dk), "r"(bf2_add(bb, bb)) : "memory");
      if (lane == 0) asm volatile("st.shared.u32 [%0], %1;" ::"r"(sb + OFF_EPOCH), "r"(par + 1) : "memory");
      par = (par + 1) & 1;
      {
        float y0 = (lane & 4) ? z[1] : z[0], y1 = (lane & 4) ? z[3] : z[2];
        y0 += __shfl_xor_sync(0xffffffffu, (lane & 4) ? z[0] : z[1], 4);
        y1 += __shfl_xor_sync(0xffffffffu, (lane & 4) ? z[2] : z[3], 4);
        float zz = (lane & 2) ? y1 : y0;
        zz += __shfl_xor_sync(0xffffffffu, (lane & 2) ? y0 : y1, 2);
        zz += __shfl_xor_sync(0xffffffffu, zz, 1);
        const float rho = 4.f * expf(zz > 40.f ? 40.f : zz);
        if ((lane & 1) == 0)
          asm volatile("st.relaxed.gpu.global.u32 [%0], %1;" ::"l"(g_gate + m * 128 + row + (lane & 4) + (lane & 2) * 4), "r"((__float_as_uint(rho) & ~1u) | par) : "memory");
      }
      if (lane == 0) TS(3, 0);
      mbar_wait(sb + OFF_GBAR, 0);
      uint32_t g0, g1, g2, g3;
      int tries = 0;
#pragma unroll 1
      do {
        asm volatile("ld.relaxed.gpu.global.v4.u32 {%0,%1,%2,%3}, [%4];" : "=r"(g0), "=r"(g1), "=r"(g2), "=r"(g3) : "l"(g_gate + m * 128 + lane * 4) : "memory");
      } while ((((g0 ^ par) | (g1 ^ par) | (g2 ^ par) | (g3 ^ par)) & 1) && ++tries < 200000);
      asm volatile("st.shared.v4.u32 [%0], {%1,%2,%3,%4};" ::"r"(sb + OFF_GS + lane * 16), "r"(g0), "r"(g1), "r"(g2), "r"(g3) : "memory");
      mbar_arrive(sb + OFF_CBAR);
      if (lane == 0) TS(3, 4);
     }
    } else {
      if (elect_one()) {
        TS(2, 0);
        mbar_init(sb + OFF_XFULL, 1); mbar_init(sb + OFF_FULL, 1); mbar_init(sb + OFF_XFULL + 8, 1);
        asm volatile("fence.mbarrier_init.release.cluster;" ::: "memory");
        asm volatile("fence.proxy.async.shared::cta;" ::: "memory");
        mbar_expect_tx(sb + OFF_XFULL, 16384);
        tma5d(sb + OFF_X + xrot * 16384, &maps.x, 0, 2 * m, sb + OFF_XFULL);
        TS(2, 3);
        mbar_expect_tx(sb + OFF_FULL, 16384);
        tma2d(sb + OFF_RING, &maps.bre, 0, s * 64, sb + OFF_FULL);
        tma2d(sb + OFF_RING + 8192, &maps.bim, 0, s * 64, sb + OFF_FULL);
        mbar_expect_tx(sb + OFF_XFULL + 8, 16384);
        tma5d(sb + OFF_X + ((xrot + 1) & 7) * 16384, &maps.x, 64, 2 * m, sb + OFF_XFULL + 8);
        for (int i = 0; i < 6; i++) { mbar_init(sb + OFF_XFULL + 16 + 8 * i, 1); mbar_init(sb + OFF_EMPTY + 8 * i, 16); if (i) mbar_init(sb + OFF_FULL + 8 * i, 1); }
        mbar_init(sb + OFF_GBAR, 64); mbar_init(sb + OFF_CBAR, 96);
        asm volatile("fence.mbarrier_init.release.cluster;" ::: "memory");
        asm volatile("fence.proxy.async.shared::cta;" ::: "memory");
        TS(2, 4);
      }
      __syncwarp();
      asm volatile("barrier.cluster.arrive.relaxed.aligned;" ::: "memory");
      asm volatile("barrier.cluster.wait.aligned;" ::: "memory");
      if (elect_one()) {
        TS(2, 1);
#pragma unroll 1
        for (int u = 1; u < 7; u++) {
          if (u < 6) {
            mbar_expect_tx(sb + OFF_FULL + 8 * u, 16384);
            tma2d_mc(sb + OFF_RING + u * 16384 + rank * 8192, rank ? &maps.bim : &maps.bre, u * 64, s * 64, sb + OFF_FULL + 8 * u);
          }
          mbar_expect_tx(sb + OFF_XFULL + 8 * (u + 1), 16384);
          tma5d(sb + OFF_X + ((u + 1 + xrot) & 7) * 16384, &maps.x, (u + 1) * 64, 2 * m, sb + OFF_XFULL + 8 * (u + 1));
        }
        TS(2, 5);
        const CUtensorMap* mb = rank ? &maps.bim : &maps.bre;
        const CUtensorMap* mc = rank ? &maps.cim : &maps.cre;
        int slot = 0; uint32_t ph = 0;
#pragma unroll 1
        for (int u = 6; u < 27; u++) {
          const uint32_t fb = sb + OFF_FULL + 8 * slot, dst = sb + OFF_RING + slot * 16384;
          mbar_wait(sb + OFF_EMPTY + 8 * slot, ph);
          TS2(0, u);
          if (u < 8) {
            mbar_expect_tx(fb, 16384);
            tma2d_mc(dst + rank * 8192, mb, u * 64, s * 64, fb);
          } else if (u < 16) {
            mbar_expect_tx(fb, 12288);
            tma3d_mc(dst + rank * 6144, &maps.w1b, 0, (u - 8) * 64 + rank * 32, s * 7, fb);
          } else if (u < 24) {
            mbar_expect_tx(fb, 16384);
            tma2d_mc(dst + rank * 8192, &maps.w1a, s * 224 + 96 + rank * 64, ((u - 15 + s) & 7) * 64, fb);
          } else if (u == 25) {
            mbar_expect_tx(fb, 16384);
            tma2d_mc(dst + rank * 8192, mc, s * 64, ((s + 1) & 7) * 64, fb);
          } else {
            mbar_expect_tx(fb, 14336);
            tma2d_mc(dst + rank * 7168, &maps.w2, ((s + 1) & 7) * 64, s * 224 + (u - 24) * 56 + rank * 56, fb);
          }
          if (++slot == NSLOT) { slot = 0; ph ^= 1; }
        }
#pragma unroll 1
        for (int p = 1; p < 8; p++) {
          const int piece = (s + 1 + p) & 7, grp = p % 3;
          const uint32_t fb = sb + OFF_XFULL + 8 * p, dst = grp == 1 ? sb + OFF_X + 2 * 16384 : sb + OFF_RING + grp * 24576;
          if (p >= 3) mbar_wait(sb + OFF_EMPTY + 8 * (p - 3), 0);
          else if (p == 2) mbar_wait(sb + OFF_EMPTY + 40, 1);
          TS2(0, 32 + p);
          mbar_expect_tx(fb, 45056);
          tma2d_mc(dst + rank * 7168, &maps.w2, piece * 64, s * 224 + rank * 56, fb);
          tma2d_mc(dst + 16384 + rank * 8192, mc, s * 64, piece * 64, fb);
          tma2d_mc(dst + 32768 + rank * 7168, &maps.w2, piece * 64, s * 224 + 112 + rank * 56, fb);
        }
        TS(2, 2);
      }
    }
  }
}

typedef CUresult (*EncFn)(CUtensorMap*, CUtensorMapDataType, cuuint32_t, void*, const cuuint64_t*, const cuuint64_t*, const cuuint32_t*,
                          const cuuint32_t*, CUtensorMapInterleave, CUtensorMapSwizzle, CUtensorMapL2promotion, CUtensorMapFloatOOBfill);

void encode(EncFn f, CUtensorMap* mp, const void* p, int rank, const cuuint64_t* dims, const cuuint64_t* strides, const cuuint32_t* box, CUtensorMapSwizzle sw) {
  cuuint32_t es[5] = {1, 1, 1, 1, 1};
  f(mp, CU_TENSOR_MAP_DATA_TYPE_BFLOAT16, rank, const_cast<void*>(p), dims, strides, box, es, CU_TENSOR_MAP_INTERLEAVE_NONE, sw,
    CU_TENSOR_MAP_L2_PROMOTION_L2_128B, CU_TENSOR_MAP_FLOAT_OOB_FILL_NONE);
}

}

extern "C" void kernel_launch(void* const* d_in, const int* in_sizes, int n_in, void* d_out, int out_size) {
  typedef const __nv_bfloat16* bp;
  bp x = (bp)d_in[0], lre = (bp)d_in[1], lim = (bp)d_in[2], bre = (bp)d_in[3], bim = (bp)d_in[4], cre = (bp)d_in[5], cim = (bp)d_in[6],
     ldt = (bp)d_in[7], dsk = (bp)d_in[8], w1 = (bp)d_in[10], b1 = (bp)d_in[11], w2 = (bp)d_in[12], b2 = (bp)d_in[13], gw = (bp)d_in[14];
  static EncFn enc = nullptr;
  if (!enc) {
    void* f = nullptr;
    cudaDriverEntryPointQueryResult qr;
    cudaGetDriverEntryPoint("cuTensorMapEncodeTiled", &f, cudaEnableDefault, &qr);
    enc = (EncFn)f;
    cudaFuncSetAttribute(fused_kernel, cudaFuncAttributeMaxDynamicSharedMemorySize, SMEM_BYTES);
  }
  Maps maps;
  {
    cuuint64_t d[5] = {DM, 2, 4, 8, SEQ / 64}, st[4] = {DM * 2, 16 * DM * 2, 2 * DM * 2, 64 * DM * 2};
    cuuint32_t bx[5] = {64, 2, 4, 8, 2};
    encode(enc, &maps.x, x, 5, d, st, bx, CU_TENSOR_MAP_SWIZZLE_128B);
  }
  {
    cuuint64_t d[2] = {DM, DM}, st[1] = {DM * 2};
    cuuint32_t bx[2] = {64, 64};
    encode(enc, &maps.bre, bre, 2, d, st, bx, CU_TENSOR_MAP_SWIZZLE_128B);
    encode(enc, &maps.bim, bim, 2, d, st, bx, CU_TENSOR_MAP_SWIZZLE_128B);
    encode(enc, &maps.cre, cre, 2, d, st, bx, CU_TENSOR_MAP_SWIZZLE_128B);
    encode(enc, &maps.cim, cim, 2, d, st, bx, CU_TENSOR_MAP_SWIZZLE_128B);
  }
  {
    cuuint64_t d[2] = {FF, DM}, st[1] = {FF * 2};
    cuuint32_t bx[2] = {64, 64};
    encode(enc, &maps.w1a, w1, 2, d, st, bx, CU_TENSOR_MAP_SWIZZLE_128B);
    cuuint64_t d3[3] = {32, DM, FF / 32}, st3[2] = {FF * 2, 64};
    cuuint32_t bx3[3] = {32, 32, 3};
    encode(enc, &maps.w1b, w1, 3, d3, st3, bx3, CU_TENSOR_MAP_SWIZZLE_64B);
  }
  {
    cuuint64_t d[2] = {DM, FF}, st[1] = {DM * 2};
    cuuint32_t bx[2] = {64, 56};
    encode(enc, &maps.w2, w2, 2, d, st, bx, CU_TENSOR_MAP_SWIZZLE_128B);
  }
  fused_kernel<<<128, 384, SMEM_BYTES>>>(maps, lre, lim, ldt, dsk, b1, b2, gw, w1, w2, cre, cim, x, bre, bim, (float*)d_out);
}
```

```cpp
#include <cuda_runtime.h>
#include <cuda_bf16.h>
#include <cuda.h>
#include <stdint.h>

#define PF 6
#define SEND_TMA 0
#define PREW 0
#define CK 3
#define D0 600
#define D1 500
#define DN 1
#define PROMO CU_TENSOR_MAP_L2_PROMOTION_L2_128B
#define TMP 3
#define MAP 1
#define STV4 1
#define R2E 0
#define PFK 5
namespace {

constexpr int SEQ = 2048, DM = 512, FF = 1792;
constexpr int NSLOT = 6;
constexpr uint32_t OFF_X = 0, OFF_RING = 131072, OFF_MISC = 229376;
constexpr uint32_t OFF_XFULL = OFF_MISC, OFF_FULL = OFF_XFULL + 64, OFF_EMPTY = OFF_FULL + 48, OFF_GBAR = OFF_EMPTY + 48,
                   OFF_CBAR = OFF_GBAR + 8, OFF_LBAR = OFF_CBAR + 8, OFF_EPOCH = OFF_CBAR + 24;
constexpr uint32_t OFF_LC = OFF_MISC + 256;
constexpr uint32_t OFF_GS = OFF_LC;
constexpr uint32_t OFF_DB = OFF_LC + 512;
constexpr uint32_t OFF_CARRY = OFF_LC + 1024;
constexpr uint32_t OFF_DBG = OFF_CARRY + 1024;
constexpr uint32_t SMEM_BYTES = OFF_DBG + 768;
static_assert(SMEM_BYTES <= 232448, "smem");

struct Maps {
  CUtensorMap x, bre, bim, w1b, w1a, w2, cre, cim; };

__device__ uint4 g_part[16 * 8 * 7 * 1024];
__device__ float2 g_end[8 * 16 * 64];
__device__ unsigned g_gate[SEQ];
__device__ unsigned g_epoch[128];
#define TG(role) do {} while (0)
#define TS2(role, i) do {} while (0)
#define TS(role, i) do {} while (0)
#define TDUMP() do {} while (0)

__device__ __forceinline__ void mbar_init(uint32_t bar, uint32_t cnt) { asm volatile("mbarrier.init.shared::cta.b64 [%0], %1;" ::"r"(bar), "r"(cnt)); }
__device__ __forceinline__ void mbar_expect_tx(uint32_t bar, uint32_t bytes) { asm volatile("mbarrier.arrive.expect_tx.shared::cta.b64 _, [%0], %1;" ::"r"(bar), "r"(bytes) : "memory"); }
__device__ __forceinline__ void mbar_arrive(uint32_t bar) { asm volatile("mbarrier.arrive.shared::cta.b64 _, [%0];" ::"r"(bar) : "memory"); }
__device__ __forceinline__ void mbar_arrive_cl(uint32_t cbar) { asm volatile("mbarrier.arrive.shared::cluster.b64 _, [%0];" ::"r"(cbar) : "memory"); }
__device__ __forceinline__ void mbar_wait(uint32_t bar, uint32_t parity) {
  asm volatile(
      "{\n.reg .pred p;\n.reg .u32 c;\n"
      "mbarrier.try_wait.parity.shared::cta.b64 p, [%0], %1;\n"
      "@p bra.uni LAB_DONE;\n"
      "mov.u32 c, 0;\n"
      "LAB_WAIT:\n"
      "mbarrier.try_wait.parity.shared::cta.b64 p, [%0], %1;\n"
      "@p bra.uni LAB_DONE;\n"
      "add.u32 c, c, 1;\nsetp.lt.u32 p, c, 200000;\n@p bra.uni LAB_WAIT;\n"
      "LAB_DONE:\n}" ::"r"(bar), "r"(parity) : "memory");
}
__device__ __forceinline__ void tma2d(uint32_t dst, const CUtensorMap* m, int c0, int c1, uint32_t bar) {
  asm volatile("cp.async.bulk.tensor.2d.shared::cluster.global.mbarrier::complete_tx::bytes [%0], [%1, {%3,%4}], [%2];"
               ::"r"(dst), "l"(m), "r"(bar), "r"(c0), "r"(c1) : "memory");
}
__device__ __forceinline__ void tma2d_mc(uint32_t dst, const CUtensorMap* m, int c0, int c1, uint32_t bar) {
  asm volatile("cp.async.bulk.tensor.2d.shared::cluster.global.mbarrier::complete_tx::bytes.multicast::cluster [%0], [%1, {%3,%4}], [%2], %5;"
               ::"r"(dst), "l"(m), "r"(bar), "r"(c0), "r"(c1), "h"((uint16_t)3) : "memory");
}
__device__ __forceinline__ void tma3d_mc(uint32_t dst, const CUtensorMap* m, int c0, int c1, int c2, uint32_t bar) {
  asm volatile("cp.async.bulk.tensor.3d.shared::cluster.global.mbarrier::complete_tx::bytes.multicast::cluster [%0], [%1, {%3,%4,%5}], [%2], %6;"
               ::"r"(dst), "l"(m), "r"(bar), "r"(c0), "r"(c1), "r"(c2), "h"((uint16_t)3) : "memory");
}
__device__ __forceinline__ void tma5d(uint32_t dst, const CUtensorMap* m, int c0, int c4, uint32_t bar) {
  asm volatile("cp.async.bulk.tensor.5d.shared::cluster.global.mbarrier::complete_tx::bytes [%0], [%1, {%3,%5,%5,%5,%4}], [%2];"
               ::"r"(dst), "l"(m), "r"(bar), "r"(c0), "r"(c4), "r"(0) : "memory");
}
__device__ __forceinline__ void l2_prefetch(const void* p, uint32_t bytes) { asm volatile("cp.async.bulk.prefetch.L2.global [%0], %1;" ::"l"(p), "r"(bytes) : "memory"); }
__device__ __forceinline__ bool elect_one() {
  uint32_t pred;
  asm volatile("{.reg .pred P; elect.sync _|P, 0xffffffff; selp.u32 %0, 1, 0, P;}" : "=r"(pred));
  return pred != 0;
}
__device__ __forceinline__ void wg_fence() { asm volatile("wgmma.fence.sync.aligned;" ::: "memory"); }
__device__ __forceinline__ void wg_commit() { asm volatile("wgmma.commit_group.sync.aligned;" ::: "memory"); }
template <int N> __device__ __forceinline__ void wg_wait() { asm volatile("wgmma.wait_group.sync.aligned %0;" ::"n"(N) : "memory"); }
template <int N> __device__ __forceinline__ void reg_fence(float (&d)[N]) {
#pragma unroll
  for (int i = 0; i < N; i++) asm volatile("" : "+f"(d[i])::"memory");
}
__device__ __forceinline__ void bar_sync(int id, int n) { asm volatile("bar.sync %0, %1;" ::"r"(id), "r"(n) : "memory"); }
__device__ __forceinline__ void bar_arrive(int id, int n) { asm volatile("bar.arrive %0, %1;" ::"r"(id), "r"(n) : "memory"); }
constexpr uint32_t DH128 = (1024 >> 4) | (1u << 30), DH64 = (512 >> 4) | (2u << 30);
__host__ __device__ constexpr uint32_t lbo(uint32_t bytes) { return (bytes >> 4) << 20; }
__device__ __forceinline__ uint32_t pack_bf16(float lo, float hi) { uint32_t r; asm("cvt.rn.bf16x2.f32 %0, %1, %2;" : "=r"(r) : "f"(hi), "f"(lo)); return r; }
__device__ __forceinline__ float bf_lo(uint32_t v) { return __uint_as_float(v << 16); }
__device__ __forceinline__ float bf_hi(uint32_t v) { return __uint_as_float(v & 0xffff0000u); }
__device__ __forceinline__ float bf_ld(const __nv_bfloat16* p) { return __bfloat162float(__ldg(p)); }
__device__ __forceinline__ uint32_t raw_ld(const __nv_bfloat16* p) { return __ldg(reinterpret_cast<const unsigned short*>(p)); }
__device__ __forceinline__ uint32_t late16(uint32_t bar) {
  uint32_t r;
  asm volatile("{.reg .pred p; mbarrier.test_wait.parity.shared::cta.b64 p, [%1], 0; selp.u32 %0, 16, 0, p;}" : "=r"(r) : "r"(bar) : "memory");
  return r;
}
__device__ __forceinline__ float2 lds_f2(uint32_t a) { float2 v; asm volatile("ld.shared.v2.f32 {%0,%1}, [%2];" : "=f"(v.x), "=f"(v.y) : "r"(a)); return v; }
__device__ __forceinline__ float lds_f(uint32_t a) { float v; asm volatile("ld.shared.f32 %0, [%1];" : "=f"(v) : "r"(a)); return v; }
__device__ __forceinline__ uint32_t lds_h(uint32_t a) { uint32_t v; asm volatile("ld.shared.u16 %0, [%1];" : "=r"(v) : "r"(a)); return v; }
__device__ __forceinline__ uint32_t lds_u(uint32_t a) { uint32_t v; asm volatile("ld.shared.u32 %0, [%1];" : "=r"(v) : "r"(a)); return v; }
__device__ __forceinline__ uint4 lds_u4(uint32_t a) { uint4 v; asm volatile("ld.shared.v4.u32 {%0,%1,%2,%3}, [%4];" : "=r"(v.x), "=r"(v.y), "=r"(v.z), "=r"(v.w) : "r"(a)); return v; }
__device__ __forceinline__ void st_b128(uint4* p, uint32_t a, uint32_t b, uint32_t c, uint32_t d) {
  asm volatile("st.relaxed.gpu.global.v4.b32 [%0], {%1,%2,%3,%4};" ::"l"(p), "r"(a), "r"(b), "r"(c), "r"(d) : "memory");
}
__device__ __forceinline__ void ld_b128(const uint4* p, uint32_t& a, uint32_t& b, uint32_t& c, uint32_t& d) {
  asm volatile("{.reg .b64 l, h; .reg .b128 v; ld.relaxed.gpu.global.b128 v, [%4]; mov.b128 {l,h}, v; mov.b64 {%0,%1}, l; mov.b64 {%2,%3}, h;}"
               : "=r"(a), "=r"(b), "=r"(c), "=r"(d) : "l"(p) : "memory");
}
__device__ __forceinline__ float tanh_fast(float x) { float y; asm("tanh.approx.f32 %0, %1;" : "=f"(y) : "f"(x)); return y; }
__device__ __forceinline__ float gelu2(float v) {
  float p = fmaf(v * v, 0.0356774081363f, 0.7978845608029f);
  return fmaf(v, tanh_fast(v * p), v);
}
__device__ __forceinline__ uint32_t bf2_mul(uint32_t a, uint32_t b) { uint32_t r; asm("mul.rn.bf16x2 %0, %1, %2;" : "=r"(r) : "r"(a), "r"(b)); return r; }
__device__ __forceinline__ uint32_t bf2_add(uint32_t a, uint32_t b) { uint32_t r; asm("add.rn.bf16x2 %0, %1, %2;" : "=r"(r) : "r"(a), "r"(b)); return r; }
__device__ __forceinline__ uint32_t bf2_fma(uint32_t a, uint32_t b, uint32_t c) { uint32_t r; asm("fma.rn.bf16x2 %0, %1, %2, %3;" : "=r"(r) : "r"(a), "r"(b), "r"(c)); return r; }
__device__ __forceinline__ void pin(float& a) { asm volatile("" : "+f"(a)::"memory"); }
__device__ __forceinline__ void pin(uint32_t& a) { asm volatile("" : "+r"(a)::"memory"); }
struct cplx { float re, im; };
__device__ __forceinline__ cplx cmul(cplx a, cplx b) { return {fmaf(a.re, b.re, -a.im * b.im), fmaf(a.re, b.im, a.im * b.re)}; }
__device__ __forceinline__ cplx cfma(cplx a, cplx b, cplx c) {
  return {fmaf(a.re, b.re, fmaf(-a.im, b.im, c.re)), fmaf(a.re, b.im, fmaf(a.im, b.re, c.im))};
}
__device__ __forceinline__ cplx make_lam(float lre, float lim, float ldt) {
  float dt = __bfloat162float(__float2bfloat16_rn(expf(ldt)));
  float mag = expf(dt * lre), sn, cs;
  sincospif(dt * lim * 0.31830988618379067f, &sn, &cs);
  return {mag * cs, mag * sn};
}

template<int TA,int TB,uint32_t AH,uint32_t BH> __device__ __forceinline__ void wgmma_n64_ss(float (&d)[32], uint32_t al, uint32_t ao, uint32_t bl, uint32_t bo, int scale_d){
  asm volatile("{.reg .pred p; .reg .b32 t, v; .reg .b64 da, db; setp.ne.b32 p, %36, 0; add.u32 t, %32, %33; mov.b64 da, {t, %39}; add.u32 v, %34, %35; mov.b64 db, {v, %40};\n"
   "wgmma.mma_async.sync.aligned.m64n64k16.f32.bf16.bf16 {%0,%1,%2,%3,%4,%5,%6,%7,%8,%9,%10,%11,%12,%13,%14,%15,%16,%17,%18,%19,%20,%21,%22,%23,%24,%25,%26,%27,%28,%29,%30,%31}, da, db, p, 1, 1, %37, %38;}"
   : "+f"(d[0]),"+f"(d[1]),"+f"(d[2]),"+f"(d[3]),"+f"(d[4]),"+f"(d[5]),"+f"(d[6]),"+f"(d[7]),"+f"(d[8]),"+f"(d[9]),"+f"(d[10]),"+f"(d[11]),"+f"(d[12]),"+f"(d[13]),"+f"(d[14]),"+f"(d[15]),"+f"(d[16]),"+f"(d[17]),"+f"(d[18]),"+f"(d[19]),"+f"(d[20]),"+f"(d[21]),"+f"(d[22]),"+f"(d[23]),"+f"(d[24]),"+f"(d[25]),"+f"(d[26]),"+f"(d[27]),"+f"(d[28]),"+f"(d[29]),"+f"(d[30]),"+f"(d[31])
   : "r"(al),"r"(ao >> 4),"r"(bl),"r"(bo >> 4),"r"(scale_d),"n"(TA),"n"(TB),"n"(AH),"n"(BH));
}
template<int TB,uint32_t BH> __device__ __forceinline__ void wgmma_n64_rs(float (&d)[32], uint32_t a0,uint32_t a1,uint32_t a2,uint32_t a3, uint32_t bl, uint32_t bo, int scale_d){
  asm volatile("{.reg .pred p; .reg .b32 t; .reg .b64 db; setp.ne.b32 p, %38, 0; add.u32 t, %36, %37; mov.b64 db, {t, %40};\n"
   "wgmma.mma_async.sync.aligned.m64n64k16.f32.bf16.bf16 {%0,%1,%2,%3,%4,%5,%6,%7,%8,%9,%10,%11,%12,%13,%14,%15,%16,%17,%18,%19,%20,%21,%22,%23,%24,%25,%26,%27,%28,%29,%30,%31}, {%32,%33,%34,%35}, db, p, 1, 1, %39;}"
   : "+f"(d[0]),"+f"(d[1]),"+f"(d[2]),"+f"(d[3]),"+f"(d[4]),"+f"(d[5]),"+f"(d[6]),"+f"(d[7]),"+f"(d[8]),"+f"(d[9]),"+f"(d[10]),"+f"(d[11]),"+f"(d[12]),"+f"(d[13]),"+f"(d[14]),"+f"(d[15]),"+f"(d[16]),"+f"(d[17]),"+f"(d[18]),"+f"(d[19]),"+f"(d[20]),"+f"(d[21]),"+f"(d[22]),"+f"(d[23]),"+f"(d[24]),"+f"(d[25]),"+f"(d[26]),"+f"(d[27]),"+f"(d[28]),"+f"(d[29]),"+f"(d[30]),"+f"(d[31])
   : "r"(a0),"r"(a1),"r"(a2),"r"(a3),"r"(bl),"r"(bo >> 4),"r"(scale_d),"n"(TB),"n"(BH));
}
template<int TA,int TB,uint32_t AH,uint32_t BH> __device__ __forceinline__ void wgmma_n96_ss(float (&d)[48], uint32_t al, uint32_t ao, uint32_t bl, uint32_t bo, int scale_d){
  asm volatile("{.reg .pred p; .reg .b32 t, v; .reg .b64 da, db; setp.ne.b32 p, %52, 0; add.u32 t, %48, %49; mov.b64 da, {t, %55}; add.u32 v, %50, %51; mov.b64 db, {v, %56};\n"
   "wgmma.mma_async.sync.aligned.m64n96k16.f32.bf16.bf16 {%0,%1,%2,%3,%4,%5,%6,%7,%8,%9,%10,%11,%12,%13,%14,%15,%16,%17,%18,%19,%20,%21,%22,%23,%24,%25,%26,%27,%28,%29,%30,%31,%32,%33,%34,%35,%36,%37,%38,%39,%40,%41,%42,%43,%44,%45,%46,%47}, da, db, p, 1, 1, %53, %54;}"
   : "+f"(d[0]),"+f"(d[1]),"+f"(d[2]),"+f"(d[3]),"+f"(d[4]),"+f"(d[5]),"+f"(d[6]),"+f"(d[7]),"+f"(d[8]),"+f"(d[9]),"+f"(d[10]),"+f"(d[11]),"+f"(d[12]),"+f"(d[13]),"+f"(d[14]),"+f"(d[15]),"+f"(d[16]),"+f"(d[17]),"+f"(d[18]),"+f"(d[19]),"+f"(d[20]),"+f"(d[21]),"+f"(d[22]),"+f"(d[23]),"+f"(d[24]),"+f"(d[25]),"+f"(d[26]),"+f"(d[27]),"+f"(d[28]),"+f"(d[29]),"+f"(d[30]),"+f"(d[31]),"+f"(d[32]),"+f"(d[33]),"+f"(d[34]),"+f"(d[35]),"+f"(d[36]),"+f"(d[37]),"+f"(d[38]),"+f"(d[39]),"+f"(d[40]),"+f"(d[41]),"+f"(d[42]),"+f"(d[43]),"+f"(d[44]),"+f"(d[45]),"+f"(d[46]),"+f"(d[47])
   : "r"(al),"r"(ao >> 4),"r"(bl),"r"(bo >> 4),"r"(scale_d),"n"(TA),"n"(TB),"n"(AH),"n"(BH));
}
template<int TA,int TB,uint32_t AH,uint32_t BH> __device__ __forceinline__ void wgmma_n128_ss(float (&d)[64], uint32_t al, uint32_t ao, uint32_t bl, uint32_t bo, int scale_d){
  asm volatile("{.reg .pred p; .reg .b32 t, v; .reg .b64 da, db; setp.ne.b32 p, %68, 0; add.u32 t, %64, %65; mov.b64 da, {t, %71}; add.u32 v, %66, %67; mov.b64 db, {v, %72};\n"
   "wgmma.mma_async.sync.aligned.m64n128k16.f32.bf16.bf16 {%0,%1,%2,%3,%4,%5,%6,%7,%8,%9,%10,%11,%12,%13,%14,%15,%16,%17,%18,%19,%20,%21,%22,%23,%24,%25,%26,%27,%28,%29,%30,%31,%32,%33,%34,%35,%36,%37,%38,%39,%40,%41,%42,%43,%44,%45,%46,%47,%48,%49,%50,%51,%52,%53,%54,%55,%56,%57,%58,%59,%60,%61,%62,%63}, da, db, p, 1, 1, %69, %70;}"
   : "+f"(d[0]),"+f"(d[1]),"+f"(d[2]),"+f"(d[3]),"+f"(d[4]),"+f"(d[5]),"+f"(d[6]),"+f"(d[7]),"+f"(d[8]),"+f"(d[9]),"+f"(d[10]),"+f"(d[11]),"+f"(d[12]),"+f"(d[13]),"+f"(d[14]),"+f"(d[15]),"+f"(d[16]),"+f"(d[17]),"+f"(d[18]),"+f"(d[19]),"+f"(d[20]),"+f"(d[21]),"+f"(d[22]),"+f"(d[23]),"+f"(d[24]),"+f"(d[25]),"+f"(d[26]),"+f"(d[27]),"+f"(d[28]),"+f"(d[29]),"+f"(d[30]),"+f"(d[31]),"+f"(d[32]),"+f"(d[33]),"+f"(d[34]),"+f"(d[35]),"+f"(d[36]),"+f"(d[37]),"+f"(d[38]),"+f"(d[39]),"+f"(d[40]),"+f"(d[41]),"+f"(d[42]),"+f"(d[43]),"+f"(d[44]),"+f"(d[45]),"+f"(d[46]),"+f"(d[47]),"+f"(d[48]),"+f"(d[49]),"+f"(d[50]),"+f"(d[51]),"+f"(d[52]),"+f"(d[53]),"+f"(d[54]),"+f"(d[55]),"+f"(d[56]),"+f"(d[57]),"+f"(d[58]),"+f"(d[59]),"+f"(d[60]),"+f"(d[61]),"+f"(d[62]),"+f"(d[63])
   : "r"(al),"r"(ao >> 4),"r"(bl),"r"(bo >> 4),"r"(scale_d),"n"(TA),"n"(TB),"n"(AH),"n"(BH));
}

__global__ void __cluster_dims__(2, 1, 1) __launch_bounds__(384, 1)
fused_kernel(const __nv_bfloat16* __restrict__ lam_re,
             const __nv_bfloat16* __restrict__ lam_im, const __nv_bfloat16* __restrict__ log_dt, const __nv_bfloat16* __restrict__ dskip,
             const __nv_bfloat16* __restrict__ b1, const __nv_bfloat16* __restrict__ b2, const __nv_bfloat16* __restrict__ gate_w,
             const __nv_bfloat16* __restrict__ pf_w1, const __nv_bfloat16* __restrict__ pf_w2, const __nv_bfloat16* __restrict__ pf_cre,
             const __nv_bfloat16* __restrict__ pf_cim, float* __restrict__ out, const __grid_constant__ Maps maps) {
  extern __shared__ __align__(1024) unsigned char smem_raw[];
  const uint32_t sb = (uint32_t)__cvta_generic_to_shared(smem_raw);
  const int b = blockIdx.x;
  const int rank = b & 1, cl = b >> 1;
  const int s = cl >> 3, mi = cl & 7;
  const int m = mi * 2 + rank;
  const int warp = __shfl_sync(0xffffffffu, (int)(threadIdx.x >> 5), 0);
  const int lane = threadIdx.x & 31;
  const int xrot = 7 - s;

  if (elect_one()) {
    if (warp == 8) TS(2, 0);
    if (warp < TMP) asm volatile("prefetch.tensormap [%0];" ::"l"(&maps.x + warp) : "memory");
    const uint32_t c = warp < 7 ? 1 : warp < 10 ? 16 : 64;
    mbar_init(sb + OFF_XFULL + 16 * warp, c);
    mbar_init(sb + OFF_XFULL + 16 * warp + 8, warp < 10 ? c : 96);
    asm volatile("fence.mbarrier_init.release.cluster;" ::: "memory");
  }
  __syncwarp();
  asm volatile("barrier.cluster.arrive.relaxed.aligned;" ::: "memory");
  if (warp < 8) {
    const int wg = warp >> 2, w = warp & 3, q = lane & 3, gr = lane >> 2;
    uint32_t bv[28];
#pragma unroll
    for (int j = 0; j < 28; j++) bv[j] = __ldg(reinterpret_cast<const uint32_t*>(b1 + s * 224 + j * 8) + q);
    asm volatile("setmaxnreg.inc.sync.aligned.u32 224;");
    asm volatile("barrier.cluster.wait.aligned;" ::: "memory");
    TS(wg, 0);
    uint32_t ebar;
    asm volatile("mapa.shared::cluster.u32 %0, %1, %2;" : "=r"(ebar) : "r"(sb + OFF_EMPTY), "r"(lane & 1));
    auto release = [&](int slot) { if (lane < 2) mbar_arrive_cl(ebar + 8 * slot); };
    const uint32_t xw = sb + OFF_X + wg * 8192, fullb = sb + OFF_FULL;
    const uint32_t dxw = (xw & 0x3FFFF) >> 4, dring = ((sb + OFF_RING) & 0x3FFFF) >> 4;

    float ure[32], uim[32], aa[48], ab[64];
    cplx lam[2], coef[2], l16[2], l32[2], lq[2], pre[2], e[2];
    uint32_t sh16, mhi;
    TS(wg, 24);

#pragma unroll
    for (int kb = 0; kb < 8; kb++) {
      const int slot = kb % NSLOT;
      TS2(1, kb);
      mbar_wait(sb + OFF_XFULL + 8 * kb, 0);
      if (kb == 0) TS(wg, 18);
      mbar_wait(fullb + 8 * slot, (kb / NSLOT) & 1);
      TS2(2, kb);
      if (kb == 0) TS(wg, 1);
      wg_fence();
      const uint32_t dxa = dxw + ((kb + xrot) & 7) * 1024;
#pragma unroll
      for (int kk = 0; kk < 4; kk++) {
        wgmma_n64_ss<0, 0, DH128, DH128>(ure, dring, slot * 16384 + kk * 32, dxa, kk * 32, (kb | kk) != 0);
        wgmma_n64_ss<0, 0, DH128, DH128>(uim, dring, slot * 16384 + 8192 + kk * 32, dxa, kk * 32, (kb | kk) != 0);
      }
      wg_commit();
      if (kb > 0) { wg_wait<1>(); release((kb - 1) % NSLOT); }
      if (kb == 1) { sh16 = late16(sb + OFF_XFULL); mhi = 0xffffffffu << sh16; }
      if (kb >= 1 && kb < 5) {
#pragma unroll
        for (int j = (kb - 1) * 7; j < kb * 7; j++) {
          pin(bv[j]);
          float* d = j < 12 ? aa + 4 * j : ab + 4 * (j - 12);
          d[0] = d[2] = __uint_as_float(bv[j] << sh16); d[1] = d[3] = __uint_as_float(bv[j] & mhi);
          pin(d[0]); pin(d[1]); pin(d[2]); pin(d[3]);
        }
      }
      if (kb == 4) {
        mbar_wait(sb + OFF_LBAR, 0);
#pragma unroll
        for (int h = 0; h < 2; h++) {
          const uint4 v = lds_u4(sb + OFF_LC + (w * 16 + gr + 8 * h) * 16);
          lam[h] = cplx{__uint_as_float(v.x), __uint_as_float(v.y)};
          coef[h] = cplx{__uint_as_float(v.z), __uint_as_float(v.w)};
        }
      }
      if (kb == 5) {
#pragma unroll
        for (int h = 0; h < 2; h++) {
          pin(lam[h].re); pin(lam[h].im);
          cplx t = cmul(lam[h], lam[h]); t = cmul(t, t); t = cmul(t, t);
          l16[h] = cmul(t, t); l32[h] = cmul(l16[h], l16[h]);
          pin(l32[h].re); pin(l32[h].im);
        }
      }
      if (kb == 6) {
#pragma unroll
        for (int h = 0; h < 2; h++) {
          pin(l16[h].re); pin(l16[h].im);
          const cplx a = (q & 1) ? l16[h] : cplx{1.f, 0.f}, c = (q & 2) ? l32[h] : cplx{1.f, 0.f};
          lq[h] = cmul(cmul(a, c), coef[h]);
          pin(lq[h].re); pin(lq[h].im);
        }
      }
    }
    TS(wg, 2);
    auto scale_u = [&](int i0, int i1) {
#pragma unroll
      for (int i = 0; i < 32; i++) if (i >= i0 && i < i1) {
        pin(ure[i]); pin(uim[i]);
        const cplx v = cmul(coef[(i >> 1) & 1], cplx{ure[i], uim[i]});
        ure[i] = v.re; uim[i] = v.im;
        pin(ure[i]); pin(uim[i]);
      }
    };
#pragma unroll
    for (int kb = 0; kb < 8; kb++) {
      const int u = 8 + kb, slot = u % NSLOT;
      TS2(1, u);
      mbar_wait(fullb + 8 * slot, (u / NSLOT) & 1);
      TS2(2, u);
      wg_fence();
      const uint32_t dxa = dxw + ((kb + xrot) & 7) * 1024;
#pragma unroll
      for (int kk = 0; kk < 4; kk++)
        wgmma_n96_ss<0, 1, DH128, DH64>(aa, dxa, kk * 32, dring, slot * 16384 + (kk >> 1) * 6144 + (kk & 1) * 1024 + lbo(2048), 1);
      wg_commit();
      wg_wait<1>();
      release((u - 1) % NSLOT);
      if (kb == 0) {
        reg_fence(ure); reg_fence(uim);
#pragma unroll
        for (int h = 0; h < 2; h++) e[h] = cplx{ure[2 * h], uim[2 * h]};
      }
      if (kb == 0 || kb == 2 || kb == 3) {
        const int ch = kb ? kb - 1 : 0;
#pragma unroll
        for (int t = 1 + 5 * ch; t < 6 + 5 * ch; t++)
#pragma unroll
          for (int h = 0; h < 2; h++) { const int i = 4 * (t >> 1) + 2 * h + (t & 1); e[h] = cfma(lam[h], e[h], cplx{ure[i], uim[i]}); }
#pragma unroll
        for (int h = 0; h < 2; h++) { pin(e[h].re); pin(e[h].im); }
      } else if (kb == 4) {
#pragma unroll
        for (int h = 0; h < 2; h++) {
          cplx y = {__shfl_up_sync(0xffffffffu, e[h].re, 1, 4), __shfl_up_sync(0xffffffffu, e[h].im, 1, 4)};
          if (q >= 1) e[h] = cfma(l16[h], y, e[h]);
          y = cplx{__shfl_up_sync(0xffffffffu, e[h].re, 2, 4), __shfl_up_sync(0xffffffffu, e[h].im, 2, 4)};
          if (q >= 2) e[h] = cfma(l32[h], y, e[h]);
        }
        if (q == 3) {
#pragma unroll
          for (int h = 0; h < 2; h++)
            asm volatile("st.shared.v2.f32 [%0], {%1,%2};" ::"r"(sb + OFF_CARRY + wg * 512 + (w * 16 + gr + 8 * h) * 8), "f"(e[h].re), "f"(e[h].im) : "memory");
          mbar_arrive(sb + OFF_GBAR);
        }
#pragma unroll
        for (int h = 0; h < 2; h++) {
          const cplx y = {__shfl_up_sync(0xffffffffu, e[h].re, 1, 4), __shfl_up_sync(0xffffffffu, e[h].im, 1, 4)};
          pre[h] = (q >= 1) ? cmul(coef[h], y) : cplx{0.f, 0.f};
          pin(pre[h].re); pin(pre[h].im);
        }
        TS(wg, 3);
      } else if (kb > 4) {
        scale_u(kb == 5 ? 0 : kb == 6 ? 4 : 12, kb == 5 ? 4 : kb == 6 ? 12 : 20);
      }
    }
    TS(wg, 4);
    uint32_t H[56];
    cplx hst[2];
    const uint32_t dh = dxw;
    const uint32_t hst_addr = xw + (w * 16 + (lane & 15)) * 128 + (((lane >> 4) ^ (lane & 7)) << 4);
#pragma unroll
    for (int kb = 0; kb < 8; kb++) {
      const int u = 16 + kb, slot = u % NSLOT;
      TS2(1, u);
      mbar_wait(fullb + 8 * slot, (u / NSLOT) & 1);
      TS2(2, u);
      wg_fence();
#pragma unroll
      for (int kk = 0; kk < 4; kk++)
        wgmma_n128_ss<0, 1, DH128, DH128>(ab, dxw, kb * 16384 + kk * 32, dring, slot * 16384 + kk * 2048 + lbo(8192), 1);
      wg_commit();
      wg_wait<1>();
      release((u - 1) % NSLOT);
      if (kb == 0) scale_u(20, 32);
      if (kb < 5 && kb != 1) {
        const int ch = kb ? kb - 1 : 0;
#pragma unroll
        for (int i = ch * 6; i < ch * 6 + 6; i++) {
          pin(aa[2 * i]); pin(aa[2 * i + 1]);
          H[i] = pack_bf16(gelu2(aa[2 * i]), gelu2(aa[2 * i + 1]));
          pin(H[i]);
        }
      }
      if (kb >= 4) {
        if (kb == 4) {
          TS(wg, 5);
          mbar_wait(sb + OFF_CBAR, 0);
          TS(wg, 6);
#pragma unroll
          for (int h = 0; h < 2; h++) {
            const float2 c = lds_f2(sb + OFF_CARRY + wg * 512 + (w * 16 + gr + 8 * h) * 8);
            hst[h] = cfma(lq[h], cplx{c.x, c.y}, pre[h]);
          }
        }
        const int j0 = (kb - 4) * 2;
        uint32_t rr[4], ri[4];
#pragma unroll
        for (int jj = 0; jj < 2; jj++) {
          const int j = j0 + jj;
          const uint32_t g2 = lds_u(sb + OFF_GS + (wg * 64 + j * 8 + q * 2) * 2);
#pragma unroll
          for (int h = 0; h < 2; h++) {
            const int i = 4 * j + 2 * h;
            const cplx h0 = cfma(lam[h], hst[h], cplx{ure[i], uim[i]});
            hst[h] = cfma(lam[h], h0, cplx{ure[i + 1], uim[i + 1]});
            rr[jj * 2 + h] = bf2_mul(pack_bf16(h0.re, hst[h].re), g2);
            ri[jj * 2 + h] = bf2_mul(pack_bf16(-h0.im, -hst[h].im), g2);
          }
        }
        const uint32_t a = hst_addr ^ (j0 << 4);
        asm volatile("stmatrix.sync.aligned.m8n8.x4.shared.b16 [%0], {%1,%2,%3,%4};" ::"r"(a), "r"(rr[0]), "r"(rr[1]), "r"(rr[2]), "r"(rr[3]) : "memory");
        asm volatile("stmatrix.sync.aligned.m8n8.x4.shared.b16 [%0], {%1,%2,%3,%4};" ::"r"(a + 16384), "r"(ri[0]), "r"(ri[1]), "r"(ri[2]), "r"(ri[3]) : "memory");
      }
    }
    TS(wg, 7);

    uint4* const psend = g_part + (size_t)m * (8 * 7 * 1024) + warp * 128;
    const uint4* const precv = g_part + (size_t)(m * 8 + s) * (7 * 1024) + warp * 128 + lane;
    const uint32_t stg = sb + OFF_X + 5 * 16384 + warp * 2048;
    const uint32_t dx0 = ((sb + OFF_X) & 0x3FFFF) >> 4;
    float o[32], fin[32], rho[2];
    uint32_t r0[16], r1[16], r2[16], sum[16], tag;
    auto send = [&](int p) {
#pragma unroll
      for (int i = 0; i < 4; i++) {
        uint32_t t0;
        asm("lop3.b32 %0, %1, 1, %2, 0xb8;" : "=r"(t0) : "r"(pack_bf16(o[8 * i], o[8 * i + 1])), "r"(tag));
        st_b128(psend + (((s + 1 + p) & 7) * 7 + p) * 1024 + i * 32 + lane, t0, pack_bf16(o[8 * i + 2], o[8 * i + 3]), pack_bf16(o[8 * i + 4], o[8 * i + 5]),
                pack_bf16(o[8 * i + 6], o[8 * i + 7]));
      }
    };
    auto recv_issue = [&](uint32_t (&r)[16], int p) {
#pragma unroll
      for (int i = 0; i < 4; i++) ld_b128(precv + p * 1024 + i * 32, r[4 * i], r[4 * i + 1], r[4 * i + 2], r[4 * i + 3]);
    };
    auto stale = [&](uint32_t (&r)[16]) {
      uint32_t t0, t1;
      asm("lop3.b32 %0, %1, %2, %3, 0x7e;" : "=r"(t0) : "r"(r[0]), "r"(r[4]), "r"(tag));
      asm("lop3.b32 %0, %1, %2, %3, 0x7e;" : "=r"(t1) : "r"(r[8]), "r"(r[12]), "r"(tag));
      uint32_t r_;
      asm volatile("{.reg .pred p; .reg .b32 t; lop3.b32 t, %1, %2, 1, 0xa8; setp.ne.u32 p, t, 0; vote.sync.any.pred p, p, 0xffffffff; selp.u32 %0, 1, 0, p;}" : "=r"(r_) : "r"(t0), "r"(t1));
      return r_ != 0;
    };
    auto recv_check = [&](uint32_t (&r)[16], int p) {
      if (__builtin_expect(stale(r), 0)) {
        int tries = 0;
#pragma unroll 1
        do { recv_issue(r, p); } while (stale(r) && ++tries < 200000);
      }
    };
    auto gelu_b = [&](int i0, int i1) {
#pragma unroll
      for (int i = i0; i < i1; i++) {
        pin(ab[2 * i]); pin(ab[2 * i + 1]);
        H[24 + i] = pack_bf16(gelu2(ab[2 * i]), gelu2(ab[2 * i + 1]));
        pin(H[24 + i]);
      }
    };
    auto mma = [&](float (&o)[32], uint32_t wo, int k0, int k1, int acc) {
      wg_fence();
#pragma unroll
      for (int k = k0; k < k1; k++) {
        if (k >= 6 && k < 14) {
          const int kk = k - 6;
          wgmma_n64_ss<1, 0, DH128, DH128>(o, dh, (kk >> 2) * 16384 + (kk & 3) * 2048, dx0, wo + 16384 + (kk >> 2) * 8192 + (kk & 3) * 32, 1);
        } else {
          const int kk = k < 6 ? k : k - 8;
          wgmma_n64_rs<1, DH128>(o, H[4 * kk], H[4 * kk + 1], H[4 * kk + 2], H[4 * kk + 3], dx0, wo + (kk / 7) * 32768 + (kk % 7) * 2048, k != 0 || acc);
        }
      }
      wg_commit();
    };
#pragma unroll
    for (int p = 0; p < 8; p++) {
      const uint32_t wo = (p % 3) == 1 ? 2 * 16384 : OFF_RING + (p % 3) * 24576;
      if (p == 0) {
        mbar_wait(fullb, 0);
        mma(o, wo, 0, 3, 0);
        asm volatile("fence.proxy.async.shared::cta;" ::: "memory");
        wg_wait<1>(); release(5);
        gelu_b(0, 4);
        mma(o, wo, 3, 6, 0);
        gelu_b(4, 10);
        bar_sync(1 + wg, 128);
        mbar_wait(fullb + 8, 0);
        mma(o, wo, 6, 10, 0);
        gelu_b(10, 16);
        mma(o, wo, 10, 15, 0);
        gelu_b(16, 24);
        mbar_wait(fullb + 16, 0);
        mma(o, wo, 15, 18, 0);
        gelu_b(24, 32);
        if (wg == 1) bar_sync(4, 256);
        mma(o, wo, 18, 22, 0);
      } else {
        mbar_wait(sb + OFF_XFULL + 8 * p, 1);
        if (p == 6) TS(wg, 19);
        bar_sync(3 + wg, 256);
        if (p < 7) mma(o, wo, 0, 22, 0); else mma(fin, wo, 0, 22, 1);
      }
      if (p < 7 || wg == 0) bar_arrive(4 - wg, 256);
      if (p == 6) TS(wg, 21);
      if (R2E && p == 7) recv_issue(r2, 6);
      if (p == 0 || p >= 3) tag = lds_u(sb + OFF_EPOCH);
      if (p >= 1 && p <= 4) {
        if (p == 1) {
#pragma unroll
          for (int h = 0; h < 2; h++) rho[h] = 0.5f * bf_lo(lds_h(sb + OFF_GS + (wg * 64 + w * 16 + gr + 8 * h) * 2));
        }
#pragma unroll
        for (int j = (p - 1) * 2; j < p * 2; j++) {
          const float2 db = lds_f2(sb + OFF_DB + j * 32 + q * 8);
#pragma unroll
          for (int h = 0; h < 2; h++) {
            const uint32_t xd = bf2_mul(lds_u(xw + 7 * 16384 + (w * 16 + gr + 8 * h) * 128 + ((j ^ gr) << 4) + q * 4), __float_as_uint(db.x));
            fin[4 * j + 2 * h] = fmaf(bf_lo(xd), rho[h], bf_lo(__float_as_uint(db.y)));
            fin[4 * j + 2 * h + 1] = fmaf(bf_hi(xd), rho[h], bf_hi(__float_as_uint(db.y)));
            pin(fin[4 * j + 2 * h]); pin(fin[4 * j + 2 * h + 1]);
          }
        }
      }
      if (p >= 3) {
        if (p == 7) TS(wg, 25);
        recv_check(r0, p - 3);
        if (p == 7) TS(wg, 26);
        if (p == 7) recv_check(r1, 5);
#pragma unroll
        for (int i = 0; i < 16; i++) sum[i] = p == 3 ? r0[i] : bf2_add(sum[i], p == 7 ? bf2_add(r0[i], r1[i]) : r0[i]);
        if (p == 7) TS(wg, 20);
      }
      if (p >= 2 && p < 7) recv_issue(r0, p - 2);
      if (!R2E && p == 7) recv_issue(r2, 6);
      wg_wait<0>();
      if (p < 5) release(p);
      if (p < 7) reg_fence(o); else reg_fence(fin);
      if (p == 6) TS(wg, 22);
      if (p < 7) send(p);
      if (p == 6) TS(wg, 23);
      if (p == 6) recv_issue(r1, 5);
      TS(wg, 8 + p);
    }
    {
      float fs[2];
#pragma unroll
      for (int h = 0; h < 2; h++) fs[h] = __fdividef(1.f, 2.f + rho[h]);
#pragma unroll
      for (int i = 0; i < 16; i++) { o[2 * i] = (fin[2 * i] + bf_lo(sum[i])) * fs[i & 1]; o[2 * i + 1] = (fin[2 * i + 1] + bf_hi(sum[i])) * fs[i & 1]; }
      reg_fence(o);
      tag = lds_u(sb + OFF_EPOCH);
      recv_check(r2, 6);
      TS(wg, 16);
      const uint32_t tb = sb + OFF_X + 5 * 16384 + warp * 4096;
      const uint32_t ta = tb + gr * 256 + ((gr & 3) << 5) + q * 8;
#pragma unroll
      for (int i = 0; i < 16; i++)
        asm volatile("st.shared.v2.f32 [%0], {%1,%2};" ::"r"((ta ^ (((i >> 1) & 3) << 5)) + (i & 1) * 2048 + (i >> 3) * 128),
                     "f"(fmaf(bf_lo(r2[i]), fs[i & 1], o[2 * i])), "f"(fmaf(bf_hi(r2[i]), fs[i & 1], o[2 * i + 1])) : "memory");
      __syncwarp();
      const uint32_t la = tb + (lane >> 3) * 256 + (((lane & 7) << 4) ^ ((lane >> 3) << 5));
      float* op = out + (size_t)(m * 128 + wg * 64 + (lane >> 4) * 16 + w * 4 + ((lane >> 3) & 1)) * DM + s * 64 + (lane & 7) * 4;
#pragma unroll
      for (int i = 0; i < 8; i++)
        *reinterpret_cast<uint4*>(op + (((i >> 1) & 1) * 32 + (i >> 2) * 2) * DM + (i & 1) * 32) = lds_u4(la + (i >> 1) * 1024 + (i & 1) * 128);
      if (threadIdx.x == 128) g_epoch[b] = tag;
      TS(wg, 17); TG(wg); TDUMP();
    }
  } else {
    asm volatile("setmaxnreg.dec.sync.aligned.u32 56;");
    int wsel = warp;
    asm("" : "+r"(wsel));
    if (wsel > 8) {
     if (warp != 11) {
      const int t = threadIdx.x - 288;
      unsigned par;
      asm volatile("ld.relaxed.gpu.global.u32 %0, [%1];" : "=r"(par) : "l"(g_epoch + b) : "memory");
      const float pr = bf_ld(lam_re + s * 64 + t), pi = bf_ld(lam_im + s * 64 + t), pd = bf_ld(log_dt + s * 64 + t);
      asm volatile("barrier.cluster.wait.aligned;" ::: "memory");
      par = (par + 1) & 1;
      cplx l64 = make_lam(pr, pi, pd);
      {
        const float inv = __fdividef(1.f, fmaf(pr, pr, pi * pi));
        const cplx cf = cmul(cplx{l64.re - 1.f, l64.im}, cplx{pr * inv, -pi * inv});
        asm volatile("st.shared.v4.f32 [%0], {%1,%2,%3,%4};" ::"r"(sb + OFF_LC + t * 16), "f"(l64.re), "f"(l64.im), "f"(cf.re), "f"(cf.im) : "memory");
        mbar_arrive(sb + OFF_LBAR);
      }
#pragma unroll
      for (int i = 0; i < 6; i++) l64 = cmul(l64, l64);
      cplx l128 = cmul(l64, l64);
      pin(l128.re); pin(l128.im);
      mbar_wait(sb + OFF_GBAR, 0);
      const float2 e0 = lds_f2(sb + OFF_CARRY + t * 8), e1 = lds_f2(sb + OFF_CARRY + 512 + t * 8);
      float2* eb = g_end + s * 1024 + t;
      {
        const cplx e = cfma(l64, cplx{e0.x, e0.y}, cplx{e1.x, e1.y});
        const unsigned long long v = ((unsigned long long)__float_as_uint(e.im) << 32) | ((__float_as_uint(e.re) & ~1u) | par);
        asm volatile("st.relaxed.gpu.global.b64 [%0], %1;" ::"l"(eb + m * 64), "l"(v) : "memory");
      }
      if (t == 0) TS(3, 1);
      cplx S = {0.f, 0.f};
      {
        unsigned long long v[15];
        uint32_t bad;
        int tries = 0;
        const float2* e15 = eb + (m - 15) * 64;
#pragma unroll 1
        do {
#pragma unroll
          for (int i = 0; i < 15; i++) {
            v[i] = par;
            asm volatile("{.reg .pred p; setp.ge.s32 p, %2, %3; @p ld.relaxed.gpu.global.b64 %0, [%1];}" : "+l"(v[i]) : "l"(e15 + i * 64), "r"(m), "r"(15 - i) : "memory");
          }
          bad = 0;
#pragma unroll
          for (int i = 0; i < 15; i++) bad |= (uint32_t)v[i] ^ par;
        } while ((bad & 1) && ++tries < 200000);
        if (t == 0) TS(3, 2);
#pragma unroll
        for (int i = 0; i < 15; i++) S = cfma(l128, S, cplx{__uint_as_float((uint32_t)v[i] & ~1u), __uint_as_float((uint32_t)(v[i] >> 32))});
      }
      const cplx S1 = cfma(l64, S, cplx{e0.x, e0.y});
      asm volatile("st.shared.v2.f32 [%0], {%1,%2};" ::"r"(sb + OFF_CARRY + t * 8), "f"(S.re), "f"(S.im) : "memory");
      asm volatile("st.shared.v2.f32 [%0], {%1,%2};" ::"r"(sb + OFF_CARRY + 512 + t * 8), "f"(S1.re), "f"(S1.im) : "memory");
      mbar_arrive(sb + OFF_CBAR);
      if (t == 0) TS(3, 3);
     } else {
      if (lane == 0) TG(2);
      const uint4* gwp = reinterpret_cast<const uint4*>(gate_w) + (lane & 7);
      uint4 gw[4];
#pragma unroll
      for (int i = 0; i < 4; i++) gw[i] = __ldg(gwp + i * 8);
      unsigned par;
      asm volatile("ld.relaxed.gpu.global.u32 %0, [%1];" : "=r"(par) : "l"(g_epoch + b) : "memory");
      const uint32_t dk = __ldg(reinterpret_cast<const uint32_t*>(dskip + s * 64) + lane), bb = __ldg(reinterpret_cast<const uint32_t*>(b2 + s * 64) + lane);
      asm volatile("barrier.cluster.wait.aligned;" ::: "memory");
      const int row = s * 16 + (lane >> 3);
      const uint32_t xr0 = sb + OFF_X + row * 128 + (((lane & 7) ^ (row & 7)) << 4), xr1 = (xr0 + 512) ^ 64;
      float z[4] = {0.f, 0.f, 0.f, 0.f};
#pragma unroll
      for (int kb = 0; kb < 8; kb++) {
        const uint32_t wv[4] = {gw[kb & 3].x, gw[kb & 3].y, gw[kb & 3].z, gw[kb & 3].w};
        if (kb < 4) gw[kb] = __ldg(gwp + (kb + 4) * 8);
        mbar_wait(sb + OFF_XFULL + 8 * kb, 0);
        if ((PF & 2) && kb == PFK && elect_one()) {
          l2_prefetch(pf_w1 + b * 7168, 14336);
          l2_prefetch(pf_cre + b * 2048, 4096);
          l2_prefetch(pf_cim + b * 2048, 4096);
          l2_prefetch(pf_w2 + b * 7168, 14336);
        }
        const uint32_t xo = ((kb + xrot) & 7) * 16384;
#pragma unroll
        for (int r = 0; r < 4; r++) {
          const uint4 a = lds_u4(((r & 1) ? xr1 : xr0) + xo + (r >> 1) * 1024);
          const uint32_t p = bf2_fma(a.w, wv[3], bf2_fma(a.z, wv[2], bf2_fma(a.y, wv[1], bf2_mul(a.x, wv[0]))));
          z[r] += bf_lo(p); z[r] += bf_hi(p);
        }
      }
      if (lane == 0) asm volatile("st.shared.u32 [%0], %1;" ::"r"(sb + OFF_EPOCH), "r"(par + 1) : "memory");
      par = (par + 1) & 1;
      {
        float y0 = (lane & 4) ? z[1] : z[0], y1 = (lane & 4) ? z[3] : z[2];
        y0 += __shfl_xor_sync(0xffffffffu, (lane & 4) ? z[0] : z[1], 4);
        y1 += __shfl_xor_sync(0xffffffffu, (lane & 4) ? z[2] : z[3], 4);
        float zz = (lane & 2) ? y1 : y0;
        zz += __shfl_xor_sync(0xffffffffu, (lane & 2) ? y0 : y1, 2);
        zz += __shfl_xor_sync(0xffffffffu, zz, 1);
        const float rho = 4.f * expf(zz > 40.f ? 40.f : zz);
        if ((lane & 1) == 0)
          asm volatile("st.relaxed.gpu.global.u32 [%0], %1;" ::"l"(g_gate + m * 128 + row + (lane & 4) + (lane & 2) * 4), "r"((__float_as_uint(rho) & ~1u) | par) : "memory");
      }
      if (lane == 0) TS(3, 0);
      mbar_wait(sb + OFF_GBAR, 0);
      asm volatile("st.shared.v2.u32 [%0], {%1,%2};" ::"r"(sb + OFF_DB + lane * 8), "r"(dk), "r"(bf2_add(bb, bb)) : "memory");
      uint32_t g0, g1, g2, g3;
      int tries = 0;
#pragma unroll 1
      do {
        asm volatile("ld.relaxed.gpu.global.v4.u32 {%0,%1,%2,%3}, [%4];" : "=r"(g0), "=r"(g1), "=r"(g2), "=r"(g3) : "l"(g_gate + m * 128 + lane * 4) : "memory");
      } while ((((g0 ^ par) | (g1 ^ par) | (g2 ^ par) | (g3 ^ par)) & 1) && ++tries < 200000);
      asm volatile("st.shared.v2.u32 [%0], {%1,%2};" ::"r"(sb + OFF_GS + lane * 8), "r"(pack_bf16(__uint_as_float(g0), __uint_as_float(g1))),
                   "r"(pack_bf16(__uint_as_float(g2), __uint_as_float(g3))) : "memory");
      mbar_arrive(sb + OFF_CBAR);
      if (lane == 0) TS(3, 4);
     }
    } else {
      asm volatile("barrier.cluster.wait.aligned;" ::: "memory");
      if (elect_one()) {
        TS(2, 1);
        const CUtensorMap* mb = rank ? &maps.bim : &maps.bre;
        const uint32_t t0 = clock();
#pragma unroll 1
        for (int u = 0; u < 8; u++) {
          if (u >= DN) while ((uint32_t)clock() - t0 < D0 + (u - DN) * D1) {}
          mbar_expect_tx(sb + OFF_XFULL + 8 * u, 16384);
          tma5d(sb + OFF_X + ((u + xrot) & 7) * 16384, &maps.x, u * 64, 2 * m, sb + OFF_XFULL + 8 * u);
          if (u < 6) {
            mbar_expect_tx(sb + OFF_FULL + 8 * u, 16384);
            tma2d_mc(sb + OFF_RING + u * 16384 + rank * 8192, mb, u * 64, s * 64, sb + OFF_FULL + 8 * u);
          } else if (PF & 4) {
            asm volatile("cp.async.bulk.prefetch.tensor.2d.L2.global [%0, {%1,%2}];" ::"l"(mb), "r"(u * 64), "r"(s * 64) : "memory");
          }
        }
        TS(2, 5);
        const CUtensorMap* mc = rank ? &maps.cim : &maps.cre;
        int slot = 0; uint32_t ph = 0;
#pragma unroll 1
        for (int u = 6; u < 27; u++) {
          const uint32_t fb = sb + OFF_FULL + 8 * slot, dst = sb + OFF_RING + slot * 16384;
          mbar_wait(sb + OFF_EMPTY + 8 * slot, ph);
          TS2(0, u);
          if (u < 8) {
            mbar_expect_tx(fb, 16384);
            tma2d_mc(dst + rank * 8192, mb, u * 64, s * 64, fb);
          } else if (u < 16) {
            mbar_expect_tx(fb, 12288);
            tma3d_mc(dst + rank * 6144, &maps.w1b, 0, (u - 8) * 64 + rank * 32, s * 7, fb);
          } else if (u < 24) {
            mbar_expect_tx(fb, 16384);
            tma2d_mc(dst + rank * 8192, &maps.w1a, s * 224 + 96 + rank * 64, ((u - 15 + s) & 7) * 64, fb);
          } else if (u == 25) {
            mbar_expect_tx(fb, 16384);
            tma2d_mc(dst + rank * 8192, mc, s * 64, ((s + 1) & 7) * 64, fb);
          } else {
            mbar_expect_tx(fb, 14336);
            tma2d_mc(dst + rank * 7168, &maps.w2, ((s + 1) & 7) * 64, s * 224 + (u - 24) * 56 + rank * 56, fb);
          }
          if (++slot == NSLOT) { slot = 0; ph ^= 1; }
        }
#pragma unroll 1
        for (int p = 1; p < 8; p++) {
          const int piece = (s + 1 + p) & 7, grp = p % 3;
          const uint32_t fb = sb + OFF_XFULL + 8 * p, dst = grp == 1 ? sb + OFF_X + 2 * 16384 : sb + OFF_RING + grp * 24576;
          if (p >= 3) mbar_wait(sb + OFF_EMPTY + 8 * (p - 3), 0);
          else if (p == 2) mbar_wait(sb + OFF_EMPTY + 40, 1);
          TS2(0, 32 + p);
          mbar_expect_tx(fb, 45056);
          tma2d_mc(dst + rank * 7168, &maps.w2, piece * 64, s * 224 + rank * 56, fb);
          tma2d_mc(dst + 16384 + rank * 8192, mc, s * 64, piece * 64, fb);
          tma2d_mc(dst + 32768 + rank * 7168, &maps.w2, piece * 64, s * 224 + 112 + rank * 56, fb);
        }
        TS(2, 2);
      }
    }
  }
}

typedef CUresult (*EncFn)(CUtensorMap*, CUtensorMapDataType, cuuint32_t, void*, const cuuint64_t*, const cuuint64_t*, const cuuint32_t*,
                          const cuuint32_t*, CUtensorMapInterleave, CUtensorMapSwizzle, CUtensorMapL2promotion, CUtensorMapFloatOOBfill);

void encode(EncFn f, CUtensorMap* mp, const void* p, int rank, const cuuint64_t* dims, const cuuint64_t* strides, const cuuint32_t* box, CUtensorMapSwizzle sw) {
  cuuint32_t es[5] = {1, 1, 1, 1, 1};
  f(mp, CU_TENSOR_MAP_DATA_TYPE_BFLOAT16, rank, const_cast<void*>(p), dims, strides, box, es, CU_TENSOR_MAP_INTERLEAVE_NONE, sw,
    PROMO, CU_TENSOR_MAP_FLOAT_OOB_FILL_NONE);
}

}

extern "C" void kernel_launch(void* const* d_in, const int* in_sizes, int n_in, void* d_out, int out_size) {
  typedef const __nv_bfloat16* bp;
  bp x = (bp)d_in[0], lre = (bp)d_in[1], lim = (bp)d_in[2], bre = (bp)d_in[3], bim = (bp)d_in[4], cre = (bp)d_in[5], cim = (bp)d_in[6],
     ldt = (bp)d_in[7], dsk = (bp)d_in[8], w1 = (bp)d_in[10], b1 = (bp)d_in[11], w2 = (bp)d_in[12], b2 = (bp)d_in[13], gw = (bp)d_in[14];
  static EncFn enc = nullptr;
  if (!enc) {
    void* f = nullptr;
    cudaDriverEntryPointQueryResult qr;
    cudaGetDriverEntryPoint("cuTensorMapEncodeTiled", &f, cudaEnableDefault, &qr);
    enc = (EncFn)f;
    cudaFuncSetAttribute(fused_kernel, cudaFuncAttributeMaxDynamicSharedMemorySize, SMEM_BYTES);
  }
  Maps maps;
  {
    cuuint64_t d[5] = {DM, 2, 4, 8, SEQ / 64}, st[4] = {DM * 2, 16 * DM * 2, 2 * DM * 2, 64 * DM * 2};
    cuuint32_t bx[5] = {64, 2, 4, 8, 2};
    encode(enc, &maps.x, x, 5, d, st, bx, CU_TENSOR_MAP_SWIZZLE_128B);
  }
  {
    cuuint64_t d[2] = {DM, DM}, st[1] = {DM * 2};
    cuuint32_t bx[2] = {64, 64};
    encode(enc, &maps.bre, bre, 2, d, st, bx, CU_TENSOR_MAP_SWIZZLE_128B);
    encode(enc, &maps.bim, bim, 2, d, st, bx, CU_TENSOR_MAP_SWIZZLE_128B);
    encode(enc, &maps.cre, cre, 2, d, st, bx, CU_TENSOR_MAP_SWIZZLE_128B);
    encode(enc, &maps.cim, cim, 2, d, st, bx, CU_TENSOR_MAP_SWIZZLE_128B);
  }
  {
    cuuint64_t d[2] = {FF, DM}, st[1] = {FF * 2};
    cuuint32_t bx[2] = {64, 64};
    encode(enc, &maps.w1a, w1, 2, d, st, bx, CU_TENSOR_MAP_SWIZZLE_128B);
    cuuint64_t d3[3] = {32, DM, FF / 32}, st3[2] = {FF * 2, 64};
    cuuint32_t bx3[3] = {32, 32, 3};
    encode(enc, &maps.w1b, w1, 3, d3, st3, bx3, CU_TENSOR_MAP_SWIZZLE_64B);
  }
  {
    cuuint64_t d[2] = {DM, FF}, st[1] = {DM * 2};
    cuuint32_t bx[2] = {64, 56};
    encode(enc, &maps.w2, w2, 2, d, st, bx, CU_TENSOR_MAP_SWIZZLE_128B);
  }
  fused_kernel<<<128, 384, SMEM_BYTES>>>(lre, lim, ldt, dsk, b1, b2, gw, w1, w2, cre, cim, (float*)d_out, maps);
}
```

```cpp
#include <cuda_runtime.h>
#include <cuda_bf16.h>
#include <cuda.h>
#include <stdint.h>

#define PF 6
#define SEND_TMA 0
#define PREW 0
#define CK 3
#define D0 600
#define D1 500
#define DN 1
#define PROMO CU_TENSOR_MAP_L2_PROMOTION_L2_128B
#define TMP 3
#define MAP 1
#define STV4 1
#define R2E 0
#define EARLYW 0
#define GELUP 0
#define FINP 5
#define PFK 5
namespace {

constexpr int SEQ = 2048, DM = 512, FF = 1792;
constexpr int NSLOT = 6;
constexpr uint32_t OFF_X = 0, OFF_RING = 131072, OFF_MISC = 229376;
constexpr uint32_t OFF_XFULL = OFF_MISC, OFF_FULL = OFF_XFULL + 64, OFF_EMPTY = OFF_FULL + 48, OFF_GBAR = OFF_EMPTY + 48,
                   OFF_CBAR = OFF_GBAR + 8, OFF_LBAR = OFF_CBAR + 8, OFF_EPOCH = OFF_CBAR + 24;
constexpr uint32_t OFF_LC = OFF_MISC + 256;
constexpr uint32_t OFF_GS = OFF_LC;
constexpr uint32_t OFF_DB = OFF_LC + 512;
constexpr uint32_t OFF_CARRY = OFF_LC + 1024;
constexpr uint32_t OFF_DBG = OFF_CARRY + 1024;
constexpr uint32_t SMEM_BYTES = OFF_DBG + 768;
static_assert(SMEM_BYTES <= 232448, "smem");

struct Maps {
  CUtensorMap x, bre, bim, w1b, w1a, w2, cre, cim; };

__device__ uint4 g_part[16 * 8 * 7 * 1024];
__device__ float2 g_end[8 * 16 * 64];
__device__ unsigned g_gate[SEQ];
__device__ unsigned g_epoch[128];
#define TG(role) do {} while (0)
#define TS2(role, i) do {} while (0)
#define TS(role, i) do {} while (0)
#define TDUMP() do {} while (0)

__device__ __forceinline__ void mbar_init(uint32_t bar, uint32_t cnt) { asm volatile("mbarrier.init.shared::cta.b64 [%0], %1;" ::"r"(bar), "r"(cnt)); }
__device__ __forceinline__ void mbar_expect_tx(uint32_t bar, uint32_t bytes) { asm volatile("mbarrier.arrive.expect_tx.shared::cta.b64 _, [%0], %1;" ::"r"(bar), "r"(bytes) : "memory"); }
__device__ __forceinline__ void mbar_arrive(uint32_t bar) { asm volatile("mbarrier.arrive.shared::cta.b64 _, [%0];" ::"r"(bar) : "memory"); }
__device__ __forceinline__ void mbar_arrive_cl(uint32_t cbar) { asm volatile("mbarrier.arrive.shared::cluster.b64 _, [%0];" ::"r"(cbar) : "memory"); }
__device__ __forceinline__ void mbar_wait(uint32_t bar, uint32_t parity) {
  asm volatile(
      "{\n.reg .pred p;\n.reg .u32 c;\n"
      "mbarrier.try_wait.parity.shared::cta.b64 p, [%0], %1;\n"
      "@p bra.uni LAB_DONE;\n"
      "mov.u32 c, 0;\n"
      "LAB_WAIT:\n"
      "mbarrier.try_wait.parity.shared::cta.b64 p, [%0], %1;\n"
      "@p bra.uni LAB_DONE;\n"
      "add.u32 c, c, 1;\nsetp.lt.u32 p, c, 200000;\n@p bra.uni LAB_WAIT;\n"
      "LAB_DONE:\n}" ::"r"(bar), "r"(parity) : "memory");
}
__device__ __forceinline__ void tma2d(uint32_t dst, const CUtensorMap* m, int c0, int c1, uint32_t bar) {
  asm volatile("cp.async.bulk.tensor.2d.shared::cluster.global.mbarrier::complete_tx::bytes [%0], [%1, {%3,%4}], [%2];"
               ::"r"(dst), "l"(m), "r"(bar), "r"(c0), "r"(c1) : "memory");
}
__device__ __forceinline__ void tma2d_mc(uint32_t dst, const CUtensorMap* m, int c0, int c1, uint32_t bar) {
  asm volatile("cp.async.bulk.tensor.2d.shared::cluster.global.mbarrier::complete_tx::bytes.multicast::cluster [%0], [%1, {%3,%4}], [%2], %5;"
               ::"r"(dst), "l"(m), "r"(bar), "r"(c0), "r"(c1), "h"((uint16_t)3) : "memory");
}
__device__ __forceinline__ void tma3d_mc(uint32_t dst, const CUtensorMap* m, int c0, int c1, int c2, uint32_t bar) {
  asm volatile("cp.async.bulk.tensor.3d.shared::cluster.global.mbarrier::complete_tx::bytes.multicast::cluster [%0], [%1, {%3,%4,%5}], [%2], %6;"
               ::"r"(dst), "l"(m), "r"(bar), "r"(c0), "r"(c1), "r"(c2), "h"((uint16_t)3) : "memory");
}
__device__ __forceinline__ void tma5d(uint32_t dst, const CUtensorMap* m, int c0, int c4, uint32_t bar) {
  asm volatile("cp.async.bulk.tensor.5d.shared::cluster.global.mbarrier::complete_tx::bytes [%0], [%1, {%3,%5,%5,%5,%4}], [%2];"
               ::"r"(dst), "l"(m), "r"(bar), "r"(c0), "r"(c4), "r"(0) : "memory");
}
__device__ __forceinline__ void l2_prefetch(const void* p, uint32_t bytes) { asm volatile("cp.async.bulk.prefetch.L2.global [%0], %1;" ::"l"(p), "r"(bytes) : "memory"); }
__device__ __forceinline__ bool elect_one() {
  uint32_t pred;
  asm volatile("{.reg .pred P; elect.sync _|P, 0xffffffff; selp.u32 %0, 1, 0, P;}" : "=r"(pred));
  return pred != 0;
}
__device__ __forceinline__ void wg_fence() { asm volatile("wgmma.fence.sync.aligned;" ::: "memory"); }
__device__ __forceinline__ void wg_commit() { asm volatile("wgmma.commit_group.sync.aligned;" ::: "memory"); }
template <int N> __device__ __forceinline__ void wg_wait() { asm volatile("wgmma.wait_group.sync.aligned %0;" ::"n"(N) : "memory"); }
template <int N> __device__ __forceinline__ void reg_fence(float (&d)[N]) {
#pragma unroll
  for (int i = 0; i < N; i++) asm volatile("" : "+f"(d[i])::"memory");
}
__device__ __forceinline__ void bar_sync(int id, int n) { asm volatile("bar.sync %0, %1;" ::"r"(id), "r"(n) : "memory"); }
__device__ __forceinline__ void bar_arrive(int id, int n) { asm volatile("bar.arrive %0, %1;" ::"r"(id), "r"(n) : "memory"); }
constexpr uint32_t DH128 = (1024 >> 4) | (1u << 30), DH64 = (512 >> 4) | (2u << 30);
__host__ __device__ constexpr uint32_t lbo(uint32_t bytes) { return (bytes >> 4) << 20; }
__device__ __forceinline__ uint32_t pack_bf16(float lo, float hi) { uint32_t r; asm("cvt.rn.bf16x2.f32 %0, %1, %2;" : "=r"(r) : "f"(hi), "f"(lo)); return r; }
__device__ __forceinline__ float bf_lo(uint32_t v) { return __uint_as_float(v << 16); }
__device__ __forceinline__ float bf_hi(uint32_t v) { return __uint_as_float(v & 0xffff0000u); }
__device__ __forceinline__ float bf_ld(const __nv_bfloat16* p) { return __bfloat162float(__ldg(p)); }
__device__ __forceinline__ uint32_t raw_ld(const __nv_bfloat16* p) { return __ldg(reinterpret_cast<const unsigned short*>(p)); }
__device__ __forceinline__ uint32_t late16(uint32_t bar) {
  uint32_t r;
  asm volatile("{.reg .pred p; mbarrier.test_wait.parity.shared::cta.b64 p, [%1], 0; selp.u32 %0, 16, 0, p;}" : "=r"(r) : "r"(bar) : "memory");
  return r;
}
__device__ __forceinline__ float2 lds_f2(uint32_t a) { float2 v; asm volatile("ld.shared.v2.f32 {%0,%1}, [%2];" : "=f"(v.x), "=f"(v.y) : "r"(a)); return v; }
__device__ __forceinline__ float lds_f(uint32_t a) { float v; asm volatile("ld.shared.f32 %0, [%1];" : "=f"(v) : "r"(a)); return v; }
__device__ __forceinline__ uint32_t lds_h(uint32_t a) { uint32_t v; asm volatile("ld.shared.u16 %0, [%1];" : "=r"(v) : "r"(a)); return v; }
__device__ __forceinline__ uint32_t lds_u(uint32_t a) { uint32_t v; asm volatile("ld.shared.u32 %0, [%1];" : "=r"(v) : "r"(a)); return v; }
__device__ __forceinline__ uint4 lds_u4(uint32_t a) { uint4 v; asm volatile("ld.shared.v4.u32 {%0,%1,%2,%3}, [%4];" : "=r"(v.x), "=r"(v.y), "=r"(v.z), "=r"(v.w) : "r"(a)); return v; }
__device__ __forceinline__ void st_b128(uint4* p, uint32_t a, uint32_t b, uint32_t c, uint32_t d) {
  asm volatile("st.relaxed.gpu.global.v4.b32 [%0], {%1,%2,%3,%4};" ::"l"(p), "r"(a), "r"(b), "r"(c), "r"(d) : "memory");
}
__device__ __forceinline__ void ld_b128(const uint4* p, uint32_t& a, uint32_t& b, uint32_t& c, uint32_t& d) {
  asm volatile("{.reg .b64 l, h; .reg .b128 v; ld.relaxed.gpu.global.b128 v, [%4]; mov.b128 {l,h}, v; mov.b64 {%0,%1}, l; mov.b64 {%2,%3}, h;}"
               : "=r"(a), "=r"(b), "=r"(c), "=r"(d) : "l"(p) : "memory");
}
__device__ __forceinline__ float tanh_fast(float x) { float y; asm("tanh.approx.f32 %0, %1;" : "=f"(y) : "f"(x)); return y; }
__device__ __forceinline__ float gelu2(float v) {
  float p = fmaf(v * v, 0.0356774081363f, 0.7978845608029f);
  return fmaf(v, tanh_fast(v * p), v);
}
__device__ __forceinline__ uint32_t bf2_mul(uint32_t a, uint32_t b) { uint32_t r; asm("mul.rn.bf16x2 %0, %1, %2;" : "=r"(r) : "r"(a), "r"(b)); return r; }
__device__ __forceinline__ uint32_t bf2_add(uint32_t a, uint32_t b) { uint32_t r; asm("add.rn.bf16x2 %0, %1, %2;" : "=r"(r) : "r"(a), "r"(b)); return r; }
__device__ __forceinline__ uint32_t bf2_fma(uint32_t a, uint32_t b, uint32_t c) { uint32_t r; asm("fma.rn.bf16x2 %0, %1, %2, %3;" : "=r"(r) : "r"(a), "r"(b), "r"(c)); return r; }
__device__ __forceinline__ uint32_t gelu2_pair(float a, float b) {
  return pack_bf16(gelu2(a), gelu2(b));
}
__device__ __forceinline__ void pin(float& a) { asm volatile("" : "+f"(a)::"memory"); }
__device__ __forceinline__ void pin(uint32_t& a) { asm volatile("" : "+r"(a)::"memory"); }
struct cplx { float re, im; };
__device__ __forceinline__ cplx cmul(cplx a, cplx b) { return {fmaf(a.re, b.re, -a.im * b.im), fmaf(a.re, b.im, a.im * b.re)}; }
__device__ __forceinline__ cplx csq(cplx a) { return {fmaf(a.re, a.re, -a.im * a.im), (a.re + a.re) * a.im}; }
__device__ __forceinline__ cplx cfma(cplx a, cplx b, cplx c) {
  return {fmaf(a.re, b.re, fmaf(-a.im, b.im, c.re)), fmaf(a.re, b.im, fmaf(a.im, b.re, c.im))};
}
__device__ __forceinline__ cplx make_lam(float lre, float lim, float ldt) {
  float dt = __bfloat162float(__float2bfloat16_rn(expf(ldt)));
  float mag = expf(dt * lre), sn, cs;
  sincospif(dt * lim * 0.31830988618379067f, &sn, &cs);
  return {mag * cs, mag * sn};
}

template<int TA,int TB,uint32_t AH,uint32_t BH> __device__ __forceinline__ void wgmma_n64_ss(float (&d)[32], uint32_t al, uint32_t ao, uint32_t bl, uint32_t bo, int scale_d){
  asm volatile("{.reg .pred p; .reg .b32 t, v; .reg .b64 da, db; setp.ne.b32 p, %36, 0; add.u32 t, %32, %33; mov.b64 da, {t, %39}; add.u32 v, %34, %35; mov.b64 db, {v, %40};\n"
   "wgmma.mma_async.sync.aligned.m64n64k16.f32.bf16.bf16 {%0,%1,%2,%3,%4,%5,%6,%7,%8,%9,%10,%11,%12,%13,%14,%15,%16,%17,%18,%19,%20,%21,%22,%23,%24,%25,%26,%27,%28,%29,%30,%31}, da, db, p, 1, 1, %37, %38;}"
   : "+f"(d[0]),"+f"(d[1]),"+f"(d[2]),"+f"(d[3]),"+f"(d[4]),"+f"(d[5]),"+f"(d[6]),"+f"(d[7]),"+f"(d[8]),"+f"(d[9]),"+f"(d[10]),"+f"(d[11]),"+f"(d[12]),"+f"(d[13]),"+f"(d[14]),"+f"(d[15]),"+f"(d[16]),"+f"(d[17]),"+f"(d[18]),"+f"(d[19]),"+f"(d[20]),"+f"(d[21]),"+f"(d[22]),"+f"(d[23]),"+f"(d[24]),"+f"(d[25]),"+f"(d[26]),"+f"(d[27]),"+f"(d[28]),"+f"(d[29]),"+f"(d[30]),"+f"(d[31])
   : "r"(al),"r"(ao >> 4),"r"(bl),"r"(bo >> 4),"r"(scale_d),"n"(TA),"n"(TB),"n"(AH),"n"(BH));
}
template<int TB,uint32_t BH> __device__ __forceinline__ void wgmma_n64_rs(float (&d)[32], uint32_t a0,uint32_t a1,uint32_t a2,uint32_t a3, uint32_t bl, uint32_t bo, int scale_d){
  asm volatile("{.reg .pred p; .reg .b32 t; .reg .b64 db; setp.ne.b32 p, %38, 0; add.u32 t, %36, %37; mov.b64 db, {t, %40};\n"
   "wgmma.mma_async.sync.aligned.m64n64k16.f32.bf16.bf16 {%0,%1,%2,%3,%4,%5,%6,%7,%8,%9,%10,%11,%12,%13,%14,%15,%16,%17,%18,%19,%20,%21,%22,%23,%24,%25,%26,%27,%28,%29,%30,%31}, {%32,%33,%34,%35}, db, p, 1, 1, %39;}"
   : "+f"(d[0]),"+f"(d[1]),"+f"(d[2]),"+f"(d[3]),"+f"(d[4]),"+f"(d[5]),"+f"(d[6]),"+f"(d[7]),"+f"(d[8]),"+f"(d[9]),"+f"(d[10]),"+f"(d[11]),"+f"(d[12]),"+f"(d[13]),"+f"(d[14]),"+f"(d[15]),"+f"(d[16]),"+f"(d[17]),"+f"(d[18]),"+f"(d[19]),"+f"(d[20]),"+f"(d[21]),"+f"(d[22]),"+f"(d[23]),"+f"(d[24]),"+f"(d[25]),"+f"(d[26]),"+f"(d[27]),"+f"(d[28]),"+f"(d[29]),"+f"(d[30]),"+f"(d[31])
   : "r"(a0),"r"(a1),"r"(a2),"r"(a3),"r"(bl),"r"(bo >> 4),"r"(scale_d),"n"(TB),"n"(BH));
}
template<int TA,int TB,uint32_t AH,uint32_t BH> __device__ __forceinline__ void wgmma_n96_ss(float (&d)[48], uint32_t al, uint32_t ao, uint32_t bl, uint32_t bo, int scale_d){
  asm volatile("{.reg .pred p; .reg .b32 t, v; .reg .b64 da, db; setp.ne.b32 p, %52, 0; add.u32 t, %48, %49; mov.b64 da, {t, %55}; add.u32 v, %50, %51; mov.b64 db, {v, %56};\n"
   "wgmma.mma_async.sync.aligned.m64n96k16.f32.bf16.bf16 {%0,%1,%2,%3,%4,%5,%6,%7,%8,%9,%10,%11,%12,%13,%14,%15,%16,%17,%18,%19,%20,%21,%22,%23,%24,%25,%26,%27,%28,%29,%30,%31,%32,%33,%34,%35,%36,%37,%38,%39,%40,%41,%42,%43,%44,%45,%46,%47}, da, db, p, 1, 1, %53, %54;}"
   : "+f"(d[0]),"+f"(d[1]),"+f"(d[2]),"+f"(d[3]),"+f"(d[4]),"+f"(d[5]),"+f"(d[6]),"+f"(d[7]),"+f"(d[8]),"+f"(d[9]),"+f"(d[10]),"+f"(d[11]),"+f"(d[12]),"+f"(d[13]),"+f"(d[14]),"+f"(d[15]),"+f"(d[16]),"+f"(d[17]),"+f"(d[18]),"+f"(d[19]),"+f"(d[20]),"+f"(d[21]),"+f"(d[22]),"+f"(d[23]),"+f"(d[24]),"+f"(d[25]),"+f"(d[26]),"+f"(d[27]),"+f"(d[28]),"+f"(d[29]),"+f"(d[30]),"+f"(d[31]),"+f"(d[32]),"+f"(d[33]),"+f"(d[34]),"+f"(d[35]),"+f"(d[36]),"+f"(d[37]),"+f"(d[38]),"+f"(d[39]),"+f"(d[40]),"+f"(d[41]),"+f"(d[42]),"+f"(d[43]),"+f"(d[44]),"+f"(d[45]),"+f"(d[46]),"+f"(d[47])
   : "r"(al),"r"(ao >> 4),"r"(bl),"r"(bo >> 4),"r"(scale_d),"n"(TA),"n"(TB),"n"(AH),"n"(BH));
}
template<int TA,int TB,uint32_t AH,uint32_t BH> __device__ __forceinline__ void wgmma_n128_ss(float (&d)[64], uint32_t al, uint32_t ao, uint32_t bl, uint32_t bo, int scale_d){
  asm volatile("{.reg .pred p; .reg .b32 t, v; .reg .b64 da, db; setp.ne.b32 p, %68, 0; add.u32 t, %64, %65; mov.b64 da, {t, %71}; add.u32 v, %66, %67; mov.b64 db, {v, %72};\n"
   "wgmma.mma_async.sync.aligned.m64n128k16.f32.bf16.bf16 {%0,%1,%2,%3,%4,%5,%6,%7,%8,%9,%10,%11,%12,%13,%14,%15,%16,%17,%18,%19,%20,%21,%22,%23,%24,%25,%26,%27,%28,%29,%30,%31,%32,%33,%34,%35,%36,%37,%38,%39,%40,%41,%42,%43,%44,%45,%46,%47,%48,%49,%50,%51,%52,%53,%54,%55,%56,%57,%58,%59,%60,%61,%62,%63}, da, db, p, 1, 1, %69, %70;}"
   : "+f"(d[0]),"+f"(d[1]),"+f"(d[2]),"+f"(d[3]),"+f"(d[4]),"+f"(d[5]),"+f"(d[6]),"+f"(d[7]),"+f"(d[8]),"+f"(d[9]),"+f"(d[10]),"+f"(d[11]),"+f"(d[12]),"+f"(d[13]),"+f"(d[14]),"+f"(d[15]),"+f"(d[16]),"+f"(d[17]),"+f"(d[18]),"+f"(d[19]),"+f"(d[20]),"+f"(d[21]),"+f"(d[22]),"+f"(d[23]),"+f"(d[24]),"+f"(d[25]),"+f"(d[26]),"+f"(d[27]),"+f"(d[28]),"+f"(d[29]),"+f"(d[30]),"+f"(d[31]),"+f"(d[32]),"+f"(d[33]),"+f"(d[34]),"+f"(d[35]),"+f"(d[36]),"+f"(d[37]),"+f"(d[38]),"+f"(d[39]),"+f"(d[40]),"+f"(d[41]),"+f"(d[42]),"+f"(d[43]),"+f"(d[44]),"+f"(d[45]),"+f"(d[46]),"+f"(d[47]),"+f"(d[48]),"+f"(d[49]),"+f"(d[50]),"+f"(d[51]),"+f"(d[52]),"+f"(d[53]),"+f"(d[54]),"+f"(d[55]),"+f"(d[56]),"+f"(d[57]),"+f"(d[58]),"+f"(d[59]),"+f"(d[60]),"+f"(d[61]),"+f"(d[62]),"+f"(d[63])
   : "r"(al),"r"(ao >> 4),"r"(bl),"r"(bo >> 4),"r"(scale_d),"n"(TA),"n"(TB),"n"(AH),"n"(BH));
}

__global__ void __cluster_dims__(2, 1, 1) __launch_bounds__(384, 1)
fused_kernel(const __nv_bfloat16* __restrict__ lam_re,
             const __nv_bfloat16* __restrict__ lam_im, const __nv_bfloat16* __restrict__ log_dt, const __nv_bfloat16* __restrict__ dskip,
             const __nv_bfloat16* __restrict__ b1, const __nv_bfloat16* __restrict__ b2, const __nv_bfloat16* __restrict__ gate_w,
             const __nv_bfloat16* __restrict__ pf_w1, const __nv_bfloat16* __restrict__ pf_w2, const __nv_bfloat16* __restrict__ pf_cre,
             const __nv_bfloat16* __restrict__ pf_cim, float* __restrict__ out, const __grid_constant__ Maps maps) {
  extern __shared__ __align__(1024) unsigned char smem_raw[];
  const uint32_t sb = (uint32_t)__cvta_generic_to_shared(smem_raw);
  const int b = blockIdx.x;
  const int rank = b & 1, cl = b >> 1;
  const int s = cl >> 3, mi = cl & 7;
  const int m = mi * 2 + rank;
  const int warp = __shfl_sync(0xffffffffu, (int)(threadIdx.x >> 5), 0);
  const int lane = threadIdx.x & 31;
  const int xrot = 7 - s;

  if (elect_one()) {
    if (warp == 8) TS(2, 0);
    if (warp < TMP) asm volatile("prefetch.tensormap [%0];" ::"l"(&maps.x + warp) : "memory");
    const uint32_t c = warp < 7 ? 1 : warp < 10 ? 16 : 64;
    mbar_init(sb + OFF_XFULL + 16 * warp, c);
    mbar_init(sb + OFF_XFULL + 16 * warp + 8, warp < 10 ? c : 96);
    asm volatile("fence.mbarrier_init.release.cluster;" ::: "memory");
  }
  __syncwarp();
  asm volatile("barrier.cluster.arrive.relaxed.aligned;" ::: "memory");
  if (warp < 8) {
    const int wg = warp >> 2, w = warp & 3, q = lane & 3, gr = lane >> 2;
    uint32_t bv[28];
#pragma unroll
    for (int j = 0; j < 28; j++) bv[j] = __ldg(reinterpret_cast<const uint32_t*>(b1 + s * 224 + j * 8) + q);
    asm volatile("setmaxnreg.inc.sync.aligned.u32 224;");
    asm volatile("barrier.cluster.wait.aligned;" ::: "memory");
    TS(wg, 0);
    uint32_t ebar;
    asm volatile("mapa.shared::cluster.u32 %0, %1, %2;" : "=r"(ebar) : "r"(sb + OFF_EMPTY), "r"(lane & 1));
    auto release = [&](int slot) { if (lane < 2) mbar_arrive_cl(ebar + 8 * slot); };
    const uint32_t xw = sb + OFF_X + wg * 8192, fullb = sb + OFF_FULL;
    const uint32_t dxw = (xw & 0x3FFFF) >> 4, dring = ((sb + OFF_RING) & 0x3FFFF) >> 4;

    float ure[32], uim[32], aa[48], ab[64];
    cplx lam[2], coef[2], l16[2], l32[2], lq[2], pre[2], e[2];
    uint32_t sh16, mhi;
    TS(wg, 24);

#pragma unroll
    for (int kb = 0; kb < 8; kb++) {
      const int slot = kb % NSLOT;
      TS2(1, kb);
      mbar_wait(sb + OFF_XFULL + 8 * kb, 0);
      if (kb == 0) TS(wg, 18);
      mbar_wait(fullb + 8 * slot, (kb / NSLOT) & 1);
      TS2(2, kb);
      if (kb == 0) TS(wg, 1);
      wg_fence();
      const uint32_t dxa = dxw + ((kb + xrot) & 7) * 1024;
#pragma unroll
      for (int kk = 0; kk < 4; kk++) {
        wgmma_n64_ss<0, 0, DH128, DH128>(ure, dring, slot * 16384 + kk * 32, dxa, kk * 32, (kb | kk) != 0);
        wgmma_n64_ss<0, 0, DH128, DH128>(uim, dring, slot * 16384 + 8192 + kk * 32, dxa, kk * 32, (kb | kk) != 0);
      }
      wg_commit();
      if (kb > 0) { wg_wait<1>(); release((kb - 1) % NSLOT); }
      if (kb == 1) { sh16 = late16(sb + OFF_XFULL); mhi = 0xffffffffu << sh16; }
      if (kb == 1 || (kb >= 3 && kb < 6)) {
#pragma unroll
        for (int j = 0; j < 28; j++) if (j / 7 == (kb == 1 ? 0 : kb - 2)) {
          pin(bv[j]);
          float* d = j < 12 ? aa + 4 * j : ab + 4 * (j - 12);
          d[0] = d[2] = __uint_as_float(bv[j] << sh16); d[1] = d[3] = __uint_as_float(bv[j] & mhi);
          pin(d[0]); pin(d[1]); pin(d[2]); pin(d[3]);
        }
      }
      if (kb == 5) {
        mbar_wait(sb + OFF_LBAR, 0);
#pragma unroll
        for (int h = 0; h < 2; h++) {
          const uint4 v = lds_u4(sb + OFF_LC + (w * 16 + gr + 8 * h) * 16);
          lam[h] = cplx{__uint_as_float(v.x), __uint_as_float(v.y)};
          coef[h] = cplx{__uint_as_float(v.z), __uint_as_float(v.w)};
        }
      }
      if (kb == 6) {
#pragma unroll
        for (int h = 0; h < 2; h++) {
          pin(lam[h].re); pin(lam[h].im);
          l16[h] = csq(csq(csq(csq(lam[h])))); l32[h] = csq(l16[h]);
          pin(l32[h].re); pin(l32[h].im);
        }
      }
      if (kb == 7) {
#pragma unroll
        for (int h = 0; h < 2; h++) {
          pin(l16[h].re); pin(l16[h].im);
          const cplx a = (q & 1) ? l16[h] : cplx{1.f, 0.f}, c = (q & 2) ? l32[h] : cplx{1.f, 0.f};
          lq[h] = cmul(cmul(a, c), coef[h]);
          pin(lq[h].re); pin(lq[h].im);
        }
      }
    }
    TS(wg, 2);
    auto scale_u = [&](int i0, int i1) {
#pragma unroll
      for (int i = 0; i < 32; i++) if (i >= i0 && i < i1) {
        pin(ure[i]); pin(uim[i]);
        const cplx v = cmul(coef[(i >> 1) & 1], cplx{ure[i], uim[i]});
        ure[i] = v.re; uim[i] = v.im;
        pin(ure[i]); pin(uim[i]);
      }
    };
#pragma unroll
    for (int kb = 0; kb < 8; kb++) {
      const int u = 8 + kb, slot = u % NSLOT;
      TS2(1, u);
      mbar_wait(fullb + 8 * slot, (u / NSLOT) & 1);
      TS2(2, u);
      wg_fence();
      const uint32_t dxa = dxw + ((kb + xrot) & 7) * 1024;
#pragma unroll
      for (int kk = 0; kk < 4; kk++)
        wgmma_n96_ss<0, 1, DH128, DH64>(aa, dxa, kk * 32, dring, slot * 16384 + (kk >> 1) * 6144 + (kk & 1) * 1024 + lbo(2048), 1);
      wg_commit();
      wg_wait<1>();
      release((u - 1) % NSLOT);
      if (kb == 0) {
        reg_fence(ure); reg_fence(uim);
#pragma unroll
        for (int h = 0; h < 2; h++) e[h] = cplx{ure[2 * h], uim[2 * h]};
      }
      if (kb == 0 || kb == 2 || kb == 3) {
        const int ch = kb ? kb - 1 : 0;
#pragma unroll
        for (int t = 1 + 5 * ch; t < 6 + 5 * ch; t++)
#pragma unroll
          for (int h = 0; h < 2; h++) { const int i = 4 * (t >> 1) + 2 * h + (t & 1); e[h] = cfma(lam[h], e[h], cplx{ure[i], uim[i]}); }
#pragma unroll
        for (int h = 0; h < 2; h++) { pin(e[h].re); pin(e[h].im); }
      } else if (kb == 4) {
#pragma unroll
        for (int h = 0; h < 2; h++) {
          cplx y = {__shfl_up_sync(0xffffffffu, e[h].re, 1, 4), __shfl_up_sync(0xffffffffu, e[h].im, 1, 4)};
          if (q >= 1) e[h] = cfma(l16[h], y, e[h]);
          y = cplx{__shfl_up_sync(0xffffffffu, e[h].re, 2, 4), __shfl_up_sync(0xffffffffu, e[h].im, 2, 4)};
          if (q >= 2) e[h] = cfma(l32[h], y, e[h]);
        }
        if (q == 3) {
#pragma unroll
          for (int h = 0; h < 2; h++)
            asm volatile("st.shared.v2.f32 [%0], {%1,%2};" ::"r"(sb + OFF_CARRY + wg * 512 + (w * 16 + gr + 8 * h) * 8), "f"(e[h].re), "f"(e[h].im) : "memory");
          mbar_arrive(sb + OFF_GBAR);
        }
#pragma unroll
        for (int h = 0; h < 2; h++) {
          const cplx y = {__shfl_up_sync(0xffffffffu, e[h].re, 1, 4), __shfl_up_sync(0xffffffffu, e[h].im, 1, 4)};
          pre[h] = (q >= 1) ? cmul(coef[h], y) : cplx{0.f, 0.f};
          pin(pre[h].re); pin(pre[h].im);
        }
        TS(wg, 3);
      } else if (kb > 4) {
        scale_u(kb == 5 ? 0 : kb == 6 ? 4 : 12, kb == 5 ? 4 : kb == 6 ? 12 : 20);
      }
    }
    TS(wg, 4);
    uint32_t H[56];
    cplx hst[2];
    const uint32_t dh = dxw;
    const uint32_t hst_addr = xw + (w * 16 + (lane & 15)) * 128 + (((lane >> 4) ^ (lane & 7)) << 4);
#pragma unroll
    for (int kb = 0; kb < 8; kb++) {
      const int u = 16 + kb, slot = u % NSLOT;
      TS2(1, u);
      mbar_wait(fullb + 8 * slot, (u / NSLOT) & 1);
      TS2(2, u);
      wg_fence();
#pragma unroll
      for (int kk = 0; kk < 4; kk++)
        wgmma_n128_ss<0, 1, DH128, DH128>(ab, dxw, kb * 16384 + kk * 32, dring, slot * 16384 + kk * 2048 + lbo(8192), 1);
      wg_commit();
      wg_wait<1>();
      release((u - 1) % NSLOT);
      if (kb == 0) scale_u(20, 32);
      if (kb < 5 && kb != 1) {
        const int ch = kb ? kb - 1 : 0;
#pragma unroll
        for (int i = ch * 6; i < ch * 6 + 6; i++) {
          pin(aa[2 * i]); pin(aa[2 * i + 1]);
          H[i] = gelu2_pair(aa[2 * i], aa[2 * i + 1]);
          pin(H[i]);
        }
      }
      if (kb >= 4) {
        if (kb == 4) {
          TS(wg, 5);
          mbar_wait(sb + OFF_CBAR, 0);
          TS(wg, 6);
#pragma unroll
          for (int h = 0; h < 2; h++) {
            const float2 c = lds_f2(sb + OFF_CARRY + wg * 512 + (w * 16 + gr + 8 * h) * 8);
            hst[h] = cfma(lq[h], cplx{c.x, c.y}, pre[h]);
          }
        }
        const int j0 = (kb - 4) * 2;
        uint32_t rr[4], ri[4];
#pragma unroll
        for (int jj = 0; jj < 2; jj++) {
          const int j = j0 + jj;
          const uint32_t g2 = lds_u(sb + OFF_GS + (wg * 64 + j * 8 + q * 2) * 2);
#pragma unroll
          for (int h = 0; h < 2; h++) {
            const int i = 4 * j + 2 * h;
            const cplx h0 = cfma(lam[h], hst[h], cplx{ure[i], uim[i]});
            hst[h] = cfma(lam[h], h0, cplx{ure[i + 1], uim[i + 1]});
            rr[jj * 2 + h] = bf2_mul(pack_bf16(h0.re, hst[h].re), g2);
            ri[jj * 2 + h] = bf2_mul(pack_bf16(h0.im, hst[h].im), g2 ^ 0x80008000u);
          }
        }
        const uint32_t a = hst_addr ^ (j0 << 4);
        asm volatile("stmatrix.sync.aligned.m8n8.x4.shared.b16 [%0], {%1,%2,%3,%4};" ::"r"(a), "r"(rr[0]), "r"(rr[1]), "r"(rr[2]), "r"(rr[3]) : "memory");
        asm volatile("stmatrix.sync.aligned.m8n8.x4.shared.b16 [%0], {%1,%2,%3,%4};" ::"r"(a + 16384), "r"(ri[0]), "r"(ri[1]), "r"(ri[2]), "r"(ri[3]) : "memory");
      }
    }
    TS(wg, 7);

    uint4* const psend = g_part + (size_t)m * (8 * 7 * 1024) + warp * 128;
    const uint4* const precv = g_part + (size_t)(m * 8 + s) * (7 * 1024) + warp * 128 + lane;
    const uint32_t stg = sb + OFF_X + 5 * 16384 + warp * 2048;
    const uint32_t dx0 = ((sb + OFF_X) & 0x3FFFF) >> 4;
    float o[32], fin[32], fs[2];
    uint32_t r0[16], r1[16], r2[16], sum[16], tag, zero;
    auto retag = [&]() { asm volatile("{.reg .b32 c; mov.u32 c, %%clock; lop3.b32 %0, %0, c, %1, 0x78;}" : "+r"(tag) : "r"(zero)); };
    auto send = [&](int p) {
#pragma unroll
      for (int i = 0; i < 4; i++) {
        uint32_t t0;
        asm("lop3.b32 %0, %1, 1, %2, 0xb8;" : "=r"(t0) : "r"(pack_bf16(o[8 * i], o[8 * i + 1])), "r"(tag));
        st_b128(psend + (((s + 1 + p) & 7) * 7 + p) * 1024 + i * 32 + lane, t0, pack_bf16(o[8 * i + 2], o[8 * i + 3]), pack_bf16(o[8 * i + 4], o[8 * i + 5]),
                pack_bf16(o[8 * i + 6], o[8 * i + 7]));
      }
    };
    auto recv_issue = [&](uint32_t (&r)[16], int p) {
#pragma unroll
      for (int i = 0; i < 4; i++) ld_b128(precv + p * 1024 + i * 32, r[4 * i], r[4 * i + 1], r[4 * i + 2], r[4 * i + 3]);
    };
    auto stale = [&](uint32_t (&r)[16]) {
      uint32_t t0, t1;
      asm("lop3.b32 %0, %1, %2, %3, 0x7e;" : "=r"(t0) : "r"(r[0]), "r"(r[4]), "r"(tag));
      asm("lop3.b32 %0, %1, %2, %3, 0x7e;" : "=r"(t1) : "r"(r[8]), "r"(r[12]), "r"(tag));
      uint32_t r_;
      asm volatile("{.reg .pred p; .reg .b32 t; lop3.b32 t, %1, %2, 1, 0xa8; setp.ne.u32 p, t, 0; vote.sync.any.pred p, p, 0xffffffff; selp.u32 %0, 1, 0, p;}" : "=r"(r_) : "r"(t0), "r"(t1));
      return r_ != 0;
    };
    auto recv_check = [&](uint32_t (&r)[16], int p) {
      if (__builtin_expect(stale(r), 0)) {
        int tries = 0;
#pragma unroll 1
        do { recv_issue(r, p); } while (stale(r) && ++tries < 200000);
      }
    };
    auto gelu_b = [&](int i0, int i1) {
#pragma unroll
      for (int i = i0; i < i1; i++) {
        pin(ab[2 * i]); pin(ab[2 * i + 1]);
        H[24 + i] = gelu2_pair(ab[2 * i], ab[2 * i + 1]);
        pin(H[24 + i]);
      }
    };
    auto mma = [&](float (&o)[32], uint32_t wo, int k0, int k1, int acc) {
      wg_fence();
#pragma unroll
      for (int k = k0; k < k1; k++) {
        if (k >= 6 && k < 14) {
          const int kk = k - 6;
          wgmma_n64_ss<1, 0, DH128, DH128>(o, dh, (kk >> 2) * 16384 + (kk & 3) * 2048, dx0, wo + 16384 + (kk >> 2) * 8192 + (kk & 3) * 32, 1);
        } else {
          const int kk = k < 6 ? k : k - 8;
          wgmma_n64_rs<1, DH128>(o, H[4 * kk], H[4 * kk + 1], H[4 * kk + 2], H[4 * kk + 3], dx0, wo + (kk / 7) * 32768 + (kk % 7) * 2048, k != 0 || acc);
        }
      }
      wg_commit();
    };
#pragma unroll
    for (int p = 0; p < 8; p++) {
      const uint32_t wo = (p % 3) == 1 ? 2 * 16384 : OFF_RING + (p % 3) * 24576;
      if (p == 0) {
        mbar_wait(fullb, 0);
        mma(o, wo, 0, 3, 0);
        asm volatile("fence.proxy.async.shared::cta;" ::: "memory");
        wg_wait<1>(); release(5);
        gelu_b(0, 4);
        mma(o, wo, 3, 6, 0);
        gelu_b(4, 10);
        bar_sync(1 + wg, 128);
        mbar_wait(fullb + 8, 0);
        mma(o, wo, 6, 10, 0);
        gelu_b(10, 16);
        mma(o, wo, 10, 15, 0);
        gelu_b(16, 24);
        mbar_wait(fullb + 16, 0);
        mma(o, wo, 15, 18, 0);
        gelu_b(24, 32);
        if (wg == 1) bar_sync(4, 256);
        mma(o, wo, 18, 22, 0);
      } else {
        if (!EARLYW) mbar_wait(sb + OFF_XFULL + 8 * p, 1);
        bar_sync(3 + wg, 256);
        if (p < 7) mma(o, wo, 0, 22, 0); else mma(fin, wo, 0, 22, 1);
      }
      if (p < 7 || wg == 0) bar_arrive(4 - wg, 256);
      TS(wg, 8 + p);
      if (R2E && p == 7) recv_issue(r2, 6);
      if (p == 0) { const float2 t2 = lds_f2(sb + OFF_EPOCH); tag = __float_as_uint(t2.x); zero = __float_as_uint(t2.y); }
      if (p >= 3) retag();
      if (p == 1) {
#pragma unroll
        for (int h = 0; h < 2; h++) { fs[h] = __fdividef(2.f, 4.f + bf_lo(lds_h(sb + OFF_GS + (wg * 64 + w * 16 + gr + 8 * h) * 2))); pin(fs[h]); }
      }
      if (p >= 3) {
        recv_check(r0, p - 3);
        if (p == 7) recv_check(r1, 5);
#pragma unroll
        for (int i = 0; i < 16; i++) sum[i] = p == 3 ? r0[i] : bf2_add(sum[i], p == 7 ? bf2_add(r0[i], r1[i]) : r0[i]);
      }
      if (!SEND_TMA && p >= 2 && p < 7) recv_issue(r0, p - 2);
      if (EARLYW && p < 7) mbar_wait(sb + OFF_XFULL + 8 * (p + 1), 1);
      if (!R2E && p == 7) recv_issue(r2, 6);
      if (p == FINP) {
        mbar_wait(sb + OFF_LBAR, 1);
#pragma unroll
        for (int j = 0; j < 8; j++) {
          const uint4 v = lds_u4(sb + OFF_X + 5 * 16384 + j * 4096 + threadIdx.x * 16);
          fin[4 * j] = __uint_as_float(v.x); fin[4 * j + 1] = __uint_as_float(v.y); fin[4 * j + 2] = __uint_as_float(v.z); fin[4 * j + 3] = __uint_as_float(v.w);
        }
      }
      wg_wait<0>();
      if (p < 5) release(p);
      if (p < 7) reg_fence(o); else reg_fence(fin);
      if (p < 7) send(p);
      if (SEND_TMA && p >= 2 && p < 7) recv_issue(r0, p - 2);
      if (p == 6) recv_issue(r1, 5);
    }
    {
#pragma unroll
      for (int i = 0; i < 16; i++) { o[2 * i] = (fin[2 * i] + bf_lo(sum[i])) * fs[i & 1]; o[2 * i + 1] = (fin[2 * i + 1] + bf_hi(sum[i])) * fs[i & 1]; }
      reg_fence(o);
      retag();
      recv_check(r2, 6);
      TS(wg, 16);
      const uint32_t tb = sb + OFF_RING + 3 * 16384 + warp * 4096;
      const uint32_t ta = tb + gr * 256 + ((gr & 3) << 5) + q * 8;
#pragma unroll
      for (int i = 0; i < 16; i++)
        asm volatile("st.shared.v2.f32 [%0], {%1,%2};" ::"r"((ta ^ (((i >> 1) & 3) << 5)) + (i & 1) * 2048 + (i >> 3) * 128),
                     "f"(fmaf(bf_lo(r2[i]), fs[i & 1], o[2 * i])), "f"(fmaf(bf_hi(r2[i]), fs[i & 1], o[2 * i + 1])) : "memory");
      __syncwarp();
      const uint32_t la = tb + (lane >> 3) * 256 + (((lane & 7) << 4) ^ ((lane >> 3) << 5));
      float* op = out + (size_t)(m * 128 + wg * 64 + (lane >> 4) * 16 + w * 4 + ((lane >> 3) & 1)) * DM + s * 64 + (lane & 7) * 4;
#pragma unroll
      for (int i = 0; i < 8; i++)
        *reinterpret_cast<uint4*>(op + (((i >> 1) & 1) * 32 + (i >> 2) * 2) * DM + (i & 1) * 32) = lds_u4(la + (i >> 1) * 1024 + (i & 1) * 128);
      if (threadIdx.x == 128) g_epoch[b] = tag;
      TS(wg, 17); TG(wg); TDUMP();
    }
  } else {
    asm volatile("setmaxnreg.dec.sync.aligned.u32 56;");
    int wsel = warp;
    asm("" : "+r"(wsel));
    if (wsel > 8) {
     if (warp != 11) {
      const int t = threadIdx.x - 288;
      unsigned par;
      asm volatile("ld.relaxed.gpu.global.u32 %0, [%1];" : "=r"(par) : "l"(g_epoch + b) : "memory");
      const float pr = bf_ld(lam_re + s * 64 + t), pi = bf_ld(lam_im + s * 64 + t), pd = bf_ld(log_dt + s * 64 + t);
      asm volatile("barrier.cluster.wait.aligned;" ::: "memory");
      par = (par + 1) & 1;
      cplx l64 = make_lam(pr, pi, pd);
      {
        const float inv = __fdividef(1.f, fmaf(pr, pr, pi * pi));
        const cplx cf = cmul(cplx{l64.re - 1.f, l64.im}, cplx{pr * inv, -pi * inv});
        asm volatile("st.shared.v4.f32 [%0], {%1,%2,%3,%4};" ::"r"(sb + OFF_LC + t * 16), "f"(l64.re), "f"(l64.im), "f"(cf.re), "f"(cf.im) : "memory");
        mbar_arrive(sb + OFF_LBAR);
      }
#pragma unroll
      for (int i = 0; i < 6; i++) l64 = cmul(l64, l64);
      cplx l128 = cmul(l64, l64);
      pin(l128.re); pin(l128.im);
      mbar_wait(sb + OFF_GBAR, 0);
      const float2 e0 = lds_f2(sb + OFF_CARRY + t * 8), e1 = lds_f2(sb + OFF_CARRY + 512 + t * 8);
      float2* eb = g_end + s * 1024 + t;
      {
        const cplx e = cfma(l64, cplx{e0.x, e0.y}, cplx{e1.x, e1.y});
        const unsigned long long v = ((unsigned long long)__float_as_uint(e.im) << 32) | ((__float_as_uint(e.re) & ~1u) | par);
        asm volatile("st.relaxed.gpu.global.b64 [%0], %1;" ::"l"(eb + m * 64), "l"(v) : "memory");
      }
      if (t == 0) TS(3, 1);
      cplx S = {0.f, 0.f};
      {
        unsigned long long v[15];
        uint32_t bad;
        int tries = 0;
        const float2* e15 = eb + (m - 15) * 64;
#pragma unroll 1
        do {
#pragma unroll
          for (int i = 0; i < 15; i++) {
            v[i] = par;
            asm volatile("{.reg .pred p; setp.ge.s32 p, %2, %3; @p ld.relaxed.gpu.global.b64 %0, [%1];}" : "+l"(v[i]) : "l"(e15 + i * 64), "r"(m), "r"(15 - i) : "memory");
          }
          bad = 0;
#pragma unroll
          for (int i = 0; i < 15; i++) bad |= (uint32_t)v[i] ^ par;
        } while ((bad & 1) && ++tries < 200000);
        if (t == 0) TS(3, 2);
#pragma unroll
        for (int i = 0; i < 15; i++) S = cfma(l128, S, cplx{__uint_as_float((uint32_t)v[i] & ~1u), __uint_as_float((uint32_t)(v[i] >> 32))});
      }
      const cplx S1 = cfma(l64, S, cplx{e0.x, e0.y});
      asm volatile("st.shared.v2.f32 [%0], {%1,%2};" ::"r"(sb + OFF_CARRY + t * 8), "f"(S.re), "f"(S.im) : "memory");
      asm volatile("st.shared.v2.f32 [%0], {%1,%2};" ::"r"(sb + OFF_CARRY + 512 + t * 8), "f"(S1.re), "f"(S1.im) : "memory");
      mbar_arrive(sb + OFF_CBAR);
      if (t == 0) TS(3, 3);
      mbar_wait(sb + OFF_CBAR, 0);
      mbar_wait(sb + OFF_XFULL + 16, 1);
      const int gr = (t >> 2) & 7, q = t & 3;
#pragma unroll 1
      for (int cw = t >> 5; cw < 8; cw += 2) {
        const int row = cw * 16 + gr;
        const float r0 = 0.5f * bf_lo(lds_h(sb + OFF_GS + row * 2)), r1 = 0.5f * bf_lo(lds_h(sb + OFF_GS + row * 2 + 16));
        const uint32_t xa = sb + OFF_X + 7 * 16384 + row * 128 + (gr << 4) + q * 4;
#pragma unroll
        for (int j = 0; j < 8; j++) {
          const float2 db = lds_f2(sb + OFF_DB + j * 32 + q * 8);
          const uint32_t x0 = bf2_mul(lds_u(xa ^ (j << 4)), __float_as_uint(db.x)), x1 = bf2_mul(lds_u((xa ^ (j << 4)) + 1024), __float_as_uint(db.x));
          const float bl = bf_lo(__float_as_uint(db.y)), bh = bf_hi(__float_as_uint(db.y));
          asm volatile("st.shared.v4.f32 [%0], {%1,%2,%3,%4};" ::"r"(sb + OFF_X + 5 * 16384 + j * 4096 + (cw * 32 + lane) * 16), "f"(fmaf(bf_lo(x0), r0, bl)),
                       "f"(fmaf(bf_hi(x0), r0, bh)), "f"(fmaf(bf_lo(x1), r1, bl)), "f"(fmaf(bf_hi(x1), r1, bh)) : "memory");
        }
      }
      mbar_arrive(sb + OFF_LBAR);
      if (t == 0) TS(3, 5);
     } else {
      if (lane == 0) TG(2);
      const uint4* gwp = reinterpret_cast<const uint4*>(gate_w) + (lane & 7);
      uint4 gw[4];
#pragma unroll
      for (int i = 0; i < 4; i++) gw[i] = __ldg(gwp + i * 8);
      unsigned par;
      asm volatile("ld.relaxed.gpu.global.u32 %0, [%1];" : "=r"(par) : "l"(g_epoch + b) : "memory");
      const uint32_t dk = __ldg(reinterpret_cast<const uint32_t*>(dskip + s * 64) + lane), bb = __ldg(reinterpret_cast<const uint32_t*>(b2 + s * 64) + lane);
      asm volatile("barrier.cluster.wait.aligned;" ::: "memory");
      const int row = s * 16 + (lane >> 3);
      const uint32_t xr0 = sb + OFF_X + row * 128 + (((lane & 7) ^ (row & 7)) << 4), xr1 = (xr0 + 512) ^ 64;
      float z[4] = {0.f, 0.f, 0.f, 0.f};
#pragma unroll
      for (int kb = 0; kb < 8; kb++) {
        const uint32_t wv[4] = {gw[kb & 3].x, gw[kb & 3].y, gw[kb & 3].z, gw[kb & 3].w};
        if (kb < 4) gw[kb] = __ldg(gwp + (kb + 4) * 8);
        mbar_wait(sb + OFF_XFULL + 8 * kb, 0);
        if ((PF & 2) && kb == PFK && elect_one()) {
          l2_prefetch(pf_w1 + b * 7168, 14336);
          l2_prefetch(pf_cre + b * 2048, 4096);
          l2_prefetch(pf_cim + b * 2048, 4096);
          l2_prefetch(pf_w2 + b * 7168, 14336);
        }
        const uint32_t xo = ((kb + xrot) & 7) * 16384;
#pragma unroll
        for (int r = 0; r < 4; r++) {
          const uint4 a = lds_u4(((r & 1) ? xr1 : xr0) + xo + (r >> 1) * 1024);
          const uint32_t p = bf2_fma(a.w, wv[3], bf2_fma(a.z, wv[2], bf2_fma(a.y, wv[1], bf2_mul(a.x, wv[0]))));
          z[r] += bf_lo(p); z[r] += bf_hi(p);
        }
      }
      if (lane == 0) asm volatile("st.shared.v2.u32 [%0], {%1,%2};" ::"r"(sb + OFF_EPOCH), "r"(par + 1), "r"(0) : "memory");
      par = (par + 1) & 1;
      {
        float y0 = (lane & 4) ? z[1] : z[0], y1 = (lane & 4) ? z[3] : z[2];
        y0 += __shfl_xor_sync(0xffffffffu, (lane & 4) ? z[0] : z[1], 4);
        y1 += __shfl_xor_sync(0xffffffffu, (lane & 4) ? z[2] : z[3], 4);
        float zz = (lane & 2) ? y1 : y0;
        zz += __shfl_xor_sync(0xffffffffu, (lane & 2) ? y0 : y1, 2);
        zz += __shfl_xor_sync(0xffffffffu, zz, 1);
        const float rho = 4.f * expf(zz > 40.f ? 40.f : zz);
        if ((lane & 1) == 0)
          asm volatile("st.relaxed.gpu.global.u32 [%0], %1;" ::"l"(g_gate + m * 128 + row + (lane & 4) + (lane & 2) * 4), "r"((__float_as_uint(rho) & ~1u) | par) : "memory");
      }
      if (lane == 0) TS(3, 0);
      mbar_wait(sb + OFF_GBAR, 0);
      asm volatile("st.shared.v2.u32 [%0], {%1,%2};" ::"r"(sb + OFF_DB + lane * 8), "r"(dk), "r"(bf2_add(bb, bb)) : "memory");
      uint32_t g0, g1, g2, g3;
      int tries = 0;
#pragma unroll 1
      do {
        asm volatile("ld.relaxed.gpu.global.v4.u32 {%0,%1,%2,%3}, [%4];" : "=r"(g0), "=r"(g1), "=r"(g2), "=r"(g3) : "l"(g_gate + m * 128 + lane * 4) : "memory");
      } while ((((g0 ^ par) | (g1 ^ par) | (g2 ^ par) | (g3 ^ par)) & 1) && ++tries < 200000);
      asm volatile("st.shared.v2.u32 [%0], {%1,%2};" ::"r"(sb + OFF_GS + lane * 8), "r"(pack_bf16(__uint_as_float(g0), __uint_as_float(g1))),
                   "r"(pack_bf16(__uint_as_float(g2), __uint_as_float(g3))) : "memory");
      mbar_arrive(sb + OFF_CBAR);
      if (lane == 0) TS(3, 4);
     }
    } else {
      asm volatile("barrier.cluster.wait.aligned;" ::: "memory");
      if (elect_one()) {
        TS(2, 1);
        const CUtensorMap* mb = rank ? &maps.bim : &maps.bre;
        const uint32_t t0 = clock();
#pragma unroll 1
        for (int u = 0; u < 8; u++) {
          if (u >= DN) while ((uint32_t)clock() - t0 < D0 + (u - DN) * D1) {}
          mbar_expect_tx(sb + OFF_XFULL + 8 * u, 16384);
          tma5d(sb + OFF_X + ((u + xrot) & 7) * 16384, &maps.x, u * 64, 2 * m, sb + OFF_XFULL + 8 * u);
          if (u < 6) {
            mbar_expect_tx(sb + OFF_FULL + 8 * u, 16384);
            tma2d_mc(sb + OFF_RING + u * 16384 + rank * 8192, mb, u * 64, s * 64, sb + OFF_FULL + 8 * u);
          } else if (PF & 4) {
            asm volatile("cp.async.bulk.prefetch.tensor.2d.L2.global [%0, {%1,%2}];" ::"l"(mb), "r"(u * 64), "r"(s * 64) : "memory");
          }
        }
        TS(2, 5);
        const CUtensorMap* mc = rank ? &maps.cim : &maps.cre;
        int slot = 0; uint32_t ph = 0;
#pragma unroll 1
        for (int u = 6; u < 27; u++) {
          const uint32_t fb = sb + OFF_FULL + 8 * slot, dst = sb + OFF_RING + slot * 16384;
          mbar_wait(sb + OFF_EMPTY + 8 * slot, ph);
          TS2(0, u);
          if (u < 8) {
            mbar_expect_tx(fb, 16384);
            tma2d_mc(dst + rank * 8192, mb, u * 64, s * 64, fb);
          } else if (u < 16) {
            mbar_expect_tx(fb, 12288);
            tma3d_mc(dst + rank * 6144, &maps.w1b, 0, (u - 8) * 64 + rank * 32, s * 7, fb);
          } else if (u < 24) {
            mbar_expect_tx(fb, 16384);
            tma2d_mc(dst + rank * 8192, &maps.w1a, s * 224 + 96 + rank * 64, ((u - 15 + s) & 7) * 64, fb);
          } else if (u == 25) {
            mbar_expect_tx(fb, 16384);
            tma2d_mc(dst + rank * 8192, mc, s * 64, ((s + 1) & 7) * 64, fb);
          } else {
            mbar_expect_tx(fb, 14336);
            tma2d_mc(dst + rank * 7168, &maps.w2, ((s + 1) & 7) * 64, s * 224 + (u - 24) * 56 + rank * 56, fb);
          }
          if (++slot == NSLOT) { slot = 0; ph ^= 1; }
        }
#pragma unroll 1
        for (int p = 1; p < 8; p++) {
          const int piece = (s + 1 + p) & 7, grp = p % 3;
          const uint32_t fb = sb + OFF_XFULL + 8 * p, dst = grp == 1 ? sb + OFF_X + 2 * 16384 : sb + OFF_RING + grp * 24576;
          if (p >= 3) mbar_wait(sb + OFF_EMPTY + 8 * (p - 3), 0);
          else if (p == 2) mbar_wait(sb + OFF_EMPTY + 40, 1);
          TS2(0, 32 + p);
          mbar_expect_tx(fb, 45056);
          tma2d_mc(dst + rank * 7168, &maps.w2, piece * 64, s * 224 + rank * 56, fb);
          tma2d_mc(dst + 16384 + rank * 8192, mc, s * 64, piece * 64, fb);
          tma2d_mc(dst + 32768 + rank * 7168, &maps.w2, piece * 64, s * 224 + 112 + rank * 56, fb);
        }
        TS(2, 2);
      }
    }
  }
}

typedef CUresult (*EncFn)(CUtensorMap*, CUtensorMapDataType, cuuint32_t, void*, const cuuint64_t*, const cuuint64_t*, const cuuint32_t*,
                          const cuuint32_t*, CUtensorMapInterleave, CUtensorMapSwizzle, CUtensorMapL2promotion, CUtensorMapFloatOOBfill);

void encode(EncFn f, CUtensorMap* mp, const void* p, int rank, const cuuint64_t* dims, const cuuint64_t* strides, const cuuint32_t* box, CUtensorMapSwizzle sw) {
  cuuint32_t es[5] = {1, 1, 1, 1, 1};
  f(mp, CU_TENSOR_MAP_DATA_TYPE_BFLOAT16, rank, const_cast<void*>(p), dims, strides, box, es, CU_TENSOR_MAP_INTERLEAVE_NONE, sw,
    PROMO, CU_TENSOR_MAP_FLOAT_OOB_FILL_NONE);
}

}

extern "C" void kernel_launch(void* const* d_in, const int* in_sizes, int n_in, void* d_out, int out_size) {
  typedef const __nv_bfloat16* bp;
  bp x = (bp)d_in[0], lre = (bp)d_in[1], lim = (bp)d_in[2], bre = (bp)d_in[3], bim = (bp)d_in[4], cre = (bp)d_in[5], cim = (bp)d_in[6],
     ldt = (bp)d_in[7], dsk = (bp)d_in[8], w1 = (bp)d_in[10], b1 = (bp)d_in[11], w2 = (bp)d_in[12], b2 = (bp)d_in[13], gw = (bp)d_in[14];
  static EncFn enc = nullptr;
  if (!enc) {
    void* f = nullptr;
    cudaDriverEntryPointQueryResult qr;
    cudaGetDriverEntryPoint("cuTensorMapEncodeTiled", &f, cudaEnableDefault, &qr);
    enc = (EncFn)f;
    cudaFuncSetAttribute(fused_kernel, cudaFuncAttributeMaxDynamicSharedMemorySize, SMEM_BYTES);
  }
  Maps maps;
  {
    cuuint64_t d[5] = {DM, 2, 4, 8, SEQ / 64}, st[4] = {DM * 2, 16 * DM * 2, 2 * DM * 2, 64 * DM * 2};
    cuuint32_t bx[5] = {64, 2, 4, 8, 2};
    encode(enc, &maps.x, x, 5, d, st, bx, CU_TENSOR_MAP_SWIZZLE_128B);
  }
  {
    cuuint64_t d[2] = {DM, DM}, st[1] = {DM * 2};
    cuuint32_t bx[2] = {64, 64};
    encode(enc, &maps.bre, bre, 2, d, st, bx, CU_TENSOR_MAP_SWIZZLE_128B);
    encode(enc, &maps.bim, bim, 2, d, st, bx, CU_TENSOR_MAP_SWIZZLE_128B);
    encode(enc, &maps.cre, cre, 2, d, st, bx, CU_TENSOR_MAP_SWIZZLE_128B);
    encode(enc, &maps.cim, cim, 2, d, st, bx, CU_TENSOR_MAP_SWIZZLE_128B);
  }
  {
    cuuint64_t d[2] = {FF, DM}, st[1] = {FF * 2};
    cuuint32_t bx[2] = {64, 64};
    encode(enc, &maps.w1a, w1, 2, d, st, bx, CU_TENSOR_MAP_SWIZZLE_128B);
    cuuint64_t d3[3] = {32, DM, FF / 32}, st3[2] = {FF * 2, 64};
    cuuint32_t bx3[3] = {32, 32, 3};
    encode(enc, &maps.w1b, w1, 3, d3, st3, bx3, CU_TENSOR_MAP_SWIZZLE_64B);
  }
  {
    cuuint64_t d[2] = {DM, FF}, st[1] = {DM * 2};
    cuuint32_t bx[2] = {64, 56};
    encode(enc, &maps.w2, w2, 2, d, st, bx, CU_TENSOR_MAP_SWIZZLE_128B);
  }
  fused_kernel<<<128, 384, SMEM_BYTES>>>(lre, lim, ldt, dsk, b1, b2, gw, w1, w2, cre, cim, (float*)d_out, maps);
}
```

```cpp
#include <cuda_runtime.h>
#include <cuda_bf16.h>
#include <cuda.h>
#include <stdint.h>

#define PF 6
#define SEND_TMA 0
#define PREW 0
#define CK 3
#define D0 600
#define D1 500
#define DN 1
#define PROMO CU_TENSOR_MAP_L2_PROMOTION_L2_128B
#define TMP 3
#define MAP 1
#define STV4 1
#define R2E 0
#define EARLYW 0
#define TP 4
#define TW 0
#define NTMA 6
#define PFK 5
namespace {

constexpr int SEQ = 2048, DM = 512, FF = 1792;
constexpr int NSLOT = 6;
constexpr uint32_t OFF_X = 0, OFF_RING = 131072, OFF_MISC = 229376;
constexpr uint32_t OFF_XFULL = OFF_MISC, OFF_FULL = OFF_XFULL + 64, OFF_EMPTY = OFF_FULL + 48, OFF_GBAR = OFF_EMPTY + 48,
                   OFF_CBAR = OFF_GBAR + 8, OFF_LBAR = OFF_CBAR + 8, OFF_EPOCH = OFF_CBAR + 24;
constexpr uint32_t OFF_LC = OFF_MISC + 256;
constexpr uint32_t OFF_GS = OFF_LC;
constexpr uint32_t OFF_DB = OFF_LC + 512;
constexpr uint32_t OFF_CARRY = OFF_LC + 1024;
constexpr uint32_t OFF_DBG = OFF_CARRY + 1024;
constexpr uint32_t SMEM_BYTES = OFF_DBG + 768;
static_assert(SMEM_BYTES <= 232448, "smem");

struct Maps {
  CUtensorMap x, bre, bim, w1b, w1a, w2, cre, cim; };

__device__ uint4 g_part[16 * 8 * 7 * 1024];
__device__ float2 g_end[8 * 16 * 64];
__device__ unsigned g_gate[SEQ];
__device__ unsigned g_epoch[128];
#define TG(role) do {} while (0)
#define TS2(role, i) do {} while (0)
#define TS(role, i) do {} while (0)
#define TDUMP() do {} while (0)
#define TR(i) do {} while (0)
#define TRD() do {} while (0)

__device__ __forceinline__ void mbar_init(uint32_t bar, uint32_t cnt) { asm volatile("mbarrier.init.shared::cta.b64 [%0], %1;" ::"r"(bar), "r"(cnt)); }
__device__ __forceinline__ void mbar_expect_tx(uint32_t bar, uint32_t bytes) { asm volatile("mbarrier.arrive.expect_tx.shared::cta.b64 _, [%0], %1;" ::"r"(bar), "r"(bytes) : "memory"); }
__device__ __forceinline__ void mbar_arrive(uint32_t bar) { asm volatile("mbarrier.arrive.shared::cta.b64 _, [%0];" ::"r"(bar) : "memory"); }
__device__ __forceinline__ void mbar_arrive_cl(uint32_t cbar) { asm volatile("mbarrier.arrive.shared::cluster.b64 _, [%0];" ::"r"(cbar) : "memory"); }
__device__ __forceinline__ void mbar_wait(uint32_t bar, uint32_t parity) {
  asm volatile(
      "{\n.reg .pred p;\n.reg .u32 c;\n"
      "mbarrier.try_wait.parity.shared::cta.b64 p, [%0], %1;\n"
      "@p bra.uni LAB_DONE;\n"
      "mov.u32 c, 0;\n"
      "LAB_WAIT:\n"
      "mbarrier.try_wait.parity.shared::cta.b64 p, [%0], %1;\n"
      "@p bra.uni LAB_DONE;\n"
      "add.u32 c, c, 1;\nsetp.lt.u32 p, c, 200000;\n@p bra.uni LAB_WAIT;\n"
      "LAB_DONE:\n}" ::"r"(bar), "r"(parity) : "memory");
}
__device__ __forceinline__ void tma2d(uint32_t dst, const CUtensorMap* m, int c0, int c1, uint32_t bar) {
  asm volatile("cp.async.bulk.tensor.2d.shared::cluster.global.mbarrier::complete_tx::bytes [%0], [%1, {%3,%4}], [%2];"
               ::"r"(dst), "l"(m), "r"(bar), "r"(c0), "r"(c1) : "memory");
}
__device__ __forceinline__ void tma2d_mc(uint32_t dst, const CUtensorMap* m, int c0, int c1, uint32_t bar) {
  asm volatile("cp.async.bulk.tensor.2d.shared::cluster.global.mbarrier::complete_tx::bytes.multicast::cluster [%0], [%1, {%3,%4}], [%2], %5;"
               ::"r"(dst), "l"(m), "r"(bar), "r"(c0), "r"(c1), "h"((uint16_t)3) : "memory");
}
__device__ __forceinline__ void tma3d_mc(uint32_t dst, const CUtensorMap* m, int c0, int c1, int c2, uint32_t bar) {
  asm volatile("cp.async.bulk.tensor.3d.shared::cluster.global.mbarrier::complete_tx::bytes.multicast::cluster [%0], [%1, {%3,%4,%5}], [%2], %6;"
               ::"r"(dst), "l"(m), "r"(bar), "r"(c0), "r"(c1), "r"(c2), "h"((uint16_t)3) : "memory");
}
__device__ __forceinline__ void tma5d(uint32_t dst, const CUtensorMap* m, int c0, int c4, uint32_t bar) {
  asm volatile("cp.async.bulk.tensor.5d.shared::cluster.global.mbarrier::complete_tx::bytes [%0], [%1, {%3,%5,%5,%5,%4}], [%2];"
               ::"r"(dst), "l"(m), "r"(bar), "r"(c0), "r"(c4), "r"(0) : "memory");
}
__device__ __forceinline__ void l2_prefetch(const void* p, uint32_t bytes) { asm volatile("cp.async.bulk.prefetch.L2.global [%0], %1;" ::"l"(p), "r"(bytes) : "memory"); }
__device__ __forceinline__ bool elect_one() {
  uint32_t pred;
  asm volatile("{.reg .pred P; elect.sync _|P, 0xffffffff; selp.u32 %0, 1, 0, P;}" : "=r"(pred));
  return pred != 0;
}
__device__ __forceinline__ void wg_fence() { asm volatile("wgmma.fence.sync.aligned;" ::: "memory"); }
__device__ __forceinline__ void wg_commit() { asm volatile("wgmma.commit_group.sync.aligned;" ::: "memory"); }
template <int N> __device__ __forceinline__ void wg_wait() { asm volatile("wgmma.wait_group.sync.aligned %0;" ::"n"(N) : "memory"); }
template <int N> __device__ __forceinline__ void reg_fence(float (&d)[N]) {
#pragma unroll
  for (int i = 0; i < N; i++) asm volatile("" : "+f"(d[i])::"memory");
}
__device__ __forceinline__ void bar_sync(int id, int n) { asm volatile("bar.sync %0, %1;" ::"r"(id), "r"(n) : "memory"); }
__device__ __forceinline__ void bar_arrive(int id, int n) { asm volatile("bar.arrive %0, %1;" ::"r"(id), "r"(n) : "memory"); }
constexpr uint32_t DH128 = (1024 >> 4) | (1u << 30), DH64 = (512 >> 4) | (2u << 30);
__host__ __device__ constexpr uint32_t lbo(uint32_t bytes) { return (bytes >> 4) << 20; }
__device__ __forceinline__ uint32_t pack_bf16(float lo, float hi) { uint32_t r; asm("cvt.rn.bf16x2.f32 %0, %1, %2;" : "=r"(r) : "f"(hi), "f"(lo)); return r; }
__device__ __forceinline__ float bf_lo(uint32_t v) { return __uint_as_float(v << 16); }
__device__ __forceinline__ float bf_hi(uint32_t v) { return __uint_as_float(v & 0xffff0000u); }
__device__ __forceinline__ float bf_ld(const __nv_bfloat16* p) { return __bfloat162float(__ldg(p)); }
__device__ __forceinline__ uint32_t raw_ld(const __nv_bfloat16* p) { return __ldg(reinterpret_cast<const unsigned short*>(p)); }
__device__ __forceinline__ uint32_t late16(uint32_t bar) {
  uint32_t r;
  asm volatile("{.reg .pred p; mbarrier.test_wait.parity.shared::cta.b64 p, [%1], 0; selp.u32 %0, 16, 0, p;}" : "=r"(r) : "r"(bar) : "memory");
  return r;
}
__device__ __forceinline__ float2 lds_f2(uint32_t a) { float2 v; asm volatile("ld.shared.v2.f32 {%0,%1}, [%2];" : "=f"(v.x), "=f"(v.y) : "r"(a)); return v; }
__device__ __forceinline__ float lds_f(uint32_t a) { float v; asm volatile("ld.shared.f32 %0, [%1];" : "=f"(v) : "r"(a)); return v; }
__device__ __forceinline__ uint32_t lds_h(uint32_t a) { uint32_t v; asm volatile("ld.shared.u16 %0, [%1];" : "=r"(v) : "r"(a)); return v; }
__device__ __forceinline__ uint32_t lds_u(uint32_t a) { uint32_t v; asm volatile("ld.shared.u32 %0, [%1];" : "=r"(v) : "r"(a)); return v; }
__device__ __forceinline__ uint4 lds_u4(uint32_t a) { uint4 v; asm volatile("ld.shared.v4.u32 {%0,%1,%2,%3}, [%4];" : "=r"(v.x), "=r"(v.y), "=r"(v.z), "=r"(v.w) : "r"(a)); return v; }
__device__ __forceinline__ void st_b128(uint4* p, uint32_t a, uint32_t b, uint32_t c, uint32_t d) {
  asm volatile("st.relaxed.gpu.global.v4.b32 [%0], {%1,%2,%3,%4};" ::"l"(p), "r"(a), "r"(b), "r"(c), "r"(d) : "memory");
}
__device__ __forceinline__ void ld_b128(const uint4* p, uint32_t& a, uint32_t& b, uint32_t& c, uint32_t& d) {
  asm volatile("{.reg .b64 l, h; .reg .b128 v; ld.relaxed.gpu.global.b128 v, [%4]; mov.b128 {l,h}, v; mov.b64 {%0,%1}, l; mov.b64 {%2,%3}, h;}"
               : "=r"(a), "=r"(b), "=r"(c), "=r"(d) : "l"(p) : "memory");
}
__device__ __forceinline__ float tanh_fast(float x) { float y; asm("tanh.approx.f32 %0, %1;" : "=f"(y) : "f"(x)); return y; }
__device__ __forceinline__ float gelu2(float v) {
  float p = fmaf(v * v, 0.0356774081363f, 0.7978845608029f);
  return fmaf(v, tanh_fast(v * p), v);
}
__device__ __forceinline__ uint32_t bf2_mul(uint32_t a, uint32_t b) { uint32_t r; asm("mul.rn.bf16x2 %0, %1, %2;" : "=r"(r) : "r"(a), "r"(b)); return r; }
__device__ __forceinline__ uint32_t bf2_add(uint32_t a, uint32_t b) { uint32_t r; asm("add.rn.bf16x2 %0, %1, %2;" : "=r"(r) : "r"(a), "r"(b)); return r; }
__device__ __forceinline__ uint32_t bf2_fma(uint32_t a, uint32_t b, uint32_t c) { uint32_t r; asm("fma.rn.bf16x2 %0, %1, %2, %3;" : "=r"(r) : "r"(a), "r"(b), "r"(c)); return r; }
__device__ __forceinline__ void pin(float& a) { asm volatile("" : "+f"(a)::"memory"); }
__device__ __forceinline__ void pin(uint32_t& a) { asm volatile("" : "+r"(a)::"memory"); }
struct cplx { float re, im; };
__device__ __forceinline__ cplx cmul(cplx a, cplx b) { return {fmaf(a.re, b.re, -a.im * b.im), fmaf(a.re, b.im, a.im * b.re)}; }
__device__ __forceinline__ cplx cfma(cplx a, cplx b, cplx c) {
  return {fmaf(a.re, b.re, fmaf(-a.im, b.im, c.re)), fmaf(a.re, b.im, fmaf(a.im, b.re, c.im))};
}
__device__ __forceinline__ cplx make_lam(float lre, float lim, float ldt) {
  float dt = __bfloat162float(__float2bfloat16_rn(expf(ldt)));
  float mag = expf(dt * lre), sn, cs;
  sincospif(dt * lim * 0.31830988618379067f, &sn, &cs);
  return {mag * cs, mag * sn};
}

template<int TA,int TB,uint32_t AH,uint32_t BH> __device__ __forceinline__ void wgmma_n64_ss(float (&d)[32], uint32_t al, uint32_t ao, uint32_t bl, uint32_t bo, int scale_d){
  asm volatile("{.reg .pred p; .reg .b32 t, v; .reg .b64 da, db; setp.ne.b32 p, %36, 0; add.u32 t, %32, %33; mov.b64 da, {t, %39}; add.u32 v, %34, %35; mov.b64 db, {v, %40};\n"
   "wgmma.mma_async.sync.aligned.m64n64k16.f32.bf16.bf16 {%0,%1,%2,%3,%4,%5,%6,%7,%8,%9,%10,%11,%12,%13,%14,%15,%16,%17,%18,%19,%20,%21,%22,%23,%24,%25,%26,%27,%28,%29,%30,%31}, da, db, p, 1, 1, %37, %38;}"
   : "+f"(d[0]),"+f"(d[1]),"+f"(d[2]),"+f"(d[3]),"+f"(d[4]),"+f"(d[5]),"+f"(d[6]),"+f"(d[7]),"+f"(d[8]),"+f"(d[9]),"+f"(d[10]),"+f"(d[11]),"+f"(d[12]),"+f"(d[13]),"+f"(d[14]),"+f"(d[15]),"+f"(d[16]),"+f"(d[17]),"+f"(d[18]),"+f"(d[19]),"+f"(d[20]),"+f"(d[21]),"+f"(d[22]),"+f"(d[23]),"+f"(d[24]),"+f"(d[25]),"+f"(d[26]),"+f"(d[27]),"+f"(d[28]),"+f"(d[29]),"+f"(d[30]),"+f"(d[31])
   : "r"(al),"r"(ao >> 4),"r"(bl),"r"(bo >> 4),"r"(scale_d),"n"(TA),"n"(TB),"n"(AH),"n"(BH));
}
template<int TB,uint32_t BH> __device__ __forceinline__ void wgmma_n64_rs(float (&d)[32], uint32_t a0,uint32_t a1,uint32_t a2,uint32_t a3, uint32_t bl, uint32_t bo, int scale_d){
  asm volatile("{.reg .pred p; .reg .b32 t; .reg .b64 db; setp.ne.b32 p, %38, 0; add.u32 t, %36, %37; mov.b64 db, {t, %40};\n"
   "wgmma.mma_async.sync.aligned.m64n64k16.f32.bf16.bf16 {%0,%1,%2,%3,%4,%5,%6,%7,%8,%9,%10,%11,%12,%13,%14,%15,%16,%17,%18,%19,%20,%21,%22,%23,%24,%25,%26,%27,%28,%29,%30,%31}, {%32,%33,%34,%35}, db, p, 1, 1, %39;}"
   : "+f"(d[0]),"+f"(d[1]),"+f"(d[2]),"+f"(d[3]),"+f"(d[4]),"+f"(d[5]),"+f"(d[6]),"+f"(d[7]),"+f"(d[8]),"+f"(d[9]),"+f"(d[10]),"+f"(d[11]),"+f"(d[12]),"+f"(d[13]),"+f"(d[14]),"+f"(d[15]),"+f"(d[16]),"+f"(d[17]),"+f"(d[18]),"+f"(d[19]),"+f"(d[20]),"+f"(d[21]),"+f"(d[22]),"+f"(d[23]),"+f"(d[24]),"+f"(d[25]),"+f"(d[26]),"+f"(d[27]),"+f"(d[28]),"+f"(d[29]),"+f"(d[30]),"+f"(d[31])
   : "r"(a0),"r"(a1),"r"(a2),"r"(a3),"r"(bl),"r"(bo >> 4),"r"(scale_d),"n"(TB),"n"(BH));
}
template<int TA,int TB,uint32_t AH,uint32_t BH> __device__ __forceinline__ void wgmma_n96_ss(float (&d)[48], uint32_t al, uint32_t ao, uint32_t bl, uint32_t bo, int scale_d){
  asm volatile("{.reg .pred p; .reg .b32 t, v; .reg .b64 da, db; setp.ne.b32 p, %52, 0; add.u32 t, %48, %49; mov.b64 da, {t, %55}; add.u32 v, %50, %51; mov.b64 db, {v, %56};\n"
   "wgmma.mma_async.sync.aligned.m64n96k16.f32.bf16.bf16 {%0,%1,%2,%3,%4,%5,%6,%7,%8,%9,%10,%11,%12,%13,%14,%15,%16,%17,%18,%19,%20,%21,%22,%23,%24,%25,%26,%27,%28,%29,%30,%31,%32,%33,%34,%35,%36,%37,%38,%39,%40,%41,%42,%43,%44,%45,%46,%47}, da, db, p, 1, 1, %53, %54;}"
   : "+f"(d[0]),"+f"(d[1]),"+f"(d[2]),"+f"(d[3]),"+f"(d[4]),"+f"(d[5]),"+f"(d[6]),"+f"(d[7]),"+f"(d[8]),"+f"(d[9]),"+f"(d[10]),"+f"(d[11]),"+f"(d[12]),"+f"(d[13]),"+f"(d[14]),"+f"(d[15]),"+f"(d[16]),"+f"(d[17]),"+f"(d[18]),"+f"(d[19]),"+f"(d[20]),"+f"(d[21]),"+f"(d[22]),"+f"(d[23]),"+f"(d[24]),"+f"(d[25]),"+f"(d[26]),"+f"(d[27]),"+f"(d[28]),"+f"(d[29]),"+f"(d[30]),"+f"(d[31]),"+f"(d[32]),"+f"(d[33]),"+f"(d[34]),"+f"(d[35]),"+f"(d[36]),"+f"(d[37]),"+f"(d[38]),"+f"(d[39]),"+f"(d[40]),"+f"(d[41]),"+f"(d[42]),"+f"(d[43]),"+f"(d[44]),"+f"(d[45]),"+f"(d[46]),"+f"(d[47])
   : "r"(al),"r"(ao >> 4),"r"(bl),"r"(bo >> 4),"r"(scale_d),"n"(TA),"n"(TB),"n"(AH),"n"(BH));
}
template<int TA,int TB,uint32_t AH,uint32_t BH> __device__ __forceinline__ void wgmma_n128_ss(float (&d)[64], uint32_t al, uint32_t ao, uint32_t bl, uint32_t bo, int scale_d){
  asm volatile("{.reg .pred p; .reg .b32 t, v; .reg .b64 da, db; setp.ne.b32 p, %68, 0; add.u32 t, %64, %65; mov.b64 da, {t, %71}; add.u32 v, %66, %67; mov.b64 db, {v, %72};\n"
   "wgmma.mma_async.sync.aligned.m64n128k16.f32.bf16.bf16 {%0,%1,%2,%3,%4,%5,%6,%7,%8,%9,%10,%11,%12,%13,%14,%15,%16,%17,%18,%19,%20,%21,%22,%23,%24,%25,%26,%27,%28,%29,%30,%31,%32,%33,%34,%35,%36,%37,%38,%39,%40,%41,%42,%43,%44,%45,%46,%47,%48,%49,%50,%51,%52,%53,%54,%55,%56,%57,%58,%59,%60,%61,%62,%63}, da, db, p, 1, 1, %69, %70;}"
   : "+f"(d[0]),"+f"(d[1]),"+f"(d[2]),"+f"(d[3]),"+f"(d[4]),"+f"(d[5]),"+f"(d[6]),"+f"(d[7]),"+f"(d[8]),"+f"(d[9]),"+f"(d[10]),"+f"(d[11]),"+f"(d[12]),"+f"(d[13]),"+f"(d[14]),"+f"(d[15]),"+f"(d[16]),"+f"(d[17]),"+f"(d[18]),"+f"(d[19]),"+f"(d[20]),"+f"(d[21]),"+f"(d[22]),"+f"(d[23]),"+f"(d[24]),"+f"(d[25]),"+f"(d[26]),"+f"(d[27]),"+f"(d[28]),"+f"(d[29]),"+f"(d[30]),"+f"(d[31]),"+f"(d[32]),"+f"(d[33]),"+f"(d[34]),"+f"(d[35]),"+f"(d[36]),"+f"(d[37]),"+f"(d[38]),"+f"(d[39]),"+f"(d[40]),"+f"(d[41]),"+f"(d[42]),"+f"(d[43]),"+f"(d[44]),"+f"(d[45]),"+f"(d[46]),"+f"(d[47]),"+f"(d[48]),"+f"(d[49]),"+f"(d[50]),"+f"(d[51]),"+f"(d[52]),"+f"(d[53]),"+f"(d[54]),"+f"(d[55]),"+f"(d[56]),"+f"(d[57]),"+f"(d[58]),"+f"(d[59]),"+f"(d[60]),"+f"(d[61]),"+f"(d[62]),"+f"(d[63])
   : "r"(al),"r"(ao >> 4),"r"(bl),"r"(bo >> 4),"r"(scale_d),"n"(TA),"n"(TB),"n"(AH),"n"(BH));
}

__global__ void __cluster_dims__(2, 1, 1) __launch_bounds__(384, 1)
fused_kernel(const __nv_bfloat16* __restrict__ lam_re,
             const __nv_bfloat16* __restrict__ lam_im, const __nv_bfloat16* __restrict__ log_dt, const __nv_bfloat16* __restrict__ dskip,
             const __nv_bfloat16* __restrict__ b1, const __nv_bfloat16* __restrict__ b2, const __nv_bfloat16* __restrict__ gate_w,
             const __nv_bfloat16* __restrict__ pf_w1, const __nv_bfloat16* __restrict__ pf_w2, const __nv_bfloat16* __restrict__ pf_cre,
             const __nv_bfloat16* __restrict__ pf_cim, float* __restrict__ out, const __grid_constant__ Maps maps) {
  extern __shared__ __align__(1024) unsigned char smem_raw[];
  const uint32_t sb = (uint32_t)__cvta_generic_to_shared(smem_raw);
  const int b = blockIdx.x;
  const int rank = b & 1, cl = b >> 1;
  const int s = cl >> 3, mi = cl & 7;
  const int m = mi * 2 + rank;
  const int warp = __shfl_sync(0xffffffffu, (int)(threadIdx.x >> 5), 0);
  const int lane = threadIdx.x & 31;
  const int xrot = 7 - s;

  if (elect_one()) {
    if (warp == 8) TS(2, 0);
    if (warp < TMP) asm volatile("prefetch.tensormap [%0];" ::"l"(&maps.x + warp) : "memory");
    const uint32_t c = warp < 7 ? 1 : warp < 10 ? 16 : 64;
    mbar_init(sb + OFF_XFULL + 16 * warp, c);
    mbar_init(sb + OFF_XFULL + 16 * warp + 8, warp < 10 ? c : 96);
    asm volatile("fence.mbarrier_init.release.cluster;" ::: "memory");
  }
  __syncwarp();
  asm volatile("barrier.cluster.arrive.relaxed.aligned;" ::: "memory");
  if (warp < 8) {
    const int wg = warp >> 2, w = warp & 3, q = lane & 3, gr = lane >> 2;
    uint32_t bv[28];
#pragma unroll
    for (int j = 0; j < 28; j++) bv[j] = __ldg(reinterpret_cast<const uint32_t*>(b1 + s * 224 + j * 8) + q);
    asm volatile("setmaxnreg.inc.sync.aligned.u32 224;");
    asm volatile("barrier.cluster.wait.aligned;" ::: "memory");
    TS(wg, 0);
    uint32_t ebar;
    asm volatile("mapa.shared::cluster.u32 %0, %1, %2;" : "=r"(ebar) : "r"(sb + OFF_EMPTY), "r"(lane & 1));
    auto release = [&](int slot) { if (lane < 2) mbar_arrive_cl(ebar + 8 * slot); };
    const uint32_t xw = sb + OFF_X + wg * 8192, fullb = sb + OFF_FULL;
    const uint32_t dxw = (xw & 0x3FFFF) >> 4, dring = ((sb + OFF_RING) & 0x3FFFF) >> 4;

    float ure[32], uim[32], aa[48], ab[64];
    cplx lam[2], coef[2], l16[2], l32[2], lq[2], pre[2], e[2];
    uint32_t sh16, mhi;

#pragma unroll
    for (int kb = 0; kb < 8; kb++) {
      const int slot = kb % NSLOT;
      TS2(1, kb);
      mbar_wait(sb + OFF_XFULL + 8 * kb, 0);
      if (kb == 0) TS(wg, 18);
      mbar_wait(fullb + 8 * slot, (kb / NSLOT) & 1);
      TS2(2, kb);
      if (kb == 0) TS(wg, 1);
      wg_fence();
      const uint32_t dxa = dxw + ((kb + xrot) & 7) * 1024;
#pragma unroll
      for (int kk = 0; kk < 4; kk++) {
        wgmma_n64_ss<0, 0, DH128, DH128>(ure, dring, slot * 16384 + kk * 32, dxa, kk * 32, (kb | kk) != 0);
        wgmma_n64_ss<0, 0, DH128, DH128>(uim, dring, slot * 16384 + 8192 + kk * 32, dxa, kk * 32, (kb | kk) != 0);
      }
      wg_commit();
      if (kb > 0) { wg_wait<1>(); release((kb - 1) % NSLOT); }
      if (kb == 1) { sh16 = late16(sb + OFF_XFULL); mhi = 0xffffffffu << sh16; }
      if (kb >= 1 && kb < 5) {
#pragma unroll
        for (int j = (kb - 1) * 7; j < kb * 7; j++) {
          pin(bv[j]);
          float* d = j < 12 ? aa + 4 * j : ab + 4 * (j - 12);
          d[0] = d[2] = __uint_as_float(bv[j] << sh16); d[1] = d[3] = __uint_as_float(bv[j] & mhi);
          pin(d[0]); pin(d[1]); pin(d[2]); pin(d[3]);
        }
      }
      if (kb == 4) {
        mbar_wait(sb + OFF_LBAR, 0);
#pragma unroll
        for (int h = 0; h < 2; h++) {
          const uint4 v = lds_u4(sb + OFF_LC + (w * 16 + gr + 8 * h) * 16);
          lam[h] = cplx{__uint_as_float(v.x), __uint_as_float(v.y)};
          coef[h] = cplx{__uint_as_float(v.z), __uint_as_float(v.w)};
        }
      }
      if (kb == 5) {
#pragma unroll
        for (int h = 0; h < 2; h++) {
          pin(lam[h].re); pin(lam[h].im);
          cplx t = cmul(lam[h], lam[h]); t = cmul(t, t); t = cmul(t, t);
          l16[h] = cmul(t, t); l32[h] = cmul(l16[h], l16[h]);
          pin(l32[h].re); pin(l32[h].im);
        }
      }
      if (kb == 6) {
#pragma unroll
        for (int h = 0; h < 2; h++) {
          pin(l16[h].re); pin(l16[h].im);
          const cplx a = (q & 1) ? l16[h] : cplx{1.f, 0.f}, c = (q & 2) ? l32[h] : cplx{1.f, 0.f};
          lq[h] = cmul(cmul(a, c), coef[h]);
          pin(lq[h].re); pin(lq[h].im);
        }
      }
    }
    TS(wg, 2);
    auto scale_u = [&](int i0, int i1) {
#pragma unroll
      for (int i = 0; i < 32; i++) if (i >= i0 && i < i1) {
        pin(ure[i]); pin(uim[i]);
        const cplx v = cmul(coef[(i >> 1) & 1], cplx{ure[i], uim[i]});
        ure[i] = v.re; uim[i] = v.im;
        pin(ure[i]); pin(uim[i]);
      }
    };
#pragma unroll
    for (int kb = 0; kb < 8; kb++) {
      const int u = 8 + kb, slot = u % NSLOT;
      TS2(1, u);
      mbar_wait(fullb + 8 * slot, (u / NSLOT) & 1);
      TS2(2, u);
      wg_fence();
      const uint32_t dxa = dxw + ((kb + xrot) & 7) * 1024;
#pragma unroll
      for (int kk = 0; kk < 4; kk++)
        wgmma_n96_ss<0, 1, DH128, DH64>(aa, dxa, kk * 32, dring, slot * 16384 + (kk >> 1) * 6144 + (kk & 1) * 1024 + lbo(2048), 1);
      wg_commit();
      wg_wait<1>();
      release((u - 1) % NSLOT);
      if (kb == 0) {
        reg_fence(ure); reg_fence(uim);
#pragma unroll
        for (int h = 0; h < 2; h++) e[h] = cplx{ure[2 * h], uim[2 * h]};
      }
      if (kb == 0 || kb == 2 || kb == 3) {
        const int ch = kb ? kb - 1 : 0;
#pragma unroll
        for (int t = 1 + 5 * ch; t < 6 + 5 * ch; t++)
#pragma unroll
          for (int h = 0; h < 2; h++) { const int i = 4 * (t >> 1) + 2 * h + (t & 1); e[h] = cfma(lam[h], e[h], cplx{ure[i], uim[i]}); }
#pragma unroll
        for (int h = 0; h < 2; h++) { pin(e[h].re); pin(e[h].im); }
      } else if (kb == 4) {
#pragma unroll
        for (int h = 0; h < 2; h++) {
          cplx y = {__shfl_up_sync(0xffffffffu, e[h].re, 1, 4), __shfl_up_sync(0xffffffffu, e[h].im, 1, 4)};
          if (q >= 1) e[h] = cfma(l16[h], y, e[h]);
          y = cplx{__shfl_up_sync(0xffffffffu, e[h].re, 2, 4), __shfl_up_sync(0xffffffffu, e[h].im, 2, 4)};
          if (q >= 2) e[h] = cfma(l32[h], y, e[h]);
        }
        if (q == 3) {
#pragma unroll
          for (int h = 0; h < 2; h++)
            asm volatile("st.shared.v2.f32 [%0], {%1,%2};" ::"r"(sb + OFF_CARRY + wg * 512 + (w * 16 + gr + 8 * h) * 8), "f"(e[h].re), "f"(e[h].im) : "memory");
          mbar_arrive(sb + OFF_GBAR);
        }
#pragma unroll
        for (int h = 0; h < 2; h++) {
          const cplx y = {__shfl_up_sync(0xffffffffu, e[h].re, 1, 4), __shfl_up_sync(0xffffffffu, e[h].im, 1, 4)};
          pre[h] = (q >= 1) ? cmul(coef[h], y) : cplx{0.f, 0.f};
          pin(pre[h].re); pin(pre[h].im);
        }
        TS(wg, 3);
      } else if (kb > 4) {
        scale_u(kb == 5 ? 0 : kb == 6 ? 4 : 12, kb == 5 ? 4 : kb == 6 ? 12 : 20);
      }
    }
    TS(wg, 4);
    uint32_t H[56];
    cplx hst[2];
    const uint32_t dh = dxw;
    const uint32_t hst_addr = xw + (w * 16 + (lane & 15)) * 128 + (((lane >> 4) ^ (lane & 7)) << 4);
#pragma unroll
    for (int kb = 0; kb < 8; kb++) {
      const int u = 16 + kb, slot = u % NSLOT;
      TS2(1, u);
      mbar_wait(fullb + 8 * slot, (u / NSLOT) & 1);
      TS2(2, u);
      wg_fence();
#pragma unroll
      for (int kk = 0; kk < 4; kk++)
        wgmma_n128_ss<0, 1, DH128, DH128>(ab, dxw, kb * 16384 + kk * 32, dring, slot * 16384 + kk * 2048 + lbo(8192), 1);
      wg_commit();
      wg_wait<1>();
      release((u - 1) % NSLOT);
      if (kb == 0) scale_u(20, 32);
      if (kb < 5 && kb != 1) {
        const int ch = kb ? kb - 1 : 0;
#pragma unroll
        for (int i = ch * 6; i < ch * 6 + 6; i++) {
          pin(aa[2 * i]); pin(aa[2 * i + 1]);
          H[i] = pack_bf16(gelu2(aa[2 * i]), gelu2(aa[2 * i + 1]));
          pin(H[i]);
        }
      }
      if (kb >= 4) {
        if (kb == 4) {
          TS(wg, 5);
          mbar_wait(sb + OFF_CBAR, 0);
          TS(wg, 6);
#pragma unroll
          for (int h = 0; h < 2; h++) {
            const float2 c = lds_f2(sb + OFF_CARRY + wg * 512 + (w * 16 + gr + 8 * h) * 8);
            hst[h] = cfma(lq[h], cplx{c.x, c.y}, pre[h]);
          }
        }
        const int j0 = (kb - 4) * 2;
        uint32_t rr[4], ri[4];
#pragma unroll
        for (int jj = 0; jj < 2; jj++) {
          const int j = j0 + jj;
          const uint32_t g2 = lds_u(sb + OFF_GS + (wg * 64 + j * 8 + q * 2) * 2);
#pragma unroll
          for (int h = 0; h < 2; h++) {
            const int i = 4 * j + 2 * h;
            const cplx h0 = cfma(lam[h], hst[h], cplx{ure[i], uim[i]});
            hst[h] = cfma(lam[h], h0, cplx{ure[i + 1], uim[i + 1]});
            rr[jj * 2 + h] = bf2_mul(pack_bf16(h0.re, hst[h].re), g2);
            ri[jj * 2 + h] = bf2_mul(pack_bf16(h0.im, hst[h].im), g2 ^ 0x80008000u);
          }
        }
        const uint32_t a = hst_addr ^ (j0 << 4);
        asm volatile("stmatrix.sync.aligned.m8n8.x4.shared.b16 [%0], {%1,%2,%3,%4};" ::"r"(a), "r"(rr[0]), "r"(rr[1]), "r"(rr[2]), "r"(rr[3]) : "memory");
        asm volatile("stmatrix.sync.aligned.m8n8.x4.shared.b16 [%0], {%1,%2,%3,%4};" ::"r"(a + 16384), "r"(ri[0]), "r"(ri[1]), "r"(ri[2]), "r"(ri[3]) : "memory");
      }
    }
    TS(wg, 7);

    uint4* const psend = g_part + (size_t)m * (8 * 7 * 1024) + warp * 128;
    const uint4* const precv = g_part + (size_t)(m * 8 + s) * (7 * 1024) + warp * 128 + lane;
    const uint32_t stg = sb + OFF_X + 5 * 16384 + warp * 2048 + lane * 16;
    const uint32_t dx0 = ((sb + OFF_X) & 0x3FFFF) >> 4;
    float o[32], fin[32], rho[2];
    uint32_t tr[8];
    uint32_t r0[16], r1[16], r2[16], sum[16], tag;
    auto send = [&](int p) {
#pragma unroll
      for (int i = 0; i < 4; i++) {
        uint32_t t0;
        asm("lop3.b32 %0, %1, 1, %2, 0xb8;" : "=r"(t0) : "r"(pack_bf16(o[8 * i], o[8 * i + 1])), "r"(tag));
        if (p < NTMA)
          asm volatile("st.shared.v4.u32 [%0], {%1,%2,%3,%4};" ::"r"(stg + i * 512), "r"(t0), "r"(pack_bf16(o[8 * i + 2], o[8 * i + 3])),
                       "r"(pack_bf16(o[8 * i + 4], o[8 * i + 5])), "r"(pack_bf16(o[8 * i + 6], o[8 * i + 7])) : "memory");
        else
          st_b128(psend + (((s + 1 + p) & 7) * 7 + p) * 1024 + i * 32 + lane, t0, pack_bf16(o[8 * i + 2], o[8 * i + 3]), pack_bf16(o[8 * i + 4], o[8 * i + 5]),
                  pack_bf16(o[8 * i + 6], o[8 * i + 7]));
      }
      if (p < NTMA) { __syncwarp(); if (lane < 16) mbar_arrive(sb + OFF_GBAR + wg * 16); }
    };
    auto recv_issue = [&](uint32_t (&r)[16], int p) {
#pragma unroll
      for (int i = 0; i < 4; i++) ld_b128(precv + p * 1024 + i * 32, r[4 * i], r[4 * i + 1], r[4 * i + 2], r[4 * i + 3]);
    };
    auto stale = [&](uint32_t (&r)[16]) {
      uint32_t t0, t1;
      asm("lop3.b32 %0, %1, %2, %3, 0x7e;" : "=r"(t0) : "r"(r[0]), "r"(r[4]), "r"(tag));
      asm("lop3.b32 %0, %1, %2, %3, 0x7e;" : "=r"(t1) : "r"(r[8]), "r"(r[12]), "r"(tag));
      uint32_t r_;
      asm volatile("{.reg .pred p; .reg .b32 t; lop3.b32 t, %1, %2, 1, 0xa8; setp.ne.u32 p, t, 0; vote.sync.any.pred p, p, 0xffffffff; selp.u32 %0, 1, 0, p;}" : "=r"(r_) : "r"(t0), "r"(t1));
      return r_ != 0;
    };
    auto recv_check = [&](uint32_t (&r)[16], int p) {
      if (__builtin_expect(stale(r), 0)) {
        int tries = 0;
#pragma unroll 1
        do { recv_issue(r, p); } while (stale(r) && ++tries < 200000);
      }
    };
    auto gelu_b = [&](int i0, int i1) {
#pragma unroll
      for (int i = i0; i < i1; i++) {
        pin(ab[2 * i]); pin(ab[2 * i + 1]);
        H[24 + i] = pack_bf16(gelu2(ab[2 * i]), gelu2(ab[2 * i + 1]));
        pin(H[24 + i]);
      }
    };
    auto mma = [&](float (&o)[32], uint32_t wo, int k0, int k1, int acc) {
      wg_fence();
#pragma unroll
      for (int k = k0; k < k1; k++) {
        if (k >= 6 && k < 14) {
          const int kk = k - 6;
          wgmma_n64_ss<1, 0, DH128, DH128>(o, dh, (kk >> 2) * 16384 + (kk & 3) * 2048, dx0, wo + 16384 + (kk >> 2) * 8192 + (kk & 3) * 32, 1);
        } else {
          const int kk = k < 6 ? k : k - 8;
          wgmma_n64_rs<1, DH128>(o, H[4 * kk], H[4 * kk + 1], H[4 * kk + 2], H[4 * kk + 3], dx0, wo + (kk / 7) * 32768 + (kk % 7) * 2048, k != 0 || acc);
        }
      }
      wg_commit();
    };
#pragma unroll
    for (int p = 0; p < 8; p++) {
      const uint32_t wo = (p % 3) == 1 ? 2 * 16384 : OFF_RING + (p % 3) * 24576;
      if (p == 0) {
        mbar_wait(fullb, 0);
        mma(o, wo, 0, 3, 0);
        asm volatile("fence.proxy.async.shared::cta;" ::: "memory");
        wg_wait<1>(); release(5);
        gelu_b(0, 4);
        mma(o, wo, 3, 6, 0);
        gelu_b(4, 10);
        bar_sync(1 + wg, 128);
        mbar_wait(fullb + 8, 0);
        mma(o, wo, 6, 10, 0);
        gelu_b(10, 16);
        mma(o, wo, 10, 15, 0);
        gelu_b(16, 24);
        mbar_wait(fullb + 16, 0);
        mma(o, wo, 15, 18, 0);
        gelu_b(24, 32);
        if (wg == 1) bar_sync(4, 256);
        mma(o, wo, 18, 22, 0);
      } else {
        TR(0);
        if (!EARLYW) mbar_wait(sb + OFF_XFULL + 8 * p, 1);
        TR(1);
        bar_sync(3 + wg, 256);
        if (p < 7) mma(o, wo, 0, 22, 0); else mma(fin, wo, 0, 22, 1);
      }
      if (p < 7 || wg == 0) bar_arrive(4 - wg, 256);
      TR(2);
      if (p != TP) TS(wg, 8 + p);
      if (R2E && p == 7) recv_issue(r2, 6);
      if (p == 0 || p >= 3) tag = lds_u(sb + OFF_EPOCH);
      if (p >= 1 && p <= 4) {
        if (p == 1) {
#pragma unroll
          for (int h = 0; h < 2; h++) rho[h] = 0.5f * bf_lo(lds_h(sb + OFF_GS + (wg * 64 + w * 16 + gr + 8 * h) * 2));
        }
#pragma unroll
        for (int j = (p - 1) * 2; j < p * 2; j++) {
          const float2 db = lds_f2(sb + OFF_DB + j * 32 + q * 8);
#pragma unroll
          for (int h = 0; h < 2; h++) {
            const uint32_t xd = bf2_mul(lds_u(xw + 7 * 16384 + (w * 16 + gr + 8 * h) * 128 + ((j ^ gr) << 4) + q * 4), __float_as_uint(db.x));
            fin[4 * j + 2 * h] = fmaf(bf_lo(xd), rho[h], bf_lo(__float_as_uint(db.y)));
            fin[4 * j + 2 * h + 1] = fmaf(bf_hi(xd), rho[h], bf_hi(__float_as_uint(db.y)));
            pin(fin[4 * j + 2 * h]); pin(fin[4 * j + 2 * h + 1]);
          }
        }
      }
      if (p >= 3) {
        TR(3);
        recv_check(r0, p - 3);
        TR(4);
        if (p == 7) recv_check(r1, 5);
#pragma unroll
        for (int i = 0; i < 16; i++) sum[i] = p == 3 ? r0[i] : bf2_add(sum[i], p == 7 ? bf2_add(r0[i], r1[i]) : r0[i]);
      }
      if (p >= 2 && p < 7) recv_issue(r0, p - 2);
      if (p >= 1 && p < NTMA) mbar_wait(fullb + 24 + wg * 8, (p - 1) & 1);
      if (EARLYW && p < 7) mbar_wait(sb + OFF_XFULL + 8 * (p + 1), 1);
      if (!R2E && p == 7) recv_issue(r2, 6);
      TR(5);
      wg_wait<0>();
      TR(6);
      if (p < 5) release(p);
      if (p < 7) reg_fence(o); else reg_fence(fin);
      if (p < 7) send(p);
      TR(7);
      if (p == 6) recv_issue(r1, 5);
    }
    {
      float fs[2];
#pragma unroll
      for (int h = 0; h < 2; h++) fs[h] = __fdividef(1.f, 2.f + rho[h]);
#pragma unroll
      for (int i = 0; i < 16; i++) { o[2 * i] = (fin[2 * i] + bf_lo(sum[i])) * fs[i & 1]; o[2 * i + 1] = (fin[2 * i + 1] + bf_hi(sum[i])) * fs[i & 1]; }
      reg_fence(o);
      tag = lds_u(sb + OFF_EPOCH);
      recv_check(r2, 6);
      TS(wg, 16);
      const uint32_t tb = sb + OFF_RING + 3 * 16384 + warp * 4096;
      const uint32_t ta = tb + gr * 256 + ((gr & 3) << 5) + q * 8;
#pragma unroll
      for (int i = 0; i < 16; i++)
        asm volatile("st.shared.v2.f32 [%0], {%1,%2};" ::"r"((ta ^ (((i >> 1) & 3) << 5)) + (i & 1) * 2048 + (i >> 3) * 128),
                     "f"(fmaf(bf_lo(r2[i]), fs[i & 1], o[2 * i])), "f"(fmaf(bf_hi(r2[i]), fs[i & 1], o[2 * i + 1])) : "memory");
      __syncwarp();
      const uint32_t la = tb + (lane >> 3) * 256 + (((lane & 7) << 4) ^ ((lane >> 3) << 5));
      float* op = out + (size_t)(m * 128 + wg * 64 + (lane >> 4) * 16 + w * 4 + ((lane >> 3) & 1)) * DM + s * 64 + (lane & 7) * 4;
#pragma unroll
      for (int i = 0; i < 8; i++)
        *reinterpret_cast<uint4*>(op + (((i >> 1) & 1) * 32 + (i >> 2) * 2) * DM + (i & 1) * 32) = lds_u4(la + (i >> 1) * 1024 + (i & 1) * 128);
      if (threadIdx.x == 128) g_epoch[b] = tag;
      TS(wg, 17); TG(wg); TRD(); TDUMP();
    }
  } else {
    asm volatile("setmaxnreg.dec.sync.aligned.u32 56;");
    int wsel = warp;
    asm("" : "+r"(wsel));
    if (wsel > 8) {
     if (warp != 11) {
      const int t = threadIdx.x - 288;
      unsigned par;
      asm volatile("ld.relaxed.gpu.global.u32 %0, [%1];" : "=r"(par) : "l"(g_epoch + b) : "memory");
      const float pr = bf_ld(lam_re + s * 64 + t), pi = bf_ld(lam_im + s * 64 + t), pd = bf_ld(log_dt + s * 64 + t);
      asm volatile("barrier.cluster.wait.aligned;" ::: "memory");
      par = (par + 1) & 1;
      cplx l64 = make_lam(pr, pi, pd);
      {
        const float inv = __fdividef(1.f, fmaf(pr, pr, pi * pi));
        const cplx cf = cmul(cplx{l64.re - 1.f, l64.im}, cplx{pr * inv, -pi * inv});
        asm volatile("st.shared.v4.f32 [%0], {%1,%2,%3,%4};" ::"r"(sb + OFF_LC + t * 16), "f"(l64.re), "f"(l64.im), "f"(cf.re), "f"(cf.im) : "memory");
        mbar_arrive(sb + OFF_LBAR);
      }
#pragma unroll
      for (int i = 0; i < 6; i++) l64 = cmul(l64, l64);
      cplx l128 = cmul(l64, l64);
      pin(l128.re); pin(l128.im);
      mbar_wait(sb + OFF_GBAR, 0);
      const float2 e0 = lds_f2(sb + OFF_CARRY + t * 8), e1 = lds_f2(sb + OFF_CARRY + 512 + t * 8);
      float2* eb = g_end + s * 1024 + t;
      {
        const cplx e = cfma(l64, cplx{e0.x, e0.y}, cplx{e1.x, e1.y});
        const unsigned long long v = ((unsigned long long)__float_as_uint(e.im) << 32) | ((__float_as_uint(e.re) & ~1u) | par);
        asm volatile("st.relaxed.gpu.global.b64 [%0], %1;" ::"l"(eb + m * 64), "l"(v) : "memory");
      }
      if (t == 0) TS(3, 1);
      cplx S = {0.f, 0.f};
      {
        unsigned long long v[15];
        uint32_t bad;
        int tries = 0;
        const float2* e15 = eb + (m - 15) * 64;
#pragma unroll 1
        do {
#pragma unroll
          for (int i = 0; i < 15; i++) {
            v[i] = par;
            asm volatile("{.reg .pred p; setp.ge.s32 p, %2, %3; @p ld.relaxed.gpu.global.b64 %0, [%1];}" : "+l"(v[i]) : "l"(e15 + i * 64), "r"(m), "r"(15 - i) : "memory");
          }
          bad = 0;
#pragma unroll
          for (int i = 0; i < 15; i++) bad |= (uint32_t)v[i] ^ par;
        } while ((bad & 1) && ++tries < 200000);
        if (t == 0) TS(3, 2);
#pragma unroll
        for (int i = 0; i < 15; i++) S = cfma(l128, S, cplx{__uint_as_float((uint32_t)v[i] & ~1u), __uint_as_float((uint32_t)(v[i] >> 32))});
      }
      const cplx S1 = cfma(l64, S, cplx{e0.x, e0.y});
      asm volatile("st.shared.v2.f32 [%0], {%1,%2};" ::"r"(sb + OFF_CARRY + t * 8), "f"(S.re), "f"(S.im) : "memory");
      asm volatile("st.shared.v2.f32 [%0], {%1,%2};" ::"r"(sb + OFF_CARRY + 512 + t * 8), "f"(S1.re), "f"(S1.im) : "memory");
      mbar_arrive(sb + OFF_CBAR);
      if (t == 0) TS(3, 3);
      if (elect_one()) {
        const int g = warp - 9;
#pragma unroll 1
        for (int p = 0; p < NTMA; p++) {
          mbar_wait(sb + OFF_GBAR + g * 16, (p + 1) & 1);
          asm volatile("fence.proxy.async.shared::cta;" ::: "memory");
          asm volatile("cp.async.bulk.global.shared::cta.bulk_group [%0], [%1], 8192;" ::"l"(g_part + (size_t)(m * 56 + ((s + 1 + p) & 7) * 7 + p) * 1024 + g * 512),
                       "r"(sb + OFF_X + 5 * 16384 + g * 8192) : "memory");
          asm volatile("cp.async.bulk.commit_group;" ::: "memory");
          asm volatile("cp.async.bulk.wait_group.read 0;" ::: "memory");
          mbar_arrive(sb + OFF_FULL + 24 + g * 8);
        }
      }
     } else {
      if (lane == 0) TG(2);
      const uint4* gwp = reinterpret_cast<const uint4*>(gate_w) + (lane & 7);
      uint4 gw[4];
#pragma unroll
      for (int i = 0; i < 4; i++) gw[i] = __ldg(gwp + i * 8);
      unsigned par;
      asm volatile("ld.relaxed.gpu.global.u32 %0, [%1];" : "=r"(par) : "l"(g_epoch + b) : "memory");
      const uint32_t dk = __ldg(reinterpret_cast<const uint32_t*>(dskip + s * 64) + lane), bb = __ldg(reinterpret_cast<const uint32_t*>(b2 + s * 64) + lane);
      asm volatile("barrier.cluster.wait.aligned;" ::: "memory");
      const int row = s * 16 + (lane >> 3);
      const uint32_t xr0 = sb + OFF_X + row * 128 + (((lane & 7) ^ (row & 7)) << 4), xr1 = (xr0 + 512) ^ 64;
      float z[4] = {0.f, 0.f, 0.f, 0.f};
#pragma unroll
      for (int kb = 0; kb < 8; kb++) {
        const uint32_t wv[4] = {gw[kb & 3].x, gw[kb & 3].y, gw[kb & 3].z, gw[kb & 3].w};
        if (kb < 4) gw[kb] = __ldg(gwp + (kb + 4) * 8);
        mbar_wait(sb + OFF_XFULL + 8 * kb, 0);
        if ((PF & 2) && kb == PFK && elect_one()) {
          l2_prefetch(pf_w1 + b * 7168, 14336);
          l2_prefetch(pf_cre + b * 2048, 4096);
          l2_prefetch(pf_cim + b * 2048, 4096);
          l2_prefetch(pf_w2 + b * 7168, 14336);
        }
        const uint32_t xo = ((kb + xrot) & 7) * 16384;
#pragma unroll
        for (int r = 0; r < 4; r++) {
          const uint4 a = lds_u4(((r & 1) ? xr1 : xr0) + xo + (r >> 1) * 1024);
          const uint32_t p = bf2_fma(a.w, wv[3], bf2_fma(a.z, wv[2], bf2_fma(a.y, wv[1], bf2_mul(a.x, wv[0]))));
          z[r] += bf_lo(p); z[r] += bf_hi(p);
        }
      }
      if (lane == 0) asm volatile("st.shared.u32 [%0], %1;" ::"r"(sb + OFF_EPOCH), "r"(par + 1) : "memory");
      par = (par + 1) & 1;
      {
        float y0 = (lane & 4) ? z[1] : z[0], y1 = (lane & 4) ? z[3] : z[2];
        y0 += __shfl_xor_sync(0xffffffffu, (lane & 4) ? z[0] : z[1], 4);
        y1 += __shfl_xor_sync(0xffffffffu, (lane & 4) ? z[2] : z[3], 4);
        float zz = (lane & 2) ? y1 : y0;
        zz += __shfl_xor_sync(0xffffffffu, (lane & 2) ? y0 : y1, 2);
        zz += __shfl_xor_sync(0xffffffffu, zz, 1);
        const float rho = 4.f * expf(zz > 40.f ? 40.f : zz);
        if ((lane & 1) == 0)
          asm volatile("st.relaxed.gpu.global.u32 [%0], %1;" ::"l"(g_gate + m * 128 + row + (lane & 4) + (lane & 2) * 4), "r"((__float_as_uint(rho) & ~1u) | par) : "memory");
      }
      if (lane == 0) TS(3, 0);
      mbar_wait(sb + OFF_GBAR, 0);
      asm volatile("st.shared.v2.u32 [%0], {%1,%2};" ::"r"(sb + OFF_DB + lane * 8), "r"(dk), "r"(bf2_add(bb, bb)) : "memory");
      uint32_t g0, g1, g2, g3;
      int tries = 0;
#pragma unroll 1
      do {
        asm volatile("ld.relaxed.gpu.global.v4.u32 {%0,%1,%2,%3}, [%4];" : "=r"(g0), "=r"(g1), "=r"(g2), "=r"(g3) : "l"(g_gate + m * 128 + lane * 4) : "memory");
      } while ((((g0 ^ par) | (g1 ^ par) | (g2 ^ par) | (g3 ^ par)) & 1) && ++tries < 200000);
      asm volatile("st.shared.v2.u32 [%0], {%1,%2};" ::"r"(sb + OFF_GS + lane * 8), "r"(pack_bf16(__uint_as_float(g0), __uint_as_float(g1))),
                   "r"(pack_bf16(__uint_as_float(g2), __uint_as_float(g3))) : "memory");
      mbar_arrive(sb + OFF_CBAR);
      if (lane == 0) TS(3, 4);
     }
    } else {
      asm volatile("barrier.cluster.wait.aligned;" ::: "memory");
      if (elect_one()) {
        TS(2, 1);
        const CUtensorMap* mb = rank ? &maps.bim : &maps.bre;
        const uint32_t t0 = clock();
#pragma unroll 1
        for (int u = 0; u < 8; u++) {
          if (u >= DN) while ((uint32_t)clock() - t0 < D0 + (u - DN) * D1) {}
          mbar_expect_tx(sb + OFF_XFULL + 8 * u, 16384);
          tma5d(sb + OFF_X + ((u + xrot) & 7) * 16384, &maps.x, u * 64, 2 * m, sb + OFF_XFULL + 8 * u);
          if (u < 6) {
            mbar_expect_tx(sb + OFF_FULL + 8 * u, 16384);
            tma2d_mc(sb + OFF_RING + u * 16384 + rank * 8192, mb, u * 64, s * 64, sb + OFF_FULL + 8 * u);
          } else if (PF & 4) {
            asm volatile("cp.async.bulk.prefetch.tensor.2d.L2.global [%0, {%1,%2}];" ::"l"(mb), "r"(u * 64), "r"(s * 64) : "memory");
          }
        }
        TS(2, 5);
        const CUtensorMap* mc = rank ? &maps.cim : &maps.cre;
        int slot = 0; uint32_t ph = 0;
#pragma unroll 1
        for (int u = 6; u < 27; u++) {
          const uint32_t fb = sb + OFF_FULL + 8 * slot, dst = sb + OFF_RING + slot * 16384;
          mbar_wait(sb + OFF_EMPTY + 8 * slot, ph);
          TS2(0, u);
          if (u < 8) {
            mbar_expect_tx(fb, 16384);
            tma2d_mc(dst + rank * 8192, mb, u * 64, s * 64, fb);
          } else if (u < 16) {
            mbar_expect_tx(fb, 12288);
            tma3d_mc(dst + rank * 6144, &maps.w1b, 0, (u - 8) * 64 + rank * 32, s * 7, fb);
          } else if (u < 24) {
            mbar_expect_tx(fb, 16384);
            tma2d_mc(dst + rank * 8192, &maps.w1a, s * 224 + 96 + rank * 64, ((u - 15 + s) & 7) * 64, fb);
          } else if (u == 25) {
            mbar_expect_tx(fb, 16384);
            tma2d_mc(dst + rank * 8192, mc, s * 64, ((s + 1) & 7) * 64, fb);
          } else {
            mbar_expect_tx(fb, 14336);
            tma2d_mc(dst + rank * 7168, &maps.w2, ((s + 1) & 7) * 64, s * 224 + (u - 24) * 56 + rank * 56, fb);
          }
          if (++slot == NSLOT) { slot = 0; ph ^= 1; }
        }
#pragma unroll 1
        for (int p = 1; p < 8; p++) {
          const int piece = (s + 1 + p) & 7, grp = p % 3;
          const uint32_t fb = sb + OFF_XFULL + 8 * p, dst = grp == 1 ? sb + OFF_X + 2 * 16384 : sb + OFF_RING + grp * 24576;
          if (p >= 3) mbar_wait(sb + OFF_EMPTY + 8 * (p - 3), 0);
          else if (p == 2) mbar_wait(sb + OFF_EMPTY + 40, 1);
          TS2(0, 32 + p);
          mbar_expect_tx(fb, 45056);
          tma2d_mc(dst + rank * 7168, &maps.w2, piece * 64, s * 224 + rank * 56, fb);
          tma2d_mc(dst + 16384 + rank * 8192, mc, s * 64, piece * 64, fb);
          tma2d_mc(dst + 32768 + rank * 7168, &maps.w2, piece * 64, s * 224 + 112 + rank * 56, fb);
        }
        TS(2, 2);
      }
    }
  }
}

typedef CUresult (*EncFn)(CUtensorMap*, CUtensorMapDataType, cuuint32_t, void*, const cuuint64_t*, const cuuint64_t*, const cuuint32_t*,
                          const cuuint32_t*, CUtensorMapInterleave, CUtensorMapSwizzle, CUtensorMapL2promotion, CUtensorMapFloatOOBfill);

void encode(EncFn f, CUtensorMap* mp, const void* p, int rank, const cuuint64_t* dims, const cuuint64_t* strides, const cuuint32_t* box, CUtensorMapSwizzle sw) {
  cuuint32_t es[5] = {1, 1, 1, 1, 1};
  f(mp, CU_TENSOR_MAP_DATA_TYPE_BFLOAT16, rank, const_cast<void*>(p), dims, strides, box, es, CU_TENSOR_MAP_INTERLEAVE_NONE, sw,
    PROMO, CU_TENSOR_MAP_FLOAT_OOB_FILL_NONE);
}

}

extern "C" void kernel_launch(void* const* d_in, const int* in_sizes, int n_in, void* d_out, int out_size) {
  typedef const __nv_bfloat16* bp;
  bp x = (bp)d_in[0], lre = (bp)d_in[1], lim = (bp)d_in[2], bre = (bp)d_in[3], bim = (bp)d_in[4], cre = (bp)d_in[5], cim = (bp)d_in[6],
     ldt = (bp)d_in[7], dsk = (bp)d_in[8], w1 = (bp)d_in[10], b1 = (bp)d_in[11], w2 = (bp)d_in[12], b2 = (bp)d_in[13], gw = (bp)d_in[14];
  static EncFn enc = nullptr;
  if (!enc) {
    void* f = nullptr;
    cudaDriverEntryPointQueryResult qr;
    cudaGetDriverEntryPoint("cuTensorMapEncodeTiled", &f, cudaEnableDefault, &qr);
    enc = (EncFn)f;
    cudaFuncSetAttribute(fused_kernel, cudaFuncAttributeMaxDynamicSharedMemorySize, SMEM_BYTES);
  }
  Maps maps;
  {
    cuuint64_t d[5] = {DM, 2, 4, 8, SEQ / 64}, st[4] = {DM * 2, 16 * DM * 2, 2 * DM * 2, 64 * DM * 2};
    cuuint32_t bx[5] = {64, 2, 4, 8, 2};
    encode(enc, &maps.x, x, 5, d, st, bx, CU_TENSOR_MAP_SWIZZLE_128B);
  }
  {
    cuuint64_t d[2] = {DM, DM}, st[1] = {DM * 2};
    cuuint32_t bx[2] = {64, 64};
    encode(enc, &maps.bre, bre, 2, d, st, bx, CU_TENSOR_MAP_SWIZZLE_128B);
    encode(enc, &maps.bim, bim, 2, d, st, bx, CU_TENSOR_MAP_SWIZZLE_128B);
    encode(enc, &maps.cre, cre, 2, d, st, bx, CU_TENSOR_MAP_SWIZZLE_128B);
    encode(enc, &maps.cim, cim, 2, d, st, bx, CU_TENSOR_MAP_SWIZZLE_128B);
  }
  {
    cuuint64_t d[2] = {FF, DM}, st[1] = {FF * 2};
    cuuint32_t bx[2] = {64, 64};
    encode(enc, &maps.w1a, w1, 2, d, st, bx, CU_TENSOR_MAP_SWIZZLE_128B);
    cuuint64_t d3[3] = {32, DM, FF / 32}, st3[2] = {FF * 2, 64};
    cuuint32_t bx3[3] = {32, 32, 3};
    encode(enc, &maps.w1b, w1, 3, d3, st3, bx3, CU_TENSOR_MAP_SWIZZLE_64B);
  }
  {
    cuuint64_t d[2] = {DM, FF}, st[1] = {DM * 2};
    cuuint32_t bx[2] = {64, 56};
    encode(enc, &maps.w2, w2, 2, d, st, bx, CU_TENSOR_MAP_SWIZZLE_128B);
  }
  fused_kernel<<<128, 384, SMEM_BYTES>>>(lre, lim, ldt, dsk, b1, b2, gw, w1, w2, cre, cim, (float*)d_out, maps);
}
```

```cpp
#include <cuda_runtime.h>
#include <cuda_bf16.h>
#include <cuda.h>
#include <stdint.h>

#define MAP 0
#define D0 600
#define D1 500
#define PF 6
#define PFK 5
#define GELUP 0
#define TP 9
#define TW 0

namespace {

constexpr int SEQ = 2048, DM = 512, FF = 1792;
constexpr int NSLOT = 6;
constexpr uint32_t OFF_X = 0, OFF_RING = 131072, OFF_MISC = 229376;
constexpr uint32_t OFF_XFULL = OFF_MISC, OFF_FULL = OFF_XFULL + 64, OFF_RBAR = OFF_FULL + 48, OFF_EMPTY = OFF_RBAR + 16, OFF_KBAR = OFF_EMPTY + 48,
                   OFF_GBAR = OFF_KBAR + 16, OFF_LBAR = OFF_GBAR + 8, OFF_CBAR = OFF_LBAR + 8, OFF_EPOCH = OFF_CBAR + 8;
constexpr uint32_t OFF_LC = OFF_MISC + 256;
constexpr uint32_t OFF_GS = OFF_LC;
constexpr uint32_t OFF_DB = OFF_LC + 512;
constexpr uint32_t OFF_CARRY = OFF_LC + 1024;
constexpr uint32_t OFF_DBG = OFF_CARRY + 1024;
constexpr uint32_t SMEM_BYTES = OFF_DBG + 768;
static_assert(SMEM_BYTES <= 232448, "smem");

struct Maps { CUtensorMap x, bre, bim, w1b, w1a, w2, cre, cim; };

__device__ uint4 g_part[16 * 8 * 3 * 1024];
__device__ float2 g_end[8 * 16 * 64];
__device__ unsigned g_gate[SEQ];
__device__ unsigned g_epoch[128];
#define TG(role) do {} while (0)
#define TS2(role, i) do {} while (0)
#define TS(role, i) do {} while (0)
#define TDUMP() do {} while (0)
#define TR(i) do {} while (0)
#define TRD() do {} while (0)

__device__ __forceinline__ void mbar_init(uint32_t bar, uint32_t cnt) { asm volatile("mbarrier.init.shared::cta.b64 [%0], %1;" ::"r"(bar), "r"(cnt)); }
__device__ __forceinline__ void mbar_expect_tx(uint32_t bar, uint32_t bytes) { asm volatile("mbarrier.arrive.expect_tx.shared::cta.b64 _, [%0], %1;" ::"r"(bar), "r"(bytes) : "memory"); }
__device__ __forceinline__ void mbar_arrive(uint32_t bar) { asm volatile("mbarrier.arrive.shared::cta.b64 _, [%0];" ::"r"(bar) : "memory"); }
__device__ __forceinline__ void mbar_arrive_cl(uint32_t cbar) { asm volatile("mbarrier.arrive.shared::cluster.b64 _, [%0];" ::"r"(cbar) : "memory"); }
__device__ __forceinline__ void mbar_wait(uint32_t bar, uint32_t parity) {
  asm volatile(
      "{\n.reg .pred p;\n.reg .u32 c;\n"
      "mbarrier.try_wait.parity.shared::cta.b64 p, [%0], %1;\n"
      "@p bra.uni LAB_DONE;\n"
      "mov.u32 c, 0;\n"
      "LAB_WAIT:\n"
      "mbarrier.try_wait.parity.shared::cta.b64 p, [%0], %1;\n"
      "@p bra.uni LAB_DONE;\n"
      "add.u32 c, c, 1;\nsetp.lt.u32 p, c, 200000;\n@p bra.uni LAB_WAIT;\n"
      "LAB_DONE:\n}" ::"r"(bar), "r"(parity) : "memory");
}
__device__ __forceinline__ void tma2d(uint32_t dst, const CUtensorMap* m, int c0, int c1, uint32_t bar) {
  asm volatile("cp.async.bulk.tensor.2d.shared::cluster.global.mbarrier::complete_tx::bytes [%0], [%1, {%3,%4}], [%2];"
               ::"r"(dst), "l"(m), "r"(bar), "r"(c0), "r"(c1) : "memory");
}
__device__ __forceinline__ void tma3d(uint32_t dst, const CUtensorMap* m, int c0, int c1, int c2, uint32_t bar) {
  asm volatile("cp.async.bulk.tensor.3d.shared::cluster.global.mbarrier::complete_tx::bytes [%0], [%1, {%3,%4,%5}], [%2];"
               ::"r"(dst), "l"(m), "r"(bar), "r"(c0), "r"(c1), "r"(c2) : "memory");
}
__device__ __forceinline__ void tma5d_mc(uint32_t dst, const CUtensorMap* m, int c0, int c4, uint32_t bar) {
  asm volatile("cp.async.bulk.tensor.5d.shared::cluster.global.mbarrier::complete_tx::bytes.multicast::cluster [%0], [%1, {%3,%5,%5,%5,%4}], [%2], %6;"
               ::"r"(dst), "l"(m), "r"(bar), "r"(c0), "r"(c4), "r"(0), "h"((uint16_t)3) : "memory");
}
__device__ __forceinline__ void l2_prefetch(const void* p, uint32_t bytes) { asm volatile("cp.async.bulk.prefetch.L2.global [%0], %1;" ::"l"(p), "r"(bytes) : "memory"); }
__device__ __forceinline__ bool elect_one() {
  uint32_t pred;
  asm volatile("{.reg .pred P; elect.sync _|P, 0xffffffff; selp.u32 %0, 1, 0, P;}" : "=r"(pred));
  return pred != 0;
}
__device__ __forceinline__ void wg_fence() { asm volatile("wgmma.fence.sync.aligned;" ::: "memory"); }
__device__ __forceinline__ void wg_commit() { asm volatile("wgmma.commit_group.sync.aligned;" ::: "memory"); }
template <int N> __device__ __forceinline__ void wg_wait() { asm volatile("wgmma.wait_group.sync.aligned %0;" ::"n"(N) : "memory"); }
__device__ __forceinline__ void pin(float& a) { asm volatile("" : "+f"(a)::"memory"); }
__device__ __forceinline__ void pin(uint32_t& a) { asm volatile("" : "+r"(a)::"memory"); }
template <int N> __device__ __forceinline__ void reg_fence(float (&d)[N]) {
#pragma unroll
  for (int i = 0; i < N; i++) pin(d[i]);
}
__device__ __forceinline__ void bar_sync(int id, int n) { asm volatile("bar.sync %0, %1;" ::"r"(id), "r"(n) : "memory"); }
__device__ __forceinline__ void bar_arrive(int id, int n) { asm volatile("bar.arrive %0, %1;" ::"r"(id), "r"(n) : "memory"); }
constexpr uint32_t DH128 = (1024 >> 4) | (1u << 30), DH64 = (512 >> 4) | (2u << 30);
__host__ __device__ constexpr uint32_t lbo(uint32_t bytes) { return (bytes >> 4) << 20; }
__device__ __forceinline__ uint32_t pack_bf16(float lo, float hi) { uint32_t r; asm("cvt.rn.bf16x2.f32 %0, %1, %2;" : "=r"(r) : "f"(hi), "f"(lo)); return r; }
__device__ __forceinline__ float bf_lo(uint32_t v) { return __uint_as_float(v << 16); }
__device__ __forceinline__ float bf_hi(uint32_t v) { return __uint_as_float(v & 0xffff0000u); }
__device__ __forceinline__ float bf_ld(const __nv_bfloat16* p) { return __bfloat162float(__ldg(p)); }
__device__ __forceinline__ uint32_t late16(uint32_t bar) {
  uint32_t r;
  asm volatile("{.reg .pred p; mbarrier.test_wait.parity.shared::cta.b64 p, [%1], 0; selp.u32 %0, 16, 0, p;}" : "=r"(r) : "r"(bar) : "memory");
  return r;
}
__device__ __forceinline__ float2 lds_f2(uint32_t a) { float2 v; asm volatile("ld.shared.v2.f32 {%0,%1}, [%2];" : "=f"(v.x), "=f"(v.y) : "r"(a)); return v; }
__device__ __forceinline__ uint32_t lds_h(uint32_t a) { uint32_t v; asm volatile("ld.shared.u16 %0, [%1];" : "=r"(v) : "r"(a)); return v; }
__device__ __forceinline__ uint32_t lds_u(uint32_t a) { uint32_t v; asm volatile("ld.shared.u32 %0, [%1];" : "=r"(v) : "r"(a)); return v; }
__device__ __forceinline__ uint4 lds_u4(uint32_t a) { uint4 v; asm volatile("ld.shared.v4.u32 {%0,%1,%2,%3}, [%4];" : "=r"(v.x), "=r"(v.y), "=r"(v.z), "=r"(v.w) : "r"(a)); return v; }
__device__ __forceinline__ void st_b128(uint4* p, uint32_t a, uint32_t b, uint32_t c, uint32_t d) {
  asm volatile("st.relaxed.gpu.global.v4.b32 [%0], {%1,%2,%3,%4};" ::"l"(p), "r"(a), "r"(b), "r"(c), "r"(d) : "memory");
}
__device__ __forceinline__ void ld_b128(const uint4* p, uint32_t& a, uint32_t& b, uint32_t& c, uint32_t& d) {
  asm volatile("{.reg .b64 l, h; .reg .b128 v; ld.relaxed.gpu.global.b128 v, [%4]; mov.b128 {l,h}, v; mov.b64 {%0,%1}, l; mov.b64 {%2,%3}, h;}"
               : "=r"(a), "=r"(b), "=r"(c), "=r"(d) : "l"(p) : "memory");
}
__device__ __forceinline__ float tanh_fast(float x) { float y; asm("tanh.approx.f32 %0, %1;" : "=f"(y) : "f"(x)); return y; }
__device__ __forceinline__ float gelu2(float v) {
  float p = fmaf(v * v, 0.0356774081363f, 0.7978845608029f);
  return fmaf(v, tanh_fast(v * p), v);
}
__device__ __forceinline__ uint32_t bf2_mul(uint32_t a, uint32_t b) { uint32_t r; asm("mul.rn.bf16x2 %0, %1, %2;" : "=r"(r) : "r"(a), "r"(b)); return r; }
__device__ __forceinline__ uint32_t bf2_add(uint32_t a, uint32_t b) { uint32_t r; asm("add.rn.bf16x2 %0, %1, %2;" : "=r"(r) : "r"(a), "r"(b)); return r; }
__device__ __forceinline__ uint32_t bf2_fma(uint32_t a, uint32_t b, uint32_t c) { uint32_t r; asm("fma.rn.bf16x2 %0, %1, %2, %3;" : "=r"(r) : "r"(a), "r"(b), "r"(c)); return r; }
__device__ __forceinline__ uint32_t gelu2_pair(float a, float b) {
  return pack_bf16(gelu2(a), gelu2(b));
}
struct cplx { float re, im; };
__device__ __forceinline__ cplx cmul(cplx a, cplx b) { return {fmaf(a.re, b.re, -a.im * b.im), fmaf(a.re, b.im, a.im * b.re)}; }
__device__ __forceinline__ cplx cfma(cplx a, cplx b, cplx c) {
  return {fmaf(a.re, b.re, fmaf(-a.im, b.im, c.re)), fmaf(a.re, b.im, fmaf(a.im, b.re, c.im))};
}
__device__ __forceinline__ cplx make_lam(float lre, float lim, float ldt) {
  float dt = __bfloat162float(__float2bfloat16_rn(expf(ldt)));
  float mag = expf(dt * lre), sn, cs;
  sincospif(dt * lim * 0.31830988618379067f, &sn, &cs);
  return {mag * cs, mag * sn};
}

template<int TA,int TB,uint32_t AH,uint32_t BH> __device__ __forceinline__ void wgmma_n64_ss(float (&d)[32], uint32_t al, uint32_t ao, uint32_t bl, uint32_t bo, int scale_d){
  asm volatile("{.reg .pred p; .reg .b32 t, v; .reg .b64 da, db; setp.ne.b32 p, %36, 0; add.u32 t, %32, %33; mov.b64 da, {t, %39}; add.u32 v, %34, %35; mov.b64 db, {v, %40};\n"
   "wgmma.mma_async.sync.aligned.m64n64k16.f32.bf16.bf16 {%0,%1,%2,%3,%4,%5,%6,%7,%8,%9,%10,%11,%12,%13,%14,%15,%16,%17,%18,%19,%20,%21,%22,%23,%24,%25,%26,%27,%28,%29,%30,%31}, da, db, p, 1, 1, %37, %38;}"
   : "+f"(d[0]),"+f"(d[1]),"+f"(d[2]),"+f"(d[3]),"+f"(d[4]),"+f"(d[5]),"+f"(d[6]),"+f"(d[7]),"+f"(d[8]),"+f"(d[9]),"+f"(d[10]),"+f"(d[11]),"+f"(d[12]),"+f"(d[13]),"+f"(d[14]),"+f"(d[15]),"+f"(d[16]),"+f"(d[17]),"+f"(d[18]),"+f"(d[19]),"+f"(d[20]),"+f"(d[21]),"+f"(d[22]),"+f"(d[23]),"+f"(d[24]),"+f"(d[25]),"+f"(d[26]),"+f"(d[27]),"+f"(d[28]),"+f"(d[29]),"+f"(d[30]),"+f"(d[31])
   : "r"(al),"r"(ao >> 4),"r"(bl),"r"(bo >> 4),"r"(scale_d),"n"(TA),"n"(TB),"n"(AH),"n"(BH));
}
template<int TB,uint32_t BH> __device__ __forceinline__ void wgmma_n64_rs(float (&d)[32], uint32_t a0,uint32_t a1,uint32_t a2,uint32_t a3, uint32_t bl, uint32_t bo, int scale_d){
  asm volatile("{.reg .pred p; .reg .b32 t; .reg .b64 db; setp.ne.b32 p, %38, 0; add.u32 t, %36, %37; mov.b64 db, {t, %40};\n"
   "wgmma.mma_async.sync.aligned.m64n64k16.f32.bf16.bf16 {%0,%1,%2,%3,%4,%5,%6,%7,%8,%9,%10,%11,%12,%13,%14,%15,%16,%17,%18,%19,%20,%21,%22,%23,%24,%25,%26,%27,%28,%29,%30,%31}, {%32,%33,%34,%35}, db, p, 1, 1, %39;}"
   : "+f"(d[0]),"+f"(d[1]),"+f"(d[2]),"+f"(d[3]),"+f"(d[4]),"+f"(d[5]),"+f"(d[6]),"+f"(d[7]),"+f"(d[8]),"+f"(d[9]),"+f"(d[10]),"+f"(d[11]),"+f"(d[12]),"+f"(d[13]),"+f"(d[14]),"+f"(d[15]),"+f"(d[16]),"+f"(d[17]),"+f"(d[18]),"+f"(d[19]),"+f"(d[20]),"+f"(d[21]),"+f"(d[22]),"+f"(d[23]),"+f"(d[24]),"+f"(d[25]),"+f"(d[26]),"+f"(d[27]),"+f"(d[28]),"+f"(d[29]),"+f"(d[30]),"+f"(d[31])
   : "r"(a0),"r"(a1),"r"(a2),"r"(a3),"r"(bl),"r"(bo >> 4),"r"(scale_d),"n"(TB),"n"(BH));
}
template<int TA,int TB,uint32_t AH,uint32_t BH> __device__ __forceinline__ void wgmma_n96_ss(float (&d)[48], uint32_t al, uint32_t ao, uint32_t bl, uint32_t bo, int scale_d){
  asm volatile("{.reg .pred p; .reg .b32 t, v; .reg .b64 da, db; setp.ne.b32 p, %52, 0; add.u32 t, %48, %49; mov.b64 da, {t, %55}; add.u32 v, %50, %51; mov.b64 db, {v, %56};\n"
   "wgmma.mma_async.sync.aligned.m64n96k16.f32.bf16.bf16 {%0,%1,%2,%3,%4,%5,%6,%7,%8,%9,%10,%11,%12,%13,%14,%15,%16,%17,%18,%19,%20,%21,%22,%23,%24,%25,%26,%27,%28,%29,%30,%31,%32,%33,%34,%35,%36,%37,%38,%39,%40,%41,%42,%43,%44,%45,%46,%47}, da, db, p, 1, 1, %53, %54;}"
   : "+f"(d[0]),"+f"(d[1]),"+f"(d[2]),"+f"(d[3]),"+f"(d[4]),"+f"(d[5]),"+f"(d[6]),"+f"(d[7]),"+f"(d[8]),"+f"(d[9]),"+f"(d[10]),"+f"(d[11]),"+f"(d[12]),"+f"(d[13]),"+f"(d[14]),"+f"(d[15]),"+f"(d[16]),"+f"(d[17]),"+f"(d[18]),"+f"(d[19]),"+f"(d[20]),"+f"(d[21]),"+f"(d[22]),"+f"(d[23]),"+f"(d[24]),"+f"(d[25]),"+f"(d[26]),"+f"(d[27]),"+f"(d[28]),"+f"(d[29]),"+f"(d[30]),"+f"(d[31]),"+f"(d[32]),"+f"(d[33]),"+f"(d[34]),"+f"(d[35]),"+f"(d[36]),"+f"(d[37]),"+f"(d[38]),"+f"(d[39]),"+f"(d[40]),"+f"(d[41]),"+f"(d[42]),"+f"(d[43]),"+f"(d[44]),"+f"(d[45]),"+f"(d[46]),"+f"(d[47])
   : "r"(al),"r"(ao >> 4),"r"(bl),"r"(bo >> 4),"r"(scale_d),"n"(TA),"n"(TB),"n"(AH),"n"(BH));
}
template<int TA,int TB,uint32_t AH,uint32_t BH> __device__ __forceinline__ void wgmma_n128_ss(float (&d)[64], uint32_t al, uint32_t ao, uint32_t bl, uint32_t bo, int scale_d){
  asm volatile("{.reg .pred p; .reg .b32 t, v; .reg .b64 da, db; setp.ne.b32 p, %68, 0; add.u32 t, %64, %65; mov.b64 da, {t, %71}; add.u32 v, %66, %67; mov.b64 db, {v, %72};\n"
   "wgmma.mma_async.sync.aligned.m64n128k16.f32.bf16.bf16 {%0,%1,%2,%3,%4,%5,%6,%7,%8,%9,%10,%11,%12,%13,%14,%15,%16,%17,%18,%19,%20,%21,%22,%23,%24,%25,%26,%27,%28,%29,%30,%31,%32,%33,%34,%35,%36,%37,%38,%39,%40,%41,%42,%43,%44,%45,%46,%47,%48,%49,%50,%51,%52,%53,%54,%55,%56,%57,%58,%59,%60,%61,%62,%63}, da, db, p, 1, 1, %69, %70;}"
   : "+f"(d[0]),"+f"(d[1]),"+f"(d[2]),"+f"(d[3]),"+f"(d[4]),"+f"(d[5]),"+f"(d[6]),"+f"(d[7]),"+f"(d[8]),"+f"(d[9]),"+f"(d[10]),"+f"(d[11]),"+f"(d[12]),"+f"(d[13]),"+f"(d[14]),"+f"(d[15]),"+f"(d[16]),"+f"(d[17]),"+f"(d[18]),"+f"(d[19]),"+f"(d[20]),"+f"(d[21]),"+f"(d[22]),"+f"(d[23]),"+f"(d[24]),"+f"(d[25]),"+f"(d[26]),"+f"(d[27]),"+f"(d[28]),"+f"(d[29]),"+f"(d[30]),"+f"(d[31]),"+f"(d[32]),"+f"(d[33]),"+f"(d[34]),"+f"(d[35]),"+f"(d[36]),"+f"(d[37]),"+f"(d[38]),"+f"(d[39]),"+f"(d[40]),"+f"(d[41]),"+f"(d[42]),"+f"(d[43]),"+f"(d[44]),"+f"(d[45]),"+f"(d[46]),"+f"(d[47]),"+f"(d[48]),"+f"(d[49]),"+f"(d[50]),"+f"(d[51]),"+f"(d[52]),"+f"(d[53]),"+f"(d[54]),"+f"(d[55]),"+f"(d[56]),"+f"(d[57]),"+f"(d[58]),"+f"(d[59]),"+f"(d[60]),"+f"(d[61]),"+f"(d[62]),"+f"(d[63])
   : "r"(al),"r"(ao >> 4),"r"(bl),"r"(bo >> 4),"r"(scale_d),"n"(TA),"n"(TB),"n"(AH),"n"(BH));
}

__global__ void __cluster_dims__(2, 1, 1) __launch_bounds__(384, 1)
fused_kernel(const __nv_bfloat16* __restrict__ lam_re, const __nv_bfloat16* __restrict__ lam_im, const __nv_bfloat16* __restrict__ log_dt,
             const __nv_bfloat16* __restrict__ dskip, const __nv_bfloat16* __restrict__ b1, const __nv_bfloat16* __restrict__ b2,
             const __nv_bfloat16* __restrict__ gate_w, const __nv_bfloat16* __restrict__ pf_w1, const __nv_bfloat16* __restrict__ pf_w2,
             const __nv_bfloat16* __restrict__ pf_cre, const __nv_bfloat16* __restrict__ pf_cim, float* __restrict__ out,
             const __grid_constant__ Maps maps) {
  extern __shared__ __align__(1024) unsigned char smem_raw[];
  const uint32_t sb = (uint32_t)__cvta_generic_to_shared(smem_raw);
  const int b = blockIdx.x;
  const int rank = b & 1, cl = b >> 1;
  const int sp = cl & 3, m = cl >> 2;
  const int s = sp * 2 + rank;
  const int warp = __shfl_sync(0xffffffffu, (int)(threadIdx.x >> 5), 0);
  const int lane = threadIdx.x & 31;
  const int xrot = 6 - 2 * sp;

  if (elect_one()) {
    if (warp == 8) TS(2, 0);
    if (warp < 3) {
      asm volatile("prefetch.tensormap [%0];" ::"l"(&maps.x + warp) : "memory");
      mbar_init(sb + OFF_GBAR + 8 * warp, warp < 2 ? 64 : 96);
    }
    const uint32_t c = warp < 8 ? 1 : warp < 11 ? 8 : 4;
    mbar_init(sb + OFF_XFULL + 16 * warp, c);
    mbar_init(sb + OFF_XFULL + 16 * warp + 8, c);
    asm volatile("fence.mbarrier_init.release.cluster;" ::: "memory");
  }
  __syncwarp();
  asm volatile("barrier.cluster.arrive.relaxed.aligned;" ::: "memory");

  if (warp < 8) {
    const int wg = warp >> 2, w = warp & 3, q = lane & 3, gr = lane >> 2;
    uint32_t bv[28];
#pragma unroll
    for (int j = 0; j < 28; j++) bv[j] = __ldg(reinterpret_cast<const uint32_t*>(b1 + s * 224 + j * 8) + q);
    asm volatile("setmaxnreg.inc.sync.aligned.u32 224;");
    asm volatile("barrier.cluster.wait.aligned;" ::: "memory");
    TS(wg, 0);
    auto release = [&](int slot) { if (lane == 0) mbar_arrive(sb + OFF_EMPTY + 8 * slot); };
    const uint32_t xw = sb + OFF_X + wg * 8192, fullb = sb + OFF_FULL;
    const uint32_t dxw = (xw & 0x3FFFF) >> 4, dring = ((sb + OFF_RING) & 0x3FFFF) >> 4;

    float ure[32], uim[32], aa[48], ab[64];
    cplx lam[2], coef[2], l16[2], l32[2], lq[2], pre[2], e[2];
    uint32_t sh16, mhi;

#pragma unroll
    for (int kb = 0; kb < 8; kb++) {
      const int slot = kb % NSLOT;
      mbar_wait(sb + OFF_XFULL + 8 * kb, 0);
      if (kb == 0) TS(wg, 18);
      mbar_wait(fullb + 8 * slot, (kb / NSLOT) & 1);
      TS2(2, kb);
      if (kb == 0) TS(wg, 1);
      wg_fence();
      const uint32_t dxa = dxw + ((kb + xrot) & 7) * 1024;
#pragma unroll
      for (int kk = 0; kk < 4; kk++) {
        wgmma_n64_ss<0, 0, DH128, DH128>(ure, dring, slot * 16384 + kk * 32, dxa, kk * 32, (kb | kk) != 0);
        wgmma_n64_ss<0, 0, DH128, DH128>(uim, dring, slot * 16384 + 8192 + kk * 32, dxa, kk * 32, (kb | kk) != 0);
      }
      wg_commit();
      if (kb > 0) { wg_wait<1>(); release((kb - 1) % NSLOT); }
      if (kb == 1) { sh16 = late16(sb + OFF_XFULL); mhi = 0xffffffffu << sh16; }
      if (kb == 1 || (kb >= 3 && kb < 6)) {
#pragma unroll
        for (int j = 0; j < 28; j++) if (j / 7 == (kb == 1 ? 0 : kb - 2)) {
          pin(bv[j]);
          float* d = j < 12 ? aa + 4 * j : ab + 4 * (j - 12);
          d[0] = d[2] = __uint_as_float(bv[j] << sh16); d[1] = d[3] = __uint_as_float(bv[j] & mhi);
          pin(d[0]); pin(d[1]); pin(d[2]); pin(d[3]);
        }
      }
      if (kb == 5) {
        mbar_wait(sb + OFF_LBAR, 0);
#pragma unroll
        for (int h = 0; h < 2; h++) {
          const uint4 v = lds_u4(sb + OFF_LC + (w * 16 + gr + 8 * h) * 16);
          lam[h] = cplx{__uint_as_float(v.x), __uint_as_float(v.y)};
          coef[h] = cplx{__uint_as_float(v.z), __uint_as_float(v.w)};
        }
      }
      if (kb == 6) {
#pragma unroll
        for (int h = 0; h < 2; h++) {
          pin(lam[h].re); pin(lam[h].im);
          cplx t = cmul(lam[h], lam[h]); t = cmul(t, t); t = cmul(t, t);
          l16[h] = cmul(t, t);
          pin(l16[h].re); pin(l16[h].im);
        }
      }
      if (kb == 7) {
#pragma unroll
        for (int h = 0; h < 2; h++) {
          pin(l16[h].re); pin(l16[h].im);
          l32[h] = cmul(l16[h], l16[h]);
          const cplx a = (q & 1) ? l16[h] : cplx{1.f, 0.f}, c = (q & 2) ? l32[h] : cplx{1.f, 0.f};
          lq[h] = cmul(cmul(a, c), coef[h]);
          pin(lq[h].re); pin(lq[h].im);
        }
      }
    }
    TS(wg, 2);
    auto scale_u = [&](int i0, int i1) {
#pragma unroll
      for (int i = 0; i < 32; i++) if (i >= i0 && i < i1) {
        pin(ure[i]); pin(uim[i]);
        const cplx v = cmul(coef[(i >> 1) & 1], cplx{ure[i], uim[i]});
        ure[i] = v.re; uim[i] = v.im;
        pin(ure[i]); pin(uim[i]);
      }
    };
#pragma unroll
    for (int kb = 0; kb < 8; kb++) {
      const int u = 8 + kb, slot = u % NSLOT;
      mbar_wait(fullb + 8 * slot, (u / NSLOT) & 1);
      wg_fence();
      const uint32_t dxa = dxw + ((kb + xrot) & 7) * 1024;
#pragma unroll
      for (int kk = 0; kk < 4; kk++)
        wgmma_n96_ss<0, 1, DH128, DH64>(aa, dxa, kk * 32, dring, slot * 16384 + kk * 1024 + lbo(4096), 1);
      wg_commit();
      wg_wait<1>();
      release((u - 1) % NSLOT);
      if (kb == 0) {
        reg_fence(ure); reg_fence(uim);
#pragma unroll
        for (int h = 0; h < 2; h++) e[h] = cplx{ure[2 * h], uim[2 * h]};
      }
      if (kb == 0 || kb == 2 || kb == 3) {
        const int ch = kb ? kb - 1 : 0;
#pragma unroll
        for (int t = 1 + 5 * ch; t < 6 + 5 * ch; t++)
#pragma unroll
          for (int h = 0; h < 2; h++) { const int i = 4 * (t >> 1) + 2 * h + (t & 1); e[h] = cfma(lam[h], e[h], cplx{ure[i], uim[i]}); }
#pragma unroll
        for (int h = 0; h < 2; h++) { pin(e[h].re); pin(e[h].im); }
      } else if (kb == 4) {
#pragma unroll
        for (int h = 0; h < 2; h++) {
          cplx y = {__shfl_up_sync(0xffffffffu, e[h].re, 1, 4), __shfl_up_sync(0xffffffffu, e[h].im, 1, 4)};
          if (q >= 1) e[h] = cfma(l16[h], y, e[h]);
          y = cplx{__shfl_up_sync(0xffffffffu, e[h].re, 2, 4), __shfl_up_sync(0xffffffffu, e[h].im, 2, 4)};
          if (q >= 2) e[h] = cfma(l32[h], y, e[h]);
        }
        if (q == 3) {
#pragma unroll
          for (int h = 0; h < 2; h++)
            asm volatile("st.shared.v2.f32 [%0], {%1,%2};" ::"r"(sb + OFF_CARRY + wg * 512 + (w * 16 + gr + 8 * h) * 8), "f"(e[h].re), "f"(e[h].im) : "memory");
          mbar_arrive(sb + OFF_GBAR);
        }
#pragma unroll
        for (int h = 0; h < 2; h++) {
          const cplx y = {__shfl_up_sync(0xffffffffu, e[h].re, 1, 4), __shfl_up_sync(0xffffffffu, e[h].im, 1, 4)};
          pre[h] = (q >= 1) ? cmul(coef[h], y) : cplx{0.f, 0.f};
          pin(pre[h].re); pin(pre[h].im);
        }
        TS(wg, 3);
      } else if (kb > 4) {
        scale_u(kb == 5 ? 0 : kb == 6 ? 4 : 12, kb == 5 ? 4 : kb == 6 ? 12 : 20);
      }
    }
    TS(wg, 4);
    uint32_t H[56];
    cplx hst[2];
    const uint32_t hst_addr = xw + (w * 16 + (lane & 15)) * 128 + (((lane >> 4) ^ (lane & 7)) << 4);
    uint32_t peer;
    asm volatile("mapa.shared::cluster.u32 %0, %1, %2;" : "=r"(peer) : "r"(sb), "r"(rank ^ 1));
    auto credit = [&]() { if (lane == 0) mbar_arrive_cl(peer + OFF_KBAR + wg * 8); };
#pragma unroll
    for (int kb = 0; kb < 8; kb++) {
      const int u = 16 + kb, slot = u % NSLOT;
      mbar_wait(fullb + 8 * slot, (u / NSLOT) & 1);
      wg_fence();
#pragma unroll
      for (int kk = 0; kk < 4; kk++)
        wgmma_n128_ss<0, 1, DH128, DH128>(ab, dxw, kb * 16384 + kk * 32, dring, slot * 16384 + kk * 2048 + lbo(8192), 1);
      wg_commit();
      wg_wait<1>();
      release((u - 1) % NSLOT);
      if (kb == 6) credit();
      if (kb == 0) scale_u(20, 32);
      if (kb < 5 && kb != 1) {
        const int ch = kb ? kb - 1 : 0;
#pragma unroll
        for (int i = ch * 6; i < ch * 6 + 6; i++) {
          pin(aa[2 * i]); pin(aa[2 * i + 1]);
          H[i] = gelu2_pair(aa[2 * i], aa[2 * i + 1]);
          pin(H[i]);
        }
      }
      if (kb >= 4) {
        if (kb == 4) {
          TS(wg, 5);
          mbar_wait(sb + OFF_CBAR, 0);
          TS(wg, 6);
#pragma unroll
          for (int h = 0; h < 2; h++) {
            const float2 c = lds_f2(sb + OFF_CARRY + wg * 512 + (w * 16 + gr + 8 * h) * 8);
            hst[h] = cfma(lq[h], cplx{c.x, c.y}, pre[h]);
          }
        }
        const int j0 = (kb - 4) * 2;
        uint32_t rr[4], ri[4];
#pragma unroll
        for (int jj = 0; jj < 2; jj++) {
          const int j = j0 + jj;
          const uint32_t g2 = lds_u(sb + OFF_GS + (wg * 64 + j * 8 + q * 2) * 2);
#pragma unroll
          for (int h = 0; h < 2; h++) {
            const int i = 4 * j + 2 * h;
            const cplx h0 = cfma(lam[h], hst[h], cplx{ure[i], uim[i]});
            hst[h] = cfma(lam[h], h0, cplx{ure[i + 1], uim[i + 1]});
            rr[jj * 2 + h] = bf2_mul(pack_bf16(h0.re, hst[h].re), g2);
            ri[jj * 2 + h] = bf2_mul(pack_bf16(h0.im, hst[h].im), g2 ^ 0x80008000u);
          }
        }
        const uint32_t a = hst_addr ^ (j0 << 4);
        asm volatile("stmatrix.sync.aligned.m8n8.x4.shared.b16 [%0], {%1,%2,%3,%4};" ::"r"(a), "r"(rr[0]), "r"(rr[1]), "r"(rr[2]), "r"(rr[3]) : "memory");
        asm volatile("stmatrix.sync.aligned.m8n8.x4.shared.b16 [%0], {%1,%2,%3,%4};" ::"r"(a + 16384), "r"(ri[0]), "r"(ri[1]), "r"(ri[2]), "r"(ri[3]) : "memory");
      }
    }
    TS(wg, 7);

    uint4* const psend = g_part + (size_t)(m * 8 + rank) * 3072 + warp * 128 + lane;
    const uint4* const precv = g_part + (size_t)(m * 8 + s) * 3072 + warp * 128 + lane;
    const uint32_t pbuf = OFF_X + 5 * 16384 + warp * 2048 + lane * 16;
    const uint32_t dx0 = ((sb + OFF_X) & 0x3FFFF) >> 4;
    float o[32], fin[32], rho[2];
    uint32_t tr[8];
    uint32_t r0[16], pt[16], sum[16], tag;
    auto recv_issue = [&](uint32_t (&r)[16], int k) {
#pragma unroll
      for (int i = 0; i < 4; i++) ld_b128(precv + k * 1024 + i * 32, r[4 * i], r[4 * i + 1], r[4 * i + 2], r[4 * i + 3]);
    };
    auto stale = [&](uint32_t (&r)[16]) {
      uint32_t t0, t1, r_;
      asm("lop3.b32 %0, %1, %2, %3, 0x7e;" : "=r"(t0) : "r"(r[0]), "r"(r[4]), "r"(tag));
      asm("lop3.b32 %0, %1, %2, %3, 0x7e;" : "=r"(t1) : "r"(r[8]), "r"(r[12]), "r"(tag));
      asm volatile("{.reg .pred p; .reg .b32 t; lop3.b32 t, %1, %2, 1, 0xa8; setp.ne.u32 p, t, 0; vote.sync.any.pred p, p, 0xffffffff; selp.u32 %0, 1, 0, p;}" : "=r"(r_) : "r"(t0), "r"(t1));
      return r_ != 0;
    };
    auto recv_check = [&](uint32_t (&r)[16], int k) {
      if (__builtin_expect(stale(r), 0)) {
        int tries = 0;
#pragma unroll 1
        do { recv_issue(r, k); } while (stale(r) && ++tries < 200000);
      }
    };
    auto gelu_b = [&](int i0, int i1) {
#pragma unroll
      for (int i = i0; i < i1; i++) {
        pin(ab[2 * i]); pin(ab[2 * i + 1]);
        H[24 + i] = gelu2_pair(ab[2 * i], ab[2 * i + 1]);
        pin(H[24 + i]);
      }
    };
    auto mma = [&](float (&o)[32], uint32_t wo, int k0, int k1, int acc) {
      wg_fence();
#pragma unroll
      for (int k = k0; k < k1; k++) {
        if (k >= 6 && k < 14) {
          const int kk = k - 6;
          wgmma_n64_ss<1, 0, DH128, DH128>(o, dxw, (kk >> 2) * 16384 + (kk & 3) * 2048, dx0, wo + 16384 + (kk >> 2) * 8192 + (kk & 3) * 32, 1);
        } else {
          const int kk = k < 6 ? k : k - 8;
          wgmma_n64_rs<1, DH128>(o, H[4 * kk], H[4 * kk + 1], H[4 * kk + 2], H[4 * kk + 3], dx0, wo + (kk / 7) * 32768 + (kk % 7) * 2048, k != 0 || acc);
        }
      }
      wg_commit();
    };
#pragma unroll
    for (int p = 0; p < 8; p++) {
      const uint32_t wo = (p % 3) == 1 ? 2 * 16384 : OFF_RING + (p % 3) * 24576;
      if (p == 0) {
        mbar_wait(fullb, 0);
        mma(o, wo, 0, 3, 0);
        asm volatile("fence.proxy.async.shared::cta;" ::: "memory");
        wg_wait<1>(); release(5);
        gelu_b(0, 4);
        mma(o, wo, 3, 6, 0);
        gelu_b(4, 10);
        bar_sync(1 + wg, 128);
        mbar_wait(fullb + 8, 0);
        mma(o, wo, 6, 10, 0);
        gelu_b(10, 16);
        mma(o, wo, 10, 15, 0);
        gelu_b(16, 24);
        mbar_wait(fullb + 16, 0);
        mma(o, wo, 15, 18, 0);
        gelu_b(24, 32);
        if (wg == 1) bar_sync(4, 256);
        mma(o, wo, 18, 22, 0);
      } else {
        TR(0);
        mbar_wait(sb + OFF_XFULL + 8 * p, 1);
        TR(1);
        bar_sync(3 + wg, 256);
        if (p < 7) mma(o, wo, 0, 22, 0); else mma(fin, wo, 0, 22, 1);
      }
      if (p < 7 || wg == 0) bar_arrive(4 - wg, 256);
      TR(2);
      if (p != TP) TS(wg, 8 + p);
      if ((p & 1) == 0) {
        if ((threadIdx.x & 127) == 0) mbar_expect_tx(sb + OFF_RBAR + wg * 8, 8192);
        if (p == 2 || p == 4) {
          if (p == 2) {
#pragma unroll
            for (int h = 0; h < 2; h++) rho[h] = 0.5f * bf_lo(lds_h(sb + OFF_GS + (wg * 64 + w * 16 + gr + 8 * h) * 2));
          }
#pragma unroll
          for (int j = (p - 2) * 2; j < p * 2; j++) {
            const float2 db = lds_f2(sb + OFF_DB + j * 32 + q * 8);
#pragma unroll
            for (int h = 0; h < 2; h++) {
              const uint32_t xd = bf2_mul(lds_u(xw + (6 + rank) * 16384 + (w * 16 + gr + 8 * h) * 128 + ((j ^ gr) << 4) + q * 4), __float_as_uint(db.x));
              fin[4 * j + 2 * h] = fmaf(bf_lo(xd), rho[h], bf_lo(__float_as_uint(db.y)));
              fin[4 * j + 2 * h + 1] = fmaf(bf_hi(xd), rho[h], bf_hi(__float_as_uint(db.y)));
              pin(fin[4 * j + 2 * h]); pin(fin[4 * j + 2 * h + 1]);
            }
          }
        }
        if (p == 6) {
          tag = lds_u(sb + OFF_EPOCH);
          recv_check(sum, 0); recv_check(r0, 1);
#pragma unroll
          for (int i = 0; i < 16; i++) sum[i] = bf2_add(sum[i], r0[i]);
        }
        mbar_wait(sb + OFF_KBAR + wg * 8, (p >> 1) & 1);
      } else {
        if (p == 1 || p == 7) tag = lds_u(sb + OFF_EPOCH);
        if (p == 5) { recv_issue(sum, 0); recv_issue(r0, 1); }
        mbar_wait(sb + OFF_RBAR + wg * 8, (p >> 1) & 1);
#pragma unroll
        for (int i = 0; i < 4; i++) { const uint4 v = lds_u4(sb + pbuf + i * 512); pt[4 * i] = v.x; pt[4 * i + 1] = v.y; pt[4 * i + 2] = v.z; pt[4 * i + 3] = v.w; }
        if (p == 7) {
          recv_check(r0, 2);
#pragma unroll
          for (int i = 0; i < 16; i++) sum[i] = bf2_add(sum[i], bf2_add(r0[i], pt[i]));
        }
      }
      TR(5);
      wg_wait<0>();
      TR(6);
      if (p < 5) release(p);
      if (p < 7) reg_fence(o); else reg_fence(fin);
      if ((p & 1) == 0) {
#pragma unroll
        for (int i = 0; i < 4; i++)
          asm volatile("st.async.shared::cluster.mbarrier::complete_tx::bytes.v4.b32 [%0], {%1,%2,%3,%4}, [%5];" ::"r"(peer + pbuf + i * 512),
                       "r"(pack_bf16(o[8 * i], o[8 * i + 1])), "r"(pack_bf16(o[8 * i + 2], o[8 * i + 3])), "r"(pack_bf16(o[8 * i + 4], o[8 * i + 5])),
                       "r"(pack_bf16(o[8 * i + 6], o[8 * i + 7])), "r"(peer + OFF_RBAR + wg * 8) : "memory");
        if (p == 6) recv_issue(r0, 2);
      } else if (p < 7) {
#pragma unroll
        for (int i = 0; i < 16; i++) pt[i] = bf2_add(pt[i], pack_bf16(o[2 * i], o[2 * i + 1]));
        __syncwarp();
        credit();
#pragma unroll
        for (int i = 0; i < 4; i++) {
          uint32_t t0;
          asm("lop3.b32 %0, %1, 1, %2, 0xb8;" : "=r"(t0) : "r"(pt[4 * i]), "r"(tag));
          st_b128(psend + (((sp + 1 + (p >> 1)) & 3) * 6 + (p >> 1)) * 1024 + i * 32, t0, pt[4 * i + 1], pt[4 * i + 2], pt[4 * i + 3]);
        }
      }
      TR(7);
    }
    {
      TS(wg, 16);
      float fs[2];
#pragma unroll
      for (int h = 0; h < 2; h++) fs[h] = __fdividef(1.f, 2.f + rho[h]);
      const uint32_t tb = sb + OFF_RING + 3 * 16384 + warp * 4096;
      const uint32_t ta = tb + gr * 256 + ((gr & 3) << 5) + q * 8;
#pragma unroll
      for (int i = 0; i < 16; i++)
        asm volatile("st.shared.v2.f32 [%0], {%1,%2};" ::"r"((ta ^ (((i >> 1) & 3) << 5)) + (i & 1) * 2048 + (i >> 3) * 128),
                     "f"((fin[2 * i] + bf_lo(sum[i])) * fs[i & 1]), "f"((fin[2 * i + 1] + bf_hi(sum[i])) * fs[i & 1]) : "memory");
      __syncwarp();
      const uint32_t la = tb + (lane >> 3) * 256 + (((lane & 7) << 4) ^ ((lane >> 3) << 5));
      float* op = out + (size_t)(m * 128 + wg * 64 + (lane >> 4) * 16 + w * 4 + ((lane >> 3) & 1)) * DM + s * 64 + (lane & 7) * 4;
#pragma unroll
      for (int i = 0; i < 8; i++)
        *reinterpret_cast<uint4*>(op + (((i >> 1) & 1) * 32 + (i >> 2) * 2) * DM + (i & 1) * 32) = lds_u4(la + (i >> 1) * 1024 + (i & 1) * 128);
      if (threadIdx.x == 128) g_epoch[b] = tag;
      TS(wg, 17); TG(wg); TRD(); TDUMP();
    }
  } else {
    asm volatile("setmaxnreg.dec.sync.aligned.u32 56;");
    int wsel = warp;
    asm("" : "+r"(wsel));
    if (wsel > 8) {
      if (warp != 11) {
        const int t = threadIdx.x - 288;
        unsigned par;
        asm volatile("ld.relaxed.gpu.global.u32 %0, [%1];" : "=r"(par) : "l"(g_epoch + b) : "memory");
        const float pr = bf_ld(lam_re + s * 64 + t), pi = bf_ld(lam_im + s * 64 + t), pd = bf_ld(log_dt + s * 64 + t);
        asm volatile("barrier.cluster.wait.aligned;" ::: "memory");
        par = (par + 1) & 1;
        cplx l64 = make_lam(pr, pi, pd);
        {
          const float inv = __fdividef(1.f, fmaf(pr, pr, pi * pi));
          const cplx cf = cmul(cplx{l64.re - 1.f, l64.im}, cplx{pr * inv, -pi * inv});
          asm volatile("st.shared.v4.f32 [%0], {%1,%2,%3,%4};" ::"r"(sb + OFF_LC + t * 16), "f"(l64.re), "f"(l64.im), "f"(cf.re), "f"(cf.im) : "memory");
          mbar_arrive(sb + OFF_LBAR);
        }
#pragma unroll
        for (int i = 0; i < 6; i++) l64 = cmul(l64, l64);
        cplx l128 = cmul(l64, l64);
        pin(l128.re); pin(l128.im);
        mbar_wait(sb + OFF_GBAR, 0);
        const float2 e0 = lds_f2(sb + OFF_CARRY + t * 8), e1 = lds_f2(sb + OFF_CARRY + 512 + t * 8);
        float2* eb = g_end + s * 1024 + t;
        {
          const cplx e = cfma(l64, cplx{e0.x, e0.y}, cplx{e1.x, e1.y});
          const unsigned long long v = ((unsigned long long)__float_as_uint(e.im) << 32) | ((__float_as_uint(e.re) & ~1u) | par);
          asm volatile("st.relaxed.gpu.global.b64 [%0], %1;" ::"l"(eb + m * 64), "l"(v) : "memory");
        }
        if (t == 0) TS(3, 1);
        cplx S = {0.f, 0.f};
        {
          unsigned long long v[15];
          uint32_t bad;
          int tries = 0;
          const float2* e15 = eb + (m - 15) * 64;
#pragma unroll 1
          do {
#pragma unroll
            for (int i = 0; i < 15; i++) {
              v[i] = par;
              asm volatile("{.reg .pred p; setp.ge.s32 p, %2, %3; @p ld.relaxed.gpu.global.b64 %0, [%1];}" : "+l"(v[i]) : "l"(e15 + i * 64), "r"(m), "r"(15 - i) : "memory");
            }
            bad = 0;
#pragma unroll
            for (int i = 0; i < 15; i++) bad |= (uint32_t)v[i] ^ par;
          } while ((bad & 1) && ++tries < 200000);
          if (t == 0) TS(3, 2);
#pragma unroll
          for (int i = 0; i < 15; i++) S = cfma(l128, S, cplx{__uint_as_float((uint32_t)v[i] & ~1u), __uint_as_float((uint32_t)(v[i] >> 32))});
        }
        const cplx S1 = cfma(l64, S, cplx{e0.x, e0.y});
        asm volatile("st.shared.v2.f32 [%0], {%1,%2};" ::"r"(sb + OFF_CARRY + t * 8), "f"(S.re), "f"(S.im) : "memory");
        asm volatile("st.shared.v2.f32 [%0], {%1,%2};" ::"r"(sb + OFF_CARRY + 512 + t * 8), "f"(S1.re), "f"(S1.im) : "memory");
        mbar_arrive(sb + OFF_CBAR);
        if (t == 0) TS(3, 3);
      } else {
        if (lane == 0) TG(2);
        const uint4* gwp = reinterpret_cast<const uint4*>(gate_w) + (lane & 7);
        uint4 gw[4];
#pragma unroll
        for (int i = 0; i < 4; i++) gw[i] = __ldg(gwp + i * 8);
        unsigned par;
        asm volatile("ld.relaxed.gpu.global.u32 %0, [%1];" : "=r"(par) : "l"(g_epoch + b) : "memory");
        const uint32_t dk = __ldg(reinterpret_cast<const uint32_t*>(dskip + s * 64) + lane), bb = __ldg(reinterpret_cast<const uint32_t*>(b2 + s * 64) + lane);
        asm volatile("barrier.cluster.wait.aligned;" ::: "memory");
        const int row = s * 16 + (lane >> 3);
        const uint32_t xr0 = sb + OFF_X + row * 128 + (((lane & 7) ^ (row & 7)) << 4), xr1 = (xr0 + 512) ^ 64;
        float z[4] = {0.f, 0.f, 0.f, 0.f};
#pragma unroll
        for (int kb = 0; kb < 8; kb++) {
          const uint32_t wv[4] = {gw[kb & 3].x, gw[kb & 3].y, gw[kb & 3].z, gw[kb & 3].w};
          if (kb < 4) gw[kb] = __ldg(gwp + (kb + 4) * 8);
          mbar_wait(sb + OFF_XFULL + 8 * kb, 0);
          if ((PF & 2) && kb == PFK && elect_one()) {
            l2_prefetch(pf_w1 + b * 7168, 14336);
            l2_prefetch(pf_cre + b * 2048, 4096);
            l2_prefetch(pf_cim + b * 2048, 4096);
            l2_prefetch(pf_w2 + b * 7168, 14336);
          }
          const uint32_t xo = ((kb + xrot) & 7) * 16384;
#pragma unroll
          for (int r = 0; r < 4; r++) {
            const uint4 a = lds_u4(((r & 1) ? xr1 : xr0) + xo + (r >> 1) * 1024);
            const uint32_t p = bf2_fma(a.w, wv[3], bf2_fma(a.z, wv[2], bf2_fma(a.y, wv[1], bf2_mul(a.x, wv[0]))));
            z[r] += bf_lo(p); z[r] += bf_hi(p);
          }
        }
        if (lane == 0) asm volatile("st.shared.u32 [%0], %1;" ::"r"(sb + OFF_EPOCH), "r"(par + 1) : "memory");
        par = (par + 1) & 1;
        {
          float y0 = (lane & 4) ? z[1] : z[0], y1 = (lane & 4) ? z[3] : z[2];
          y0 += __shfl_xor_sync(0xffffffffu, (lane & 4) ? z[0] : z[1], 4);
          y1 += __shfl_xor_sync(0xffffffffu, (lane & 4) ? z[2] : z[3], 4);
          float zz = (lane & 2) ? y1 : y0;
          zz += __shfl_xor_sync(0xffffffffu, (lane & 2) ? y0 : y1, 2);
          zz += __shfl_xor_sync(0xffffffffu, zz, 1);
          const float rho = 4.f * expf(zz > 40.f ? 40.f : zz);
          if ((lane & 1) == 0)
            asm volatile("st.relaxed.gpu.global.u32 [%0], %1;" ::"l"(g_gate + m * 128 + row + (lane & 4) + (lane & 2) * 4), "r"((__float_as_uint(rho) & ~1u) | par) : "memory");
        }
        if (lane == 0) TS(3, 0);
        mbar_wait(sb + OFF_GBAR, 0);
        asm volatile("st.shared.v2.u32 [%0], {%1,%2};" ::"r"(sb + OFF_DB + lane * 8), "r"(dk), "r"(bf2_add(bb, bb)) : "memory");
        uint32_t g0, g1, g2, g3;
        int tries = 0;
#pragma unroll 1
        do {
          asm volatile("ld.relaxed.gpu.global.v4.u32 {%0,%1,%2,%3}, [%4];" : "=r"(g0), "=r"(g1), "=r"(g2), "=r"(g3) : "l"(g_gate + m * 128 + lane * 4) : "memory");
        } while ((((g0 ^ par) | (g1 ^ par) | (g2 ^ par) | (g3 ^ par)) & 1) && ++tries < 200000);
        asm volatile("st.shared.v2.u32 [%0], {%1,%2};" ::"r"(sb + OFF_GS + lane * 8), "r"(pack_bf16(__uint_as_float(g0), __uint_as_float(g1))),
                     "r"(pack_bf16(__uint_as_float(g2), __uint_as_float(g3))) : "memory");
        mbar_arrive(sb + OFF_CBAR);
        if (lane == 0) TS(3, 4);
      }
    } else {
      asm volatile("barrier.cluster.wait.aligned;" ::: "memory");
      if (elect_one()) {
        TS(2, 1);
        const uint32_t t0 = clock();
#pragma unroll 1
        for (int u = 0; u < 8; u++) {
          if (u >= 1) while ((uint32_t)clock() - t0 < D0 + (u - 1) * D1) {}
          mbar_expect_tx(sb + OFF_XFULL + 8 * u, 16384);
          tma5d_mc(sb + OFF_X + ((u + xrot) & 7) * 16384 + rank * 8192, &maps.x, u * 64, 2 * m + rank, sb + OFF_XFULL + 8 * u);
          if (u < 6) {
            mbar_expect_tx(sb + OFF_FULL + 8 * u, 16384);
            tma2d(sb + OFF_RING + u * 16384, &maps.bre, u * 64, s * 64, sb + OFF_FULL + 8 * u);
            tma2d(sb + OFF_RING + u * 16384 + 8192, &maps.bim, u * 64, s * 64, sb + OFF_FULL + 8 * u);
          } else if (PF & 4) {
            asm volatile("cp.async.bulk.prefetch.tensor.2d.L2.global [%0, {%1,%2}];" ::"l"((m & 1) ? &maps.bim : &maps.bre), "r"(u * 64), "r"(s * 64) : "memory");
          }
        }
        TS(2, 5);
        const int piece0 = ((sp + 1) & 3) * 2 + (rank ^ 1);
        int slot = 0; uint32_t ph = 0;
#pragma unroll 1
        for (int u = 6; u < 27; u++) {
          const uint32_t fb = sb + OFF_FULL + 8 * slot, dst = sb + OFF_RING + slot * 16384;
          mbar_wait(sb + OFF_EMPTY + 8 * slot, ph);
          TS2(0, u);
          if (u < 8) {
            mbar_expect_tx(fb, 16384);
            tma2d(dst, &maps.bre, u * 64, s * 64, fb);
            tma2d(dst + 8192, &maps.bim, u * 64, s * 64, fb);
          } else if (u < 16) {
            mbar_expect_tx(fb, 12288);
            tma3d(dst, &maps.w1b, 0, (u - 8) * 64, s * 7, fb);
          } else if (u < 24) {
            mbar_expect_tx(fb, 16384);
            tma2d(dst, &maps.w1a, s * 224 + 96, ((u - xrot) & 7) * 64, fb);
            tma2d(dst + 8192, &maps.w1a, s * 224 + 160, ((u - xrot) & 7) * 64, fb);
          } else if (u == 25) {
            mbar_expect_tx(fb, 16384);
            tma2d(dst, &maps.cre, s * 64, piece0 * 64, fb);
            tma2d(dst + 8192, &maps.cim, s * 64, piece0 * 64, fb);
          } else {
            mbar_expect_tx(fb, 14336);
            tma2d(dst, &maps.w2, piece0 * 64, s * 224 + (u - 24) * 56, fb);
          }
          if (++slot == NSLOT) { slot = 0; ph ^= 1; }
        }
#pragma unroll 1
        for (int p = 1; p < 8; p++) {
          const int piece = ((sp + 1 + (p >> 1)) & 3) * 2 + ((rank ^ p ^ 1) & 1), grp = p % 3;
          const uint32_t fb = sb + OFF_XFULL + 8 * p, dst = grp == 1 ? sb + OFF_X + 2 * 16384 : sb + OFF_RING + grp * 24576;
          if (p >= 3) mbar_wait(sb + OFF_EMPTY + 8 * (p - 3), 0);
          else if (p == 2) mbar_wait(sb + OFF_EMPTY + 40, 1);
          TS2(0, 32 + p);
          mbar_expect_tx(fb, 45056);
          tma2d(dst, &maps.w2, piece * 64, s * 224, fb);
          tma2d(dst + 16384, &maps.cre, s * 64, piece * 64, fb);
          tma2d(dst + 24576, &maps.cim, s * 64, piece * 64, fb);
          tma2d(dst + 32768, &maps.w2, piece * 64, s * 224 + 112, fb);
        }
        TS(2, 2);
      }
    }
  }
}

typedef CUresult (*EncFn)(CUtensorMap*, CUtensorMapDataType, cuuint32_t, void*, const cuuint64_t*, const cuuint64_t*, const cuuint32_t*,
                          const cuuint32_t*, CUtensorMapInterleave, CUtensorMapSwizzle, CUtensorMapL2promotion, CUtensorMapFloatOOBfill);

void encode(EncFn f, CUtensorMap* mp, const void* p, int rank, const cuuint64_t* dims, const cuuint64_t* strides, const cuuint32_t* box, CUtensorMapSwizzle sw) {
  cuuint32_t es[5] = {1, 1, 1, 1, 1};
  f(mp, CU_TENSOR_MAP_DATA_TYPE_BFLOAT16, rank, const_cast<void*>(p), dims, strides, box, es, CU_TENSOR_MAP_INTERLEAVE_NONE, sw,
    CU_TENSOR_MAP_L2_PROMOTION_L2_128B, CU_TENSOR_MAP_FLOAT_OOB_FILL_NONE);
}

}

extern "C" void kernel_launch(void* const* d_in, const int* in_sizes, int n_in, void* d_out, int out_size) {
  typedef const __nv_bfloat16* bp;
  bp x = (bp)d_in[0], lre = (bp)d_in[1], lim = (bp)d_in[2], bre = (bp)d_in[3], bim = (bp)d_in[4], cre = (bp)d_in[5], cim = (bp)d_in[6],
     ldt = (bp)d_in[7], dsk = (bp)d_in[8], w1 = (bp)d_in[10], b1 = (bp)d_in[11], w2 = (bp)d_in[12], b2 = (bp)d_in[13], gw = (bp)d_in[14];
  static EncFn enc = nullptr;
  if (!enc) {
    void* f = nullptr;
    cudaDriverEntryPointQueryResult qr;
    cudaGetDriverEntryPoint("cuTensorMapEncodeTiled", &f, cudaEnableDefault, &qr);
    enc = (EncFn)f;
    cudaFuncSetAttribute(fused_kernel, cudaFuncAttributeMaxDynamicSharedMemorySize, SMEM_BYTES);
  }
  Maps maps;
  {
    cuuint64_t d[5] = {DM, 2, 4, 8, SEQ / 64}, st[4] = {DM * 2, 16 * DM * 2, 2 * DM * 2, 64 * DM * 2};
    cuuint32_t bx[5] = {64, 2, 4, 8, 1};
    encode(enc, &maps.x, x, 5, d, st, bx, CU_TENSOR_MAP_SWIZZLE_128B);
  }
  {
    cuuint64_t d[2] = {DM, DM}, st[1] = {DM * 2};
    cuuint32_t bx[2] = {64, 64};
    encode(enc, &maps.bre, bre, 2, d, st, bx, CU_TENSOR_MAP_SWIZZLE_128B);
    encode(enc, &maps.bim, bim, 2, d, st, bx, CU_TENSOR_MAP_SWIZZLE_128B);
    encode(enc, &maps.cre, cre, 2, d, st, bx, CU_TENSOR_MAP_SWIZZLE_128B);
    encode(enc, &maps.cim, cim, 2, d, st, bx, CU_TENSOR_MAP_SWIZZLE_128B);
  }
  {
    cuuint64_t d[2] = {FF, DM}, st[1] = {FF * 2};
    cuuint32_t bx[2] = {64, 64};
    encode(enc, &maps.w1a, w1, 2, d, st, bx, CU_TENSOR_MAP_SWIZZLE_128B);
    cuuint64_t d3[3] = {32, DM, FF / 32}, st3[2] = {FF * 2, 64};
    cuuint32_t bx3[3] = {32, 64, 3};
    encode(enc, &maps.w1b, w1, 3, d3, st3, bx3, CU_TENSOR_MAP_SWIZZLE_64B);
  }
  {
    cuuint64_t d[2] = {DM, FF}, st[1] = {DM * 2};
    cuuint32_t bx[2] = {64, 112};
    encode(enc, &maps.w2, w2, 2, d, st, bx, CU_TENSOR_MAP_SWIZZLE_128B);
  }
  fused_kernel<<<128, 384, SMEM_BYTES>>>(lre, lim, ldt, dsk, b1, b2, gw, w1, w2, cre, cim, (float*)d_out, maps);
}
```

```cpp
#include <cuda_runtime.h>
#include <cuda_bf16.h>
#include <cuda.h>
#include <stdint.h>

#define MAP 1
#define D0 600
#define D1 500
#define PF 6
#define PFK 5
#define GELUP 0
#define EW 1
#define K1E 0
#define K2E 0
#define QS 1
#define TP 9
#define TW 0

namespace {

constexpr int SEQ = 2048, DM = 512, FF = 1792;
constexpr int NSLOT = 6;
constexpr uint32_t OFF_X = 0, OFF_RING = 131072, OFF_MISC = 229376;
constexpr uint32_t OFF_XFULL = OFF_MISC, OFF_FULL = OFF_XFULL + 64, OFF_RBAR = OFF_FULL + 48, OFF_EMPTY = OFF_RBAR + 16, OFF_KBAR = OFF_EMPTY + 48,
                   OFF_GBAR = OFF_KBAR + 16, OFF_LBAR = OFF_GBAR + 8, OFF_CBAR = OFF_LBAR + 8, OFF_EPOCH = OFF_CBAR + 8;
constexpr uint32_t OFF_LC = OFF_MISC + 256;
constexpr uint32_t OFF_GS = OFF_LC;
constexpr uint32_t OFF_DB = OFF_LC + 512;
constexpr uint32_t OFF_CARRY = OFF_LC + 1024;
constexpr uint32_t OFF_DBG = OFF_CARRY + 1024;
constexpr uint32_t SMEM_BYTES = OFF_DBG + 768;
static_assert(SMEM_BYTES <= 232448, "smem");

struct Maps { CUtensorMap x, bre, bim, w1b, w1a, w2, cre, cim; };

__device__ uint4 g_part[16 * 8 * 3 * 1024];
__device__ float2 g_end[8 * 16 * 64];
__device__ unsigned g_gate[SEQ];
__device__ unsigned g_epoch[128];
#define TG(role) do {} while (0)
#define TS2(role, i) do {} while (0)
#define TS(role, i) do {} while (0)
#define TDUMP() do {} while (0)
#define TR(i) do {} while (0)
#define TRD() do {} while (0)

__device__ __forceinline__ void mbar_init(uint32_t bar, uint32_t cnt) { asm volatile("mbarrier.init.shared::cta.b64 [%0], %1;" ::"r"(bar), "r"(cnt)); }
__device__ __forceinline__ void mbar_expect_tx(uint32_t bar, uint32_t bytes) { asm volatile("mbarrier.arrive.expect_tx.shared::cta.b64 _, [%0], %1;" ::"r"(bar), "r"(bytes) : "memory"); }
__device__ __forceinline__ void mbar_arrive(uint32_t bar) { asm volatile("mbarrier.arrive.shared::cta.b64 _, [%0];" ::"r"(bar) : "memory"); }
__device__ __forceinline__ void mbar_arrive_cl(uint32_t cbar) { asm volatile("mbarrier.arrive.shared::cluster.b64 _, [%0];" ::"r"(cbar) : "memory"); }
__device__ __forceinline__ void mbar_wait(uint32_t bar, uint32_t parity) {
  asm volatile(
      "{\n.reg .pred p;\n.reg .u32 c;\n"
      "mbarrier.try_wait.parity.shared::cta.b64 p, [%0], %1;\n"
      "@p bra.uni LAB_DONE;\n"
      "mov.u32 c, 0;\n"
      "LAB_WAIT:\n"
      "mbarrier.try_wait.parity.shared::cta.b64 p, [%0], %1;\n"
      "@p bra.uni LAB_DONE;\n"
      "add.u32 c, c, 1;\nsetp.lt.u32 p, c, 200000;\n@p bra.uni LAB_WAIT;\n"
      "LAB_DONE:\n}" ::"r"(bar), "r"(parity) : "memory");
}
__device__ __forceinline__ void tma2d(uint32_t dst, const CUtensorMap* m, int c0, int c1, uint32_t bar) {
  asm volatile("cp.async.bulk.tensor.2d.shared::cluster.global.mbarrier::complete_tx::bytes [%0], [%1, {%3,%4}], [%2];"
               ::"r"(dst), "l"(m), "r"(bar), "r"(c0), "r"(c1) : "memory");
}
__device__ __forceinline__ void tma3d(uint32_t dst, const CUtensorMap* m, int c0, int c1, int c2, uint32_t bar) {
  asm volatile("cp.async.bulk.tensor.3d.shared::cluster.global.mbarrier::complete_tx::bytes [%0], [%1, {%3,%4,%5}], [%2];"
               ::"r"(dst), "l"(m), "r"(bar), "r"(c0), "r"(c1), "r"(c2) : "memory");
}
__device__ __forceinline__ void tma5d_mc(uint32_t dst, const CUtensorMap* m, int c0, int c4, uint32_t bar) {
  asm volatile("cp.async.bulk.tensor.5d.shared::cluster.global.mbarrier::complete_tx::bytes.multicast::cluster [%0], [%1, {%3,%5,%5,%5,%4}], [%2], %6;"
               ::"r"(dst), "l"(m), "r"(bar), "r"(c0), "r"(c4), "r"(0), "h"((uint16_t)3) : "memory");
}
__device__ __forceinline__ void l2_prefetch(const void* p, uint32_t bytes) { asm volatile("cp.async.bulk.prefetch.L2.global [%0], %1;" ::"l"(p), "r"(bytes) : "memory"); }
__device__ __forceinline__ bool elect_one() {
  uint32_t pred;
  asm volatile("{.reg .pred P; elect.sync _|P, 0xffffffff; selp.u32 %0, 1, 0, P;}" : "=r"(pred));
  return pred != 0;
}
__device__ __forceinline__ void wg_fence() { asm volatile("wgmma.fence.sync.aligned;" ::: "memory"); }
__device__ __forceinline__ void wg_commit() { asm volatile("wgmma.commit_group.sync.aligned;" ::: "memory"); }
template <int N> __device__ __forceinline__ void wg_wait() { asm volatile("wgmma.wait_group.sync.aligned %0;" ::"n"(N) : "memory"); }
__device__ __forceinline__ void pin(float& a) { asm volatile("" : "+f"(a)::"memory"); }
__device__ __forceinline__ void pin(uint32_t& a) { asm volatile("" : "+r"(a)::"memory"); }
template <int N> __device__ __forceinline__ void reg_fence(float (&d)[N]) {
#pragma unroll
  for (int i = 0; i < N; i++) pin(d[i]);
}
__device__ __forceinline__ void bar_sync(int id, int n) { asm volatile("bar.sync %0, %1;" ::"r"(id), "r"(n) : "memory"); }
__device__ __forceinline__ void bar_arrive(int id, int n) { asm volatile("bar.arrive %0, %1;" ::"r"(id), "r"(n) : "memory"); }
constexpr uint32_t DH128 = (1024 >> 4) | (1u << 30), DH64 = (512 >> 4) | (2u << 30);
__host__ __device__ constexpr uint32_t lbo(uint32_t bytes) { return (bytes >> 4) << 20; }
__device__ __forceinline__ uint32_t pack_bf16(float lo, float hi) { uint32_t r; asm("cvt.rn.bf16x2.f32 %0, %1, %2;" : "=r"(r) : "f"(hi), "f"(lo)); return r; }
__device__ __forceinline__ float bf_lo(uint32_t v) { return __uint_as_float(v << 16); }
__device__ __forceinline__ float bf_hi(uint32_t v) { return __uint_as_float(v & 0xffff0000u); }
__device__ __forceinline__ float bf_ld(const __nv_bfloat16* p) { return __bfloat162float(__ldg(p)); }
__device__ __forceinline__ uint32_t late16(uint32_t bar) {
  uint32_t r;
  asm volatile("{.reg .pred p; mbarrier.test_wait.parity.shared::cta.b64 p, [%1], 0; selp.u32 %0, 16, 0, p;}" : "=r"(r) : "r"(bar) : "memory");
  return r;
}
__device__ __forceinline__ float2 lds_f2(uint32_t a) { float2 v; asm volatile("ld.shared.v2.f32 {%0,%1}, [%2];" : "=f"(v.x), "=f"(v.y) : "r"(a)); return v; }
__device__ __forceinline__ uint32_t lds_h(uint32_t a) { uint32_t v; asm volatile("ld.shared.u16 %0, [%1];" : "=r"(v) : "r"(a)); return v; }
__device__ __forceinline__ uint32_t lds_u(uint32_t a) { uint32_t v; asm volatile("ld.shared.u32 %0, [%1];" : "=r"(v) : "r"(a)); return v; }
__device__ __forceinline__ uint4 lds_u4(uint32_t a) { uint4 v; asm volatile("ld.shared.v4.u32 {%0,%1,%2,%3}, [%4];" : "=r"(v.x), "=r"(v.y), "=r"(v.z), "=r"(v.w) : "r"(a)); return v; }
__device__ __forceinline__ void st_b128(uint4* p, uint32_t a, uint32_t b, uint32_t c, uint32_t d) {
  asm volatile("st.relaxed.gpu.global.v4.b32 [%0], {%1,%2,%3,%4};" ::"l"(p), "r"(a), "r"(b), "r"(c), "r"(d) : "memory");
}
__device__ __forceinline__ void ld_b128(const uint4* p, uint32_t& a, uint32_t& b, uint32_t& c, uint32_t& d) {
  asm volatile("{.reg .b64 l, h; .reg .b128 v; ld.relaxed.gpu.global.b128 v, [%4]; mov.b128 {l,h}, v; mov.b64 {%0,%1}, l; mov.b64 {%2,%3}, h;}"
               : "=r"(a), "=r"(b), "=r"(c), "=r"(d) : "l"(p) : "memory");
}
__device__ __forceinline__ float tanh_fast(float x) { float y; asm("tanh.approx.f32 %0, %1;" : "=f"(y) : "f"(x)); return y; }
__device__ __forceinline__ float gelu2(float v) {
  float p = fmaf(v * v, 0.0356774081363f, 0.7978845608029f);
  return fmaf(v, tanh_fast(v * p), v);
}
__device__ __forceinline__ uint32_t bf2_mul(uint32_t a, uint32_t b) { uint32_t r; asm("mul.rn.bf16x2 %0, %1, %2;" : "=r"(r) : "r"(a), "r"(b)); return r; }
__device__ __forceinline__ uint32_t bf2_add(uint32_t a, uint32_t b) { uint32_t r; asm("add.rn.bf16x2 %0, %1, %2;" : "=r"(r) : "r"(a), "r"(b)); return r; }
__device__ __forceinline__ uint32_t bf2_fma(uint32_t a, uint32_t b, uint32_t c) { uint32_t r; asm("fma.rn.bf16x2 %0, %1, %2, %3;" : "=r"(r) : "r"(a), "r"(b), "r"(c)); return r; }
__device__ __forceinline__ uint32_t gelu2_pair(float a, float b) {
  return pack_bf16(gelu2(a), gelu2(b));
}
struct cplx { float re, im; };
__device__ __forceinline__ cplx cmul(cplx a, cplx b) { return {fmaf(a.re, b.re, -a.im * b.im), fmaf(a.re, b.im, a.im * b.re)}; }
__device__ __forceinline__ cplx cfma(cplx a, cplx b, cplx c) {
  return {fmaf(a.re, b.re, fmaf(-a.im, b.im, c.re)), fmaf(a.re, b.im, fmaf(a.im, b.re, c.im))};
}
__device__ __forceinline__ cplx make_lam(float lre, float lim, float ldt) {
  float dt = __bfloat162float(__float2bfloat16_rn(expf(ldt)));
  float mag = expf(dt * lre), sn, cs;
  sincospif(dt * lim * 0.31830988618379067f, &sn, &cs);
  return {mag * cs, mag * sn};
}

template<int TA,int TB,uint32_t AH,uint32_t BH> __device__ __forceinline__ void wgmma_n64_ss(float (&d)[32], uint32_t al, uint32_t ao, uint32_t bl, uint32_t bo, int scale_d){
  asm volatile("{.reg .pred p; .reg .b32 t, v; .reg .b64 da, db; setp.ne.b32 p, %36, 0; add.u32 t, %32, %33; mov.b64 da, {t, %39}; add.u32 v, %34, %35; mov.b64 db, {v, %40};\n"
   "wgmma.mma_async.sync.aligned.m64n64k16.f32.bf16.bf16 {%0,%1,%2,%3,%4,%5,%6,%7,%8,%9,%10,%11,%12,%13,%14,%15,%16,%17,%18,%19,%20,%21,%22,%23,%24,%25,%26,%27,%28,%29,%30,%31}, da, db, p, 1, 1, %37, %38;}"
   : "+f"(d[0]),"+f"(d[1]),"+f"(d[2]),"+f"(d[3]),"+f"(d[4]),"+f"(d[5]),"+f"(d[6]),"+f"(d[7]),"+f"(d[8]),"+f"(d[9]),"+f"(d[10]),"+f"(d[11]),"+f"(d[12]),"+f"(d[13]),"+f"(d[14]),"+f"(d[15]),"+f"(d[16]),"+f"(d[17]),"+f"(d[18]),"+f"(d[19]),"+f"(d[20]),"+f"(d[21]),"+f"(d[22]),"+f"(d[23]),"+f"(d[24]),"+f"(d[25]),"+f"(d[26]),"+f"(d[27]),"+f"(d[28]),"+f"(d[29]),"+f"(d[30]),"+f"(d[31])
   : "r"(al),"r"(ao >> 4),"r"(bl),"r"(bo >> 4),"r"(scale_d),"n"(TA),"n"(TB),"n"(AH),"n"(BH));
}
template<int TB,uint32_t BH> __device__ __forceinline__ void wgmma_n64_rs(float (&d)[32], uint32_t a0,uint32_t a1,uint32_t a2,uint32_t a3, uint32_t bl, uint32_t bo, int scale_d){
  asm volatile("{.reg .pred p; .reg .b32 t; .reg .b64 db; setp.ne.b32 p, %38, 0; add.u32 t, %36, %37; mov.b64 db, {t, %40};\n"
   "wgmma.mma_async.sync.aligned.m64n64k16.f32.bf16.bf16 {%0,%1,%2,%3,%4,%5,%6,%7,%8,%9,%10,%11,%12,%13,%14,%15,%16,%17,%18,%19,%20,%21,%22,%23,%24,%25,%26,%27,%28,%29,%30,%31}, {%32,%33,%34,%35}, db, p, 1, 1, %39;}"
   : "+f"(d[0]),"+f"(d[1]),"+f"(d[2]),"+f"(d[3]),"+f"(d[4]),"+f"(d[5]),"+f"(d[6]),"+f"(d[7]),"+f"(d[8]),"+f"(d[9]),"+f"(d[10]),"+f"(d[11]),"+f"(d[12]),"+f"(d[13]),"+f"(d[14]),"+f"(d[15]),"+f"(d[16]),"+f"(d[17]),"+f"(d[18]),"+f"(d[19]),"+f"(d[20]),"+f"(d[21]),"+f"(d[22]),"+f"(d[23]),"+f"(d[24]),"+f"(d[25]),"+f"(d[26]),"+f"(d[27]),"+f"(d[28]),"+f"(d[29]),"+f"(d[30]),"+f"(d[31])
   : "r"(a0),"r"(a1),"r"(a2),"r"(a3),"r"(bl),"r"(bo >> 4),"r"(scale_d),"n"(TB),"n"(BH));
}
template<int TA,int TB,uint32_t AH,uint32_t BH> __device__ __forceinline__ void wgmma_n96_ss(float (&d)[48], uint32_t al, uint32_t ao, uint32_t bl, uint32_t bo, int scale_d){
  asm volatile("{.reg .pred p; .reg .b32 t, v; .reg .b64 da, db; setp.ne.b32 p, %52, 0; add.u32 t, %48, %49; mov.b64 da, {t, %55}; add.u32 v, %50, %51; mov.b64 db, {v, %56};\n"
   "wgmma.mma_async.sync.aligned.m64n96k16.f32.bf16.bf16 {%0,%1,%2,%3,%4,%5,%6,%7,%8,%9,%10,%11,%12,%13,%14,%15,%16,%17,%18,%19,%20,%21,%22,%23,%24,%25,%26,%27,%28,%29,%30,%31,%32,%33,%34,%35,%36,%37,%38,%39,%40,%41,%42,%43,%44,%45,%46,%47}, da, db, p, 1, 1, %53, %54;}"
   : "+f"(d[0]),"+f"(d[1]),"+f"(d[2]),"+f"(d[3]),"+f"(d[4]),"+f"(d[5]),"+f"(d[6]),"+f"(d[7]),"+f"(d[8]),"+f"(d[9]),"+f"(d[10]),"+f"(d[11]),"+f"(d[12]),"+f"(d[13]),"+f"(d[14]),"+f"(d[15]),"+f"(d[16]),"+f"(d[17]),"+f"(d[18]),"+f"(d[19]),"+f"(d[20]),"+f"(d[21]),"+f"(d[22]),"+f"(d[23]),"+f"(d[24]),"+f"(d[25]),"+f"(d[26]),"+f"(d[27]),"+f"(d[28]),"+f"(d[29]),"+f"(d[30]),"+f"(d[31]),"+f"(d[32]),"+f"(d[33]),"+f"(d[34]),"+f"(d[35]),"+f"(d[36]),"+f"(d[37]),"+f"(d[38]),"+f"(d[39]),"+f"(d[40]),"+f"(d[41]),"+f"(d[42]),"+f"(d[43]),"+f"(d[44]),"+f"(d[45]),"+f"(d[46]),"+f"(d[47])
   : "r"(al),"r"(ao >> 4),"r"(bl),"r"(bo >> 4),"r"(scale_d),"n"(TA),"n"(TB),"n"(AH),"n"(BH));
}
template<int TA,int TB,uint32_t AH,uint32_t BH> __device__ __forceinline__ void wgmma_n128_ss(float (&d)[64], uint32_t al, uint32_t ao, uint32_t bl, uint32_t bo, int scale_d){
  asm volatile("{.reg .pred p; .reg .b32 t, v; .reg .b64 da, db; setp.ne.b32 p, %68, 0; add.u32 t, %64, %65; mov.b64 da, {t, %71}; add.u32 v, %66, %67; mov.b64 db, {v, %72};\n"
   "wgmma.mma_async.sync.aligned.m64n128k16.f32.bf16.bf16 {%0,%1,%2,%3,%4,%5,%6,%7,%8,%9,%10,%11,%12,%13,%14,%15,%16,%17,%18,%19,%20,%21,%22,%23,%24,%25,%26,%27,%28,%29,%30,%31,%32,%33,%34,%35,%36,%37,%38,%39,%40,%41,%42,%43,%44,%45,%46,%47,%48,%49,%50,%51,%52,%53,%54,%55,%56,%57,%58,%59,%60,%61,%62,%63}, da, db, p, 1, 1, %69, %70;}"
   : "+f"(d[0]),"+f"(d[1]),"+f"(d[2]),"+f"(d[3]),"+f"(d[4]),"+f"(d[5]),"+f"(d[6]),"+f"(d[7]),"+f"(d[8]),"+f"(d[9]),"+f"(d[10]),"+f"(d[11]),"+f"(d[12]),"+f"(d[13]),"+f"(d[14]),"+f"(d[15]),"+f"(d[16]),"+f"(d[17]),"+f"(d[18]),"+f"(d[19]),"+f"(d[20]),"+f"(d[21]),"+f"(d[22]),"+f"(d[23]),"+f"(d[24]),"+f"(d[25]),"+f"(d[26]),"+f"(d[27]),"+f"(d[28]),"+f"(d[29]),"+f"(d[30]),"+f"(d[31]),"+f"(d[32]),"+f"(d[33]),"+f"(d[34]),"+f"(d[35]),"+f"(d[36]),"+f"(d[37]),"+f"(d[38]),"+f"(d[39]),"+f"(d[40]),"+f"(d[41]),"+f"(d[42]),"+f"(d[43]),"+f"(d[44]),"+f"(d[45]),"+f"(d[46]),"+f"(d[47]),"+f"(d[48]),"+f"(d[49]),"+f"(d[50]),"+f"(d[51]),"+f"(d[52]),"+f"(d[53]),"+f"(d[54]),"+f"(d[55]),"+f"(d[56]),"+f"(d[57]),"+f"(d[58]),"+f"(d[59]),"+f"(d[60]),"+f"(d[61]),"+f"(d[62]),"+f"(d[63])
   : "r"(al),"r"(ao >> 4),"r"(bl),"r"(bo >> 4),"r"(scale_d),"n"(TA),"n"(TB),"n"(AH),"n"(BH));
}

__global__ void __cluster_dims__(2, 1, 1) __launch_bounds__(384, 1)
fused_kernel(const __nv_bfloat16* __restrict__ lam_re, const __nv_bfloat16* __restrict__ lam_im, const __nv_bfloat16* __restrict__ log_dt,
             const __nv_bfloat16* __restrict__ dskip, const __nv_bfloat16* __restrict__ b1, const __nv_bfloat16* __restrict__ b2,
             const __nv_bfloat16* __restrict__ gate_w, const __nv_bfloat16* __restrict__ pf_w1, const __nv_bfloat16* __restrict__ pf_w2,
             const __nv_bfloat16* __restrict__ pf_cre, const __nv_bfloat16* __restrict__ pf_cim, float* __restrict__ out,
             const __grid_constant__ Maps maps) {
  extern __shared__ __align__(1024) unsigned char smem_raw[];
  const uint32_t sb = (uint32_t)__cvta_generic_to_shared(smem_raw);
  const int b = blockIdx.x;
  const int rank = b & 1, cl = b >> 1;
  const int sp = (cl & 1) | ((cl >> 2) & 2), m = ((cl >> 1) & 3) | ((cl >> 4) << 2);
  const int s = sp * 2 + rank;
  const int warp = __shfl_sync(0xffffffffu, (int)(threadIdx.x >> 5), 0);
  const int lane = threadIdx.x & 31;
  const int xrot = 6 - 2 * sp;

  if (elect_one()) {
    if (warp == 8) TS(2, 0);
    if (warp < 3) {
      asm volatile("prefetch.tensormap [%0];" ::"l"(&maps.x + warp) : "memory");
      mbar_init(sb + OFF_GBAR + 8 * warp, warp < 2 ? 64 : 96);
    }
    const uint32_t c = warp < 8 ? 1 : warp < 11 ? 8 : 4;
    mbar_init(sb + OFF_XFULL + 16 * warp, c);
    mbar_init(sb + OFF_XFULL + 16 * warp + 8, c);
    asm volatile("fence.mbarrier_init.release.cluster;" ::: "memory");
  }
  __syncwarp();
  asm volatile("barrier.cluster.arrive.relaxed.aligned;" ::: "memory");

  if (warp < 8) {
    const int wg = warp >> 2, w = warp & 3, q = lane & 3, gr = lane >> 2;
    uint32_t bv[28];
#pragma unroll
    for (int j = 0; j < 28; j++) bv[j] = __ldg(reinterpret_cast<const uint32_t*>(b1 + s * 224 + j * 8) + q);
    asm volatile("setmaxnreg.inc.sync.aligned.u32 224;");
    asm volatile("barrier.cluster.wait.aligned;" ::: "memory");
    TS(wg, 0);
    auto release = [&](int slot) { if (lane == 0) mbar_arrive(sb + OFF_EMPTY + 8 * slot); };
    const uint32_t xw = sb + OFF_X + wg * 8192, fullb = sb + OFF_FULL;
    const uint32_t dxw = (xw & 0x3FFFF) >> 4, dring = ((sb + OFF_RING) & 0x3FFFF) >> 4;

    float ure[32], uim[32], aa[48], ab[64];
    cplx lam[2], coef[2], l16[2], l32[2], lq[2], pre[2], e[2];
    uint32_t sh16, mhi;

#pragma unroll
    for (int kb = 0; kb < 8; kb++) {
      const int slot = kb % NSLOT;
      mbar_wait(sb + OFF_XFULL + 8 * kb, 0);
      if (kb == 0) TS(wg, 18);
      mbar_wait(fullb + 8 * slot, (kb / NSLOT) & 1);
      TS2(2, kb);
      if (kb == 0) TS(wg, 1);
      wg_fence();
      const uint32_t dxa = dxw + ((kb + xrot) & 7) * 1024;
#pragma unroll
      for (int kk = 0; kk < 4; kk++) {
        wgmma_n64_ss<0, 0, DH128, DH128>(ure, dring, slot * 16384 + kk * 32, dxa, kk * 32, (kb | kk) != 0);
        wgmma_n64_ss<0, 0, DH128, DH128>(uim, dring, slot * 16384 + 8192 + kk * 32, dxa, kk * 32, (kb | kk) != 0);
      }
      wg_commit();
      if (kb > 0) { wg_wait<1>(); release((kb - 1) % NSLOT); }
      if (kb == 1) { sh16 = late16(sb + OFF_XFULL); mhi = 0xffffffffu << sh16; }
      if (kb == 1 || (kb >= 3 && kb < 6)) {
#pragma unroll
        for (int j = 0; j < 28; j++) if (j / 7 == (kb == 1 ? 0 : kb - 2)) {
          pin(bv[j]);
          float* d = j < 12 ? aa + 4 * j : ab + 4 * (j - 12);
          d[0] = d[2] = __uint_as_float(bv[j] << sh16); d[1] = d[3] = __uint_as_float(bv[j] & mhi);
          pin(d[0]); pin(d[1]); pin(d[2]); pin(d[3]);
        }
      }
      if (kb == 5) {
        mbar_wait(sb + OFF_LBAR, 0);
#pragma unroll
        for (int h = 0; h < 2; h++) {
          const uint4 v = lds_u4(sb + OFF_LC + (w * 16 + gr + 8 * h) * 16);
          lam[h] = cplx{__uint_as_float(v.x), __uint_as_float(v.y)};
          coef[h] = cplx{__uint_as_float(v.z), __uint_as_float(v.w)};
        }
      }
      if (kb == 6) {
#pragma unroll
        for (int h = 0; h < 2; h++) {
          pin(lam[h].re); pin(lam[h].im);
          cplx t = cmul(lam[h], lam[h]); t = cmul(t, t); t = cmul(t, t);
          l16[h] = cmul(t, t);
          pin(l16[h].re); pin(l16[h].im);
        }
      }
      if (kb == 7) {
#pragma unroll
        for (int h = 0; h < 2; h++) {
          pin(l16[h].re); pin(l16[h].im);
          l32[h] = cmul(l16[h], l16[h]);
          const cplx a = (q & 1) ? l16[h] : cplx{1.f, 0.f}, c = (q & 2) ? l32[h] : cplx{1.f, 0.f};
          lq[h] = cmul(cmul(a, c), coef[h]);
          pin(lq[h].re); pin(lq[h].im);
        }
      }
    }
    TS(wg, 2);
    auto scale_u = [&](int i0, int i1) {
#pragma unroll
      for (int i = 0; i < 32; i++) if (i >= i0 && i < i1) {
        pin(ure[i]); pin(uim[i]);
        const cplx v = cmul(coef[(i >> 1) & 1], cplx{ure[i], uim[i]});
        ure[i] = v.re; uim[i] = v.im;
        pin(ure[i]); pin(uim[i]);
      }
    };
#pragma unroll
    for (int kb = 0; kb < 8; kb++) {
      const int u = 8 + kb, slot = u % NSLOT;
      mbar_wait(fullb + 8 * slot, (u / NSLOT) & 1);
      wg_fence();
      const uint32_t dxa = dxw + ((kb + xrot) & 7) * 1024;
#pragma unroll
      for (int kk = 0; kk < 4; kk++)
        wgmma_n96_ss<0, 1, DH128, DH64>(aa, dxa, kk * 32, dring, slot * 16384 + kk * 1024 + lbo(4096), 1);
      wg_commit();
      wg_wait<1>();
      release((u - 1) % NSLOT);
      if (kb == 0) {
        reg_fence(ure); reg_fence(uim);
#pragma unroll
        for (int h = 0; h < 2; h++) e[h] = cplx{ure[2 * h], uim[2 * h]};
      }
      if (kb == 0 || kb == 2 || kb == 3) {
        const int ch = kb ? kb - 1 : 0;
#pragma unroll
        for (int t = 1 + 5 * ch; t < 6 + 5 * ch; t++)
#pragma unroll
          for (int h = 0; h < 2; h++) { const int i = 4 * (t >> 1) + 2 * h + (t & 1); e[h] = cfma(lam[h], e[h], cplx{ure[i], uim[i]}); }
#pragma unroll
        for (int h = 0; h < 2; h++) { pin(e[h].re); pin(e[h].im); }
      } else if (kb == 4) {
#pragma unroll
        for (int h = 0; h < 2; h++) {
          cplx y = {__shfl_up_sync(0xffffffffu, e[h].re, 1, 4), __shfl_up_sync(0xffffffffu, e[h].im, 1, 4)};
          if (q >= 1) e[h] = cfma(l16[h], y, e[h]);
          y = cplx{__shfl_up_sync(0xffffffffu, e[h].re, 2, 4), __shfl_up_sync(0xffffffffu, e[h].im, 2, 4)};
          if (q >= 2) e[h] = cfma(l32[h], y, e[h]);
        }
        if (q == 3) {
#pragma unroll
          for (int h = 0; h < 2; h++)
            asm volatile("st.shared.v2.f32 [%0], {%1,%2};" ::"r"(sb + OFF_CARRY + wg * 512 + (w * 16 + gr + 8 * h) * 8), "f"(e[h].re), "f"(e[h].im) : "memory");
          mbar_arrive(sb + OFF_GBAR);
        }
#pragma unroll
        for (int h = 0; h < 2; h++) {
          const cplx y = {__shfl_up_sync(0xffffffffu, e[h].re, 1, 4), __shfl_up_sync(0xffffffffu, e[h].im, 1, 4)};
          pre[h] = (q >= 1) ? cmul(coef[h], y) : cplx{0.f, 0.f};
          pin(pre[h].re); pin(pre[h].im);
        }
        TS(wg, 3);
      } else if (kb > 4) {
        scale_u(kb == 5 ? 0 : kb == 6 ? 4 : 12, kb == 5 ? 4 : kb == 6 ? 12 : 20);
      }
    }
    TS(wg, 4);
    uint32_t H[56];
    cplx hst[2];
    const uint32_t hst_addr = xw + (w * 16 + (lane & 15)) * 128 + (((lane >> 4) ^ (lane & 7)) << 4);
    uint32_t peer;
    asm volatile("mapa.shared::cluster.u32 %0, %1, %2;" : "=r"(peer) : "r"(sb), "r"(rank ^ 1));
    auto credit = [&]() { if (lane == 0) mbar_arrive_cl(peer + OFF_KBAR + wg * 8); };
#pragma unroll
    for (int kb = 0; kb < 8; kb++) {
      const int u = 16 + kb, slot = u % NSLOT;
      mbar_wait(fullb + 8 * slot, (u / NSLOT) & 1);
      wg_fence();
#pragma unroll
      for (int kk = 0; kk < 4; kk++)
        wgmma_n128_ss<0, 1, DH128, DH128>(ab, dxw, kb * 16384 + kk * 32, dring, slot * 16384 + kk * 2048 + lbo(8192), 1);
      wg_commit();
      wg_wait<1>();
      release((u - 1) % NSLOT);
      if (kb == 6) credit();
      if (kb == 0) scale_u(20, 32);
      if (kb < 5 && kb != 1) {
        const int ch = kb ? kb - 1 : 0;
#pragma unroll
        for (int i = ch * 6; i < ch * 6 + 6; i++) {
          pin(aa[2 * i]); pin(aa[2 * i + 1]);
          H[i] = gelu2_pair(aa[2 * i], aa[2 * i + 1]);
          pin(H[i]);
        }
      }
      if (kb >= 4) {
        if (kb == 4) {
          TS(wg, 5);
          mbar_wait(sb + OFF_CBAR, 0);
          TS(wg, 6);
#pragma unroll
          for (int h = 0; h < 2; h++) {
            const float2 c = lds_f2(sb + OFF_CARRY + wg * 512 + (w * 16 + gr + 8 * h) * 8);
            hst[h] = cfma(lq[h], cplx{c.x, c.y}, pre[h]);
          }
        }
        const int j0 = (kb - 4) * 2;
        uint32_t rr[4], ri[4];
#pragma unroll
        for (int jj = 0; jj < 2; jj++) {
          const int j = j0 + jj;
          const uint32_t g2 = lds_u(sb + OFF_GS + (wg * 64 + j * 8 + q * 2) * 2);
#pragma unroll
          for (int h = 0; h < 2; h++) {
            const int i = 4 * j + 2 * h;
            const cplx h0 = cfma(lam[h], hst[h], cplx{ure[i], uim[i]});
            hst[h] = cfma(lam[h], h0, cplx{ure[i + 1], uim[i + 1]});
            rr[jj * 2 + h] = bf2_mul(pack_bf16(h0.re, hst[h].re), g2);
            ri[jj * 2 + h] = bf2_mul(pack_bf16(h0.im, hst[h].im), g2 ^ 0x80008000u);
          }
        }
        const uint32_t a = hst_addr ^ (j0 << 4);
        asm volatile("stmatrix.sync.aligned.m8n8.x4.shared.b16 [%0], {%1,%2,%3,%4};" ::"r"(a), "r"(rr[0]), "r"(rr[1]), "r"(rr[2]), "r"(rr[3]) : "memory");
        asm volatile("stmatrix.sync.aligned.m8n8.x4.shared.b16 [%0], {%1,%2,%3,%4};" ::"r"(a + 16384), "r"(ri[0]), "r"(ri[1]), "r"(ri[2]), "r"(ri[3]) : "memory");
      }
    }
    TS(wg, 7);

    uint4* const psend = g_part + (size_t)(m * 8 + rank) * 3072 + warp * 128 + lane;
    const uint4* const precv = g_part + (size_t)(m * 8 + s) * 3072 + warp * 128 + lane;
    const uint32_t pbuf = OFF_X + 5 * 16384 + warp * 2048 + lane * 16;
    const uint32_t dx0 = ((sb + OFF_X) & 0x3FFFF) >> 4;
    const uint32_t xsk = xw + (6 + rank) * 16384 + (w * 16 + gr) * 128 + (gr << 4) + q * 4;
    float o[32], fin[32], rho[2];
    uint32_t tr[8];
    uint32_t r0[16], pt[16], sum[16], tag;
    auto recv_issue = [&](uint32_t (&r)[16], int k) {
#pragma unroll
      for (int i = 0; i < 4; i++) ld_b128(precv + k * 1024 + i * 32, r[4 * i], r[4 * i + 1], r[4 * i + 2], r[4 * i + 3]);
    };
    auto stale = [&](uint32_t (&r)[16]) {
      uint32_t t0, t1, r_;
      asm("lop3.b32 %0, %1, %2, %3, 0x7e;" : "=r"(t0) : "r"(r[0]), "r"(r[4]), "r"(tag));
      asm("lop3.b32 %0, %1, %2, %3, 0x7e;" : "=r"(t1) : "r"(r[8]), "r"(r[12]), "r"(tag));
      asm volatile("{.reg .pred p; .reg .b32 t; lop3.b32 t, %1, %2, 1, 0xa8; setp.ne.u32 p, t, 0; vote.sync.any.pred p, p, 0xffffffff; selp.u32 %0, 1, 0, p;}" : "=r"(r_) : "r"(t0), "r"(t1));
      return r_ != 0;
    };
    auto recv_check = [&](uint32_t (&r)[16], int k) {
      if (__builtin_expect(stale(r), 0)) {
        int tries = 0;
#pragma unroll 1
        do { recv_issue(r, k); } while (stale(r) && ++tries < 200000);
      }
    };
    auto gelu_b = [&](int i0, int i1) {
#pragma unroll
      for (int i = i0; i < i1; i++) {
        pin(ab[2 * i]); pin(ab[2 * i + 1]);
        H[24 + i] = gelu2_pair(ab[2 * i], ab[2 * i + 1]);
        pin(H[24 + i]);
      }
    };
    auto mma = [&](float (&o)[32], uint32_t wo, int k0, int k1, int acc) {
      wg_fence();
#pragma unroll
      for (int k = k0; k < k1; k++) {
        if (k >= 6 && k < 14) {
          const int kk = k - 6;
          wgmma_n64_ss<1, 0, DH128, DH128>(o, dxw, (kk >> 2) * 16384 + (kk & 3) * 2048, dx0, wo + 16384 + (kk >> 2) * 8192 + (kk & 3) * 32, 1);
        } else {
          const int kk = k < 6 ? k : k - 8;
          wgmma_n64_rs<1, DH128>(o, H[4 * kk], H[4 * kk + 1], H[4 * kk + 2], H[4 * kk + 3], dx0, wo + (kk / 7) * 32768 + (kk % 7) * 2048, k != 0 || acc);
        }
      }
      wg_commit();
    };
#pragma unroll
    for (int p = 0; p < 8; p++) {
      const uint32_t wo = (p % 3) == 1 ? 2 * 16384 : OFF_RING + (p % 3) * 24576;
      if (p == 0) {
        mbar_wait(fullb, 0);
        mma(o, wo, 0, 3, 0);
        asm volatile("fence.proxy.async.shared::cta;" ::: "memory");
        wg_wait<1>(); release(5);
        gelu_b(0, 4);
        mma(o, wo, 3, 6, 0);
        gelu_b(4, 10);
        bar_sync(1 + wg, 128);
        mbar_wait(fullb + 8, 0);
        mma(o, wo, 6, 10, 0);
        gelu_b(10, 16);
        mma(o, wo, 10, 15, 0);
        gelu_b(16, 24);
        mbar_wait(fullb + 16, 0);
        mma(o, wo, 15, 18, 0);
        gelu_b(24, 32);
        if (wg == 1) bar_sync(4, 256);
        mma(o, wo, 18, 22, 0);
      } else {
        TR(0);
        if (!EW || (p & 1)) mbar_wait(sb + OFF_XFULL + 8 * p, 1);
        TR(1);
        bar_sync(3 + wg, 256);
        if (p < 7) mma(o, wo, 0, 22, 0); else mma(fin, wo, 0, 22, 1);
      }
      if (p < 7 || wg == 0) bar_arrive(4 - wg, 256);
      TR(2);
      if (p != TP) TS(wg, 8 + p);
      if ((p & 1) == 0) {
        if ((threadIdx.x & 127) == 0) mbar_expect_tx(sb + OFF_RBAR + wg * 8, 8192);
        if (p == 6) {
          tag = lds_u(sb + OFF_EPOCH);
          recv_check(sum, 0); recv_check(r0, 1);
#pragma unroll
          for (int i = 0; i < 16; i++) sum[i] = bf2_add(sum[i], r0[i]);
        }
        TR(3);
        mbar_wait(sb + OFF_KBAR + wg * 8, (p >> 1) & 1);
        TR(4);
        if (K2E && p == 6) recv_issue(r0, 2);
      } else {
        if (p == 1 || p == 7) tag = lds_u(sb + OFF_EPOCH);
        if (EW && p < 7) mbar_wait(sb + OFF_XFULL + 8 * (p + 1), 1);
        TR(3);
        mbar_wait(sb + OFF_RBAR + wg * 8, (p >> 1) & 1);
        TR(4);
#pragma unroll
        for (int i = 0; i < 4; i++) { const uint4 v = lds_u4(sb + pbuf + i * 512); pt[4 * i] = v.x; pt[4 * i + 1] = v.y; pt[4 * i + 2] = v.z; pt[4 * i + 3] = v.w; }
        if (p == 7) {
          recv_check(r0, 2);
#pragma unroll
          for (int i = 0; i < 16; i++) sum[i] = bf2_add(sum[i], bf2_add(r0[i], pt[i]));
        }
      }
      TR(5);
      wg_wait<0>();
      TR(6);
      if (p < 5) release(p);
      if (p < 7) reg_fence(o); else reg_fence(fin);
      if ((p & 1) == 0) {
        if (!K2E && p == 6) recv_issue(r0, 2);
#pragma unroll
        for (int i = 0; i < 4; i++)
          asm volatile("st.async.shared::cluster.mbarrier::complete_tx::bytes.v4.b32 [%0], {%1,%2,%3,%4}, [%5];" ::"r"(peer + pbuf + i * 512),
                       "r"(pack_bf16(o[8 * i], o[8 * i + 1])), "r"(pack_bf16(o[8 * i + 2], o[8 * i + 3])), "r"(pack_bf16(o[8 * i + 4], o[8 * i + 5])),
                       "r"(pack_bf16(o[8 * i + 6], o[8 * i + 7])), "r"(peer + OFF_RBAR + wg * 8) : "memory");
        if (p == 2 || p == 4) {
          if (p == 2) {
#pragma unroll
            for (int h = 0; h < 2; h++) rho[h] = 0.5f * bf_lo(lds_h(sb + OFF_GS + (wg * 64 + w * 16 + gr + 8 * h) * 2));
          }
#pragma unroll
          for (int j = (p - 2) * 2; j < p * 2; j++) {
            const float2 db = lds_f2(sb + OFF_DB + j * 32 + q * 8);
#pragma unroll
            for (int h = 0; h < 2; h++) {
              const uint32_t xd = bf2_mul(lds_u((xsk ^ (j << 4)) + h * 1024), __float_as_uint(db.x));
              fin[4 * j + 2 * h] = fmaf(bf_lo(xd), rho[h], bf_lo(__float_as_uint(db.y)));
              fin[4 * j + 2 * h + 1] = fmaf(bf_hi(xd), rho[h], bf_hi(__float_as_uint(db.y)));
              pin(fin[4 * j + 2 * h]); pin(fin[4 * j + 2 * h + 1]);
            }
          }
          if (p == 4) {
#pragma unroll
            for (int h = 0; h < 2; h++) { rho[h] = __fdividef(1.f, 2.f + rho[h]); pin(rho[h]); }
            recv_issue(sum, 0);
            if (K1E) recv_issue(r0, 1);
          }
        }
      } else if (p < 7) {
#pragma unroll
        for (int i = 0; i < 4; i++) {
#pragma unroll
          for (int c = 4 * i; c < 4 * i + 4; c++) pt[c] = bf2_add(pt[c], pack_bf16(o[2 * c], o[2 * c + 1]));
          asm("lop3.b32 %0, %0, 1, %1, 0xb8;" : "+r"(pt[4 * i]) : "r"(tag));
          st_b128(psend + (((sp + 1 + (p >> 1)) & 3) * 6 + (p >> 1)) * 1024 + i * 32, pt[4 * i], pt[4 * i + 1], pt[4 * i + 2], pt[4 * i + 3]);
        }
        __syncwarp();
        credit();
        if (!K1E && p == 5) recv_issue(r0, 1);
      }
      TR(7);
    }
    {
      TS(wg, 16);
      const uint32_t tb = sb + OFF_RING + 3 * 16384 + warp * 4096;
      const uint32_t ta = tb + gr * 256 + ((gr & 3) << 5) + q * 8;
      const uint32_t la = tb + (lane >> 3) * 256 + (((lane & 7) << 4) ^ ((lane >> 3) << 5));
      float* op = out + (size_t)(m * 128 + wg * 64 + (lane >> 4) * 16 + w * 4 + ((lane >> 3) & 1)) * DM + s * 64 + (lane & 7) * 4;
#pragma unroll
      for (int qq = 0; qq < 4; qq += QS) {
#pragma unroll
        for (int qt = qq; qt < qq + QS; qt++) {
          const int h = qt & 1, ch = qt >> 1;
#pragma unroll
          for (int j = 0; j < 4; j++) {
            const int i = ch * 8 + j * 2 + h;
            asm volatile("st.shared.v2.f32 [%0], {%1,%2};" ::"r"((ta ^ (j << 5)) + h * 2048 + ch * 128),
                         "f"((fin[2 * i] + bf_lo(sum[i])) * rho[h]), "f"((fin[2 * i + 1] + bf_hi(sum[i])) * rho[h]) : "memory");
          }
        }
        __syncwarp();
#pragma unroll
        for (int qt = qq; qt < qq + QS; qt++) {
          const int h = qt & 1, ch = qt >> 1;
#pragma unroll
          for (int r = 0; r < 2; r++)
            *reinterpret_cast<uint4*>(op + (r * 32 + h * 2) * DM + ch * 32) = lds_u4(la + (h * 2 + r) * 1024 + ch * 128);
        }
      }
      if (threadIdx.x == 128) g_epoch[b] = tag;
      TS(wg, 17); TG(wg); TRD(); TDUMP();
    }
  } else {
    asm volatile("setmaxnreg.dec.sync.aligned.u32 56;");
    int wsel = warp;
    asm("" : "+r"(wsel));
    if (wsel > 8) {
      if (warp != 11) {
        const int t = threadIdx.x - 288;
        unsigned par;
        asm volatile("ld.relaxed.gpu.global.u32 %0, [%1];" : "=r"(par) : "l"(g_epoch + b) : "memory");
        const float pr = bf_ld(lam_re + s * 64 + t), pi = bf_ld(lam_im + s * 64 + t), pd = bf_ld(log_dt + s * 64 + t);
        asm volatile("barrier.cluster.wait.aligned;" ::: "memory");
        par = (par + 1) & 1;
        cplx l64 = make_lam(pr, pi, pd);
        {
          const float inv = __fdividef(1.f, fmaf(pr, pr, pi * pi));
          const cplx cf = cmul(cplx{l64.re - 1.f, l64.im}, cplx{pr * inv, -pi * inv});
          asm volatile("st.shared.v4.f32 [%0], {%1,%2,%3,%4};" ::"r"(sb + OFF_LC + t * 16), "f"(l64.re), "f"(l64.im), "f"(cf.re), "f"(cf.im) : "memory");
          mbar_arrive(sb + OFF_LBAR);
        }
#pragma unroll
        for (int i = 0; i < 6; i++) l64 = cmul(l64, l64);
        cplx l128 = cmul(l64, l64);
        pin(l128.re); pin(l128.im);
        mbar_wait(sb + OFF_GBAR, 0);
        const float2 e0 = lds_f2(sb + OFF_CARRY + t * 8), e1 = lds_f2(sb + OFF_CARRY + 512 + t * 8);
        float2* eb = g_end + s * 1024 + t;
        {
          const cplx e = cfma(l64, cplx{e0.x, e0.y}, cplx{e1.x, e1.y});
          const unsigned long long v = ((unsigned long long)__float_as_uint(e.im) << 32) | ((__float_as_uint(e.re) & ~1u) | par);
          asm volatile("st.relaxed.gpu.global.b64 [%0], %1;" ::"l"(eb + m * 64), "l"(v) : "memory");
        }
        if (t == 0) TS(3, 1);
        cplx S = {0.f, 0.f};
        {
          unsigned long long v[15];
          uint32_t bad;
          int tries = 0;
          const float2* e15 = eb + (m - 15) * 64;
#pragma unroll 1
          do {
#pragma unroll
            for (int i = 0; i < 15; i++) {
              v[i] = par;
              asm volatile("{.reg .pred p; setp.ge.s32 p, %2, %3; @p ld.relaxed.gpu.global.b64 %0, [%1];}" : "+l"(v[i]) : "l"(e15 + i * 64), "r"(m), "r"(15 - i) : "memory");
            }
            bad = 0;
#pragma unroll
            for (int i = 0; i < 15; i++) bad |= (uint32_t)v[i] ^ par;
          } while ((bad & 1) && ++tries < 200000);
          if (t == 0) TS(3, 2);
#pragma unroll
          for (int i = 0; i < 15; i++) S = cfma(l128, S, cplx{__uint_as_float((uint32_t)v[i] & ~1u), __uint_as_float((uint32_t)(v[i] >> 32))});
        }
        const cplx S1 = cfma(l64, S, cplx{e0.x, e0.y});
        asm volatile("st.shared.v2.f32 [%0], {%1,%2};" ::"r"(sb + OFF_CARRY + t * 8), "f"(S.re), "f"(S.im) : "memory");
        asm volatile("st.shared.v2.f32 [%0], {%1,%2};" ::"r"(sb + OFF_CARRY + 512 + t * 8), "f"(S1.re), "f"(S1.im) : "memory");
        mbar_arrive(sb + OFF_CBAR);
        if (t == 0) TS(3, 3);
      } else {
        if (lane == 0) TG(2);
        const uint4* gwp = reinterpret_cast<const uint4*>(gate_w) + (lane & 7);
        uint4 gw[4];
#pragma unroll
        for (int i = 0; i < 4; i++) gw[i] = __ldg(gwp + i * 8);
        unsigned par;
        asm volatile("ld.relaxed.gpu.global.u32 %0, [%1];" : "=r"(par) : "l"(g_epoch + b) : "memory");
        const uint32_t dk = __ldg(reinterpret_cast<const uint32_t*>(dskip + s * 64) + lane), bb = __ldg(reinterpret_cast<const uint32_t*>(b2 + s * 64) + lane);
        asm volatile("barrier.cluster.wait.aligned;" ::: "memory");
        const int row = s * 16 + (lane >> 3);
        const uint32_t xr0 = sb + OFF_X + row * 128 + (((lane & 7) ^ (row & 7)) << 4), xr1 = (xr0 + 512) ^ 64;
        float z[4] = {0.f, 0.f, 0.f, 0.f};
#pragma unroll
        for (int kb = 0; kb < 8; kb++) {
          const uint32_t wv[4] = {gw[kb & 3].x, gw[kb & 3].y, gw[kb & 3].z, gw[kb & 3].w};
          if (kb < 4) gw[kb] = __ldg(gwp + (kb + 4) * 8);
          mbar_wait(sb + OFF_XFULL + 8 * kb, 0);
          if ((PF & 2) && kb == PFK && elect_one()) {
            l2_prefetch(pf_w1 + b * 7168, 14336);
            l2_prefetch(pf_cre + b * 2048, 4096);
            l2_prefetch(pf_cim + b * 2048, 4096);
            l2_prefetch(pf_w2 + b * 7168, 14336);
          }
          const uint32_t xo = ((kb + xrot) & 7) * 16384;
#pragma unroll
          for (int r = 0; r < 4; r++) {
            const uint4 a = lds_u4(((r & 1) ? xr1 : xr0) + xo + (r >> 1) * 1024);
            const uint32_t p = bf2_fma(a.w, wv[3], bf2_fma(a.z, wv[2], bf2_fma(a.y, wv[1], bf2_mul(a.x, wv[0]))));
            z[r] += bf_lo(p); z[r] += bf_hi(p);
          }
        }
        if (lane == 0) asm volatile("st.shared.u32 [%0], %1;" ::"r"(sb + OFF_EPOCH), "r"(par + 1) : "memory");
        par = (par + 1) & 1;
        {
          float y0 = (lane & 4) ? z[1] : z[0], y1 = (lane & 4) ? z[3] : z[2];
          y0 += __shfl_xor_sync(0xffffffffu, (lane & 4) ? z[0] : z[1], 4);
          y1 += __shfl_xor_sync(0xffffffffu, (lane & 4) ? z[2] : z[3], 4);
          float zz = (lane & 2) ? y1 : y0;
          zz += __shfl_xor_sync(0xffffffffu, (lane & 2) ? y0 : y1, 2);
          zz += __shfl_xor_sync(0xffffffffu, zz, 1);
          const float rho = 4.f * expf(zz > 40.f ? 40.f : zz);
          if ((lane & 1) == 0)
            asm volatile("st.relaxed.gpu.global.u32 [%0], %1;" ::"l"(g_gate + m * 128 + row + (lane & 4) + (lane & 2) * 4), "r"((__float_as_uint(rho) & ~1u) | par) : "memory");
        }
        if (lane == 0) TS(3, 0);
        mbar_wait(sb + OFF_GBAR, 0);
        asm volatile("st.shared.v2.u32 [%0], {%1,%2};" ::"r"(sb + OFF_DB + lane * 8), "r"(dk), "r"(bf2_add(bb, bb)) : "memory");
        uint32_t g0, g1, g2, g3;
        int tries = 0;
#pragma unroll 1
        do {
          asm volatile("ld.relaxed.gpu.global.v4.u32 {%0,%1,%2,%3}, [%4];" : "=r"(g0), "=r"(g1), "=r"(g2), "=r"(g3) : "l"(g_gate + m * 128 + lane * 4) : "memory");
        } while ((((g0 ^ par) | (g1 ^ par) | (g2 ^ par) | (g3 ^ par)) & 1) && ++tries < 200000);
        asm volatile("st.shared.v2.u32 [%0], {%1,%2};" ::"r"(sb + OFF_GS + lane * 8), "r"(pack_bf16(__uint_as_float(g0), __uint_as_float(g1))),
                     "r"(pack_bf16(__uint_as_float(g2), __uint_as_float(g3))) : "memory");
        mbar_arrive(sb + OFF_CBAR);
        if (lane == 0) TS(3, 4);
      }
    } else {
      asm volatile("barrier.cluster.wait.aligned;" ::: "memory");
      if (elect_one()) {
        TS(2, 1);
        const uint32_t t0 = clock();
#pragma unroll 1
        for (int u = 0; u < 8; u++) {
          if (u >= 1) while ((uint32_t)clock() - t0 < D0 + (u - 1) * D1) {}
          mbar_expect_tx(sb + OFF_XFULL + 8 * u, 16384);
          tma5d_mc(sb + OFF_X + ((u + xrot) & 7) * 16384 + rank * 8192, &maps.x, u * 64, 2 * m + rank, sb + OFF_XFULL + 8 * u);
          if (u < 6) {
            mbar_expect_tx(sb + OFF_FULL + 8 * u, 16384);
            tma2d(sb + OFF_RING + u * 16384, &maps.bre, u * 64, s * 64, sb + OFF_FULL + 8 * u);
            tma2d(sb + OFF_RING + u * 16384 + 8192, &maps.bim, u * 64, s * 64, sb + OFF_FULL + 8 * u);
          } else if (PF & 4) {
            asm volatile("cp.async.bulk.prefetch.tensor.2d.L2.global [%0, {%1,%2}];" ::"l"((m & 1) ? &maps.bim : &maps.bre), "r"(u * 64), "r"(s * 64) : "memory");
          }
        }
        TS(2, 5);
        const int piece0 = ((sp + 1) & 3) * 2 + (rank ^ 1);
        int slot = 0; uint32_t ph = 0;
#pragma unroll 1
        for (int u = 6; u < 27; u++) {
          const uint32_t fb = sb + OFF_FULL + 8 * slot, dst = sb + OFF_RING + slot * 16384;
          mbar_wait(sb + OFF_EMPTY + 8 * slot, ph);
          TS2(0, u);
          if (u < 8) {
            mbar_expect_tx(fb, 16384);
            tma2d(dst, &maps.bre, u * 64, s * 64, fb);
            tma2d(dst + 8192, &maps.bim, u * 64, s * 64, fb);
          } else if (u < 16) {
            mbar_expect_tx(fb, 12288);
            tma3d(dst, &maps.w1b, 0, (u - 8) * 64, s * 7, fb);
          } else if (u < 24) {
            mbar_expect_tx(fb, 16384);
            tma2d(dst, &maps.w1a, s * 224 + 96, ((u - xrot) & 7) * 64, fb);
            tma2d(dst + 8192, &maps.w1a, s * 224 + 160, ((u - xrot) & 7) * 64, fb);
          } else if (u == 25) {
            mbar_expect_tx(fb, 16384);
            tma2d(dst, &maps.cre, s * 64, piece0 * 64, fb);
            tma2d(dst + 8192, &maps.cim, s * 64, piece0 * 64, fb);
          } else {
            mbar_expect_tx(fb, 14336);
            tma2d(dst, &maps.w2, piece0 * 64, s * 224 + (u - 24) * 56, fb);
          }
          if (++slot == NSLOT) { slot = 0; ph ^= 1; }
        }
#pragma unroll 1
        for (int p = 1; p < 8; p++) {
          const int piece = ((sp + 1 + (p >> 1)) & 3) * 2 + ((rank ^ p ^ 1) & 1), grp = p % 3;
          const uint32_t fb = sb + OFF_XFULL + 8 * p, dst = grp == 1 ? sb + OFF_X + 2 * 16384 : sb + OFF_RING + grp * 24576;
          if (p >= 3) mbar_wait(sb + OFF_EMPTY + 8 * (p - 3), 0);
          else if (p == 2) mbar_wait(sb + OFF_EMPTY + 40, 1);
          TS2(0, 32 + p);
          mbar_expect_tx(fb, 45056);
          tma2d(dst, &maps.w2, piece * 64, s * 224, fb);
          tma2d(dst + 16384, &maps.cre, s * 64, piece * 64, fb);
          tma2d(dst + 24576, &maps.cim, s * 64, piece * 64, fb);
          tma2d(dst + 32768, &maps.w2, piece * 64, s * 224 + 112, fb);
        }
        TS(2, 2);
      }
    }
  }
}

typedef CUresult (*EncFn)(CUtensorMap*, CUtensorMapDataType, cuuint32_t, void*, const cuuint64_t*, const cuuint64_t*, const cuuint32_t*,
                          const cuuint32_t*, CUtensorMapInterleave, CUtensorMapSwizzle, CUtensorMapL2promotion, CUtensorMapFloatOOBfill);

void encode(EncFn f, CUtensorMap* mp, const void* p, int rank, const cuuint64_t* dims, const cuuint64_t* strides, const cuuint32_t* box, CUtensorMapSwizzle sw) {
  cuuint32_t es[5] = {1, 1, 1, 1, 1};
  f(mp, CU_TENSOR_MAP_DATA_TYPE_BFLOAT16, rank, const_cast<void*>(p), dims, strides, box, es, CU_TENSOR_MAP_INTERLEAVE_NONE, sw,
    CU_TENSOR_MAP_L2_PROMOTION_L2_128B, CU_TENSOR_MAP_FLOAT_OOB_FILL_NONE);
}

}

extern "C" void kernel_launch(void* const* d_in, const int* in_sizes, int n_in, void* d_out, int out_size) {
  typedef const __nv_bfloat16* bp;
  bp x = (bp)d_in[0], lre = (bp)d_in[1], lim = (bp)d_in[2], bre = (bp)d_in[3], bim = (bp)d_in[4], cre = (bp)d_in[5], cim = (bp)d_in[6],
     ldt = (bp)d_in[7], dsk = (bp)d_in[8], w1 = (bp)d_in[10], b1 = (bp)d_in[11], w2 = (bp)d_in[12], b2 = (bp)d_in[13], gw = (bp)d_in[14];
  static EncFn enc = nullptr;
  if (!enc) {
    void* f = nullptr;
    cudaDriverEntryPointQueryResult qr;
    cudaGetDriverEntryPoint("cuTensorMapEncodeTiled", &f, cudaEnableDefault, &qr);
    enc = (EncFn)f;
    cudaFuncSetAttribute(fused_kernel, cudaFuncAttributeMaxDynamicSharedMemorySize, SMEM_BYTES);
  }
  Maps maps;
  {
    cuuint64_t d[5] = {DM, 2, 4, 8, SEQ / 64}, st[4] = {DM * 2, 16 * DM * 2, 2 * DM * 2, 64 * DM * 2};
    cuuint32_t bx[5] = {64, 2, 4, 8, 1};
    encode(enc, &maps.x, x, 5, d, st, bx, CU_TENSOR_MAP_SWIZZLE_128B);
  }
  {
    cuuint64_t d[2] = {DM, DM}, st[1] = {DM * 2};
    cuuint32_t bx[2] = {64, 64};
    encode(enc, &maps.bre, bre, 2, d, st, bx, CU_TENSOR_MAP_SWIZZLE_128B);
    encode(enc, &maps.bim, bim, 2, d, st, bx, CU_TENSOR_MAP_SWIZZLE_128B);
    encode(enc, &maps.cre, cre, 2, d, st, bx, CU_TENSOR_MAP_SWIZZLE_128B);
    encode(enc, &maps.cim, cim, 2, d, st, bx, CU_TENSOR_MAP_SWIZZLE_128B);
  }
  {
    cuuint64_t d[2] = {FF, DM}, st[1] = {FF * 2};
    cuuint32_t bx[2] = {64, 64};
    encode(enc, &maps.w1a, w1, 2, d, st, bx, CU_TENSOR_MAP_SWIZZLE_128B);
    cuuint64_t d3[3] = {32, DM, FF / 32}, st3[2] = {FF * 2, 64};
    cuuint32_t bx3[3] = {32, 64, 3};
    encode(enc, &maps.w1b, w1, 3, d3, st3, bx3, CU_TENSOR_MAP_SWIZZLE_64B);
  }
  {
    cuuint64_t d[2] = {DM, FF}, st[1] = {DM * 2};
    cuuint32_t bx[2] = {64, 112};
    encode(enc, &maps.w2, w2, 2, d, st, bx, CU_TENSOR_MAP_SWIZZLE_128B);
  }
  fused_kernel<<<128, 384, SMEM_BYTES>>>(lre, lim, ldt, dsk, b1, b2, gw, w1, w2, cre, cim, (float*)d_out, maps);
}
```

```cpp
#include <cuda_runtime.h>
#include <cuda_bf16.h>
#include <cuda.h>
#include <stdint.h>

#define MAP 1
#define D0 600
#define D1 500
#define PF 6
#define PFK 5
#define GELUP 0
#define EW 1
#define K1E 0
#define K2E 1
#define QS 1
#define GAP 8
#define TP 9
#define TW 0

namespace {

constexpr int SEQ = 2048, DM = 512, FF = 1792;
constexpr int NSLOT = 6;
constexpr uint32_t OFF_X = 0, OFF_RING = 131072, OFF_MISC = 229376;
constexpr uint32_t OFF_XFULL = OFF_MISC, OFF_FULL = OFF_XFULL + 64, OFF_RBAR = OFF_FULL + 48, OFF_EMPTY = OFF_RBAR + 16, OFF_KBAR = OFF_EMPTY + 48,
                   OFF_GBAR = OFF_KBAR + 16, OFF_LBAR = OFF_GBAR + 8, OFF_CBAR = OFF_LBAR + 8, OFF_EPOCH = OFF_CBAR + 8;
constexpr uint32_t OFF_LC = OFF_MISC + 256;
constexpr uint32_t OFF_GS = OFF_LC;
constexpr uint32_t OFF_DB = OFF_LC + 512;
constexpr uint32_t OFF_CARRY = OFF_LC + 1024;
constexpr uint32_t OFF_DBG = OFF_CARRY + 1024;
constexpr uint32_t SMEM_BYTES = OFF_DBG + 768;
static_assert(SMEM_BYTES <= 232448, "smem");

struct Maps { CUtensorMap x, bre, bim, w1b, w1a, w2, cre, cim; };

__device__ uint4 g_part[16 * 8 * 3 * 1024];
__device__ float2 g_end[8 * 16 * 64];
__device__ unsigned g_gate[SEQ];
__device__ unsigned g_epoch[128];
#define TG(role) do {} while (0)
#define TS2(role, i) do {} while (0)
#define TS(role, i) do {} while (0)
#define TDUMP() do {} while (0)
#define TR(i) do {} while (0)
#define TRD() do {} while (0)

__device__ __forceinline__ void mbar_init(uint32_t bar, uint32_t cnt) { asm volatile("mbarrier.init.shared::cta.b64 [%0], %1;" ::"r"(bar), "r"(cnt)); }
__device__ __forceinline__ void mbar_expect_tx(uint32_t bar, uint32_t bytes) { asm volatile("mbarrier.arrive.expect_tx.shared::cta.b64 _, [%0], %1;" ::"r"(bar), "r"(bytes) : "memory"); }
__device__ __forceinline__ void mbar_arrive(uint32_t bar) { asm volatile("mbarrier.arrive.shared::cta.b64 _, [%0];" ::"r"(bar) : "memory"); }
__device__ __forceinline__ void mbar_arrive_cl(uint32_t cbar) { asm volatile("mbarrier.arrive.shared::cluster.b64 _, [%0];" ::"r"(cbar) : "memory"); }
__device__ __forceinline__ void mbar_wait(uint32_t bar, uint32_t parity) {
  asm volatile(
      "{\n.reg .pred p;\n.reg .u32 c;\n"
      "mbarrier.try_wait.parity.shared::cta.b64 p, [%0], %1;\n"
      "@p bra.uni LAB_DONE;\n"
      "mov.u32 c, 0;\n"
      "LAB_WAIT:\n"
      "mbarrier.try_wait.parity.shared::cta.b64 p, [%0], %1;\n"
      "@p bra.uni LAB_DONE;\n"
      "add.u32 c, c, 1;\nsetp.lt.u32 p, c, 200000;\n@p bra.uni LAB_WAIT;\n"
      "LAB_DONE:\n}" ::"r"(bar), "r"(parity) : "memory");
}
__device__ __forceinline__ void tma2d(uint32_t dst, const CUtensorMap* m, int c0, int c1, uint32_t bar) {
  asm volatile("cp.async.bulk.tensor.2d.shared::cluster.global.mbarrier::complete_tx::bytes [%0], [%1, {%3,%4}], [%2];"
               ::"r"(dst), "l"(m), "r"(bar), "r"(c0), "r"(c1) : "memory");
}
__device__ __forceinline__ void tma3d(uint32_t dst, const CUtensorMap* m, int c0, int c1, int c2, uint32_t bar) {
  asm volatile("cp.async.bulk.tensor.3d.shared::cluster.global.mbarrier::complete_tx::bytes [%0], [%1, {%3,%4,%5}], [%2];"
               ::"r"(dst), "l"(m), "r"(bar), "r"(c0), "r"(c1), "r"(c2) : "memory");
}
__device__ __forceinline__ void tma5d_mc(uint32_t dst, const CUtensorMap* m, int c0, int c4, uint32_t bar) {
  asm volatile("cp.async.bulk.tensor.5d.shared::cluster.global.mbarrier::complete_tx::bytes.multicast::cluster [%0], [%1, {%3,%5,%5,%5,%4}], [%2], %6;"
               ::"r"(dst), "l"(m), "r"(bar), "r"(c0), "r"(c4), "r"(0), "h"((uint16_t)3) : "memory");
}
__device__ __forceinline__ void l2_prefetch(const void* p, uint32_t bytes) { asm volatile("cp.async.bulk.prefetch.L2.global [%0], %1;" ::"l"(p), "r"(bytes) : "memory"); }
__device__ __forceinline__ bool elect_one() {
  uint32_t pred;
  asm volatile("{.reg .pred P; elect.sync _|P, 0xffffffff; selp.u32 %0, 1, 0, P;}" : "=r"(pred));
  return pred != 0;
}
__device__ __forceinline__ void wg_fence() { asm volatile("wgmma.fence.sync.aligned;" ::: "memory"); }
__device__ __forceinline__ void wg_commit() { asm volatile("wgmma.commit_group.sync.aligned;" ::: "memory"); }
template <int N> __device__ __forceinline__ void wg_wait() { asm volatile("wgmma.wait_group.sync.aligned %0;" ::"n"(N) : "memory"); }
__device__ __forceinline__ void pin(float& a) { asm volatile("" : "+f"(a)::"memory"); }
__device__ __forceinline__ void pin(uint32_t& a) { asm volatile("" : "+r"(a)::"memory"); }
template <int N> __device__ __forceinline__ void reg_fence(float (&d)[N]) {
#pragma unroll
  for (int i = 0; i < N; i++) pin(d[i]);
}
__device__ __forceinline__ void bar_sync(int id, int n) { asm volatile("bar.sync %0, %1;" ::"r"(id), "r"(n) : "memory"); }
__device__ __forceinline__ void bar_arrive(int id, int n) { asm volatile("bar.arrive %0, %1;" ::"r"(id), "r"(n) : "memory"); }
constexpr uint32_t DH128 = (1024 >> 4) | (1u << 30), DH64 = (512 >> 4) | (2u << 30);
__host__ __device__ constexpr uint32_t lbo(uint32_t bytes) { return (bytes >> 4) << 20; }
__device__ __forceinline__ uint32_t pack_bf16(float lo, float hi) { uint32_t r; asm("cvt.rn.bf16x2.f32 %0, %1, %2;" : "=r"(r) : "f"(hi), "f"(lo)); return r; }
__device__ __forceinline__ float bf_lo(uint32_t v) { return __uint_as_float(v << 16); }
__device__ __forceinline__ float bf_hi(uint32_t v) { return __uint_as_float(v & 0xffff0000u); }
__device__ __forceinline__ float bf_ld(const __nv_bfloat16* p) { return __bfloat162float(__ldg(p)); }
__device__ __forceinline__ uint32_t late16(uint32_t bar) {
  uint32_t r;
  asm volatile("{.reg .pred p; mbarrier.test_wait.parity.shared::cta.b64 p, [%1], 0; selp.u32 %0, 16, 0, p;}" : "=r"(r) : "r"(bar) : "memory");
  return r;
}
__device__ __forceinline__ float2 lds_f2(uint32_t a) { float2 v; asm volatile("ld.shared.v2.f32 {%0,%1}, [%2];" : "=f"(v.x), "=f"(v.y) : "r"(a)); return v; }
__device__ __forceinline__ uint32_t lds_h(uint32_t a) { uint32_t v; asm volatile("ld.shared.u16 %0, [%1];" : "=r"(v) : "r"(a)); return v; }
__device__ __forceinline__ uint32_t lds_u(uint32_t a) { uint32_t v; asm volatile("ld.shared.u32 %0, [%1];" : "=r"(v) : "r"(a)); return v; }
__device__ __forceinline__ uint4 lds_u4(uint32_t a) { uint4 v; asm volatile("ld.shared.v4.u32 {%0,%1,%2,%3}, [%4];" : "=r"(v.x), "=r"(v.y), "=r"(v.z), "=r"(v.w) : "r"(a)); return v; }
__device__ __forceinline__ void st_b128(uint4* p, uint32_t a, uint32_t b, uint32_t c, uint32_t d) {
  asm volatile("st.relaxed.gpu.global.v4.b32 [%0], {%1,%2,%3,%4};" ::"l"(p), "r"(a), "r"(b), "r"(c), "r"(d) : "memory");
}
__device__ __forceinline__ void ld_b128(const uint4* p, uint32_t& a, uint32_t& b, uint32_t& c, uint32_t& d) {
  asm volatile("{.reg .b64 l, h; .reg .b128 v; ld.relaxed.gpu.global.b128 v, [%4]; mov.b128 {l,h}, v; mov.b64 {%0,%1}, l; mov.b64 {%2,%3}, h;}"
               : "=r"(a), "=r"(b), "=r"(c), "=r"(d) : "l"(p) : "memory");
}
__device__ __forceinline__ float tanh_fast(float x) { float y; asm("tanh.approx.f32 %0, %1;" : "=f"(y) : "f"(x)); return y; }
__device__ __forceinline__ float gelu2(float v) {
  float p = fmaf(v * v, 0.0356774081363f, 0.7978845608029f);
  return fmaf(v, tanh_fast(v * p), v);
}
__device__ __forceinline__ uint32_t bf2_mul(uint32_t a, uint32_t b) { uint32_t r; asm("mul.rn.bf16x2 %0, %1, %2;" : "=r"(r) : "r"(a), "r"(b)); return r; }
__device__ __forceinline__ uint32_t bf2_add(uint32_t a, uint32_t b) { uint32_t r; asm("add.rn.bf16x2 %0, %1, %2;" : "=r"(r) : "r"(a), "r"(b)); return r; }
__device__ __forceinline__ uint32_t bf2_fma(uint32_t a, uint32_t b, uint32_t c) { uint32_t r; asm("fma.rn.bf16x2 %0, %1, %2, %3;" : "=r"(r) : "r"(a), "r"(b), "r"(c)); return r; }
__device__ __forceinline__ uint32_t gelu2_pair(float a, float b) {
  return pack_bf16(gelu2(a), gelu2(b));
}
struct cplx { float re, im; };
__device__ __forceinline__ cplx cmul(cplx a, cplx b) { return {fmaf(a.re, b.re, -a.im * b.im), fmaf(a.re, b.im, a.im * b.re)}; }
__device__ __forceinline__ cplx cfma(cplx a, cplx b, cplx c) {
  return {fmaf(a.re, b.re, fmaf(-a.im, b.im, c.re)), fmaf(a.re, b.im, fmaf(a.im, b.re, c.im))};
}
__device__ __forceinline__ cplx make_lam(float lre, float lim, float ldt) {
  float dt = __bfloat162float(__float2bfloat16_rn(expf(ldt)));
  float mag = expf(dt * lre), sn, cs;
  sincospif(dt * lim * 0.31830988618379067f, &sn, &cs);
  return {mag * cs, mag * sn};
}

template<int TA,int TB,uint32_t AH,uint32_t BH> __device__ __forceinline__ void wgmma_n64_ss(float (&d)[32], uint32_t al, uint32_t ao, uint32_t bl, uint32_t bo, int scale_d){
  asm volatile("{.reg .pred p; .reg .b32 t, v; .reg .b64 da, db; setp.ne.b32 p, %36, 0; add.u32 t, %32, %33; mov.b64 da, {t, %39}; add.u32 v, %34, %35; mov.b64 db, {v, %40};\n"
   "wgmma.mma_async.sync.aligned.m64n64k16.f32.bf16.bf16 {%0,%1,%2,%3,%4,%5,%6,%7,%8,%9,%10,%11,%12,%13,%14,%15,%16,%17,%18,%19,%20,%21,%22,%23,%24,%25,%26,%27,%28,%29,%30,%31}, da, db, p, 1, 1, %37, %38;}"
   : "+f"(d[0]),"+f"(d[1]),"+f"(d[2]),"+f"(d[3]),"+f"(d[4]),"+f"(d[5]),"+f"(d[6]),"+f"(d[7]),"+f"(d[8]),"+f"(d[9]),"+f"(d[10]),"+f"(d[11]),"+f"(d[12]),"+f"(d[13]),"+f"(d[14]),"+f"(d[15]),"+f"(d[16]),"+f"(d[17]),"+f"(d[18]),"+f"(d[19]),"+f"(d[20]),"+f"(d[21]),"+f"(d[22]),"+f"(d[23]),"+f"(d[24]),"+f"(d[25]),"+f"(d[26]),"+f"(d[27]),"+f"(d[28]),"+f"(d[29]),"+f"(d[30]),"+f"(d[31])
   : "r"(al),"r"(ao >> 4),"r"(bl),"r"(bo >> 4),"r"(scale_d),"n"(TA),"n"(TB),"n"(AH),"n"(BH));
}
template<int TB,uint32_t BH> __device__ __forceinline__ void wgmma_n64_rs(float (&d)[32], uint32_t a0,uint32_t a1,uint32_t a2,uint32_t a3, uint32_t bl, uint32_t bo, int scale_d){
  asm volatile("{.reg .pred p; .reg .b32 t; .reg .b64 db; setp.ne.b32 p, %38, 0; add.u32 t, %36, %37; mov.b64 db, {t, %40};\n"
   "wgmma.mma_async.sync.aligned.m64n64k16.f32.bf16.bf16 {%0,%1,%2,%3,%4,%5,%6,%7,%8,%9,%10,%11,%12,%13,%14,%15,%16,%17,%18,%19,%20,%21,%22,%23,%24,%25,%26,%27,%28,%29,%30,%31}, {%32,%33,%34,%35}, db, p, 1, 1, %39;}"
   : "+f"(d[0]),"+f"(d[1]),"+f"(d[2]),"+f"(d[3]),"+f"(d[4]),"+f"(d[5]),"+f"(d[6]),"+f"(d[7]),"+f"(d[8]),"+f"(d[9]),"+f"(d[10]),"+f"(d[11]),"+f"(d[12]),"+f"(d[13]),"+f"(d[14]),"+f"(d[15]),"+f"(d[16]),"+f"(d[17]),"+f"(d[18]),"+f"(d[19]),"+f"(d[20]),"+f"(d[21]),"+f"(d[22]),"+f"(d[23]),"+f"(d[24]),"+f"(d[25]),"+f"(d[26]),"+f"(d[27]),"+f"(d[28]),"+f"(d[29]),"+f"(d[30]),"+f"(d[31])
   : "r"(a0),"r"(a1),"r"(a2),"r"(a3),"r"(bl),"r"(bo >> 4),"r"(scale_d),"n"(TB),"n"(BH));
}
template<int TA,int TB,uint32_t AH,uint32_t BH> __device__ __forceinline__ void wgmma_n96_ss(float (&d)[48], uint32_t al, uint32_t ao, uint32_t bl, uint32_t bo, int scale_d){
  asm volatile("{.reg .pred p; .reg .b32 t, v; .reg .b64 da, db; setp.ne.b32 p, %52, 0; add.u32 t, %48, %49; mov.b64 da, {t, %55}; add.u32 v, %50, %51; mov.b64 db, {v, %56};\n"
   "wgmma.mma_async.sync.aligned.m64n96k16.f32.bf16.bf16 {%0,%1,%2,%3,%4,%5,%6,%7,%8,%9,%10,%11,%12,%13,%14,%15,%16,%17,%18,%19,%20,%21,%22,%23,%24,%25,%26,%27,%28,%29,%30,%31,%32,%33,%34,%35,%36,%37,%38,%39,%40,%41,%42,%43,%44,%45,%46,%47}, da, db, p, 1, 1, %53, %54;}"
   : "+f"(d[0]),"+f"(d[1]),"+f"(d[2]),"+f"(d[3]),"+f"(d[4]),"+f"(d[5]),"+f"(d[6]),"+f"(d[7]),"+f"(d[8]),"+f"(d[9]),"+f"(d[10]),"+f"(d[11]),"+f"(d[12]),"+f"(d[13]),"+f"(d[14]),"+f"(d[15]),"+f"(d[16]),"+f"(d[17]),"+f"(d[18]),"+f"(d[19]),"+f"(d[20]),"+f"(d[21]),"+f"(d[22]),"+f"(d[23]),"+f"(d[24]),"+f"(d[25]),"+f"(d[26]),"+f"(d[27]),"+f"(d[28]),"+f"(d[29]),"+f"(d[30]),"+f"(d[31]),"+f"(d[32]),"+f"(d[33]),"+f"(d[34]),"+f"(d[35]),"+f"(d[36]),"+f"(d[37]),"+f"(d[38]),"+f"(d[39]),"+f"(d[40]),"+f"(d[41]),"+f"(d[42]),"+f"(d[43]),"+f"(d[44]),"+f"(d[45]),"+f"(d[46]),"+f"(d[47])
   : "r"(al),"r"(ao >> 4),"r"(bl),"r"(bo >> 4),"r"(scale_d),"n"(TA),"n"(TB),"n"(AH),"n"(BH));
}
template<int TA,int TB,uint32_t AH,uint32_t BH> __device__ __forceinline__ void wgmma_n128_ss(float (&d)[64], uint32_t al, uint32_t ao, uint32_t bl, uint32_t bo, int scale_d){
  asm volatile("{.reg .pred p; .reg .b32 t, v; .reg .b64 da, db; setp.ne.b32 p, %68, 0; add.u32 t, %64, %65; mov.b64 da, {t, %71}; add.u32 v, %66, %67; mov.b64 db, {v, %72};\n"
   "wgmma.mma_async.sync.aligned.m64n128k16.f32.bf16.bf16 {%0,%1,%2,%3,%4,%5,%6,%7,%8,%9,%10,%11,%12,%13,%14,%15,%16,%17,%18,%19,%20,%21,%22,%23,%24,%25,%26,%27,%28,%29,%30,%31,%32,%33,%34,%35,%36,%37,%38,%39,%40,%41,%42,%43,%44,%45,%46,%47,%48,%49,%50,%51,%52,%53,%54,%55,%56,%57,%58,%59,%60,%61,%62,%63}, da, db, p, 1, 1, %69, %70;}"
   : "+f"(d[0]),"+f"(d[1]),"+f"(d[2]),"+f"(d[3]),"+f"(d[4]),"+f"(d[5]),"+f"(d[6]),"+f"(d[7]),"+f"(d[8]),"+f"(d[9]),"+f"(d[10]),"+f"(d[11]),"+f"(d[12]),"+f"(d[13]),"+f"(d[14]),"+f"(d[15]),"+f"(d[16]),"+f"(d[17]),"+f"(d[18]),"+f"(d[19]),"+f"(d[20]),"+f"(d[21]),"+f"(d[22]),"+f"(d[23]),"+f"(d[24]),"+f"(d[25]),"+f"(d[26]),"+f"(d[27]),"+f"(d[28]),"+f"(d[29]),"+f"(d[30]),"+f"(d[31]),"+f"(d[32]),"+f"(d[33]),"+f"(d[34]),"+f"(d[35]),"+f"(d[36]),"+f"(d[37]),"+f"(d[38]),"+f"(d[39]),"+f"(d[40]),"+f"(d[41]),"+f"(d[42]),"+f"(d[43]),"+f"(d[44]),"+f"(d[45]),"+f"(d[46]),"+f"(d[47]),"+f"(d[48]),"+f"(d[49]),"+f"(d[50]),"+f"(d[51]),"+f"(d[52]),"+f"(d[53]),"+f"(d[54]),"+f"(d[55]),"+f"(d[56]),"+f"(d[57]),"+f"(d[58]),"+f"(d[59]),"+f"(d[60]),"+f"(d[61]),"+f"(d[62]),"+f"(d[63])
   : "r"(al),"r"(ao >> 4),"r"(bl),"r"(bo >> 4),"r"(scale_d),"n"(TA),"n"(TB),"n"(AH),"n"(BH));
}

__global__ void __cluster_dims__(2, 1, 1) __launch_bounds__(384, 1)
fused_kernel(const __nv_bfloat16* __restrict__ lam_re, const __nv_bfloat16* __restrict__ lam_im, const __nv_bfloat16* __restrict__ log_dt,
             const __nv_bfloat16* __restrict__ dskip, const __nv_bfloat16* __restrict__ b1, const __nv_bfloat16* __restrict__ b2,
             const __nv_bfloat16* __restrict__ gate_w, const __nv_bfloat16* __restrict__ pf_w1, const __nv_bfloat16* __restrict__ pf_w2,
             const __nv_bfloat16* __restrict__ pf_cre, const __nv_bfloat16* __restrict__ pf_cim, float* __restrict__ out,
             const __grid_constant__ Maps maps) {
  extern __shared__ __align__(1024) unsigned char smem_raw[];
  const uint32_t sb = (uint32_t)__cvta_generic_to_shared(smem_raw);
  const int b = blockIdx.x;
  const int rank = b & 1, cl = b >> 1;
  const int sp = (cl & 1) | ((cl >> 2) & 2), m = ((cl >> 1) & 3) | ((cl >> 4) << 2);
  const int s = sp * 2 + rank;
  const int warp = __shfl_sync(0xffffffffu, (int)(threadIdx.x >> 5), 0);
  const int lane = threadIdx.x & 31;
  const int xrot = 6 - 2 * sp;

  if (elect_one()) {
    if (warp == 8) TS(2, 0);
    if (warp < 3) {
      asm volatile("prefetch.tensormap [%0];" ::"l"(&maps.x + warp) : "memory");
      mbar_init(sb + OFF_GBAR + 8 * warp, warp < 2 ? 64 : 96);
    }
    const uint32_t c = warp < 8 ? 1 : warp < 11 ? 8 : 4;
    mbar_init(sb + OFF_XFULL + 16 * warp, c);
    mbar_init(sb + OFF_XFULL + 16 * warp + 8, c);
    asm volatile("fence.mbarrier_init.release.cluster;" ::: "memory");
  }
  __syncwarp();
  asm volatile("barrier.cluster.arrive.relaxed.aligned;" ::: "memory");

  if (warp < 8) {
    const int wg = warp >> 2, w = warp & 3, q = lane & 3, gr = lane >> 2;
    uint32_t bv[28];
#pragma unroll
    for (int j = 0; j < 28; j++) bv[j] = __ldg(reinterpret_cast<const uint32_t*>(b1 + s * 224 + j * 8) + q);
    asm volatile("setmaxnreg.inc.sync.aligned.u32 224;");
    asm volatile("barrier.cluster.wait.aligned;" ::: "memory");
    TS(wg, 0);
    auto release = [&](int slot) { if (lane == 0) mbar_arrive(sb + OFF_EMPTY + 8 * slot); };
    const uint32_t xw = sb + OFF_X + wg * 8192, fullb = sb + OFF_FULL;
    const uint32_t dxw = (xw & 0x3FFFF) >> 4, dring = ((sb + OFF_RING) & 0x3FFFF) >> 4;

    float ure[32], uim[32], aa[48], ab[64];
    cplx lam[2], coef[2], l16[2], l32[2], lq[2], pre[2], e[2];
    uint32_t sh16, mhi;

#pragma unroll
    for (int kb = 0; kb < 8; kb++) {
      const int slot = kb % NSLOT;
      mbar_wait(sb + OFF_XFULL + 8 * kb, 0);
      if (kb == 0) TS(wg, 18);
      mbar_wait(fullb + 8 * slot, (kb / NSLOT) & 1);
      TS2(2, kb);
      if (kb == 0) TS(wg, 1);
      wg_fence();
      const uint32_t dxa = dxw + ((kb + xrot) & 7) * 1024;
#pragma unroll
      for (int kk = 0; kk < 4; kk++) {
        wgmma_n64_ss<0, 0, DH128, DH128>(ure, dring, slot * 16384 + kk * 32, dxa, kk * 32, (kb | kk) != 0);
        wgmma_n64_ss<0, 0, DH128, DH128>(uim, dring, slot * 16384 + 8192 + kk * 32, dxa, kk * 32, (kb | kk) != 0);
      }
      wg_commit();
      if (kb > 0) { wg_wait<1>(); release((kb - 1) % NSLOT); }
      if (kb == 1) { sh16 = late16(sb + OFF_XFULL); mhi = 0xffffffffu << sh16; }
      if (kb == 1 || (kb >= 3 && kb < 6)) {
#pragma unroll
        for (int j = 0; j < 28; j++) if (j / 7 == (kb == 1 ? 0 : kb - 2)) {
          pin(bv[j]);
          float* d = j < 12 ? aa + 4 * j : ab + 4 * (j - 12);
          d[0] = d[2] = __uint_as_float(bv[j] << sh16); d[1] = d[3] = __uint_as_float(bv[j] & mhi);
          pin(d[0]); pin(d[1]); pin(d[2]); pin(d[3]);
        }
      }
      if (kb == 5) {
        mbar_wait(sb + OFF_LBAR, 0);
#pragma unroll
        for (int h = 0; h < 2; h++) {
          const uint4 v = lds_u4(sb + OFF_LC + (w * 16 + gr + 8 * h) * 16);
          lam[h] = cplx{__uint_as_float(v.x), __uint_as_float(v.y)};
          coef[h] = cplx{__uint_as_float(v.z), __uint_as_float(v.w)};
        }
      }
      if (kb == 6) {
#pragma unroll
        for (int h = 0; h < 2; h++) {
          pin(lam[h].re); pin(lam[h].im);
          cplx t = cmul(lam[h], lam[h]); t = cmul(t, t); t = cmul(t, t);
          l16[h] = cmul(t, t);
          pin(l16[h].re); pin(l16[h].im);
        }
      }
      if (kb == 7) {
#pragma unroll
        for (int h = 0; h < 2; h++) {
          pin(l16[h].re); pin(l16[h].im);
          l32[h] = cmul(l16[h], l16[h]);
          const cplx a = (q & 1) ? l16[h] : cplx{1.f, 0.f}, c = (q & 2) ? l32[h] : cplx{1.f, 0.f};
          lq[h] = cmul(cmul(a, c), coef[h]);
          pin(lq[h].re); pin(lq[h].im);
        }
      }
    }
    TS(wg, 2);
    auto scale_u = [&](int i0, int i1) {
#pragma unroll
      for (int i = 0; i < 32; i++) if (i >= i0 && i < i1) {
        pin(ure[i]); pin(uim[i]);
        const cplx v = cmul(coef[(i >> 1) & 1], cplx{ure[i], uim[i]});
        ure[i] = v.re; uim[i] = v.im;
        pin(ure[i]); pin(uim[i]);
      }
    };
#pragma unroll
    for (int kb = 0; kb < 8; kb++) {
      const int u = 8 + kb, slot = u % NSLOT;
      mbar_wait(fullb + 8 * slot, (u / NSLOT) & 1);
      wg_fence();
      const uint32_t dxa = dxw + ((kb + xrot) & 7) * 1024;
#pragma unroll
      for (int kk = 0; kk < 4; kk++)
        wgmma_n96_ss<0, 1, DH128, DH64>(aa, dxa, kk * 32, dring, slot * 16384 + kk * 1024 + lbo(4096), 1);
      wg_commit();
      wg_wait<1>();
      release((u - 1) % NSLOT);
      if (kb == 0) {
        reg_fence(ure); reg_fence(uim);
#pragma unroll
        for (int h = 0; h < 2; h++) e[h] = cplx{ure[2 * h], uim[2 * h]};
      }
      if (kb == 0 || kb == 2 || kb == 3) {
        const int ch = kb ? kb - 1 : 0;
#pragma unroll
        for (int t = 1 + 5 * ch; t < 6 + 5 * ch; t++)
#pragma unroll
          for (int h = 0; h < 2; h++) { const int i = 4 * (t >> 1) + 2 * h + (t & 1); e[h] = cfma(lam[h], e[h], cplx{ure[i], uim[i]}); }
#pragma unroll
        for (int h = 0; h < 2; h++) { pin(e[h].re); pin(e[h].im); }
      } else if (kb == 4) {
#pragma unroll
        for (int h = 0; h < 2; h++) {
          cplx y = {__shfl_up_sync(0xffffffffu, e[h].re, 1, 4), __shfl_up_sync(0xffffffffu, e[h].im, 1, 4)};
          if (q >= 1) e[h] = cfma(l16[h], y, e[h]);
          y = cplx{__shfl_up_sync(0xffffffffu, e[h].re, 2, 4), __shfl_up_sync(0xffffffffu, e[h].im, 2, 4)};
          if (q >= 2) e[h] = cfma(l32[h], y, e[h]);
        }
        if (q == 3) {
#pragma unroll
          for (int h = 0; h < 2; h++)
            asm volatile("st.shared.v2.f32 [%0], {%1,%2};" ::"r"(sb + OFF_CARRY + wg * 512 + (w * 16 + gr + 8 * h) * 8), "f"(e[h].re), "f"(e[h].im) : "memory");
          mbar_arrive(sb + OFF_GBAR);
        }
#pragma unroll
        for (int h = 0; h < 2; h++) {
          const cplx y = {__shfl_up_sync(0xffffffffu, e[h].re, 1, 4), __shfl_up_sync(0xffffffffu, e[h].im, 1, 4)};
          pre[h] = (q >= 1) ? cmul(coef[h], y) : cplx{0.f, 0.f};
          pin(pre[h].re); pin(pre[h].im);
        }
        TS(wg, 3);
      } else if (kb > 4) {
        scale_u(kb == 5 ? 0 : kb == 6 ? 4 : 12, kb == 5 ? 4 : kb == 6 ? 12 : 20);
      }
    }
    TS(wg, 4);
    uint32_t H[56];
    cplx hst[2];
    const uint32_t hst_addr = xw + (w * 16 + (lane & 15)) * 128 + (((lane >> 4) ^ (lane & 7)) << 4);
    uint32_t peer;
    asm volatile("mapa.shared::cluster.u32 %0, %1, %2;" : "=r"(peer) : "r"(sb), "r"(rank ^ 1));
    auto credit = [&]() { if (lane == 0) mbar_arrive_cl(peer + OFF_KBAR + wg * 8); };
#pragma unroll
    for (int kb = 0; kb < 8; kb++) {
      const int u = 16 + kb, slot = u % NSLOT;
      mbar_wait(fullb + 8 * slot, (u / NSLOT) & 1);
      wg_fence();
#pragma unroll
      for (int kk = 0; kk < 4; kk++)
        wgmma_n128_ss<0, 1, DH128, DH128>(ab, dxw, kb * 16384 + kk * 32, dring, slot * 16384 + kk * 2048 + lbo(8192), 1);
      wg_commit();
      wg_wait<1>();
      release((u - 1) % NSLOT);
      if (kb == 6) credit();
      if (kb == 0) scale_u(20, 32);
      if (kb < 5 && kb != 1) {
        const int ch = kb ? kb - 1 : 0;
#pragma unroll
        for (int i = ch * 6; i < ch * 6 + 6; i++) {
          pin(aa[2 * i]); pin(aa[2 * i + 1]);
          H[i] = gelu2_pair(aa[2 * i], aa[2 * i + 1]);
          pin(H[i]);
        }
      }
      if (kb >= 4) {
        if (kb == 4) {
          TS(wg, 5);
          mbar_wait(sb + OFF_CBAR, 0);
          TS(wg, 6);
#pragma unroll
          for (int h = 0; h < 2; h++) {
            const float2 c = lds_f2(sb + OFF_CARRY + wg * 512 + (w * 16 + gr + 8 * h) * 8);
            hst[h] = cfma(lq[h], cplx{c.x, c.y}, pre[h]);
          }
        }
        const int j0 = (kb - 4) * 2;
        uint32_t rr[4], ri[4];
#pragma unroll
        for (int jj = 0; jj < 2; jj++) {
          const int j = j0 + jj;
          const uint32_t g2 = lds_u(sb + OFF_GS + (wg * 64 + j * 8 + q * 2) * 2);
#pragma unroll
          for (int h = 0; h < 2; h++) {
            const int i = 4 * j + 2 * h;
            const cplx h0 = cfma(lam[h], hst[h], cplx{ure[i], uim[i]});
            hst[h] = cfma(lam[h], h0, cplx{ure[i + 1], uim[i + 1]});
            rr[jj * 2 + h] = bf2_mul(pack_bf16(h0.re, hst[h].re), g2);
            ri[jj * 2 + h] = bf2_mul(pack_bf16(h0.im, hst[h].im), g2 ^ 0x80008000u);
          }
        }
        const uint32_t a = hst_addr ^ (j0 << 4);
        asm volatile("stmatrix.sync.aligned.m8n8.x4.shared.b16 [%0], {%1,%2,%3,%4};" ::"r"(a), "r"(rr[0]), "r"(rr[1]), "r"(rr[2]), "r"(rr[3]) : "memory");
        asm volatile("stmatrix.sync.aligned.m8n8.x4.shared.b16 [%0], {%1,%2,%3,%4};" ::"r"(a + 16384), "r"(ri[0]), "r"(ri[1]), "r"(ri[2]), "r"(ri[3]) : "memory");
      }
    }
    TS(wg, 7);

    uint4* const psend = g_part + (size_t)(m * 8 + rank) * 3072 + warp * 128 + lane;
    const uint4* const precv = g_part + (size_t)(m * 8 + s) * 3072 + warp * 128 + lane;
    const uint32_t pbuf = OFF_X + 5 * 16384 + warp * 2048 + lane * 16;
    const uint32_t dx0 = ((sb + OFF_X) & 0x3FFFF) >> 4;
    const uint32_t xsk = hst_addr + (6 + rank) * 16384;
    float o[32], fin[32], rho[2];
    uint32_t tr[8];
    uint32_t r0[16], pt[16], sum[16], tag;
    auto recv_issue = [&](uint32_t (&r)[16], int k) {
#pragma unroll
      for (int i = 0; i < 4; i++) ld_b128(precv + k * 1024 + i * 32, r[4 * i], r[4 * i + 1], r[4 * i + 2], r[4 * i + 3]);
    };
    auto stale = [&](uint32_t (&r)[16]) {
      uint32_t t0, t1, r_;
      asm("lop3.b32 %0, %1, %2, %3, 0x7e;" : "=r"(t0) : "r"(r[0]), "r"(r[4]), "r"(tag));
      asm("lop3.b32 %0, %1, %2, %3, 0x7e;" : "=r"(t1) : "r"(r[8]), "r"(r[12]), "r"(tag));
      asm volatile("{.reg .pred p; .reg .b32 t; lop3.b32 t, %1, %2, 1, 0xa8; setp.ne.u32 p, t, 0; vote.sync.any.pred p, p, 0xffffffff; selp.u32 %0, 1, 0, p;}" : "=r"(r_) : "r"(t0), "r"(t1));
      return r_ != 0;
    };
    auto recv_check = [&](uint32_t (&r)[16], int k) {
      if (__builtin_expect(stale(r), 0)) {
        int tries = 0;
#pragma unroll 1
        do { recv_issue(r, k); } while (stale(r) && ++tries < 200000);
      }
    };
    auto gelu_b = [&](int i0, int i1) {
#pragma unroll
      for (int i = i0; i < i1; i++) {
        pin(ab[2 * i]); pin(ab[2 * i + 1]);
        H[24 + i] = gelu2_pair(ab[2 * i], ab[2 * i + 1]);
        pin(H[24 + i]);
      }
    };
    auto mma = [&](float (&o)[32], uint32_t wo, int k0, int k1, int acc) {
      wg_fence();
#pragma unroll
      for (int k = k0; k < k1; k++) {
        if (k >= 6 && k < 14) {
          const int kk = k - 6;
          wgmma_n64_ss<1, 0, DH128, DH128>(o, dxw, (kk >> 2) * 16384 + (kk & 3) * 2048, dx0, wo + 16384 + (kk >> 2) * 8192 + (kk & 3) * 32, 1);
        } else {
          const int kk = k < 6 ? k : k - 8;
          wgmma_n64_rs<1, DH128>(o, H[4 * kk], H[4 * kk + 1], H[4 * kk + 2], H[4 * kk + 3], dx0, wo + (kk / 7) * 32768 + (kk % 7) * 2048, k != 0 || acc);
        }
      }
      wg_commit();
    };
    auto send_peer = [&]() {
#pragma unroll
      for (int i = 0; i < 4; i++)
        asm volatile("st.async.shared::cluster.mbarrier::complete_tx::bytes.v4.b32 [%0], {%1,%2,%3,%4}, [%5];" ::"r"(peer + pbuf + i * 512),
                     "r"(pack_bf16(o[8 * i], o[8 * i + 1])), "r"(pack_bf16(o[8 * i + 2], o[8 * i + 3])), "r"(pack_bf16(o[8 * i + 4], o[8 * i + 5])),
                     "r"(pack_bf16(o[8 * i + 6], o[8 * i + 7])), "r"(peer + OFF_RBAR + wg * 8) : "memory");
    };
    auto recv_peer = [&](int k) {
      mbar_wait(sb + OFF_RBAR + wg * 8, k & 1);
#pragma unroll
      for (int i = 0; i < 4; i++) { const uint4 v = lds_u4(sb + pbuf + i * 512); pt[4 * i] = v.x; pt[4 * i + 1] = v.y; pt[4 * i + 2] = v.z; pt[4 * i + 3] = v.w; }
    };
    auto stage = [&](int p) { return (p % 3) == 1 ? 2u * 16384 : OFF_RING + (p % 3) * 24576; };
    uint32_t xs[8];
    uint4 db[4];
#pragma unroll
    for (int p = 0; p < 6; p++) {
      const uint32_t wo = stage(p);
      if (p == 0) {
        mbar_wait(fullb, 0);
        mma(o, wo, 0, 3, 0);
        asm volatile("fence.proxy.async.shared::cta;" ::: "memory");
        wg_wait<1>(); release(5);
        gelu_b(0, 4);
        mma(o, wo, 3, 6, 0);
        gelu_b(4, 10);
        bar_sync(1 + wg, 128);
        mbar_wait(fullb + 8, 0);
        mma(o, wo, 6, 10, 0);
        gelu_b(10, 16);
        mma(o, wo, 10, 15, 0);
        gelu_b(16, 24);
        mbar_wait(fullb + 16, 0);
        mma(o, wo, 15, 18, 0);
        gelu_b(24, 32);
        if (wg == 1) bar_sync(4, 256);
        mma(o, wo, 18, 22, 0);
      } else {
        TR(0);
        if (p & 1) mbar_wait(sb + OFF_XFULL + 8 * p, 1);
        TR(1);
        bar_sync(3 + wg, 256);
        mma(o, wo, 0, 22, 0);
      }
      bar_arrive(4 - wg, 256);
      TR(2);
      if (p != TP) TS(wg, 8 + p);
      if ((p & 1) == 0) {
        if ((threadIdx.x & 127) == 0) mbar_expect_tx(sb + OFF_RBAR + wg * 8, 8192);
        if (p >= 2) {
          uint32_t lz;
          asm volatile("{.reg .b32 c; mov.u32 c, %%clock; and.b32 %0, c, %1;}" : "=r"(lz) : "r"(db[0].y));
#pragma unroll
          for (int jj = 0; jj < 4; jj++) {
            const int j = (p - 2) * 2 + jj;
#pragma unroll
            for (int h = 0; h < 2; h++) {
              const uint32_t xd = bf2_fma(xs[2 * jj + h], db[jj].x, lz);
              fin[4 * j + 2 * h] = fmaf(bf_lo(xd), rho[h], __uint_as_float(db[jj].z));
              fin[4 * j + 2 * h + 1] = fmaf(bf_hi(xd), rho[h], __uint_as_float(db[jj].w));
              pin(fin[4 * j + 2 * h]); pin(fin[4 * j + 2 * h + 1]);
            }
          }
        }
        TR(3);
        mbar_wait(sb + OFF_KBAR + wg * 8, (p >> 1) & 1);
        TR(4);
      } else {
        if (p == 1) tag = lds_u(sb + OFF_EPOCH);
        mbar_wait(sb + OFF_XFULL + 8 * (p + 1), 1);
        TR(3);
        recv_peer(p >> 1);
        TR(4);
        if (p == 1) {
#pragma unroll
          for (int h = 0; h < 2; h++) rho[h] = 0.5f * bf_lo(lds_h(sb + OFF_GS + (wg * 64 + w * 16 + gr + 8 * h) * 2));
        }
        if (p < 5) {
#pragma unroll
          for (int i = 0; i < 2; i++)
            asm volatile("ldmatrix.sync.aligned.m8n8.x4.shared.b16 {%0,%1,%2,%3}, [%4];" : "=r"(xs[4 * i]), "=r"(xs[4 * i + 1]), "=r"(xs[4 * i + 2]), "=r"(xs[4 * i + 3])
                         : "r"(xsk ^ ((p - 1 + i) << 5)));
#pragma unroll
          for (int jj = 0; jj < 4; jj++) db[jj] = lds_u4(sb + OFF_DB + ((p - 1) * 2 + jj) * 64 + q * 16);
        }
      }
      TR(5);
      wg_wait<0>();
      TR(6);
      if (p < 5) release(p);
      reg_fence(o);
      if ((p & 1) == 0) {
        send_peer();
        if (p == 4) {
          recv_issue(sum, 0);
          if (K1E) recv_issue(r0, 1);
#pragma unroll
          for (int h = 0; h < 2; h++) { rho[h] = __fdividef(1.f, 2.f + rho[h]); pin(rho[h]); }
        }
      } else {
#pragma unroll
        for (int i = 0; i < 4; i++) {
#pragma unroll
          for (int c = 4 * i; c < 4 * i + 4; c++) pt[c] = bf2_add(pt[c], pack_bf16(o[2 * c], o[2 * c + 1]));
          asm("lop3.b32 %0, %0, 1, %1, 0xb8;" : "+r"(pt[4 * i]) : "r"(tag));
          st_b128(psend + (((sp + 1 + (p >> 1)) & 3) * 6 + (p >> 1)) * 1024 + i * 32, pt[4 * i], pt[4 * i + 1], pt[4 * i + 2], pt[4 * i + 3]);
        }
        __syncwarp();
        credit();
        if (p == 5) {
          if ((threadIdx.x & 127) == 0) mbar_expect_tx(sb + OFF_RBAR + wg * 8, 8192);
          if (!K1E) recv_issue(r0, 1);
        }
      }
      TR(7);
    }
    {
      uint32_t r1[16];
      bar_sync(3 + wg, 256);
      mma(o, stage(6), 0, 22, 0);
      TS(wg, 14);
      mbar_wait(sb + OFF_XFULL + 56, 1);
      mbar_wait(sb + OFF_KBAR + wg * 8, 1);
      mma(fin, stage(7), 0, GAP, 1);
      wg_wait<1>();
      reg_fence(o);
      if (K2E) recv_issue(r1, 2);
      send_peer();
      mma(fin, stage(7), GAP, 22, 1);
      if (wg == 0) bar_arrive(4, 256);
      TS(wg, 15);
      tag = lds_u(sb + OFF_EPOCH);
      recv_check(sum, 0); recv_check(r0, 1);
      if (!K2E) recv_issue(r1, 2);
#pragma unroll
      for (int i = 0; i < 16; i++) sum[i] = bf2_add(sum[i], r0[i]);
      recv_peer(3);
      recv_check(r1, 2);
#pragma unroll
      for (int i = 0; i < 16; i++) sum[i] = bf2_add(sum[i], bf2_add(r1[i], pt[i]));
      wg_wait<0>();
      reg_fence(fin);
    }
    {
      TS(wg, 16);
      const uint32_t tb = sb + OFF_RING + 3 * 16384 + warp * 4096;
      const uint32_t ta = tb + gr * 256 + ((gr & 3) << 5) + q * 8;
      const uint32_t la = tb + (lane >> 3) * 256 + (((lane & 7) << 4) ^ ((lane >> 3) << 5));
      float* op = out + (size_t)(m * 128 + wg * 64 + (lane >> 4) * 16 + w * 4 + ((lane >> 3) & 1)) * DM + s * 64 + (lane & 7) * 4;
#pragma unroll
      for (int qq = 0; qq < 4; qq += QS) {
#pragma unroll
        for (int qt = qq; qt < qq + QS; qt++) {
          const int h = qt & 1, ch = qt >> 1;
#pragma unroll
          for (int j = 0; j < 4; j++) {
            const int i = ch * 8 + j * 2 + h;
            asm volatile("st.shared.v2.f32 [%0], {%1,%2};" ::"r"((ta ^ (j << 5)) + h * 2048 + ch * 128),
                         "f"((fin[2 * i] + bf_lo(sum[i])) * rho[h]), "f"((fin[2 * i + 1] + bf_hi(sum[i])) * rho[h]) : "memory");
          }
        }
        __syncwarp();
#pragma unroll
        for (int qt = qq; qt < qq + QS; qt++) {
          const int h = qt & 1, ch = qt >> 1;
#pragma unroll
          for (int r = 0; r < 2; r++)
            *reinterpret_cast<uint4*>(op + (r * 32 + h * 2) * DM + ch * 32) = lds_u4(la + (h * 2 + r) * 1024 + ch * 128);
        }
      }
      if (threadIdx.x == 128) g_epoch[b] = tag;
      TS(wg, 17); TG(wg); TRD(); TDUMP();
    }
  } else {
    asm volatile("setmaxnreg.dec.sync.aligned.u32 56;");
    int wsel = warp;
    asm("" : "+r"(wsel));
    if (wsel > 8) {
      if (warp != 11) {
        const int t = threadIdx.x - 288;
        unsigned par;
        asm volatile("ld.relaxed.gpu.global.u32 %0, [%1];" : "=r"(par) : "l"(g_epoch + b) : "memory");
        const float pr = bf_ld(lam_re + s * 64 + t), pi = bf_ld(lam_im + s * 64 + t), pd = bf_ld(log_dt + s * 64 + t);
        asm volatile("barrier.cluster.wait.aligned;" ::: "memory");
        par = (par + 1) & 1;
        cplx l64 = make_lam(pr, pi, pd);
        {
          const float inv = __fdividef(1.f, fmaf(pr, pr, pi * pi));
          const cplx cf = cmul(cplx{l64.re - 1.f, l64.im}, cplx{pr * inv, -pi * inv});
          asm volatile("st.shared.v4.f32 [%0], {%1,%2,%3,%4};" ::"r"(sb + OFF_LC + t * 16), "f"(l64.re), "f"(l64.im), "f"(cf.re), "f"(cf.im) : "memory");
          mbar_arrive(sb + OFF_LBAR);
        }
#pragma unroll
        for (int i = 0; i < 6; i++) l64 = cmul(l64, l64);
        cplx l128 = cmul(l64, l64);
        pin(l128.re); pin(l128.im);
        mbar_wait(sb + OFF_GBAR, 0);
        const float2 e0 = lds_f2(sb + OFF_CARRY + t * 8), e1 = lds_f2(sb + OFF_CARRY + 512 + t * 8);
        float2* eb = g_end + s * 1024 + t;
        {
          const cplx e = cfma(l64, cplx{e0.x, e0.y}, cplx{e1.x, e1.y});
          const unsigned long long v = ((unsigned long long)__float_as_uint(e.im) << 32) | ((__float_as_uint(e.re) & ~1u) | par);
          asm volatile("st.relaxed.gpu.global.b64 [%0], %1;" ::"l"(eb + m * 64), "l"(v) : "memory");
        }
        if (t == 0) TS(3, 1);
        cplx S = {0.f, 0.f};
        {
          unsigned long long v[15];
          uint32_t bad;
          int tries = 0;
          const float2* e15 = eb + (m - 15) * 64;
#pragma unroll 1
          do {
#pragma unroll
            for (int i = 0; i < 15; i++) {
              v[i] = par;
              asm volatile("{.reg .pred p; setp.ge.s32 p, %2, %3; @p ld.relaxed.gpu.global.b64 %0, [%1];}" : "+l"(v[i]) : "l"(e15 + i * 64), "r"(m), "r"(15 - i) : "memory");
            }
            bad = 0;
#pragma unroll
            for (int i = 0; i < 15; i++) bad |= (uint32_t)v[i] ^ par;
          } while ((bad & 1) && ++tries < 200000);
          if (t == 0) TS(3, 2);
#pragma unroll
          for (int i = 0; i < 15; i++) S = cfma(l128, S, cplx{__uint_as_float((uint32_t)v[i] & ~1u), __uint_as_float((uint32_t)(v[i] >> 32))});
        }
        const cplx S1 = cfma(l64, S, cplx{e0.x, e0.y});
        asm volatile("st.shared.v2.f32 [%0], {%1,%2};" ::"r"(sb + OFF_CARRY + t * 8), "f"(S.re), "f"(S.im) : "memory");
        asm volatile("st.shared.v2.f32 [%0], {%1,%2};" ::"r"(sb + OFF_CARRY + 512 + t * 8), "f"(S1.re), "f"(S1.im) : "memory");
        mbar_arrive(sb + OFF_CBAR);
        if (t == 0) TS(3, 3);
      } else {
        if (lane == 0) TG(2);
        const uint4* gwp = reinterpret_cast<const uint4*>(gate_w) + (lane & 7);
        uint4 gw[4];
#pragma unroll
        for (int i = 0; i < 4; i++) gw[i] = __ldg(gwp + i * 8);
        unsigned par;
        asm volatile("ld.relaxed.gpu.global.u32 %0, [%1];" : "=r"(par) : "l"(g_epoch + b) : "memory");
        const uint32_t dk = __ldg(reinterpret_cast<const uint32_t*>(dskip + s * 64) + lane), bb = __ldg(reinterpret_cast<const uint32_t*>(b2 + s * 64) + lane);
        asm volatile("barrier.cluster.wait.aligned;" ::: "memory");
        const int row = s * 16 + (lane >> 3);
        const uint32_t xr0 = sb + OFF_X + row * 128 + (((lane & 7) ^ (row & 7)) << 4), xr1 = (xr0 + 512) ^ 64;
        float z[4] = {0.f, 0.f, 0.f, 0.f};
#pragma unroll
        for (int kb = 0; kb < 8; kb++) {
          const uint32_t wv[4] = {gw[kb & 3].x, gw[kb & 3].y, gw[kb & 3].z, gw[kb & 3].w};
          if (kb < 4) gw[kb] = __ldg(gwp + (kb + 4) * 8);
          mbar_wait(sb + OFF_XFULL + 8 * kb, 0);
          if ((PF & 2) && kb == PFK && elect_one()) {
            l2_prefetch(pf_w1 + b * 7168, 14336);
            l2_prefetch(pf_cre + b * 2048, 4096);
            l2_prefetch(pf_cim + b * 2048, 4096);
            l2_prefetch(pf_w2 + b * 7168, 14336);
          }
          const uint32_t xo = ((kb + xrot) & 7) * 16384;
#pragma unroll
          for (int r = 0; r < 4; r++) {
            const uint4 a = lds_u4(((r & 1) ? xr1 : xr0) + xo + (r >> 1) * 1024);
            const uint32_t p = bf2_fma(a.w, wv[3], bf2_fma(a.z, wv[2], bf2_fma(a.y, wv[1], bf2_mul(a.x, wv[0]))));
            z[r] += bf_lo(p); z[r] += bf_hi(p);
          }
        }
        if (lane == 0) asm volatile("st.shared.u32 [%0], %1;" ::"r"(sb + OFF_EPOCH), "r"(par + 1) : "memory");
        par = (par + 1) & 1;
        {
          float y0 = (lane & 4) ? z[1] : z[0], y1 = (lane & 4) ? z[3] : z[2];
          y0 += __shfl_xor_sync(0xffffffffu, (lane & 4) ? z[0] : z[1], 4);
          y1 += __shfl_xor_sync(0xffffffffu, (lane & 4) ? z[2] : z[3], 4);
          float zz = (lane & 2) ? y1 : y0;
          zz += __shfl_xor_sync(0xffffffffu, (lane & 2) ? y0 : y1, 2);
          zz += __shfl_xor_sync(0xffffffffu, zz, 1);
          const float rho = 4.f * expf(zz > 40.f ? 40.f : zz);
          if ((lane & 1) == 0)
            asm volatile("st.relaxed.gpu.global.u32 [%0], %1;" ::"l"(g_gate + m * 128 + row + (lane & 4) + (lane & 2) * 4), "r"((__float_as_uint(rho) & ~1u) | par) : "memory");
        }
        if (lane == 0) TS(3, 0);
        mbar_wait(sb + OFF_GBAR, 0);
        asm volatile("st.shared.v4.b32 [%0], {%1,%2,%3,%4};" ::"r"(sb + OFF_DB + lane * 16), "r"(dk), "r"(0), "f"(2.f * bf_lo(bb)), "f"(2.f * bf_hi(bb)) : "memory");
        uint32_t g0, g1, g2, g3;
        int tries = 0;
#pragma unroll 1
        do {
          asm volatile("ld.relaxed.gpu.global.v4.u32 {%0,%1,%2,%3}, [%4];" : "=r"(g0), "=r"(g1), "=r"(g2), "=r"(g3) : "l"(g_gate + m * 128 + lane * 4) : "memory");
        } while ((((g0 ^ par) | (g1 ^ par) | (g2 ^ par) | (g3 ^ par)) & 1) && ++tries < 200000);
        asm volatile("st.shared.v2.u32 [%0], {%1,%2};" ::"r"(sb + OFF_GS + lane * 8), "r"(pack_bf16(__uint_as_float(g0), __uint_as_float(g1))),
                     "r"(pack_bf16(__uint_as_float(g2), __uint_as_float(g3))) : "memory");
        mbar_arrive(sb + OFF_CBAR);
        if (lane == 0) TS(3, 4);
      }
    } else {
      asm volatile("barrier.cluster.wait.aligned;" ::: "memory");
      if (elect_one()) {
        TS(2, 1);
        const uint32_t t0 = clock();
#pragma unroll 1
        for (int u = 0; u < 8; u++) {
          if (u >= 1) while ((uint32_t)clock() - t0 < D0 + (u - 1) * D1) {}
          mbar_expect_tx(sb + OFF_XFULL + 8 * u, 16384);
          tma5d_mc(sb + OFF_X + ((u + xrot) & 7) * 16384 + rank * 8192, &maps.x, u * 64, 2 * m + rank, sb + OFF_XFULL + 8 * u);
          if (u < 6) {
            mbar_expect_tx(sb + OFF_FULL + 8 * u, 16384);
            tma2d(sb + OFF_RING + u * 16384, &maps.bre, u * 64, s * 64, sb + OFF_FULL + 8 * u);
            tma2d(sb + OFF_RING + u * 16384 + 8192, &maps.bim, u * 64, s * 64, sb + OFF_FULL + 8 * u);
          } else if (PF & 4) {
            asm volatile("cp.async.bulk.prefetch.tensor.2d.L2.global [%0, {%1,%2}];" ::"l"((m & 1) ? &maps.bim : &maps.bre), "r"(u * 64), "r"(s * 64) : "memory");
          }
        }
        TS(2, 5);
        const int piece0 = ((sp + 1) & 3) * 2 + (rank ^ 1);
        int slot = 0; uint32_t ph = 0;
#pragma unroll 1
        for (int u = 6; u < 27; u++) {
          const uint32_t fb = sb + OFF_FULL + 8 * slot, dst = sb + OFF_RING + slot * 16384;
          mbar_wait(sb + OFF_EMPTY + 8 * slot, ph);
          TS2(0, u);
          if (u < 8) {
            mbar_expect_tx(fb, 16384);
            tma2d(dst, &maps.bre, u * 64, s * 64, fb);
            tma2d(dst + 8192, &maps.bim, u * 64, s * 64, fb);
          } else if (u < 16) {
            mbar_expect_tx(fb, 12288);
            tma3d(dst, &maps.w1b, 0, (u - 8) * 64, s * 7, fb);
          } else if (u < 24) {
            mbar_expect_tx(fb, 16384);
            tma2d(dst, &maps.w1a, s * 224 + 96, ((u - xrot) & 7) * 64, fb);
            tma2d(dst + 8192, &maps.w1a, s * 224 + 160, ((u - xrot) & 7) * 64, fb);
          } else if (u == 25) {
            mbar_expect_tx(fb, 16384);
            tma2d(dst, &maps.cre, s * 64, piece0 * 64, fb);
            tma2d(dst + 8192, &maps.cim, s * 64, piece0 * 64, fb);
          } else {
            mbar_expect_tx(fb, 14336);
            tma2d(dst, &maps.w2, piece0 * 64, s * 224 + (u - 24) * 56, fb);
          }
          if (++slot == NSLOT) { slot = 0; ph ^= 1; }
        }
#pragma unroll 1
        for (int p = 1; p < 8; p++) {
          const int piece = ((sp + 1 + (p >> 1)) & 3) * 2 + ((rank ^ p ^ 1) & 1), grp = p % 3;
          const uint32_t fb = sb + OFF_XFULL + 8 * p, dst = grp == 1 ? sb + OFF_X + 2 * 16384 : sb + OFF_RING + grp * 24576;
          if (p >= 3) mbar_wait(sb + OFF_EMPTY + 8 * (p - 3), 0);
          else if (p == 2) mbar_wait(sb + OFF_EMPTY + 40, 1);
          TS2(0, 32 + p);
          mbar_expect_tx(fb, 45056);
          tma2d(dst, &maps.w2, piece * 64, s * 224, fb);
          tma2d(dst + 16384, &maps.cre, s * 64, piece * 64, fb);
          tma2d(dst + 24576, &maps.cim, s * 64, piece * 64, fb);
          tma2d(dst + 32768, &maps.w2, piece * 64, s * 224 + 112, fb);
        }
        TS(2, 2);
      }
    }
  }
}

typedef CUresult (*EncFn)(CUtensorMap*, CUtensorMapDataType, cuuint32_t, void*, const cuuint64_t*, const cuuint64_t*, const cuuint32_t*,
                          const cuuint32_t*, CUtensorMapInterleave, CUtensorMapSwizzle, CUtensorMapL2promotion, CUtensorMapFloatOOBfill);

void encode(EncFn f, CUtensorMap* mp, const void* p, int rank, const cuuint64_t* dims, const cuuint64_t* strides, const cuuint32_t* box, CUtensorMapSwizzle sw) {
  cuuint32_t es[5] = {1, 1, 1, 1, 1};
  f(mp, CU_TENSOR_MAP_DATA_TYPE_BFLOAT16, rank, const_cast<void*>(p), dims, strides, box, es, CU_TENSOR_MAP_INTERLEAVE_NONE, sw,
    CU_TENSOR_MAP_L2_PROMOTION_L2_128B, CU_TENSOR_MAP_FLOAT_OOB_FILL_NONE);
}

}

extern "C" void kernel_launch(void* const* d_in, const int* in_sizes, int n_in, void* d_out, int out_size) {
  typedef const __nv_bfloat16* bp;
  bp x = (bp)d_in[0], lre = (bp)d_in[1], lim = (bp)d_in[2], bre = (bp)d_in[3], bim = (bp)d_in[4], cre = (bp)d_in[5], cim = (bp)d_in[6],
     ldt = (bp)d_in[7], dsk = (bp)d_in[8], w1 = (bp)d_in[10], b1 = (bp)d_in[11], w2 = (bp)d_in[12], b2 = (bp)d_in[13], gw = (bp)d_in[14];
  static EncFn enc = nullptr;
  if (!enc) {
    void* f = nullptr;
    cudaDriverEntryPointQueryResult qr;
    cudaGetDriverEntryPoint("cuTensorMapEncodeTiled", &f, cudaEnableDefault, &qr);
    enc = (EncFn)f;
    cudaFuncSetAttribute(fused_kernel, cudaFuncAttributeMaxDynamicSharedMemorySize, SMEM_BYTES);
  }
  Maps maps;
  {
    cuuint64_t d[5] = {DM, 2, 4, 8, SEQ / 64}, st[4] = {DM * 2, 16 * DM * 2, 2 * DM * 2, 64 * DM * 2};
    cuuint32_t bx[5] = {64, 2, 4, 8, 1};
    encode(enc, &maps.x, x, 5, d, st, bx, CU_TENSOR_MAP_SWIZZLE_128B);
  }
  {
    cuuint64_t d[2] = {DM, DM}, st[1] = {DM * 2};
    cuuint32_t bx[2] = {64, 64};
    encode(enc, &maps.bre, bre, 2, d, st, bx, CU_TENSOR_MAP_SWIZZLE_128B);
    encode(enc, &maps.bim, bim, 2, d, st, bx, CU_TENSOR_MAP_SWIZZLE_128B);
    encode(enc, &maps.cre, cre, 2, d, st, bx, CU_TENSOR_MAP_SWIZZLE_128B);
    encode(enc, &maps.cim, cim, 2, d, st, bx, CU_TENSOR_MAP_SWIZZLE_128B);
  }
  {
    cuuint64_t d[2] = {FF, DM}, st[1] = {FF * 2};
    cuuint32_t bx[2] = {64, 64};
    encode(enc, &maps.w1a, w1, 2, d, st, bx, CU_TENSOR_MAP_SWIZZLE_128B);
    cuuint64_t d3[3] = {32, DM, FF / 32}, st3[2] = {FF * 2, 64};
    cuuint32_t bx3[3] = {32, 64, 3};
    encode(enc, &maps.w1b, w1, 3, d3, st3, bx3, CU_TENSOR_MAP_SWIZZLE_64B);
  }
  {
    cuuint64_t d[2] = {DM, FF}, st[1] = {DM * 2};
    cuuint32_t bx[2] = {64, 112};
    encode(enc, &maps.w2, w2, 2, d, st, bx, CU_TENSOR_MAP_SWIZZLE_128B);
  }
  fused_kernel<<<128, 384, SMEM_BYTES>>>(lre, lim, ldt, dsk, b1, b2, gw, w1, w2, cre, cim, (float*)d_out, maps);
}
```

```cpp
#include <cuda_runtime.h>
#include <cuda_bf16.h>
#include <cuda.h>
#include <stdint.h>

#define MAP 1
#define D0 600
#define D1 500
#define PF 6
#define PFK 5
#define GELUP 0
#define EW 1
#define K1E 0
#define K2E 1
#define QS 2
#define GAP 8
#define A0 7
#define A1 5
#define OUT_TMA 1
#define TP 9
#define TW 0

namespace {

constexpr int SEQ = 2048, DM = 512, FF = 1792;
constexpr int NSLOT = 6;
constexpr uint32_t OFF_X = 0, OFF_RING = 131072, OFF_MISC = 229376;
constexpr uint32_t OFF_XFULL = OFF_MISC, OFF_FULL = OFF_XFULL + 64, OFF_RBAR = OFF_FULL + 48, OFF_EMPTY = OFF_RBAR + 16, OFF_KBAR = OFF_EMPTY + 48,
                   OFF_GBAR = OFF_KBAR + 16, OFF_LBAR = OFF_GBAR + 8, OFF_CBAR = OFF_LBAR + 8, OFF_EPOCH = OFF_CBAR + 8;
constexpr uint32_t OFF_LC = OFF_MISC + 256;
constexpr uint32_t OFF_GS = OFF_LC;
constexpr uint32_t OFF_DB = OFF_LC + 512;
constexpr uint32_t OFF_CARRY = OFF_LC + 1024;
constexpr uint32_t OFF_DBG = OFF_CARRY + 1024;
constexpr uint32_t SMEM_BYTES = OFF_DBG + 768;
static_assert(SMEM_BYTES <= 232448, "smem");

struct Maps { CUtensorMap x, bre, bim, w1b, w1a, w2, cre, cim, out; };
__host__ __device__ constexpr uint32_t stage_off(int p) { return 49152 + 45056 * (((p >> 1) & 1) + 2 * (p & 1)); }

__device__ uint4 g_part[16 * 8 * 3 * 1024];
__device__ float2 g_end[8 * 16 * 64];
__device__ unsigned g_gate[SEQ];
__device__ unsigned g_epoch[128];
#define TG(role) do {} while (0)
#define TS2(role, i) do {} while (0)
#define TS(role, i) do {} while (0)
#define TDUMP() do {} while (0)
#define TR(i) do {} while (0)
#define TRD() do {} while (0)

__device__ __forceinline__ void mbar_init(uint32_t bar, uint32_t cnt) { asm volatile("mbarrier.init.shared::cta.b64 [%0], %1;" ::"r"(bar), "r"(cnt)); }
__device__ __forceinline__ void mbar_expect_tx(uint32_t bar, uint32_t bytes) { asm volatile("mbarrier.arrive.expect_tx.shared::cta.b64 _, [%0], %1;" ::"r"(bar), "r"(bytes) : "memory"); }
__device__ __forceinline__ void mbar_arrive(uint32_t bar) { asm volatile("mbarrier.arrive.shared::cta.b64 _, [%0];" ::"r"(bar) : "memory"); }
__device__ __forceinline__ void mbar_arrive_cl(uint32_t cbar) { asm volatile("mbarrier.arrive.shared::cluster.b64 _, [%0];" ::"r"(cbar) : "memory"); }
__device__ __forceinline__ void mbar_wait(uint32_t bar, uint32_t parity) {
  asm volatile(
      "{\n.reg .pred p;\n.reg .u32 c;\n"
      "mbarrier.try_wait.parity.shared::cta.b64 p, [%0], %1;\n"
      "@p bra.uni LAB_DONE;\n"
      "mov.u32 c, 0;\n"
      "LAB_WAIT:\n"
      "mbarrier.try_wait.parity.shared::cta.b64 p, [%0], %1;\n"
      "@p bra.uni LAB_DONE;\n"
      "add.u32 c, c, 1;\nsetp.lt.u32 p, c, 200000;\n@p bra.uni LAB_WAIT;\n"
      "LAB_DONE:\n}" ::"r"(bar), "r"(parity) : "memory");
}
__device__ __forceinline__ void tma2d(uint32_t dst, const CUtensorMap* m, int c0, int c1, uint32_t bar) {
  asm volatile("cp.async.bulk.tensor.2d.shared::cluster.global.mbarrier::complete_tx::bytes [%0], [%1, {%3,%4}], [%2];"
               ::"r"(dst), "l"(m), "r"(bar), "r"(c0), "r"(c1) : "memory");
}
__device__ __forceinline__ void tma3d(uint32_t dst, const CUtensorMap* m, int c0, int c1, int c2, uint32_t bar) {
  asm volatile("cp.async.bulk.tensor.3d.shared::cluster.global.mbarrier::complete_tx::bytes [%0], [%1, {%3,%4,%5}], [%2];"
               ::"r"(dst), "l"(m), "r"(bar), "r"(c0), "r"(c1), "r"(c2) : "memory");
}
__device__ __forceinline__ void tma5d_mc(uint32_t dst, const CUtensorMap* m, int c0, int c4, uint32_t bar) {
  asm volatile("cp.async.bulk.tensor.5d.shared::cluster.global.mbarrier::complete_tx::bytes.multicast::cluster [%0], [%1, {%3,%5,%5,%5,%4}], [%2], %6;"
               ::"r"(dst), "l"(m), "r"(bar), "r"(c0), "r"(c4), "r"(0), "h"((uint16_t)3) : "memory");
}
__device__ __forceinline__ void l2_prefetch(const void* p, uint32_t bytes) { asm volatile("cp.async.bulk.prefetch.L2.global [%0], %1;" ::"l"(p), "r"(bytes) : "memory"); }
__device__ __forceinline__ bool elect_one() {
  uint32_t pred;
  asm volatile("{.reg .pred P; elect.sync _|P, 0xffffffff; selp.u32 %0, 1, 0, P;}" : "=r"(pred));
  return pred != 0;
}
__device__ __forceinline__ void wg_fence() { asm volatile("wgmma.fence.sync.aligned;" ::: "memory"); }
__device__ __forceinline__ void wg_commit() { asm volatile("wgmma.commit_group.sync.aligned;" ::: "memory"); }
template <int N> __device__ __forceinline__ void wg_wait() { asm volatile("wgmma.wait_group.sync.aligned %0;" ::"n"(N) : "memory"); }
__device__ __forceinline__ void pin(float& a) { asm volatile("" : "+f"(a)::"memory"); }
__device__ __forceinline__ void pin(uint32_t& a) { asm volatile("" : "+r"(a)::"memory"); }
template <int N> __device__ __forceinline__ void reg_fence(float (&d)[N]) {
#pragma unroll
  for (int i = 0; i < N; i++) pin(d[i]);
}
__device__ __forceinline__ void bar_sync(int id, int n) { asm volatile("bar.sync %0, %1;" ::"r"(id), "r"(n) : "memory"); }
__device__ __forceinline__ void bar_arrive(int id, int n) { asm volatile("bar.arrive %0, %1;" ::"r"(id), "r"(n) : "memory"); }
constexpr uint32_t DH128 = (1024 >> 4) | (1u << 30), DH64 = (512 >> 4) | (2u << 30);
__host__ __device__ constexpr uint32_t lbo(uint32_t bytes) { return (bytes >> 4) << 20; }
__device__ __forceinline__ uint32_t pack_bf16(float lo, float hi) { uint32_t r; asm("cvt.rn.bf16x2.f32 %0, %1, %2;" : "=r"(r) : "f"(hi), "f"(lo)); return r; }
__device__ __forceinline__ float bf_lo(uint32_t v) { return __uint_as_float(v << 16); }
__device__ __forceinline__ float bf_hi(uint32_t v) { return __uint_as_float(v & 0xffff0000u); }
__device__ __forceinline__ float bf_ld(const __nv_bfloat16* p) { return __bfloat162float(__ldg(p)); }
__device__ __forceinline__ uint32_t late16(uint32_t bar) {
  uint32_t r;
  asm volatile("{.reg .pred p; mbarrier.test_wait.parity.shared::cta.b64 p, [%1], 0; selp.u32 %0, 16, 0, p;}" : "=r"(r) : "r"(bar) : "memory");
  return r;
}
__device__ __forceinline__ float2 lds_f2(uint32_t a) { float2 v; asm volatile("ld.shared.v2.f32 {%0,%1}, [%2];" : "=f"(v.x), "=f"(v.y) : "r"(a)); return v; }
__device__ __forceinline__ uint32_t lds_h(uint32_t a) { uint32_t v; asm volatile("ld.shared.u16 %0, [%1];" : "=r"(v) : "r"(a)); return v; }
__device__ __forceinline__ uint32_t lds_u(uint32_t a) { uint32_t v; asm volatile("ld.shared.u32 %0, [%1];" : "=r"(v) : "r"(a)); return v; }
__device__ __forceinline__ uint4 lds_u4(uint32_t a) { uint4 v; asm volatile("ld.shared.v4.u32 {%0,%1,%2,%3}, [%4];" : "=r"(v.x), "=r"(v.y), "=r"(v.z), "=r"(v.w) : "r"(a)); return v; }
__device__ __forceinline__ void st_b128(uint4* p, uint32_t a, uint32_t b, uint32_t c, uint32_t d) {
  asm volatile("st.relaxed.gpu.global.v4.b32 [%0], {%1,%2,%3,%4};" ::"l"(p), "r"(a), "r"(b), "r"(c), "r"(d) : "memory");
}
__device__ __forceinline__ void ld_b128(const uint4* p, uint32_t& a, uint32_t& b, uint32_t& c, uint32_t& d) {
  asm volatile("{.reg .b64 l, h; .reg .b128 v; ld.relaxed.gpu.global.b128 v, [%4]; mov.b128 {l,h}, v; mov.b64 {%0,%1}, l; mov.b64 {%2,%3}, h;}"
               : "=r"(a), "=r"(b), "=r"(c), "=r"(d) : "l"(p) : "memory");
}
__device__ __forceinline__ float tanh_fast(float x) { float y; asm("tanh.approx.f32 %0, %1;" : "=f"(y) : "f"(x)); return y; }
__device__ __forceinline__ float gelu2(float v) {
  float p = fmaf(v * v, 0.0356774081363f, 0.7978845608029f);
  return fmaf(v, tanh_fast(v * p), v);
}
__device__ __forceinline__ uint32_t bf2_mul(uint32_t a, uint32_t b) { uint32_t r; asm("mul.rn.bf16x2 %0, %1, %2;" : "=r"(r) : "r"(a), "r"(b)); return r; }
__device__ __forceinline__ uint32_t bf2_add(uint32_t a, uint32_t b) { uint32_t r; asm("add.rn.bf16x2 %0, %1, %2;" : "=r"(r) : "r"(a), "r"(b)); return r; }
__device__ __forceinline__ uint32_t bf2_fma(uint32_t a, uint32_t b, uint32_t c) { uint32_t r; asm("fma.rn.bf16x2 %0, %1, %2, %3;" : "=r"(r) : "r"(a), "r"(b), "r"(c)); return r; }
__device__ __forceinline__ uint32_t gelu2_pair(float a, float b) {
  return pack_bf16(gelu2(a), gelu2(b));
}
struct cplx { float re, im; };
__device__ __forceinline__ cplx cmul(cplx a, cplx b) { return {fmaf(a.re, b.re, -a.im * b.im), fmaf(a.re, b.im, a.im * b.re)}; }
__device__ __forceinline__ cplx cfma(cplx a, cplx b, cplx c) {
  return {fmaf(a.re, b.re, fmaf(-a.im, b.im, c.re)), fmaf(a.re, b.im, fmaf(a.im, b.re, c.im))};
}
__device__ __forceinline__ cplx make_lam(float lre, float lim, float ldt) {
  float dt = __bfloat162float(__float2bfloat16_rn(expf(ldt)));
  float mag = expf(dt * lre), sn, cs;
  sincospif(dt * lim * 0.31830988618379067f, &sn, &cs);
  return {mag * cs, mag * sn};
}

template<int TA,int TB,uint32_t AH,uint32_t BH> __device__ __forceinline__ void wgmma_n64_ss(float (&d)[32], uint32_t al, uint32_t ao, uint32_t bl, uint32_t bo, int scale_d){
  asm volatile("{.reg .pred p; .reg .b32 t, v; .reg .b64 da, db; setp.ne.b32 p, %36, 0; add.u32 t, %32, %33; mov.b64 da, {t, %39}; add.u32 v, %34, %35; mov.b64 db, {v, %40};\n"
   "wgmma.mma_async.sync.aligned.m64n64k16.f32.bf16.bf16 {%0,%1,%2,%3,%4,%5,%6,%7,%8,%9,%10,%11,%12,%13,%14,%15,%16,%17,%18,%19,%20,%21,%22,%23,%24,%25,%26,%27,%28,%29,%30,%31}, da, db, p, 1, 1, %37, %38;}"
   : "+f"(d[0]),"+f"(d[1]),"+f"(d[2]),"+f"(d[3]),"+f"(d[4]),"+f"(d[5]),"+f"(d[6]),"+f"(d[7]),"+f"(d[8]),"+f"(d[9]),"+f"(d[10]),"+f"(d[11]),"+f"(d[12]),"+f"(d[13]),"+f"(d[14]),"+f"(d[15]),"+f"(d[16]),"+f"(d[17]),"+f"(d[18]),"+f"(d[19]),"+f"(d[20]),"+f"(d[21]),"+f"(d[22]),"+f"(d[23]),"+f"(d[24]),"+f"(d[25]),"+f"(d[26]),"+f"(d[27]),"+f"(d[28]),"+f"(d[29]),"+f"(d[30]),"+f"(d[31])
   : "r"(al),"r"(ao >> 4),"r"(bl),"r"(bo >> 4),"r"(scale_d),"n"(TA),"n"(TB),"n"(AH),"n"(BH));
}
template<int TB,uint32_t BH> __device__ __forceinline__ void wgmma_n64_rs(float (&d)[32], uint32_t a0,uint32_t a1,uint32_t a2,uint32_t a3, uint32_t bl, uint32_t bo, int scale_d){
  asm volatile("{.reg .pred p; .reg .b32 t; .reg .b64 db; setp.ne.b32 p, %38, 0; add.u32 t, %36, %37; mov.b64 db, {t, %40};\n"
   "wgmma.mma_async.sync.aligned.m64n64k16.f32.bf16.bf16 {%0,%1,%2,%3,%4,%5,%6,%7,%8,%9,%10,%11,%12,%13,%14,%15,%16,%17,%18,%19,%20,%21,%22,%23,%24,%25,%26,%27,%28,%29,%30,%31}, {%32,%33,%34,%35}, db, p, 1, 1, %39;}"
   : "+f"(d[0]),"+f"(d[1]),"+f"(d[2]),"+f"(d[3]),"+f"(d[4]),"+f"(d[5]),"+f"(d[6]),"+f"(d[7]),"+f"(d[8]),"+f"(d[9]),"+f"(d[10]),"+f"(d[11]),"+f"(d[12]),"+f"(d[13]),"+f"(d[14]),"+f"(d[15]),"+f"(d[16]),"+f"(d[17]),"+f"(d[18]),"+f"(d[19]),"+f"(d[20]),"+f"(d[21]),"+f"(d[22]),"+f"(d[23]),"+f"(d[24]),"+f"(d[25]),"+f"(d[26]),"+f"(d[27]),"+f"(d[28]),"+f"(d[29]),"+f"(d[30]),"+f"(d[31])
   : "r"(a0),"r"(a1),"r"(a2),"r"(a3),"r"(bl),"r"(bo >> 4),"r"(scale_d),"n"(TB),"n"(BH));
}
template<int TA,int TB,uint32_t AH,uint32_t BH> __device__ __forceinline__ void wgmma_n96_ss(float (&d)[48], uint32_t al, uint32_t ao, uint32_t bl, uint32_t bo, int scale_d){
  asm volatile("{.reg .pred p; .reg .b32 t, v; .reg .b64 da, db; setp.ne.b32 p, %52, 0; add.u32 t, %48, %49; mov.b64 da, {t, %55}; add.u32 v, %50, %51; mov.b64 db, {v, %56};\n"
   "wgmma.mma_async.sync.aligned.m64n96k16.f32.bf16.bf16 {%0,%1,%2,%3,%4,%5,%6,%7,%8,%9,%10,%11,%12,%13,%14,%15,%16,%17,%18,%19,%20,%21,%22,%23,%24,%25,%26,%27,%28,%29,%30,%31,%32,%33,%34,%35,%36,%37,%38,%39,%40,%41,%42,%43,%44,%45,%46,%47}, da, db, p, 1, 1, %53, %54;}"
   : "+f"(d[0]),"+f"(d[1]),"+f"(d[2]),"+f"(d[3]),"+f"(d[4]),"+f"(d[5]),"+f"(d[6]),"+f"(d[7]),"+f"(d[8]),"+f"(d[9]),"+f"(d[10]),"+f"(d[11]),"+f"(d[12]),"+f"(d[13]),"+f"(d[14]),"+f"(d[15]),"+f"(d[16]),"+f"(d[17]),"+f"(d[18]),"+f"(d[19]),"+f"(d[20]),"+f"(d[21]),"+f"(d[22]),"+f"(d[23]),"+f"(d[24]),"+f"(d[25]),"+f"(d[26]),"+f"(d[27]),"+f"(d[28]),"+f"(d[29]),"+f"(d[30]),"+f"(d[31]),"+f"(d[32]),"+f"(d[33]),"+f"(d[34]),"+f"(d[35]),"+f"(d[36]),"+f"(d[37]),"+f"(d[38]),"+f"(d[39]),"+f"(d[40]),"+f"(d[41]),"+f"(d[42]),"+f"(d[43]),"+f"(d[44]),"+f"(d[45]),"+f"(d[46]),"+f"(d[47])
   : "r"(al),"r"(ao >> 4),"r"(bl),"r"(bo >> 4),"r"(scale_d),"n"(TA),"n"(TB),"n"(AH),"n"(BH));
}
template<int TA,int TB,uint32_t AH,uint32_t BH> __device__ __forceinline__ void wgmma_n128_ss(float (&d)[64], uint32_t al, uint32_t ao, uint32_t bl, uint32_t bo, int scale_d){
  asm volatile("{.reg .pred p; .reg .b32 t, v; .reg .b64 da, db; setp.ne.b32 p, %68, 0; add.u32 t, %64, %65; mov.b64 da, {t, %71}; add.u32 v, %66, %67; mov.b64 db, {v, %72};\n"
   "wgmma.mma_async.sync.aligned.m64n128k16.f32.bf16.bf16 {%0,%1,%2,%3,%4,%5,%6,%7,%8,%9,%10,%11,%12,%13,%14,%15,%16,%17,%18,%19,%20,%21,%22,%23,%24,%25,%26,%27,%28,%29,%30,%31,%32,%33,%34,%35,%36,%37,%38,%39,%40,%41,%42,%43,%44,%45,%46,%47,%48,%49,%50,%51,%52,%53,%54,%55,%56,%57,%58,%59,%60,%61,%62,%63}, da, db, p, 1, 1, %69, %70;}"
   : "+f"(d[0]),"+f"(d[1]),"+f"(d[2]),"+f"(d[3]),"+f"(d[4]),"+f"(d[5]),"+f"(d[6]),"+f"(d[7]),"+f"(d[8]),"+f"(d[9]),"+f"(d[10]),"+f"(d[11]),"+f"(d[12]),"+f"(d[13]),"+f"(d[14]),"+f"(d[15]),"+f"(d[16]),"+f"(d[17]),"+f"(d[18]),"+f"(d[19]),"+f"(d[20]),"+f"(d[21]),"+f"(d[22]),"+f"(d[23]),"+f"(d[24]),"+f"(d[25]),"+f"(d[26]),"+f"(d[27]),"+f"(d[28]),"+f"(d[29]),"+f"(d[30]),"+f"(d[31]),"+f"(d[32]),"+f"(d[33]),"+f"(d[34]),"+f"(d[35]),"+f"(d[36]),"+f"(d[37]),"+f"(d[38]),"+f"(d[39]),"+f"(d[40]),"+f"(d[41]),"+f"(d[42]),"+f"(d[43]),"+f"(d[44]),"+f"(d[45]),"+f"(d[46]),"+f"(d[47]),"+f"(d[48]),"+f"(d[49]),"+f"(d[50]),"+f"(d[51]),"+f"(d[52]),"+f"(d[53]),"+f"(d[54]),"+f"(d[55]),"+f"(d[56]),"+f"(d[57]),"+f"(d[58]),"+f"(d[59]),"+f"(d[60]),"+f"(d[61]),"+f"(d[62]),"+f"(d[63])
   : "r"(al),"r"(ao >> 4),"r"(bl),"r"(bo >> 4),"r"(scale_d),"n"(TA),"n"(TB),"n"(AH),"n"(BH));
}

__global__ void __cluster_dims__(2, 1, 1) __launch_bounds__(384, 1)
fused_kernel(const __nv_bfloat16* __restrict__ lam_re, const __nv_bfloat16* __restrict__ lam_im, const __nv_bfloat16* __restrict__ log_dt,
             const __nv_bfloat16* __restrict__ dskip, const __nv_bfloat16* __restrict__ b1, const __nv_bfloat16* __restrict__ b2,
             const __nv_bfloat16* __restrict__ gate_w, const __nv_bfloat16* __restrict__ pf_w1, const __nv_bfloat16* __restrict__ pf_w2,
             const __nv_bfloat16* __restrict__ pf_cre, const __nv_bfloat16* __restrict__ pf_cim, float* __restrict__ out,
             const __grid_constant__ Maps maps) {
  extern __shared__ __align__(1024) unsigned char smem_raw[];
  const uint32_t sb = (uint32_t)__cvta_generic_to_shared(smem_raw);
  const int b = blockIdx.x;
  const int rank = b & 1, cl = b >> 1;
  const int sp = (cl & 1) | ((cl >> 2) & 2), m = ((cl >> 1) & 3) | ((cl >> 4) << 2);
  const int s = sp * 2 + rank;
  const int warp = __shfl_sync(0xffffffffu, (int)(threadIdx.x >> 5), 0);
  const int lane = threadIdx.x & 31;
  const int xrot = 9 - 2 * sp;

  if (elect_one()) {
    if (warp == 8) TS(2, 0);
    if (warp < 3) {
      asm volatile("prefetch.tensormap [%0];" ::"l"(&maps.x + warp) : "memory");
      mbar_init(sb + OFF_GBAR + 8 * warp, warp < 2 ? 64 : 96);
    }
    const uint32_t c = warp < 8 ? 1 : warp < 11 ? 8 : 4;
    mbar_init(sb + OFF_XFULL + 16 * warp, c);
    mbar_init(sb + OFF_XFULL + 16 * warp + 8, c);
    asm volatile("fence.mbarrier_init.release.cluster;" ::: "memory");
  }
  __syncwarp();
  asm volatile("barrier.cluster.arrive.relaxed.aligned;" ::: "memory");

  if (warp < 8) {
    const int wg = warp >> 2, w = warp & 3, q = lane & 3, gr = lane >> 2;
    uint32_t bv[28];
#pragma unroll
    for (int j = 0; j < 28; j++) bv[j] = __ldg(reinterpret_cast<const uint32_t*>(b1 + s * 224 + j * 8) + q);
    asm volatile("setmaxnreg.inc.sync.aligned.u32 224;");
    asm volatile("barrier.cluster.wait.aligned;" ::: "memory");
    TS(wg, 0);
    auto release = [&](int slot) { if (lane == 0) mbar_arrive(sb + OFF_EMPTY + 8 * slot); };
    const uint32_t xw = sb + OFF_X + wg * 8192, fullb = sb + OFF_FULL;
    const uint32_t dxw = (xw & 0x3FFFF) >> 4, dring = ((sb + OFF_RING) & 0x3FFFF) >> 4;

    float ure[32], uim[32], aa[48], ab[64];
    cplx lam[2], coef[2], l16[2], l32[2], lq[2], pre[2], e[2];
    uint32_t sh16, mhi;

#pragma unroll
    for (int kb = 0; kb < 8; kb++) {
      const int slot = kb % NSLOT;
      mbar_wait(sb + OFF_XFULL + 8 * kb, 0);
      if (kb == 0) TS(wg, 18);
      mbar_wait(fullb + 8 * slot, (kb / NSLOT) & 1);
      TS2(2, kb);
      if (kb == 0) TS(wg, 1);
      wg_fence();
      const uint32_t dxa = dxw + ((kb + xrot) & 7) * 1024;
#pragma unroll
      for (int kk = 0; kk < 4; kk++) {
        wgmma_n64_ss<0, 0, DH128, DH128>(ure, dring, slot * 16384 + kk * 32, dxa, kk * 32, (kb | kk) != 0);
        wgmma_n64_ss<0, 0, DH128, DH128>(uim, dring, slot * 16384 + 8192 + kk * 32, dxa, kk * 32, (kb | kk) != 0);
      }
      wg_commit();
      if (kb > 0) { wg_wait<1>(); release((kb - 1) % NSLOT); }
      if (kb == 1) { sh16 = late16(sb + OFF_XFULL); mhi = 0xffffffffu << sh16; }
      if (kb == 1 || (kb >= 3 && kb < 6)) {
#pragma unroll
        for (int j = 0; j < 28; j++) if (j / 7 == (kb == 1 ? 0 : kb - 2)) {
          pin(bv[j]);
          float* d = j < 12 ? aa + 4 * j : ab + 4 * (j - 12);
          d[0] = d[2] = __uint_as_float(bv[j] << sh16); d[1] = d[3] = __uint_as_float(bv[j] & mhi);
          pin(d[0]); pin(d[1]); pin(d[2]); pin(d[3]);
        }
      }
      if (kb == 5) {
        mbar_wait(sb + OFF_LBAR, 0);
#pragma unroll
        for (int h = 0; h < 2; h++) {
          const uint4 v = lds_u4(sb + OFF_LC + (w * 16 + gr + 8 * h) * 16);
          lam[h] = cplx{__uint_as_float(v.x), __uint_as_float(v.y)};
          coef[h] = cplx{__uint_as_float(v.z), __uint_as_float(v.w)};
        }
      }
      if (kb == 6) {
#pragma unroll
        for (int h = 0; h < 2; h++) {
          pin(lam[h].re); pin(lam[h].im);
          cplx t = cmul(lam[h], lam[h]); t = cmul(t, t); t = cmul(t, t);
          l16[h] = cmul(t, t);
          pin(l16[h].re); pin(l16[h].im);
        }
      }
      if (kb == 7) {
#pragma unroll
        for (int h = 0; h < 2; h++) {
          pin(l16[h].re); pin(l16[h].im);
          l32[h] = cmul(l16[h], l16[h]);
          const cplx a = (q & 1) ? l16[h] : cplx{1.f, 0.f}, c = (q & 2) ? l32[h] : cplx{1.f, 0.f};
          lq[h] = cmul(cmul(a, c), coef[h]);
          pin(lq[h].re); pin(lq[h].im);
        }
      }
    }
    TS(wg, 2);
    auto scale_u = [&](int i0, int i1) {
#pragma unroll
      for (int i = 0; i < 32; i++) if (i >= i0 && i < i1) {
        pin(ure[i]); pin(uim[i]);
        const cplx v = cmul(coef[(i >> 1) & 1], cplx{ure[i], uim[i]});
        ure[i] = v.re; uim[i] = v.im;
        pin(ure[i]); pin(uim[i]);
      }
    };
#pragma unroll
    for (int kb = 0; kb < 8; kb++) {
      const int u = 8 + kb, slot = u % NSLOT;
      mbar_wait(fullb + 8 * slot, (u / NSLOT) & 1);
      wg_fence();
      const uint32_t dxa = dxw + ((kb + xrot) & 7) * 1024;
#pragma unroll
      for (int kk = 0; kk < 4; kk++)
        wgmma_n96_ss<0, 1, DH128, DH64>(aa, dxa, kk * 32, dring, slot * 16384 + kk * 1024 + lbo(4096), 1);
      wg_commit();
      wg_wait<1>();
      release((u - 1) % NSLOT);
      if (kb == 0) {
        reg_fence(ure); reg_fence(uim);
#pragma unroll
        for (int h = 0; h < 2; h++) e[h] = cplx{ure[2 * h], uim[2 * h]};
      }
      if (kb == 0 || kb == 2 || kb == 3) {
        const int ch = kb ? kb - 1 : 0;
#pragma unroll
        for (int t = 1 + 5 * ch; t < 6 + 5 * ch; t++)
#pragma unroll
          for (int h = 0; h < 2; h++) { const int i = 4 * (t >> 1) + 2 * h + (t & 1); e[h] = cfma(lam[h], e[h], cplx{ure[i], uim[i]}); }
#pragma unroll
        for (int h = 0; h < 2; h++) { pin(e[h].re); pin(e[h].im); }
      } else if (kb == 4) {
#pragma unroll
        for (int h = 0; h < 2; h++) {
          cplx y = {__shfl_up_sync(0xffffffffu, e[h].re, 1, 4), __shfl_up_sync(0xffffffffu, e[h].im, 1, 4)};
          if (q >= 1) e[h] = cfma(l16[h], y, e[h]);
          y = cplx{__shfl_up_sync(0xffffffffu, e[h].re, 2, 4), __shfl_up_sync(0xffffffffu, e[h].im, 2, 4)};
          if (q >= 2) e[h] = cfma(l32[h], y, e[h]);
        }
        if (q == 3) {
#pragma unroll
          for (int h = 0; h < 2; h++)
            asm volatile("st.shared.v2.f32 [%0], {%1,%2};" ::"r"(sb + OFF_CARRY + wg * 512 + (w * 16 + gr + 8 * h) * 8), "f"(e[h].re), "f"(e[h].im) : "memory");
          mbar_arrive(sb + OFF_GBAR);
        }
#pragma unroll
        for (int h = 0; h < 2; h++) {
          const cplx y = {__shfl_up_sync(0xffffffffu, e[h].re, 1, 4), __shfl_up_sync(0xffffffffu, e[h].im, 1, 4)};
          pre[h] = (q >= 1) ? cmul(coef[h], y) : cplx{0.f, 0.f};
          pin(pre[h].re); pin(pre[h].im);
        }
        TS(wg, 3);
      } else if (kb > 4) {
        scale_u(kb == 5 ? 0 : kb == 6 ? 4 : 12, kb == 5 ? 4 : kb == 6 ? 12 : 20);
      }
    }
    TS(wg, 4);
    uint32_t H[56];
    cplx hst[2];
    const uint32_t hst_addr = xw + (w * 16 + (lane & 15)) * 128 + (((lane >> 4) ^ (lane & 7)) << 4);
    const uint32_t him = (2 - rank) * 16384;
    uint32_t peer;
    asm volatile("mapa.shared::cluster.u32 %0, %1, %2;" : "=r"(peer) : "r"(sb), "r"(rank ^ 1));
    auto credit = [&]() { if (lane == 0) mbar_arrive_cl(peer + OFF_KBAR + wg * 8); };
#pragma unroll
    for (int kb = 0; kb < 8; kb++) {
      const int u = 16 + kb, slot = u % NSLOT;
      mbar_wait(fullb + 8 * slot, (u / NSLOT) & 1);
      wg_fence();
#pragma unroll
      for (int kk = 0; kk < 4; kk++)
        wgmma_n128_ss<0, 1, DH128, DH128>(ab, dxw, kb * 16384 + kk * 32, dring, slot * 16384 + kk * 2048 + lbo(8192), 1);
      wg_commit();
      wg_wait<1>();
      release((u - 1) % NSLOT);
      if (kb == 0) scale_u(20, 32);
      if (kb < 5 && kb != 1) {
        const int ch = kb ? kb - 1 : 0;
#pragma unroll
        for (int i = ch * 6; i < ch * 6 + 6; i++) {
          pin(aa[2 * i]); pin(aa[2 * i + 1]);
          H[i] = gelu2_pair(aa[2 * i], aa[2 * i + 1]);
          pin(H[i]);
        }
      }
      if (kb >= 4) {
        if (kb == 4) {
          TS(wg, 5);
          mbar_wait(sb + OFF_CBAR, 0);
          TS(wg, 6);
#pragma unroll
          for (int h = 0; h < 2; h++) {
            const float2 c = lds_f2(sb + OFF_CARRY + wg * 512 + (w * 16 + gr + 8 * h) * 8);
            hst[h] = cfma(lq[h], cplx{c.x, c.y}, pre[h]);
          }
        }
        const int j0 = (kb - 4) * 2;
        uint32_t rr[4], ri[4];
#pragma unroll
        for (int jj = 0; jj < 2; jj++) {
          const int j = j0 + jj;
          const uint32_t g2 = lds_u(sb + OFF_GS + (wg * 64 + j * 8 + q * 2) * 2);
#pragma unroll
          for (int h = 0; h < 2; h++) {
            const int i = 4 * j + 2 * h;
            const cplx h0 = cfma(lam[h], hst[h], cplx{ure[i], uim[i]});
            hst[h] = cfma(lam[h], h0, cplx{ure[i + 1], uim[i + 1]});
            rr[jj * 2 + h] = bf2_mul(pack_bf16(h0.re, hst[h].re), g2);
            ri[jj * 2 + h] = bf2_mul(pack_bf16(h0.im, hst[h].im), g2 ^ 0x80008000u);
          }
        }
        const uint32_t a = hst_addr ^ (j0 << 4);
        asm volatile("stmatrix.sync.aligned.m8n8.x4.shared.b16 [%0], {%1,%2,%3,%4};" ::"r"(a), "r"(rr[0]), "r"(rr[1]), "r"(rr[2]), "r"(rr[3]) : "memory");
        asm volatile("stmatrix.sync.aligned.m8n8.x4.shared.b16 [%0], {%1,%2,%3,%4};" ::"r"(a + him), "r"(ri[0]), "r"(ri[1]), "r"(ri[2]), "r"(ri[3]) : "memory");
      }
    }
    TS(wg, 7);

    uint4* const psend = g_part + (size_t)(m * 8 + rank) * 3072 + warp * 128 + lane;
    const uint4* const precv = g_part + (size_t)(m * 8 + s) * 3072 + warp * 128 + lane;
    const uint32_t pbuf = OFF_X + warp * 2048 + lane * 16;
    const uint32_t dx0 = ((sb + OFF_X) & 0x3FFFF) >> 4, dhi = dxw + (him >> 4);
    float o[32], o2[32], rho[2];
    uint32_t tr[8];
    uint32_t r0[16], pt[16], sum[16], xs[16], tag;
    auto recv_issue = [&](uint32_t (&r)[16], int k) {
#pragma unroll
      for (int i = 0; i < 4; i++) ld_b128(precv + k * 1024 + i * 32, r[4 * i], r[4 * i + 1], r[4 * i + 2], r[4 * i + 3]);
    };
    auto stale = [&](uint32_t (&r)[16]) {
      uint32_t t0, t1, r_;
      asm("lop3.b32 %0, %1, %2, %3, 0x7e;" : "=r"(t0) : "r"(r[0]), "r"(r[4]), "r"(tag));
      asm("lop3.b32 %0, %1, %2, %3, 0x7e;" : "=r"(t1) : "r"(r[8]), "r"(r[12]), "r"(tag));
      asm volatile("{.reg .pred p; .reg .b32 t; lop3.b32 t, %1, %2, 1, 0xa8; setp.ne.u32 p, t, 0; vote.sync.any.pred p, p, 0xffffffff; selp.u32 %0, 1, 0, p;}" : "=r"(r_) : "r"(t0), "r"(t1));
      return r_ != 0;
    };
    auto recv_check = [&](uint32_t (&r)[16], int k) {
      if (__builtin_expect(stale(r), 0)) {
        int tries = 0;
#pragma unroll 1
        do { recv_issue(r, k); } while (stale(r) && ++tries < 200000);
      }
    };
    auto gelu_b = [&](int i0, int i1) {
#pragma unroll
      for (int i = i0; i < i1; i++) {
        pin(ab[2 * i]); pin(ab[2 * i + 1]);
        H[24 + i] = gelu2_pair(ab[2 * i], ab[2 * i + 1]);
        pin(H[24 + i]);
      }
    };
    auto step = [&](float (&d)[32], int p, int k, int acc) {
      const uint32_t wo = stage_off(p);
      if (k >= 6 && k < 14) {
        const int kk = k - 6;
        wgmma_n64_ss<1, 0, DH128, DH128>(d, kk < 4 ? dxw : dhi, (kk & 3) * 2048, dx0, wo + 14336 + (kk >> 2) * 8192 + (kk & 3) * 32, 1);
      } else {
        const int kk = k < 6 ? k : k - 8;
        wgmma_n64_rs<1, DH128>(d, H[4 * kk], H[4 * kk + 1], H[4 * kk + 2], H[4 * kk + 3], dx0, wo + (kk / 7) * 30720 + (kk % 7) * 2048, k != 0 || acc);
      }
    };
    auto mma = [&](float (&d)[32], int p, int k0, int k1, int acc) {
      wg_fence();
#pragma unroll
      for (int k = k0; k < k1; k++) step(d, p, k, acc);
      wg_commit();
    };
    auto mma2 = [&](int k0, int k1) {
      wg_fence();
#pragma unroll
      for (int k = k0; k < k1; k++) { step(o, 0, k, 0); step(o2, 1, k, 0); }
      wg_commit();
    };
    auto send_peer = [&](int i0, int i1) {
#pragma unroll
      for (int i = i0; i < i1; i++)
        asm volatile("st.async.shared::cluster.mbarrier::complete_tx::bytes.v4.b32 [%0], {%1,%2,%3,%4}, [%5];" ::"r"(peer + pbuf + him + i * 512),
                     "r"(pack_bf16(o[8 * i], o[8 * i + 1])), "r"(pack_bf16(o[8 * i + 2], o[8 * i + 3])), "r"(pack_bf16(o[8 * i + 4], o[8 * i + 5])),
                     "r"(pack_bf16(o[8 * i + 6], o[8 * i + 7])), "r"(peer + OFF_RBAR + wg * 8) : "memory");
    };
    auto recv_peer = [&](int d) {
      mbar_wait(sb + OFF_RBAR + wg * 8, d & 1);
#pragma unroll
      for (int i = 0; i < 4; i++) { const uint4 v = lds_u4(sb + pbuf + (49152 - him) + i * 512); pt[4 * i] = v.x; pt[4 * i + 1] = v.y; pt[4 * i + 2] = v.z; pt[4 * i + 3] = v.w; }
    };
    auto arm = [&]() { if ((threadIdx.x & 127) == 0) mbar_expect_tx(sb + OFF_RBAR + wg * 8, 8192); };
    float2 b2v[8];
#pragma unroll
    for (int d = 0; d < 3; d++) {
      const int p = d;
      if (d == 0) {
        mbar_wait(fullb, 0);
        mma2(0, 3);
        asm volatile("fence.proxy.async.shared::cta;" ::: "memory");
#pragma unroll
        for (int i = 0; i < 4; i++)
          asm volatile("ldmatrix.sync.aligned.m8n8.x4.shared.b16 {%0,%1,%2,%3}, [%4];" : "=r"(xs[4 * i]), "=r"(xs[4 * i + 1]), "=r"(xs[4 * i + 2]), "=r"(xs[4 * i + 3])
                       : "r"((hst_addr ^ (i << 5)) + (49152 - him)) : "memory");
        tag = lds_u(sb + OFF_EPOCH);
        arm();
        wg_wait<1>(); release(5);
        bar_sync(1 + wg, 128);
        credit();
        mbar_wait(fullb + 8, 0);
        if (wg == 1) bar_sync(4, 256);
        mma2(3, 6);   gelu_b(0, 4);
        mma2(6, 8);   gelu_b(4, 8);
        mma2(8, 11);  gelu_b(8, 12);
        mma2(11, 13); gelu_b(12, 16);
        if (A1 == 4 && wg == 1) bar_arrive(3, 256);
        mma2(13, 15); gelu_b(16, 20);
        if (A1 == 5 && wg == 1) bar_arrive(3, 256);
        mbar_wait(fullb + 16, 0);
        mma2(15, 17); gelu_b(20, 24);
        if ((A1 == 6 && wg == 1) || (A0 == 6 && wg == 0)) bar_arrive(4 - wg, 256);
        mma2(17, 19); gelu_b(24, 28);
        if ((A1 == 7 && wg == 1) || (A0 == 7 && wg == 0)) bar_arrive(4 - wg, 256);
        mma2(19, 21); gelu_b(28, 32);
        if ((A1 == 8 && wg == 1) || (A0 == 8 && wg == 0)) bar_arrive(4 - wg, 256);
        mma2(21, 22);
        TS(wg, 8);
        mbar_wait(sb + OFF_KBAR + wg * 8, 0);
        wg_wait<0>();
      } else {
        TR(0);
        bar_sync(3 + wg, 256);
        mma(o, 2 * d, 0, 22, 0);
        mma(o2, 2 * d + 1, 0, 22, 0);
        bar_arrive(4 - wg, 256);
        TR(1);
        if (p != TP) TS(wg, 8 + d);
        mbar_wait(sb + OFF_KBAR + wg * 8, d & 1);
        wg_wait<1>();
      }
      reg_fence(o);
      send_peer(0, 4);
      TR(2);
      if (d == 1) {
        const uint4 d0 = lds_u4(sb + OFF_DB + q * 32), d1 = lds_u4(sb + OFF_DB + q * 32 + 16);
        const uint32_t dk[8] = {d0.x, d0.y, d0.z, d0.w, d1.x, d1.y, d1.z, d1.w};
#pragma unroll
        for (int i = 0; i < 16; i++) { xs[i] = bf2_mul(xs[i], dk[i >> 1]); pin(xs[i]); }
#pragma unroll
        for (int h = 0; h < 2; h++) rho[h] = 0.5f * bf_lo(lds_h(sb + OFF_GS + (wg * 64 + w * 16 + gr + 8 * h) * 2));
      }
      if (d == 2) {
        recv_issue(sum, 0); recv_issue(r0, 1);
#pragma unroll
        for (int i = 0; i < 4; i++) {
          const uint4 v = lds_u4(sb + OFF_DB + 128 + q * 64 + i * 16);
          b2v[2 * i] = make_float2(__uint_as_float(v.x), __uint_as_float(v.y)); b2v[2 * i + 1] = make_float2(__uint_as_float(v.z), __uint_as_float(v.w));
        }
      }
      if (d > 0) wg_wait<0>();
      release(d);
      reg_fence(o2);
      mbar_wait(sb + OFF_XFULL + 8 * (d + 1), 1);
      TR(3);
      recv_peer(d);
      TR(4);
      arm();
#pragma unroll
      for (int i = 0; i < 4; i++) {
#pragma unroll
        for (int c = 4 * i; c < 4 * i + 4; c++) pt[c] = bf2_add(pt[c], pack_bf16(o2[2 * c], o2[2 * c + 1]));
        asm("lop3.b32 %0, %0, 1, %1, 0xb8;" : "+r"(pt[4 * i]) : "r"(tag));
        if (i == 3) { __syncwarp(); credit(); }
        st_b128(psend + (((sp + 1 + d) & 3) * 6 + d) * 1024 + i * 32, pt[4 * i], pt[4 * i + 1], pt[4 * i + 2], pt[4 * i + 3]);
      }
      TR(5);
      if (d == 2) {
#pragma unroll
        for (int i = 0; i < 16; i++) {
          o2[2 * i] = fmaf(bf_lo(xs[i]), rho[i & 1], b2v[i >> 1].x);
          o2[2 * i + 1] = fmaf(bf_hi(xs[i]), rho[i & 1], b2v[i >> 1].y);
        }
        reg_fence(o2);
#pragma unroll
        for (int h = 0; h < 2; h++) { rho[h] = __fdividef(1.f, 2.f + rho[h]); pin(rho[h]); }
        TR(6);
        recv_check(sum, 0); recv_check(r0, 1);
#pragma unroll
        for (int i = 0; i < 16; i++) { sum[i] = bf2_add(sum[i], r0[i]); pin(sum[i]); }
      }
      TR(7);
    }
    {
      const int p = 3;
      TR(0);
      bar_sync(3 + wg, 256);
      mma(o, 6, 0, 22, 0);
      TR(1);
      recv_issue(r0, 2);
      mbar_wait(sb + OFF_KBAR + wg * 8, 1);
      mma(o2, 7, 0, GAP, 1);
      wg_wait<1>();
      reg_fence(o);
      send_peer(0, 2);
      mma(o2, 7, GAP, GAP + 4, 1);
      send_peer(2, 4);
      mma(o2, 7, GAP + 4, 22, 1);
      if (wg == 0) bar_arrive(4, 256);
      TR(2);
      if (p != TP) TS(wg, 11);
      tag = lds_u(sb + OFF_EPOCH);
      mbar_wait(sb + OFF_EMPTY + 16, 0);
      recv_check(r0, 2);
#pragma unroll
      for (int i = 0; i < 16; i++) sum[i] = bf2_add(sum[i], r0[i]);
      TR(3);
      recv_peer(3);
      TR(4);
#pragma unroll
      for (int i = 0; i < 16; i++) sum[i] = bf2_add(sum[i], pt[i]);
      wg_wait<0>();
      reg_fence(o2);
      TR(5);
      const uint32_t tb = sb + OFF_X + 49152 + warp * 4096;
      const uint32_t ta = tb + gr * 128 + (((q >> 1) ^ gr) << 4) + (q & 1) * 8;
#pragma unroll
      for (int ch = 0; ch < 2; ch++) {
#pragma unroll
        for (int i = ch * 8; i < ch * 8 + 8; i++)
          asm volatile("st.shared.v2.f32 [%0], {%1,%2};" ::"r"((ta ^ (((i >> 1) & 3) << 5)) + (i & 1) * 1024 + ch * 2048),
                       "f"((o2[2 * i] + bf_lo(sum[i])) * rho[i & 1]), "f"((o2[2 * i + 1] + bf_hi(sum[i])) * rho[i & 1]) : "memory");
        if (OUT_TMA == 2 || ch == 1) {
          asm volatile("fence.proxy.async.shared::cta;" ::: "memory");
          __syncwarp();
          if (elect_one()) {
#pragma unroll
            for (int c2 = (OUT_TMA == 2 ? ch : 0); c2 <= ch; c2++)
              asm volatile("cp.async.bulk.tensor.5d.global.shared::cta.bulk_group [%0, {%2,%5,%5,%3,%4}], [%1];"
                           ::"l"(&maps.out), "r"(tb + c2 * 2048), "r"(s * 64 + c2 * 32), "r"(2 * w), "r"(2 * m + wg), "r"(0) : "memory");
            asm volatile("cp.async.bulk.commit_group;" ::: "memory");
          }
        }
      }
      TR(6);
      if (elect_one()) asm volatile("cp.async.bulk.wait_group.read 0;" ::: "memory");
      TR(7);
      if (threadIdx.x == 128) g_epoch[b] = tag;
      TS(wg, 17); TG(wg); TRD(); TDUMP();
    }
  } else {
    asm volatile("setmaxnreg.dec.sync.aligned.u32 56;");
    int wsel = warp;
    asm("" : "+r"(wsel));
    if (wsel > 8) {
      if (warp != 11) {
        const int t = threadIdx.x - 288;
        unsigned par;
        asm volatile("ld.relaxed.gpu.global.u32 %0, [%1];" : "=r"(par) : "l"(g_epoch + b) : "memory");
        const float pr = bf_ld(lam_re + s * 64 + t), pi = bf_ld(lam_im + s * 64 + t), pd = bf_ld(log_dt + s * 64 + t);
        asm volatile("barrier.cluster.wait.aligned;" ::: "memory");
        par = (par + 1) & 1;
        cplx l64 = make_lam(pr, pi, pd);
        {
          const float inv = __fdividef(1.f, fmaf(pr, pr, pi * pi));
          const cplx cf = cmul(cplx{l64.re - 1.f, l64.im}, cplx{pr * inv, -pi * inv});
          asm volatile("st.shared.v4.f32 [%0], {%1,%2,%3,%4};" ::"r"(sb + OFF_LC + t * 16), "f"(l64.re), "f"(l64.im), "f"(cf.re), "f"(cf.im) : "memory");
          mbar_arrive(sb + OFF_LBAR);
        }
#pragma unroll
        for (int i = 0; i < 6; i++) l64 = cmul(l64, l64);
        cplx l128 = cmul(l64, l64);
        pin(l128.re); pin(l128.im);
        mbar_wait(sb + OFF_GBAR, 0);
        const float2 e0 = lds_f2(sb + OFF_CARRY + t * 8), e1 = lds_f2(sb + OFF_CARRY + 512 + t * 8);
        float2* eb = g_end + s * 1024 + t;
        {
          const cplx e = cfma(l64, cplx{e0.x, e0.y}, cplx{e1.x, e1.y});
          const unsigned long long v = ((unsigned long long)__float_as_uint(e.im) << 32) | ((__float_as_uint(e.re) & ~1u) | par);
          asm volatile("st.relaxed.gpu.global.b64 [%0], %1;" ::"l"(eb + m * 64), "l"(v) : "memory");
        }
        if (t == 0) TS(3, 1);
        cplx S = {0.f, 0.f};
        {
          unsigned long long v[15];
          uint32_t bad;
          int tries = 0;
          const float2* e15 = eb + (m - 15) * 64;
#pragma unroll 1
          do {
#pragma unroll
            for (int i = 0; i < 15; i++) {
              v[i] = par;
              asm volatile("{.reg .pred p; setp.ge.s32 p, %2, %3; @p ld.relaxed.gpu.global.b64 %0, [%1];}" : "+l"(v[i]) : "l"(e15 + i * 64), "r"(m), "r"(15 - i) : "memory");
            }
            bad = 0;
#pragma unroll
            for (int i = 0; i < 15; i++) bad |= (uint32_t)v[i] ^ par;
          } while ((bad & 1) && ++tries < 200000);
          if (t == 0) TS(3, 2);
#pragma unroll
          for (int i = 0; i < 15; i++) S = cfma(l128, S, cplx{__uint_as_float((uint32_t)v[i] & ~1u), __uint_as_float((uint32_t)(v[i] >> 32))});
        }
        const cplx S1 = cfma(l64, S, cplx{e0.x, e0.y});
        asm volatile("st.shared.v2.f32 [%0], {%1,%2};" ::"r"(sb + OFF_CARRY + t * 8), "f"(S.re), "f"(S.im) : "memory");
        asm volatile("st.shared.v2.f32 [%0], {%1,%2};" ::"r"(sb + OFF_CARRY + 512 + t * 8), "f"(S1.re), "f"(S1.im) : "memory");
        mbar_arrive(sb + OFF_CBAR);
        if (t == 0) TS(3, 3);
      } else {
        if (lane == 0) TG(2);
        const uint4* gwp = reinterpret_cast<const uint4*>(gate_w) + (lane & 7);
        uint4 gw[4];
#pragma unroll
        for (int i = 0; i < 4; i++) gw[i] = __ldg(gwp + i * 8);
        unsigned par;
        asm volatile("ld.relaxed.gpu.global.u32 %0, [%1];" : "=r"(par) : "l"(g_epoch + b) : "memory");
        const uint32_t dk = __ldg(reinterpret_cast<const uint32_t*>(dskip + s * 64) + lane), bb = __ldg(reinterpret_cast<const uint32_t*>(b2 + s * 64) + lane);
        asm volatile("barrier.cluster.wait.aligned;" ::: "memory");
        const int row = s * 16 + (lane >> 3);
        const uint32_t xr0 = sb + OFF_X + row * 128 + (((lane & 7) ^ (row & 7)) << 4), xr1 = (xr0 + 512) ^ 64;
        float z[4] = {0.f, 0.f, 0.f, 0.f};
#pragma unroll
        for (int kb = 0; kb < 8; kb++) {
          const uint32_t wv[4] = {gw[kb & 3].x, gw[kb & 3].y, gw[kb & 3].z, gw[kb & 3].w};
          if (kb < 4) gw[kb] = __ldg(gwp + (kb + 4) * 8);
          mbar_wait(sb + OFF_XFULL + 8 * kb, 0);
          if ((PF & 2) && kb == PFK && elect_one()) {
            l2_prefetch(pf_w1 + b * 7168, 14336);
            l2_prefetch(pf_cre + b * 2048, 4096);
            l2_prefetch(pf_cim + b * 2048, 4096);
            l2_prefetch(pf_w2 + b * 7168, 14336);
          }
          const uint32_t xo = ((kb + xrot) & 7) * 16384;
#pragma unroll
          for (int r = 0; r < 4; r++) {
            const uint4 a = lds_u4(((r & 1) ? xr1 : xr0) + xo + (r >> 1) * 1024);
            const uint32_t p = bf2_fma(a.w, wv[3], bf2_fma(a.z, wv[2], bf2_fma(a.y, wv[1], bf2_mul(a.x, wv[0]))));
            z[r] += bf_lo(p); z[r] += bf_hi(p);
          }
        }
        if (lane == 0) asm volatile("st.shared.u32 [%0], %1;" ::"r"(sb + OFF_EPOCH), "r"(par + 1) : "memory");
        par = (par + 1) & 1;
        {
          float y0 = (lane & 4) ? z[1] : z[0], y1 = (lane & 4) ? z[3] : z[2];
          y0 += __shfl_xor_sync(0xffffffffu, (lane & 4) ? z[0] : z[1], 4);
          y1 += __shfl_xor_sync(0xffffffffu, (lane & 4) ? z[2] : z[3], 4);
          float zz = (lane & 2) ? y1 : y0;
          zz += __shfl_xor_sync(0xffffffffu, (lane & 2) ? y0 : y1, 2);
          zz += __shfl_xor_sync(0xffffffffu, zz, 1);
          const float rho = 4.f * expf(zz > 40.f ? 40.f : zz);
          if ((lane & 1) == 0)
            asm volatile("st.relaxed.gpu.global.u32 [%0], %1;" ::"l"(g_gate + m * 128 + row + (lane & 4) + (lane & 2) * 4), "r"((__float_as_uint(rho) & ~1u) | par) : "memory");
        }
        if (lane == 0) TS(3, 0);
        mbar_wait(sb + OFF_GBAR, 0);
        asm volatile("st.shared.b32 [%0], %1;" ::"r"(sb + OFF_DB + (lane & 3) * 32 + (lane >> 2) * 4), "r"(dk) : "memory");
        asm volatile("st.shared.v2.f32 [%0], {%1,%2};" ::"r"(sb + OFF_DB + 128 + (lane & 3) * 64 + (lane >> 2) * 8), "f"(2.f * bf_lo(bb)), "f"(2.f * bf_hi(bb)) : "memory");
        uint32_t g0, g1, g2, g3;
        int tries = 0;
#pragma unroll 1
        do {
          asm volatile("ld.relaxed.gpu.global.v4.u32 {%0,%1,%2,%3}, [%4];" : "=r"(g0), "=r"(g1), "=r"(g2), "=r"(g3) : "l"(g_gate + m * 128 + lane * 4) : "memory");
        } while ((((g0 ^ par) | (g1 ^ par) | (g2 ^ par) | (g3 ^ par)) & 1) && ++tries < 200000);
        asm volatile("st.shared.v2.u32 [%0], {%1,%2};" ::"r"(sb + OFF_GS + lane * 8), "r"(pack_bf16(__uint_as_float(g0), __uint_as_float(g1))),
                     "r"(pack_bf16(__uint_as_float(g2), __uint_as_float(g3))) : "memory");
        mbar_arrive(sb + OFF_CBAR);
        if (lane == 0) TS(3, 4);
      }
    } else {
      asm volatile("barrier.cluster.wait.aligned;" ::: "memory");
      if (elect_one()) {
        TS(2, 1);
        const uint32_t t0 = clock();
#pragma unroll 1
        for (int u = 0; u < 8; u++) {
          if (u >= 1) while ((uint32_t)clock() - t0 < D0 + (u - 1) * D1) {}
          mbar_expect_tx(sb + OFF_XFULL + 8 * u, 16384);
          tma5d_mc(sb + OFF_X + ((u + xrot) & 7) * 16384 + rank * 8192, &maps.x, u * 64, 2 * m + rank, sb + OFF_XFULL + 8 * u);
          if (u < 6) {
            mbar_expect_tx(sb + OFF_FULL + 8 * u, 16384);
            tma2d(sb + OFF_RING + u * 16384, &maps.bre, u * 64, s * 64, sb + OFF_FULL + 8 * u);
            tma2d(sb + OFF_RING + u * 16384 + 8192, &maps.bim, u * 64, s * 64, sb + OFF_FULL + 8 * u);
          } else if (PF & 4) {
            asm volatile("cp.async.bulk.prefetch.tensor.2d.L2.global [%0, {%1,%2}];" ::"l"((m & 1) ? &maps.bim : &maps.bre), "r"(u * 64), "r"(s * 64) : "memory");
          }
        }
        TS(2, 5);
        int slot = 0; uint32_t ph = 0;
#pragma unroll 1
        for (int u = 6; u < 24; u++) {
          const uint32_t fb = sb + OFF_FULL + 8 * slot, dst = sb + OFF_RING + slot * 16384;
          mbar_wait(sb + OFF_EMPTY + 8 * slot, ph);
          TS2(0, u);
          if (u < 8) {
            mbar_expect_tx(fb, 16384);
            tma2d(dst, &maps.bre, u * 64, s * 64, fb);
            tma2d(dst + 8192, &maps.bim, u * 64, s * 64, fb);
          } else if (u < 16) {
            mbar_expect_tx(fb, 12288);
            tma3d(dst, &maps.w1b, 0, (u - 8) * 64, s * 7, fb);
          } else {
            mbar_expect_tx(fb, 16384);
            tma2d(dst, &maps.w1a, s * 224 + 96, ((u - xrot) & 7) * 64, fb);
            tma2d(dst + 8192, &maps.w1a, s * 224 + 160, ((u - xrot) & 7) * 64, fb);
          }
          if (++slot == NSLOT) { slot = 0; ph ^= 1; }
        }
#pragma unroll 1
        for (int d = 0; d < 4; d++) {
          const int col = ((sp + 1 + d) & 3) * 128;
          const uint32_t dst = sb + OFF_X + 49152 + (d & 1) * 45056;
          uint32_t fb = sb + OFF_XFULL + 8 * d;
          if (d) {
            mbar_wait(sb + OFF_EMPTY + (d == 1 ? 40 : (d - 2) * 8), d == 1);
            mbar_expect_tx(fb, 90112);
          }
          TS2(0, 32 + d);
#pragma unroll 1
          for (int j = 0; j < 3; j++) {
            if (d == 0) {
              fb = sb + OFF_FULL + 8 * j;
              mbar_wait(sb + OFF_EMPTY + 8 + 8 * j, 1);
              mbar_expect_tx(fb, j == 1 ? 32768 : 28672);
            }
#pragma unroll
            for (int e = 0; e < 2; e++) {
              const int c = col + ((rank ^ e ^ 1) << 6);
              if (j == 1) {
                tma2d(dst + e * 90112 + 14336, &maps.cre, s * 64, c, fb);
                tma2d(dst + e * 90112 + 22528, &maps.cim, s * 64, c, fb);
              } else {
                tma2d(dst + e * 90112 + j * 15360, &maps.w2, c, s * 224 + j * 56, fb);
              }
            }
          }
        }
        asm volatile("prefetch.tensormap [%0];" ::"l"(&maps.out) : "memory");
        TS(2, 2);
      }
    }
  }
}

typedef CUresult (*EncFn)(CUtensorMap*, CUtensorMapDataType, cuuint32_t, void*, const cuuint64_t*, const cuuint64_t*, const cuuint32_t*,
                          const cuuint32_t*, CUtensorMapInterleave, CUtensorMapSwizzle, CUtensorMapL2promotion, CUtensorMapFloatOOBfill);

void encode(EncFn f, CUtensorMap* mp, const void* p, int rank, const cuuint64_t* dims, const cuuint64_t* strides, const cuuint32_t* box, CUtensorMapSwizzle sw,
            CUtensorMapDataType ty = CU_TENSOR_MAP_DATA_TYPE_BFLOAT16) {
  cuuint32_t es[5] = {1, 1, 1, 1, 1};
  f(mp, ty, rank, const_cast<void*>(p), dims, strides, box, es, CU_TENSOR_MAP_INTERLEAVE_NONE, sw,
    CU_TENSOR_MAP_L2_PROMOTION_L2_128B, CU_TENSOR_MAP_FLOAT_OOB_FILL_NONE);
}

}

extern "C" void kernel_launch(void* const* d_in, const int* in_sizes, int n_in, void* d_out, int out_size) {
  typedef const __nv_bfloat16* bp;
  bp x = (bp)d_in[0], lre = (bp)d_in[1], lim = (bp)d_in[2], bre = (bp)d_in[3], bim = (bp)d_in[4], cre = (bp)d_in[5], cim = (bp)d_in[6],
     ldt = (bp)d_in[7], dsk = (bp)d_in[8], w1 = (bp)d_in[10], b1 = (bp)d_in[11], w2 = (bp)d_in[12], b2 = (bp)d_in[13], gw = (bp)d_in[14];
  static EncFn enc = nullptr;
  if (!enc) {
    void* f = nullptr;
    cudaDriverEntryPointQueryResult qr;
    cudaGetDriverEntryPoint("cuTensorMapEncodeTiled", &f, cudaEnableDefault, &qr);
    enc = (EncFn)f;
    cudaFuncSetAttribute(fused_kernel, cudaFuncAttributeMaxDynamicSharedMemorySize, SMEM_BYTES);
  }
  Maps maps;
  {
    cuuint64_t d[5] = {DM, 2, 4, 8, SEQ / 64}, st[4] = {DM * 2, 16 * DM * 2, 2 * DM * 2, 64 * DM * 2};
    cuuint32_t bx[5] = {64, 2, 4, 8, 1};
    encode(enc, &maps.x, x, 5, d, st, bx, CU_TENSOR_MAP_SWIZZLE_128B);
    cuuint64_t so[4] = {DM * 4, 16 * DM * 4, 2 * DM * 4, 64 * DM * 4};
    cuuint32_t bo[5] = {32, 2, 4, 2, 1};
    encode(enc, &maps.out, d_out, 5, d, so, bo, CU_TENSOR_MAP_SWIZZLE_128B, CU_TENSOR_MAP_DATA_TYPE_FLOAT32);
  }
  {
    cuuint64_t d[2] = {DM, DM}, st[1] = {DM * 2};
    cuuint32_t bx[2] = {64, 64};
    encode(enc, &maps.bre, bre, 2, d, st, bx, CU_TENSOR_MAP_SWIZZLE_128B);
    encode(enc, &maps.bim, bim, 2, d, st, bx, CU_TENSOR_MAP_SWIZZLE_128B);
    encode(enc, &maps.cre, cre, 2, d, st, bx, CU_TENSOR_MAP_SWIZZLE_128B);
    encode(enc, &maps.cim, cim, 2, d, st, bx, CU_TENSOR_MAP_SWIZZLE_128B);
  }
  {
    cuuint64_t d[2] = {FF, DM}, st[1] = {FF * 2};
    cuuint32_t bx[2] = {64, 64};
    encode(enc, &maps.w1a, w1, 2, d, st, bx, CU_TENSOR_MAP_SWIZZLE_128B);
    cuuint64_t d3[3] = {32, DM, FF / 32}, st3[2] = {FF * 2, 64};
    cuuint32_t bx3[3] = {32, 64, 3};
    encode(enc, &maps.w1b, w1, 3, d3, st3, bx3, CU_TENSOR_MAP_SWIZZLE_64B);
  }
  {
    cuuint64_t d[2] = {DM, FF}, st[1] = {DM * 2};
    cuuint32_t bx[2] = {64, 112};
    encode(enc, &maps.w2, w2, 2, d, st, bx, CU_TENSOR_MAP_SWIZZLE_128B);
  }
  fused_kernel<<<128, 384, SMEM_BYTES>>>(lre, lim, ldt, dsk, b1, b2, gw, w1, w2, cre, cim, (float*)d_out, maps);
}
```

```cpp
#include <cuda_runtime.h>
#include <cuda_bf16.h>
#include <cuda.h>
#include <stdint.h>

#define MAP 1
#define D0 600
#define D1 500
#define PF 6
#define PFK 5
#define GELUP 0
#define EW 1
#define K1E 0
#define K2E 1
#define QS 2
#define GAP 8
#define A0 7
#define A1 5
#define OUT_TMA 1
#define G1 8
#define G2 15
#define TP 9
#define TW 0

namespace {

constexpr int SEQ = 2048, DM = 512, FF = 1792;
constexpr int NSLOT = 6;
constexpr uint32_t OFF_X = 0, OFF_RING = 131072, OFF_MISC = 229376;
constexpr uint32_t OFF_XFULL = OFF_MISC, OFF_FULL = OFF_XFULL + 64, OFF_RBAR = OFF_FULL + 48, OFF_EMPTY = OFF_RBAR + 16, OFF_KBAR = OFF_EMPTY + 48,
                   OFF_GBAR = OFF_KBAR + 16, OFF_LBAR = OFF_GBAR + 8, OFF_CBAR = OFF_LBAR + 8, OFF_EPOCH = OFF_CBAR + 8;
constexpr uint32_t OFF_LC = OFF_MISC + 256;
constexpr uint32_t OFF_GS = OFF_LC;
constexpr uint32_t OFF_DB = OFF_LC + 512;
constexpr uint32_t OFF_CARRY = OFF_LC + 1024;
constexpr uint32_t OFF_DBG = OFF_CARRY + 1024;
constexpr uint32_t SMEM_BYTES = OFF_DBG + 768;
static_assert(SMEM_BYTES <= 232448, "smem");

struct Maps { CUtensorMap x, bre, bim, w1b, w1a, w2, cre, cim, out; };
__host__ __device__ constexpr uint32_t stage_off(int p) { return 49152 + 45056 * (((p >> 1) & 1) + 2 * (p & 1)); }

__device__ uint4 g_part[16 * 8 * 3 * 1024];
__device__ float2 g_end[8 * 16 * 64];
__device__ unsigned g_gate[SEQ];
__device__ unsigned g_epoch[128];
#define TG(role) do {} while (0)
#define TS2(role, i) do {} while (0)
#define TS(role, i) do {} while (0)
#define TDUMP() do {} while (0)
#define TR(i) do {} while (0)
#define TRD() do {} while (0)

__device__ __forceinline__ void mbar_init(uint32_t bar, uint32_t cnt) { asm volatile("mbarrier.init.shared::cta.b64 [%0], %1;" ::"r"(bar), "r"(cnt)); }
__device__ __forceinline__ void mbar_expect_tx(uint32_t bar, uint32_t bytes) { asm volatile("mbarrier.arrive.expect_tx.shared::cta.b64 _, [%0], %1;" ::"r"(bar), "r"(bytes) : "memory"); }
__device__ __forceinline__ void mbar_arrive(uint32_t bar) { asm volatile("mbarrier.arrive.shared::cta.b64 _, [%0];" ::"r"(bar) : "memory"); }
__device__ __forceinline__ void mbar_arrive_cl(uint32_t cbar) { asm volatile("mbarrier.arrive.shared::cluster.b64 _, [%0];" ::"r"(cbar) : "memory"); }
__device__ __forceinline__ void mbar_wait(uint32_t bar, uint32_t parity) {
  asm volatile(
      "{\n.reg .pred p;\n.reg .u32 c;\n"
      "mbarrier.try_wait.parity.shared::cta.b64 p, [%0], %1;\n"
      "@p bra.uni LAB_DONE;\n"
      "mov.u32 c, 0;\n"
      "LAB_WAIT:\n"
      "mbarrier.try_wait.parity.shared::cta.b64 p, [%0], %1;\n"
      "@p bra.uni LAB_DONE;\n"
      "add.u32 c, c, 1;\nsetp.lt.u32 p, c, 200000;\n@p bra.uni LAB_WAIT;\n"
      "LAB_DONE:\n}" ::"r"(bar), "r"(parity) : "memory");
}
__device__ __forceinline__ void tma2d(uint32_t dst, const CUtensorMap* m, int c0, int c1, uint32_t bar) {
  asm volatile("cp.async.bulk.tensor.2d.shared::cluster.global.mbarrier::complete_tx::bytes [%0], [%1, {%3,%4}], [%2];"
               ::"r"(dst), "l"(m), "r"(bar), "r"(c0), "r"(c1) : "memory");
}
__device__ __forceinline__ void tma3d(uint32_t dst, const CUtensorMap* m, int c0, int c1, int c2, uint32_t bar) {
  asm volatile("cp.async.bulk.tensor.3d.shared::cluster.global.mbarrier::complete_tx::bytes [%0], [%1, {%3,%4,%5}], [%2];"
               ::"r"(dst), "l"(m), "r"(bar), "r"(c0), "r"(c1), "r"(c2) : "memory");
}
__device__ __forceinline__ void tma5d_mc(uint32_t dst, const CUtensorMap* m, int c0, int c4, uint32_t bar) {
  asm volatile("cp.async.bulk.tensor.5d.shared::cluster.global.mbarrier::complete_tx::bytes.multicast::cluster [%0], [%1, {%3,%5,%5,%5,%4}], [%2], %6;"
               ::"r"(dst), "l"(m), "r"(bar), "r"(c0), "r"(c4), "r"(0), "h"((uint16_t)3) : "memory");
}
__device__ __forceinline__ void l2_prefetch(const void* p, uint32_t bytes) { asm volatile("cp.async.bulk.prefetch.L2.global [%0], %1;" ::"l"(p), "r"(bytes) : "memory"); }
__device__ __forceinline__ bool elect_one() {
  uint32_t pred;
  asm volatile("{.reg .pred P; elect.sync _|P, 0xffffffff; selp.u32 %0, 1, 0, P;}" : "=r"(pred));
  return pred != 0;
}
__device__ __forceinline__ void wg_fence() { asm volatile("wgmma.fence.sync.aligned;" ::: "memory"); }
__device__ __forceinline__ void wg_commit() { asm volatile("wgmma.commit_group.sync.aligned;" ::: "memory"); }
template <int N> __device__ __forceinline__ void wg_wait() { asm volatile("wgmma.wait_group.sync.aligned %0;" ::"n"(N) : "memory"); }
__device__ __forceinline__ void pin(float& a) { asm volatile("" : "+f"(a)::"memory"); }
__device__ __forceinline__ void pin(uint32_t& a) { asm volatile("" : "+r"(a)::"memory"); }
template <int N> __device__ __forceinline__ void reg_fence(float (&d)[N]) {
#pragma unroll
  for (int i = 0; i < N; i++) pin(d[i]);
}
__device__ __forceinline__ void bar_sync(int id, int n) { asm volatile("bar.sync %0, %1;" ::"r"(id), "r"(n) : "memory"); }
__device__ __forceinline__ void bar_arrive(int id, int n) { asm volatile("bar.arrive %0, %1;" ::"r"(id), "r"(n) : "memory"); }
constexpr uint32_t DH128 = (1024 >> 4) | (1u << 30), DH64 = (512 >> 4) | (2u << 30);
__host__ __device__ constexpr uint32_t lbo(uint32_t bytes) { return (bytes >> 4) << 20; }
__device__ __forceinline__ uint32_t pack_bf16(float lo, float hi) { uint32_t r; asm("cvt.rn.bf16x2.f32 %0, %1, %2;" : "=r"(r) : "f"(hi), "f"(lo)); return r; }
__device__ __forceinline__ float bf_lo(uint32_t v) { return __uint_as_float(v << 16); }
__device__ __forceinline__ float bf_hi(uint32_t v) { return __uint_as_float(v & 0xffff0000u); }
__device__ __forceinline__ float bf_ld(const __nv_bfloat16* p) { return __bfloat162float(__ldg(p)); }
__device__ __forceinline__ uint32_t late16(uint32_t bar) {
  uint32_t r;
  asm volatile("{.reg .pred p; mbarrier.test_wait.parity.shared::cta.b64 p, [%1], 0; selp.u32 %0, 16, 0, p;}" : "=r"(r) : "r"(bar) : "memory");
  return r;
}
__device__ __forceinline__ float2 lds_f2(uint32_t a) { float2 v; asm volatile("ld.shared.v2.f32 {%0,%1}, [%2];" : "=f"(v.x), "=f"(v.y) : "r"(a)); return v; }
__device__ __forceinline__ uint32_t lds_h(uint32_t a) { uint32_t v; asm volatile("ld.shared.u16 %0, [%1];" : "=r"(v) : "r"(a)); return v; }
__device__ __forceinline__ uint32_t lds_u(uint32_t a) { uint32_t v; asm volatile("ld.shared.u32 %0, [%1];" : "=r"(v) : "r"(a)); return v; }
__device__ __forceinline__ uint4 lds_u4(uint32_t a) { uint4 v; asm volatile("ld.shared.v4.u32 {%0,%1,%2,%3}, [%4];" : "=r"(v.x), "=r"(v.y), "=r"(v.z), "=r"(v.w) : "r"(a)); return v; }
__device__ __forceinline__ void st_b128(uint4* p, uint32_t a, uint32_t b, uint32_t c, uint32_t d) {
  asm volatile("st.relaxed.gpu.global.v4.b32 [%0], {%1,%2,%3,%4};" ::"l"(p), "r"(a), "r"(b), "r"(c), "r"(d) : "memory");
}
__device__ __forceinline__ void ld_b128(const uint4* p, uint32_t& a, uint32_t& b, uint32_t& c, uint32_t& d) {
  asm volatile("{.reg .b64 l, h; .reg .b128 v; ld.relaxed.gpu.global.b128 v, [%4]; mov.b128 {l,h}, v; mov.b64 {%0,%1}, l; mov.b64 {%2,%3}, h;}"
               : "=r"(a), "=r"(b), "=r"(c), "=r"(d) : "l"(p) : "memory");
}
__device__ __forceinline__ float tanh_fast(float x) { float y; asm("tanh.approx.f32 %0, %1;" : "=f"(y) : "f"(x)); return y; }
__device__ __forceinline__ float gelu2(float v) {
  float p = fmaf(v * v, 0.0356774081363f, 0.7978845608029f);
  return fmaf(v, tanh_fast(v * p), v);
}
__device__ __forceinline__ uint32_t bf2_mul(uint32_t a, uint32_t b) { uint32_t r; asm("mul.rn.bf16x2 %0, %1, %2;" : "=r"(r) : "r"(a), "r"(b)); return r; }
__device__ __forceinline__ uint32_t bf2_add(uint32_t a, uint32_t b) { uint32_t r; asm("add.rn.bf16x2 %0, %1, %2;" : "=r"(r) : "r"(a), "r"(b)); return r; }
__device__ __forceinline__ uint32_t bf2_fma(uint32_t a, uint32_t b, uint32_t c) { uint32_t r; asm("fma.rn.bf16x2 %0, %1, %2, %3;" : "=r"(r) : "r"(a), "r"(b), "r"(c)); return r; }
__device__ __forceinline__ uint32_t gelu2_pair(float a, float b) {
  return pack_bf16(gelu2(a), gelu2(b));
}
struct cplx { float re, im; };
__device__ __forceinline__ cplx cmul(cplx a, cplx b) { return {fmaf(a.re, b.re, -a.im * b.im), fmaf(a.re, b.im, a.im * b.re)}; }
__device__ __forceinline__ cplx cfma(cplx a, cplx b, cplx c) {
  return {fmaf(a.re, b.re, fmaf(-a.im, b.im, c.re)), fmaf(a.re, b.im, fmaf(a.im, b.re, c.im))};
}
__device__ __forceinline__ cplx make_lam(float lre, float lim, float ldt) {
  float dt = __bfloat162float(__float2bfloat16_rn(expf(ldt)));
  float mag = expf(dt * lre), sn, cs;
  sincospif(dt * lim * 0.31830988618379067f, &sn, &cs);
  return {mag * cs, mag * sn};
}

template<int TA,int TB,uint32_t AH,uint32_t BH> __device__ __forceinline__ void wgmma_n64_ss(float (&d)[32], uint32_t al, uint32_t ao, uint32_t bl, uint32_t bo, int scale_d){
  asm volatile("{.reg .pred p; .reg .b32 t, v; .reg .b64 da, db; setp.ne.b32 p, %36, 0; add.u32 t, %32, %33; mov.b64 da, {t, %39}; add.u32 v, %34, %35; mov.b64 db, {v, %40};\n"
   "wgmma.mma_async.sync.aligned.m64n64k16.f32.bf16.bf16 {%0,%1,%2,%3,%4,%5,%6,%7,%8,%9,%10,%11,%12,%13,%14,%15,%16,%17,%18,%19,%20,%21,%22,%23,%24,%25,%26,%27,%28,%29,%30,%31}, da, db, p, 1, 1, %37, %38;}"
   : "+f"(d[0]),"+f"(d[1]),"+f"(d[2]),"+f"(d[3]),"+f"(d[4]),"+f"(d[5]),"+f"(d[6]),"+f"(d[7]),"+f"(d[8]),"+f"(d[9]),"+f"(d[10]),"+f"(d[11]),"+f"(d[12]),"+f"(d[13]),"+f"(d[14]),"+f"(d[15]),"+f"(d[16]),"+f"(d[17]),"+f"(d[18]),"+f"(d[19]),"+f"(d[20]),"+f"(d[21]),"+f"(d[22]),"+f"(d[23]),"+f"(d[24]),"+f"(d[25]),"+f"(d[26]),"+f"(d[27]),"+f"(d[28]),"+f"(d[29]),"+f"(d[30]),"+f"(d[31])
   : "r"(al),"r"(ao >> 4),"r"(bl),"r"(bo >> 4),"r"(scale_d),"n"(TA),"n"(TB),"n"(AH),"n"(BH));
}
template<int TB,uint32_t BH> __device__ __forceinline__ void wgmma_n64_rs(float (&d)[32], uint32_t a0,uint32_t a1,uint32_t a2,uint32_t a3, uint32_t bl, uint32_t bo, int scale_d){
  asm volatile("{.reg .pred p; .reg .b32 t; .reg .b64 db; setp.ne.b32 p, %38, 0; add.u32 t, %36, %37; mov.b64 db, {t, %40};\n"
   "wgmma.mma_async.sync.aligned.m64n64k16.f32.bf16.bf16 {%0,%1,%2,%3,%4,%5,%6,%7,%8,%9,%10,%11,%12,%13,%14,%15,%16,%17,%18,%19,%20,%21,%22,%23,%24,%25,%26,%27,%28,%29,%30,%31}, {%32,%33,%34,%35}, db, p, 1, 1, %39;}"
   : "+f"(d[0]),"+f"(d[1]),"+f"(d[2]),"+f"(d[3]),"+f"(d[4]),"+f"(d[5]),"+f"(d[6]),"+f"(d[7]),"+f"(d[8]),"+f"(d[9]),"+f"(d[10]),"+f"(d[11]),"+f"(d[12]),"+f"(d[13]),"+f"(d[14]),"+f"(d[15]),"+f"(d[16]),"+f"(d[17]),"+f"(d[18]),"+f"(d[19]),"+f"(d[20]),"+f"(d[21]),"+f"(d[22]),"+f"(d[23]),"+f"(d[24]),"+f"(d[25]),"+f"(d[26]),"+f"(d[27]),"+f"(d[28]),"+f"(d[29]),"+f"(d[30]),"+f"(d[31])
   : "r"(a0),"r"(a1),"r"(a2),"r"(a3),"r"(bl),"r"(bo >> 4),"r"(scale_d),"n"(TB),"n"(BH));
}
template<int TA,int TB,uint32_t AH,uint32_t BH> __device__ __forceinline__ void wgmma_n96_ss(float (&d)[48], uint32_t al, uint32_t ao, uint32_t bl, uint32_t bo, int scale_d){
  asm volatile("{.reg .pred p; .reg .b32 t, v; .reg .b64 da, db; setp.ne.b32 p, %52, 0; add.u32 t, %48, %49; mov.b64 da, {t, %55}; add.u32 v, %50, %51; mov.b64 db, {v, %56};\n"
   "wgmma.mma_async.sync.aligned.m64n96k16.f32.bf16.bf16 {%0,%1,%2,%3,%4,%5,%6,%7,%8,%9,%10,%11,%12,%13,%14,%15,%16,%17,%18,%19,%20,%21,%22,%23,%24,%25,%26,%27,%28,%29,%30,%31,%32,%33,%34,%35,%36,%37,%38,%39,%40,%41,%42,%43,%44,%45,%46,%47}, da, db, p, 1, 1, %53, %54;}"
   : "+f"(d[0]),"+f"(d[1]),"+f"(d[2]),"+f"(d[3]),"+f"(d[4]),"+f"(d[5]),"+f"(d[6]),"+f"(d[7]),"+f"(d[8]),"+f"(d[9]),"+f"(d[10]),"+f"(d[11]),"+f"(d[12]),"+f"(d[13]),"+f"(d[14]),"+f"(d[15]),"+f"(d[16]),"+f"(d[17]),"+f"(d[18]),"+f"(d[19]),"+f"(d[20]),"+f"(d[21]),"+f"(d[22]),"+f"(d[23]),"+f"(d[24]),"+f"(d[25]),"+f"(d[26]),"+f"(d[27]),"+f"(d[28]),"+f"(d[29]),"+f"(d[30]),"+f"(d[31]),"+f"(d[32]),"+f"(d[33]),"+f"(d[34]),"+f"(d[35]),"+f"(d[36]),"+f"(d[37]),"+f"(d[38]),"+f"(d[39]),"+f"(d[40]),"+f"(d[41]),"+f"(d[42]),"+f"(d[43]),"+f"(d[44]),"+f"(d[45]),"+f"(d[46]),"+f"(d[47])
   : "r"(al),"r"(ao >> 4),"r"(bl),"r"(bo >> 4),"r"(scale_d),"n"(TA),"n"(TB),"n"(AH),"n"(BH));
}
template<int TA,int TB,uint32_t AH,uint32_t BH> __device__ __forceinline__ void wgmma_n128_ss(float (&d)[64], uint32_t al, uint32_t ao, uint32_t bl, uint32_t bo, int scale_d){
  asm volatile("{.reg .pred p; .reg .b32 t, v; .reg .b64 da, db; setp.ne.b32 p, %68, 0; add.u32 t, %64, %65; mov.b64 da, {t, %71}; add.u32 v, %66, %67; mov.b64 db, {v, %72};\n"
   "wgmma.mma_async.sync.aligned.m64n128k16.f32.bf16.bf16 {%0,%1,%2,%3,%4,%5,%6,%7,%8,%9,%10,%11,%12,%13,%14,%15,%16,%17,%18,%19,%20,%21,%22,%23,%24,%25,%26,%27,%28,%29,%30,%31,%32,%33,%34,%35,%36,%37,%38,%39,%40,%41,%42,%43,%44,%45,%46,%47,%48,%49,%50,%51,%52,%53,%54,%55,%56,%57,%58,%59,%60,%61,%62,%63}, da, db, p, 1, 1, %69, %70;}"
   : "+f"(d[0]),"+f"(d[1]),"+f"(d[2]),"+f"(d[3]),"+f"(d[4]),"+f"(d[5]),"+f"(d[6]),"+f"(d[7]),"+f"(d[8]),"+f"(d[9]),"+f"(d[10]),"+f"(d[11]),"+f"(d[12]),"+f"(d[13]),"+f"(d[14]),"+f"(d[15]),"+f"(d[16]),"+f"(d[17]),"+f"(d[18]),"+f"(d[19]),"+f"(d[20]),"+f"(d[21]),"+f"(d[22]),"+f"(d[23]),"+f"(d[24]),"+f"(d[25]),"+f"(d[26]),"+f"(d[27]),"+f"(d[28]),"+f"(d[29]),"+f"(d[30]),"+f"(d[31]),"+f"(d[32]),"+f"(d[33]),"+f"(d[34]),"+f"(d[35]),"+f"(d[36]),"+f"(d[37]),"+f"(d[38]),"+f"(d[39]),"+f"(d[40]),"+f"(d[41]),"+f"(d[42]),"+f"(d[43]),"+f"(d[44]),"+f"(d[45]),"+f"(d[46]),"+f"(d[47]),"+f"(d[48]),"+f"(d[49]),"+f"(d[50]),"+f"(d[51]),"+f"(d[52]),"+f"(d[53]),"+f"(d[54]),"+f"(d[55]),"+f"(d[56]),"+f"(d[57]),"+f"(d[58]),"+f"(d[59]),"+f"(d[60]),"+f"(d[61]),"+f"(d[62]),"+f"(d[63])
   : "r"(al),"r"(ao >> 4),"r"(bl),"r"(bo >> 4),"r"(scale_d),"n"(TA),"n"(TB),"n"(AH),"n"(BH));
}

__global__ void __cluster_dims__(2, 1, 1) __launch_bounds__(384, 1)
fused_kernel(const __nv_bfloat16* __restrict__ lam_re, const __nv_bfloat16* __restrict__ lam_im, const __nv_bfloat16* __restrict__ log_dt,
             const __nv_bfloat16* __restrict__ dskip, const __nv_bfloat16* __restrict__ b1, const __nv_bfloat16* __restrict__ b2,
             const __nv_bfloat16* __restrict__ gate_w, const __nv_bfloat16* __restrict__ pf_w1, const __nv_bfloat16* __restrict__ pf_w2,
             const __nv_bfloat16* __restrict__ pf_cre, const __nv_bfloat16* __restrict__ pf_cim, float* __restrict__ out,
             const __grid_constant__ Maps maps) {
  extern __shared__ __align__(1024) unsigned char smem_raw[];
  const uint32_t sb = (uint32_t)__cvta_generic_to_shared(smem_raw);
  const int b = blockIdx.x;
  const int rank = b & 1, cl = b >> 1;
  const int sp = (cl & 1) | ((cl >> 2) & 2), m = ((cl >> 1) & 3) | ((cl >> 4) << 2);
  const int s = sp * 2 + rank;
  const int warp = __shfl_sync(0xffffffffu, (int)(threadIdx.x >> 5), 0);
  const int lane = threadIdx.x & 31;
  const int xrot = 9 - 2 * sp;

  if (elect_one()) {
    if (warp == 8) TS(2, 0);
    if (warp < 3) {
      asm volatile("prefetch.tensormap [%0];" ::"l"(&maps.x + warp) : "memory");
      mbar_init(sb + OFF_GBAR + 8 * warp, warp < 2 ? 64 : 96);
    }
    const uint32_t c = warp < 8 ? 1 : warp < 11 ? 8 : 4;
    mbar_init(sb + OFF_XFULL + 16 * warp, c);
    mbar_init(sb + OFF_XFULL + 16 * warp + 8, c);
    asm volatile("fence.mbarrier_init.release.cluster;" ::: "memory");
  }
  __syncwarp();
  asm volatile("barrier.cluster.arrive.relaxed.aligned;" ::: "memory");

  if (warp < 8) {
    const int wg = warp >> 2, w = warp & 3, q = lane & 3, gr = lane >> 2;
    uint32_t bv[28];
#pragma unroll
    for (int j = 0; j < 28; j++) bv[j] = __ldg(reinterpret_cast<const uint32_t*>(b1 + s * 224 + j * 8) + q);
    asm volatile("setmaxnreg.inc.sync.aligned.u32 224;");
    asm volatile("barrier.cluster.wait.aligned;" ::: "memory");
    TS(wg, 0);
    auto release = [&](int slot) { if (lane == 0) mbar_arrive(sb + OFF_EMPTY + 8 * slot); };
    const uint32_t xw = sb + OFF_X + wg * 8192, fullb = sb + OFF_FULL;
    const uint32_t dxw = (xw & 0x3FFFF) >> 4, dring = ((sb + OFF_RING) & 0x3FFFF) >> 4;

    float ure[32], uim[32], aa[48], ab[64];
    cplx lam[2], coef[2], l16[2], l32[2], lq[2], pre[2], e[2];
    uint32_t sh16, mhi;

#pragma unroll
    for (int kb = 0; kb < 8; kb++) {
      const int slot = kb % NSLOT;
      mbar_wait(sb + OFF_XFULL + 8 * kb, 0);
      if (kb == 0) TS(wg, 18);
      mbar_wait(fullb + 8 * slot, (kb / NSLOT) & 1);
      TS2(2, kb);
      if (kb == 0) TS(wg, 1);
      wg_fence();
      const uint32_t dxa = dxw + ((kb + xrot) & 7) * 1024;
#pragma unroll
      for (int kk = 0; kk < 4; kk++) {
        wgmma_n64_ss<0, 0, DH128, DH128>(ure, dring, slot * 16384 + kk * 32, dxa, kk * 32, (kb | kk) != 0);
        wgmma_n64_ss<0, 0, DH128, DH128>(uim, dring, slot * 16384 + 8192 + kk * 32, dxa, kk * 32, (kb | kk) != 0);
      }
      wg_commit();
      if (kb > 0) { wg_wait<1>(); release((kb - 1) % NSLOT); }
      if (kb == 1) { sh16 = late16(sb + OFF_XFULL); mhi = 0xffffffffu << sh16; }
      if (kb == 1 || (kb >= 3 && kb < 6)) {
#pragma unroll
        for (int j = 0; j < 28; j++) if (j / 7 == (kb == 1 ? 0 : kb - 2)) {
          pin(bv[j]);
          float* d = j < 12 ? aa + 4 * j : ab + 4 * (j - 12);
          d[0] = d[2] = __uint_as_float(bv[j] << sh16); d[1] = d[3] = __uint_as_float(bv[j] & mhi);
          pin(d[0]); pin(d[1]); pin(d[2]); pin(d[3]);
        }
      }
      if (kb == 5) {
        mbar_wait(sb + OFF_LBAR, 0);
#pragma unroll
        for (int h = 0; h < 2; h++) {
          const uint4 v = lds_u4(sb + OFF_LC + (w * 16 + gr + 8 * h) * 16);
          lam[h] = cplx{__uint_as_float(v.x), __uint_as_float(v.y)};
          coef[h] = cplx{__uint_as_float(v.z), __uint_as_float(v.w)};
        }
      }
      if (kb == 6) {
#pragma unroll
        for (int h = 0; h < 2; h++) {
          pin(lam[h].re); pin(lam[h].im);
          cplx t = cmul(lam[h], lam[h]); t = cmul(t, t); t = cmul(t, t);
          l16[h] = cmul(t, t);
          pin(l16[h].re); pin(l16[h].im);
        }
      }
      if (kb == 7) {
#pragma unroll
        for (int h = 0; h < 2; h++) {
          pin(l16[h].re); pin(l16[h].im);
          l32[h] = cmul(l16[h], l16[h]);
          const cplx a = (q & 1) ? l16[h] : cplx{1.f, 0.f}, c = (q & 2) ? l32[h] : cplx{1.f, 0.f};
          lq[h] = cmul(cmul(a, c), coef[h]);
          pin(lq[h].re); pin(lq[h].im);
        }
      }
    }
    TS(wg, 2);
    auto scale_u = [&](int i0, int i1) {
#pragma unroll
      for (int i = 0; i < 32; i++) if (i >= i0 && i < i1) {
        pin(ure[i]); pin(uim[i]);
        const cplx v = cmul(coef[(i >> 1) & 1], cplx{ure[i], uim[i]});
        ure[i] = v.re; uim[i] = v.im;
        pin(ure[i]); pin(uim[i]);
      }
    };
#pragma unroll
    for (int kb = 0; kb < 8; kb++) {
      const int u = 8 + kb, slot = u % NSLOT;
      mbar_wait(fullb + 8 * slot, (u / NSLOT) & 1);
      wg_fence();
      const uint32_t dxa = dxw + ((kb + xrot) & 7) * 1024;
#pragma unroll
      for (int kk = 0; kk < 4; kk++)
        wgmma_n96_ss<0, 1, DH128, DH64>(aa, dxa, kk * 32, dring, slot * 16384 + kk * 1024 + lbo(4096), 1);
      wg_commit();
      wg_wait<1>();
      release((u - 1) % NSLOT);
      if (kb == 0) {
        reg_fence(ure); reg_fence(uim);
#pragma unroll
        for (int h = 0; h < 2; h++) e[h] = cplx{ure[2 * h], uim[2 * h]};
      }
      if (kb == 0 || kb == 2 || kb == 3) {
        const int ch = kb ? kb - 1 : 0;
#pragma unroll
        for (int t = 1 + 5 * ch; t < 6 + 5 * ch; t++)
#pragma unroll
          for (int h = 0; h < 2; h++) { const int i = 4 * (t >> 1) + 2 * h + (t & 1); e[h] = cfma(lam[h], e[h], cplx{ure[i], uim[i]}); }
#pragma unroll
        for (int h = 0; h < 2; h++) { pin(e[h].re); pin(e[h].im); }
      } else if (kb == 4) {
#pragma unroll
        for (int h = 0; h < 2; h++) {
          cplx y = {__shfl_up_sync(0xffffffffu, e[h].re, 1, 4), __shfl_up_sync(0xffffffffu, e[h].im, 1, 4)};
          if (q >= 1) e[h] = cfma(l16[h], y, e[h]);
          y = cplx{__shfl_up_sync(0xffffffffu, e[h].re, 2, 4), __shfl_up_sync(0xffffffffu, e[h].im, 2, 4)};
          if (q >= 2) e[h] = cfma(l32[h], y, e[h]);
        }
        if (q == 3) {
#pragma unroll
          for (int h = 0; h < 2; h++)
            asm volatile("st.shared.v2.f32 [%0], {%1,%2};" ::"r"(sb + OFF_CARRY + wg * 512 + (w * 16 + gr + 8 * h) * 8), "f"(e[h].re), "f"(e[h].im) : "memory");
          mbar_arrive(sb + OFF_GBAR);
        }
#pragma unroll
        for (int h = 0; h < 2; h++) {
          const cplx y = {__shfl_up_sync(0xffffffffu, e[h].re, 1, 4), __shfl_up_sync(0xffffffffu, e[h].im, 1, 4)};
          pre[h] = (q >= 1) ? cmul(coef[h], y) : cplx{0.f, 0.f};
          pin(pre[h].re); pin(pre[h].im);
        }
        TS(wg, 3);
      } else if (kb > 4) {
        scale_u(kb == 5 ? 0 : kb == 6 ? 4 : 12, kb == 5 ? 4 : kb == 6 ? 12 : 20);
      }
    }
    TS(wg, 4);
    uint32_t H[56];
    cplx hst[2];
    const uint32_t hst_addr = xw + (w * 16 + (lane & 15)) * 128 + (((lane >> 4) ^ (lane & 7)) << 4);
    const uint32_t him = (2 - rank) * 16384;
    uint32_t peer;
    asm volatile("mapa.shared::cluster.u32 %0, %1, %2;" : "=r"(peer) : "r"(sb), "r"(rank ^ 1));
    auto credit = [&]() { if (lane == 0) mbar_arrive_cl(peer + OFF_KBAR + wg * 8); };
#pragma unroll
    for (int kb = 0; kb < 8; kb++) {
      const int u = 16 + kb, slot = u % NSLOT;
      mbar_wait(fullb + 8 * slot, (u / NSLOT) & 1);
      wg_fence();
#pragma unroll
      for (int kk = 0; kk < 4; kk++)
        wgmma_n128_ss<0, 1, DH128, DH128>(ab, dxw, kb * 16384 + kk * 32, dring, slot * 16384 + kk * 2048 + lbo(8192), 1);
      wg_commit();
      wg_wait<1>();
      release((u - 1) % NSLOT);
      if (kb == 0) scale_u(20, 32);
      if (kb < 5 && kb != 1) {
        const int ch = kb ? kb - 1 : 0;
#pragma unroll
        for (int i = ch * 6; i < ch * 6 + 6; i++) {
          pin(aa[2 * i]); pin(aa[2 * i + 1]);
          H[i] = gelu2_pair(aa[2 * i], aa[2 * i + 1]);
          pin(H[i]);
        }
      }
      if (kb >= 4) {
        if (kb == 4) {
          TS(wg, 5);
          mbar_wait(sb + OFF_CBAR, 0);
          TS(wg, 6);
#pragma unroll
          for (int h = 0; h < 2; h++) {
            const float2 c = lds_f2(sb + OFF_CARRY + wg * 512 + (w * 16 + gr + 8 * h) * 8);
            hst[h] = cfma(lq[h], cplx{c.x, c.y}, pre[h]);
          }
        }
        const int j0 = (kb - 4) * 2;
        uint32_t rr[4], ri[4];
#pragma unroll
        for (int jj = 0; jj < 2; jj++) {
          const int j = j0 + jj;
          const uint32_t g2 = lds_u(sb + OFF_GS + (wg * 64 + j * 8 + q * 2) * 2);
#pragma unroll
          for (int h = 0; h < 2; h++) {
            const int i = 4 * j + 2 * h;
            const cplx h0 = cfma(lam[h], hst[h], cplx{ure[i], uim[i]});
            hst[h] = cfma(lam[h], h0, cplx{ure[i + 1], uim[i + 1]});
            rr[jj * 2 + h] = bf2_mul(pack_bf16(h0.re, hst[h].re), g2);
            ri[jj * 2 + h] = bf2_mul(pack_bf16(h0.im, hst[h].im), g2 ^ 0x80008000u);
          }
        }
        const uint32_t a = hst_addr ^ (j0 << 4);
        asm volatile("stmatrix.sync.aligned.m8n8.x4.shared.b16 [%0], {%1,%2,%3,%4};" ::"r"(a), "r"(rr[0]), "r"(rr[1]), "r"(rr[2]), "r"(rr[3]) : "memory");
        asm volatile("stmatrix.sync.aligned.m8n8.x4.shared.b16 [%0], {%1,%2,%3,%4};" ::"r"(a + him), "r"(ri[0]), "r"(ri[1]), "r"(ri[2]), "r"(ri[3]) : "memory");
      }
    }
    TS(wg, 7);

    uint4* const psend = g_part + (size_t)(m * 8 + rank) * 3072 + warp * 128 + lane;
    const uint4* const precv = g_part + (size_t)(m * 8 + s) * 3072 + warp * 128 + lane;
    const uint32_t pbuf = OFF_X + warp * 2048 + lane * 16;
    const uint32_t dx0 = ((sb + OFF_X) & 0x3FFFF) >> 4, dhi = dxw + (him >> 4);
    float o[32], o2[32], rho[2];
    uint32_t tr[8];
    uint32_t r0[16], pt[16], sum[16], xs[16], tag;
    auto recv_issue = [&](uint32_t (&r)[16], int k) {
#pragma unroll
      for (int i = 0; i < 4; i++) ld_b128(precv + k * 1024 + i * 32, r[4 * i], r[4 * i + 1], r[4 * i + 2], r[4 * i + 3]);
    };
    auto stale = [&](uint32_t (&r)[16]) {
      uint32_t t0, t1, r_;
      asm("lop3.b32 %0, %1, %2, %3, 0x7e;" : "=r"(t0) : "r"(r[0]), "r"(r[4]), "r"(tag));
      asm("lop3.b32 %0, %1, %2, %3, 0x7e;" : "=r"(t1) : "r"(r[8]), "r"(r[12]), "r"(tag));
      asm volatile("{.reg .pred p; .reg .b32 t; lop3.b32 t, %1, %2, 1, 0xa8; setp.ne.u32 p, t, 0; vote.sync.any.pred p, p, 0xffffffff; selp.u32 %0, 1, 0, p;}" : "=r"(r_) : "r"(t0), "r"(t1));
      return r_ != 0;
    };
    auto recv_check = [&](uint32_t (&r)[16], int k) {
      if (__builtin_expect(stale(r), 0)) {
        int tries = 0;
#pragma unroll 1
        do { recv_issue(r, k); } while (stale(r) && ++tries < 200000);
      }
    };
    auto gelu_b = [&](int i0, int i1) {
#pragma unroll
      for (int i = i0; i < i1; i++) {
        pin(ab[2 * i]); pin(ab[2 * i + 1]);
        H[24 + i] = gelu2_pair(ab[2 * i], ab[2 * i + 1]);
        pin(H[24 + i]);
      }
    };
    auto step = [&](float (&d)[32], int p, int k, int acc) {
      const uint32_t wo = stage_off(p);
      if (k >= 6 && k < 14) {
        const int kk = k - 6;
        wgmma_n64_ss<1, 0, DH128, DH128>(d, kk < 4 ? dxw : dhi, (kk & 3) * 2048, dx0, wo + 14336 + (kk >> 2) * 8192 + (kk & 3) * 32, 1);
      } else {
        const int kk = k < 6 ? k : k - 8;
        wgmma_n64_rs<1, DH128>(d, H[4 * kk], H[4 * kk + 1], H[4 * kk + 2], H[4 * kk + 3], dx0, wo + (kk / 7) * 30720 + (kk % 7) * 2048, k != 0 || acc);
      }
    };
    auto mma = [&](float (&d)[32], int p, int k0, int k1, int acc) {
      wg_fence();
#pragma unroll
      for (int k = k0; k < k1; k++) step(d, p, k, acc);
      wg_commit();
    };
    auto mma2 = [&](int k0, int k1) {
      wg_fence();
#pragma unroll
      for (int k = k0; k < k1; k++) { step(o, 0, k, 0); step(o2, 1, k, 0); }
      wg_commit();
    };
    auto send_peer = [&](int i0, int i1) {
#pragma unroll
      for (int i = i0; i < i1; i++)
        asm volatile("st.async.shared::cluster.mbarrier::complete_tx::bytes.v4.b32 [%0], {%1,%2,%3,%4}, [%5];" ::"r"(peer + pbuf + him + i * 512),
                     "r"(pack_bf16(o[8 * i], o[8 * i + 1])), "r"(pack_bf16(o[8 * i + 2], o[8 * i + 3])), "r"(pack_bf16(o[8 * i + 4], o[8 * i + 5])),
                     "r"(pack_bf16(o[8 * i + 6], o[8 * i + 7])), "r"(peer + OFF_RBAR + wg * 8) : "memory");
    };
    auto recv_peer = [&](int d) {
      mbar_wait(sb + OFF_RBAR + wg * 8, d & 1);
#pragma unroll
      for (int i = 0; i < 4; i++) { const uint4 v = lds_u4(sb + pbuf + (49152 - him) + i * 512); pt[4 * i] = v.x; pt[4 * i + 1] = v.y; pt[4 * i + 2] = v.z; pt[4 * i + 3] = v.w; }
    };
    auto arm = [&]() { if ((threadIdx.x & 127) == 0) mbar_expect_tx(sb + OFF_RBAR + wg * 8, 8192); };
    auto send_owner = [&](int k, int i0, int i1) {
#pragma unroll
      for (int i = i0; i < i1; i++) {
#pragma unroll
        for (int c = 4 * i; c < 4 * i + 4; c++) pt[c] = bf2_add(pt[c], pack_bf16(o2[2 * c], o2[2 * c + 1]));
        asm("lop3.b32 %0, %0, 1, %1, 0xb8;" : "+r"(pt[4 * i]) : "r"(tag));
        st_b128(psend + (((sp + 1 + k) & 3) * 6 + k) * 1024 + i * 32, pt[4 * i], pt[4 * i + 1], pt[4 * i + 2], pt[4 * i + 3]);
      }
    };
    float2 b2v[8];
    auto start_value = [&](int i0, int i1) {
#pragma unroll
      for (int i = i0; i < i1; i++) {
        o2[2 * i] = fmaf(bf_lo(xs[i]), rho[i & 1], b2v[i >> 1].x);
        o2[2 * i + 1] = fmaf(bf_hi(xs[i]), rho[i & 1], b2v[i >> 1].y);
        pin(o2[2 * i]); pin(o2[2 * i + 1]);
      }
    };
    mbar_wait(fullb, 0);
    mma2(0, 3);
    asm volatile("fence.proxy.async.shared::cta;" ::: "memory");
#pragma unroll
    for (int i = 0; i < 4; i++)
      asm volatile("ldmatrix.sync.aligned.m8n8.x4.shared.b16 {%0,%1,%2,%3}, [%4];" : "=r"(xs[4 * i]), "=r"(xs[4 * i + 1]), "=r"(xs[4 * i + 2]), "=r"(xs[4 * i + 3])
                   : "r"((hst_addr ^ (i << 5)) + (49152 - him)) : "memory");
    tag = lds_u(sb + OFF_EPOCH);
    arm();
    wg_wait<1>(); release(5);
    bar_sync(1 + wg, 128);
    credit();
    mbar_wait(fullb + 8, 0);
    if (wg == 1) bar_sync(4, 256);
    mma2(3, 6);   gelu_b(0, 4);
    mma2(6, 8);   gelu_b(4, 8);
    mma2(8, 11);  gelu_b(8, 12);
    mma2(11, 13); gelu_b(12, 16);
    if (A0 == 4 && wg == 0) bar_arrive(4, 256);
    mma2(13, 15); gelu_b(16, 20);
    if (A0 == 5 && wg == 0) bar_arrive(4, 256);
    mbar_wait(fullb + 16, 0);
    mma2(15, 17); gelu_b(20, 24);
    if (A0 == 6 && wg == 0) bar_arrive(4, 256);
    mma2(17, 19); gelu_b(24, 28);
    if (A0 == 7 && wg == 0) bar_arrive(4, 256);
    mma2(19, 21); gelu_b(28, 32);
    if (A0 == 8 && wg == 0) bar_arrive(4, 256);
    mma2(21, 22);
    TS(wg, 9);
    mbar_wait(sb + OFF_KBAR + wg * 8, 0);
    wg_wait<0>();
    release(0); release(1);
    reg_fence(o); reg_fence(o2);
    send_peer(0, 4);
#pragma unroll
    for (int p = 2; p < 8; p++) {
      const int k = (p - 1) >> 1;
      TR(0);
      mbar_wait(sb + OFF_XFULL + 8 * p, 1);
      TR(1);
      if (p & 1) {
        mma(o2, p, 0, G1, p == 7);
        TR(2);
        mbar_wait(sb + OFF_KBAR + wg * 8, k & 1);
        wg_wait<1>();
        if (p < 6) release(p - 1);
        reg_fence(o);
        send_peer(0, 2);
        TR(3);
        mma(o2, p, G1, G2, 1);
        TR(4);
        send_peer(2, 4);
        if (p == 7) recv_issue(xs, 2);
        TR(5);
        mma(o2, p, G2, 22, 1);
        TR(6);
        if (p == 3) {
          const uint4 d0 = lds_u4(sb + OFF_DB + q * 32), d1 = lds_u4(sb + OFF_DB + q * 32 + 16);
          const uint32_t dk[8] = {d0.x, d0.y, d0.z, d0.w, d1.x, d1.y, d1.z, d1.w};
#pragma unroll
          for (int i = 0; i < 16; i++) { xs[i] = bf2_mul(xs[i], dk[i >> 1]); pin(xs[i]); }
#pragma unroll
          for (int h = 0; h < 2; h++) rho[h] = 0.5f * bf_lo(lds_h(sb + OFF_GS + (wg * 64 + w * 16 + gr + 8 * h) * 2));
        }
        if (p == 5) {
#pragma unroll
          for (int i = 0; i < 4; i++) {
            const uint4 v = lds_u4(sb + OFF_DB + 128 + q * 64 + i * 16);
            b2v[2 * i] = make_float2(__uint_as_float(v.x), __uint_as_float(v.y)); b2v[2 * i + 1] = make_float2(__uint_as_float(v.z), __uint_as_float(v.w));
          }
        }
      } else {
        mma(o, p, 0, G1, 0);
        TR(2);
        recv_peer(k);
        arm();
        if (p > 2) { wg_wait<1>(); if (p < 6) release(p - 1); reg_fence(o2); }
        send_owner(k, 0, 2);
        TR(3);
        mma(o, p, G1, G2, 0);
        TR(4);
        send_owner(k, 2, 4);
        credit();
        if (p == 6) start_value(0, 8);
        TR(5);
        mma(o, p, G2, 22, 0);
        TR(6);
        if (p == 4) recv_issue(sum, 0);
        if (p == 6) {
          recv_issue(r0, 1);
          start_value(8, 16);
#pragma unroll
          for (int h = 0; h < 2; h++) { rho[h] = __fdividef(1.f, 2.f + rho[h]); pin(rho[h]); }
        }
      }
      TR(7);
      if (p != TP) TS(wg, 8 + p);
    }
    {
      const int p = 8;
      TR(0);
      tag = lds_u(sb + OFF_EPOCH);
      mbar_wait(sb + OFF_EMPTY + 32, 0);
      recv_check(sum, 0); recv_check(r0, 1);
#pragma unroll
      for (int i = 0; i < 16; i++) sum[i] = bf2_add(sum[i], r0[i]);
      TR(1);
      recv_peer(3);
      TR(2);
#pragma unroll
      for (int i = 0; i < 16; i++) sum[i] = bf2_add(sum[i], pt[i]);
      TR(3);
      recv_check(xs, 2);
#pragma unroll
      for (int i = 0; i < 16; i++) sum[i] = bf2_add(sum[i], xs[i]);
      TR(4);
      wg_wait<0>();
      reg_fence(o2);
      TR(5);
      const uint32_t tb = sb + OFF_X + 49152 + warp * 4096;
      const uint32_t ta = tb + gr * 128 + (((q >> 1) ^ gr) << 4) + (q & 1) * 8;
#pragma unroll
      for (int ch = 0; ch < 2; ch++) {
#pragma unroll
        for (int i = ch * 8; i < ch * 8 + 8; i++)
          asm volatile("st.shared.v2.f32 [%0], {%1,%2};" ::"r"((ta ^ (((i >> 1) & 3) << 5)) + (i & 1) * 1024 + ch * 2048),
                       "f"((o2[2 * i] + bf_lo(sum[i])) * rho[i & 1]), "f"((o2[2 * i + 1] + bf_hi(sum[i])) * rho[i & 1]) : "memory");
        if (OUT_TMA == 2 || ch == 1) {
          asm volatile("fence.proxy.async.shared::cta;" ::: "memory");
          __syncwarp();
          if (elect_one()) {
#pragma unroll
            for (int c2 = (OUT_TMA == 2 ? ch : 0); c2 <= ch; c2++)
              asm volatile("cp.async.bulk.tensor.5d.global.shared::cta.bulk_group [%0, {%2,%5,%5,%3,%4}], [%1];"
                           ::"l"(&maps.out), "r"(tb + c2 * 2048), "r"(s * 64 + c2 * 32), "r"(2 * w), "r"(2 * m + wg), "r"(0) : "memory");
            asm volatile("cp.async.bulk.commit_group;" ::: "memory");
          }
        }
      }
      TR(6);
      if (elect_one()) asm volatile("cp.async.bulk.wait_group.read 0;" ::: "memory");
      TR(7);
      if (threadIdx.x == 128) g_epoch[b] = tag;
      TS(wg, 17); TG(wg); TRD(); TDUMP();
    }
  } else {
    asm volatile("setmaxnreg.dec.sync.aligned.u32 56;");
    int wsel = warp;
    asm("" : "+r"(wsel));
    if (wsel > 8) {
      if (warp != 11) {
        const int t = threadIdx.x - 288;
        unsigned par;
        asm volatile("ld.relaxed.gpu.global.u32 %0, [%1];" : "=r"(par) : "l"(g_epoch + b) : "memory");
        const float pr = bf_ld(lam_re + s * 64 + t), pi = bf_ld(lam_im + s * 64 + t), pd = bf_ld(log_dt + s * 64 + t);
        asm volatile("barrier.cluster.wait.aligned;" ::: "memory");
        par = (par + 1) & 1;
        cplx l64 = make_lam(pr, pi, pd);
        {
          const float inv = __fdividef(1.f, fmaf(pr, pr, pi * pi));
          const cplx cf = cmul(cplx{l64.re - 1.f, l64.im}, cplx{pr * inv, -pi * inv});
          asm volatile("st.shared.v4.f32 [%0], {%1,%2,%3,%4};" ::"r"(sb + OFF_LC + t * 16), "f"(l64.re), "f"(l64.im), "f"(cf.re), "f"(cf.im) : "memory");
          mbar_arrive(sb + OFF_LBAR);
        }
#pragma unroll
        for (int i = 0; i < 6; i++) l64 = cmul(l64, l64);
        cplx l128 = cmul(l64, l64);
        pin(l128.re); pin(l128.im);
        mbar_wait(sb + OFF_GBAR, 0);
        const float2 e0 = lds_f2(sb + OFF_CARRY + t * 8), e1 = lds_f2(sb + OFF_CARRY + 512 + t * 8);
        float2* eb = g_end + s * 1024 + t;
        {
          const cplx e = cfma(l64, cplx{e0.x, e0.y}, cplx{e1.x, e1.y});
          const unsigned long long v = ((unsigned long long)__float_as_uint(e.im) << 32) | ((__float_as_uint(e.re) & ~1u) | par);
          asm volatile("st.relaxed.gpu.global.b64 [%0], %1;" ::"l"(eb + m * 64), "l"(v) : "memory");
        }
        if (t == 0) TS(3, 1);
        cplx S = {0.f, 0.f};
        {
          unsigned long long v[15];
          uint32_t bad;
          int tries = 0;
          const float2* e15 = eb + (m - 15) * 64;
#pragma unroll 1
          do {
#pragma unroll
            for (int i = 0; i < 15; i++) {
              v[i] = par;
              asm volatile("{.reg .pred p; setp.ge.s32 p, %2, %3; @p ld.relaxed.gpu.global.b64 %0, [%1];}" : "+l"(v[i]) : "l"(e15 + i * 64), "r"(m), "r"(15 - i) : "memory");
            }
            bad = 0;
#pragma unroll
            for (int i = 0; i < 15; i++) bad |= (uint32_t)v[i] ^ par;
          } while ((bad & 1) && ++tries < 200000);
          if (t == 0) TS(3, 2);
#pragma unroll
          for (int i = 0; i < 15; i++) S = cfma(l128, S, cplx{__uint_as_float((uint32_t)v[i] & ~1u), __uint_as_float((uint32_t)(v[i] >> 32))});
        }
        const cplx S1 = cfma(l64, S, cplx{e0.x, e0.y});
        asm volatile("st.shared.v2.f32 [%0], {%1,%2};" ::"r"(sb + OFF_CARRY + t * 8), "f"(S.re), "f"(S.im) : "memory");
        asm volatile("st.shared.v2.f32 [%0], {%1,%2};" ::"r"(sb + OFF_CARRY + 512 + t * 8), "f"(S1.re), "f"(S1.im) : "memory");
        mbar_arrive(sb + OFF_CBAR);
        if (t == 0) TS(3, 3);
      } else {
        if (lane == 0) TG(2);
        const uint4* gwp = reinterpret_cast<const uint4*>(gate_w) + (lane & 7);
        uint4 gw[4];
#pragma unroll
        for (int i = 0; i < 4; i++) gw[i] = __ldg(gwp + i * 8);
        unsigned par;
        asm volatile("ld.relaxed.gpu.global.u32 %0, [%1];" : "=r"(par) : "l"(g_epoch + b) : "memory");
        const uint32_t dk = __ldg(reinterpret_cast<const uint32_t*>(dskip + s * 64) + lane), bb = __ldg(reinterpret_cast<const uint32_t*>(b2 + s * 64) + lane);
        asm volatile("barrier.cluster.wait.aligned;" ::: "memory");
        const int row = s * 16 + (lane >> 3);
        const uint32_t xr0 = sb + OFF_X + row * 128 + (((lane & 7) ^ (row & 7)) << 4), xr1 = (xr0 + 512) ^ 64;
        float z[4] = {0.f, 0.f, 0.f, 0.f};
#pragma unroll
        for (int kb = 0; kb < 8; kb++) {
          const uint32_t wv[4] = {gw[kb & 3].x, gw[kb & 3].y, gw[kb & 3].z, gw[kb & 3].w};
          if (kb < 4) gw[kb] = __ldg(gwp + (kb + 4) * 8);
          mbar_wait(sb + OFF_XFULL + 8 * kb, 0);
          if ((PF & 2) && kb == PFK && elect_one()) {
            l2_prefetch(pf_w1 + b * 7168, 14336);
            l2_prefetch(pf_cre + b * 2048, 4096);
            l2_prefetch(pf_cim + b * 2048, 4096);
            l2_prefetch(pf_w2 + b * 7168, 14336);
          }
          const uint32_t xo = ((kb + xrot) & 7) * 16384;
#pragma unroll
          for (int r = 0; r < 4; r++) {
            const uint4 a = lds_u4(((r & 1) ? xr1 : xr0) + xo + (r >> 1) * 1024);
            const uint32_t p = bf2_fma(a.w, wv[3], bf2_fma(a.z, wv[2], bf2_fma(a.y, wv[1], bf2_mul(a.x, wv[0]))));
            z[r] += bf_lo(p); z[r] += bf_hi(p);
          }
        }
        if (lane == 0) asm volatile("st.shared.u32 [%0], %1;" ::"r"(sb + OFF_EPOCH), "r"(par + 1) : "memory");
        par = (par + 1) & 1;
        {
          float y0 = (lane & 4) ? z[1] : z[0], y1 = (lane & 4) ? z[3] : z[2];
          y0 += __shfl_xor_sync(0xffffffffu, (lane & 4) ? z[0] : z[1], 4);
          y1 += __shfl_xor_sync(0xffffffffu, (lane & 4) ? z[2] : z[3], 4);
          float zz = (lane & 2) ? y1 : y0;
          zz += __shfl_xor_sync(0xffffffffu, (lane & 2) ? y0 : y1, 2);
          zz += __shfl_xor_sync(0xffffffffu, zz, 1);
          const float rho = 4.f * expf(zz > 40.f ? 40.f : zz);
          if ((lane & 1) == 0)
            asm volatile("st.relaxed.gpu.global.u32 [%0], %1;" ::"l"(g_gate + m * 128 + row + (lane & 4) + (lane & 2) * 4), "r"((__float_as_uint(rho) & ~1u) | par) : "memory");
        }
        if (lane == 0) TS(3, 0);
        mbar_wait(sb + OFF_GBAR, 0);
        asm volatile("st.shared.b32 [%0], %1;" ::"r"(sb + OFF_DB + (lane & 3) * 32 + (lane >> 2) * 4), "r"(dk) : "memory");
        asm volatile("st.shared.v2.f32 [%0], {%1,%2};" ::"r"(sb + OFF_DB + 128 + (lane & 3) * 64 + (lane >> 2) * 8), "f"(2.f * bf_lo(bb)), "f"(2.f * bf_hi(bb)) : "memory");
        uint32_t g0, g1, g2, g3;
        int tries = 0;
#pragma unroll 1
        do {
          asm volatile("ld.relaxed.gpu.global.v4.u32 {%0,%1,%2,%3}, [%4];" : "=r"(g0), "=r"(g1), "=r"(g2), "=r"(g3) : "l"(g_gate + m * 128 + lane * 4) : "memory");
        } while ((((g0 ^ par) | (g1 ^ par) | (g2 ^ par) | (g3 ^ par)) & 1) && ++tries < 200000);
        asm volatile("st.shared.v2.u32 [%0], {%1,%2};" ::"r"(sb + OFF_GS + lane * 8), "r"(pack_bf16(__uint_as_float(g0), __uint_as_float(g1))),
                     "r"(pack_bf16(__uint_as_float(g2), __uint_as_float(g3))) : "memory");
        mbar_arrive(sb + OFF_CBAR);
        if (lane == 0) TS(3, 4);
      }
    } else {
      asm volatile("barrier.cluster.wait.aligned;" ::: "memory");
      if (elect_one()) {
        TS(2, 1);
        const uint32_t t0 = clock();
#pragma unroll 1
        for (int u = 0; u < 8; u++) {
          if (u >= 1) while ((uint32_t)clock() - t0 < D0 + (u - 1) * D1) {}
          mbar_expect_tx(sb + OFF_XFULL + 8 * u, 16384);
          tma5d_mc(sb + OFF_X + ((u + xrot) & 7) * 16384 + rank * 8192, &maps.x, u * 64, 2 * m + rank, sb + OFF_XFULL + 8 * u);
          if (u < 6) {
            mbar_expect_tx(sb + OFF_FULL + 8 * u, 16384);
            tma2d(sb + OFF_RING + u * 16384, &maps.bre, u * 64, s * 64, sb + OFF_FULL + 8 * u);
            tma2d(sb + OFF_RING + u * 16384 + 8192, &maps.bim, u * 64, s * 64, sb + OFF_FULL + 8 * u);
          } else if (PF & 4) {
            asm volatile("cp.async.bulk.prefetch.tensor.2d.L2.global [%0, {%1,%2}];" ::"l"((m & 1) ? &maps.bim : &maps.bre), "r"(u * 64), "r"(s * 64) : "memory");
          }
        }
        TS(2, 5);
        int slot = 0; uint32_t ph = 0;
#pragma unroll 1
        for (int u = 6; u < 24; u++) {
          const uint32_t fb = sb + OFF_FULL + 8 * slot, dst = sb + OFF_RING + slot * 16384;
          mbar_wait(sb + OFF_EMPTY + 8 * slot, ph);
          TS2(0, u);
          if (u < 8) {
            mbar_expect_tx(fb, 16384);
            tma2d(dst, &maps.bre, u * 64, s * 64, fb);
            tma2d(dst + 8192, &maps.bim, u * 64, s * 64, fb);
          } else if (u < 16) {
            mbar_expect_tx(fb, 12288);
            tma3d(dst, &maps.w1b, 0, (u - 8) * 64, s * 7, fb);
          } else {
            mbar_expect_tx(fb, 16384);
            tma2d(dst, &maps.w1a, s * 224 + 96, ((u - xrot) & 7) * 64, fb);
            tma2d(dst + 8192, &maps.w1a, s * 224 + 160, ((u - xrot) & 7) * 64, fb);
          }
          if (++slot == NSLOT) { slot = 0; ph ^= 1; }
        }
#pragma unroll 1
        for (int j = 0; j < 3; j++) {
          const uint32_t fb = sb + OFF_FULL + 8 * j;
          mbar_wait(sb + OFF_EMPTY + 8 + 8 * j, 1);
          mbar_expect_tx(fb, j == 1 ? 32768 : 28672);
#pragma unroll
          for (int e = 0; e < 2; e++) {
            const int c = ((sp + 1) & 3) * 128 + ((rank ^ e ^ 1) << 6);
            const uint32_t dst = sb + OFF_X + stage_off(e);
            if (j == 1) {
              tma2d(dst + 14336, &maps.cre, s * 64, c, fb);
              tma2d(dst + 22528, &maps.cim, s * 64, c, fb);
            } else {
              tma2d(dst + j * 15360, &maps.w2, c, s * 224 + j * 56, fb);
            }
          }
        }
#pragma unroll 1
        for (int p = 2; p < 8; p++) {
          const int c = ((sp + 1 + (p >> 1)) & 3) * 128 + (((rank ^ p ^ 1) & 1) << 6);
          const uint32_t fb = sb + OFF_XFULL + 8 * p, dst = sb + OFF_X + stage_off(p);
          if (p != 3) mbar_wait(sb + OFF_EMPTY + (p == 2 ? 40 : (p - 4) * 8), p == 2);
          TS2(0, 32 + p);
          mbar_expect_tx(fb, 45056);
          tma2d(dst, &maps.w2, c, s * 224, fb);
          tma2d(dst + 14336, &maps.cre, s * 64, c, fb);
          tma2d(dst + 22528, &maps.cim, s * 64, c, fb);
          tma2d(dst + 30720, &maps.w2, c, s * 224 + 112, fb);
        }
        asm volatile("prefetch.tensormap [%0];" ::"l"(&maps.out) : "memory");
        TS(2, 2);
      }
    }
  }
}

typedef CUresult (*EncFn)(CUtensorMap*, CUtensorMapDataType, cuuint32_t, void*, const cuuint64_t*, const cuuint64_t*, const cuuint32_t*,
                          const cuuint32_t*, CUtensorMapInterleave, CUtensorMapSwizzle, CUtensorMapL2promotion, CUtensorMapFloatOOBfill);

void encode(EncFn f, CUtensorMap* mp, const void* p, int rank, const cuuint64_t* dims, const cuuint64_t* strides, const cuuint32_t* box, CUtensorMapSwizzle sw,
            CUtensorMapDataType ty = CU_TENSOR_MAP_DATA_TYPE_BFLOAT16) {
  cuuint32_t es[5] = {1, 1, 1, 1, 1};
  f(mp, ty, rank, const_cast<void*>(p), dims, strides, box, es, CU_TENSOR_MAP_INTERLEAVE_NONE, sw,
    CU_TENSOR_MAP_L2_PROMOTION_L2_128B, CU_TENSOR_MAP_FLOAT_OOB_FILL_NONE);
}

}

extern "C" void kernel_launch(void* const* d_in, const int* in_sizes, int n_in, void* d_out, int out_size) {
  typedef const __nv_bfloat16* bp;
  bp x = (bp)d_in[0], lre = (bp)d_in[1], lim = (bp)d_in[2], bre = (bp)d_in[3], bim = (bp)d_in[4], cre = (bp)d_in[5], cim = (bp)d_in[6],
     ldt = (bp)d_in[7], dsk = (bp)d_in[8], w1 = (bp)d_in[10], b1 = (bp)d_in[11], w2 = (bp)d_in[12], b2 = (bp)d_in[13], gw = (bp)d_in[14];
  static EncFn enc = nullptr;
  if (!enc) {
    void* f = nullptr;
    cudaDriverEntryPointQueryResult qr;
    cudaGetDriverEntryPoint("cuTensorMapEncodeTiled", &f, cudaEnableDefault, &qr);
    enc = (EncFn)f;
    cudaFuncSetAttribute(fused_kernel, cudaFuncAttributeMaxDynamicSharedMemorySize, SMEM_BYTES);
  }
  Maps maps;
  {
    cuuint64_t d[5] = {DM, 2, 4, 8, SEQ / 64}, st[4] = {DM * 2, 16 * DM * 2, 2 * DM * 2, 64 * DM * 2};
    cuuint32_t bx[5] = {64, 2, 4, 8, 1};
    encode(enc, &maps.x, x, 5, d, st, bx, CU_TENSOR_MAP_SWIZZLE_128B);
    cuuint64_t so[4] = {DM * 4, 16 * DM * 4, 2 * DM * 4, 64 * DM * 4};
    cuuint32_t bo[5] = {32, 2, 4, 2, 1};
    encode(enc, &maps.out, d_out, 5, d, so, bo, CU_TENSOR_MAP_SWIZZLE_128B, CU_TENSOR_MAP_DATA_TYPE_FLOAT32);
  }
  {
    cuuint64_t d[2] = {DM, DM}, st[1] = {DM * 2};
    cuuint32_t bx[2] = {64, 64};
    encode(enc, &maps.bre, bre, 2, d, st, bx, CU_TENSOR_MAP_SWIZZLE_128B);
    encode(enc, &maps.bim, bim, 2, d, st, bx, CU_TENSOR_MAP_SWIZZLE_128B);
    encode(enc, &maps.cre, cre, 2, d, st, bx, CU_TENSOR_MAP_SWIZZLE_128B);
    encode(enc, &maps.cim, cim, 2, d, st, bx, CU_TENSOR_MAP_SWIZZLE_128B);
  }
  {
    cuuint64_t d[2] = {FF, DM}, st[1] = {FF * 2};
    cuuint32_t bx[2] = {64, 64};
    encode(enc, &maps.w1a, w1, 2, d, st, bx, CU_TENSOR_MAP_SWIZZLE_128B);
    cuuint64_t d3[3] = {32, DM, FF / 32}, st3[2] = {FF * 2, 64};
    cuuint32_t bx3[3] = {32, 64, 3};
    encode(enc, &maps.w1b, w1, 3, d3, st3, bx3, CU_TENSOR_MAP_SWIZZLE_64B);
  }
  {
    cuuint64_t d[2] = {DM, FF}, st[1] = {DM * 2};
    cuuint32_t bx[2] = {64, 112};
    encode(enc, &maps.w2, w2, 2, d, st, bx, CU_TENSOR_MAP_SWIZZLE_128B);
  }
  fused_kernel<<<128, 384, SMEM_BYTES>>>(lre, lim, ldt, dsk, b1, b2, gw, w1, w2, cre, cim, (float*)d_out, maps);
}
```

```cpp
#include <cuda_runtime.h>
#include <cuda_bf16.h>
#include <cuda.h>
#include <stdint.h>

#define MAP 1
#define D0 600
#define D1 500
#define PF 6
#define PFK 5
#define GELUP 0
#define EW 1
#define K1E 0
#define K2E 2
#define QS 1
#define K2G 4
#define TP 9
#define TW 0

namespace {

constexpr int SEQ = 2048, DM = 512, FF = 1792;
constexpr int NSLOT = 6;
constexpr uint32_t OFF_X = 0, OFF_RING = 131072, OFF_MISC = 229376;
constexpr uint32_t OFF_XFULL = OFF_MISC, OFF_FULL = OFF_XFULL + 64, OFF_RBAR = OFF_FULL + 48, OFF_EMPTY = OFF_RBAR + 16, OFF_KBAR = OFF_EMPTY + 48,
                   OFF_GBAR = OFF_KBAR + 16, OFF_LBAR = OFF_GBAR + 8, OFF_CBAR = OFF_LBAR + 8, OFF_EPOCH = OFF_CBAR + 8;
constexpr uint32_t OFF_LC = OFF_MISC + 256;
constexpr uint32_t OFF_GS = OFF_LC;
constexpr uint32_t OFF_DB = OFF_LC + 512;
constexpr uint32_t OFF_CARRY = OFF_LC + 1024;
constexpr uint32_t OFF_DBG = OFF_CARRY + 1024;
constexpr uint32_t SMEM_BYTES = OFF_DBG + 768;
static_assert(SMEM_BYTES <= 232448, "smem");

struct Maps { CUtensorMap x, bre, bim, w1b, w1a, w2, cre, cim; };

__device__ uint4 g_part[16 * 8 * 3 * 1024];
__device__ float2 g_end[8 * 16 * 64];
__device__ unsigned g_gate[SEQ];
__device__ unsigned g_epoch[128];
#define TG(role) do {} while (0)
#define TS2(role, i) do {} while (0)
#define TS(role, i) do {} while (0)
#define TDUMP() do {} while (0)
#define TR(i) do {} while (0)
#define TRD() do {} while (0)

__device__ __forceinline__ void mbar_init(uint32_t bar, uint32_t cnt) { asm volatile("mbarrier.init.shared::cta.b64 [%0], %1;" ::"r"(bar), "r"(cnt)); }
__device__ __forceinline__ void mbar_expect_tx(uint32_t bar, uint32_t bytes) { asm volatile("mbarrier.arrive.expect_tx.shared::cta.b64 _, [%0], %1;" ::"r"(bar), "r"(bytes) : "memory"); }
__device__ __forceinline__ void mbar_arrive(uint32_t bar) { asm volatile("mbarrier.arrive.shared::cta.b64 _, [%0];" ::"r"(bar) : "memory"); }
__device__ __forceinline__ void mbar_arrive_cl(uint32_t cbar) { asm volatile("mbarrier.arrive.shared::cluster.b64 _, [%0];" ::"r"(cbar) : "memory"); }
__device__ __forceinline__ void mbar_wait(uint32_t bar, uint32_t parity) {
  asm volatile(
      "{\n.reg .pred p;\n.reg .u32 c;\n"
      "mbarrier.try_wait.parity.shared::cta.b64 p, [%0], %1;\n"
      "@p bra.uni LAB_DONE;\n"
      "mov.u32 c, 0;\n"
      "LAB_WAIT:\n"
      "mbarrier.try_wait.parity.shared::cta.b64 p, [%0], %1;\n"
      "@p bra.uni LAB_DONE;\n"
      "add.u32 c, c, 1;\nsetp.lt.u32 p, c, 200000;\n@p bra.uni LAB_WAIT;\n"
      "LAB_DONE:\n}" ::"r"(bar), "r"(parity) : "memory");
}
__device__ __forceinline__ void tma2d(uint32_t dst, const CUtensorMap* m, int c0, int c1, uint32_t bar) {
  asm volatile("cp.async.bulk.tensor.2d.shared::cluster.global.mbarrier::complete_tx::bytes [%0], [%1, {%3,%4}], [%2];"
               ::"r"(dst), "l"(m), "r"(bar), "r"(c0), "r"(c1) : "memory");
}
__device__ __forceinline__ void tma3d(uint32_t dst, const CUtensorMap* m, int c0, int c1, int c2, uint32_t bar) {
  asm volatile("cp.async.bulk.tensor.3d.shared::cluster.global.mbarrier::complete_tx::bytes [%0], [%1, {%3,%4,%5}], [%2];"
               ::"r"(dst), "l"(m), "r"(bar), "r"(c0), "r"(c1), "r"(c2) : "memory");
}
__device__ __forceinline__ void tma5d_mc(uint32_t dst, const CUtensorMap* m, int c0, int c4, uint32_t bar) {
  asm volatile("cp.async.bulk.tensor.5d.shared::cluster.global.mbarrier::complete_tx::bytes.multicast::cluster [%0], [%1, {%3,%5,%5,%5,%4}], [%2], %6;"
               ::"r"(dst), "l"(m), "r"(bar), "r"(c0), "r"(c4), "r"(0), "h"((uint16_t)3) : "memory");
}
__device__ __forceinline__ void l2_prefetch(const void* p, uint32_t bytes) { asm volatile("cp.async.bulk.prefetch.L2.global [%0], %1;" ::"l"(p), "r"(bytes) : "memory"); }
__device__ __forceinline__ bool elect_one() {
  uint32_t pred;
  asm volatile("{.reg .pred P; elect.sync _|P, 0xffffffff; selp.u32 %0, 1, 0, P;}" : "=r"(pred));
  return pred != 0;
}
__device__ __forceinline__ void wg_fence() { asm volatile("wgmma.fence.sync.aligned;" ::: "memory"); }
__device__ __forceinline__ void wg_commit() { asm volatile("wgmma.commit_group.sync.aligned;" ::: "memory"); }
template <int N> __device__ __forceinline__ void wg_wait() { asm volatile("wgmma.wait_group.sync.aligned %0;" ::"n"(N) : "memory"); }
__device__ __forceinline__ void pin(float& a) { asm volatile("" : "+f"(a)::"memory"); }
__device__ __forceinline__ void pin(uint32_t& a) { asm volatile("" : "+r"(a)::"memory"); }
template <int N> __device__ __forceinline__ void reg_fence(float (&d)[N]) {
#pragma unroll
  for (int i = 0; i < N; i++) pin(d[i]);
}
__device__ __forceinline__ void bar_sync(int id, int n) { asm volatile("bar.sync %0, %1;" ::"r"(id), "r"(n) : "memory"); }
__device__ __forceinline__ void bar_arrive(int id, int n) { asm volatile("bar.arrive %0, %1;" ::"r"(id), "r"(n) : "memory"); }
constexpr uint32_t DH128 = (1024 >> 4) | (1u << 30), DH64 = (512 >> 4) | (2u << 30);
__host__ __device__ constexpr uint32_t lbo(uint32_t bytes) { return (bytes >> 4) << 20; }
__device__ __forceinline__ uint32_t pack_bf16(float lo, float hi) { uint32_t r; asm("cvt.rn.bf16x2.f32 %0, %1, %2;" : "=r"(r) : "f"(hi), "f"(lo)); return r; }
__device__ __forceinline__ float bf_lo(uint32_t v) { return __uint_as_float(v << 16); }
__device__ __forceinline__ float bf_hi(uint32_t v) { return __uint_as_float(v & 0xffff0000u); }
__device__ __forceinline__ float bf_ld(const __nv_bfloat16* p) { return __bfloat162float(__ldg(p)); }
__device__ __forceinline__ uint32_t late16(uint32_t bar) {
  uint32_t r;
  asm volatile("{.reg .pred p; mbarrier.test_wait.parity.shared::cta.b64 p, [%1], 0; selp.u32 %0, 16, 0, p;}" : "=r"(r) : "r"(bar) : "memory");
  return r;
}
__device__ __forceinline__ float2 lds_f2(uint32_t a) { float2 v; asm volatile("ld.shared.v2.f32 {%0,%1}, [%2];" : "=f"(v.x), "=f"(v.y) : "r"(a)); return v; }
__device__ __forceinline__ uint32_t lds_h(uint32_t a) { uint32_t v; asm volatile("ld.shared.u16 %0, [%1];" : "=r"(v) : "r"(a)); return v; }
__device__ __forceinline__ uint32_t lds_u(uint32_t a) { uint32_t v; asm volatile("ld.shared.u32 %0, [%1];" : "=r"(v) : "r"(a)); return v; }
__device__ __forceinline__ uint4 lds_u4(uint32_t a) { uint4 v; asm volatile("ld.shared.v4.u32 {%0,%1,%2,%3}, [%4];" : "=r"(v.x), "=r"(v.y), "=r"(v.z), "=r"(v.w) : "r"(a)); return v; }
__device__ __forceinline__ void st_b128(uint4* p, uint32_t a, uint32_t b, uint32_t c, uint32_t d) {
  asm volatile("st.relaxed.gpu.global.v4.b32 [%0], {%1,%2,%3,%4};" ::"l"(p), "r"(a), "r"(b), "r"(c), "r"(d) : "memory");
}
__device__ __forceinline__ void ld_b128(const uint4* p, uint32_t& a, uint32_t& b, uint32_t& c, uint32_t& d) {
  asm volatile("{.reg .b64 l, h; .reg .b128 v; ld.relaxed.gpu.global.b128 v, [%4]; mov.b128 {l,h}, v; mov.b64 {%0,%1}, l; mov.b64 {%2,%3}, h;}"
               : "=r"(a), "=r"(b), "=r"(c), "=r"(d) : "l"(p) : "memory");
}
__device__ __forceinline__ float tanh_fast(float x) { float y; asm("tanh.approx.f32 %0, %1;" : "=f"(y) : "f"(x)); return y; }
__device__ __forceinline__ float gelu2(float v) {
  float p = fmaf(v * v, 0.0356774081363f, 0.7978845608029f);
  return fmaf(v, tanh_fast(v * p), v);
}
__device__ __forceinline__ uint32_t bf2_mul(uint32_t a, uint32_t b) { uint32_t r; asm("mul.rn.bf16x2 %0, %1, %2;" : "=r"(r) : "r"(a), "r"(b)); return r; }
__device__ __forceinline__ uint32_t bf2_add(uint32_t a, uint32_t b) { uint32_t r; asm("add.rn.bf16x2 %0, %1, %2;" : "=r"(r) : "r"(a), "r"(b)); return r; }
__device__ __forceinline__ uint32_t bf2_fma(uint32_t a, uint32_t b, uint32_t c) { uint32_t r; asm("fma.rn.bf16x2 %0, %1, %2, %3;" : "=r"(r) : "r"(a), "r"(b), "r"(c)); return r; }
__device__ __forceinline__ uint32_t gelu2_pair(float a, float b) {
  return pack_bf16(gelu2(a), gelu2(b));
}
struct cplx { float re, im; };
__device__ __forceinline__ cplx cmul(cplx a, cplx b) { return {fmaf(a.re, b.re, -a.im * b.im), fmaf(a.re, b.im, a.im * b.re)}; }
__device__ __forceinline__ cplx cfma(cplx a, cplx b, cplx c) {
  return {fmaf(a.re, b.re, fmaf(-a.im, b.im, c.re)), fmaf(a.re, b.im, fmaf(a.im, b.re, c.im))};
}
__device__ __forceinline__ cplx make_lam(float lre, float lim, float ldt) {
  float dt = __bfloat162float(__float2bfloat16_rn(expf(ldt)));
  float mag = expf(dt * lre), sn, cs;
  sincospif(dt * lim * 0.31830988618379067f, &sn, &cs);
  return {mag * cs, mag * sn};
}

template<int TA,int TB,uint32_t AH,uint32_t BH> __device__ __forceinline__ void wgmma_n64_ss(float (&d)[32], uint32_t al, uint32_t ao, uint32_t bl, uint32_t bo, int scale_d){
  asm volatile("{.reg .pred p; .reg .b32 t, v; .reg .b64 da, db; setp.ne.b32 p, %36, 0; add.u32 t, %32, %33; mov.b64 da, {t, %39}; add.u32 v, %34, %35; mov.b64 db, {v, %40};\n"
   "wgmma.mma_async.sync.aligned.m64n64k16.f32.bf16.bf16 {%0,%1,%2,%3,%4,%5,%6,%7,%8,%9,%10,%11,%12,%13,%14,%15,%16,%17,%18,%19,%20,%21,%22,%23,%24,%25,%26,%27,%28,%29,%30,%31}, da, db, p, 1, 1, %37, %38;}"
   : "+f"(d[0]),"+f"(d[1]),"+f"(d[2]),"+f"(d[3]),"+f"(d[4]),"+f"(d[5]),"+f"(d[6]),"+f"(d[7]),"+f"(d[8]),"+f"(d[9]),"+f"(d[10]),"+f"(d[11]),"+f"(d[12]),"+f"(d[13]),"+f"(d[14]),"+f"(d[15]),"+f"(d[16]),"+f"(d[17]),"+f"(d[18]),"+f"(d[19]),"+f"(d[20]),"+f"(d[21]),"+f"(d[22]),"+f"(d[23]),"+f"(d[24]),"+f"(d[25]),"+f"(d[26]),"+f"(d[27]),"+f"(d[28]),"+f"(d[29]),"+f"(d[30]),"+f"(d[31])
   : "r"(al),"r"(ao >> 4),"r"(bl),"r"(bo >> 4),"r"(scale_d),"n"(TA),"n"(TB),"n"(AH),"n"(BH));
}
template<int TB,uint32_t BH> __device__ __forceinline__ void wgmma_n64_rs(float (&d)[32], uint32_t a0,uint32_t a1,uint32_t a2,uint32_t a3, uint32_t bl, uint32_t bo, int scale_d){
  asm volatile("{.reg .pred p; .reg .b32 t; .reg .b64 db; setp.ne.b32 p, %38, 0; add.u32 t, %36, %37; mov.b64 db, {t, %40};\n"
   "wgmma.mma_async.sync.aligned.m64n64k16.f32.bf16.bf16 {%0,%1,%2,%3,%4,%5,%6,%7,%8,%9,%10,%11,%12,%13,%14,%15,%16,%17,%18,%19,%20,%21,%22,%23,%24,%25,%26,%27,%28,%29,%30,%31}, {%32,%33,%34,%35}, db, p, 1, 1, %39;}"
   : "+f"(d[0]),"+f"(d[1]),"+f"(d[2]),"+f"(d[3]),"+f"(d[4]),"+f"(d[5]),"+f"(d[6]),"+f"(d[7]),"+f"(d[8]),"+f"(d[9]),"+f"(d[10]),"+f"(d[11]),"+f"(d[12]),"+f"(d[13]),"+f"(d[14]),"+f"(d[15]),"+f"(d[16]),"+f"(d[17]),"+f"(d[18]),"+f"(d[19]),"+f"(d[20]),"+f"(d[21]),"+f"(d[22]),"+f"(d[23]),"+f"(d[24]),"+f"(d[25]),"+f"(d[26]),"+f"(d[27]),"+f"(d[28]),"+f"(d[29]),"+f"(d[30]),"+f"(d[31])
   : "r"(a0),"r"(a1),"r"(a2),"r"(a3),"r"(bl),"r"(bo >> 4),"r"(scale_d),"n"(TB),"n"(BH));
}
template<int TA,int TB,uint32_t AH,uint32_t BH> __device__ __forceinline__ void wgmma_n96_ss(float (&d)[48], uint32_t al, uint32_t ao, uint32_t bl, uint32_t bo, int scale_d){
  asm volatile("{.reg .pred p; .reg .b32 t, v; .reg .b64 da, db; setp.ne.b32 p, %52, 0; add.u32 t, %48, %49; mov.b64 da, {t, %55}; add.u32 v, %50, %51; mov.b64 db, {v, %56};\n"
   "wgmma.mma_async.sync.aligned.m64n96k16.f32.bf16.bf16 {%0,%1,%2,%3,%4,%5,%6,%7,%8,%9,%10,%11,%12,%13,%14,%15,%16,%17,%18,%19,%20,%21,%22,%23,%24,%25,%26,%27,%28,%29,%30,%31,%32,%33,%34,%35,%36,%37,%38,%39,%40,%41,%42,%43,%44,%45,%46,%47}, da, db, p, 1, 1, %53, %54;}"
   : "+f"(d[0]),"+f"(d[1]),"+f"(d[2]),"+f"(d[3]),"+f"(d[4]),"+f"(d[5]),"+f"(d[6]),"+f"(d[7]),"+f"(d[8]),"+f"(d[9]),"+f"(d[10]),"+f"(d[11]),"+f"(d[12]),"+f"(d[13]),"+f"(d[14]),"+f"(d[15]),"+f"(d[16]),"+f"(d[17]),"+f"(d[18]),"+f"(d[19]),"+f"(d[20]),"+f"(d[21]),"+f"(d[22]),"+f"(d[23]),"+f"(d[24]),"+f"(d[25]),"+f"(d[26]),"+f"(d[27]),"+f"(d[28]),"+f"(d[29]),"+f"(d[30]),"+f"(d[31]),"+f"(d[32]),"+f"(d[33]),"+f"(d[34]),"+f"(d[35]),"+f"(d[36]),"+f"(d[37]),"+f"(d[38]),"+f"(d[39]),"+f"(d[40]),"+f"(d[41]),"+f"(d[42]),"+f"(d[43]),"+f"(d[44]),"+f"(d[45]),"+f"(d[46]),"+f"(d[47])
   : "r"(al),"r"(ao >> 4),"r"(bl),"r"(bo >> 4),"r"(scale_d),"n"(TA),"n"(TB),"n"(AH),"n"(BH));
}
template<int TA,int TB,uint32_t AH,uint32_t BH> __device__ __forceinline__ void wgmma_n128_ss(float (&d)[64], uint32_t al, uint32_t ao, uint32_t bl, uint32_t bo, int scale_d){
  asm volatile("{.reg .pred p; .reg .b32 t, v; .reg .b64 da, db; setp.ne.b32 p, %68, 0; add.u32 t, %64, %65; mov.b64 da, {t, %71}; add.u32 v, %66, %67; mov.b64 db, {v, %72};\n"
   "wgmma.mma_async.sync.aligned.m64n128k16.f32.bf16.bf16 {%0,%1,%2,%3,%4,%5,%6,%7,%8,%9,%10,%11,%12,%13,%14,%15,%16,%17,%18,%19,%20,%21,%22,%23,%24,%25,%26,%27,%28,%29,%30,%31,%32,%33,%34,%35,%36,%37,%38,%39,%40,%41,%42,%43,%44,%45,%46,%47,%48,%49,%50,%51,%52,%53,%54,%55,%56,%57,%58,%59,%60,%61,%62,%63}, da, db, p, 1, 1, %69, %70;}"
   : "+f"(d[0]),"+f"(d[1]),"+f"(d[2]),"+f"(d[3]),"+f"(d[4]),"+f"(d[5]),"+f"(d[6]),"+f"(d[7]),"+f"(d[8]),"+f"(d[9]),"+f"(d[10]),"+f"(d[11]),"+f"(d[12]),"+f"(d[13]),"+f"(d[14]),"+f"(d[15]),"+f"(d[16]),"+f"(d[17]),"+f"(d[18]),"+f"(d[19]),"+f"(d[20]),"+f"(d[21]),"+f"(d[22]),"+f"(d[23]),"+f"(d[24]),"+f"(d[25]),"+f"(d[26]),"+f"(d[27]),"+f"(d[28]),"+f"(d[29]),"+f"(d[30]),"+f"(d[31]),"+f"(d[32]),"+f"(d[33]),"+f"(d[34]),"+f"(d[35]),"+f"(d[36]),"+f"(d[37]),"+f"(d[38]),"+f"(d[39]),"+f"(d[40]),"+f"(d[41]),"+f"(d[42]),"+f"(d[43]),"+f"(d[44]),"+f"(d[45]),"+f"(d[46]),"+f"(d[47]),"+f"(d[48]),"+f"(d[49]),"+f"(d[50]),"+f"(d[51]),"+f"(d[52]),"+f"(d[53]),"+f"(d[54]),"+f"(d[55]),"+f"(d[56]),"+f"(d[57]),"+f"(d[58]),"+f"(d[59]),"+f"(d[60]),"+f"(d[61]),"+f"(d[62]),"+f"(d[63])
   : "r"(al),"r"(ao >> 4),"r"(bl),"r"(bo >> 4),"r"(scale_d),"n"(TA),"n"(TB),"n"(AH),"n"(BH));
}

__global__ void __cluster_dims__(2, 1, 1) __launch_bounds__(384, 1)
fused_kernel(const __nv_bfloat16* __restrict__ lam_re, const __nv_bfloat16* __restrict__ lam_im, const __nv_bfloat16* __restrict__ log_dt,
             const __nv_bfloat16* __restrict__ dskip, const __nv_bfloat16* __restrict__ b1, const __nv_bfloat16* __restrict__ b2,
             const __nv_bfloat16* __restrict__ gate_w, const __nv_bfloat16* __restrict__ pf_w1, const __nv_bfloat16* __restrict__ pf_w2,
             const __nv_bfloat16* __restrict__ pf_cre, const __nv_bfloat16* __restrict__ pf_cim, float* __restrict__ out,
             const __grid_constant__ Maps maps) {
  extern __shared__ __align__(1024) unsigned char smem_raw[];
  const uint32_t sb = (uint32_t)__cvta_generic_to_shared(smem_raw);
  const int b = blockIdx.x;
  const int rank = b & 1, cl = b >> 1;
  const int sp = (cl & 1) | ((cl >> 2) & 2), m = ((cl >> 1) & 3) | ((cl >> 4) << 2);
  const int s = sp * 2 + rank;
  const int warp = __shfl_sync(0xffffffffu, (int)(threadIdx.x >> 5), 0);
  const int lane = threadIdx.x & 31;
  const int xrot = 6 - 2 * sp;

  if (elect_one()) {
    if (warp == 8) TS(2, 0);
    if (warp < 3) {
      asm volatile("prefetch.tensormap [%0];" ::"l"(&maps.x + warp) : "memory");
      mbar_init(sb + OFF_GBAR + 8 * warp, warp < 2 ? 64 : 96);
    }
    const uint32_t c = warp < 8 ? 1 : warp < 11 ? 8 : 4;
    mbar_init(sb + OFF_XFULL + 16 * warp, c);
    mbar_init(sb + OFF_XFULL + 16 * warp + 8, c);
    asm volatile("fence.mbarrier_init.release.cluster;" ::: "memory");
  }
  __syncwarp();
  asm volatile("barrier.cluster.arrive.relaxed.aligned;" ::: "memory");

  if (warp < 8) {
    const int wg = warp >> 2, w = warp & 3, q = lane & 3, gr = lane >> 2;
    uint32_t bv[28];
#pragma unroll
    for (int j = 0; j < 28; j++) bv[j] = __ldg(reinterpret_cast<const uint32_t*>(b1 + s * 224 + j * 8) + q);
    asm volatile("setmaxnreg.inc.sync.aligned.u32 224;");
    asm volatile("barrier.cluster.wait.aligned;" ::: "memory");
    TS(wg, 0);
    auto release = [&](int slot) { if (lane == 0) mbar_arrive(sb + OFF_EMPTY + 8 * slot); };
    const uint32_t xw = sb + OFF_X + wg * 8192, fullb = sb + OFF_FULL;
    const uint32_t dxw = (xw & 0x3FFFF) >> 4, dring = ((sb + OFF_RING) & 0x3FFFF) >> 4;

    float ure[32], uim[32], aa[48], ab[64];
    cplx lam[2], coef[2], l16[2], l32[2], lq[2], pre[2], e[2];
    uint32_t sh16, mhi;

#pragma unroll
    for (int kb = 0; kb < 8; kb++) {
      const int slot = kb % NSLOT;
      mbar_wait(sb + OFF_XFULL + 8 * kb, 0);
      if (kb == 0) TS(wg, 18);
      mbar_wait(fullb + 8 * slot, (kb / NSLOT) & 1);
      TS2(2, kb);
      if (kb == 0) TS(wg, 1);
      wg_fence();
      const uint32_t dxa = dxw + ((kb + xrot) & 7) * 1024;
#pragma unroll
      for (int kk = 0; kk < 4; kk++) {
        wgmma_n64_ss<0, 0, DH128, DH128>(ure, dring, slot * 16384 + kk * 32, dxa, kk * 32, (kb | kk) != 0);
        wgmma_n64_ss<0, 0, DH128, DH128>(uim, dring, slot * 16384 + 8192 + kk * 32, dxa, kk * 32, (kb | kk) != 0);
      }
      wg_commit();
      if (kb > 0) { wg_wait<1>(); release((kb - 1) % NSLOT); }
      if (kb == 1) { sh16 = late16(sb + OFF_XFULL); mhi = 0xffffffffu << sh16; }
      if (kb == 1 || (kb >= 3 && kb < 6)) {
#pragma unroll
        for (int j = 0; j < 28; j++) if (j / 7 == (kb == 1 ? 0 : kb - 2)) {
          pin(bv[j]);
          float* d = j < 12 ? aa + 4 * j : ab + 4 * (j - 12);
          d[0] = d[2] = __uint_as_float(bv[j] << sh16); d[1] = d[3] = __uint_as_float(bv[j] & mhi);
          pin(d[0]); pin(d[1]); pin(d[2]); pin(d[3]);
        }
      }
      if (kb == 5) {
        mbar_wait(sb + OFF_LBAR, 0);
#pragma unroll
        for (int h = 0; h < 2; h++) {
          const uint4 v = lds_u4(sb + OFF_LC + (w * 16 + gr + 8 * h) * 16);
          lam[h] = cplx{__uint_as_float(v.x), __uint_as_float(v.y)};
          coef[h] = cplx{__uint_as_float(v.z), __uint_as_float(v.w)};
        }
      }
      if (kb == 6) {
#pragma unroll
        for (int h = 0; h < 2; h++) {
          pin(lam[h].re); pin(lam[h].im);
          cplx t = cmul(lam[h], lam[h]); t = cmul(t, t); t = cmul(t, t);
          l16[h] = cmul(t, t);
          pin(l16[h].re); pin(l16[h].im);
        }
      }
      if (kb == 7) {
#pragma unroll
        for (int h = 0; h < 2; h++) {
          pin(l16[h].re); pin(l16[h].im);
          l32[h] = cmul(l16[h], l16[h]);
          const cplx a = (q & 1) ? l16[h] : cplx{1.f, 0.f}, c = (q & 2) ? l32[h] : cplx{1.f, 0.f};
          lq[h] = cmul(cmul(a, c), coef[h]);
          pin(lq[h].re); pin(lq[h].im);
        }
      }
    }
    TS(wg, 2);
    auto scale_u = [&](int i0, int i1) {
#pragma unroll
      for (int i = 0; i < 32; i++) if (i >= i0 && i < i1) {
        pin(ure[i]); pin(uim[i]);
        const cplx v = cmul(coef[(i >> 1) & 1], cplx{ure[i], uim[i]});
        ure[i] = v.re; uim[i] = v.im;
        pin(ure[i]); pin(uim[i]);
      }
    };
#pragma unroll
    for (int kb = 0; kb < 8; kb++) {
      const int u = 8 + kb, slot = u % NSLOT;
      mbar_wait(fullb + 8 * slot, (u / NSLOT) & 1);
      wg_fence();
      const uint32_t dxa = dxw + ((kb + xrot) & 7) * 1024;
#pragma unroll
      for (int kk = 0; kk < 4; kk++)
        wgmma_n96_ss<0, 1, DH128, DH64>(aa, dxa, kk * 32, dring, slot * 16384 + kk * 1024 + lbo(4096), 1);
      wg_commit();
      wg_wait<1>();
      release((u - 1) % NSLOT);
      if (kb == 0) {
        reg_fence(ure); reg_fence(uim);
#pragma unroll
        for (int h = 0; h < 2; h++) e[h] = cplx{ure[2 * h], uim[2 * h]};
      }
      if (kb == 0 || kb == 2 || kb == 3) {
        const int ch = kb ? kb - 1 : 0;
#pragma unroll
        for (int t = 1 + 5 * ch; t < 6 + 5 * ch; t++)
#pragma unroll
          for (int h = 0; h < 2; h++) { const int i = 4 * (t >> 1) + 2 * h + (t & 1); e[h] = cfma(lam[h], e[h], cplx{ure[i], uim[i]}); }
#pragma unroll
        for (int h = 0; h < 2; h++) { pin(e[h].re); pin(e[h].im); }
      } else if (kb == 4) {
#pragma unroll
        for (int h = 0; h < 2; h++) {
          cplx y = {__shfl_up_sync(0xffffffffu, e[h].re, 1, 4), __shfl_up_sync(0xffffffffu, e[h].im, 1, 4)};
          if (q >= 1) e[h] = cfma(l16[h], y, e[h]);
          y = cplx{__shfl_up_sync(0xffffffffu, e[h].re, 2, 4), __shfl_up_sync(0xffffffffu, e[h].im, 2, 4)};
          if (q >= 2) e[h] = cfma(l32[h], y, e[h]);
        }
        if (q == 3) {
#pragma unroll
          for (int h = 0; h < 2; h++)
            asm volatile("st.shared.v2.f32 [%0], {%1,%2};" ::"r"(sb + OFF_CARRY + wg * 512 + (w * 16 + gr + 8 * h) * 8), "f"(e[h].re), "f"(e[h].im) : "memory");
          mbar_arrive(sb + OFF_GBAR);
        }
#pragma unroll
        for (int h = 0; h < 2; h++) {
          const cplx y = {__shfl_up_sync(0xffffffffu, e[h].re, 1, 4), __shfl_up_sync(0xffffffffu, e[h].im, 1, 4)};
          pre[h] = (q >= 1) ? cmul(coef[h], y) : cplx{0.f, 0.f};
          pin(pre[h].re); pin(pre[h].im);
        }
        TS(wg, 3);
      } else if (kb > 4) {
        scale_u(kb == 5 ? 0 : kb == 6 ? 4 : 12, kb == 5 ? 4 : kb == 6 ? 12 : 20);
      }
    }
    TS(wg, 4);
    uint32_t H[56], hf[32];
    cplx hst[2];
    const uint32_t hst_addr = xw + (w * 16 + (lane & 15)) * 128 + (((lane >> 4) ^ (lane & 7)) << 4);
    uint32_t peer;
    asm volatile("mapa.shared::cluster.u32 %0, %1, %2;" : "=r"(peer) : "r"(sb), "r"(rank ^ 1));
    auto credit = [&]() { if (lane == 0) mbar_arrive_cl(peer + OFF_KBAR + wg * 8); };
#pragma unroll
    for (int kb = 0; kb < 8; kb++) {
      const int u = 16 + kb, slot = u % NSLOT;
      mbar_wait(fullb + 8 * slot, (u / NSLOT) & 1);
      wg_fence();
#pragma unroll
      for (int kk = 0; kk < 4; kk++)
        wgmma_n128_ss<0, 1, DH128, DH128>(ab, dxw, kb * 16384 + kk * 32, dring, slot * 16384 + kk * 2048 + lbo(8192), 1);
      wg_commit();
      wg_wait<1>();
      release((u - 1) % NSLOT);
      if (kb == 6) credit();
      if (kb == 0) scale_u(20, 32);
      if (kb < 5 && kb != 1) {
        const int ch = kb ? kb - 1 : 0;
#pragma unroll
        for (int i = ch * 6; i < ch * 6 + 6; i++) {
          pin(aa[2 * i]); pin(aa[2 * i + 1]);
          H[i] = gelu2_pair(aa[2 * i], aa[2 * i + 1]);
          pin(H[i]);
        }
      }
      if (kb >= 4) {
        if (kb == 4) {
          TS(wg, 5);
          mbar_wait(sb + OFF_CBAR, 0);
          TS(wg, 6);
#pragma unroll
          for (int h = 0; h < 2; h++) {
            const float2 c = lds_f2(sb + OFF_CARRY + wg * 512 + (w * 16 + gr + 8 * h) * 8);
            hst[h] = cfma(lq[h], cplx{c.x, c.y}, pre[h]);
          }
        }
        const int j0 = (kb - 4) * 2;
        uint32_t rr[4], ri[4];
#pragma unroll
        for (int jj = 0; jj < 2; jj++) {
          const int j = j0 + jj;
          const uint32_t g2 = lds_u(sb + OFF_GS + (wg * 64 + j * 8 + q * 2) * 2);
#pragma unroll
          for (int h = 0; h < 2; h++) {
            const int i = 4 * j + 2 * h;
            const cplx h0 = cfma(lam[h], hst[h], cplx{ure[i], uim[i]});
            hst[h] = cfma(lam[h], h0, cplx{ure[i + 1], uim[i + 1]});
            rr[jj * 2 + h] = bf2_mul(pack_bf16(h0.re, hst[h].re), g2);
            ri[jj * 2 + h] = bf2_mul(pack_bf16(h0.im, hst[h].im), g2 ^ 0x80008000u);
          }
        }
        const uint32_t a = hst_addr ^ (j0 << 4);
        asm volatile("stmatrix.sync.aligned.m8n8.x4.shared.b16 [%0], {%1,%2,%3,%4};" ::"r"(a), "r"(rr[0]), "r"(rr[1]), "r"(rr[2]), "r"(rr[3]) : "memory");
        asm volatile("stmatrix.sync.aligned.m8n8.x4.shared.b16 [%0], {%1,%2,%3,%4};" ::"r"(a + 16384), "r"(ri[0]), "r"(ri[1]), "r"(ri[2]), "r"(ri[3]) : "memory");
      }
    }
    TS(wg, 7);

    uint4* const psend = g_part + (size_t)(m * 8 + rank) * 3072 + warp * 128 + lane;
    const uint4* const precv = g_part + (size_t)(m * 8 + s) * 3072 + warp * 128 + lane;
    const uint32_t pbuf = OFF_X + 5 * 16384 + warp * 2048 + lane * 16;
    const uint32_t dx0 = ((sb + OFF_X) & 0x3FFFF) >> 4;
    float o[32], rho[2];
    uint32_t tr[8];
    uint32_t r0[16], pt[16], sum[16], tag;
    auto recv_issue = [&](uint32_t (&r)[16], int k) {
#pragma unroll
      for (int i = 0; i < 4; i++) ld_b128(precv + k * 1024 + i * 32, r[4 * i], r[4 * i + 1], r[4 * i + 2], r[4 * i + 3]);
    };
    auto stale = [&](uint32_t (&r)[16]) {
      uint32_t t0, t1, r_;
      asm("lop3.b32 %0, %1, %2, %3, 0x7e;" : "=r"(t0) : "r"(r[0]), "r"(r[4]), "r"(tag));
      asm("lop3.b32 %0, %1, %2, %3, 0x7e;" : "=r"(t1) : "r"(r[8]), "r"(r[12]), "r"(tag));
      asm volatile("{.reg .pred p; .reg .b32 t; lop3.b32 t, %1, %2, 1, 0xa8; setp.ne.u32 p, t, 0; vote.sync.any.pred p, p, 0xffffffff; selp.u32 %0, 1, 0, p;}" : "=r"(r_) : "r"(t0), "r"(t1));
      return r_ != 0;
    };
    auto recv_check = [&](uint32_t (&r)[16], int k) {
      if (__builtin_expect(stale(r), 0)) {
        int tries = 0;
#pragma unroll 1
        do { recv_issue(r, k); } while (stale(r) && ++tries < 200000);
      }
    };
    auto gelu_b = [&](int i0, int i1) {
#pragma unroll
      for (int i = i0; i < i1; i++) {
        pin(ab[2 * i]); pin(ab[2 * i + 1]);
        H[24 + i] = gelu2_pair(ab[2 * i], ab[2 * i + 1]);
        pin(H[24 + i]);
      }
    };
    auto mma = [&](float (&o)[32], uint32_t wo, int k0, int k1, int acc) {
      wg_fence();
#pragma unroll
      for (int k = k0; k < k1; k++) {
        if (k >= 6 && k < 14) {
          const int kk = k - 6;
          wgmma_n64_rs<0, DH128>(o, hf[4 * kk], hf[4 * kk + 1], hf[4 * kk + 2], hf[4 * kk + 3], dx0, wo + 16384 + (kk >> 2) * 8192 + (kk & 3) * 32, 1);
        } else {
          const int kk = k < 6 ? k : k - 8;
          wgmma_n64_rs<1, DH128>(o, H[4 * kk], H[4 * kk + 1], H[4 * kk + 2], H[4 * kk + 3], dx0, wo + (kk / 7) * 32768 + (kk % 7) * 2048, k != 0 || acc);
        }
      }
      wg_commit();
    };
#pragma unroll
    for (int p = 0; p < 8; p++) {
      const uint32_t wo = (p % 3) == 1 ? 2 * 16384 : OFF_RING + (p % 3) * 24576;
      if (p == 0) {
        mbar_wait(fullb, 0);
        mma(o, wo, 0, 3, 0);
        bar_sync(1 + wg, 128);
        {
          const uint32_t ha = xw + ((lane >> 4) * 8 + (lane & 7)) * 128 + (((2 * w + ((lane >> 3) & 1)) ^ (lane & 7)) << 4);
#pragma unroll
          for (int kk = 0; kk < 8; kk++)
            asm volatile("ldmatrix.sync.aligned.m8n8.x4.trans.shared.b16 {%0,%1,%2,%3}, [%4];" : "=r"(hf[4 * kk]), "=r"(hf[4 * kk + 1]), "=r"(hf[4 * kk + 2]), "=r"(hf[4 * kk + 3])
                         : "r"(ha + (kk >> 2) * 16384 + (kk & 3) * 2048) : "memory");
        }
        wg_wait<1>(); release(5);
        gelu_b(0, 4);
        mma(o, wo, 3, 6, 0);
        gelu_b(4, 10);
        mbar_wait(fullb + 8, 0);
        mma(o, wo, 6, 10, 0);
        gelu_b(10, 16);
        mma(o, wo, 10, 15, 0);
        gelu_b(16, 24);
        mbar_wait(fullb + 16, 0);
        mma(o, wo, 15, 18, 0);
        gelu_b(24, 32);
        if (wg == 1) bar_sync(4, 256);
        mma(o, wo, 18, 22, 0);
      } else {
        TR(0);
        if (!EW || (p & 1)) mbar_wait(sb + OFF_XFULL + 8 * p, 1);
        TR(1);
        bar_sync(3 + wg, 256);
        if (p < 7) mma(o, wo, 0, 22, 0);
        else {
          mma(o, wo, 0, K2G, 1);
          if (K2E == 2) recv_issue(r0, 2);
          mma(o, wo, K2G, 22, 1);
        }
      }
      if (p < 7 || wg == 0) bar_arrive(4 - wg, 256);
      TR(2);
      if (p != TP) TS(wg, 8 + p);
      if ((p & 1) == 0) {
        if ((threadIdx.x & 127) == 0) mbar_expect_tx(sb + OFF_RBAR + wg * 8, 8192);
        if (p == 6) {
          tag = lds_u(sb + OFF_EPOCH);
          recv_check(sum, 0); recv_check(r0, 1);
#pragma unroll
          for (int i = 0; i < 16; i++) sum[i] = bf2_add(sum[i], r0[i]);
        }
        TR(3);
        mbar_wait(sb + OFF_KBAR + wg * 8, (p >> 1) & 1);
        TR(4);
        if (p == 6) mbar_wait(sb + OFF_LBAR, 1);
        if (K2E == 1 && p == 6) recv_issue(r0, 2);
      } else {
        if (p == 1 || p == 7) tag = lds_u(sb + OFF_EPOCH);
        if (EW && p < 7) mbar_wait(sb + OFF_XFULL + 8 * (p + 1), 1);
        TR(3);
        mbar_wait(sb + OFF_RBAR + wg * 8, (p >> 1) & 1);
        TR(4);
#pragma unroll
        for (int i = 0; i < 4; i++) { const uint4 v = lds_u4(sb + pbuf + i * 512); pt[4 * i] = v.x; pt[4 * i + 1] = v.y; pt[4 * i + 2] = v.z; pt[4 * i + 3] = v.w; }
        if (p == 7) {
          recv_check(r0, 2);
#pragma unroll
          for (int i = 0; i < 16; i++) sum[i] = bf2_add(sum[i], bf2_add(r0[i], pt[i]));
        }
      }
      TR(5);
      wg_wait<0>();
      TR(6);
      if (p < 5) release(p);
      reg_fence(o);
      if ((p & 1) == 0) {
        if (!K2E && p == 6) recv_issue(r0, 2);
#pragma unroll
        for (int i = 0; i < 4; i++)
          asm volatile("st.async.shared::cluster.mbarrier::complete_tx::bytes.v4.b32 [%0], {%1,%2,%3,%4}, [%5];" ::"r"(peer + pbuf + i * 512),
                       "r"(pack_bf16(o[8 * i], o[8 * i + 1])), "r"(pack_bf16(o[8 * i + 2], o[8 * i + 3])), "r"(pack_bf16(o[8 * i + 4], o[8 * i + 5])),
                       "r"(pack_bf16(o[8 * i + 6], o[8 * i + 7])), "r"(peer + OFF_RBAR + wg * 8) : "memory");
        if (p == 2) {
#pragma unroll
          for (int h = 0; h < 2; h++) { rho[h] = __fdividef(2.f, 4.f + bf_lo(lds_h(sb + OFF_GS + (wg * 64 + w * 16 + gr + 8 * h) * 2))); pin(rho[h]); }
        }
        if (p == 4) {
          recv_issue(sum, 0);
          if (K1E) recv_issue(r0, 1);
        }
        if (p == 6) {
#pragma unroll
          for (int j = 0; j < 8; j++) {
            const uint4 v = lds_u4(sb + OFF_X + j * 4096 + threadIdx.x * 16);
            o[4 * j] = __uint_as_float(v.x); o[4 * j + 1] = __uint_as_float(v.y); o[4 * j + 2] = __uint_as_float(v.z); o[4 * j + 3] = __uint_as_float(v.w);
          }
        }
      } else if (p < 7) {
#pragma unroll
        for (int i = 0; i < 4; i++) {
#pragma unroll
          for (int c = 4 * i; c < 4 * i + 4; c++) pt[c] = bf2_add(pt[c], pack_bf16(o[2 * c], o[2 * c + 1]));
          asm("lop3.b32 %0, %0, 1, %1, 0xb8;" : "+r"(pt[4 * i]) : "r"(tag));
          st_b128(psend + (((sp + 1 + (p >> 1)) & 3) * 6 + (p >> 1)) * 1024 + i * 32, pt[4 * i], pt[4 * i + 1], pt[4 * i + 2], pt[4 * i + 3]);
        }
        __syncwarp();
        credit();
        if (!K1E && p == 5) recv_issue(r0, 1);
      }
      TR(7);
    }
    {
      TS(wg, 16);
      const uint32_t tb = sb + OFF_RING + 3 * 16384 + warp * 4096;
      const uint32_t ta = tb + gr * 256 + ((gr & 3) << 5) + q * 8;
      const uint32_t la = tb + (lane >> 3) * 256 + (((lane & 7) << 4) ^ ((lane >> 3) << 5));
      float* op = out + (size_t)(m * 128 + wg * 64 + (lane >> 4) * 16 + w * 4 + ((lane >> 3) & 1)) * DM + s * 64 + (lane & 7) * 4;
#pragma unroll
      for (int qq = 0; qq < 4; qq += QS) {
#pragma unroll
        for (int qt = qq; qt < qq + QS; qt++) {
          const int h = qt & 1, ch = qt >> 1;
#pragma unroll
          for (int j = 0; j < 4; j++) {
            const int i = ch * 8 + j * 2 + h;
            asm volatile("st.shared.v2.f32 [%0], {%1,%2};" ::"r"((ta ^ (j << 5)) + h * 2048 + ch * 128),
                         "f"((o[2 * i] + bf_lo(sum[i])) * rho[h]), "f"((o[2 * i + 1] + bf_hi(sum[i])) * rho[h]) : "memory");
          }
        }
        __syncwarp();
#pragma unroll
        for (int qt = qq; qt < qq + QS; qt++) {
          const int h = qt & 1, ch = qt >> 1;
#pragma unroll
          for (int r = 0; r < 2; r++)
            *reinterpret_cast<uint4*>(op + (r * 32 + h * 2) * DM + ch * 32) = lds_u4(la + (h * 2 + r) * 1024 + ch * 128);
        }
      }
      if (threadIdx.x == 128) g_epoch[b] = tag;
      TS(wg, 17); TG(wg); TRD(); TDUMP();
    }
  } else {
    asm volatile("setmaxnreg.dec.sync.aligned.u32 56;");
    int wsel = warp;
    asm("" : "+r"(wsel));
    if (wsel > 8) {
      if (warp != 11) {
        const int t = threadIdx.x - 288;
        unsigned par;
        asm volatile("ld.relaxed.gpu.global.u32 %0, [%1];" : "=r"(par) : "l"(g_epoch + b) : "memory");
        const float pr = bf_ld(lam_re + s * 64 + t), pi = bf_ld(lam_im + s * 64 + t), pd = bf_ld(log_dt + s * 64 + t);
        asm volatile("barrier.cluster.wait.aligned;" ::: "memory");
        par = (par + 1) & 1;
        cplx l64 = make_lam(pr, pi, pd);
        {
          const float inv = __fdividef(1.f, fmaf(pr, pr, pi * pi));
          const cplx cf = cmul(cplx{l64.re - 1.f, l64.im}, cplx{pr * inv, -pi * inv});
          asm volatile("st.shared.v4.f32 [%0], {%1,%2,%3,%4};" ::"r"(sb + OFF_LC + t * 16), "f"(l64.re), "f"(l64.im), "f"(cf.re), "f"(cf.im) : "memory");
          mbar_arrive(sb + OFF_LBAR);
        }
#pragma unroll
        for (int i = 0; i < 6; i++) l64 = cmul(l64, l64);
        cplx l128 = cmul(l64, l64);
        pin(l128.re); pin(l128.im);
        mbar_wait(sb + OFF_GBAR, 0);
        const float2 e0 = lds_f2(sb + OFF_CARRY + t * 8), e1 = lds_f2(sb + OFF_CARRY + 512 + t * 8);
        float2* eb = g_end + s * 1024 + t;
        {
          const cplx e = cfma(l64, cplx{e0.x, e0.y}, cplx{e1.x, e1.y});
          const unsigned long long v = ((unsigned long long)__float_as_uint(e.im) << 32) | ((__float_as_uint(e.re) & ~1u) | par);
          asm volatile("st.relaxed.gpu.global.b64 [%0], %1;" ::"l"(eb + m * 64), "l"(v) : "memory");
        }
        if (t == 0) TS(3, 1);
        cplx S = {0.f, 0.f};
        {
          unsigned long long v[15];
          uint32_t bad;
          int tries = 0;
          const float2* e15 = eb + (m - 15) * 64;
#pragma unroll 1
          do {
#pragma unroll
            for (int i = 0; i < 15; i++) {
              v[i] = par;
              asm volatile("{.reg .pred p; setp.ge.s32 p, %2, %3; @p ld.relaxed.gpu.global.b64 %0, [%1];}" : "+l"(v[i]) : "l"(e15 + i * 64), "r"(m), "r"(15 - i) : "memory");
            }
            bad = 0;
#pragma unroll
            for (int i = 0; i < 15; i++) bad |= (uint32_t)v[i] ^ par;
          } while ((bad & 1) && ++tries < 200000);
          if (t == 0) TS(3, 2);
#pragma unroll
          for (int i = 0; i < 15; i++) S = cfma(l128, S, cplx{__uint_as_float((uint32_t)v[i] & ~1u), __uint_as_float((uint32_t)(v[i] >> 32))});
        }
        const cplx S1 = cfma(l64, S, cplx{e0.x, e0.y});
        asm volatile("st.shared.v2.f32 [%0], {%1,%2};" ::"r"(sb + OFF_CARRY + t * 8), "f"(S.re), "f"(S.im) : "memory");
        asm volatile("st.shared.v2.f32 [%0], {%1,%2};" ::"r"(sb + OFF_CARRY + 512 + t * 8), "f"(S1.re), "f"(S1.im) : "memory");
        mbar_arrive(sb + OFF_CBAR);
        if (t == 0) TS(3, 3);
        mbar_wait(sb + OFF_CBAR, 0);
        const int gr = lane >> 2, q = lane & 3;
        float2 db[8];
#pragma unroll
        for (int j = 0; j < 8; j++) db[j] = lds_f2(sb + OFF_DB + j * 32 + q * 8);
        mbar_wait(sb + OFF_XFULL + 24, 1);
#pragma unroll 1
        for (int cw = warp - 9; cw < 8; cw += 2) {
          const float r0 = 0.5f * bf_lo(lds_h(sb + OFF_GS + (cw * 16 + gr) * 2)), r1 = 0.5f * bf_lo(lds_h(sb + OFF_GS + (cw * 16 + gr) * 2 + 16));
          const uint32_t xa = sb + OFF_X + (6 + rank) * 16384 + (cw * 16 + (lane & 15)) * 128 + (((lane >> 4) ^ (lane & 7)) << 4);
          uint32_t xv[16];
#pragma unroll
          for (int i = 0; i < 4; i++)
            asm volatile("ldmatrix.sync.aligned.m8n8.x4.shared.b16 {%0,%1,%2,%3}, [%4];" : "=r"(xv[4 * i]), "=r"(xv[4 * i + 1]), "=r"(xv[4 * i + 2]), "=r"(xv[4 * i + 3])
                         : "r"(xa ^ (i << 5)) : "memory");
#pragma unroll
          for (int j = 0; j < 8; j++) {
            const uint32_t x0 = bf2_mul(xv[2 * j], __float_as_uint(db[j].x)), x1 = bf2_mul(xv[2 * j + 1], __float_as_uint(db[j].x));
            pin(db[j].y);
            const float bl = bf_lo(__float_as_uint(db[j].y)), bh = bf_hi(__float_as_uint(db[j].y));
            asm volatile("st.shared.v4.f32 [%0], {%1,%2,%3,%4};" ::"r"(sb + OFF_X + j * 4096 + (cw * 32 + lane) * 16), "f"(fmaf(bf_lo(x0), r0, bl)),
                         "f"(fmaf(bf_hi(x0), r0, bh)), "f"(fmaf(bf_lo(x1), r1, bl)), "f"(fmaf(bf_hi(x1), r1, bh)) : "memory");
          }
        }
        mbar_arrive(sb + OFF_LBAR);
        if (t == 0) TS(3, 5);
      } else {
        if (lane == 0) TG(2);
        const uint4* gwp = reinterpret_cast<const uint4*>(gate_w) + (lane & 7);
        uint4 gw[4];
#pragma unroll
        for (int i = 0; i < 4; i++) gw[i] = __ldg(gwp + i * 8);
        unsigned par;
        asm volatile("ld.relaxed.gpu.global.u32 %0, [%1];" : "=r"(par) : "l"(g_epoch + b) : "memory");
        const uint32_t dk = __ldg(reinterpret_cast<const uint32_t*>(dskip + s * 64) + lane), bb = __ldg(reinterpret_cast<const uint32_t*>(b2 + s * 64) + lane);
        asm volatile("barrier.cluster.wait.aligned;" ::: "memory");
        const int row = s * 16 + (lane >> 3);
        const uint32_t xr0 = sb + OFF_X + row * 128 + (((lane & 7) ^ (row & 7)) << 4), xr1 = (xr0 + 512) ^ 64;
        float z[4] = {0.f, 0.f, 0.f, 0.f};
#pragma unroll
        for (int kb = 0; kb < 8; kb++) {
          const uint32_t wv[4] = {gw[kb & 3].x, gw[kb & 3].y, gw[kb & 3].z, gw[kb & 3].w};
          if (kb < 4) gw[kb] = __ldg(gwp + (kb + 4) * 8);
          mbar_wait(sb + OFF_XFULL + 8 * kb, 0);
          if ((PF & 2) && kb == PFK && elect_one()) {
            l2_prefetch(pf_w1 + b * 7168, 14336);
            l2_prefetch(pf_cre + b * 2048, 4096);
            l2_prefetch(pf_cim + b * 2048, 4096);
            l2_prefetch(pf_w2 + b * 7168, 14336);
          }
          const uint32_t xo = ((kb + xrot) & 7) * 16384;
#pragma unroll
          for (int r = 0; r < 4; r++) {
            const uint4 a = lds_u4(((r & 1) ? xr1 : xr0) + xo + (r >> 1) * 1024);
            const uint32_t p = bf2_fma(a.w, wv[3], bf2_fma(a.z, wv[2], bf2_fma(a.y, wv[1], bf2_mul(a.x, wv[0]))));
            z[r] += bf_lo(p); z[r] += bf_hi(p);
          }
        }
        if (lane == 0) asm volatile("st.shared.u32 [%0], %1;" ::"r"(sb + OFF_EPOCH), "r"(par + 1) : "memory");
        par = (par + 1) & 1;
        {
          float y0 = (lane & 4) ? z[1] : z[0], y1 = (lane & 4) ? z[3] : z[2];
          y0 += __shfl_xor_sync(0xffffffffu, (lane & 4) ? z[0] : z[1], 4);
          y1 += __shfl_xor_sync(0xffffffffu, (lane & 4) ? z[2] : z[3], 4);
          float zz = (lane & 2) ? y1 : y0;
          zz += __shfl_xor_sync(0xffffffffu, (lane & 2) ? y0 : y1, 2);
          zz += __shfl_xor_sync(0xffffffffu, zz, 1);
          const float rho = 4.f * expf(zz > 40.f ? 40.f : zz);
          if ((lane & 1) == 0)
            asm volatile("st.relaxed.gpu.global.u32 [%0], %1;" ::"l"(g_gate + m * 128 + row + (lane & 4) + (lane & 2) * 4), "r"((__float_as_uint(rho) & ~1u) | par) : "memory");
        }
        if (lane == 0) TS(3, 0);
        mbar_wait(sb + OFF_GBAR, 0);
        asm volatile("st.shared.v2.u32 [%0], {%1,%2};" ::"r"(sb + OFF_DB + lane * 8), "r"(dk), "r"(bf2_add(bb, bb)) : "memory");
        uint32_t g0, g1, g2, g3;
        int tries = 0;
#pragma unroll 1
        do {
          asm volatile("ld.relaxed.gpu.global.v4.u32 {%0,%1,%2,%3}, [%4];" : "=r"(g0), "=r"(g1), "=r"(g2), "=r"(g3) : "l"(g_gate + m * 128 + lane * 4) : "memory");
        } while ((((g0 ^ par) | (g1 ^ par) | (g2 ^ par) | (g3 ^ par)) & 1) && ++tries < 200000);
        asm volatile("st.shared.v2.u32 [%0], {%1,%2};" ::"r"(sb + OFF_GS + lane * 8), "r"(pack_bf16(__uint_as_float(g0), __uint_as_float(g1))),
                     "r"(pack_bf16(__uint_as_float(g2), __uint_as_float(g3))) : "memory");
        mbar_arrive(sb + OFF_CBAR);
        if (lane == 0) TS(3, 4);
      }
    } else {
      asm volatile("barrier.cluster.wait.aligned;" ::: "memory");
      if (elect_one()) {
        TS(2, 1);
        const uint32_t t0 = clock();
#pragma unroll 1
        for (int u = 0; u < 8; u++) {
          if (u >= 1) while ((uint32_t)clock() - t0 < D0 + (u - 1) * D1) {}
          mbar_expect_tx(sb + OFF_XFULL + 8 * u, 16384);
          tma5d_mc(sb + OFF_X + ((u + xrot) & 7) * 16384 + rank * 8192, &maps.x, u * 64, 2 * m + rank, sb + OFF_XFULL + 8 * u);
          if (u < 6) {
            mbar_expect_tx(sb + OFF_FULL + 8 * u, 16384);
            tma2d(sb + OFF_RING + u * 16384, &maps.bre, u * 64, s * 64, sb + OFF_FULL + 8 * u);
            tma2d(sb + OFF_RING + u * 16384 + 8192, &maps.bim, u * 64, s * 64, sb + OFF_FULL + 8 * u);
          } else if (PF & 4) {
            asm volatile("cp.async.bulk.prefetch.tensor.2d.L2.global [%0, {%1,%2}];" ::"l"((m & 1) ? &maps.bim : &maps.bre), "r"(u * 64), "r"(s * 64) : "memory");
          }
        }
        TS(2, 5);
        const int piece0 = ((sp + 1) & 3) * 2 + (rank ^ 1);
        int slot = 0; uint32_t ph = 0;
#pragma unroll 1
        for (int u = 6; u < 27; u++) {
          const uint32_t fb = sb + OFF_FULL + 8 * slot, dst = sb + OFF_RING + slot * 16384;
          mbar_wait(sb + OFF_EMPTY + 8 * slot, ph);
          TS2(0, u);
          if (u < 8) {
            mbar_expect_tx(fb, 16384);
            tma2d(dst, &maps.bre, u * 64, s * 64, fb);
            tma2d(dst + 8192, &maps.bim, u * 64, s * 64, fb);
          } else if (u < 16) {
            mbar_expect_tx(fb, 12288);
            tma3d(dst, &maps.w1b, 0, (u - 8) * 64, s * 7, fb);
          } else if (u < 24) {
            mbar_expect_tx(fb, 16384);
            tma2d(dst, &maps.w1a, s * 224 + 96, ((u - xrot) & 7) * 64, fb);
            tma2d(dst + 8192, &maps.w1a, s * 224 + 160, ((u - xrot) & 7) * 64, fb);
          } else if (u == 25) {
            mbar_expect_tx(fb, 16384);
            tma2d(dst, &maps.cre, s * 64, piece0 * 64, fb);
            tma2d(dst + 8192, &maps.cim, s * 64, piece0 * 64, fb);
          } else {
            mbar_expect_tx(fb, 14336);
            tma2d(dst, &maps.w2, piece0 * 64, s * 224 + (u - 24) * 56, fb);
          }
          if (++slot == NSLOT) { slot = 0; ph ^= 1; }
        }
#pragma unroll 1
        for (int p = 1; p < 8; p++) {
          const int piece = ((sp + 1 + (p >> 1)) & 3) * 2 + ((rank ^ p ^ 1) & 1), grp = p % 3;
          const uint32_t fb = sb + OFF_XFULL + 8 * p, dst = grp == 1 ? sb + OFF_X + 2 * 16384 : sb + OFF_RING + grp * 24576;
          if (p >= 3) mbar_wait(sb + OFF_EMPTY + 8 * (p - 3), 0);
          else if (p == 2) mbar_wait(sb + OFF_EMPTY + 40, 1);
          TS2(0, 32 + p);
          mbar_expect_tx(fb, 45056);
          tma2d(dst, &maps.w2, piece * 64, s * 224, fb);
          tma2d(dst + 16384, &maps.cre, s * 64, piece * 64, fb);
          tma2d(dst + 24576, &maps.cim, s * 64, piece * 64, fb);
          tma2d(dst + 32768, &maps.w2, piece * 64, s * 224 + 112, fb);
        }
        TS(2, 2);
      }
    }
  }
}

typedef CUresult (*EncFn)(CUtensorMap*, CUtensorMapDataType, cuuint32_t, void*, const cuuint64_t*, const cuuint64_t*, const cuuint32_t*,
                          const cuuint32_t*, CUtensorMapInterleave, CUtensorMapSwizzle, CUtensorMapL2promotion, CUtensorMapFloatOOBfill);

void encode(EncFn f, CUtensorMap* mp, const void* p, int rank, const cuuint64_t* dims, const cuuint64_t* strides, const cuuint32_t* box, CUtensorMapSwizzle sw) {
  cuuint32_t es[5] = {1, 1, 1, 1, 1};
  f(mp, CU_TENSOR_MAP_DATA_TYPE_BFLOAT16, rank, const_cast<void*>(p), dims, strides, box, es, CU_TENSOR_MAP_INTERLEAVE_NONE, sw,
    CU_TENSOR_MAP_L2_PROMOTION_L2_128B, CU_TENSOR_MAP_FLOAT_OOB_FILL_NONE);
}

}

extern "C" void kernel_launch(void* const* d_in, const int* in_sizes, int n_in, void* d_out, int out_size) {
  typedef const __nv_bfloat16* bp;
  bp x = (bp)d_in[0], lre = (bp)d_in[1], lim = (bp)d_in[2], bre = (bp)d_in[3], bim = (bp)d_in[4], cre = (bp)d_in[5], cim = (bp)d_in[6],
     ldt = (bp)d_in[7], dsk = (bp)d_in[8], w1 = (bp)d_in[10], b1 = (bp)d_in[11], w2 = (bp)d_in[12], b2 = (bp)d_in[13], gw = (bp)d_in[14];
  static EncFn enc = nullptr;
  if (!enc) {
    void* f = nullptr;
    cudaDriverEntryPointQueryResult qr;
    cudaGetDriverEntryPoint("cuTensorMapEncodeTiled", &f, cudaEnableDefault, &qr);
    enc = (EncFn)f;
    cudaFuncSetAttribute(fused_kernel, cudaFuncAttributeMaxDynamicSharedMemorySize, SMEM_BYTES);
  }
  Maps maps;
  {
    cuuint64_t d[5] = {DM, 2, 4, 8, SEQ / 64}, st[4] = {DM * 2, 16 * DM * 2, 2 * DM * 2, 64 * DM * 2};
    cuuint32_t bx[5] = {64, 2, 4, 8, 1};
    encode(enc, &maps.x, x, 5, d, st, bx, CU_TENSOR_MAP_SWIZZLE_128B);
  }
  {
    cuuint64_t d[2] = {DM, DM}, st[1] = {DM * 2};
    cuuint32_t bx[2] = {64, 64};
    encode(enc, &maps.bre, bre, 2, d, st, bx, CU_TENSOR_MAP_SWIZZLE_128B);
    encode(enc, &maps.bim, bim, 2, d, st, bx, CU_TENSOR_MAP_SWIZZLE_128B);
    encode(enc, &maps.cre, cre, 2, d, st, bx, CU_TENSOR_MAP_SWIZZLE_128B);
    encode(enc, &maps.cim, cim, 2, d, st, bx, CU_TENSOR_MAP_SWIZZLE_128B);
  }
  {
    cuuint64_t d[2] = {FF, DM}, st[1] = {FF * 2};
    cuuint32_t bx[2] = {64, 64};
    encode(enc, &maps.w1a, w1, 2, d, st, bx, CU_TENSOR_MAP_SWIZZLE_128B);
    cuuint64_t d3[3] = {32, DM, FF / 32}, st3[2] = {FF * 2, 64};
    cuuint32_t bx3[3] = {32, 64, 3};
    encode(enc, &maps.w1b, w1, 3, d3, st3, bx3, CU_TENSOR_MAP_SWIZZLE_64B);
  }
  {
    cuuint64_t d[2] = {DM, FF}, st[1] = {DM * 2};
    cuuint32_t bx[2] = {64, 112};
    encode(enc, &maps.w2, w2, 2, d, st, bx, CU_TENSOR_MAP_SWIZZLE_128B);
  }
  fused_kernel<<<128, 384, SMEM_BYTES>>>(lre, lim, ldt, dsk, b1, b2, gw, w1, w2, cre, cim, (float*)d_out, maps);
}
```

```cpp
#include <cuda_runtime.h>
#include <cuda_bf16.h>
#include <cuda.h>
#include <stdint.h>

#define MAP 1
#define D0 600
#define D1 500
#define PF 6
#define PFK 5
#define GELUP 0
#define EW 1
#define K1E 1
#define K2E 0
#define QS 1
#define K2G 4
#define FINP 6
#define A0 7
#define A1 7
#define E1L 0
#define TP 9
#define TW 0

namespace {

constexpr int SEQ = 2048, DM = 512, FF = 1792;
constexpr int NSLOT = 6;
constexpr uint32_t OFF_X = 0, OFF_RING = 131072, OFF_MISC = 229376;
constexpr uint32_t OFF_XFULL = OFF_MISC, OFF_FULL = OFF_XFULL + 64, OFF_RBAR = OFF_FULL + 48, OFF_EMPTY = OFF_RBAR + 16, OFF_KBAR = OFF_EMPTY + 48,
                   OFF_GBAR = OFF_KBAR + 16, OFF_LBAR = OFF_GBAR + 8, OFF_CBAR = OFF_LBAR + 8, OFF_EPOCH = OFF_CBAR + 8;
constexpr uint32_t OFF_LC = OFF_MISC + 256;
constexpr uint32_t OFF_GS = OFF_LC;
constexpr uint32_t OFF_DB = OFF_LC + 512;
constexpr uint32_t OFF_CARRY = OFF_LC + 1024;
constexpr uint32_t OFF_DBG = OFF_CARRY + 1024;
constexpr uint32_t SMEM_BYTES = OFF_DBG + 768;
static_assert(SMEM_BYTES <= 232448, "smem");

struct Maps { CUtensorMap x, bre, bim, w1b, w1a, w2, cre, cim; };
__host__ __device__ constexpr uint32_t stage_off(int p) { return 49152 + 45056 * (((p >> 1) & 1) + 2 * (p & 1)); }

__device__ uint4 g_part[16 * 8 * 3 * 1024];
__device__ float2 g_end[8 * 16 * 64];
__device__ unsigned g_gate[SEQ];
__device__ unsigned g_epoch[128];
#define TG(role) do {} while (0)
#define TS2(role, i) do {} while (0)
#define TS(role, i) do {} while (0)
#define TDUMP() do {} while (0)
#define TR(i) do {} while (0)
#define TRD() do {} while (0)

__device__ __forceinline__ void mbar_init(uint32_t bar, uint32_t cnt) { asm volatile("mbarrier.init.shared::cta.b64 [%0], %1;" ::"r"(bar), "r"(cnt)); }
__device__ __forceinline__ void mbar_expect_tx(uint32_t bar, uint32_t bytes) { asm volatile("mbarrier.arrive.expect_tx.shared::cta.b64 _, [%0], %1;" ::"r"(bar), "r"(bytes) : "memory"); }
__device__ __forceinline__ void mbar_arrive(uint32_t bar) { asm volatile("mbarrier.arrive.shared::cta.b64 _, [%0];" ::"r"(bar) : "memory"); }
__device__ __forceinline__ void mbar_arrive_cl(uint32_t cbar) { asm volatile("mbarrier.arrive.shared::cluster.b64 _, [%0];" ::"r"(cbar) : "memory"); }
__device__ __forceinline__ void mbar_wait(uint32_t bar, uint32_t parity) {
  asm volatile(
      "{\n.reg .pred p;\n.reg .u32 c;\n"
      "mbarrier.try_wait.parity.shared::cta.b64 p, [%0], %1;\n"
      "@p bra.uni LAB_DONE;\n"
      "mov.u32 c, 0;\n"
      "LAB_WAIT:\n"
      "mbarrier.try_wait.parity.shared::cta.b64 p, [%0], %1;\n"
      "@p bra.uni LAB_DONE;\n"
      "add.u32 c, c, 1;\nsetp.lt.u32 p, c, 200000;\n@p bra.uni LAB_WAIT;\n"
      "LAB_DONE:\n}" ::"r"(bar), "r"(parity) : "memory");
}
__device__ __forceinline__ void tma2d(uint32_t dst, const CUtensorMap* m, int c0, int c1, uint32_t bar) {
  asm volatile("cp.async.bulk.tensor.2d.shared::cluster.global.mbarrier::complete_tx::bytes [%0], [%1, {%3,%4}], [%2];"
               ::"r"(dst), "l"(m), "r"(bar), "r"(c0), "r"(c1) : "memory");
}
__device__ __forceinline__ void tma3d(uint32_t dst, const CUtensorMap* m, int c0, int c1, int c2, uint32_t bar) {
  asm volatile("cp.async.bulk.tensor.3d.shared::cluster.global.mbarrier::complete_tx::bytes [%0], [%1, {%3,%4,%5}], [%2];"
               ::"r"(dst), "l"(m), "r"(bar), "r"(c0), "r"(c1), "r"(c2) : "memory");
}
__device__ __forceinline__ void tma5d_mc(uint32_t dst, const CUtensorMap* m, int c0, int c4, uint32_t bar) {
  asm volatile("cp.async.bulk.tensor.5d.shared::cluster.global.mbarrier::complete_tx::bytes.multicast::cluster [%0], [%1, {%3,%5,%5,%5,%4}], [%2], %6;"
               ::"r"(dst), "l"(m), "r"(bar), "r"(c0), "r"(c4), "r"(0), "h"((uint16_t)3) : "memory");
}
__device__ __forceinline__ void l2_prefetch(const void* p, uint32_t bytes) { asm volatile("cp.async.bulk.prefetch.L2.global [%0], %1;" ::"l"(p), "r"(bytes) : "memory"); }
__device__ __forceinline__ bool elect_one() {
  uint32_t pred;
  asm volatile("{.reg .pred P; elect.sync _|P, 0xffffffff; selp.u32 %0, 1, 0, P;}" : "=r"(pred));
  return pred != 0;
}
__device__ __forceinline__ void wg_fence() { asm volatile("wgmma.fence.sync.aligned;" ::: "memory"); }
__device__ __forceinline__ void wg_commit() { asm volatile("wgmma.commit_group.sync.aligned;" ::: "memory"); }
template <int N> __device__ __forceinline__ void wg_wait() { asm volatile("wgmma.wait_group.sync.aligned %0;" ::"n"(N) : "memory"); }
__device__ __forceinline__ void pin(float& a) { asm volatile("" : "+f"(a)::"memory"); }
__device__ __forceinline__ void pin(uint32_t& a) { asm volatile("" : "+r"(a)::"memory"); }
template <int N> __device__ __forceinline__ void reg_fence(float (&d)[N]) {
#pragma unroll
  for (int i = 0; i < N; i++) pin(d[i]);
}
__device__ __forceinline__ void bar_sync(int id, int n) { asm volatile("bar.sync %0, %1;" ::"r"(id), "r"(n) : "memory"); }
__device__ __forceinline__ void bar_arrive(int id, int n) { asm volatile("bar.arrive %0, %1;" ::"r"(id), "r"(n) : "memory"); }
constexpr uint32_t DH128 = (1024 >> 4) | (1u << 30), DH64 = (512 >> 4) | (2u << 30);
__host__ __device__ constexpr uint32_t lbo(uint32_t bytes) { return (bytes >> 4) << 20; }
__device__ __forceinline__ uint32_t pack_bf16(float lo, float hi) { uint32_t r; asm("cvt.rn.bf16x2.f32 %0, %1, %2;" : "=r"(r) : "f"(hi), "f"(lo)); return r; }
__device__ __forceinline__ float bf_lo(uint32_t v) { return __uint_as_float(v << 16); }
__device__ __forceinline__ float bf_hi(uint32_t v) { return __uint_as_float(v & 0xffff0000u); }
__device__ __forceinline__ float bf_ld(const __nv_bfloat16* p) { return __bfloat162float(__ldg(p)); }
__device__ __forceinline__ uint32_t late16(uint32_t bar) {
  uint32_t r;
  asm volatile("{.reg .pred p; mbarrier.test_wait.parity.shared::cta.b64 p, [%1], 0; selp.u32 %0, 16, 0, p;}" : "=r"(r) : "r"(bar) : "memory");
  return r;
}
__device__ __forceinline__ float2 lds_f2(uint32_t a) { float2 v; asm volatile("ld.shared.v2.f32 {%0,%1}, [%2];" : "=f"(v.x), "=f"(v.y) : "r"(a)); return v; }
__device__ __forceinline__ uint32_t lds_h(uint32_t a) { uint32_t v; asm volatile("ld.shared.u16 %0, [%1];" : "=r"(v) : "r"(a)); return v; }
__device__ __forceinline__ uint32_t lds_u(uint32_t a) { uint32_t v; asm volatile("ld.shared.u32 %0, [%1];" : "=r"(v) : "r"(a)); return v; }
__device__ __forceinline__ uint4 lds_u4(uint32_t a) { uint4 v; asm volatile("ld.shared.v4.u32 {%0,%1,%2,%3}, [%4];" : "=r"(v.x), "=r"(v.y), "=r"(v.z), "=r"(v.w) : "r"(a)); return v; }
__device__ __forceinline__ void st_b128(uint4* p, uint32_t a, uint32_t b, uint32_t c, uint32_t d) {
  asm volatile("st.relaxed.gpu.global.v4.b32 [%0], {%1,%2,%3,%4};" ::"l"(p), "r"(a), "r"(b), "r"(c), "r"(d) : "memory");
}
__device__ __forceinline__ void ld_b128(const uint4* p, uint32_t& a, uint32_t& b, uint32_t& c, uint32_t& d) {
  asm volatile("{.reg .b64 l, h; .reg .b128 v; ld.relaxed.gpu.global.b128 v, [%4]; mov.b128 {l,h}, v; mov.b64 {%0,%1}, l; mov.b64 {%2,%3}, h;}"
               : "=r"(a), "=r"(b), "=r"(c), "=r"(d) : "l"(p) : "memory");
}
__device__ __forceinline__ float tanh_fast(float x) { float y; asm("tanh.approx.f32 %0, %1;" : "=f"(y) : "f"(x)); return y; }
__device__ __forceinline__ float gelu2(float v) {
  float p = fmaf(v * v, 0.0356774081363f, 0.7978845608029f);
  return fmaf(v, tanh_fast(v * p), v);
}
__device__ __forceinline__ uint32_t bf2_mul(uint32_t a, uint32_t b) { uint32_t r; asm("mul.rn.bf16x2 %0, %1, %2;" : "=r"(r) : "r"(a), "r"(b)); return r; }
__device__ __forceinline__ uint32_t bf2_add(uint32_t a, uint32_t b) { uint32_t r; asm("add.rn.bf16x2 %0, %1, %2;" : "=r"(r) : "r"(a), "r"(b)); return r; }
__device__ __forceinline__ uint32_t bf2_fma(uint32_t a, uint32_t b, uint32_t c) { uint32_t r; asm("fma.rn.bf16x2 %0, %1, %2, %3;" : "=r"(r) : "r"(a), "r"(b), "r"(c)); return r; }
__device__ __forceinline__ uint32_t gelu2_pair(float a, float b) {
  return pack_bf16(gelu2(a), gelu2(b));
}
struct cplx { float re, im; };
__device__ __forceinline__ cplx cmul(cplx a, cplx b) { return {fmaf(a.re, b.re, -a.im * b.im), fmaf(a.re, b.im, a.im * b.re)}; }
__device__ __forceinline__ cplx cfma(cplx a, cplx b, cplx c) {
  return {fmaf(a.re, b.re, fmaf(-a.im, b.im, c.re)), fmaf(a.re, b.im, fmaf(a.im, b.re, c.im))};
}
__device__ __forceinline__ cplx make_lam(float lre, float lim, float ldt) {
  float dt = __bfloat162float(__float2bfloat16_rn(expf(ldt)));
  float mag = expf(dt * lre), sn, cs;
  sincospif(dt * lim * 0.31830988618379067f, &sn, &cs);
  return {mag * cs, mag * sn};
}

template<int TA,int TB,uint32_t AH,uint32_t BH> __device__ __forceinline__ void wgmma_n64_ss(float (&d)[32], uint32_t al, uint32_t ao, uint32_t bl, uint32_t bo, int scale_d){
  asm volatile("{.reg .pred p; .reg .b32 t, v; .reg .b64 da, db; setp.ne.b32 p, %36, 0; add.u32 t, %32, %33; mov.b64 da, {t, %39}; add.u32 v, %34, %35; mov.b64 db, {v, %40};\n"
   "wgmma.mma_async.sync.aligned.m64n64k16.f32.bf16.bf16 {%0,%1,%2,%3,%4,%5,%6,%7,%8,%9,%10,%11,%12,%13,%14,%15,%16,%17,%18,%19,%20,%21,%22,%23,%24,%25,%26,%27,%28,%29,%30,%31}, da, db, p, 1, 1, %37, %38;}"
   : "+f"(d[0]),"+f"(d[1]),"+f"(d[2]),"+f"(d[3]),"+f"(d[4]),"+f"(d[5]),"+f"(d[6]),"+f"(d[7]),"+f"(d[8]),"+f"(d[9]),"+f"(d[10]),"+f"(d[11]),"+f"(d[12]),"+f"(d[13]),"+f"(d[14]),"+f"(d[15]),"+f"(d[16]),"+f"(d[17]),"+f"(d[18]),"+f"(d[19]),"+f"(d[20]),"+f"(d[21]),"+f"(d[22]),"+f"(d[23]),"+f"(d[24]),"+f"(d[25]),"+f"(d[26]),"+f"(d[27]),"+f"(d[28]),"+f"(d[29]),"+f"(d[30]),"+f"(d[31])
   : "r"(al),"r"(ao >> 4),"r"(bl),"r"(bo >> 4),"r"(scale_d),"n"(TA),"n"(TB),"n"(AH),"n"(BH));
}
template<int TB,uint32_t BH> __device__ __forceinline__ void wgmma_n64_rs(float (&d)[32], uint32_t a0,uint32_t a1,uint32_t a2,uint32_t a3, uint32_t bl, uint32_t bo, int scale_d){
  asm volatile("{.reg .pred p; .reg .b32 t; .reg .b64 db; setp.ne.b32 p, %38, 0; add.u32 t, %36, %37; mov.b64 db, {t, %40};\n"
   "wgmma.mma_async.sync.aligned.m64n64k16.f32.bf16.bf16 {%0,%1,%2,%3,%4,%5,%6,%7,%8,%9,%10,%11,%12,%13,%14,%15,%16,%17,%18,%19,%20,%21,%22,%23,%24,%25,%26,%27,%28,%29,%30,%31}, {%32,%33,%34,%35}, db, p, 1, 1, %39;}"
   : "+f"(d[0]),"+f"(d[1]),"+f"(d[2]),"+f"(d[3]),"+f"(d[4]),"+f"(d[5]),"+f"(d[6]),"+f"(d[7]),"+f"(d[8]),"+f"(d[9]),"+f"(d[10]),"+f"(d[11]),"+f"(d[12]),"+f"(d[13]),"+f"(d[14]),"+f"(d[15]),"+f"(d[16]),"+f"(d[17]),"+f"(d[18]),"+f"(d[19]),"+f"(d[20]),"+f"(d[21]),"+f"(d[22]),"+f"(d[23]),"+f"(d[24]),"+f"(d[25]),"+f"(d[26]),"+f"(d[27]),"+f"(d[28]),"+f"(d[29]),"+f"(d[30]),"+f"(d[31])
   : "r"(a0),"r"(a1),"r"(a2),"r"(a3),"r"(bl),"r"(bo >> 4),"r"(scale_d),"n"(TB),"n"(BH));
}
template<int TA,int TB,uint32_t AH,uint32_t BH> __device__ __forceinline__ void wgmma_n96_ss(float (&d)[48], uint32_t al, uint32_t ao, uint32_t bl, uint32_t bo, int scale_d){
  asm volatile("{.reg .pred p; .reg .b32 t, v; .reg .b64 da, db; setp.ne.b32 p, %52, 0; add.u32 t, %48, %49; mov.b64 da, {t, %55}; add.u32 v, %50, %51; mov.b64 db, {v, %56};\n"
   "wgmma.mma_async.sync.aligned.m64n96k16.f32.bf16.bf16 {%0,%1,%2,%3,%4,%5,%6,%7,%8,%9,%10,%11,%12,%13,%14,%15,%16,%17,%18,%19,%20,%21,%22,%23,%24,%25,%26,%27,%28,%29,%30,%31,%32,%33,%34,%35,%36,%37,%38,%39,%40,%41,%42,%43,%44,%45,%46,%47}, da, db, p, 1, 1, %53, %54;}"
   : "+f"(d[0]),"+f"(d[1]),"+f"(d[2]),"+f"(d[3]),"+f"(d[4]),"+f"(d[5]),"+f"(d[6]),"+f"(d[7]),"+f"(d[8]),"+f"(d[9]),"+f"(d[10]),"+f"(d[11]),"+f"(d[12]),"+f"(d[13]),"+f"(d[14]),"+f"(d[15]),"+f"(d[16]),"+f"(d[17]),"+f"(d[18]),"+f"(d[19]),"+f"(d[20]),"+f"(d[21]),"+f"(d[22]),"+f"(d[23]),"+f"(d[24]),"+f"(d[25]),"+f"(d[26]),"+f"(d[27]),"+f"(d[28]),"+f"(d[29]),"+f"(d[30]),"+f"(d[31]),"+f"(d[32]),"+f"(d[33]),"+f"(d[34]),"+f"(d[35]),"+f"(d[36]),"+f"(d[37]),"+f"(d[38]),"+f"(d[39]),"+f"(d[40]),"+f"(d[41]),"+f"(d[42]),"+f"(d[43]),"+f"(d[44]),"+f"(d[45]),"+f"(d[46]),"+f"(d[47])
   : "r"(al),"r"(ao >> 4),"r"(bl),"r"(bo >> 4),"r"(scale_d),"n"(TA),"n"(TB),"n"(AH),"n"(BH));
}
template<int TA,int TB,uint32_t AH,uint32_t BH> __device__ __forceinline__ void wgmma_n128_ss(float (&d)[64], uint32_t al, uint32_t ao, uint32_t bl, uint32_t bo, int scale_d){
  asm volatile("{.reg .pred p; .reg .b32 t, v; .reg .b64 da, db; setp.ne.b32 p, %68, 0; add.u32 t, %64, %65; mov.b64 da, {t, %71}; add.u32 v, %66, %67; mov.b64 db, {v, %72};\n"
   "wgmma.mma_async.sync.aligned.m64n128k16.f32.bf16.bf16 {%0,%1,%2,%3,%4,%5,%6,%7,%8,%9,%10,%11,%12,%13,%14,%15,%16,%17,%18,%19,%20,%21,%22,%23,%24,%25,%26,%27,%28,%29,%30,%31,%32,%33,%34,%35,%36,%37,%38,%39,%40,%41,%42,%43,%44,%45,%46,%47,%48,%49,%50,%51,%52,%53,%54,%55,%56,%57,%58,%59,%60,%61,%62,%63}, da, db, p, 1, 1, %69, %70;}"
   : "+f"(d[0]),"+f"(d[1]),"+f"(d[2]),"+f"(d[3]),"+f"(d[4]),"+f"(d[5]),"+f"(d[6]),"+f"(d[7]),"+f"(d[8]),"+f"(d[9]),"+f"(d[10]),"+f"(d[11]),"+f"(d[12]),"+f"(d[13]),"+f"(d[14]),"+f"(d[15]),"+f"(d[16]),"+f"(d[17]),"+f"(d[18]),"+f"(d[19]),"+f"(d[20]),"+f"(d[21]),"+f"(d[22]),"+f"(d[23]),"+f"(d[24]),"+f"(d[25]),"+f"(d[26]),"+f"(d[27]),"+f"(d[28]),"+f"(d[29]),"+f"(d[30]),"+f"(d[31]),"+f"(d[32]),"+f"(d[33]),"+f"(d[34]),"+f"(d[35]),"+f"(d[36]),"+f"(d[37]),"+f"(d[38]),"+f"(d[39]),"+f"(d[40]),"+f"(d[41]),"+f"(d[42]),"+f"(d[43]),"+f"(d[44]),"+f"(d[45]),"+f"(d[46]),"+f"(d[47]),"+f"(d[48]),"+f"(d[49]),"+f"(d[50]),"+f"(d[51]),"+f"(d[52]),"+f"(d[53]),"+f"(d[54]),"+f"(d[55]),"+f"(d[56]),"+f"(d[57]),"+f"(d[58]),"+f"(d[59]),"+f"(d[60]),"+f"(d[61]),"+f"(d[62]),"+f"(d[63])
   : "r"(al),"r"(ao >> 4),"r"(bl),"r"(bo >> 4),"r"(scale_d),"n"(TA),"n"(TB),"n"(AH),"n"(BH));
}

__global__ void __cluster_dims__(2, 1, 1) __launch_bounds__(384, 1)
fused_kernel(const __nv_bfloat16* __restrict__ lam_re, const __nv_bfloat16* __restrict__ lam_im, const __nv_bfloat16* __restrict__ log_dt,
             const __nv_bfloat16* __restrict__ dskip, const __nv_bfloat16* __restrict__ b1, const __nv_bfloat16* __restrict__ b2,
             const __nv_bfloat16* __restrict__ gate_w, const __nv_bfloat16* __restrict__ pf_w1, const __nv_bfloat16* __restrict__ pf_w2,
             const __nv_bfloat16* __restrict__ pf_cre, const __nv_bfloat16* __restrict__ pf_cim, float* __restrict__ out,
             const __grid_constant__ Maps maps) {
  extern __shared__ __align__(1024) unsigned char smem_raw[];
  const uint32_t sb = (uint32_t)__cvta_generic_to_shared(smem_raw);
  const int b = blockIdx.x;
  const int rank = b & 1, cl = b >> 1;
  const int sp = (cl & 1) | ((cl >> 2) & 2), m = ((cl >> 1) & 3) | ((cl >> 4) << 2);
  const int s = sp * 2 + rank;
  const int warp = __shfl_sync(0xffffffffu, (int)(threadIdx.x >> 5), 0);
  const int lane = threadIdx.x & 31;
  const int xrot = 9 - 2 * sp;

  if (elect_one()) {
    if (warp == 8) TS(2, 0);
    if (warp < 3) {
      asm volatile("prefetch.tensormap [%0];" ::"l"(&maps.x + warp) : "memory");
      mbar_init(sb + OFF_GBAR + 8 * warp, warp < 2 ? 64 : 96);
    }
    const uint32_t c = warp < 8 ? 1 : warp < 11 ? 8 : 4;
    mbar_init(sb + OFF_XFULL + 16 * warp, c);
    mbar_init(sb + OFF_XFULL + 16 * warp + 8, c);
    asm volatile("fence.mbarrier_init.release.cluster;" ::: "memory");
  }
  __syncwarp();
  asm volatile("barrier.cluster.arrive.relaxed.aligned;" ::: "memory");

  if (warp < 8) {
    const int wg = warp >> 2, w = warp & 3, q = lane & 3, gr = lane >> 2;
    uint32_t bv[28];
#pragma unroll
    for (int j = 0; j < 28; j++) bv[j] = __ldg(reinterpret_cast<const uint32_t*>(b1 + s * 224 + j * 8) + q);
    asm volatile("setmaxnreg.inc.sync.aligned.u32 224;");
    asm volatile("barrier.cluster.wait.aligned;" ::: "memory");
    TS(wg, 0);
    auto release = [&](int slot) { if (lane == 0) mbar_arrive(sb + OFF_EMPTY + 8 * slot); };
    const uint32_t xw = sb + OFF_X + wg * 8192, fullb = sb + OFF_FULL;
    const uint32_t dxw = (xw & 0x3FFFF) >> 4, dring = ((sb + OFF_RING) & 0x3FFFF) >> 4;

    float ure[32], uim[32], aa[48], ab[64];
    cplx lam[2], coef[2], l16[2], l32[2], lq[2], pre[2], e[2];
    uint32_t sh16, mhi;

#pragma unroll
    for (int kb = 0; kb < 8; kb++) {
      const int slot = kb % NSLOT;
      mbar_wait(sb + OFF_XFULL + 8 * kb, 0);
      if (kb == 0) TS(wg, 18);
      mbar_wait(fullb + 8 * slot, (kb / NSLOT) & 1);
      TS2(2, kb);
      if (kb == 0) TS(wg, 1);
      wg_fence();
      const uint32_t dxa = dxw + ((kb + xrot) & 7) * 1024;
#pragma unroll
      for (int kk = 0; kk < 4; kk++) {
        wgmma_n64_ss<0, 0, DH128, DH128>(ure, dring, slot * 16384 + kk * 32, dxa, kk * 32, (kb | kk) != 0);
        wgmma_n64_ss<0, 0, DH128, DH128>(uim, dring, slot * 16384 + 8192 + kk * 32, dxa, kk * 32, (kb | kk) != 0);
      }
      wg_commit();
      if (kb > 0) { wg_wait<1>(); release((kb - 1) % NSLOT); }
      if (kb == 1) { sh16 = late16(sb + OFF_XFULL); mhi = 0xffffffffu << sh16; }
      if (kb == 1 || (kb >= 3 && kb < 6)) {
#pragma unroll
        for (int j = 0; j < 28; j++) if (j / 7 == (kb == 1 ? 0 : kb - 2)) {
          pin(bv[j]);
          float* d = j < 12 ? aa + 4 * j : ab + 4 * (j - 12);
          d[0] = d[2] = __uint_as_float(bv[j] << sh16); d[1] = d[3] = __uint_as_float(bv[j] & mhi);
          pin(d[0]); pin(d[1]); pin(d[2]); pin(d[3]);
        }
      }
      if (kb == 5) {
        mbar_wait(sb + OFF_LBAR, 0);
#pragma unroll
        for (int h = 0; h < 2; h++) {
          const uint4 v = lds_u4(sb + OFF_LC + (w * 16 + gr + 8 * h) * 16);
          lam[h] = cplx{__uint_as_float(v.x), __uint_as_float(v.y)};
          coef[h] = cplx{__uint_as_float(v.z), __uint_as_float(v.w)};
        }
      }
      if (kb == 6) {
#pragma unroll
        for (int h = 0; h < 2; h++) {
          pin(lam[h].re); pin(lam[h].im);
          cplx t = cmul(lam[h], lam[h]); t = cmul(t, t); t = cmul(t, t);
          l16[h] = cmul(t, t);
          pin(l16[h].re); pin(l16[h].im);
        }
      }
      if (kb == 7) {
#pragma unroll
        for (int h = 0; h < 2; h++) {
          pin(l16[h].re); pin(l16[h].im);
          l32[h] = cmul(l16[h], l16[h]);
          const cplx a = (q & 1) ? l16[h] : cplx{1.f, 0.f}, c = (q & 2) ? l32[h] : cplx{1.f, 0.f};
          lq[h] = cmul(cmul(a, c), coef[h]);
          pin(lq[h].re); pin(lq[h].im);
        }
      }
    }
    TS(wg, 2);
    auto scale_u = [&](int i0, int i1) {
#pragma unroll
      for (int i = 0; i < 32; i++) if (i >= i0 && i < i1) {
        pin(ure[i]); pin(uim[i]);
        const cplx v = cmul(coef[(i >> 1) & 1], cplx{ure[i], uim[i]});
        ure[i] = v.re; uim[i] = v.im;
        pin(ure[i]); pin(uim[i]);
      }
    };
#pragma unroll
    for (int kb = 0; kb < 8; kb++) {
      const int u = 8 + kb, slot = u % NSLOT;
      mbar_wait(fullb + 8 * slot, (u / NSLOT) & 1);
      wg_fence();
      const uint32_t dxa = dxw + ((kb + xrot) & 7) * 1024;
#pragma unroll
      for (int kk = 0; kk < 4; kk++)
        wgmma_n96_ss<0, 1, DH128, DH64>(aa, dxa, kk * 32, dring, slot * 16384 + kk * 1024 + lbo(4096), 1);
      wg_commit();
      wg_wait<1>();
      release((u - 1) % NSLOT);
      if (kb == 0) {
        reg_fence(ure); reg_fence(uim);
#pragma unroll
        for (int h = 0; h < 2; h++) e[h] = cplx{ure[2 * h], uim[2 * h]};
      }
      if (kb == 0 || kb == 2 || kb == 3) {
        const int ch = kb ? kb - 1 : 0;
#pragma unroll
        for (int t = 1 + 5 * ch; t < 6 + 5 * ch; t++)
#pragma unroll
          for (int h = 0; h < 2; h++) { const int i = 4 * (t >> 1) + 2 * h + (t & 1); e[h] = cfma(lam[h], e[h], cplx{ure[i], uim[i]}); }
#pragma unroll
        for (int h = 0; h < 2; h++) { pin(e[h].re); pin(e[h].im); }
      } else if (kb == 4) {
#pragma unroll
        for (int h = 0; h < 2; h++) {
          cplx y = {__shfl_up_sync(0xffffffffu, e[h].re, 1, 4), __shfl_up_sync(0xffffffffu, e[h].im, 1, 4)};
          if (q >= 1) e[h] = cfma(l16[h], y, e[h]);
          y = cplx{__shfl_up_sync(0xffffffffu, e[h].re, 2, 4), __shfl_up_sync(0xffffffffu, e[h].im, 2, 4)};
          if (q >= 2) e[h] = cfma(l32[h], y, e[h]);
        }
        if (q == 3) {
#pragma unroll
          for (int h = 0; h < 2; h++)
            asm volatile("st.shared.v2.f32 [%0], {%1,%2};" ::"r"(sb + OFF_CARRY + wg * 512 + (w * 16 + gr + 8 * h) * 8), "f"(e[h].re), "f"(e[h].im) : "memory");
          mbar_arrive(sb + OFF_GBAR);
        }
#pragma unroll
        for (int h = 0; h < 2; h++) {
          const cplx y = {__shfl_up_sync(0xffffffffu, e[h].re, 1, 4), __shfl_up_sync(0xffffffffu, e[h].im, 1, 4)};
          pre[h] = (q >= 1) ? cmul(coef[h], y) : cplx{0.f, 0.f};
          pin(pre[h].re); pin(pre[h].im);
        }
        TS(wg, 3);
      } else if (kb > 4) {
        scale_u(kb == 5 ? 0 : kb == 6 ? 4 : 12, kb == 5 ? 4 : kb == 6 ? 12 : 20);
      }
    }
    TS(wg, 4);
    uint32_t H[56], hf[32];
    cplx hst[2];
    const uint32_t hst_addr = xw + (w * 16 + (lane & 15)) * 128 + (((lane >> 4) ^ (lane & 7)) << 4);
    const uint32_t him = (2 - rank) * 16384;
    uint32_t peer;
    asm volatile("mapa.shared::cluster.u32 %0, %1, %2;" : "=r"(peer) : "r"(sb), "r"(rank ^ 1));
    auto credit = [&]() { if (lane == 0) mbar_arrive_cl(peer + OFF_KBAR + wg * 8); };
#pragma unroll
    for (int kb = 0; kb < 8; kb++) {
      const int u = 16 + kb, slot = u % NSLOT;
      mbar_wait(fullb + 8 * slot, (u / NSLOT) & 1);
      wg_fence();
#pragma unroll
      for (int kk = 0; kk < 4; kk++)
        wgmma_n128_ss<0, 1, DH128, DH128>(ab, dxw, kb * 16384 + kk * 32, dring, slot * 16384 + kk * 2048 + lbo(8192), 1);
      wg_commit();
      wg_wait<1>();
      release((u - 1) % NSLOT);
      if (kb == 0) scale_u(20, 32);
      if (kb < 5 && kb != 1) {
        const int ch = kb ? kb - 1 : 0;
#pragma unroll
        for (int i = ch * 6; i < ch * 6 + 6; i++) {
          pin(aa[2 * i]); pin(aa[2 * i + 1]);
          H[i] = gelu2_pair(aa[2 * i], aa[2 * i + 1]);
          pin(H[i]);
        }
      }
      if (kb >= 4) {
        if (kb == 4) {
          TS(wg, 5);
          mbar_wait(sb + OFF_CBAR, 0);
          TS(wg, 6);
#pragma unroll
          for (int h = 0; h < 2; h++) {
            const float2 c = lds_f2(sb + OFF_CARRY + wg * 512 + (w * 16 + gr + 8 * h) * 8);
            hst[h] = cfma(lq[h], cplx{c.x, c.y}, pre[h]);
          }
        }
        const int j0 = (kb - 4) * 2;
        uint32_t rr[4], ri[4];
#pragma unroll
        for (int jj = 0; jj < 2; jj++) {
          const int j = j0 + jj;
          const uint32_t g2 = lds_u(sb + OFF_GS + (wg * 64 + j * 8 + q * 2) * 2);
#pragma unroll
          for (int h = 0; h < 2; h++) {
            const int i = 4 * j + 2 * h;
            const cplx h0 = cfma(lam[h], hst[h], cplx{ure[i], uim[i]});
            hst[h] = cfma(lam[h], h0, cplx{ure[i + 1], uim[i + 1]});
            rr[jj * 2 + h] = bf2_mul(pack_bf16(h0.re, hst[h].re), g2);
            ri[jj * 2 + h] = bf2_mul(pack_bf16(h0.im, hst[h].im), g2 ^ 0x80008000u);
          }
        }
        const uint32_t a = hst_addr ^ (j0 << 4);
        asm volatile("stmatrix.sync.aligned.m8n8.x4.shared.b16 [%0], {%1,%2,%3,%4};" ::"r"(a), "r"(rr[0]), "r"(rr[1]), "r"(rr[2]), "r"(rr[3]) : "memory");
        asm volatile("stmatrix.sync.aligned.m8n8.x4.shared.b16 [%0], {%1,%2,%3,%4};" ::"r"(a + him), "r"(ri[0]), "r"(ri[1]), "r"(ri[2]), "r"(ri[3]) : "memory");
      }
    }
    TS(wg, 7);

    uint4* const psend = g_part + (size_t)(m * 8 + rank) * 3072 + warp * 128 + lane;
    const uint4* const precv = g_part + (size_t)(m * 8 + s) * 3072 + warp * 128 + lane;
    const uint32_t pbuf = OFF_X + warp * 2048 + lane * 16;
    const uint32_t dx0 = ((sb + OFF_X) & 0x3FFFF) >> 4;
    float o[32], fin[32], rho[2];
    uint32_t tr[8];
    uint32_t r0[16], pt[16], sum[16], tag;
    auto recv_issue = [&](uint32_t (&r)[16], int k) {
#pragma unroll
      for (int i = 0; i < 4; i++) ld_b128(precv + k * 1024 + i * 32, r[4 * i], r[4 * i + 1], r[4 * i + 2], r[4 * i + 3]);
    };
    auto stale = [&](uint32_t (&r)[16]) {
      uint32_t t0, t1, r_;
      asm("lop3.b32 %0, %1, %2, %3, 0x7e;" : "=r"(t0) : "r"(r[0]), "r"(r[4]), "r"(tag));
      asm("lop3.b32 %0, %1, %2, %3, 0x7e;" : "=r"(t1) : "r"(r[8]), "r"(r[12]), "r"(tag));
      asm volatile("{.reg .pred p; .reg .b32 t; lop3.b32 t, %1, %2, 1, 0xa8; setp.ne.u32 p, t, 0; vote.sync.any.pred p, p, 0xffffffff; selp.u32 %0, 1, 0, p;}" : "=r"(r_) : "r"(t0), "r"(t1));
      return r_ != 0;
    };
    auto recv_check = [&](uint32_t (&r)[16], int k) {
      if (__builtin_expect(stale(r), 0)) {
        int tries = 0;
#pragma unroll 1
        do { recv_issue(r, k); } while (stale(r) && ++tries < 200000);
      }
    };
    auto gelu_b = [&](int i0, int i1) {
#pragma unroll
      for (int i = i0; i < i1; i++) {
        pin(ab[2 * i]); pin(ab[2 * i + 1]);
        H[24 + i] = gelu2_pair(ab[2 * i], ab[2 * i + 1]);
        pin(H[24 + i]);
      }
    };
    auto step = [&](float (&d)[32], int p, int k, int acc) {
      const uint32_t wo = stage_off(p);
      if (k >= 6 && k < 14) {
        const int kk = k - 6;
        wgmma_n64_rs<0, DH128>(d, hf[4 * kk], hf[4 * kk + 1], hf[4 * kk + 2], hf[4 * kk + 3], dx0, wo + 14336 + (kk >> 2) * 8192 + (kk & 3) * 32, 1);
      } else {
        const int kk = k < 6 ? k : k - 8;
        wgmma_n64_rs<1, DH128>(d, H[4 * kk], H[4 * kk + 1], H[4 * kk + 2], H[4 * kk + 3], dx0, wo + (kk / 7) * 30720 + (kk % 7) * 2048, k != 0 || acc);
      }
    };
    auto mma = [&](float (&d)[32], int p, int k0, int k1, int acc) {
      wg_fence();
#pragma unroll
      for (int k = k0; k < k1; k++) step(d, p, k, acc);
      wg_commit();
    };
    auto mma2 = [&](int k0, int k1) {
      wg_fence();
#pragma unroll
      for (int k = k0; k < k1; k++) { step(o, 0, k, 0); step(fin, 1, k, 0); }
      wg_commit();
    };
    auto send_peer = [&]() {
#pragma unroll
      for (int i = 0; i < 4; i++)
        asm volatile("st.async.shared::cluster.mbarrier::complete_tx::bytes.v4.b32 [%0], {%1,%2,%3,%4}, [%5];" ::"r"(peer + pbuf + i * 512),
                     "r"(pack_bf16(o[8 * i], o[8 * i + 1])), "r"(pack_bf16(o[8 * i + 2], o[8 * i + 3])), "r"(pack_bf16(o[8 * i + 4], o[8 * i + 5])),
                     "r"(pack_bf16(o[8 * i + 6], o[8 * i + 7])), "r"(peer + OFF_RBAR + wg * 8) : "memory");
    };
    auto recv_peer = [&](int k) {
      mbar_wait(sb + OFF_RBAR + wg * 8, k & 1);
#pragma unroll
      for (int i = 0; i < 4; i++) { const uint4 v = lds_u4(sb + pbuf + i * 512); pt[4 * i] = v.x; pt[4 * i + 1] = v.y; pt[4 * i + 2] = v.z; pt[4 * i + 3] = v.w; }
    };
    auto send_owner = [&](float (&d)[32], int k) {
#pragma unroll
      for (int i = 0; i < 4; i++) {
#pragma unroll
        for (int c = 4 * i; c < 4 * i + 4; c++) pt[c] = bf2_add(pt[c], pack_bf16(d[2 * c], d[2 * c + 1]));
        asm("lop3.b32 %0, %0, 1, %1, 0xb8;" : "+r"(pt[4 * i]) : "r"(tag));
        st_b128(psend + (((sp + 1 + k) & 3) * 6 + k) * 1024 + i * 32, pt[4 * i], pt[4 * i + 1], pt[4 * i + 2], pt[4 * i + 3]);
      }
      __syncwarp();
      credit();
    };
    auto arm = [&]() { if ((threadIdx.x & 127) == 0) mbar_expect_tx(sb + OFF_RBAR + wg * 8, 8192); };
    auto hand = [&](int pos) { if ((A0 == pos && wg == 0) || (A1 == pos && wg == 1)) bar_arrive(4 - wg, 256); };
    mbar_wait(fullb, 0);
    mma2(0, 3);
    bar_sync(1 + wg, 128);
    {
      const uint32_t ha = xw + ((lane >> 4) * 8 + (lane & 7)) * 128 + (((2 * w + ((lane >> 3) & 1)) ^ (lane & 7)) << 4);
#pragma unroll
      for (int kk = 0; kk < 8; kk++)
        asm volatile("ldmatrix.sync.aligned.m8n8.x4.trans.shared.b16 {%0,%1,%2,%3}, [%4];" : "=r"(hf[4 * kk]), "=r"(hf[4 * kk + 1]), "=r"(hf[4 * kk + 2]), "=r"(hf[4 * kk + 3])
                     : "r"(ha + (kk >> 2) * him + (kk & 3) * 2048) : "memory");
    }
    tag = lds_u(sb + OFF_EPOCH);
    arm();
    wg_wait<1>(); release(5);
    mbar_wait(fullb + 8, 0);
    if (wg == 1) bar_sync(4, 256);
    mma2(3, 6);   gelu_b(0, 4);
    mma2(6, 8);   credit(); gelu_b(4, 8);
    mma2(8, 11);  gelu_b(8, 12);
    mma2(11, 13); gelu_b(12, 16); hand(4);
    mma2(13, 15); gelu_b(16, 20); hand(5);
    mbar_wait(fullb + 16, 0);
    mma2(15, 17); gelu_b(20, 24); hand(6);
    mma2(17, 19); gelu_b(24, 28); hand(7);
    mma2(19, 21); gelu_b(28, 32); hand(8);
    mma2(21, 22);
    TS(wg, 9);
    mbar_wait(sb + OFF_KBAR + wg * 8, 0);
    mbar_wait(sb + OFF_XFULL + 16, 1);
    wg_wait<0>();
    release(0); release(1);
    reg_fence(o); reg_fence(fin);
    send_peer();
    if (!E1L) { recv_peer(0); send_owner(fin, 0); }
#pragma unroll
    for (int p = 2; p < 8; p++) {
      TR(0);
      if (p & 1) mbar_wait(sb + OFF_XFULL + 8 * p, 1);
      TR(1);
      bar_sync(3 + wg, 256);
      if (p < 7) mma(o, p, 0, 22, 0); else mma(fin, p, 0, 22, 1);
      if (p < 7 || wg == 0) bar_arrive(4 - wg, 256);
      TR(2);
      if (p != TP) TS(wg, 8 + p);
      if ((p & 1) == 0) {
        if (E1L && p == 2) { recv_peer(0); send_owner(fin, 0); }
        arm();
        if (p == 6) {
          tag = lds_u(sb + OFF_EPOCH);
          recv_check(sum, 0); recv_check(r0, 1);
#pragma unroll
          for (int i = 0; i < 16; i++) sum[i] = bf2_add(sum[i], r0[i]);
        }
        TR(3);
        mbar_wait(sb + OFF_KBAR + wg * 8, (p >> 1) & 1);
        TR(4);
      } else {
        if (p == 7) { tag = lds_u(sb + OFF_EPOCH); mbar_wait(sb + OFF_EMPTY + 32, 0); }
        if (p < 7) mbar_wait(sb + OFF_XFULL + 8 * (p + 1), 1);
        TR(3);
        recv_peer(p >> 1);
        TR(4);
        if (p == 7) {
          recv_check(r0, 2);
#pragma unroll
          for (int i = 0; i < 16; i++) sum[i] = bf2_add(sum[i], bf2_add(r0[i], pt[i]));
        }
      }
      if (p == FINP) {
        mbar_wait(sb + OFF_LBAR, 1);
#pragma unroll
        for (int j = 0; j < 8; j++) {
          const uint4 v = lds_u4(sb + pbuf + 16384 + (j >> 2) * 16384 + (j & 3) * 512);
          fin[4 * j] = __uint_as_float(v.x); fin[4 * j + 1] = __uint_as_float(v.y); fin[4 * j + 2] = __uint_as_float(v.z); fin[4 * j + 3] = __uint_as_float(v.w);
        }
      }
      TR(5);
      wg_wait<0>();
      TR(6);
      if (p < 5) release(p);
      if (p < 7) reg_fence(o); else reg_fence(fin);
      if ((p & 1) == 0) {
        if (p == 6) recv_issue(r0, 2);
        send_peer();
        if (p == 4) {
          recv_issue(sum, 0);
          if (K1E) recv_issue(r0, 1);
        }
      } else if (p < 7) {
        send_owner(o, p >> 1);
        if (!K1E && p == 5) recv_issue(r0, 1);
      }
      if (p == 2) {
#pragma unroll
        for (int h = 0; h < 2; h++) { rho[h] = __fdividef(2.f, 4.f + bf_lo(lds_h(sb + OFF_GS + (wg * 64 + w * 16 + gr + 8 * h) * 2))); pin(rho[h]); }
      }
      TR(7);
    }
    {
      TS(wg, 16);
      const uint32_t tb = sb + OFF_X + stage_off(0) + warp * 4096;
      const uint32_t ta = tb + gr * 256 + ((gr & 3) << 5) + q * 8;
      const uint32_t la = tb + (lane >> 3) * 256 + (((lane & 7) << 4) ^ ((lane >> 3) << 5));
      float* op = out + (size_t)(m * 128 + wg * 64 + (lane >> 4) * 16 + w * 4 + ((lane >> 3) & 1)) * DM + s * 64 + (lane & 7) * 4;
#pragma unroll
      for (int qq = 0; qq < 4; qq += QS) {
#pragma unroll
        for (int qt = qq; qt < qq + QS; qt++) {
          const int h = qt & 1, ch = qt >> 1;
#pragma unroll
          for (int j = 0; j < 4; j++) {
            const int i = ch * 8 + j * 2 + h;
            asm volatile("st.shared.v2.f32 [%0], {%1,%2};" ::"r"((ta ^ (j << 5)) + h * 2048 + ch * 128),
                         "f"((fin[2 * i] + bf_lo(sum[i])) * rho[h]), "f"((fin[2 * i + 1] + bf_hi(sum[i])) * rho[h]) : "memory");
          }
        }
        __syncwarp();
#pragma unroll
        for (int qt = qq; qt < qq + QS; qt++) {
          const int h = qt & 1, ch = qt >> 1;
#pragma unroll
          for (int r = 0; r < 2; r++)
            *reinterpret_cast<uint4*>(op + (r * 32 + h * 2) * DM + ch * 32) = lds_u4(la + (h * 2 + r) * 1024 + ch * 128);
        }
      }
      if (threadIdx.x == 128) g_epoch[b] = tag;
      TS(wg, 17); TG(wg); TRD(); TDUMP();
    }
  } else {
    asm volatile("setmaxnreg.dec.sync.aligned.u32 56;");
    int wsel = warp;
    asm("" : "+r"(wsel));
    if (wsel > 8) {
      if (warp != 11) {
        const int t = threadIdx.x - 288;
        unsigned par;
        asm volatile("ld.relaxed.gpu.global.u32 %0, [%1];" : "=r"(par) : "l"(g_epoch + b) : "memory");
        const float pr = bf_ld(lam_re + s * 64 + t), pi = bf_ld(lam_im + s * 64 + t), pd = bf_ld(log_dt + s * 64 + t);
        asm volatile("barrier.cluster.wait.aligned;" ::: "memory");
        par = (par + 1) & 1;
        cplx l64 = make_lam(pr, pi, pd);
        {
          const float inv = __fdividef(1.f, fmaf(pr, pr, pi * pi));
          const cplx cf = cmul(cplx{l64.re - 1.f, l64.im}, cplx{pr * inv, -pi * inv});
          asm volatile("st.shared.v4.f32 [%0], {%1,%2,%3,%4};" ::"r"(sb + OFF_LC + t * 16), "f"(l64.re), "f"(l64.im), "f"(cf.re), "f"(cf.im) : "memory");
          mbar_arrive(sb + OFF_LBAR);
        }
#pragma unroll
        for (int i = 0; i < 6; i++) l64 = cmul(l64, l64);
        cplx l128 = cmul(l64, l64);
        pin(l128.re); pin(l128.im);
        mbar_wait(sb + OFF_GBAR, 0);
        const float2 e0 = lds_f2(sb + OFF_CARRY + t * 8), e1 = lds_f2(sb + OFF_CARRY + 512 + t * 8);
        float2* eb = g_end + s * 1024 + t;
        {
          const cplx e = cfma(l64, cplx{e0.x, e0.y}, cplx{e1.x, e1.y});
          const unsigned long long v = ((unsigned long long)__float_as_uint(e.im) << 32) | ((__float_as_uint(e.re) & ~1u) | par);
          asm volatile("st.relaxed.gpu.global.b64 [%0], %1;" ::"l"(eb + m * 64), "l"(v) : "memory");
        }
        if (t == 0) TS(3, 1);
        cplx S = {0.f, 0.f};
        {
          unsigned long long v[15];
          uint32_t bad;
          int tries = 0;
          const float2* e15 = eb + (m - 15) * 64;
#pragma unroll 1
          do {
#pragma unroll
            for (int i = 0; i < 15; i++) {
              v[i] = par;
              asm volatile("{.reg .pred p; setp.ge.s32 p, %2, %3; @p ld.relaxed.gpu.global.b64 %0, [%1];}" : "+l"(v[i]) : "l"(e15 + i * 64), "r"(m), "r"(15 - i) : "memory");
            }
            bad = 0;
#pragma unroll
            for (int i = 0; i < 15; i++) bad |= (uint32_t)v[i] ^ par;
          } while ((bad & 1) && ++tries < 200000);
          if (t == 0) TS(3, 2);
#pragma unroll
          for (int i = 0; i < 15; i++) S = cfma(l128, S, cplx{__uint_as_float((uint32_t)v[i] & ~1u), __uint_as_float((uint32_t)(v[i] >> 32))});
        }
        const cplx S1 = cfma(l64, S, cplx{e0.x, e0.y});
        asm volatile("st.shared.v2.f32 [%0], {%1,%2};" ::"r"(sb + OFF_CARRY + t * 8), "f"(S.re), "f"(S.im) : "memory");
        asm volatile("st.shared.v2.f32 [%0], {%1,%2};" ::"r"(sb + OFF_CARRY + 512 + t * 8), "f"(S1.re), "f"(S1.im) : "memory");
        mbar_arrive(sb + OFF_CBAR);
        if (t == 0) TS(3, 3);
        mbar_wait(sb + OFF_CBAR, 0);
        const int gr = lane >> 2, q = lane & 3;
        float2 db[8];
#pragma unroll
        for (int j = 0; j < 8; j++) db[j] = lds_f2(sb + OFF_DB + j * 32 + q * 8);
        mbar_wait(sb + OFF_XFULL + 16, 1);
        mbar_wait(sb + OFF_EMPTY, 0);
#pragma unroll 1
        for (int cw = warp - 9; cw < 8; cw += 2) {
          const float r0 = 0.5f * bf_lo(lds_h(sb + OFF_GS + (cw * 16 + gr) * 2)), r1 = 0.5f * bf_lo(lds_h(sb + OFF_GS + (cw * 16 + gr) * 2 + 16));
          const uint32_t xa = sb + OFF_X + (1 + rank) * 16384 + (cw * 16 + (lane & 15)) * 128 + (((lane >> 4) ^ (lane & 7)) << 4);
          uint32_t xv[16];
#pragma unroll
          for (int i = 0; i < 4; i++)
            asm volatile("ldmatrix.sync.aligned.m8n8.x4.shared.b16 {%0,%1,%2,%3}, [%4];" : "=r"(xv[4 * i]), "=r"(xv[4 * i + 1]), "=r"(xv[4 * i + 2]), "=r"(xv[4 * i + 3])
                         : "r"(xa ^ (i << 5)) : "memory");
          __syncwarp();
#pragma unroll
          for (int j = 0; j < 8; j++) {
            const uint32_t x0 = bf2_mul(xv[2 * j], __float_as_uint(db[j].x)), x1 = bf2_mul(xv[2 * j + 1], __float_as_uint(db[j].x));
            pin(db[j].y);
            const float bl = bf_lo(__float_as_uint(db[j].y)), bh = bf_hi(__float_as_uint(db[j].y));
            asm volatile("st.shared.v4.f32 [%0], {%1,%2,%3,%4};" ::"r"(sb + OFF_X + 16384 + (j >> 2) * 16384 + cw * 2048 + (j & 3) * 512 + lane * 16), "f"(fmaf(bf_lo(x0), r0, bl)),
                         "f"(fmaf(bf_hi(x0), r0, bh)), "f"(fmaf(bf_lo(x1), r1, bl)), "f"(fmaf(bf_hi(x1), r1, bh)) : "memory");
          }
        }
        mbar_arrive(sb + OFF_LBAR);
        if (t == 0) TS(3, 5);
      } else {
        if (lane == 0) TG(2);
        const uint4* gwp = reinterpret_cast<const uint4*>(gate_w) + (lane & 7);
        uint4 gw[4];
#pragma unroll
        for (int i = 0; i < 4; i++) gw[i] = __ldg(gwp + i * 8);
        unsigned par;
        asm volatile("ld.relaxed.gpu.global.u32 %0, [%1];" : "=r"(par) : "l"(g_epoch + b) : "memory");
        const uint32_t dk = __ldg(reinterpret_cast<const uint32_t*>(dskip + s * 64) + lane), bb = __ldg(reinterpret_cast<const uint32_t*>(b2 + s * 64) + lane);
        asm volatile("barrier.cluster.wait.aligned;" ::: "memory");
        const int row = s * 16 + (lane >> 3);
        const uint32_t xr0 = sb + OFF_X + row * 128 + (((lane & 7) ^ (row & 7)) << 4), xr1 = (xr0 + 512) ^ 64;
        float z[4] = {0.f, 0.f, 0.f, 0.f};
#pragma unroll
        for (int kb = 0; kb < 8; kb++) {
          const uint32_t wv[4] = {gw[kb & 3].x, gw[kb & 3].y, gw[kb & 3].z, gw[kb & 3].w};
          if (kb < 4) gw[kb] = __ldg(gwp + (kb + 4) * 8);
          mbar_wait(sb + OFF_XFULL + 8 * kb, 0);
          if ((PF & 2) && kb == PFK && elect_one()) {
            l2_prefetch(pf_w1 + b * 7168, 14336);
            l2_prefetch(pf_cre + b * 2048, 4096);
            l2_prefetch(pf_cim + b * 2048, 4096);
            l2_prefetch(pf_w2 + b * 7168, 14336);
          }
          const uint32_t xo = ((kb + xrot) & 7) * 16384;
#pragma unroll
          for (int r = 0; r < 4; r++) {
            const uint4 a = lds_u4(((r & 1) ? xr1 : xr0) + xo + (r >> 1) * 1024);
            const uint32_t p = bf2_fma(a.w, wv[3], bf2_fma(a.z, wv[2], bf2_fma(a.y, wv[1], bf2_mul(a.x, wv[0]))));
            z[r] += bf_lo(p); z[r] += bf_hi(p);
          }
        }
        if (lane == 0) asm volatile("st.shared.u32 [%0], %1;" ::"r"(sb + OFF_EPOCH), "r"(par + 1) : "memory");
        par = (par + 1) & 1;
        {
          float y0 = (lane & 4) ? z[1] : z[0], y1 = (lane & 4) ? z[3] : z[2];
          y0 += __shfl_xor_sync(0xffffffffu, (lane & 4) ? z[0] : z[1], 4);
          y1 += __shfl_xor_sync(0xffffffffu, (lane & 4) ? z[2] : z[3], 4);
          float zz = (lane & 2) ? y1 : y0;
          zz += __shfl_xor_sync(0xffffffffu, (lane & 2) ? y0 : y1, 2);
          zz += __shfl_xor_sync(0xffffffffu, zz, 1);
          const float rho = 4.f * expf(zz > 40.f ? 40.f : zz);
          if ((lane & 1) == 0)
            asm volatile("st.relaxed.gpu.global.u32 [%0], %1;" ::"l"(g_gate + m * 128 + row + (lane & 4) + (lane & 2) * 4), "r"((__float_as_uint(rho) & ~1u) | par) : "memory");
        }
        if (lane == 0) TS(3, 0);
        mbar_wait(sb + OFF_GBAR, 0);
        asm volatile("st.shared.v2.u32 [%0], {%1,%2};" ::"r"(sb + OFF_DB + lane * 8), "r"(dk), "r"(bf2_add(bb, bb)) : "memory");
        uint32_t g0, g1, g2, g3;
        int tries = 0;
#pragma unroll 1
        do {
          asm volatile("ld.relaxed.gpu.global.v4.u32 {%0,%1,%2,%3}, [%4];" : "=r"(g0), "=r"(g1), "=r"(g2), "=r"(g3) : "l"(g_gate + m * 128 + lane * 4) : "memory");
        } while ((((g0 ^ par) | (g1 ^ par) | (g2 ^ par) | (g3 ^ par)) & 1) && ++tries < 200000);
        asm volatile("st.shared.v2.u32 [%0], {%1,%2};" ::"r"(sb + OFF_GS + lane * 8), "r"(pack_bf16(__uint_as_float(g0), __uint_as_float(g1))),
                     "r"(pack_bf16(__uint_as_float(g2), __uint_as_float(g3))) : "memory");
        mbar_arrive(sb + OFF_CBAR);
        if (lane == 0) TS(3, 4);
      }
    } else {
      asm volatile("barrier.cluster.wait.aligned;" ::: "memory");
      if (elect_one()) {
        TS(2, 1);
        const uint32_t t0 = clock();
#pragma unroll 1
        for (int u = 0; u < 8; u++) {
          if (u >= 1) while ((uint32_t)clock() - t0 < D0 + (u - 1) * D1) {}
          mbar_expect_tx(sb + OFF_XFULL + 8 * u, 16384);
          tma5d_mc(sb + OFF_X + ((u + xrot) & 7) * 16384 + rank * 8192, &maps.x, u * 64, 2 * m + rank, sb + OFF_XFULL + 8 * u);
          if (u < 6) {
            mbar_expect_tx(sb + OFF_FULL + 8 * u, 16384);
            tma2d(sb + OFF_RING + u * 16384, &maps.bre, u * 64, s * 64, sb + OFF_FULL + 8 * u);
            tma2d(sb + OFF_RING + u * 16384 + 8192, &maps.bim, u * 64, s * 64, sb + OFF_FULL + 8 * u);
          } else if (PF & 4) {
            asm volatile("cp.async.bulk.prefetch.tensor.2d.L2.global [%0, {%1,%2}];" ::"l"((m & 1) ? &maps.bim : &maps.bre), "r"(u * 64), "r"(s * 64) : "memory");
          }
        }
        TS(2, 5);
        int slot = 0; uint32_t ph = 0;
#pragma unroll 1
        for (int u = 6; u < 24; u++) {
          const uint32_t fb = sb + OFF_FULL + 8 * slot, dst = sb + OFF_RING + slot * 16384;
          mbar_wait(sb + OFF_EMPTY + 8 * slot, ph);
          TS2(0, u);
          if (u < 8) {
            mbar_expect_tx(fb, 16384);
            tma2d(dst, &maps.bre, u * 64, s * 64, fb);
            tma2d(dst + 8192, &maps.bim, u * 64, s * 64, fb);
          } else if (u < 16) {
            mbar_expect_tx(fb, 12288);
            tma3d(dst, &maps.w1b, 0, (u - 8) * 64, s * 7, fb);
          } else {
            mbar_expect_tx(fb, 16384);
            tma2d(dst, &maps.w1a, s * 224 + 96, ((u - xrot) & 7) * 64, fb);
            tma2d(dst + 8192, &maps.w1a, s * 224 + 160, ((u - xrot) & 7) * 64, fb);
          }
          if (++slot == NSLOT) { slot = 0; ph ^= 1; }
        }
#pragma unroll 1
        for (int j = 0; j < 3; j++) {
          const uint32_t fb = sb + OFF_FULL + 8 * j;
          mbar_wait(sb + OFF_EMPTY + 8 + 8 * j, 1);
          mbar_expect_tx(fb, j == 1 ? 32768 : 28672);
#pragma unroll
          for (int e = 0; e < 2; e++) {
            const int c = ((sp + 1) & 3) * 128 + ((rank ^ e ^ 1) << 6);
            const uint32_t dst = sb + OFF_X + stage_off(e);
            if (j == 1) {
              tma2d(dst + 14336, &maps.cre, s * 64, c, fb);
              tma2d(dst + 22528, &maps.cim, s * 64, c, fb);
            } else {
              tma2d(dst + j * 15360, &maps.w2, c, s * 224 + j * 56, fb);
            }
          }
        }
#pragma unroll 1
        for (int p = 2; p < 8; p++) {
          const int c = ((sp + 1 + (p >> 1)) & 3) * 128 + (((rank ^ p ^ 1) & 1) << 6);
          const uint32_t fb = sb + OFF_XFULL + 8 * p, dst = sb + OFF_X + stage_off(p);
          if (p != 3) mbar_wait(sb + OFF_EMPTY + (p == 2 ? 40 : (p - 4) * 8), p == 2);
          TS2(0, 32 + p);
          mbar_expect_tx(fb, 45056);
          tma2d(dst, &maps.w2, c, s * 224, fb);
          tma2d(dst + 14336, &maps.cre, s * 64, c, fb);
          tma2d(dst + 22528, &maps.cim, s * 64, c, fb);
          tma2d(dst + 30720, &maps.w2, c, s * 224 + 112, fb);
        }
        TS(2, 2);
      }
    }
  }
}

typedef CUresult (*EncFn)(CUtensorMap*, CUtensorMapDataType, cuuint32_t, void*, const cuuint64_t*, const cuuint64_t*, const cuuint32_t*,
                          const cuuint32_t*, CUtensorMapInterleave, CUtensorMapSwizzle, CUtensorMapL2promotion, CUtensorMapFloatOOBfill);

void encode(EncFn f, CUtensorMap* mp, const void* p, int rank, const cuuint64_t* dims, const cuuint64_t* strides, const cuuint32_t* box, CUtensorMapSwizzle sw) {
  cuuint32_t es[5] = {1, 1, 1, 1, 1};
  f(mp, CU_TENSOR_MAP_DATA_TYPE_BFLOAT16, rank, const_cast<void*>(p), dims, strides, box, es, CU_TENSOR_MAP_INTERLEAVE_NONE, sw,
    CU_TENSOR_MAP_L2_PROMOTION_L2_128B, CU_TENSOR_MAP_FLOAT_OOB_FILL_NONE);
}

}

extern "C" void kernel_launch(void* const* d_in, const int* in_sizes, int n_in, void* d_out, int out_size) {
  typedef const __nv_bfloat16* bp;
  bp x = (bp)d_in[0], lre = (bp)d_in[1], lim = (bp)d_in[2], bre = (bp)d_in[3], bim = (bp)d_in[4], cre = (bp)d_in[5], cim = (bp)d_in[6],
     ldt = (bp)d_in[7], dsk = (bp)d_in[8], w1 = (bp)d_in[10], b1 = (bp)d_in[11], w2 = (bp)d_in[12], b2 = (bp)d_in[13], gw = (bp)d_in[14];
  static EncFn enc = nullptr;
  if (!enc) {
    void* f = nullptr;
    cudaDriverEntryPointQueryResult qr;
    cudaGetDriverEntryPoint("cuTensorMapEncodeTiled", &f, cudaEnableDefault, &qr);
    enc = (EncFn)f;
    cudaFuncSetAttribute(fused_kernel, cudaFuncAttributeMaxDynamicSharedMemorySize, SMEM_BYTES);
  }
  Maps maps;
  {
    cuuint64_t d[5] = {DM, 2, 4, 8, SEQ / 64}, st[4] = {DM * 2, 16 * DM * 2, 2 * DM * 2, 64 * DM * 2};
    cuuint32_t bx[5] = {64, 2, 4, 8, 1};
    encode(enc, &maps.x, x, 5, d, st, bx, CU_TENSOR_MAP_SWIZZLE_128B);
  }
  {
    cuuint64_t d[2] = {DM, DM}, st[1] = {DM * 2};
    cuuint32_t bx[2] = {64, 64};
    encode(enc, &maps.bre, bre, 2, d, st, bx, CU_TENSOR_MAP_SWIZZLE_128B);
    encode(enc, &maps.bim, bim, 2, d, st, bx, CU_TENSOR_MAP_SWIZZLE_128B);
    encode(enc, &maps.cre, cre, 2, d, st, bx, CU_TENSOR_MAP_SWIZZLE_128B);
    encode(enc, &maps.cim, cim, 2, d, st, bx, CU_TENSOR_MAP_SWIZZLE_128B);
  }
  {
    cuuint64_t d[2] = {FF, DM}, st[1] = {FF * 2};
    cuuint32_t bx[2] = {64, 64};
    encode(enc, &maps.w1a, w1, 2, d, st, bx, CU_TENSOR_MAP_SWIZZLE_128B);
    cuuint64_t d3[3] = {32, DM, FF / 32}, st3[2] = {FF * 2, 64};
    cuuint32_t bx3[3] = {32, 64, 3};
    encode(enc, &maps.w1b, w1, 3, d3, st3, bx3, CU_TENSOR_MAP_SWIZZLE_64B);
  }
  {
    cuuint64_t d[2] = {DM, FF}, st[1] = {DM * 2};
    cuuint32_t bx[2] = {64, 112};
    encode(enc, &maps.w2, w2, 2, d, st, bx, CU_TENSOR_MAP_SWIZZLE_128B);
  }
  fused_kernel<<<128, 384, SMEM_BYTES>>>(lre, lim, ldt, dsk, b1, b2, gw, w1, w2, cre, cim, (float*)d_out, maps);
}
```

```cpp
#include <cuda_runtime.h>
#include <cuda_bf16.h>
#include <cuda.h>
#include <stdint.h>

#define MAP 1
#define D0 600
#define D1 500
#define PF 6
#define PFK 5
#define GELUP 0
#define EW 1
#define K1E 1
#define K2E 0
#define QS 1
#define K2G 4
#define FINP 6
#define A0 6
#define A1 8
#define E1L 0
#define TOK 1
#define TP 9
#define TW 0

namespace {

constexpr int SEQ = 2048, DM = 512, FF = 1792;
constexpr int NSLOT = 6;
constexpr uint32_t OFF_X = 0, OFF_RING = 131072, OFF_MISC = 229376;
constexpr uint32_t OFF_XFULL = OFF_MISC, OFF_FULL = OFF_XFULL + 64, OFF_RBAR = OFF_FULL + 48, OFF_EMPTY = OFF_RBAR + 16, OFF_KBAR = OFF_EMPTY + 48,
                   OFF_GBAR = OFF_KBAR + 16, OFF_LBAR = OFF_GBAR + 8, OFF_CBAR = OFF_LBAR + 8, OFF_EPOCH = OFF_CBAR + 8;
constexpr uint32_t OFF_LC = OFF_MISC + 256;
constexpr uint32_t OFF_GS = OFF_LC;
constexpr uint32_t OFF_DB = OFF_LC + 512;
constexpr uint32_t OFF_CARRY = OFF_LC + 1024;
constexpr uint32_t OFF_DBG = OFF_CARRY + 1024;
constexpr uint32_t SMEM_BYTES = OFF_DBG + 768;
static_assert(SMEM_BYTES <= 232448, "smem");

struct Maps { CUtensorMap x, bre, bim, w1b, w1a, w2, cre, cim; };
__host__ __device__ constexpr uint32_t stage_off(int p) { return 49152 + 45056 * (((p >> 1) & 1) + 2 * (p & 1)); }

__device__ uint4 g_part[16 * 8 * 3 * 1024];
__device__ float2 g_end[8 * 16 * 64];
__device__ unsigned g_gate[SEQ];
__device__ unsigned g_epoch[128];
#define TG(role) do {} while (0)
#define TS2(role, i) do {} while (0)
#define TS(role, i) do {} while (0)
#define TDUMP() do {} while (0)
#define TR(i) do {} while (0)
#define TRD() do {} while (0)

__device__ __forceinline__ void mbar_init(uint32_t bar, uint32_t cnt) { asm volatile("mbarrier.init.shared::cta.b64 [%0], %1;" ::"r"(bar), "r"(cnt)); }
__device__ __forceinline__ void mbar_expect_tx(uint32_t bar, uint32_t bytes) { asm volatile("mbarrier.arrive.expect_tx.shared::cta.b64 _, [%0], %1;" ::"r"(bar), "r"(bytes) : "memory"); }
__device__ __forceinline__ void mbar_arrive(uint32_t bar) { asm volatile("mbarrier.arrive.shared::cta.b64 _, [%0];" ::"r"(bar) : "memory"); }
__device__ __forceinline__ void mbar_arrive_cl(uint32_t cbar) { asm volatile("mbarrier.arrive.shared::cluster.b64 _, [%0];" ::"r"(cbar) : "memory"); }
__device__ __forceinline__ void mbar_wait(uint32_t bar, uint32_t parity) {
  asm volatile(
      "{\n.reg .pred p;\n.reg .u32 c;\n"
      "mbarrier.try_wait.parity.shared::cta.b64 p, [%0], %1;\n"
      "@p bra.uni LAB_DONE;\n"
      "mov.u32 c, 0;\n"
      "LAB_WAIT:\n"
      "mbarrier.try_wait.parity.shared::cta.b64 p, [%0], %1;\n"
      "@p bra.uni LAB_DONE;\n"
      "add.u32 c, c, 1;\nsetp.lt.u32 p, c, 200000;\n@p bra.uni LAB_WAIT;\n"
      "LAB_DONE:\n}" ::"r"(bar), "r"(parity) : "memory");
}
__device__ __forceinline__ void tma2d(uint32_t dst, const CUtensorMap* m, int c0, int c1, uint32_t bar) {
  asm volatile("cp.async.bulk.tensor.2d.shared::cluster.global.mbarrier::complete_tx::bytes [%0], [%1, {%3,%4}], [%2];"
               ::"r"(dst), "l"(m), "r"(bar), "r"(c0), "r"(c1) : "memory");
}
__device__ __forceinline__ void tma3d(uint32_t dst, const CUtensorMap* m, int c0, int c1, int c2, uint32_t bar) {
  asm volatile("cp.async.bulk.tensor.3d.shared::cluster.global.mbarrier::complete_tx::bytes [%0], [%1, {%3,%4,%5}], [%2];"
               ::"r"(dst), "l"(m), "r"(bar), "r"(c0), "r"(c1), "r"(c2) : "memory");
}
__device__ __forceinline__ void tma5d_mc(uint32_t dst, const CUtensorMap* m, int c0, int c4, uint32_t bar) {
  asm volatile("cp.async.bulk.tensor.5d.shared::cluster.global.mbarrier::complete_tx::bytes.multicast::cluster [%0], [%1, {%3,%5,%5,%5,%4}], [%2], %6;"
               ::"r"(dst), "l"(m), "r"(bar), "r"(c0), "r"(c4), "r"(0), "h"((uint16_t)3) : "memory");
}
__device__ __forceinline__ void l2_prefetch(const void* p, uint32_t bytes) { asm volatile("cp.async.bulk.prefetch.L2.global [%0], %1;" ::"l"(p), "r"(bytes) : "memory"); }
__device__ __forceinline__ bool elect_one() {
  uint32_t pred;
  asm volatile("{.reg .pred P; elect.sync _|P, 0xffffffff; selp.u32 %0, 1, 0, P;}" : "=r"(pred));
  return pred != 0;
}
__device__ __forceinline__ void wg_fence() { asm volatile("wgmma.fence.sync.aligned;" ::: "memory"); }
__device__ __forceinline__ void wg_commit() { asm volatile("wgmma.commit_group.sync.aligned;" ::: "memory"); }
template <int N> __device__ __forceinline__ void wg_wait() { asm volatile("wgmma.wait_group.sync.aligned %0;" ::"n"(N) : "memory"); }
__device__ __forceinline__ void pin(float& a) { asm volatile("" : "+f"(a)::"memory"); }
__device__ __forceinline__ void pin(uint32_t& a) { asm volatile("" : "+r"(a)::"memory"); }
template <int N> __device__ __forceinline__ void reg_fence(float (&d)[N]) {
#pragma unroll
  for (int i = 0; i < N; i++) pin(d[i]);
}
__device__ __forceinline__ void bar_sync(int id, int n) { asm volatile("bar.sync %0, %1;" ::"r"(id), "r"(n) : "memory"); }
__device__ __forceinline__ void bar_arrive(int id, int n) { asm volatile("bar.arrive %0, %1;" ::"r"(id), "r"(n) : "memory"); }
constexpr uint32_t DH128 = (1024 >> 4) | (1u << 30), DH64 = (512 >> 4) | (2u << 30);
__host__ __device__ constexpr uint32_t lbo(uint32_t bytes) { return (bytes >> 4) << 20; }
__device__ __forceinline__ uint32_t pack_bf16(float lo, float hi) { uint32_t r; asm("cvt.rn.bf16x2.f32 %0, %1, %2;" : "=r"(r) : "f"(hi), "f"(lo)); return r; }
__device__ __forceinline__ float bf_lo(uint32_t v) { return __uint_as_float(v << 16); }
__device__ __forceinline__ float bf_hi(uint32_t v) { return __uint_as_float(v & 0xffff0000u); }
__device__ __forceinline__ float bf_ld(const __nv_bfloat16* p) { return __bfloat162float(__ldg(p)); }
__device__ __forceinline__ uint32_t late16(uint32_t bar) {
  uint32_t r;
  asm volatile("{.reg .pred p; mbarrier.test_wait.parity.shared::cta.b64 p, [%1], 0; selp.u32 %0, 16, 0, p;}" : "=r"(r) : "r"(bar) : "memory");
  return r;
}
__device__ __forceinline__ float2 lds_f2(uint32_t a) { float2 v; asm volatile("ld.shared.v2.f32 {%0,%1}, [%2];" : "=f"(v.x), "=f"(v.y) : "r"(a)); return v; }
__device__ __forceinline__ uint32_t lds_h(uint32_t a) { uint32_t v; asm volatile("ld.shared.u16 %0, [%1];" : "=r"(v) : "r"(a)); return v; }
__device__ __forceinline__ uint32_t lds_u(uint32_t a) { uint32_t v; asm volatile("ld.shared.u32 %0, [%1];" : "=r"(v) : "r"(a)); return v; }
__device__ __forceinline__ uint4 lds_u4(uint32_t a) { uint4 v; asm volatile("ld.shared.v4.u32 {%0,%1,%2,%3}, [%4];" : "=r"(v.x), "=r"(v.y), "=r"(v.z), "=r"(v.w) : "r"(a)); return v; }
__device__ __forceinline__ void st_b128(uint4* p, uint32_t a, uint32_t b, uint32_t c, uint32_t d) {
  asm volatile("st.relaxed.gpu.global.v4.b32 [%0], {%1,%2,%3,%4};" ::"l"(p), "r"(a), "r"(b), "r"(c), "r"(d) : "memory");
}
__device__ __forceinline__ void ld_b128(const uint4* p, uint32_t& a, uint32_t& b, uint32_t& c, uint32_t& d) {
  asm volatile("{.reg .b64 l, h; .reg .b128 v; ld.relaxed.gpu.global.b128 v, [%4]; mov.b128 {l,h}, v; mov.b64 {%0,%1}, l; mov.b64 {%2,%3}, h;}"
               : "=r"(a), "=r"(b), "=r"(c), "=r"(d) : "l"(p) : "memory");
}
__device__ __forceinline__ float tanh_fast(float x) { float y; asm("tanh.approx.f32 %0, %1;" : "=f"(y) : "f"(x)); return y; }
__device__ __forceinline__ float gelu2(float v, float k0) {
  float p = fmaf(v * v, 0.0356774081363f, k0);
  return fmaf(v, tanh_fast(v * p), v);
}
__device__ __forceinline__ void sched_fence(uint32_t& ck) {
  asm volatile("{.reg .b32 c; mov.u32 c, %%clock; xor.b32 %0, %0, c;}" : "+r"(ck)::"memory");
}
__device__ __forceinline__ uint32_t bf2_mul(uint32_t a, uint32_t b) { uint32_t r; asm("mul.rn.bf16x2 %0, %1, %2;" : "=r"(r) : "r"(a), "r"(b)); return r; }
__device__ __forceinline__ uint32_t bf2_add(uint32_t a, uint32_t b) { uint32_t r; asm("add.rn.bf16x2 %0, %1, %2;" : "=r"(r) : "r"(a), "r"(b)); return r; }
__device__ __forceinline__ uint32_t bf2_fma(uint32_t a, uint32_t b, uint32_t c) { uint32_t r; asm("fma.rn.bf16x2 %0, %1, %2, %3;" : "=r"(r) : "r"(a), "r"(b), "r"(c)); return r; }
constexpr uint32_t GELU_K = 0x3f4c422au;
__device__ __forceinline__ uint32_t gelu2_pair(float a, float b, uint32_t k) {
  return pack_bf16(gelu2(a, __uint_as_float(k)), gelu2(b, __uint_as_float(k)));
}
struct cplx { float re, im; };
__device__ __forceinline__ cplx cmul(cplx a, cplx b) { return {fmaf(a.re, b.re, -a.im * b.im), fmaf(a.re, b.im, a.im * b.re)}; }
__device__ __forceinline__ cplx cfma(cplx a, cplx b, cplx c) {
  return {fmaf(a.re, b.re, fmaf(-a.im, b.im, c.re)), fmaf(a.re, b.im, fmaf(a.im, b.re, c.im))};
}
__device__ __forceinline__ cplx make_lam(float lre, float lim, float ldt) {
  float dt = __bfloat162float(__float2bfloat16_rn(expf(ldt)));
  float mag = expf(dt * lre), sn, cs;
  sincospif(dt * lim * 0.31830988618379067f, &sn, &cs);
  return {mag * cs, mag * sn};
}

template<int TA,int TB,uint32_t AH,uint32_t BH> __device__ __forceinline__ void wgmma_n64_ss(float (&d)[32], uint32_t al, uint32_t ao, uint32_t bl, uint32_t bo, int scale_d){
  asm volatile("{.reg .pred p; .reg .b32 t, v; .reg .b64 da, db; setp.ne.b32 p, %36, 0; add.u32 t, %32, %33; mov.b64 da, {t, %39}; add.u32 v, %34, %35; mov.b64 db, {v, %40};\n"
   "wgmma.mma_async.sync.aligned.m64n64k16.f32.bf16.bf16 {%0,%1,%2,%3,%4,%5,%6,%7,%8,%9,%10,%11,%12,%13,%14,%15,%16,%17,%18,%19,%20,%21,%22,%23,%24,%25,%26,%27,%28,%29,%30,%31}, da, db, p, 1, 1, %37, %38;}"
   : "+f"(d[0]),"+f"(d[1]),"+f"(d[2]),"+f"(d[3]),"+f"(d[4]),"+f"(d[5]),"+f"(d[6]),"+f"(d[7]),"+f"(d[8]),"+f"(d[9]),"+f"(d[10]),"+f"(d[11]),"+f"(d[12]),"+f"(d[13]),"+f"(d[14]),"+f"(d[15]),"+f"(d[16]),"+f"(d[17]),"+f"(d[18]),"+f"(d[19]),"+f"(d[20]),"+f"(d[21]),"+f"(d[22]),"+f"(d[23]),"+f"(d[24]),"+f"(d[25]),"+f"(d[26]),"+f"(d[27]),"+f"(d[28]),"+f"(d[29]),"+f"(d[30]),"+f"(d[31])
   : "r"(al),"r"(ao >> 4),"r"(bl),"r"(bo >> 4),"r"(scale_d),"n"(TA),"n"(TB),"n"(AH),"n"(BH));
}
template<int TB,uint32_t BH> __device__ __forceinline__ void wgmma_n64_rs(float (&d)[32], uint32_t a0,uint32_t a1,uint32_t a2,uint32_t a3, uint32_t bl, uint32_t bo, int scale_d){
  asm volatile("{.reg .pred p; .reg .b32 t; .reg .b64 db; setp.ne.b32 p, %38, 0; add.u32 t, %36, %37; mov.b64 db, {t, %40};\n"
   "wgmma.mma_async.sync.aligned.m64n64k16.f32.bf16.bf16 {%0,%1,%2,%3,%4,%5,%6,%7,%8,%9,%10,%11,%12,%13,%14,%15,%16,%17,%18,%19,%20,%21,%22,%23,%24,%25,%26,%27,%28,%29,%30,%31}, {%32,%33,%34,%35}, db, p, 1, 1, %39;}"
   : "+f"(d[0]),"+f"(d[1]),"+f"(d[2]),"+f"(d[3]),"+f"(d[4]),"+f"(d[5]),"+f"(d[6]),"+f"(d[7]),"+f"(d[8]),"+f"(d[9]),"+f"(d[10]),"+f"(d[11]),"+f"(d[12]),"+f"(d[13]),"+f"(d[14]),"+f"(d[15]),"+f"(d[16]),"+f"(d[17]),"+f"(d[18]),"+f"(d[19]),"+f"(d[20]),"+f"(d[21]),"+f"(d[22]),"+f"(d[23]),"+f"(d[24]),"+f"(d[25]),"+f"(d[26]),"+f"(d[27]),"+f"(d[28]),"+f"(d[29]),"+f"(d[30]),"+f"(d[31])
   : "r"(a0),"r"(a1),"r"(a2),"r"(a3),"r"(bl),"r"(bo >> 4),"r"(scale_d),"n"(TB),"n"(BH));
}
template<int TA,int TB,uint32_t AH,uint32_t BH> __device__ __forceinline__ void wgmma_n96_ss(float (&d)[48], uint32_t al, uint32_t ao, uint32_t bl, uint32_t bo, int scale_d){
  asm volatile("{.reg .pred p; .reg .b32 t, v; .reg .b64 da, db; setp.ne.b32 p, %52, 0; add.u32 t, %48, %49; mov.b64 da, {t, %55}; add.u32 v, %50, %51; mov.b64 db, {v, %56};\n"
   "wgmma.mma_async.sync.aligned.m64n96k16.f32.bf16.bf16 {%0,%1,%2,%3,%4,%5,%6,%7,%8,%9,%10,%11,%12,%13,%14,%15,%16,%17,%18,%19,%20,%21,%22,%23,%24,%25,%26,%27,%28,%29,%30,%31,%32,%33,%34,%35,%36,%37,%38,%39,%40,%41,%42,%43,%44,%45,%46,%47}, da, db, p, 1, 1, %53, %54;}"
   : "+f"(d[0]),"+f"(d[1]),"+f"(d[2]),"+f"(d[3]),"+f"(d[4]),"+f"(d[5]),"+f"(d[6]),"+f"(d[7]),"+f"(d[8]),"+f"(d[9]),"+f"(d[10]),"+f"(d[11]),"+f"(d[12]),"+f"(d[13]),"+f"(d[14]),"+f"(d[15]),"+f"(d[16]),"+f"(d[17]),"+f"(d[18]),"+f"(d[19]),"+f"(d[20]),"+f"(d[21]),"+f"(d[22]),"+f"(d[23]),"+f"(d[24]),"+f"(d[25]),"+f"(d[26]),"+f"(d[27]),"+f"(d[28]),"+f"(d[29]),"+f"(d[30]),"+f"(d[31]),"+f"(d[32]),"+f"(d[33]),"+f"(d[34]),"+f"(d[35]),"+f"(d[36]),"+f"(d[37]),"+f"(d[38]),"+f"(d[39]),"+f"(d[40]),"+f"(d[41]),"+f"(d[42]),"+f"(d[43]),"+f"(d[44]),"+f"(d[45]),"+f"(d[46]),"+f"(d[47])
   : "r"(al),"r"(ao >> 4),"r"(bl),"r"(bo >> 4),"r"(scale_d),"n"(TA),"n"(TB),"n"(AH),"n"(BH));
}
template<int TA,int TB,uint32_t AH,uint32_t BH> __device__ __forceinline__ void wgmma_n128_ss(float (&d)[64], uint32_t al, uint32_t ao, uint32_t bl, uint32_t bo, int scale_d){
  asm volatile("{.reg .pred p; .reg .b32 t, v; .reg .b64 da, db; setp.ne.b32 p, %68, 0; add.u32 t, %64, %65; mov.b64 da, {t, %71}; add.u32 v, %66, %67; mov.b64 db, {v, %72};\n"
   "wgmma.mma_async.sync.aligned.m64n128k16.f32.bf16.bf16 {%0,%1,%2,%3,%4,%5,%6,%7,%8,%9,%10,%11,%12,%13,%14,%15,%16,%17,%18,%19,%20,%21,%22,%23,%24,%25,%26,%27,%28,%29,%30,%31,%32,%33,%34,%35,%36,%37,%38,%39,%40,%41,%42,%43,%44,%45,%46,%47,%48,%49,%50,%51,%52,%53,%54,%55,%56,%57,%58,%59,%60,%61,%62,%63}, da, db, p, 1, 1, %69, %70;}"
   : "+f"(d[0]),"+f"(d[1]),"+f"(d[2]),"+f"(d[3]),"+f"(d[4]),"+f"(d[5]),"+f"(d[6]),"+f"(d[7]),"+f"(d[8]),"+f"(d[9]),"+f"(d[10]),"+f"(d[11]),"+f"(d[12]),"+f"(d[13]),"+f"(d[14]),"+f"(d[15]),"+f"(d[16]),"+f"(d[17]),"+f"(d[18]),"+f"(d[19]),"+f"(d[20]),"+f"(d[21]),"+f"(d[22]),"+f"(d[23]),"+f"(d[24]),"+f"(d[25]),"+f"(d[26]),"+f"(d[27]),"+f"(d[28]),"+f"(d[29]),"+f"(d[30]),"+f"(d[31]),"+f"(d[32]),"+f"(d[33]),"+f"(d[34]),"+f"(d[35]),"+f"(d[36]),"+f"(d[37]),"+f"(d[38]),"+f"(d[39]),"+f"(d[40]),"+f"(d[41]),"+f"(d[42]),"+f"(d[43]),"+f"(d[44]),"+f"(d[45]),"+f"(d[46]),"+f"(d[47]),"+f"(d[48]),"+f"(d[49]),"+f"(d[50]),"+f"(d[51]),"+f"(d[52]),"+f"(d[53]),"+f"(d[54]),"+f"(d[55]),"+f"(d[56]),"+f"(d[57]),"+f"(d[58]),"+f"(d[59]),"+f"(d[60]),"+f"(d[61]),"+f"(d[62]),"+f"(d[63])
   : "r"(al),"r"(ao >> 4),"r"(bl),"r"(bo >> 4),"r"(scale_d),"n"(TA),"n"(TB),"n"(AH),"n"(BH));
}

__global__ void __cluster_dims__(2, 1, 1) __launch_bounds__(384, 1)
fused_kernel(const __nv_bfloat16* __restrict__ lam_re, const __nv_bfloat16* __restrict__ lam_im, const __nv_bfloat16* __restrict__ log_dt,
             const __nv_bfloat16* __restrict__ dskip, const __nv_bfloat16* __restrict__ b1, const __nv_bfloat16* __restrict__ b2,
             const __nv_bfloat16* __restrict__ gate_w, const __nv_bfloat16* __restrict__ pf_w1, const __nv_bfloat16* __restrict__ pf_w2,
             const __nv_bfloat16* __restrict__ pf_cre, const __nv_bfloat16* __restrict__ pf_cim, float* __restrict__ out,
             const __grid_constant__ Maps maps) {
  extern __shared__ __align__(1024) unsigned char smem_raw[];
  const uint32_t sb = (uint32_t)__cvta_generic_to_shared(smem_raw);
  const int b = blockIdx.x;
  const int rank = b & 1, cl = b >> 1;
  const int sp = (cl & 1) | ((cl >> 2) & 2), m = ((cl >> 1) & 3) | ((cl >> 4) << 2);
  const int s = sp * 2 + rank;
  const int warp = __shfl_sync(0xffffffffu, (int)(threadIdx.x >> 5), 0);
  const int lane = threadIdx.x & 31;
  const int xrot = 9 - 2 * sp;

  if (elect_one()) {
    if (warp == 8) TS(2, 0);
    if (warp < 3) {
      asm volatile("prefetch.tensormap [%0];" ::"l"(&maps.x + warp) : "memory");
      mbar_init(sb + OFF_GBAR + 8 * warp, warp < 2 ? 64 : 96);
    }
    const uint32_t c = warp < 8 ? 1 : warp < 11 ? 8 : 4;
    mbar_init(sb + OFF_XFULL + 16 * warp, c);
    mbar_init(sb + OFF_XFULL + 16 * warp + 8, c);
    asm volatile("fence.mbarrier_init.release.cluster;" ::: "memory");
  }
  __syncwarp();
  asm volatile("barrier.cluster.arrive.relaxed.aligned;" ::: "memory");

  if (warp < 8) {
    const int wg = warp >> 2, w = warp & 3, q = lane & 3, gr = lane >> 2;
    uint32_t bv[28];
#pragma unroll
    for (int j = 0; j < 28; j++) bv[j] = __ldg(reinterpret_cast<const uint32_t*>(b1 + s * 224 + j * 8) + q);
    asm volatile("setmaxnreg.inc.sync.aligned.u32 232;");
    asm volatile("barrier.cluster.wait.aligned;" ::: "memory");
    TS(wg, 0);
    auto release = [&](int slot) { if (lane == 0) mbar_arrive(sb + OFF_EMPTY + 8 * slot); };
    const uint32_t xw = sb + OFF_X + wg * 8192, fullb = sb + OFF_FULL;
    const uint32_t dxw = (xw & 0x3FFFF) >> 4, dring = ((sb + OFF_RING) & 0x3FFFF) >> 4;

    float ure[32], uim[32], aa[48], ab[64];
    cplx lam[2], coef[2], l16[2], l32[2], lq[2], pre[2], e[2];
    uint32_t sh16, mhi, ck = 0;

#pragma unroll
    for (int kb = 0; kb < 8; kb++) {
      const int slot = kb % NSLOT;
      mbar_wait(sb + OFF_XFULL + 8 * kb, 0);
      if (kb == 0) TS(wg, 18);
      mbar_wait(fullb + 8 * slot, (kb / NSLOT) & 1);
      TS2(2, kb);
      if (kb == 0) TS(wg, 1);
      wg_fence();
      const uint32_t dxa = dxw + ((kb + xrot) & 7) * 1024;
#pragma unroll
      for (int kk = 0; kk < 4; kk++) {
        wgmma_n64_ss<0, 0, DH128, DH128>(ure, dring, slot * 16384 + kk * 32, dxa, kk * 32, (kb | kk) != 0);
        wgmma_n64_ss<0, 0, DH128, DH128>(uim, dring, slot * 16384 + 8192 + kk * 32, dxa, kk * 32, (kb | kk) != 0);
      }
      wg_commit();
      if (kb > 0) { wg_wait<1>(); release((kb - 1) % NSLOT); }
      if (kb == 1) { sh16 = late16(sb + OFF_XFULL); mhi = 0xffffffffu << sh16; }
      if (kb == 1 || (kb >= 3 && kb < 6)) {
#pragma unroll
        for (int j = 0; j < 28; j++) if (j / 7 == (kb == 1 ? 0 : kb - 2)) {
          pin(bv[j]);
          float* d = j < 12 ? aa + 4 * j : ab + 4 * (j - 12);
          d[0] = d[2] = __uint_as_float(bv[j] << sh16); d[1] = d[3] = __uint_as_float(bv[j] & mhi);
          pin(d[0]); pin(d[1]); pin(d[2]); pin(d[3]);
        }
      }
      if (kb == 5) {
        mbar_wait(sb + OFF_LBAR, 0);
#pragma unroll
        for (int h = 0; h < 2; h++) {
          const uint4 v = lds_u4(sb + OFF_LC + (w * 16 + gr + 8 * h) * 16);
          lam[h] = cplx{__uint_as_float(v.x), __uint_as_float(v.y)};
          coef[h] = cplx{__uint_as_float(v.z), __uint_as_float(v.w)};
        }
      }
      if (kb == 6) {
#pragma unroll
        for (int h = 0; h < 2; h++) {
          pin(lam[h].re); pin(lam[h].im);
          cplx t = cmul(lam[h], lam[h]); t = cmul(t, t); t = cmul(t, t);
          l16[h] = cmul(t, t);
          pin(l16[h].re); pin(l16[h].im);
        }
      }
      if (kb == 7) {
#pragma unroll
        for (int h = 0; h < 2; h++) {
          pin(l16[h].re); pin(l16[h].im);
          l32[h] = cmul(l16[h], l16[h]);
          const cplx a = (q & 1) ? l16[h] : cplx{1.f, 0.f}, c = (q & 2) ? l32[h] : cplx{1.f, 0.f};
          lq[h] = cmul(cmul(a, c), coef[h]);
          pin(lq[h].re); pin(lq[h].im);
        }
      }
    }
    TS(wg, 2);
    auto scale_u = [&](int i0, int i1) {
#pragma unroll
      for (int i = 0; i < 32; i++) if (i >= i0 && i < i1) {
        pin(ure[i]); pin(uim[i]);
        const cplx v = cmul(coef[(i >> 1) & 1], cplx{ure[i], uim[i]});
        ure[i] = v.re; uim[i] = v.im;
        pin(ure[i]); pin(uim[i]);
      }
    };
#pragma unroll
    for (int kb = 0; kb < 8; kb++) {
      const int u = 8 + kb, slot = u % NSLOT;
      mbar_wait(fullb + 8 * slot, (u / NSLOT) & 1);
      wg_fence();
      const uint32_t dxa = dxw + ((kb + xrot) & 7) * 1024;
#pragma unroll
      for (int kk = 0; kk < 4; kk++)
        wgmma_n96_ss<0, 1, DH128, DH64>(aa, dxa, kk * 32, dring, slot * 16384 + kk * 1024 + lbo(4096), 1);
      wg_commit();
      wg_wait<1>();
      release((u - 1) % NSLOT);
      if (kb == 0) {
        reg_fence(ure); reg_fence(uim);
#pragma unroll
        for (int h = 0; h < 2; h++) e[h] = cplx{ure[2 * h], uim[2 * h]};
      }
      if (TOK ? kb < 3 : (kb == 0 || kb == 2 || kb == 3)) {
        const int ch = TOK ? kb : kb ? kb - 1 : 0;
        if (kb) sched_fence(ck);
#pragma unroll
        for (int t = 1 + 5 * ch; t < 6 + 5 * ch; t++)
#pragma unroll
          for (int h = 0; h < 2; h++) { const int i = 4 * (t >> 1) + 2 * h + (t & 1); e[h] = cfma(lam[h], e[h], cplx{ure[i], uim[i]}); }
#pragma unroll
        for (int h = 0; h < 2; h++) { pin(e[h].re); pin(e[h].im); }
      } else if (kb == (TOK ? 3 : 4)) {
        sched_fence(ck);
#pragma unroll
        for (int h = 0; h < 2; h++) {
          cplx y = {__shfl_up_sync(0xffffffffu, e[h].re, 1, 4), __shfl_up_sync(0xffffffffu, e[h].im, 1, 4)};
          if (q >= 1) e[h] = cfma(l16[h], y, e[h]);
          y = cplx{__shfl_up_sync(0xffffffffu, e[h].re, 2, 4), __shfl_up_sync(0xffffffffu, e[h].im, 2, 4)};
          if (q >= 2) e[h] = cfma(l32[h], y, e[h]);
        }
        if (q == 3) {
#pragma unroll
          for (int h = 0; h < 2; h++)
            asm volatile("st.shared.v2.f32 [%0], {%1,%2};" ::"r"(sb + OFF_CARRY + wg * 512 + (w * 16 + gr + 8 * h) * 8), "f"(e[h].re), "f"(e[h].im) : "memory");
          mbar_arrive(sb + OFF_GBAR);
        }
#pragma unroll
        for (int h = 0; h < 2; h++) {
          const cplx y = {__shfl_up_sync(0xffffffffu, e[h].re, 1, 4), __shfl_up_sync(0xffffffffu, e[h].im, 1, 4)};
          pre[h] = (q >= 1) ? cmul(coef[h], y) : cplx{0.f, 0.f};
          pin(pre[h].re); pin(pre[h].im);
        }
        TS(wg, 3);
      } else if (TOK) {
        sched_fence(ck);
        scale_u((kb - 4) * 8, (kb - 3) * 8);
      } else if (kb > 4) {
        scale_u(kb == 5 ? 0 : kb == 6 ? 4 : 12, kb == 5 ? 4 : kb == 6 ? 12 : 20);
      }
    }
    TS(wg, 4);
    uint32_t H[56], hf[32];
    cplx hst[2];
    const uint32_t hst_addr = xw + (w * 16 + (lane & 15)) * 128 + (((lane >> 4) ^ (lane & 7)) << 4);
    const uint32_t him = (2 - rank) * 16384;
    uint32_t peer;
    asm volatile("mapa.shared::cluster.u32 %0, %1, %2;" : "=r"(peer) : "r"(sb), "r"(rank ^ 1));
    auto credit = [&]() { if (lane == 0) mbar_arrive_cl(peer + OFF_KBAR + wg * 8); };
#pragma unroll
    for (int kb = 0; kb < 8; kb++) {
      const int u = 16 + kb, slot = u % NSLOT;
      mbar_wait(fullb + 8 * slot, (u / NSLOT) & 1);
      wg_fence();
#pragma unroll
      for (int kk = 0; kk < 4; kk++)
        wgmma_n128_ss<0, 1, DH128, DH128>(ab, dxw, kb * 16384 + kk * 32, dring, slot * 16384 + kk * 2048 + lbo(8192), 1);
      wg_commit();
      wg_wait<1>();
      release((u - 1) % NSLOT);
      if (!TOK && kb == 0) scale_u(20, 32);
      if (TOK ? kb < 4 : (kb < 5 && kb != 1)) {
        const int ch = TOK ? kb : kb ? kb - 1 : 0;
        sched_fence(ck);
        const uint32_t gk = GELU_K;
#pragma unroll
        for (int i = ch * 6; i < ch * 6 + 6; i++) {
          pin(aa[2 * i]); pin(aa[2 * i + 1]);
          H[i] = gelu2_pair(aa[2 * i], aa[2 * i + 1], gk);
          pin(H[i]);
        }
      }
      if (kb >= 4) {
        if (kb == 4) {
          TS(wg, 5);
          mbar_wait(sb + OFF_CBAR, 0);
          TS(wg, 6);
#pragma unroll
          for (int h = 0; h < 2; h++) {
            const float2 c = lds_f2(sb + OFF_CARRY + wg * 512 + (w * 16 + gr + 8 * h) * 8);
            hst[h] = cfma(lq[h], cplx{c.x, c.y}, pre[h]);
          }
        }
        if (kb > 4) sched_fence(ck);
        const int j0 = (kb - 4) * 2;
        uint32_t rr[4], ri[4];
#pragma unroll
        for (int jj = 0; jj < 2; jj++) {
          const int j = j0 + jj;
          const uint32_t g2 = lds_u(sb + OFF_GS + (wg * 64 + j * 8 + q * 2) * 2);
#pragma unroll
          for (int h = 0; h < 2; h++) {
            const int i = 4 * j + 2 * h;
            const cplx h0 = cfma(lam[h], hst[h], cplx{ure[i], uim[i]});
            hst[h] = cfma(lam[h], h0, cplx{ure[i + 1], uim[i + 1]});
            rr[jj * 2 + h] = bf2_mul(pack_bf16(h0.re, hst[h].re), g2);
            ri[jj * 2 + h] = bf2_mul(pack_bf16(h0.im, hst[h].im), g2 ^ 0x80008000u);
          }
        }
        const uint32_t a = hst_addr ^ (j0 << 4);
        asm volatile("stmatrix.sync.aligned.m8n8.x4.shared.b16 [%0], {%1,%2,%3,%4};" ::"r"(a), "r"(rr[0]), "r"(rr[1]), "r"(rr[2]), "r"(rr[3]) : "memory");
        asm volatile("stmatrix.sync.aligned.m8n8.x4.shared.b16 [%0], {%1,%2,%3,%4};" ::"r"(a + him), "r"(ri[0]), "r"(ri[1]), "r"(ri[2]), "r"(ri[3]) : "memory");
      }
    }
    TS(wg, 7);

    uint4* const psend = g_part + (size_t)(m * 8 + rank) * 3072 + warp * 128 + lane;
    const uint4* const precv = g_part + (size_t)(m * 8 + s) * 3072 + warp * 128 + lane;
    const uint32_t pbuf = OFF_X + warp * 2048 + lane * 16;
    const uint32_t dx0 = ((sb + OFF_X) & 0x3FFFF) >> 4;
    float o[32], fin[32], rho[2];
    uint32_t tr[8];
    uint32_t r0[16], pt[16], sum[16], tag;
    auto recv_issue = [&](uint32_t (&r)[16], int k) {
#pragma unroll
      for (int i = 0; i < 4; i++) ld_b128(precv + k * 1024 + i * 32, r[4 * i], r[4 * i + 1], r[4 * i + 2], r[4 * i + 3]);
    };
    auto stale = [&](uint32_t (&r)[16]) {
      uint32_t t0, t1, r_;
      asm("lop3.b32 %0, %1, %2, %3, 0x7e;" : "=r"(t0) : "r"(r[0]), "r"(r[4]), "r"(tag));
      asm("lop3.b32 %0, %1, %2, %3, 0x7e;" : "=r"(t1) : "r"(r[8]), "r"(r[12]), "r"(tag));
      asm volatile("{.reg .pred p; .reg .b32 t; lop3.b32 t, %1, %2, 1, 0xa8; setp.ne.u32 p, t, 0; vote.sync.any.pred p, p, 0xffffffff; selp.u32 %0, 1, 0, p;}" : "=r"(r_) : "r"(t0), "r"(t1));
      return r_ != 0;
    };
    auto recv_check = [&](uint32_t (&r)[16], int k) {
      if (__builtin_expect(stale(r), 0)) {
        int tries = 0;
#pragma unroll 1
        do { recv_issue(r, k); } while (stale(r) && ++tries < 200000);
      }
    };
    auto gelu_b = [&](int i0, int i1) {
      sched_fence(ck);
        const uint32_t gk = GELU_K;
#pragma unroll
      for (int i = i0; i < i1; i++) {
        pin(ab[2 * i]); pin(ab[2 * i + 1]);
        H[24 + i] = gelu2_pair(ab[2 * i], ab[2 * i + 1], gk);
        pin(H[24 + i]);
      }
    };
    auto step = [&](float (&d)[32], int p, int k, int acc) {
      const uint32_t wo = stage_off(p);
      if (k >= 6 && k < 14) {
        const int kk = k - 6;
        wgmma_n64_rs<0, DH128>(d, hf[4 * kk], hf[4 * kk + 1], hf[4 * kk + 2], hf[4 * kk + 3], dx0, wo + 14336 + (kk >> 2) * 8192 + (kk & 3) * 32, 1);
      } else {
        const int kk = k < 6 ? k : k - 8;
        wgmma_n64_rs<1, DH128>(d, H[4 * kk], H[4 * kk + 1], H[4 * kk + 2], H[4 * kk + 3], dx0, wo + (kk / 7) * 30720 + (kk % 7) * 2048, k != 0 || acc);
      }
    };
    auto mma = [&](float (&d)[32], int p, int k0, int k1, int acc) {
      wg_fence();
#pragma unroll
      for (int k = k0; k < k1; k++) step(d, p, k, acc);
      wg_commit();
    };
    auto mma2 = [&](int k0, int k1) {
      wg_fence();
#pragma unroll
      for (int k = k0; k < k1; k++) { step(o, 0, k, 0); step(fin, 1, k, 0); }
      wg_commit();
    };
    auto send_peer = [&]() {
#pragma unroll
      for (int i = 0; i < 4; i++)
        asm volatile("st.async.shared::cluster.mbarrier::complete_tx::bytes.v4.b32 [%0], {%1,%2,%3,%4}, [%5];" ::"r"(peer + pbuf + i * 512),
                     "r"(pack_bf16(o[8 * i], o[8 * i + 1])), "r"(pack_bf16(o[8 * i + 2], o[8 * i + 3])), "r"(pack_bf16(o[8 * i + 4], o[8 * i + 5])),
                     "r"(pack_bf16(o[8 * i + 6], o[8 * i + 7])), "r"(peer + OFF_RBAR + wg * 8) : "memory");
    };
    auto recv_peer = [&](int k) {
      mbar_wait(sb + OFF_RBAR + wg * 8, k & 1);
#pragma unroll
      for (int i = 0; i < 4; i++) { const uint4 v = lds_u4(sb + pbuf + i * 512); pt[4 * i] = v.x; pt[4 * i + 1] = v.y; pt[4 * i + 2] = v.z; pt[4 * i + 3] = v.w; }
    };
    auto send_owner = [&](float (&d)[32], int k) {
#pragma unroll
      for (int i = 0; i < 4; i++) {
#pragma unroll
        for (int c = 4 * i; c < 4 * i + 4; c++) pt[c] = bf2_add(pt[c], pack_bf16(d[2 * c], d[2 * c + 1]));
        asm("lop3.b32 %0, %0, 1, %1, 0xb8;" : "+r"(pt[4 * i]) : "r"(tag));
        st_b128(psend + (((sp + 1 + k) & 3) * 6 + k) * 1024 + i * 32, pt[4 * i], pt[4 * i + 1], pt[4 * i + 2], pt[4 * i + 3]);
      }
      __syncwarp();
      credit();
    };
    auto arm = [&]() { if ((threadIdx.x & 127) == 0) mbar_expect_tx(sb + OFF_RBAR + wg * 8, 8192); };
    auto hand = [&](int pos) { if ((A0 == pos && wg == 0) || (A1 == pos && wg == 1)) bar_arrive(4 - wg, 256); };
    mbar_wait(fullb, 0);
    mma2(0, 3);
    bar_sync(1 + wg, 128);
    {
      const uint32_t ha = xw + ((lane >> 4) * 8 + (lane & 7)) * 128 + (((2 * w + ((lane >> 3) & 1)) ^ (lane & 7)) << 4);
#pragma unroll
      for (int kk = 0; kk < 8; kk++)
        asm volatile("ldmatrix.sync.aligned.m8n8.x4.trans.shared.b16 {%0,%1,%2,%3}, [%4];" : "=r"(hf[4 * kk]), "=r"(hf[4 * kk + 1]), "=r"(hf[4 * kk + 2]), "=r"(hf[4 * kk + 3])
                     : "r"(ha + (kk >> 2) * him + (kk & 3) * 2048) : "memory");
    }
    tag = lds_u(sb + OFF_EPOCH);
    arm();
    wg_wait<1>(); release(5);
    mbar_wait(fullb + 8, 0);
    if (A0 && wg == 1) bar_sync(4, 256);
    mma2(3, 6);   gelu_b(0, 4); hand(1);
    mma2(6, 8);   credit(); gelu_b(4, 8); hand(2);
    mma2(8, 11);  gelu_b(8, 12); hand(3);
    mma2(11, 13); gelu_b(12, 16); hand(4);
    mma2(13, 15); gelu_b(16, 20); hand(5);
    mbar_wait(fullb + 16, 0);
    mma2(15, 17); gelu_b(20, 24); hand(6);
    mma2(17, 19); gelu_b(24, 28); hand(7);
    mma2(19, 21); gelu_b(28, 32); hand(8);
    mma2(21, 22);
    TS(wg, 9);
    if (TOK) asm volatile("st.shared.u32 [%0], %1;" ::"r"(sb + OFF_EPOCH + 4), "r"(ck) : "memory");
    mbar_wait(sb + OFF_KBAR + wg * 8, 0);
    mbar_wait(sb + OFF_XFULL + 16, 1);
    wg_wait<0>();
    release(0); release(1);
    reg_fence(o); reg_fence(fin);
    send_peer();
    if (!E1L) { recv_peer(0); send_owner(fin, 0); }
#pragma unroll
    for (int p = 2; p < 8; p++) {
      TR(0);
      if (p & 1) mbar_wait(sb + OFF_XFULL + 8 * p, 1);
      TR(1);
      bar_sync(3 + wg, 256);
      if (p < 7) mma(o, p, 0, 22, 0); else mma(fin, p, 0, 22, 1);
      if (p < 7 || wg == 0) bar_arrive(4 - wg, 256);
      TR(2);
      if (p != TP) TS(wg, 8 + p);
      if ((p & 1) == 0) {
        if (E1L && p == 2) { recv_peer(0); send_owner(fin, 0); }
        arm();
        if (p == 6) {
          tag = lds_u(sb + OFF_EPOCH);
          recv_check(sum, 0); recv_check(r0, 1);
#pragma unroll
          for (int i = 0; i < 16; i++) sum[i] = bf2_add(sum[i], r0[i]);
        }
        TR(3);
        mbar_wait(sb + OFF_KBAR + wg * 8, (p >> 1) & 1);
        TR(4);
      } else {
        if (p == 7) { tag = lds_u(sb + OFF_EPOCH); mbar_wait(sb + OFF_EMPTY + 32, 0); }
        if (p < 7) mbar_wait(sb + OFF_XFULL + 8 * (p + 1), 1);
        TR(3);
        recv_peer(p >> 1);
        TR(4);
        if (p == 7) {
          recv_check(r0, 2);
#pragma unroll
          for (int i = 0; i < 16; i++) sum[i] = bf2_add(sum[i], bf2_add(r0[i], pt[i]));
        }
      }
      if (p == FINP) {
        mbar_wait(sb + OFF_LBAR, 1);
#pragma unroll
        for (int j = 0; j < 8; j++) {
          const uint4 v = lds_u4(sb + pbuf + 16384 + (j >> 2) * 16384 + (j & 3) * 512);
          fin[4 * j] = __uint_as_float(v.x); fin[4 * j + 1] = __uint_as_float(v.y); fin[4 * j + 2] = __uint_as_float(v.z); fin[4 * j + 3] = __uint_as_float(v.w);
        }
      }
      TR(5);
      wg_wait<0>();
      TR(6);
      if (p < 5) release(p);
      if (p < 7) reg_fence(o); else reg_fence(fin);
      if ((p & 1) == 0) {
        if (p == 6) recv_issue(r0, 2);
        send_peer();
        if (p == 4) {
          recv_issue(sum, 0);
          if (K1E) recv_issue(r0, 1);
        }
      } else if (p < 7) {
        send_owner(o, p >> 1);
        if (!K1E && p == 5) recv_issue(r0, 1);
      }
      if (p == 2) {
#pragma unroll
        for (int h = 0; h < 2; h++) { rho[h] = __fdividef(2.f, 4.f + bf_lo(lds_h(sb + OFF_GS + (wg * 64 + w * 16 + gr + 8 * h) * 2))); pin(rho[h]); }
      }
      TR(7);
    }
    {
      TS(wg, 16);
      const uint32_t tb = sb + OFF_X + stage_off(0) + warp * 4096;
      const uint32_t ta = tb + gr * 256 + ((gr & 3) << 5) + q * 8;
      const uint32_t la = tb + (lane >> 3) * 256 + (((lane & 7) << 4) ^ ((lane >> 3) << 5));
      float* op = out + (size_t)(m * 128 + wg * 64 + (lane >> 4) * 16 + w * 4 + ((lane >> 3) & 1)) * DM + s * 64 + (lane & 7) * 4;
#pragma unroll
      for (int qq = 0; qq < 4; qq += QS) {
#pragma unroll
        for (int qt = qq; qt < qq + QS; qt++) {
          const int h = qt & 1, ch = qt >> 1;
#pragma unroll
          for (int j = 0; j < 4; j++) {
            const int i = ch * 8 + j * 2 + h;
            asm volatile("st.shared.v2.f32 [%0], {%1,%2};" ::"r"((ta ^ (j << 5)) + h * 2048 + ch * 128),
                         "f"((fin[2 * i] + bf_lo(sum[i])) * rho[h]), "f"((fin[2 * i + 1] + bf_hi(sum[i])) * rho[h]) : "memory");
          }
        }
        __syncwarp();
#pragma unroll
        for (int qt = qq; qt < qq + QS; qt++) {
          const int h = qt & 1, ch = qt >> 1;
#pragma unroll
          for (int r = 0; r < 2; r++)
            *reinterpret_cast<uint4*>(op + (r * 32 + h * 2) * DM + ch * 32) = lds_u4(la + (h * 2 + r) * 1024 + ch * 128);
        }
      }
      if (threadIdx.x == 128) g_epoch[b] = tag;
      TS(wg, 17); TG(wg); TRD(); TDUMP();
    }
  } else {
    asm volatile("setmaxnreg.dec.sync.aligned.u32 40;");
    int wsel = warp;
    asm("" : "+r"(wsel));
    if (wsel > 8) {
      if (warp != 11) {
        const int t = threadIdx.x - 288;
        unsigned par;
        asm volatile("ld.relaxed.gpu.global.u32 %0, [%1];" : "=r"(par) : "l"(g_epoch + b) : "memory");
        const float pr = bf_ld(lam_re + s * 64 + t), pi = bf_ld(lam_im + s * 64 + t), pd = bf_ld(log_dt + s * 64 + t);
        asm volatile("barrier.cluster.wait.aligned;" ::: "memory");
        par = __shfl_sync(0xffffffffu, (par + 1) & 1, 0);
        cplx l64 = make_lam(pr, pi, pd);
        {
          const float inv = __fdividef(1.f, fmaf(pr, pr, pi * pi));
          const cplx cf = cmul(cplx{l64.re - 1.f, l64.im}, cplx{pr * inv, -pi * inv});
          asm volatile("st.shared.v4.f32 [%0], {%1,%2,%3,%4};" ::"r"(sb + OFF_LC + t * 16), "f"(l64.re), "f"(l64.im), "f"(cf.re), "f"(cf.im) : "memory");
          mbar_arrive(sb + OFF_LBAR);
        }
#pragma unroll
        for (int i = 0; i < 6; i++) l64 = cmul(l64, l64);
        pin(l64.re); pin(l64.im);
        mbar_wait(sb + OFF_GBAR, 0);
        float2* e15 = g_end + s * 1024 + t + (m - 15) * 64;
        {
          const float2 e0 = lds_f2(sb + OFF_CARRY + t * 8), e1 = lds_f2(sb + OFF_CARRY + 512 + t * 8);
          const cplx e = cfma(l64, cplx{e0.x, e0.y}, cplx{e1.x, e1.y});
          const unsigned long long v = ((unsigned long long)__float_as_uint(e.im) << 32) | ((__float_as_uint(e.re) & ~1u) | par);
          asm volatile("st.relaxed.gpu.global.b64 [%0], %1;" ::"l"(e15 + 15 * 64), "l"(v) : "memory");
        }
        asm volatile("st.shared.v2.f32 [%0], {%1,%2};" ::"r"(sb + OFF_CARRY + 512 + t * 8), "f"(l64.re), "f"(l64.im) : "memory");
        if (t == 0) TS(3, 1);
        cplx S = {0.f, 0.f};
        {
          uint32_t vr[15], vi[15];
#pragma unroll
          for (int i = 0; i < 15; i++) { vr[i] = par; vi[i] = 0; }
          int tries = 0;
          bool bad;
#pragma unroll 1
          do {
#pragma unroll
            for (int i = 0; i < 15; i++)
              asm volatile("{.reg .pred p; .reg .b64 v; mov.b64 v, {%0,%1}; setp.ge.s32 p, %3, %4; @p ld.relaxed.gpu.global.b64 v, [%2]; mov.b64 {%0,%1}, v;}"
                           : "+r"(vr[i]), "+r"(vi[i]) : "l"(e15 + i * 64), "r"(m), "r"(15 - i) : "memory");
            uint32_t x = vr[0] ^ par;
#pragma unroll
            for (int i = 1; i < 15; i++) asm("lop3.b32 %0, %0, %1, %2, 0xf6;" : "+r"(x) : "r"(vr[i]), "r"(par));
            bad = __any_sync(0xffffffffu, x & 1);
          } while (bad && ++tries < 200000);
          if (t == 0) TS(3, 2);
          const float2 lp = lds_f2(sb + OFF_CARRY + 512 + t * 8);
          const cplx l128 = cmul(cplx{lp.x, lp.y}, cplx{lp.x, lp.y});
#pragma unroll
          for (int i = 0; i < 15; i++) S = cfma(l128, S, cplx{__uint_as_float(vr[i] & ~1u), __uint_as_float(vi[i])});
        }
        const float2 lp = lds_f2(sb + OFF_CARRY + 512 + t * 8);
        const float2 e0 = lds_f2(sb + OFF_CARRY + t * 8);
        const cplx S1 = cfma(cplx{lp.x, lp.y}, S, cplx{e0.x, e0.y});
        asm volatile("st.shared.v2.f32 [%0], {%1,%2};" ::"r"(sb + OFF_CARRY + t * 8), "f"(S.re), "f"(S.im) : "memory");
        asm volatile("st.shared.v2.f32 [%0], {%1,%2};" ::"r"(sb + OFF_CARRY + 512 + t * 8), "f"(S1.re), "f"(S1.im) : "memory");
        mbar_arrive(sb + OFF_CBAR);
        if (t == 0) TS(3, 3);
        mbar_wait(sb + OFF_CBAR, 0);
        const int gr = lane >> 2, q = lane & 3;
        mbar_wait(sb + OFF_XFULL + 16, 1);
        mbar_wait(sb + OFF_EMPTY, 0);
#pragma unroll 1
        for (int cw = warp - 9; cw < 8; cw += 2) {
          const float r0 = 0.5f * bf_lo(lds_h(sb + OFF_GS + (cw * 16 + gr) * 2)), r1 = 0.5f * bf_lo(lds_h(sb + OFF_GS + (cw * 16 + gr) * 2 + 16));
          const uint32_t xa = sb + OFF_X + (1 + rank) * 16384 + (cw * 16 + (lane & 15)) * 128 + (((lane >> 4) ^ (lane & 7)) << 4);
          uint32_t xv[16];
#pragma unroll
          for (int i = 0; i < 4; i++)
            asm volatile("ldmatrix.sync.aligned.m8n8.x4.shared.b16 {%0,%1,%2,%3}, [%4];" : "=r"(xv[4 * i]), "=r"(xv[4 * i + 1]), "=r"(xv[4 * i + 2]), "=r"(xv[4 * i + 3])
                         : "r"(xa ^ (i << 5)) : "memory");
          __syncwarp();
          uint4 db[2];
#pragma unroll
          for (int j = 0; j < 8; j++) {
            if ((j & 3) == 0) { db[0] = lds_u4(sb + OFF_DB + q * 64 + j * 8); db[1] = lds_u4(sb + OFF_DB + q * 64 + j * 8 + 16); }
            const uint32_t dk = (j & 1) ? db[(j >> 1) & 1].z : db[(j >> 1) & 1].x, bb = (j & 1) ? db[(j >> 1) & 1].w : db[(j >> 1) & 1].y;
            const uint32_t x0 = bf2_mul(xv[2 * j], dk), x1 = bf2_mul(xv[2 * j + 1], dk);
            const float bl = bf_lo(bb), bh = bf_hi(bb);
            asm volatile("st.shared.v4.f32 [%0], {%1,%2,%3,%4};" ::"r"(sb + OFF_X + 16384 + (j >> 2) * 16384 + cw * 2048 + (j & 3) * 512 + lane * 16), "f"(fmaf(bf_lo(x0), r0, bl)),
                         "f"(fmaf(bf_hi(x0), r0, bh)), "f"(fmaf(bf_lo(x1), r1, bl)), "f"(fmaf(bf_hi(x1), r1, bh)) : "memory");
          }
        }
        mbar_arrive(sb + OFF_LBAR);
        if (t == 0) TS(3, 5);
      } else {
        if (lane == 0) TG(2);
        uint4 gw[2];
#pragma unroll
        for (int i = 0; i < 2; i++) gw[i] = __ldg(reinterpret_cast<const uint4*>(gate_w) + i * 32 + lane);
        unsigned par;
        asm volatile("ld.relaxed.gpu.global.u32 %0, [%1];" : "=r"(par) : "l"(g_epoch + b) : "memory");
        asm volatile("barrier.cluster.wait.aligned;" ::: "memory");
        par = __shfl_sync(0xffffffffu, par + 1, 0);
        const int row = s * 16 + (lane >> 3);
        const uint32_t xr0 = sb + OFF_X + row * 128 + (((lane & 7) ^ (row & 7)) << 4), xr1 = (xr0 + 512) ^ 64;
        float z[4] = {0.f, 0.f, 0.f, 0.f};
        uint32_t ck = 0;
#pragma unroll
        for (int kb = 0; kb < 8; kb++) {
          const int src = (kb & 3) * 8 + (lane & 7);
          const uint32_t wv[4] = {__shfl_sync(0xffffffffu, gw[kb >> 2].x, src), __shfl_sync(0xffffffffu, gw[kb >> 2].y, src),
                                  __shfl_sync(0xffffffffu, gw[kb >> 2].z, src), __shfl_sync(0xffffffffu, gw[kb >> 2].w, src)};
          mbar_wait(sb + OFF_XFULL + 8 * kb, 0);
          if ((PF & 2) && kb == PFK && elect_one()) {
            l2_prefetch(pf_w1 + b * 7168, 14336);
            l2_prefetch(pf_cre + b * 2048, 4096);
            l2_prefetch(pf_cim + b * 2048, 4096);
            l2_prefetch(pf_w2 + b * 7168, 14336);
          }
          const uint32_t xo = ((kb + xrot) & 7) * 16384;
#pragma unroll
          for (int r = 0; r < 4; r++) {
            if (r == 2) sched_fence(ck);
            const uint4 a = lds_u4(((r & 1) ? xr1 : xr0) + xo + (r >> 1) * 1024);
            const uint32_t p = bf2_fma(a.w, wv[3], bf2_fma(a.z, wv[2], bf2_fma(a.y, wv[1], bf2_mul(a.x, wv[0]))));
            z[r] += bf_lo(p); z[r] += bf_hi(p);
          }
        }
        uint32_t dk, bb;
        asm volatile("ld.global.nc.u32 %0, [%1];" : "=r"(dk) : "l"(dskip + s * 64 + lane * 2) : "memory");
        asm volatile("ld.global.nc.u32 %0, [%1];" : "=r"(bb) : "l"(b2 + s * 64 + lane * 2) : "memory");
        if (lane == 0) asm volatile("st.shared.v2.u32 [%0], {%1,%2};" ::"r"(sb + OFF_EPOCH), "r"(par), "r"(ck) : "memory");
        par &= 1;
        {
          float y0 = (lane & 4) ? z[1] : z[0], y1 = (lane & 4) ? z[3] : z[2];
          y0 += __shfl_xor_sync(0xffffffffu, (lane & 4) ? z[0] : z[1], 4);
          y1 += __shfl_xor_sync(0xffffffffu, (lane & 4) ? z[2] : z[3], 4);
          float zz = (lane & 2) ? y1 : y0;
          zz += __shfl_xor_sync(0xffffffffu, (lane & 2) ? y0 : y1, 2);
          zz += __shfl_xor_sync(0xffffffffu, zz, 1);
          const float rho = 4.f * expf(zz > 40.f ? 40.f : zz);
          if ((lane & 1) == 0)
            asm volatile("st.relaxed.gpu.global.u32 [%0], %1;" ::"l"(g_gate + m * 128 + row + (lane & 4) + (lane & 2) * 4), "r"((__float_as_uint(rho) & ~1u) | par) : "memory");
        }
        if (lane == 0) TS(3, 0);
        mbar_wait(sb + OFF_GBAR, 0);
        asm volatile("st.shared.v2.u32 [%0], {%1,%2};" ::"r"(sb + OFF_DB + (lane & 3) * 64 + (lane >> 2) * 8), "r"(dk), "r"(bf2_add(bb, bb)) : "memory");
        uint32_t g0, g1, g2, g3;
        int tries = 0;
#pragma unroll 1
        do {
          asm volatile("ld.relaxed.gpu.global.v4.u32 {%0,%1,%2,%3}, [%4];" : "=r"(g0), "=r"(g1), "=r"(g2), "=r"(g3) : "l"(g_gate + m * 128 + lane * 4) : "memory");
        } while ((((g0 ^ par) | (g1 ^ par) | (g2 ^ par) | (g3 ^ par)) & 1) && ++tries < 200000);
        asm volatile("st.shared.v2.u32 [%0], {%1,%2};" ::"r"(sb + OFF_GS + lane * 8), "r"(pack_bf16(__uint_as_float(g0), __uint_as_float(g1))),
                     "r"(pack_bf16(__uint_as_float(g2), __uint_as_float(g3))) : "memory");
        mbar_arrive(sb + OFF_CBAR);
        if (lane == 0) TS(3, 4);
      }
    } else {
      asm volatile("barrier.cluster.wait.aligned;" ::: "memory");
      if (elect_one()) {
        TS(2, 1);
        const uint32_t t0 = clock();
#pragma unroll 1
        for (int u = 0; u < 8; u++) {
          if (u >= 1) while ((uint32_t)clock() - t0 < D0 + (u - 1) * D1) {}
          mbar_expect_tx(sb + OFF_XFULL + 8 * u, 16384);
          tma5d_mc(sb + OFF_X + ((u + xrot) & 7) * 16384 + rank * 8192, &maps.x, u * 64, 2 * m + rank, sb + OFF_XFULL + 8 * u);
          if (u < 6) {
            mbar_expect_tx(sb + OFF_FULL + 8 * u, 16384);
            tma2d(sb + OFF_RING + u * 16384, &maps.bre, u * 64, s * 64, sb + OFF_FULL + 8 * u);
            tma2d(sb + OFF_RING + u * 16384 + 8192, &maps.bim, u * 64, s * 64, sb + OFF_FULL + 8 * u);
          } else if (PF & 4) {
            asm volatile("cp.async.bulk.prefetch.tensor.2d.L2.global [%0, {%1,%2}];" ::"l"((m & 1) ? &maps.bim : &maps.bre), "r"(u * 64), "r"(s * 64) : "memory");
          }
        }
        TS(2, 5);
        int slot = 0; uint32_t ph = 0;
#pragma unroll 1
        for (int u = 6; u < 24; u++) {
          const uint32_t fb = sb + OFF_FULL + 8 * slot, dst = sb + OFF_RING + slot * 16384;
          mbar_wait(sb + OFF_EMPTY + 8 * slot, ph);
          TS2(0, u);
          if (u < 8) {
            mbar_expect_tx(fb, 16384);
            tma2d(dst, &maps.bre, u * 64, s * 64, fb);
            tma2d(dst + 8192, &maps.bim, u * 64, s * 64, fb);
          } else if (u < 16) {
            mbar_expect_tx(fb, 12288);
            tma3d(dst, &maps.w1b, 0, (u - 8) * 64, s * 7, fb);
          } else {
            mbar_expect_tx(fb, 16384);
            tma2d(dst, &maps.w1a, s * 224 + 96, ((u - xrot) & 7) * 64, fb);
            tma2d(dst + 8192, &maps.w1a, s * 224 + 160, ((u - xrot) & 7) * 64, fb);
          }
          if (++slot == NSLOT) { slot = 0; ph ^= 1; }
        }
#pragma unroll 1
        for (int j = 0; j < 3; j++) {
          const uint32_t fb = sb + OFF_FULL + 8 * j;
          mbar_wait(sb + OFF_EMPTY + 8 + 8 * j, 1);
          mbar_expect_tx(fb, j == 1 ? 32768 : 28672);
#pragma unroll
          for (int e = 0; e < 2; e++) {
            const int c = ((sp + 1) & 3) * 128 + ((rank ^ e ^ 1) << 6);
            const uint32_t dst = sb + OFF_X + stage_off(e);
            if (j == 1) {
              tma2d(dst + 14336, &maps.cre, s * 64, c, fb);
              tma2d(dst + 22528, &maps.cim, s * 64, c, fb);
            } else {
              tma2d(dst + j * 15360, &maps.w2, c, s * 224 + j * 56, fb);
            }
          }
        }
#pragma unroll 1
        for (int p = 2; p < 8; p++) {
          const int c = ((sp + 1 + (p >> 1)) & 3) * 128 + (((rank ^ p ^ 1) & 1) << 6);
          const uint32_t fb = sb + OFF_XFULL + 8 * p, dst = sb + OFF_X + stage_off(p);
          if (p != 3) mbar_wait(sb + OFF_EMPTY + (p == 2 ? 40 : (p - 4) * 8), p == 2);
          TS2(0, 32 + p);
          mbar_expect_tx(fb, 45056);
          tma2d(dst, &maps.w2, c, s * 224, fb);
          tma2d(dst + 14336, &maps.cre, s * 64, c, fb);
          tma2d(dst + 22528, &maps.cim, s * 64, c, fb);
          tma2d(dst + 30720, &maps.w2, c, s * 224 + 112, fb);
        }
        TS(2, 2);
      }
    }
  }
}

typedef CUresult (*EncFn)(CUtensorMap*, CUtensorMapDataType, cuuint32_t, void*, const cuuint64_t*, const cuuint64_t*, const cuuint32_t*,
                          const cuuint32_t*, CUtensorMapInterleave, CUtensorMapSwizzle, CUtensorMapL2promotion, CUtensorMapFloatOOBfill);

void encode(EncFn f, CUtensorMap* mp, const void* p, int rank, const cuuint64_t* dims, const cuuint64_t* strides, const cuuint32_t* box, CUtensorMapSwizzle sw) {
  cuuint32_t es[5] = {1, 1, 1, 1, 1};
  f(mp, CU_TENSOR_MAP_DATA_TYPE_BFLOAT16, rank, const_cast<void*>(p), dims, strides, box, es, CU_TENSOR_MAP_INTERLEAVE_NONE, sw,
    CU_TENSOR_MAP_L2_PROMOTION_L2_128B, CU_TENSOR_MAP_FLOAT_OOB_FILL_NONE);
}

}

extern "C" void kernel_launch(void* const* d_in, const int* in_sizes, int n_in, void* d_out, int out_size) {
  typedef const __nv_bfloat16* bp;
  bp x = (bp)d_in[0], lre = (bp)d_in[1], lim = (bp)d_in[2], bre = (bp)d_in[3], bim = (bp)d_in[4], cre = (bp)d_in[5], cim = (bp)d_in[6],
     ldt = (bp)d_in[7], dsk = (bp)d_in[8], w1 = (bp)d_in[10], b1 = (bp)d_in[11], w2 = (bp)d_in[12], b2 = (bp)d_in[13], gw = (bp)d_in[14];
  static EncFn enc = nullptr;
  if (!enc) {
    void* f = nullptr;
    cudaDriverEntryPointQueryResult qr;
    cudaGetDriverEntryPoint("cuTensorMapEncodeTiled", &f, cudaEnableDefault, &qr);
    enc = (EncFn)f;
    cudaFuncSetAttribute(fused_kernel, cudaFuncAttributeMaxDynamicSharedMemorySize, SMEM_BYTES);
  }
  Maps maps;
  {
    cuuint64_t d[5] = {DM, 2, 4, 8, SEQ / 64}, st[4] = {DM * 2, 16 * DM * 2, 2 * DM * 2, 64 * DM * 2};
    cuuint32_t bx[5] = {64, 2, 4, 8, 1};
    encode(enc, &maps.x, x, 5, d, st, bx, CU_TENSOR_MAP_SWIZZLE_128B);
  }
  {
    cuuint64_t d[2] = {DM, DM}, st[1] = {DM * 2};
    cuuint32_t bx[2] = {64, 64};
    encode(enc, &maps.bre, bre, 2, d, st, bx, CU_TENSOR_MAP_SWIZZLE_128B);
    encode(enc, &maps.bim, bim, 2, d, st, bx, CU_TENSOR_MAP_SWIZZLE_128B);
    encode(enc, &maps.cre, cre, 2, d, st, bx, CU_TENSOR_MAP_SWIZZLE_128B);
    encode(enc, &maps.cim, cim, 2, d, st, bx, CU_TENSOR_MAP_SWIZZLE_128B);
  }
  {
    cuuint64_t d[2] = {FF, DM}, st[1] = {FF * 2};
    cuuint32_t bx[2] = {64, 64};
    encode(enc, &maps.w1a, w1, 2, d, st, bx, CU_TENSOR_MAP_SWIZZLE_128B);
    cuuint64_t d3[3] = {32, DM, FF / 32}, st3[2] = {FF * 2, 64};
    cuuint32_t bx3[3] = {32, 64, 3};
    encode(enc, &maps.w1b, w1, 3, d3, st3, bx3, CU_TENSOR_MAP_SWIZZLE_64B);
  }
  {
    cuuint64_t d[2] = {DM, FF}, st[1] = {DM * 2};
    cuuint32_t bx[2] = {64, 112};
    encode(enc, &maps.w2, w2, 2, d, st, bx, CU_TENSOR_MAP_SWIZZLE_128B);
  }
  fused_kernel<<<128, 384, SMEM_BYTES>>>(lre, lim, ldt, dsk, b1, b2, gw, w1, w2, cre, cim, (float*)d_out, maps);
}
```

```cpp
#include <cuda_runtime.h>
#include <cuda_bf16.h>
#include <cuda.h>
#include <stdint.h>

#define MAP 1
#define D0 600
#define D1 500
#define PF 20
#define PFK 5
#define GELUP 0
#define EW 1
#define K1E 1
#define K2E 0
#define QS 1
#define K2G 4
#define FINP 4
#define LBD 300
#define PFS 32
#define SB0 2
#define PFD 2
#define HOLD 0
#define GAP 14
#define FINW 0
#define TP 9
#define TW 0

namespace {

constexpr int SEQ = 2048, DM = 512, FF = 1792;
constexpr int NSLOT = 6;
constexpr uint32_t OFF_X = 0, OFF_RING = 131072, OFF_MISC = 229376;
constexpr uint32_t OFF_XFULL = OFF_MISC, OFF_FULL = OFF_XFULL + 64, OFF_RBAR = OFF_FULL + 48, OFF_EMPTY = OFF_RBAR + 16, OFF_KBAR = OFF_EMPTY + 48,
                   OFF_GBAR = OFF_KBAR + 16, OFF_LBAR = OFF_GBAR + 8, OFF_CBAR = OFF_LBAR + 8, OFF_EPOCH = OFF_CBAR + 8;
constexpr uint32_t OFF_LC = OFF_MISC + 256;
constexpr uint32_t OFF_GS = OFF_LC;
constexpr uint32_t OFF_DB = OFF_LC + 512;
constexpr uint32_t OFF_CARRY = OFF_LC + 1024;
constexpr uint32_t OFF_DBG = OFF_CARRY + 1024;
constexpr uint32_t SMEM_BYTES = OFF_DBG + 768;
static_assert(SMEM_BYTES <= 232448, "smem");

struct Maps { CUtensorMap x, bre, bim, w1b, w1a, w2, cre, cim; };
__host__ __device__ constexpr uint32_t stage_off(int p) { return 49152 + 45056 * (((p >> 1) & 1) + 2 * (p & 1)); }

__device__ uint4 g_part[16 * 8 * 3 * 1024];
__device__ float2 g_end[8 * 16 * 64];
__device__ unsigned g_gate[SEQ];
__device__ unsigned g_epoch[128];
#define TG(role) do {} while (0)
#define TS2(role, i) do {} while (0)
#define TS(role, i) do {} while (0)
#define TDUMP() do {} while (0)
#define TR(i) do {} while (0)
#define TRD() do {} while (0)

__device__ __forceinline__ void mbar_init(uint32_t bar, uint32_t cnt) { asm volatile("mbarrier.init.shared::cta.b64 [%0], %1;" ::"r"(bar), "r"(cnt)); }
__device__ __forceinline__ void mbar_expect_tx(uint32_t bar, uint32_t bytes) { asm volatile("mbarrier.arrive.expect_tx.shared::cta.b64 _, [%0], %1;" ::"r"(bar), "r"(bytes) : "memory"); }
__device__ __forceinline__ void mbar_arrive(uint32_t bar) { asm volatile("mbarrier.arrive.shared::cta.b64 _, [%0];" ::"r"(bar) : "memory"); }
__device__ __forceinline__ void mbar_arrive_cl(uint32_t cbar) { asm volatile("mbarrier.arrive.shared::cluster.b64 _, [%0];" ::"r"(cbar) : "memory"); }
__device__ __forceinline__ void mbar_wait(uint32_t bar, uint32_t parity) {
  asm volatile(
      "{\n.reg .pred p;\n.reg .u32 c;\n"
      "mbarrier.try_wait.parity.shared::cta.b64 p, [%0], %1;\n"
      "@p bra.uni LAB_DONE;\n"
      "mov.u32 c, 0;\n"
      "LAB_WAIT:\n"
      "mbarrier.try_wait.parity.shared::cta.b64 p, [%0], %1;\n"
      "@p bra.uni LAB_DONE;\n"
      "add.u32 c, c, 1;\nsetp.lt.u32 p, c, 200000;\n@p bra.uni LAB_WAIT;\n"
      "LAB_DONE:\n}" ::"r"(bar), "r"(parity) : "memory");
}
__device__ __forceinline__ void tma2d(uint32_t dst, const CUtensorMap* m, int c0, int c1, uint32_t bar) {
  asm volatile("cp.async.bulk.tensor.2d.shared::cluster.global.mbarrier::complete_tx::bytes [%0], [%1, {%3,%4}], [%2];"
               ::"r"(dst), "l"(m), "r"(bar), "r"(c0), "r"(c1) : "memory");
}
__device__ __forceinline__ void tma3d(uint32_t dst, const CUtensorMap* m, int c0, int c1, int c2, uint32_t bar) {
  asm volatile("cp.async.bulk.tensor.3d.shared::cluster.global.mbarrier::complete_tx::bytes [%0], [%1, {%3,%4,%5}], [%2];"
               ::"r"(dst), "l"(m), "r"(bar), "r"(c0), "r"(c1), "r"(c2) : "memory");
}
__device__ __forceinline__ void tma5d_mc(uint32_t dst, const CUtensorMap* m, int c0, int c4, uint32_t bar) {
  asm volatile("cp.async.bulk.tensor.5d.shared::cluster.global.mbarrier::complete_tx::bytes.multicast::cluster [%0], [%1, {%3,%5,%5,%5,%4}], [%2], %6;"
               ::"r"(dst), "l"(m), "r"(bar), "r"(c0), "r"(c4), "r"(0), "h"((uint16_t)3) : "memory");
}
__device__ __forceinline__ void l2_prefetch(const void* p, uint32_t bytes) { asm volatile("cp.async.bulk.prefetch.L2.global [%0], %1;" ::"l"(p), "r"(bytes) : "memory"); }
__device__ __forceinline__ bool elect_one() {
  uint32_t pred;
  asm volatile("{.reg .pred P; elect.sync _|P, 0xffffffff; selp.u32 %0, 1, 0, P;}" : "=r"(pred));
  return pred != 0;
}
__device__ __forceinline__ void wg_fence() { asm volatile("wgmma.fence.sync.aligned;" ::: "memory"); }
__device__ __forceinline__ void wg_commit() { asm volatile("wgmma.commit_group.sync.aligned;" ::: "memory"); }
template <int N> __device__ __forceinline__ void wg_wait() { asm volatile("wgmma.wait_group.sync.aligned %0;" ::"n"(N) : "memory"); }
__device__ __forceinline__ void pin(float& a) { asm volatile("" : "+f"(a)::"memory"); }
__device__ __forceinline__ void pin(uint32_t& a) { asm volatile("" : "+r"(a)::"memory"); }
template <int N> __device__ __forceinline__ void reg_fence(float (&d)[N]) {
#pragma unroll
  for (int i = 0; i < N; i++) pin(d[i]);
}
__device__ __forceinline__ void bar_sync(int id, int n) { asm volatile("bar.sync %0, %1;" ::"r"(id), "r"(n) : "memory"); }
__device__ __forceinline__ void bar_arrive(int id, int n) { asm volatile("bar.arrive %0, %1;" ::"r"(id), "r"(n) : "memory"); }
constexpr uint32_t DH128 = (1024 >> 4) | (1u << 30), DH64 = (512 >> 4) | (2u << 30);
__host__ __device__ constexpr uint32_t lbo(uint32_t bytes) { return (bytes >> 4) << 20; }
__device__ __forceinline__ uint32_t pack_bf16(float lo, float hi) { uint32_t r; asm("cvt.rn.bf16x2.f32 %0, %1, %2;" : "=r"(r) : "f"(hi), "f"(lo)); return r; }
__device__ __forceinline__ float bf_lo(uint32_t v) { return __uint_as_float(v << 16); }
__device__ __forceinline__ float bf_hi(uint32_t v) { return __uint_as_float(v & 0xffff0000u); }
__device__ __forceinline__ float bf_ld(const __nv_bfloat16* p) { return __bfloat162float(__ldg(p)); }
__device__ __forceinline__ uint32_t late16(uint32_t bar) {
  uint32_t r;
  asm volatile("{.reg .pred p; mbarrier.test_wait.parity.shared::cta.b64 p, [%1], 0; selp.u32 %0, 16, 0, p;}" : "=r"(r) : "r"(bar) : "memory");
  return r;
}
__device__ __forceinline__ float2 lds_f2(uint32_t a) { float2 v; asm volatile("ld.shared.v2.f32 {%0,%1}, [%2];" : "=f"(v.x), "=f"(v.y) : "r"(a)); return v; }
__device__ __forceinline__ uint32_t lds_h(uint32_t a) { uint32_t v; asm volatile("ld.shared.u16 %0, [%1];" : "=r"(v) : "r"(a)); return v; }
__device__ __forceinline__ uint32_t lds_u(uint32_t a) { uint32_t v; asm volatile("ld.shared.u32 %0, [%1];" : "=r"(v) : "r"(a)); return v; }
__device__ __forceinline__ uint4 lds_u4(uint32_t a) { uint4 v; asm volatile("ld.shared.v4.u32 {%0,%1,%2,%3}, [%4];" : "=r"(v.x), "=r"(v.y), "=r"(v.z), "=r"(v.w) : "r"(a)); return v; }
__device__ __forceinline__ void st_b128(uint4* p, uint32_t a, uint32_t b, uint32_t c, uint32_t d) {
  asm volatile("st.relaxed.gpu.global.v4.b32 [%0], {%1,%2,%3,%4};" ::"l"(p), "r"(a), "r"(b), "r"(c), "r"(d) : "memory");
}
__device__ __forceinline__ void ld_b128(const uint4* p, uint32_t& a, uint32_t& b, uint32_t& c, uint32_t& d) {
  asm volatile("{.reg .b64 l, h; .reg .b128 v; ld.relaxed.gpu.global.b128 v, [%4]; mov.b128 {l,h}, v; mov.b64 {%0,%1}, l; mov.b64 {%2,%3}, h;}"
               : "=r"(a), "=r"(b), "=r"(c), "=r"(d) : "l"(p) : "memory");
}
__device__ __forceinline__ float tanh_fast(float x) { float y; asm("tanh.approx.f32 %0, %1;" : "=f"(y) : "f"(x)); return y; }
__device__ __forceinline__ float gelu2(float v) {
  float p = fmaf(v * v, 0.0356774081363f, 0.7978845608029f);
  return fmaf(v, tanh_fast(v * p), v);
}
__device__ __forceinline__ uint32_t bf2_mul(uint32_t a, uint32_t b) { uint32_t r; asm("mul.rn.bf16x2 %0, %1, %2;" : "=r"(r) : "r"(a), "r"(b)); return r; }
__device__ __forceinline__ uint32_t bf2_add(uint32_t a, uint32_t b) { uint32_t r; asm("add.rn.bf16x2 %0, %1, %2;" : "=r"(r) : "r"(a), "r"(b)); return r; }
__device__ __forceinline__ uint32_t bf2_fma(uint32_t a, uint32_t b, uint32_t c) { uint32_t r; asm("fma.rn.bf16x2 %0, %1, %2, %3;" : "=r"(r) : "r"(a), "r"(b), "r"(c)); return r; }
__device__ __forceinline__ uint32_t gelu2_pair(float a, float b) {
  return pack_bf16(gelu2(a), gelu2(b));
}
struct cplx { float re, im; };
__device__ __forceinline__ cplx cmul(cplx a, cplx b) { return {fmaf(a.re, b.re, -a.im * b.im), fmaf(a.re, b.im, a.im * b.re)}; }
__device__ __forceinline__ cplx cfma(cplx a, cplx b, cplx c) {
  return {fmaf(a.re, b.re, fmaf(-a.im, b.im, c.re)), fmaf(a.re, b.im, fmaf(a.im, b.re, c.im))};
}
__device__ __forceinline__ cplx make_lam(float lre, float lim, float ldt) {
  float dt = __bfloat162float(__float2bfloat16_rn(expf(ldt)));
  float mag = expf(dt * lre), sn, cs;
  sincospif(dt * lim * 0.31830988618379067f, &sn, &cs);
  return {mag * cs, mag * sn};
}

template<int TA,int TB,uint32_t AH,uint32_t BH> __device__ __forceinline__ void wgmma_n64_ss(float (&d)[32], uint32_t al, uint32_t ao, uint32_t bl, uint32_t bo, int scale_d){
  asm volatile("{.reg .pred p; .reg .b32 t, v; .reg .b64 da, db; setp.ne.b32 p, %36, 0; add.u32 t, %32, %33; mov.b64 da, {t, %39}; add.u32 v, %34, %35; mov.b64 db, {v, %40};\n"
   "wgmma.mma_async.sync.aligned.m64n64k16.f32.bf16.bf16 {%0,%1,%2,%3,%4,%5,%6,%7,%8,%9,%10,%11,%12,%13,%14,%15,%16,%17,%18,%19,%20,%21,%22,%23,%24,%25,%26,%27,%28,%29,%30,%31}, da, db, p, 1, 1, %37, %38;}"
   : "+f"(d[0]),"+f"(d[1]),"+f"(d[2]),"+f"(d[3]),"+f"(d[4]),"+f"(d[5]),"+f"(d[6]),"+f"(d[7]),"+f"(d[8]),"+f"(d[9]),"+f"(d[10]),"+f"(d[11]),"+f"(d[12]),"+f"(d[13]),"+f"(d[14]),"+f"(d[15]),"+f"(d[16]),"+f"(d[17]),"+f"(d[18]),"+f"(d[19]),"+f"(d[20]),"+f"(d[21]),"+f"(d[22]),"+f"(d[23]),"+f"(d[24]),"+f"(d[25]),"+f"(d[26]),"+f"(d[27]),"+f"(d[28]),"+f"(d[29]),"+f"(d[30]),"+f"(d[31])
   : "r"(al),"r"(ao >> 4),"r"(bl),"r"(bo >> 4),"r"(scale_d),"n"(TA),"n"(TB),"n"(AH),"n"(BH));
}
template<int TB,uint32_t BH> __device__ __forceinline__ void wgmma_n64_rs(float (&d)[32], uint32_t a0,uint32_t a1,uint32_t a2,uint32_t a3, uint32_t bl, uint32_t bo, int scale_d){
  asm volatile("{.reg .pred p; .reg .b32 t; .reg .b64 db; setp.ne.b32 p, %38, 0; add.u32 t, %36, %37; mov.b64 db, {t, %40};\n"
   "wgmma.mma_async.sync.aligned.m64n64k16.f32.bf16.bf16 {%0,%1,%2,%3,%4,%5,%6,%7,%8,%9,%10,%11,%12,%13,%14,%15,%16,%17,%18,%19,%20,%21,%22,%23,%24,%25,%26,%27,%28,%29,%30,%31}, {%32,%33,%34,%35}, db, p, 1, 1, %39;}"
   : "+f"(d[0]),"+f"(d[1]),"+f"(d[2]),"+f"(d[3]),"+f"(d[4]),"+f"(d[5]),"+f"(d[6]),"+f"(d[7]),"+f"(d[8]),"+f"(d[9]),"+f"(d[10]),"+f"(d[11]),"+f"(d[12]),"+f"(d[13]),"+f"(d[14]),"+f"(d[15]),"+f"(d[16]),"+f"(d[17]),"+f"(d[18]),"+f"(d[19]),"+f"(d[20]),"+f"(d[21]),"+f"(d[22]),"+f"(d[23]),"+f"(d[24]),"+f"(d[25]),"+f"(d[26]),"+f"(d[27]),"+f"(d[28]),"+f"(d[29]),"+f"(d[30]),"+f"(d[31])
   : "r"(a0),"r"(a1),"r"(a2),"r"(a3),"r"(bl),"r"(bo >> 4),"r"(scale_d),"n"(TB),"n"(BH));
}
template<int TA,int TB,uint32_t AH,uint32_t BH> __device__ __forceinline__ void wgmma_n96_ss(float (&d)[48], uint32_t al, uint32_t ao, uint32_t bl, uint32_t bo, int scale_d){
  asm volatile("{.reg .pred p; .reg .b32 t, v; .reg .b64 da, db; setp.ne.b32 p, %52, 0; add.u32 t, %48, %49; mov.b64 da, {t, %55}; add.u32 v, %50, %51; mov.b64 db, {v, %56};\n"
   "wgmma.mma_async.sync.aligned.m64n96k16.f32.bf16.bf16 {%0,%1,%2,%3,%4,%5,%6,%7,%8,%9,%10,%11,%12,%13,%14,%15,%16,%17,%18,%19,%20,%21,%22,%23,%24,%25,%26,%27,%28,%29,%30,%31,%32,%33,%34,%35,%36,%37,%38,%39,%40,%41,%42,%43,%44,%45,%46,%47}, da, db, p, 1, 1, %53, %54;}"
   : "+f"(d[0]),"+f"(d[1]),"+f"(d[2]),"+f"(d[3]),"+f"(d[4]),"+f"(d[5]),"+f"(d[6]),"+f"(d[7]),"+f"(d[8]),"+f"(d[9]),"+f"(d[10]),"+f"(d[11]),"+f"(d[12]),"+f"(d[13]),"+f"(d[14]),"+f"(d[15]),"+f"(d[16]),"+f"(d[17]),"+f"(d[18]),"+f"(d[19]),"+f"(d[20]),"+f"(d[21]),"+f"(d[22]),"+f"(d[23]),"+f"(d[24]),"+f"(d[25]),"+f"(d[26]),"+f"(d[27]),"+f"(d[28]),"+f"(d[29]),"+f"(d[30]),"+f"(d[31]),"+f"(d[32]),"+f"(d[33]),"+f"(d[34]),"+f"(d[35]),"+f"(d[36]),"+f"(d[37]),"+f"(d[38]),"+f"(d[39]),"+f"(d[40]),"+f"(d[41]),"+f"(d[42]),"+f"(d[43]),"+f"(d[44]),"+f"(d[45]),"+f"(d[46]),"+f"(d[47])
   : "r"(al),"r"(ao >> 4),"r"(bl),"r"(bo >> 4),"r"(scale_d),"n"(TA),"n"(TB),"n"(AH),"n"(BH));
}
template<int TA,int TB,uint32_t AH,uint32_t BH> __device__ __forceinline__ void wgmma_n128_ss(float (&d)[64], uint32_t al, uint32_t ao, uint32_t bl, uint32_t bo, int scale_d){
  asm volatile("{.reg .pred p; .reg .b32 t, v; .reg .b64 da, db; setp.ne.b32 p, %68, 0; add.u32 t, %64, %65; mov.b64 da, {t, %71}; add.u32 v, %66, %67; mov.b64 db, {v, %72};\n"
   "wgmma.mma_async.sync.aligned.m64n128k16.f32.bf16.bf16 {%0,%1,%2,%3,%4,%5,%6,%7,%8,%9,%10,%11,%12,%13,%14,%15,%16,%17,%18,%19,%20,%21,%22,%23,%24,%25,%26,%27,%28,%29,%30,%31,%32,%33,%34,%35,%36,%37,%38,%39,%40,%41,%42,%43,%44,%45,%46,%47,%48,%49,%50,%51,%52,%53,%54,%55,%56,%57,%58,%59,%60,%61,%62,%63}, da, db, p, 1, 1, %69, %70;}"
   : "+f"(d[0]),"+f"(d[1]),"+f"(d[2]),"+f"(d[3]),"+f"(d[4]),"+f"(d[5]),"+f"(d[6]),"+f"(d[7]),"+f"(d[8]),"+f"(d[9]),"+f"(d[10]),"+f"(d[11]),"+f"(d[12]),"+f"(d[13]),"+f"(d[14]),"+f"(d[15]),"+f"(d[16]),"+f"(d[17]),"+f"(d[18]),"+f"(d[19]),"+f"(d[20]),"+f"(d[21]),"+f"(d[22]),"+f"(d[23]),"+f"(d[24]),"+f"(d[25]),"+f"(d[26]),"+f"(d[27]),"+f"(d[28]),"+f"(d[29]),"+f"(d[30]),"+f"(d[31]),"+f"(d[32]),"+f"(d[33]),"+f"(d[34]),"+f"(d[35]),"+f"(d[36]),"+f"(d[37]),"+f"(d[38]),"+f"(d[39]),"+f"(d[40]),"+f"(d[41]),"+f"(d[42]),"+f"(d[43]),"+f"(d[44]),"+f"(d[45]),"+f"(d[46]),"+f"(d[47]),"+f"(d[48]),"+f"(d[49]),"+f"(d[50]),"+f"(d[51]),"+f"(d[52]),"+f"(d[53]),"+f"(d[54]),"+f"(d[55]),"+f"(d[56]),"+f"(d[57]),"+f"(d[58]),"+f"(d[59]),"+f"(d[60]),"+f"(d[61]),"+f"(d[62]),"+f"(d[63])
   : "r"(al),"r"(ao >> 4),"r"(bl),"r"(bo >> 4),"r"(scale_d),"n"(TA),"n"(TB),"n"(AH),"n"(BH));
}

__global__ void __cluster_dims__(2, 1, 1) __launch_bounds__(384, 1)
fused_kernel(const __nv_bfloat16* __restrict__ pf_x, const __nv_bfloat16* __restrict__ pf_bre, const __nv_bfloat16* __restrict__ pf_bim,
             const __nv_bfloat16* __restrict__ lam_re, const __nv_bfloat16* __restrict__ lam_im, const __nv_bfloat16* __restrict__ log_dt,
             const __nv_bfloat16* __restrict__ dskip, const __nv_bfloat16* __restrict__ b1, const __nv_bfloat16* __restrict__ b2,
             const __nv_bfloat16* __restrict__ gate_w, const __nv_bfloat16* __restrict__ pf_w1, const __nv_bfloat16* __restrict__ pf_w2,
             const __nv_bfloat16* __restrict__ pf_cre, const __nv_bfloat16* __restrict__ pf_cim, float* __restrict__ out,
             const __grid_constant__ Maps maps) {
  extern __shared__ __align__(1024) unsigned char smem_raw[];
  const uint32_t sb = (uint32_t)__cvta_generic_to_shared(smem_raw);
  const int b = blockIdx.x;
  const int rank = b & 1, cl = b >> 1;
  const int sp = (cl & 1) | ((cl >> 2) & 2), m = ((cl >> 1) & 3) | ((cl >> 4) << 2);
  const int s = sp * 2 + rank;
  const int warp = __shfl_sync(0xffffffffu, (int)(threadIdx.x >> 5), 0);
  const int lane = threadIdx.x & 31;
  const int xrot = 9 - 2 * sp;

  if (elect_one()) {
    if (warp == 8) TS(2, 0);
    if (warp < 3) {
      asm volatile("prefetch.tensormap [%0];" ::"l"(&maps.x + warp) : "memory");
      mbar_init(sb + OFF_GBAR + 8 * warp, warp < 2 ? 64 : 96);
    }
    const uint32_t c = warp < 8 ? 1 : warp < 11 ? 8 : 4;
    mbar_init(sb + OFF_XFULL + 16 * warp, c);
    mbar_init(sb + OFF_XFULL + 16 * warp + 8, c);
    asm volatile("fence.mbarrier_init.release.cluster;" ::: "memory");
  }
  __syncwarp();
  asm volatile("barrier.cluster.arrive.relaxed.aligned;" ::: "memory");

  if (warp < 8) {
    const int wg = warp >> 2, w = warp & 3, q = lane & 3, gr = lane >> 2;
    uint32_t bv[28];
#pragma unroll
    for (int j = 0; j < 28; j++) bv[j] = __ldg(reinterpret_cast<const uint32_t*>(b1 + s * 224 + j * 8) + q);
    asm volatile("setmaxnreg.inc.sync.aligned.u32 224;");
    asm volatile("barrier.cluster.wait.aligned;" ::: "memory");
    TS(wg, 0);
    auto release = [&](int slot) { if (lane == 0) mbar_arrive(sb + OFF_EMPTY + 8 * slot); };
    const uint32_t xw = sb + OFF_X + wg * 8192, fullb = sb + OFF_FULL;
    const uint32_t dxw = (xw & 0x3FFFF) >> 4, dring = ((sb + OFF_RING) & 0x3FFFF) >> 4;

    float ure[32], uim[32], aa[48], ab[64];
    cplx lam[2], coef[2], l16[2], l32[2], lq[2], pre[2], e[2];
    uint32_t sh16, mhi;

    auto bias = [&](int c) {
#pragma unroll
      for (int j = c * 7; j < c * 7 + 7; j++) {
        pin(bv[j]);
        float* d = j < 12 ? aa + 4 * j : ab + 4 * (j - 12);
        d[0] = d[2] = __uint_as_float(bv[j] << sh16); d[1] = d[3] = __uint_as_float(bv[j] & mhi);
        pin(d[0]); pin(d[1]); pin(d[2]); pin(d[3]);
      }
    };
#pragma unroll
    for (int kb = 0; kb < 8; kb++) {
      const int slot = kb % NSLOT;
      mbar_wait(sb + OFF_XFULL + 8 * kb, 0);
      if (kb == 0) TS(wg, 18);
      mbar_wait(fullb + 8 * slot, (kb / NSLOT) & 1);
      TS2(2, kb);
      if (kb == 0) TS(wg, 1);
      wg_fence();
      const uint32_t dxa = dxw + ((kb + xrot) & 7) * 1024;
#pragma unroll
      for (int kk = 0; kk < 4; kk++) {
        wgmma_n64_ss<0, 0, DH128, DH128>(ure, dring, slot * 16384 + kk * 32, dxa, kk * 32, (kb | kk) != 0);
        wgmma_n64_ss<0, 0, DH128, DH128>(uim, dring, slot * 16384 + 8192 + kk * 32, dxa, kk * 32, (kb | kk) != 0);
      }
      wg_commit();
      if (kb > 0) { wg_wait<1>(); release((kb - 1) % NSLOT); }
      if (kb == SB0) { sh16 = late16(sb + OFF_XFULL); mhi = 0xffffffffu << sh16; bias(0); }
      if (kb == 4) bias(1);
      if (kb == 6) bias(2);
      if (kb == 3) {
        mbar_wait(sb + OFF_LBAR, 0);
#pragma unroll
        for (int h = 0; h < 2; h++) {
          const uint4 v = lds_u4(sb + OFF_LC + (w * 16 + gr + 8 * h) * 16);
          lam[h] = cplx{__uint_as_float(v.x), __uint_as_float(v.y)};
          coef[h] = cplx{__uint_as_float(v.z), __uint_as_float(v.w)};
        }
      }
      if (kb == 5) {
#pragma unroll
        for (int h = 0; h < 2; h++) {
          pin(lam[h].re); pin(lam[h].im);
          cplx t = cmul(lam[h], lam[h]); t = cmul(t, t); t = cmul(t, t);
          l16[h] = cmul(t, t);
          pin(l16[h].re); pin(l16[h].im);
        }
      }
      if (kb == 7) {
#pragma unroll
        for (int h = 0; h < 2; h++) {
          pin(l16[h].re); pin(l16[h].im);
          l32[h] = cmul(l16[h], l16[h]);
          const cplx a = (q & 1) ? l16[h] : cplx{1.f, 0.f}, c = (q & 2) ? l32[h] : cplx{1.f, 0.f};
          lq[h] = cmul(cmul(a, c), coef[h]);
          pin(lq[h].re); pin(lq[h].im);
        }
      }
    }
    TS(wg, 2);
    auto scale_u = [&](int i0, int i1) {
#pragma unroll
      for (int i = 0; i < 32; i++) if (i >= i0 && i < i1) {
        pin(ure[i]); pin(uim[i]);
        const cplx v = cmul(coef[(i >> 1) & 1], cplx{ure[i], uim[i]});
        ure[i] = v.re; uim[i] = v.im;
        pin(ure[i]); pin(uim[i]);
      }
    };
#pragma unroll
    for (int kb = 0; kb < 8; kb++) {
      const int u = 8 + kb, slot = u % NSLOT;
      mbar_wait(fullb + 8 * slot, (u / NSLOT) & 1);
      wg_fence();
      const uint32_t dxa = dxw + ((kb + xrot) & 7) * 1024;
#pragma unroll
      for (int kk = 0; kk < 4; kk++)
        wgmma_n96_ss<0, 1, DH128, DH64>(aa, dxa, kk * 32, dring, slot * 16384 + kk * 1024 + lbo(4096), 1);
      wg_commit();
      if (kb == 0) bias(3);
      wg_wait<1>();
      release((u - 1) % NSLOT);
      if (kb == 0) {
        reg_fence(ure); reg_fence(uim);
#pragma unroll
        for (int h = 0; h < 2; h++) e[h] = cplx{ure[2 * h], uim[2 * h]};
      }
      if (kb == 0 || kb == 2 || kb == 3) {
        const int ch = kb ? kb - 1 : 0;
#pragma unroll
        for (int t = 1 + 5 * ch; t < 6 + 5 * ch; t++)
#pragma unroll
          for (int h = 0; h < 2; h++) { const int i = 4 * (t >> 1) + 2 * h + (t & 1); e[h] = cfma(lam[h], e[h], cplx{ure[i], uim[i]}); }
#pragma unroll
        for (int h = 0; h < 2; h++) { pin(e[h].re); pin(e[h].im); }
      } else if (kb == 4) {
#pragma unroll
        for (int h = 0; h < 2; h++) {
          cplx y = {__shfl_up_sync(0xffffffffu, e[h].re, 1, 4), __shfl_up_sync(0xffffffffu, e[h].im, 1, 4)};
          if (q >= 1) e[h] = cfma(l16[h], y, e[h]);
          y = cplx{__shfl_up_sync(0xffffffffu, e[h].re, 2, 4), __shfl_up_sync(0xffffffffu, e[h].im, 2, 4)};
          if (q >= 2) e[h] = cfma(l32[h], y, e[h]);
        }
        if (q == 3) {
#pragma unroll
          for (int h = 0; h < 2; h++)
            asm volatile("st.shared.v2.f32 [%0], {%1,%2};" ::"r"(sb + OFF_CARRY + wg * 512 + (w * 16 + gr + 8 * h) * 8), "f"(e[h].re), "f"(e[h].im) : "memory");
          mbar_arrive(sb + OFF_GBAR);
        }
#pragma unroll
        for (int h = 0; h < 2; h++) {
          const cplx y = {__shfl_up_sync(0xffffffffu, e[h].re, 1, 4), __shfl_up_sync(0xffffffffu, e[h].im, 1, 4)};
          pre[h] = (q >= 1) ? cmul(coef[h], y) : cplx{0.f, 0.f};
          pin(pre[h].re); pin(pre[h].im);
        }
        TS(wg, 3);
      } else if (kb > 4) {
        scale_u(kb == 5 ? 0 : kb == 6 ? 4 : 12, kb == 5 ? 4 : kb == 6 ? 12 : 20);
      }
    }
    TS(wg, 4);
    uint32_t H[56], hf[32];
    cplx hst[2];
    const uint32_t hst_addr = xw + (w * 16 + (lane & 15)) * 128 + (((lane >> 4) ^ (lane & 7)) << 4);
    const uint32_t him = (2 - rank) * 16384;
    uint32_t peer;
    asm volatile("mapa.shared::cluster.u32 %0, %1, %2;" : "=r"(peer) : "r"(sb), "r"(rank ^ 1));
    auto credit = [&]() { if (lane == 0) mbar_arrive_cl(peer + OFF_KBAR + wg * 8); };
#pragma unroll
    for (int kb = 0; kb < 8; kb++) {
      const int u = 16 + kb, slot = u % NSLOT;
      mbar_wait(fullb + 8 * slot, (u / NSLOT) & 1);
      wg_fence();
#pragma unroll
      for (int kk = 0; kk < 4; kk++)
        wgmma_n128_ss<0, 1, DH128, DH128>(ab, dxw, kb * 16384 + kk * 32, dring, slot * 16384 + kk * 2048 + lbo(8192), 1);
      wg_commit();
      wg_wait<1>();
      release((u - 1) % NSLOT);
      if (kb == 0) scale_u(20, 32);
      if (kb < 5 && kb != 1) {
        const int ch = kb ? kb - 1 : 0;
#pragma unroll
        for (int i = ch * 6; i < ch * 6 + 6; i++) {
          pin(aa[2 * i]); pin(aa[2 * i + 1]);
          H[i] = gelu2_pair(aa[2 * i], aa[2 * i + 1]);
          pin(H[i]);
        }
      }
      if (kb >= 4) {
        if (kb == 4) {
          TS(wg, 5);
          mbar_wait(sb + OFF_CBAR, 0);
          TS(wg, 6);
#pragma unroll
          for (int h = 0; h < 2; h++) {
            const float2 c = lds_f2(sb + OFF_CARRY + wg * 512 + (w * 16 + gr + 8 * h) * 8);
            hst[h] = cfma(lq[h], cplx{c.x, c.y}, pre[h]);
          }
        }
        const int j0 = (kb - 4) * 2;
        uint32_t rr[4], ri[4];
#pragma unroll
        for (int jj = 0; jj < 2; jj++) {
          const int j = j0 + jj;
          const uint32_t g2 = lds_u(sb + OFF_GS + (wg * 64 + j * 8 + q * 2) * 2);
#pragma unroll
          for (int h = 0; h < 2; h++) {
            const int i = 4 * j + 2 * h;
            const cplx h0 = cfma(lam[h], hst[h], cplx{ure[i], uim[i]});
            hst[h] = cfma(lam[h], h0, cplx{ure[i + 1], uim[i + 1]});
            rr[jj * 2 + h] = bf2_mul(pack_bf16(h0.re, hst[h].re), g2);
            ri[jj * 2 + h] = bf2_mul(pack_bf16(h0.im, hst[h].im), g2 ^ 0x80008000u);
          }
        }
        const uint32_t a = hst_addr ^ (j0 << 4);
        asm volatile("stmatrix.sync.aligned.m8n8.x4.shared.b16 [%0], {%1,%2,%3,%4};" ::"r"(a), "r"(rr[0]), "r"(rr[1]), "r"(rr[2]), "r"(rr[3]) : "memory");
        asm volatile("stmatrix.sync.aligned.m8n8.x4.shared.b16 [%0], {%1,%2,%3,%4};" ::"r"(a + him), "r"(ri[0]), "r"(ri[1]), "r"(ri[2]), "r"(ri[3]) : "memory");
      }
    }
    TS(wg, 7);

    uint4* const psend = g_part + (size_t)(m * 8 + rank) * 3072 + warp * 128 + lane;
    const uint4* const precv = g_part + (size_t)(m * 8 + s) * 3072 + warp * 128 + lane;
    const uint32_t pbuf = OFF_X + warp * 2048 + lane * 16;
    const uint32_t dx0 = ((sb + OFF_X) & 0x3FFFF) >> 4;
    float o[32], fin[32], rho[2];
    uint32_t tr[8];
    uint32_t r0[16], pt[16], sum[16], tag;
    auto recv_issue = [&](uint32_t (&r)[16], int k) {
#pragma unroll
      for (int i = 0; i < 4; i++) ld_b128(precv + k * 1024 + i * 32, r[4 * i], r[4 * i + 1], r[4 * i + 2], r[4 * i + 3]);
    };
    auto stale = [&](uint32_t (&r)[16]) {
      uint32_t t0, t1, r_;
      asm("lop3.b32 %0, %1, %2, %3, 0x7e;" : "=r"(t0) : "r"(r[0]), "r"(r[4]), "r"(tag));
      asm("lop3.b32 %0, %1, %2, %3, 0x7e;" : "=r"(t1) : "r"(r[8]), "r"(r[12]), "r"(tag));
      asm volatile("{.reg .pred p; .reg .b32 t; lop3.b32 t, %1, %2, 1, 0xa8; setp.ne.u32 p, t, 0; vote.sync.any.pred p, p, 0xffffffff; selp.u32 %0, 1, 0, p;}" : "=r"(r_) : "r"(t0), "r"(t1));
      return r_ != 0;
    };
    auto recv_check = [&](uint32_t (&r)[16], int k) {
      if (__builtin_expect(stale(r), 0)) {
        int tries = 0;
#pragma unroll 1
        do { recv_issue(r, k); } while (stale(r) && ++tries < 200000);
      }
    };
    auto gelu_b = [&](int i0, int i1) {
#pragma unroll
      for (int i = i0; i < i1; i++) {
        pin(ab[2 * i]); pin(ab[2 * i + 1]);
        H[24 + i] = gelu2_pair(ab[2 * i], ab[2 * i + 1]);
        pin(H[24 + i]);
      }
    };
    auto step = [&](float (&d)[32], int p, int k, int acc) {
      const uint32_t wo = stage_off(p);
      if (k >= 6 && k < 14) {
        const int kk = k - 6;
        wgmma_n64_rs<0, DH128>(d, hf[4 * kk], hf[4 * kk + 1], hf[4 * kk + 2], hf[4 * kk + 3], dx0, wo + 14336 + (kk >> 2) * 8192 + (kk & 3) * 32, 1);
      } else {
        const int kk = k < 6 ? k : k - 8;
        wgmma_n64_rs<1, DH128>(d, H[4 * kk], H[4 * kk + 1], H[4 * kk + 2], H[4 * kk + 3], dx0, wo + (kk / 7) * 30720 + (kk % 7) * 2048, k != 0 || acc);
      }
    };
    auto mma = [&](float (&d)[32], int p, int k0, int k1, int acc) {
      wg_fence();
#pragma unroll
      for (int k = k0; k < k1; k++) step(d, p, k, acc);
      wg_commit();
    };
    auto send_peer = [&]() {
#pragma unroll
      for (int i = 0; i < 4; i++)
        asm volatile("st.async.shared::cluster.mbarrier::complete_tx::bytes.v4.b32 [%0], {%1,%2,%3,%4}, [%5];" ::"r"(peer + pbuf + i * 512),
                     "r"(pack_bf16(o[8 * i], o[8 * i + 1])), "r"(pack_bf16(o[8 * i + 2], o[8 * i + 3])), "r"(pack_bf16(o[8 * i + 4], o[8 * i + 5])),
                     "r"(pack_bf16(o[8 * i + 6], o[8 * i + 7])), "r"(peer + OFF_RBAR + wg * 8) : "memory");
    };
    auto recv_peer = [&](int k) {
      mbar_wait(sb + OFF_RBAR + wg * 8, k & 1);
#pragma unroll
      for (int i = 0; i < 4; i++) { const uint4 v = lds_u4(sb + pbuf + i * 512); pt[4 * i] = v.x; pt[4 * i + 1] = v.y; pt[4 * i + 2] = v.z; pt[4 * i + 3] = v.w; }
    };
    auto send_owner = [&](float (&d)[32], int k) {
#pragma unroll
      for (int i = 0; i < 4; i++) {
#pragma unroll
        for (int c = 4 * i; c < 4 * i + 4; c++) pt[c] = bf2_add(pt[c], pack_bf16(d[2 * c], d[2 * c + 1]));
        asm("lop3.b32 %0, %0, 1, %1, 0xb8;" : "+r"(pt[4 * i]) : "r"(tag));
        st_b128(psend + (((sp + 1 + k) & 3) * 6 + k) * 1024 + i * 32, pt[4 * i], pt[4 * i + 1], pt[4 * i + 2], pt[4 * i + 3]);
      }
      __syncwarp();
      credit();
    };
    auto load_fin = [&]() {
      mbar_wait(sb + OFF_LBAR, 1);
#pragma unroll
      for (int j = 0; j < 8; j++) {
        const uint4 v = lds_u4(sb + pbuf + 16384 + (j >> 2) * 16384 + (j & 3) * 512);
        fin[4 * j] = __uint_as_float(v.x); fin[4 * j + 1] = __uint_as_float(v.y); fin[4 * j + 2] = __uint_as_float(v.z); fin[4 * j + 3] = __uint_as_float(v.w);
      }
    };
    auto arm = [&]() { if ((threadIdx.x & 127) == 0) mbar_expect_tx(sb + OFF_RBAR + wg * 8, 8192); };
#pragma unroll
    for (int p = 0; p < 8; p++) {
      if (p == 0) {
        mbar_wait(fullb, 0);
        mma(o, 0, 0, 3, 0);
        wg_wait<1>(); release(5);
        gelu_b(0, 4);
        mma(o, 0, 3, 6, 0);
        bar_sync(1 + wg, 128);
        {
          const uint32_t ha = xw + ((lane >> 4) * 8 + (lane & 7)) * 128 + (((2 * w + ((lane >> 3) & 1)) ^ (lane & 7)) << 4);
#pragma unroll
          for (int kk = 0; kk < 8; kk++)
            asm volatile("ldmatrix.sync.aligned.m8n8.x4.trans.shared.b16 {%0,%1,%2,%3}, [%4];" : "=r"(hf[4 * kk]), "=r"(hf[4 * kk + 1]), "=r"(hf[4 * kk + 2]), "=r"(hf[4 * kk + 3])
                         : "r"(ha + (kk >> 2) * him + (kk & 3) * 2048) : "memory");
        }
        gelu_b(4, 10);
        mbar_wait(fullb + 8, 0);
        mma(o, 0, 6, 10, 0);
        credit();
        gelu_b(10, 16);
        mma(o, 0, 10, 15, 0);
        gelu_b(16, 24);
        mbar_wait(fullb + 16, 0);
        mma(o, 0, 15, 18, 0);
        gelu_b(24, 32);
        if (wg == 1) bar_sync(4, 256);
        mma(o, 0, 18, 22, 0);
      } else {
        TR(0);
        if (EW == 0 || (EW == 1 && (p & 1))) mbar_wait(sb + OFF_XFULL + 8 * p, 1);
        TR(1);
        bar_sync(3 + wg, 256);
        if (p < 7) mma(o, p, 0, 22, 0);
        else if (GAP == 0) mma(fin, p, 0, 22, 1);
        else {
          mma(fin, p, 0, GAP, 1);
          recv_peer(3);
          tag = lds_u(sb + OFF_EPOCH);
          mma(fin, p, GAP, 22, 1);
        }
      }
      if (p < 7 || wg == 0) bar_arrive(4 - wg, 256);
      TR(2);
      if (p != TP) TS(wg, 8 + p);
      if (p < 7 && (EW == 2 || (EW == 1 && (p & 1)))) mbar_wait(sb + OFF_XFULL + 8 * (p + 1), 1);
      if ((p & 1) == 0) {
        arm();
        if (p == 6) {
          mbar_wait(sb + OFF_EMPTY + 32, 0);
          tag = lds_u(sb + OFF_EPOCH);
          recv_check(sum, 0); recv_check(r0, 1);
#pragma unroll
          for (int i = 0; i < 16; i++) sum[i] = bf2_add(sum[i], r0[i]);
        }
        TR(3);
        mbar_wait(sb + OFF_KBAR + wg * 8, (p >> 1) & 1);
        TR(4);
      } else {
        if (p == 1 || (p == 7 && GAP == 0)) tag = lds_u(sb + OFF_EPOCH);
        TR(3);
        if (p < 7 || GAP == 0) recv_peer(p >> 1);
        TR(4);
        if (p == 7) {
          recv_check(r0, 2);
#pragma unroll
          for (int i = 0; i < 16; i++) sum[i] = bf2_add(sum[i], bf2_add(r0[i], pt[i]));
        }
      }
      if (p == FINP && !FINW) load_fin();
      TR(5);
      wg_wait<0>();
      TR(6);
      if (p < 5) release(p);
      if (p < 7) reg_fence(o); else reg_fence(fin);
      if ((p & 1) == 0) {
        if (p == 6) recv_issue(r0, 2);
        send_peer();
        if (p == FINP && FINW) load_fin();
        if (p == 4) { recv_issue(sum, 0); recv_issue(r0, 1); }
      } else if (p < 7) {
        send_owner(o, p >> 1);
      }
      if (p == 2) {
#pragma unroll
        for (int h = 0; h < 2; h++) { rho[h] = __fdividef(2.f, 4.f + bf_lo(lds_h(sb + OFF_GS + (wg * 64 + w * 16 + gr + 8 * h) * 2))); pin(rho[h]); }
      }
      TR(7);
    }
    {
      TS(wg, 16);
      const uint32_t tb = sb + OFF_X + stage_off(0) + warp * 4096;
      const uint32_t ta = tb + gr * 256 + ((gr & 3) << 5) + q * 8;
      const uint32_t la = tb + (lane >> 3) * 256 + (((lane & 7) << 4) ^ ((lane >> 3) << 5));
      float* op = out + (size_t)(m * 128 + wg * 64 + (lane >> 4) * 16 + w * 4 + ((lane >> 3) & 1)) * DM + s * 64 + (lane & 7) * 4;
#pragma unroll
      for (int qq = 0; qq < 4; qq += QS) {
#pragma unroll
        for (int qt = qq; qt < qq + QS; qt++) {
          const int h = qt & 1, ch = qt >> 1;
#pragma unroll
          for (int j = 0; j < 4; j++) {
            const int i = ch * 8 + j * 2 + h;
            asm volatile("st.shared.v2.f32 [%0], {%1,%2};" ::"r"((ta ^ (j << 5)) + h * 2048 + ch * 128),
                         "f"((fin[2 * i] + bf_lo(sum[i])) * rho[h]), "f"((fin[2 * i + 1] + bf_hi(sum[i])) * rho[h]) : "memory");
          }
        }
        __syncwarp();
#pragma unroll
        for (int qt = qq; qt < qq + QS; qt++) {
          const int h = qt & 1, ch = qt >> 1;
#pragma unroll
          for (int r = 0; r < 2; r++)
            *reinterpret_cast<uint4*>(op + (r * 32 + h * 2) * DM + ch * 32) = lds_u4(la + (h * 2 + r) * 1024 + ch * 128);
        }
      }
      if (threadIdx.x == 128) g_epoch[b] = tag;
      TS(wg, 17); TG(wg); TRD(); TDUMP();
    }
  } else {
    asm volatile("setmaxnreg.dec.sync.aligned.u32 56;");
    int wsel = warp;
    asm("" : "+r"(wsel));
    if (wsel > 8) {
      if (warp != 11) {
        const int t = threadIdx.x - 288;
        unsigned par;
        asm volatile("ld.relaxed.gpu.global.u32 %0, [%1];" : "=r"(par) : "l"(g_epoch + b) : "memory");
        const float pr = bf_ld(lam_re + s * 64 + t), pi = bf_ld(lam_im + s * 64 + t), pd = bf_ld(log_dt + s * 64 + t);
        asm volatile("barrier.cluster.wait.aligned;" ::: "memory");
        par = __shfl_sync(0xffffffffu, (par + 1) & 1, 0);
        cplx l64 = make_lam(pr, pi, pd);
        {
          const float inv = __fdividef(1.f, fmaf(pr, pr, pi * pi));
          const cplx cf = cmul(cplx{l64.re - 1.f, l64.im}, cplx{pr * inv, -pi * inv});
          asm volatile("st.shared.v4.f32 [%0], {%1,%2,%3,%4};" ::"r"(sb + OFF_LC + t * 16), "f"(l64.re), "f"(l64.im), "f"(cf.re), "f"(cf.im) : "memory");
          mbar_arrive(sb + OFF_LBAR);
        }
#pragma unroll
        for (int i = 0; i < 6; i++) l64 = cmul(l64, l64);
        cplx l128 = cmul(l64, l64);
        pin(l128.re); pin(l128.im);
        uint32_t vr[15], vi[15];
#pragma unroll
        for (int i = 0; i < 15; i++) { vr[i] = par; vi[i] = 0; pin(vr[i]); pin(vi[i]); }
        mbar_wait(sb + OFF_GBAR, 0);
        const float2 e0 = lds_f2(sb + OFF_CARRY + t * 8), e1 = lds_f2(sb + OFF_CARRY + 512 + t * 8);
        float2* eb = g_end + s * 1024 + t;
        {
          const cplx e = cfma(l64, cplx{e0.x, e0.y}, cplx{e1.x, e1.y});
          const unsigned long long v = ((unsigned long long)__float_as_uint(e.im) << 32) | ((__float_as_uint(e.re) & ~1u) | par);
          asm volatile("st.relaxed.gpu.global.b64 [%0], %1;" ::"l"(eb + m * 64), "l"(v) : "memory");
        }
        if (t == 0) TS(3, 1);
        cplx S = {0.f, 0.f};
        {
          if (LBD) __nanosleep(LBD);
          const float2* e15 = eb + (m - 15) * 64;
          int tries = 0;
          bool bad;
#pragma unroll 1
          do {
#pragma unroll
            for (int i = 0; i < 15; i++)
              asm volatile("{.reg .pred p; .reg .b64 v; mov.b64 v, {%0,%1}; setp.ge.s32 p, %3, %4; @p ld.relaxed.gpu.global.b64 v, [%2]; mov.b64 {%0,%1}, v;}"
                           : "+r"(vr[i]), "+r"(vi[i]) : "l"(e15 + i * 64), "r"(m), "r"(15 - i) : "memory");
            uint32_t x = vr[0] ^ par;
#pragma unroll
            for (int i = 1; i < 15; i++) asm("lop3.b32 %0, %0, %1, %2, 0xf6;" : "+r"(x) : "r"(vr[i]), "r"(par));
            bad = __any_sync(0xffffffffu, x & 1);
          } while (bad && ++tries < 200000);
          if (t == 0) TS(3, 2);
          S = cplx{__uint_as_float(vr[0]), __uint_as_float(vi[0])};
#pragma unroll
          for (int i = 1; i < 15; i++) S = cfma(l128, S, cplx{__uint_as_float(vr[i]), __uint_as_float(vi[i])});
        }
        const cplx S1 = cfma(l64, S, cplx{e0.x, e0.y});
        asm volatile("st.shared.v2.f32 [%0], {%1,%2};" ::"r"(sb + OFF_CARRY + t * 8), "f"(S.re), "f"(S.im) : "memory");
        asm volatile("st.shared.v2.f32 [%0], {%1,%2};" ::"r"(sb + OFF_CARRY + 512 + t * 8), "f"(S1.re), "f"(S1.im) : "memory");
        mbar_arrive(sb + OFF_CBAR);
        if (t == 0) TS(3, 3);
        mbar_wait(sb + OFF_CBAR, 0);
        const int gr = lane >> 2, q = lane & 3;
        float2 db[8];
#pragma unroll
        for (int j = 0; j < 8; j++) db[j] = lds_f2(sb + OFF_DB + j * 32 + q * 8);
        mbar_wait(sb + OFF_XFULL + 16, 1);
        mbar_wait(sb + OFF_EMPTY, 0);
#pragma unroll 1
        for (int cw = warp - 9; cw < 8; cw += 2) {
          const float r0 = 0.5f * bf_lo(lds_h(sb + OFF_GS + (cw * 16 + gr) * 2)), r1 = 0.5f * bf_lo(lds_h(sb + OFF_GS + (cw * 16 + gr) * 2 + 16));
          const uint32_t xa = sb + OFF_X + (1 + rank) * 16384 + (cw * 16 + (lane & 15)) * 128 + (((lane >> 4) ^ (lane & 7)) << 4);
          uint32_t xv[16];
#pragma unroll
          for (int i = 0; i < 4; i++)
            asm volatile("ldmatrix.sync.aligned.m8n8.x4.shared.b16 {%0,%1,%2,%3}, [%4];" : "=r"(xv[4 * i]), "=r"(xv[4 * i + 1]), "=r"(xv[4 * i + 2]), "=r"(xv[4 * i + 3])
                         : "r"(xa ^ (i << 5)) : "memory");
          __syncwarp();
#pragma unroll
          for (int j = 0; j < 8; j++) {
            const uint32_t x0 = bf2_mul(xv[2 * j], __float_as_uint(db[j].x)), x1 = bf2_mul(xv[2 * j + 1], __float_as_uint(db[j].x));
            pin(db[j].y);
            const float bl = bf_lo(__float_as_uint(db[j].y)), bh = bf_hi(__float_as_uint(db[j].y));
            asm volatile("st.shared.v4.f32 [%0], {%1,%2,%3,%4};" ::"r"(sb + OFF_X + 16384 + (j >> 2) * 16384 + cw * 2048 + (j & 3) * 512 + lane * 16), "f"(fmaf(bf_lo(x0), r0, bl)),
                         "f"(fmaf(bf_hi(x0), r0, bh)), "f"(fmaf(bf_lo(x1), r1, bl)), "f"(fmaf(bf_hi(x1), r1, bh)) : "memory");
          }
        }
        mbar_arrive(sb + OFF_LBAR);
        if (t == 0) TS(3, 5);
      } else {
        if (lane == 0) TG(2);
        const uint4* gwp = reinterpret_cast<const uint4*>(gate_w) + (lane & 7);
        uint4 gw[4];
#pragma unroll
        for (int i = 0; i < 4; i++) gw[i] = __ldg(gwp + i * 8);
        unsigned par;
        asm volatile("ld.relaxed.gpu.global.u32 %0, [%1];" : "=r"(par) : "l"(g_epoch + b) : "memory");
        const uint32_t dk = __ldg(reinterpret_cast<const uint32_t*>(dskip + s * 64) + lane), bb = __ldg(reinterpret_cast<const uint32_t*>(b2 + s * 64) + lane);
        asm volatile("barrier.cluster.wait.aligned;" ::: "memory");
        const int row = s * 16 + (lane >> 3);
        const uint32_t xr0 = sb + OFF_X + row * 128 + (((lane & 7) ^ (row & 7)) << 4), xr1 = (xr0 + 512) ^ 64;
        float z[4] = {0.f, 0.f, 0.f, 0.f};
#pragma unroll
        for (int kb = 0; kb < 8; kb++) {
          const uint32_t wv[4] = {gw[kb & 3].x, gw[kb & 3].y, gw[kb & 3].z, gw[kb & 3].w};
          if (kb < 4) gw[kb] = __ldg(gwp + (kb + 4) * 8);
          mbar_wait(sb + OFF_XFULL + 8 * kb, 0);
          if ((PF & 2) && kb == PFK && elect_one()) {
            l2_prefetch(pf_w1 + b * 7168, 14336);
            l2_prefetch(pf_cre + b * 2048, 4096);
            l2_prefetch(pf_cim + b * 2048, 4096);
            l2_prefetch(pf_w2 + b * 7168, 14336);
          }
          const uint32_t xo = ((kb + xrot) & 7) * 16384;
#pragma unroll
          for (int r = 0; r < 4; r++) {
            const uint4 a = lds_u4(((r & 1) ? xr1 : xr0) + xo + (r >> 1) * 1024);
            const uint32_t p = bf2_fma(a.w, wv[3], bf2_fma(a.z, wv[2], bf2_fma(a.y, wv[1], bf2_mul(a.x, wv[0]))));
            z[r] += bf_lo(p); z[r] += bf_hi(p);
          }
        }
        if (lane == 0) asm volatile("st.shared.u32 [%0], %1;" ::"r"(sb + OFF_EPOCH), "r"(par + 1) : "memory");
        par = (par + 1) & 1;
        {
          float y0 = (lane & 4) ? z[1] : z[0], y1 = (lane & 4) ? z[3] : z[2];
          y0 += __shfl_xor_sync(0xffffffffu, (lane & 4) ? z[0] : z[1], 4);
          y1 += __shfl_xor_sync(0xffffffffu, (lane & 4) ? z[2] : z[3], 4);
          float zz = (lane & 2) ? y1 : y0;
          zz += __shfl_xor_sync(0xffffffffu, (lane & 2) ? y0 : y1, 2);
          zz += __shfl_xor_sync(0xffffffffu, zz, 1);
          const float rho = 4.f * expf(zz > 40.f ? 40.f : zz);
          if ((lane & 1) == 0)
            asm volatile("st.relaxed.gpu.global.u32 [%0], %1;" ::"l"(g_gate + m * 128 + row + (lane & 4) + (lane & 2) * 4), "r"((__float_as_uint(rho) & ~1u) | par) : "memory");
        }
        if ((PF & 8) && elect_one()) {
          l2_prefetch(pf_w2 + b * 7168, 14336);
          l2_prefetch(pf_cre + b * 2048, 4096);
          l2_prefetch(pf_cim + b * 2048, 4096);
        }
        if (lane == 0) TS(3, 0);
        mbar_wait(sb + OFF_GBAR, 0);
        asm volatile("st.shared.v2.u32 [%0], {%1,%2};" ::"r"(sb + OFF_DB + lane * 8), "r"(dk), "r"(bf2_add(bb, bb)) : "memory");
        uint32_t g0, g1, g2, g3;
        int tries = 0;
#pragma unroll 1
        do {
          asm volatile("ld.relaxed.gpu.global.v4.u32 {%0,%1,%2,%3}, [%4];" : "=r"(g0), "=r"(g1), "=r"(g2), "=r"(g3) : "l"(g_gate + m * 128 + lane * 4) : "memory");
        } while ((((g0 ^ par) | (g1 ^ par) | (g2 ^ par) | (g3 ^ par)) & 1) && ++tries < 200000);
        asm volatile("st.shared.v2.u32 [%0], {%1,%2};" ::"r"(sb + OFF_GS + lane * 8), "r"(pack_bf16(__uint_as_float(g0), __uint_as_float(g1))),
                     "r"(pack_bf16(__uint_as_float(g2), __uint_as_float(g3))) : "memory");
        mbar_arrive(sb + OFF_CBAR);
        if (lane == 0) TS(3, 4);
      }
    } else {
      asm volatile("barrier.cluster.wait.aligned;" ::: "memory");
      if (elect_one()) {
        TS(2, 1);
        const uint32_t t0 = clock();
#pragma unroll 1
        for (int u = 0; u < 8; u++) {
          if (u >= 1) while ((uint32_t)clock() - t0 < D0 + (u - 1) * D1) {}
          mbar_expect_tx(sb + OFF_XFULL + 8 * u, 16384);
          tma5d_mc(sb + OFF_X + ((u + xrot) & 7) * 16384 + rank * 8192, &maps.x, u * 64, 2 * m + rank, sb + OFF_XFULL + 8 * u);
          if (u < 6) {
            mbar_expect_tx(sb + OFF_FULL + 8 * u, 16384);
            tma2d(sb + OFF_RING + u * 16384, &maps.bre, u * 64, s * 64, sb + OFF_FULL + 8 * u);
            tma2d(sb + OFF_RING + u * 16384 + 8192, &maps.bim, u * 64, s * 64, sb + OFF_FULL + 8 * u);
          } else if (PF & 4) {
            asm volatile("cp.async.bulk.prefetch.tensor.2d.L2.global [%0, {%1,%2}];" ::"l"((m & 1) ? &maps.bim : &maps.bre), "r"(u * 64), "r"(s * 64) : "memory");
          }
        }
        TS(2, 5);
        int slot = 0; uint32_t ph = 0;
#pragma unroll 1
        for (int u = 6; u < 24; u++) {
          const uint32_t fb = sb + OFF_FULL + 8 * slot, dst = sb + OFF_RING + slot * 16384;
          mbar_wait(sb + OFF_EMPTY + 8 * slot, ph);
          TS2(0, u);
          if (u < 8) {
            mbar_expect_tx(fb, 16384);
            tma2d(dst, &maps.bre, u * 64, s * 64, fb);
            tma2d(dst + 8192, &maps.bim, u * 64, s * 64, fb);
          } else if (u < 16) {
            mbar_expect_tx(fb, 12288);
            tma3d(dst, &maps.w1b, 0, (u - 8) * 64, s * 7, fb);
          } else {
            mbar_expect_tx(fb, 16384);
            tma2d(dst, &maps.w1a, s * 224 + 96, ((u - xrot) & 7) * 64, fb);
            tma2d(dst + 8192, &maps.w1a, s * 224 + 160, ((u - xrot) & 7) * 64, fb);
          }
          if (++slot == NSLOT) { slot = 0; ph ^= 1; }
        }
#pragma unroll 1
        for (int j = 0; j < 3; j++) {
          const uint32_t fb = sb + OFF_FULL + 8 * j, dst = sb + OFF_X + stage_off(0);
          const int c = ((sp + 1) & 3) * 128 + ((rank ^ 1) << 6);
          mbar_wait(sb + OFF_EMPTY + 8 + 8 * j, 1);
          mbar_expect_tx(fb, j == 1 ? 16384 : 14336);
          if (j == 1) {
            tma2d(dst + 14336, &maps.cre, s * 64, c, fb);
            tma2d(dst + 22528, &maps.cim, s * 64, c, fb);
          } else {
            tma2d(dst + j * 15360, &maps.w2, c, s * 224 + j * 56, fb);
          }
        }
#pragma unroll 1
        for (int p = 1; p < 8; p++) {
          const int c = ((sp + 1 + (p >> 1)) & 3) * 128 + (((rank ^ p ^ 1) & 1) << 6);
          const uint32_t fb = sb + OFF_XFULL + 8 * p, dst = sb + OFF_X + stage_off(p);
          if (p == 2 || p > 3) mbar_wait(sb + OFF_EMPTY + (p == 2 ? 40 : (p - 4) * 8), p == 2);
          TS2(0, 32 + p);
          mbar_expect_tx(fb, 45056);
          tma2d(dst, &maps.w2, c, s * 224, fb);
          tma2d(dst + 14336, &maps.cre, s * 64, c, fb);
          tma2d(dst + 22528, &maps.cim, s * 64, c, fb);
          tma2d(dst + 30720, &maps.w2, c, s * 224 + 112, fb);
        }
        TS(2, 2);
      }
    }
  }
}

typedef CUresult (*EncFn)(CUtensorMap*, CUtensorMapDataType, cuuint32_t, void*, const cuuint64_t*, const cuuint64_t*, const cuuint32_t*,
                          const cuuint32_t*, CUtensorMapInterleave, CUtensorMapSwizzle, CUtensorMapL2promotion, CUtensorMapFloatOOBfill);

void encode(EncFn f, CUtensorMap* mp, const void* p, int rank, const cuuint64_t* dims, const cuuint64_t* strides, const cuuint32_t* box, CUtensorMapSwizzle sw) {
  cuuint32_t es[5] = {1, 1, 1, 1, 1};
  f(mp, CU_TENSOR_MAP_DATA_TYPE_BFLOAT16, rank, const_cast<void*>(p), dims, strides, box, es, CU_TENSOR_MAP_INTERLEAVE_NONE, sw,
    CU_TENSOR_MAP_L2_PROMOTION_L2_128B, CU_TENSOR_MAP_FLOAT_OOB_FILL_NONE);
}

}

extern "C" void kernel_launch(void* const* d_in, const int* in_sizes, int n_in, void* d_out, int out_size) {
  typedef const __nv_bfloat16* bp;
  bp x = (bp)d_in[0], lre = (bp)d_in[1], lim = (bp)d_in[2], bre = (bp)d_in[3], bim = (bp)d_in[4], cre = (bp)d_in[5], cim = (bp)d_in[6],
     ldt = (bp)d_in[7], dsk = (bp)d_in[8], w1 = (bp)d_in[10], b1 = (bp)d_in[11], w2 = (bp)d_in[12], b2 = (bp)d_in[13], gw = (bp)d_in[14];
  static EncFn enc = nullptr;
  if (!enc) {
    void* f = nullptr;
    cudaDriverEntryPointQueryResult qr;
    cudaGetDriverEntryPoint("cuTensorMapEncodeTiled", &f, cudaEnableDefault, &qr);
    enc = (EncFn)f;
    cudaFuncSetAttribute(fused_kernel, cudaFuncAttributeMaxDynamicSharedMemorySize, SMEM_BYTES);
  }
  Maps maps;
  {
    cuuint64_t d[5] = {DM, 2, 4, 8, SEQ / 64}, st[4] = {DM * 2, 16 * DM * 2, 2 * DM * 2, 64 * DM * 2};
    cuuint32_t bx[5] = {64, 2, 4, 8, 1};
    encode(enc, &maps.x, x, 5, d, st, bx, CU_TENSOR_MAP_SWIZZLE_128B);
  }
  {
    cuuint64_t d[2] = {DM, DM}, st[1] = {DM * 2};
    cuuint32_t bx[2] = {64, 64};
    encode(enc, &maps.bre, bre, 2, d, st, bx, CU_TENSOR_MAP_SWIZZLE_128B);
    encode(enc, &maps.bim, bim, 2, d, st, bx, CU_TENSOR_MAP_SWIZZLE_128B);
    encode(enc, &maps.cre, cre, 2, d, st, bx, CU_TENSOR_MAP_SWIZZLE_128B);
    encode(enc, &maps.cim, cim, 2, d, st, bx, CU_TENSOR_MAP_SWIZZLE_128B);
  }
  {
    cuuint64_t d[2] = {FF, DM}, st[1] = {FF * 2};
    cuuint32_t bx[2] = {64, 64};
    encode(enc, &maps.w1a, w1, 2, d, st, bx, CU_TENSOR_MAP_SWIZZLE_128B);
    cuuint64_t d3[3] = {32, DM, FF / 32}, st3[2] = {FF * 2, 64};
    cuuint32_t bx3[3] = {32, 64, 3};
    encode(enc, &maps.w1b, w1, 3, d3, st3, bx3, CU_TENSOR_MAP_SWIZZLE_64B);
  }
  {
    cuuint64_t d[2] = {DM, FF}, st[1] = {DM * 2};
    cuuint32_t bx[2] = {64, 112};
    encode(enc, &maps.w2, w2, 2, d, st, bx, CU_TENSOR_MAP_SWIZZLE_128B);
  }
  fused_kernel<<<128, 384, SMEM_BYTES>>>(x, bre, bim, lre, lim, ldt, dsk, b1, b2, gw, w1, w2, cre, cim, (float*)d_out, maps);
}
```

```cpp
#include <cuda_runtime.h>
#include <cuda_bf16.h>
#include <cuda.h>
#include <stdint.h>

#define MAP 1
#define D0 600
#define D1 500
#define PF 20
#define PFK 5
#define GELUP 1
#define EW 2
#define K1E 1
#define K2E 0
#define QS 1
#define K2G 4
#define FINP 4
#define LBD 300
#define PFS 32
#define SB0 2
#define PFD 2
#define HOLD 0
#define GAP 14
#define FINW 0
#define K0P 33
#define K1P 53
#define TP 9
#define TW 0

namespace {

constexpr int SEQ = 2048, DM = 512, FF = 1792;
constexpr int NSLOT = 6;
constexpr uint32_t OFF_X = 0, OFF_RING = 131072, OFF_MISC = 229376;
constexpr uint32_t OFF_XFULL = OFF_MISC, OFF_FULL = OFF_XFULL + 64, OFF_RBAR = OFF_FULL + 48, OFF_EMPTY = OFF_RBAR + 16, OFF_KBAR = OFF_EMPTY + 48,
                   OFF_GBAR = OFF_KBAR + 16, OFF_LBAR = OFF_GBAR + 8, OFF_CBAR = OFF_LBAR + 8, OFF_EPOCH = OFF_CBAR + 8;
constexpr uint32_t OFF_LC = OFF_MISC + 256;
constexpr uint32_t OFF_GS = OFF_LC;
constexpr uint32_t OFF_DB = OFF_LC + 512;
constexpr uint32_t OFF_CARRY = OFF_LC + 1024;
constexpr uint32_t OFF_DBG = OFF_CARRY + 1024;
constexpr uint32_t SMEM_BYTES = OFF_DBG + 768;
static_assert(SMEM_BYTES <= 232448, "smem");

struct Maps { CUtensorMap x, bre, bim, w1b, w1a, w2, cre, cim; };
__host__ __device__ constexpr uint32_t stage_off(int p) { return 49152 + 45056 * (((p >> 1) & 1) + 2 * (p & 1)); }

__device__ uint4 g_part[16 * 8 * 3 * 1024];
__device__ float2 g_end[8 * 16 * 64];
__device__ unsigned g_gate[SEQ];
__device__ unsigned g_epoch[128];
#define TG(role) do {} while (0)
#define TS2(role, i) do {} while (0)
#define TS(role, i) do {} while (0)
#define TDUMP() do {} while (0)
#define TR(i) do {} while (0)
#define TRD() do {} while (0)

__device__ __forceinline__ void mbar_init(uint32_t bar, uint32_t cnt) { asm volatile("mbarrier.init.shared::cta.b64 [%0], %1;" ::"r"(bar), "r"(cnt)); }
__device__ __forceinline__ void mbar_expect_tx(uint32_t bar, uint32_t bytes) { asm volatile("mbarrier.arrive.expect_tx.shared::cta.b64 _, [%0], %1;" ::"r"(bar), "r"(bytes) : "memory"); }
__device__ __forceinline__ void mbar_arrive(uint32_t bar) { asm volatile("mbarrier.arrive.shared::cta.b64 _, [%0];" ::"r"(bar) : "memory"); }
__device__ __forceinline__ void mbar_arrive_cl(uint32_t cbar) { asm volatile("mbarrier.arrive.shared::cluster.b64 _, [%0];" ::"r"(cbar) : "memory"); }
__device__ __forceinline__ void mbar_wait(uint32_t bar, uint32_t parity) {
  asm volatile(
      "{\n.reg .pred p;\n.reg .u32 c;\n"
      "mbarrier.try_wait.parity.shared::cta.b64 p, [%0], %1;\n"
      "@p bra.uni LAB_DONE;\n"
      "mov.u32 c, 0;\n"
      "LAB_WAIT:\n"
      "mbarrier.try_wait.parity.shared::cta.b64 p, [%0], %1;\n"
      "@p bra.uni LAB_DONE;\n"
      "add.u32 c, c, 1;\nsetp.lt.u32 p, c, 200000;\n@p bra.uni LAB_WAIT;\n"
      "LAB_DONE:\n}" ::"r"(bar), "r"(parity) : "memory");
}
__device__ __forceinline__ void tma2d(uint32_t dst, const CUtensorMap* m, int c0, int c1, uint32_t bar) {
  asm volatile("cp.async.bulk.tensor.2d.shared::cluster.global.mbarrier::complete_tx::bytes [%0], [%1, {%3,%4}], [%2];"
               ::"r"(dst), "l"(m), "r"(bar), "r"(c0), "r"(c1) : "memory");
}
__device__ __forceinline__ void tma3d(uint32_t dst, const CUtensorMap* m, int c0, int c1, int c2, uint32_t bar) {
  asm volatile("cp.async.bulk.tensor.3d.shared::cluster.global.mbarrier::complete_tx::bytes [%0], [%1, {%3,%4,%5}], [%2];"
               ::"r"(dst), "l"(m), "r"(bar), "r"(c0), "r"(c1), "r"(c2) : "memory");
}
__device__ __forceinline__ void tma5d_mc(uint32_t dst, const CUtensorMap* m, int c0, int c4, uint32_t bar) {
  asm volatile("cp.async.bulk.tensor.5d.shared::cluster.global.mbarrier::complete_tx::bytes.multicast::cluster [%0], [%1, {%3,%5,%5,%5,%4}], [%2], %6;"
               ::"r"(dst), "l"(m), "r"(bar), "r"(c0), "r"(c4), "r"(0), "h"((uint16_t)3) : "memory");
}
__device__ __forceinline__ void l2_prefetch(const void* p, uint32_t bytes) { asm volatile("cp.async.bulk.prefetch.L2.global [%0], %1;" ::"l"(p), "r"(bytes) : "memory"); }
__device__ __forceinline__ bool elect_one() {
  uint32_t pred;
  asm volatile("{.reg .pred P; elect.sync _|P, 0xffffffff; selp.u32 %0, 1, 0, P;}" : "=r"(pred));
  return pred != 0;
}
__device__ __forceinline__ void wg_fence() { asm volatile("wgmma.fence.sync.aligned;" ::: "memory"); }
__device__ __forceinline__ void wg_commit() { asm volatile("wgmma.commit_group.sync.aligned;" ::: "memory"); }
template <int N> __device__ __forceinline__ void wg_wait() { asm volatile("wgmma.wait_group.sync.aligned %0;" ::"n"(N) : "memory"); }
__device__ __forceinline__ void pin(float& a) { asm volatile("" : "+f"(a)::"memory"); }
__device__ __forceinline__ void pin(uint32_t& a) { asm volatile("" : "+r"(a)::"memory"); }
template <int N> __device__ __forceinline__ void reg_fence(float (&d)[N]) {
#pragma unroll
  for (int i = 0; i < N; i++) pin(d[i]);
}
__device__ __forceinline__ void bar_sync(int id, int n) { asm volatile("bar.sync %0, %1;" ::"r"(id), "r"(n) : "memory"); }
__device__ __forceinline__ void bar_arrive(int id, int n) { asm volatile("bar.arrive %0, %1;" ::"r"(id), "r"(n) : "memory"); }
constexpr uint32_t DH128 = (1024 >> 4) | (1u << 30), DH64 = (512 >> 4) | (2u << 30);
__host__ __device__ constexpr uint32_t lbo(uint32_t bytes) { return (bytes >> 4) << 20; }
__device__ __forceinline__ uint32_t pack_bf16(float lo, float hi) { uint32_t r; asm("cvt.rn.bf16x2.f32 %0, %1, %2;" : "=r"(r) : "f"(hi), "f"(lo)); return r; }
__device__ __forceinline__ float bf_lo(uint32_t v) { return __uint_as_float(v << 16); }
__device__ __forceinline__ float bf_hi(uint32_t v) { return __uint_as_float(v & 0xffff0000u); }
__device__ __forceinline__ float bf_ld(const __nv_bfloat16* p) { return __bfloat162float(__ldg(p)); }
__device__ __forceinline__ uint32_t late16(uint32_t bar) {
  uint32_t r;
  asm volatile("{.reg .pred p; mbarrier.test_wait.parity.shared::cta.b64 p, [%1], 0; selp.u32 %0, 16, 0, p;}" : "=r"(r) : "r"(bar) : "memory");
  return r;
}
__device__ __forceinline__ float2 lds_f2(uint32_t a) { float2 v; asm volatile("ld.shared.v2.f32 {%0,%1}, [%2];" : "=f"(v.x), "=f"(v.y) : "r"(a)); return v; }
__device__ __forceinline__ uint32_t lds_h(uint32_t a) { uint32_t v; asm volatile("ld.shared.u16 %0, [%1];" : "=r"(v) : "r"(a)); return v; }
__device__ __forceinline__ uint32_t lds_u(uint32_t a) { uint32_t v; asm volatile("ld.shared.u32 %0, [%1];" : "=r"(v) : "r"(a)); return v; }
__device__ __forceinline__ uint4 lds_u4(uint32_t a) { uint4 v; asm volatile("ld.shared.v4.u32 {%0,%1,%2,%3}, [%4];" : "=r"(v.x), "=r"(v.y), "=r"(v.z), "=r"(v.w) : "r"(a)); return v; }
__device__ __forceinline__ void st_b128(uint4* p, uint32_t a, uint32_t b, uint32_t c, uint32_t d) {
  asm volatile("st.relaxed.gpu.global.v4.b32 [%0], {%1,%2,%3,%4};" ::"l"(p), "r"(a), "r"(b), "r"(c), "r"(d) : "memory");
}
__device__ __forceinline__ void ld_b128(const uint4* p, uint32_t& a, uint32_t& b, uint32_t& c, uint32_t& d) {
  asm volatile("{.reg .b64 l, h; .reg .b128 v; ld.relaxed.gpu.global.b128 v, [%4]; mov.b128 {l,h}, v; mov.b64 {%0,%1}, l; mov.b64 {%2,%3}, h;}"
               : "=r"(a), "=r"(b), "=r"(c), "=r"(d) : "l"(p) : "memory");
}
__device__ __forceinline__ float tanh_fast(float x) { float y; asm("tanh.approx.f32 %0, %1;" : "=f"(y) : "f"(x)); return y; }
__device__ __forceinline__ float gelu2(float v) {
  float p = fmaf(v * v, 0.0356774081363f, 0.7978845608029f);
  return fmaf(v, tanh_fast(v * p), v);
}
__device__ __forceinline__ uint32_t bf2_mul(uint32_t a, uint32_t b) { uint32_t r; asm("mul.rn.bf16x2 %0, %1, %2;" : "=r"(r) : "r"(a), "r"(b)); return r; }
__device__ __forceinline__ uint32_t bf2_add(uint32_t a, uint32_t b) { uint32_t r; asm("add.rn.bf16x2 %0, %1, %2;" : "=r"(r) : "r"(a), "r"(b)); return r; }
__device__ __forceinline__ uint32_t bf2_fma(uint32_t a, uint32_t b, uint32_t c) { uint32_t r; asm("fma.rn.bf16x2 %0, %1, %2, %3;" : "=r"(r) : "r"(a), "r"(b), "r"(c)); return r; }
__device__ __forceinline__ uint32_t gelu2_pair(float a, float b) {
  const uint32_t v = pack_bf16(a, b);
  uint32_t t;
  asm("tanh.approx.bf16x2 %0, %1;" : "=r"(t) : "r"(bf2_fma(v, bf2_fma(bf2_mul(v, v), 0x3d123d12u, 0xbe4fbe4fu), v)));
  return bf2_fma(v, t, v);
}
struct cplx { float re, im; };
__device__ __forceinline__ cplx cmul(cplx a, cplx b) { return {fmaf(a.re, b.re, -a.im * b.im), fmaf(a.re, b.im, a.im * b.re)}; }
__device__ __forceinline__ cplx cfma(cplx a, cplx b, cplx c) {
  return {fmaf(a.re, b.re, fmaf(-a.im, b.im, c.re)), fmaf(a.re, b.im, fmaf(a.im, b.re, c.im))};
}
__device__ __forceinline__ cplx make_lam(float lre, float lim, float ldt) {
  float dt = __bfloat162float(__float2bfloat16_rn(expf(ldt)));
  float mag = expf(dt * lre), sn, cs;
  sincospif(dt * lim * 0.31830988618379067f, &sn, &cs);
  return {mag * cs, mag * sn};
}

template<int TA,int TB,uint32_t AH,uint32_t BH> __device__ __forceinline__ void wgmma_n64_ss(float (&d)[32], uint32_t al, uint32_t ao, uint32_t bl, uint32_t bo, int scale_d){
  asm volatile("{.reg .pred p; .reg .b32 t, v; .reg .b64 da, db; setp.ne.b32 p, %36, 0; add.u32 t, %32, %33; mov.b64 da, {t, %39}; add.u32 v, %34, %35; mov.b64 db, {v, %40};\n"
   "wgmma.mma_async.sync.aligned.m64n64k16.f32.bf16.bf16 {%0,%1,%2,%3,%4,%5,%6,%7,%8,%9,%10,%11,%12,%13,%14,%15,%16,%17,%18,%19,%20,%21,%22,%23,%24,%25,%26,%27,%28,%29,%30,%31}, da, db, p, 1, 1, %37, %38;}"
   : "+f"(d[0]),"+f"(d[1]),"+f"(d[2]),"+f"(d[3]),"+f"(d[4]),"+f"(d[5]),"+f"(d[6]),"+f"(d[7]),"+f"(d[8]),"+f"(d[9]),"+f"(d[10]),"+f"(d[11]),"+f"(d[12]),"+f"(d[13]),"+f"(d[14]),"+f"(d[15]),"+f"(d[16]),"+f"(d[17]),"+f"(d[18]),"+f"(d[19]),"+f"(d[20]),"+f"(d[21]),"+f"(d[22]),"+f"(d[23]),"+f"(d[24]),"+f"(d[25]),"+f"(d[26]),"+f"(d[27]),"+f"(d[28]),"+f"(d[29]),"+f"(d[30]),"+f"(d[31])
   : "r"(al),"r"(ao >> 4),"r"(bl),"r"(bo >> 4),"r"(scale_d),"n"(TA),"n"(TB),"n"(AH),"n"(BH));
}
template<int TB,uint32_t BH> __device__ __forceinline__ void wgmma_n64_rs(float (&d)[32], uint32_t a0,uint32_t a1,uint32_t a2,uint32_t a3, uint32_t bl, uint32_t bo, int scale_d){
  asm volatile("{.reg .pred p; .reg .b32 t; .reg .b64 db; setp.ne.b32 p, %38, 0; add.u32 t, %36, %37; mov.b64 db, {t, %40};\n"
   "wgmma.mma_async.sync.aligned.m64n64k16.f32.bf16.bf16 {%0,%1,%2,%3,%4,%5,%6,%7,%8,%9,%10,%11,%12,%13,%14,%15,%16,%17,%18,%19,%20,%21,%22,%23,%24,%25,%26,%27,%28,%29,%30,%31}, {%32,%33,%34,%35}, db, p, 1, 1, %39;}"
   : "+f"(d[0]),"+f"(d[1]),"+f"(d[2]),"+f"(d[3]),"+f"(d[4]),"+f"(d[5]),"+f"(d[6]),"+f"(d[7]),"+f"(d[8]),"+f"(d[9]),"+f"(d[10]),"+f"(d[11]),"+f"(d[12]),"+f"(d[13]),"+f"(d[14]),"+f"(d[15]),"+f"(d[16]),"+f"(d[17]),"+f"(d[18]),"+f"(d[19]),"+f"(d[20]),"+f"(d[21]),"+f"(d[22]),"+f"(d[23]),"+f"(d[24]),"+f"(d[25]),"+f"(d[26]),"+f"(d[27]),"+f"(d[28]),"+f"(d[29]),"+f"(d[30]),"+f"(d[31])
   : "r"(a0),"r"(a1),"r"(a2),"r"(a3),"r"(bl),"r"(bo >> 4),"r"(scale_d),"n"(TB),"n"(BH));
}
template<int TA,int TB,uint32_t AH,uint32_t BH> __device__ __forceinline__ void wgmma_n96_ss(float (&d)[48], uint32_t al, uint32_t ao, uint32_t bl, uint32_t bo, int scale_d){
  asm volatile("{.reg .pred p; .reg .b32 t, v; .reg .b64 da, db; setp.ne.b32 p, %52, 0; add.u32 t, %48, %49; mov.b64 da, {t, %55}; add.u32 v, %50, %51; mov.b64 db, {v, %56};\n"
   "wgmma.mma_async.sync.aligned.m64n96k16.f32.bf16.bf16 {%0,%1,%2,%3,%4,%5,%6,%7,%8,%9,%10,%11,%12,%13,%14,%15,%16,%17,%18,%19,%20,%21,%22,%23,%24,%25,%26,%27,%28,%29,%30,%31,%32,%33,%34,%35,%36,%37,%38,%39,%40,%41,%42,%43,%44,%45,%46,%47}, da, db, p, 1, 1, %53, %54;}"
   : "+f"(d[0]),"+f"(d[1]),"+f"(d[2]),"+f"(d[3]),"+f"(d[4]),"+f"(d[5]),"+f"(d[6]),"+f"(d[7]),"+f"(d[8]),"+f"(d[9]),"+f"(d[10]),"+f"(d[11]),"+f"(d[12]),"+f"(d[13]),"+f"(d[14]),"+f"(d[15]),"+f"(d[16]),"+f"(d[17]),"+f"(d[18]),"+f"(d[19]),"+f"(d[20]),"+f"(d[21]),"+f"(d[22]),"+f"(d[23]),"+f"(d[24]),"+f"(d[25]),"+f"(d[26]),"+f"(d[27]),"+f"(d[28]),"+f"(d[29]),"+f"(d[30]),"+f"(d[31]),"+f"(d[32]),"+f"(d[33]),"+f"(d[34]),"+f"(d[35]),"+f"(d[36]),"+f"(d[37]),"+f"(d[38]),"+f"(d[39]),"+f"(d[40]),"+f"(d[41]),"+f"(d[42]),"+f"(d[43]),"+f"(d[44]),"+f"(d[45]),"+f"(d[46]),"+f"(d[47])
   : "r"(al),"r"(ao >> 4),"r"(bl),"r"(bo >> 4),"r"(scale_d),"n"(TA),"n"(TB),"n"(AH),"n"(BH));
}
template<int TA,int TB,uint32_t AH,uint32_t BH> __device__ __forceinline__ void wgmma_n128_ss(float (&d)[64], uint32_t al, uint32_t ao, uint32_t bl, uint32_t bo, int scale_d){
  asm volatile("{.reg .pred p; .reg .b32 t, v; .reg .b64 da, db; setp.ne.b32 p, %68, 0; add.u32 t, %64, %65; mov.b64 da, {t, %71}; add.u32 v, %66, %67; mov.b64 db, {v, %72};\n"
   "wgmma.mma_async.sync.aligned.m64n128k16.f32.bf16.bf16 {%0,%1,%2,%3,%4,%5,%6,%7,%8,%9,%10,%11,%12,%13,%14,%15,%16,%17,%18,%19,%20,%21,%22,%23,%24,%25,%26,%27,%28,%29,%30,%31,%32,%33,%34,%35,%36,%37,%38,%39,%40,%41,%42,%43,%44,%45,%46,%47,%48,%49,%50,%51,%52,%53,%54,%55,%56,%57,%58,%59,%60,%61,%62,%63}, da, db, p, 1, 1, %69, %70;}"
   : "+f"(d[0]),"+f"(d[1]),"+f"(d[2]),"+f"(d[3]),"+f"(d[4]),"+f"(d[5]),"+f"(d[6]),"+f"(d[7]),"+f"(d[8]),"+f"(d[9]),"+f"(d[10]),"+f"(d[11]),"+f"(d[12]),"+f"(d[13]),"+f"(d[14]),"+f"(d[15]),"+f"(d[16]),"+f"(d[17]),"+f"(d[18]),"+f"(d[19]),"+f"(d[20]),"+f"(d[21]),"+f"(d[22]),"+f"(d[23]),"+f"(d[24]),"+f"(d[25]),"+f"(d[26]),"+f"(d[27]),"+f"(d[28]),"+f"(d[29]),"+f"(d[30]),"+f"(d[31]),"+f"(d[32]),"+f"(d[33]),"+f"(d[34]),"+f"(d[35]),"+f"(d[36]),"+f"(d[37]),"+f"(d[38]),"+f"(d[39]),"+f"(d[40]),"+f"(d[41]),"+f"(d[42]),"+f"(d[43]),"+f"(d[44]),"+f"(d[45]),"+f"(d[46]),"+f"(d[47]),"+f"(d[48]),"+f"(d[49]),"+f"(d[50]),"+f"(d[51]),"+f"(d[52]),"+f"(d[53]),"+f"(d[54]),"+f"(d[55]),"+f"(d[56]),"+f"(d[57]),"+f"(d[58]),"+f"(d[59]),"+f"(d[60]),"+f"(d[61]),"+f"(d[62]),"+f"(d[63])
   : "r"(al),"r"(ao >> 4),"r"(bl),"r"(bo >> 4),"r"(scale_d),"n"(TA),"n"(TB),"n"(AH),"n"(BH));
}

__global__ void __cluster_dims__(2, 1, 1) __launch_bounds__(384, 1)
fused_kernel(const __nv_bfloat16* __restrict__ lam_re, const __nv_bfloat16* __restrict__ lam_im, const __nv_bfloat16* __restrict__ log_dt,
             const __nv_bfloat16* __restrict__ dskip, const __nv_bfloat16* __restrict__ b1, const __nv_bfloat16* __restrict__ b2,
             const __nv_bfloat16* __restrict__ gate_w, const __nv_bfloat16* __restrict__ pf_w1, const __nv_bfloat16* __restrict__ pf_w2,
             const __nv_bfloat16* __restrict__ pf_cre, const __nv_bfloat16* __restrict__ pf_cim, float* __restrict__ out,
             const __grid_constant__ Maps maps) {
  extern __shared__ __align__(1024) unsigned char smem_raw[];
  const uint32_t sb = (uint32_t)__cvta_generic_to_shared(smem_raw);
  const int b = blockIdx.x;
  const int rank = b & 1, cl = b >> 1;
  const int sp = (cl & 1) | ((cl >> 2) & 2), m = ((cl >> 1) & 3) | ((cl >> 4) << 2);
  const int s = sp * 2 + rank;
  const int warp = __shfl_sync(0xffffffffu, (int)(threadIdx.x >> 5), 0);
  const int lane = threadIdx.x & 31;
  const int xrot = 9 - 2 * sp;

  if (elect_one()) {
    if (warp == 8) TS(2, 0);
    if (warp < 3) {
      asm volatile("prefetch.tensormap [%0];" ::"l"(&maps.x + warp) : "memory");
      mbar_init(sb + OFF_GBAR + 8 * warp, warp < 2 ? 64 : 96);
    }
    const uint32_t c = warp < 8 ? 1 : warp < 11 ? 8 : 4;
    mbar_init(sb + OFF_XFULL + 16 * warp, c);
    mbar_init(sb + OFF_XFULL + 16 * warp + 8, c);
    asm volatile("fence.mbarrier_init.release.cluster;" ::: "memory");
  }
  __syncwarp();
  asm volatile("barrier.cluster.arrive.relaxed.aligned;" ::: "memory");

  if (warp < 8) {
    const int wg = warp >> 2, w = warp & 3, q = lane & 3, gr = lane >> 2;
    uint32_t bv[28];
#pragma unroll
    for (int j = 0; j < 28; j++) bv[j] = __ldg(reinterpret_cast<const uint32_t*>(b1 + s * 224 + j * 8) + q);
    asm volatile("setmaxnreg.inc.sync.aligned.u32 224;");
    asm volatile("barrier.cluster.wait.aligned;" ::: "memory");
    TS(wg, 0);
    auto release = [&](int slot) { if (lane == 0) mbar_arrive(sb + OFF_EMPTY + 8 * slot); };
    const uint32_t xw = sb + OFF_X + wg * 8192, fullb = sb + OFF_FULL;
    const uint32_t dxw = (xw & 0x3FFFF) >> 4, dring = ((sb + OFF_RING) & 0x3FFFF) >> 4;

    float ure[32], uim[32], aa[48], ab[64];
    cplx lam[2], coef[2], l16[2], l32[2], lq[2], pre[2], e[2];
    uint32_t sh16, mhi;

    auto bias = [&](int c) {
#pragma unroll
      for (int j = c * 7; j < c * 7 + 7; j++) {
        pin(bv[j]);
        float* d = j < 12 ? aa + 4 * j : ab + 4 * (j - 12);
        d[0] = d[2] = __uint_as_float(bv[j] << sh16); d[1] = d[3] = __uint_as_float(bv[j] & mhi);
        pin(d[0]); pin(d[1]); pin(d[2]); pin(d[3]);
      }
    };
    if (SB0 < 0) { sh16 = 16; mhi = 0xffff0000u; bias(0); bias(1); bias(2); bias(3); TS(wg, 27); }
#pragma unroll
    for (int kb = 0; kb < 8; kb++) {
      const int slot = kb % NSLOT;
      mbar_wait(sb + OFF_XFULL + 8 * kb, 0);
      if (kb == 0) TS(wg, 18);
      mbar_wait(fullb + 8 * slot, (kb / NSLOT) & 1);
      TS2(2, kb);
      if (kb == 0) TS(wg, 1);
      wg_fence();
      const uint32_t dxa = dxw + ((kb + xrot) & 7) * 1024;
#pragma unroll
      for (int kk = 0; kk < 4; kk++) {
        wgmma_n64_ss<0, 0, DH128, DH128>(ure, dring, slot * 16384 + kk * 32, dxa, kk * 32, (kb | kk) != 0);
        wgmma_n64_ss<0, 0, DH128, DH128>(uim, dring, slot * 16384 + 8192 + kk * 32, dxa, kk * 32, (kb | kk) != 0);
      }
      wg_commit();
      if (kb > 0) { wg_wait<1>(); release((kb - 1) % NSLOT); }
      if (SB0 >= 0) {
        if (kb == SB0) { sh16 = late16(sb + OFF_XFULL); mhi = 0xffffffffu << sh16; bias(0); }
        if (kb == 4) bias(1);
        if (kb == 6) bias(2);
      }
      if (kb == 3) {
        mbar_wait(sb + OFF_LBAR, 0);
#pragma unroll
        for (int h = 0; h < 2; h++) {
          const uint4 v = lds_u4(sb + OFF_LC + (w * 16 + gr + 8 * h) * 16);
          lam[h] = cplx{__uint_as_float(v.x), __uint_as_float(v.y)};
          coef[h] = cplx{__uint_as_float(v.z), __uint_as_float(v.w)};
        }
      }
      if (kb == 5) {
#pragma unroll
        for (int h = 0; h < 2; h++) {
          pin(lam[h].re); pin(lam[h].im);
          cplx t = cmul(lam[h], lam[h]); t = cmul(t, t); t = cmul(t, t);
          l16[h] = cmul(t, t);
          pin(l16[h].re); pin(l16[h].im);
        }
      }
      if (kb == 7) {
#pragma unroll
        for (int h = 0; h < 2; h++) {
          pin(l16[h].re); pin(l16[h].im);
          l32[h] = cmul(l16[h], l16[h]);
          const cplx a = (q & 1) ? l16[h] : cplx{1.f, 0.f}, c = (q & 2) ? l32[h] : cplx{1.f, 0.f};
          lq[h] = cmul(cmul(a, c), coef[h]);
          pin(lq[h].re); pin(lq[h].im);
        }
      }
    }
    TS(wg, 2);
    auto scale_u = [&](int i0, int i1) {
#pragma unroll
      for (int i = 0; i < 32; i++) if (i >= i0 && i < i1) {
        pin(ure[i]); pin(uim[i]);
        const cplx v = cmul(coef[(i >> 1) & 1], cplx{ure[i], uim[i]});
        ure[i] = v.re; uim[i] = v.im;
        pin(ure[i]); pin(uim[i]);
      }
    };
#pragma unroll
    for (int kb = 0; kb < 8; kb++) {
      const int u = 8 + kb, slot = u % NSLOT;
      mbar_wait(fullb + 8 * slot, (u / NSLOT) & 1);
      wg_fence();
      const uint32_t dxa = dxw + ((kb + xrot) & 7) * 1024;
#pragma unroll
      for (int kk = 0; kk < 4; kk++)
        wgmma_n96_ss<0, 1, DH128, DH64>(aa, dxa, kk * 32, dring, slot * 16384 + kk * 1024 + lbo(4096), 1);
      wg_commit();
      if (SB0 >= 0 && kb == 0) bias(3);
      wg_wait<1>();
      release((u - 1) % NSLOT);
      if (kb == 0) {
        reg_fence(ure); reg_fence(uim);
#pragma unroll
        for (int h = 0; h < 2; h++) e[h] = cplx{ure[2 * h], uim[2 * h]};
      }
      if (kb == 0 || kb == 2 || kb == 3) {
        const int ch = kb ? kb - 1 : 0;
#pragma unroll
        for (int t = 1 + 5 * ch; t < 6 + 5 * ch; t++)
#pragma unroll
          for (int h = 0; h < 2; h++) { const int i = 4 * (t >> 1) + 2 * h + (t & 1); e[h] = cfma(lam[h], e[h], cplx{ure[i], uim[i]}); }
#pragma unroll
        for (int h = 0; h < 2; h++) { pin(e[h].re); pin(e[h].im); }
      } else if (kb == 4) {
#pragma unroll
        for (int h = 0; h < 2; h++) {
          cplx y = {__shfl_up_sync(0xffffffffu, e[h].re, 1, 4), __shfl_up_sync(0xffffffffu, e[h].im, 1, 4)};
          if (q >= 1) e[h] = cfma(l16[h], y, e[h]);
          y = cplx{__shfl_up_sync(0xffffffffu, e[h].re, 2, 4), __shfl_up_sync(0xffffffffu, e[h].im, 2, 4)};
          if (q >= 2) e[h] = cfma(l32[h], y, e[h]);
        }
        if (q == 3) {
#pragma unroll
          for (int h = 0; h < 2; h++)
            asm volatile("st.shared.v2.f32 [%0], {%1,%2};" ::"r"(sb + OFF_CARRY + wg * 512 + (w * 16 + gr + 8 * h) * 8), "f"(e[h].re), "f"(e[h].im) : "memory");
          mbar_arrive(sb + OFF_GBAR);
        }
#pragma unroll
        for (int h = 0; h < 2; h++) {
          const cplx y = {__shfl_up_sync(0xffffffffu, e[h].re, 1, 4), __shfl_up_sync(0xffffffffu, e[h].im, 1, 4)};
          pre[h] = (q >= 1) ? cmul(coef[h], y) : cplx{0.f, 0.f};
          pin(pre[h].re); pin(pre[h].im);
        }
        TS(wg, 3);
      } else if (kb > 4) {
        scale_u(kb == 5 ? 0 : kb == 6 ? 4 : 12, kb == 5 ? 4 : kb == 6 ? 12 : 20);
      }
    }
    TS(wg, 4);
    uint32_t H[56], hf[32];
    cplx hst[2];
    const uint32_t hst_addr = xw + (w * 16 + (lane & 15)) * 128 + (((lane >> 4) ^ (lane & 7)) << 4);
    const uint32_t him = (2 - rank) * 16384;
    uint32_t peer;
    asm volatile("mapa.shared::cluster.u32 %0, %1, %2;" : "=r"(peer) : "r"(sb), "r"(rank ^ 1));
    auto credit = [&]() { if (lane == 0) mbar_arrive_cl(peer + OFF_KBAR + wg * 8); };
#pragma unroll
    for (int kb = 0; kb < 8; kb++) {
      const int u = 16 + kb, slot = u % NSLOT;
      mbar_wait(fullb + 8 * slot, (u / NSLOT) & 1);
      wg_fence();
#pragma unroll
      for (int kk = 0; kk < 4; kk++)
        wgmma_n128_ss<0, 1, DH128, DH128>(ab, dxw, kb * 16384 + kk * 32, dring, slot * 16384 + kk * 2048 + lbo(8192), 1);
      wg_commit();
      wg_wait<1>();
      release((u - 1) % NSLOT);
      if (kb == 0) scale_u(20, 32);
      if (kb < 5 && kb != 1) {
        const int ch = kb ? kb - 1 : 0;
#pragma unroll
        for (int i = ch * 6; i < ch * 6 + 6; i++) {
          pin(aa[2 * i]); pin(aa[2 * i + 1]);
          H[i] = gelu2_pair(aa[2 * i], aa[2 * i + 1]);
          pin(H[i]);
        }
      }
      if (kb >= 4) {
        if (kb == 4) {
          TS(wg, 5);
          mbar_wait(sb + OFF_CBAR, 0);
          TS(wg, 6);
#pragma unroll
          for (int h = 0; h < 2; h++) {
            const float2 c = lds_f2(sb + OFF_CARRY + wg * 512 + (w * 16 + gr + 8 * h) * 8);
            hst[h] = cfma(lq[h], cplx{c.x, c.y}, pre[h]);
          }
        }
        const int j0 = (kb - 4) * 2;
        uint32_t rr[4], ri[4];
#pragma unroll
        for (int jj = 0; jj < 2; jj++) {
          const int j = j0 + jj;
          const uint32_t g2 = lds_u(sb + OFF_GS + (wg * 64 + j * 8 + q * 2) * 2);
#pragma unroll
          for (int h = 0; h < 2; h++) {
            const int i = 4 * j + 2 * h;
            const cplx h0 = cfma(lam[h], hst[h], cplx{ure[i], uim[i]});
            hst[h] = cfma(lam[h], h0, cplx{ure[i + 1], uim[i + 1]});
            rr[jj * 2 + h] = bf2_mul(pack_bf16(h0.re, hst[h].re), g2);
            ri[jj * 2 + h] = bf2_mul(pack_bf16(h0.im, hst[h].im), g2 ^ 0x80008000u);
          }
        }
        const uint32_t a = hst_addr ^ (j0 << 4);
        asm volatile("stmatrix.sync.aligned.m8n8.x4.shared.b16 [%0], {%1,%2,%3,%4};" ::"r"(a), "r"(rr[0]), "r"(rr[1]), "r"(rr[2]), "r"(rr[3]) : "memory");
        asm volatile("stmatrix.sync.aligned.m8n8.x4.shared.b16 [%0], {%1,%2,%3,%4};" ::"r"(a + him), "r"(ri[0]), "r"(ri[1]), "r"(ri[2]), "r"(ri[3]) : "memory");
      }
    }
    TS(wg, 7);

    uint4* const psend = g_part + (size_t)(m * 8 + rank) * 3072 + warp * 128 + lane;
    const uint4* const precv = g_part + (size_t)(m * 8 + s) * 3072 + warp * 128 + lane;
    const uint32_t pbuf = OFF_X + warp * 2048 + lane * 16;
    const uint32_t dx0 = ((sb + OFF_X) & 0x3FFFF) >> 4;
    float o[32], fin[32], rho[2];
    uint32_t tr[8];
    uint32_t r0[16], pt[16], sum[16], tag;
    auto recv_issue = [&](uint32_t (&r)[16], int k) {
#pragma unroll
      for (int i = 0; i < 4; i++) ld_b128(precv + k * 1024 + i * 32, r[4 * i], r[4 * i + 1], r[4 * i + 2], r[4 * i + 3]);
    };
    auto stale = [&](uint32_t (&r)[16]) {
      uint32_t t0, t1, r_;
      asm("lop3.b32 %0, %1, %2, %3, 0x7e;" : "=r"(t0) : "r"(r[0]), "r"(r[4]), "r"(tag));
      asm("lop3.b32 %0, %1, %2, %3, 0x7e;" : "=r"(t1) : "r"(r[8]), "r"(r[12]), "r"(tag));
      asm volatile("{.reg .pred p; .reg .b32 t; lop3.b32 t, %1, %2, 1, 0xa8; setp.ne.u32 p, t, 0; vote.sync.any.pred p, p, 0xffffffff; selp.u32 %0, 1, 0, p;}" : "=r"(r_) : "r"(t0), "r"(t1));
      return r_ != 0;
    };
    auto recv_check = [&](uint32_t (&r)[16], int k) {
      if (__builtin_expect(stale(r), 0)) {
        int tries = 0;
#pragma unroll 1
        do { recv_issue(r, k); } while (stale(r) && ++tries < 200000);
      }
    };
    auto gelu_b = [&](int i0, int i1) {
#pragma unroll
      for (int i = i0; i < i1; i++) {
        pin(ab[2 * i]); pin(ab[2 * i + 1]);
        H[24 + i] = gelu2_pair(ab[2 * i], ab[2 * i + 1]);
        pin(H[24 + i]);
      }
    };
    auto step = [&](float (&d)[32], int p, int k, int acc) {
      const uint32_t wo = stage_off(p);
      if (k >= 6 && k < 14) {
        const int kk = k - 6;
        wgmma_n64_rs<0, DH128>(d, hf[4 * kk], hf[4 * kk + 1], hf[4 * kk + 2], hf[4 * kk + 3], dx0, wo + 14336 + (kk >> 2) * 8192 + (kk & 3) * 32, 1);
      } else {
        const int kk = k < 6 ? k : k - 8;
        wgmma_n64_rs<1, DH128>(d, H[4 * kk], H[4 * kk + 1], H[4 * kk + 2], H[4 * kk + 3], dx0, wo + (kk / 7) * 30720 + (kk % 7) * 2048, k != 0 || acc);
      }
    };
    auto mma = [&](float (&d)[32], int p, int k0, int k1, int acc) {
      wg_fence();
#pragma unroll
      for (int k = k0; k < k1; k++) step(d, p, k, acc);
      wg_commit();
    };
    auto send_peer = [&]() {
#pragma unroll
      for (int i = 0; i < 4; i++)
        asm volatile("st.async.shared::cluster.mbarrier::complete_tx::bytes.v4.b32 [%0], {%1,%2,%3,%4}, [%5];" ::"r"(peer + pbuf + i * 512),
                     "r"(pack_bf16(o[8 * i], o[8 * i + 1])), "r"(pack_bf16(o[8 * i + 2], o[8 * i + 3])), "r"(pack_bf16(o[8 * i + 4], o[8 * i + 5])),
                     "r"(pack_bf16(o[8 * i + 6], o[8 * i + 7])), "r"(peer + OFF_RBAR + wg * 8) : "memory");
    };
    auto recv_peer = [&](int k) {
      mbar_wait(sb + OFF_RBAR + wg * 8, k & 1);
#pragma unroll
      for (int i = 0; i < 4; i++) { const uint4 v = lds_u4(sb + pbuf + i * 512); pt[4 * i] = v.x; pt[4 * i + 1] = v.y; pt[4 * i + 2] = v.z; pt[4 * i + 3] = v.w; }
    };
    auto send_owner = [&](float (&d)[32], int k) {
#pragma unroll
      for (int i = 0; i < 4; i++) {
#pragma unroll
        for (int c = 4 * i; c < 4 * i + 4; c++) pt[c] = bf2_add(pt[c], pack_bf16(d[2 * c], d[2 * c + 1]));
        asm("lop3.b32 %0, %0, 1, %1, 0xb8;" : "+r"(pt[4 * i]) : "r"(tag));
        st_b128(psend + (((sp + 1 + k) & 3) * 6 + k) * 1024 + i * 32, pt[4 * i], pt[4 * i + 1], pt[4 * i + 2], pt[4 * i + 3]);
      }
      __syncwarp();
      credit();
    };
    auto load_fin = [&]() {
      mbar_wait(sb + OFF_LBAR, 1);
#pragma unroll
      for (int j = 0; j < 8; j++) {
        const uint4 v = lds_u4(sb + pbuf + 16384 + (j >> 2) * 16384 + (j & 3) * 512);
        fin[4 * j] = __uint_as_float(v.x); fin[4 * j + 1] = __uint_as_float(v.y); fin[4 * j + 2] = __uint_as_float(v.z); fin[4 * j + 3] = __uint_as_float(v.w);
      }
    };
    auto ldk = [&](int pos) { if (pos == K0P) recv_issue(sum, 0); if (pos == K1P) recv_issue(r0, 1); };
    auto arm = [&]() { if ((threadIdx.x & 127) == 0) mbar_expect_tx(sb + OFF_RBAR + wg * 8, 8192); };
#pragma unroll
    for (int p = 0; p < 8; p++) {
      if (p == 0) {
        mbar_wait(fullb, 0);
        mma(o, 0, 0, 3, 0);
        wg_wait<1>(); release(5);
        gelu_b(0, 4);
        mma(o, 0, 3, 6, 0);
        bar_sync(1 + wg, 128);
        {
          const uint32_t ha = xw + ((lane >> 4) * 8 + (lane & 7)) * 128 + (((2 * w + ((lane >> 3) & 1)) ^ (lane & 7)) << 4);
#pragma unroll
          for (int kk = 0; kk < 8; kk++)
            asm volatile("ldmatrix.sync.aligned.m8n8.x4.trans.shared.b16 {%0,%1,%2,%3}, [%4];" : "=r"(hf[4 * kk]), "=r"(hf[4 * kk + 1]), "=r"(hf[4 * kk + 2]), "=r"(hf[4 * kk + 3])
                         : "r"(ha + (kk >> 2) * him + (kk & 3) * 2048) : "memory");
        }
        gelu_b(4, 10);
        mbar_wait(fullb + 8, 0);
        mma(o, 0, 6, 10, 0);
        credit();
        gelu_b(10, 16);
        mma(o, 0, 10, 15, 0);
        gelu_b(16, 24);
        mbar_wait(fullb + 16, 0);
        mma(o, 0, 15, 18, 0);
        gelu_b(24, 32);
        if (wg == 1) bar_sync(4, 256);
        mma(o, 0, 18, 22, 0);
      } else {
        TR(0);
        if (EW == 0 || (EW == 1 && (p & 1))) mbar_wait(sb + OFF_XFULL + 8 * p, 1);
        TR(1);
        bar_sync(3 + wg, 256);
        if (p < 7) mma(o, p, 0, 22, 0);
        else if (GAP == 0) mma(fin, p, 0, 22, 1);
        else {
          mma(fin, p, 0, GAP, 1);
          recv_peer(3);
          tag = lds_u(sb + OFF_EPOCH);
          mma(fin, p, GAP, 22, 1);
        }
      }
      if (p < 7 || wg == 0) bar_arrive(4 - wg, 256);
      TR(2);
      if (p != TP) TS(wg, 8 + p);
      if (p < 7 && (EW == 2 || (EW == 1 && (p & 1)))) mbar_wait(sb + OFF_XFULL + 8 * (p + 1), 1);
      ldk(10 * p);
      if ((p & 1) == 0) {
        arm();
        if (p == 6) {
          mbar_wait(sb + OFF_EMPTY + 32, 0);
          tag = lds_u(sb + OFF_EPOCH);
          recv_check(sum, 0); recv_check(r0, 1);
#pragma unroll
          for (int i = 0; i < 16; i++) sum[i] = bf2_add(sum[i], r0[i]);
        }
        TR(3);
        mbar_wait(sb + OFF_KBAR + wg * 8, (p >> 1) & 1);
        TR(4);
      } else {
        if (p == 1 || (p == 7 && GAP == 0)) tag = lds_u(sb + OFF_EPOCH);
        TR(3);
        if (p < 7 || GAP == 0) recv_peer(p >> 1);
        TR(4);
        if (p == 7) {
          recv_check(r0, 2);
#pragma unroll
          for (int i = 0; i < 16; i++) sum[i] = bf2_add(sum[i], bf2_add(r0[i], pt[i]));
        }
      }
      if (p == FINP && !FINW) load_fin();
      ldk(10 * p + 1);
      TR(5);
      wg_wait<0>();
      TR(6);
      if (p < 5) release(p);
      if (p < 7) reg_fence(o); else reg_fence(fin);
      ldk(10 * p + 2);
      if ((p & 1) == 0) {
        if (p == 6) recv_issue(r0, 2);
        send_peer();
        if (p == FINP && FINW) load_fin();
      } else if (p < 7) {
        send_owner(o, p >> 1);
      }
      ldk(10 * p + 3);
      if (p == 2) {
#pragma unroll
        for (int h = 0; h < 2; h++) { rho[h] = __fdividef(2.f, 4.f + bf_lo(lds_h(sb + OFF_GS + (wg * 64 + w * 16 + gr + 8 * h) * 2))); pin(rho[h]); }
      }
      TR(7);
    }
    {
      TS(wg, 16);
      const uint32_t tb = sb + OFF_X + stage_off(0) + warp * 4096;
      const uint32_t ta = tb + gr * 256 + ((gr & 3) << 5) + q * 8;
      const uint32_t la = tb + (lane >> 3) * 256 + (((lane & 7) << 4) ^ ((lane >> 3) << 5));
      float* op = out + (size_t)(m * 128 + wg * 64 + (lane >> 4) * 16 + w * 4 + ((lane >> 3) & 1)) * DM + s * 64 + (lane & 7) * 4;
#pragma unroll
      for (int qq = 0; qq < 4; qq += QS) {
#pragma unroll
        for (int qt = qq; qt < qq + QS; qt++) {
          const int h = qt & 1, ch = qt >> 1;
#pragma unroll
          for (int j = 0; j < 4; j++) {
            const int i = ch * 8 + j * 2 + h;
            asm volatile("st.shared.v2.f32 [%0], {%1,%2};" ::"r"((ta ^ (j << 5)) + h * 2048 + ch * 128),
                         "f"((fin[2 * i] + bf_lo(sum[i])) * rho[h]), "f"((fin[2 * i + 1] + bf_hi(sum[i])) * rho[h]) : "memory");
          }
        }
        __syncwarp();
#pragma unroll
        for (int qt = qq; qt < qq + QS; qt++) {
          const int h = qt & 1, ch = qt >> 1;
#pragma unroll
          for (int r = 0; r < 2; r++)
            *reinterpret_cast<uint4*>(op + (r * 32 + h * 2) * DM + ch * 32) = lds_u4(la + (h * 2 + r) * 1024 + ch * 128);
        }
      }
      if (threadIdx.x == 128) g_epoch[b] = tag;
      TS(wg, 17); TG(wg); TRD(); TDUMP();
    }
  } else {
    asm volatile("setmaxnreg.dec.sync.aligned.u32 56;");
    int wsel = warp;
    asm("" : "+r"(wsel));
    if (wsel > 8) {
      if (warp != 11) {
        const int t = threadIdx.x - 288;
        unsigned par;
        asm volatile("ld.relaxed.gpu.global.u32 %0, [%1];" : "=r"(par) : "l"(g_epoch + b) : "memory");
        const float pr = bf_ld(lam_re + s * 64 + t), pi = bf_ld(lam_im + s * 64 + t), pd = bf_ld(log_dt + s * 64 + t);
        asm volatile("barrier.cluster.wait.aligned;" ::: "memory");
        par = __shfl_sync(0xffffffffu, (par + 1) & 1, 0);
        cplx l64 = make_lam(pr, pi, pd);
        {
          const float inv = __fdividef(1.f, fmaf(pr, pr, pi * pi));
          const cplx cf = cmul(cplx{l64.re - 1.f, l64.im}, cplx{pr * inv, -pi * inv});
          asm volatile("st.shared.v4.f32 [%0], {%1,%2,%3,%4};" ::"r"(sb + OFF_LC + t * 16), "f"(l64.re), "f"(l64.im), "f"(cf.re), "f"(cf.im) : "memory");
          mbar_arrive(sb + OFF_LBAR);
        }
#pragma unroll
        for (int i = 0; i < 6; i++) l64 = cmul(l64, l64);
        cplx l128 = cmul(l64, l64);
        pin(l128.re); pin(l128.im);
        uint32_t vr[15], vi[15];
#pragma unroll
        for (int i = 0; i < 15; i++) { vr[i] = par; vi[i] = 0; pin(vr[i]); pin(vi[i]); }
        mbar_wait(sb + OFF_GBAR, 0);
        const float2 e0 = lds_f2(sb + OFF_CARRY + t * 8), e1 = lds_f2(sb + OFF_CARRY + 512 + t * 8);
        float2* eb = g_end + s * 1024 + t;
        {
          const cplx e = cfma(l64, cplx{e0.x, e0.y}, cplx{e1.x, e1.y});
          const unsigned long long v = ((unsigned long long)__float_as_uint(e.im) << 32) | ((__float_as_uint(e.re) & ~1u) | par);
          asm volatile("st.relaxed.gpu.global.b64 [%0], %1;" ::"l"(eb + m * 64), "l"(v) : "memory");
        }
        if (t == 0) TS(3, 1);
        cplx S = {0.f, 0.f};
        {
          if (LBD) __nanosleep(LBD);
          const float2* e15 = eb + (m - 15) * 64;
          int tries = 0;
          bool bad;
#pragma unroll 1
          do {
#pragma unroll
            for (int i = 0; i < 15; i++)
              asm volatile("{.reg .pred p; .reg .b64 v; mov.b64 v, {%0,%1}; setp.ge.s32 p, %3, %4; @p ld.relaxed.gpu.global.b64 v, [%2]; mov.b64 {%0,%1}, v;}"
                           : "+r"(vr[i]), "+r"(vi[i]) : "l"(e15 + i * 64), "r"(m), "r"(15 - i) : "memory");
            uint32_t x = vr[0] ^ par;
#pragma unroll
            for (int i = 1; i < 15; i++) asm("lop3.b32 %0, %0, %1, %2, 0xf6;" : "+r"(x) : "r"(vr[i]), "r"(par));
            bad = __any_sync(0xffffffffu, x & 1);
          } while (bad && ++tries < 200000);
          if (t == 0) TS(3, 2);
          S = cplx{__uint_as_float(vr[0]), __uint_as_float(vi[0])};
#pragma unroll
          for (int i = 1; i < 15; i++) S = cfma(l128, S, cplx{__uint_as_float(vr[i]), __uint_as_float(vi[i])});
        }
        const cplx S1 = cfma(l64, S, cplx{e0.x, e0.y});
        asm volatile("st.shared.v2.f32 [%0], {%1,%2};" ::"r"(sb + OFF_CARRY + t * 8), "f"(S.re), "f"(S.im) : "memory");
        asm volatile("st.shared.v2.f32 [%0], {%1,%2};" ::"r"(sb + OFF_CARRY + 512 + t * 8), "f"(S1.re), "f"(S1.im) : "memory");
        mbar_arrive(sb + OFF_CBAR);
        if (t == 0) TS(3, 3);
        mbar_wait(sb + OFF_CBAR, 0);
        const int gr = lane >> 2, q = lane & 3;
        float2 db[8];
#pragma unroll
        for (int j = 0; j < 8; j++) db[j] = lds_f2(sb + OFF_DB + j * 32 + q * 8);
        mbar_wait(sb + OFF_XFULL + 16, 1);
        mbar_wait(sb + OFF_EMPTY, 0);
#pragma unroll 1
        for (int cw = warp - 9; cw < 8; cw += 2) {
          const float r0 = 0.5f * bf_lo(lds_h(sb + OFF_GS + (cw * 16 + gr) * 2)), r1 = 0.5f * bf_lo(lds_h(sb + OFF_GS + (cw * 16 + gr) * 2 + 16));
          const uint32_t xa = sb + OFF_X + (1 + rank) * 16384 + (cw * 16 + (lane & 15)) * 128 + (((lane >> 4) ^ (lane & 7)) << 4);
          uint32_t xv[16];
#pragma unroll
          for (int i = 0; i < 4; i++)
            asm volatile("ldmatrix.sync.aligned.m8n8.x4.shared.b16 {%0,%1,%2,%3}, [%4];" : "=r"(xv[4 * i]), "=r"(xv[4 * i + 1]), "=r"(xv[4 * i + 2]), "=r"(xv[4 * i + 3])
                         : "r"(xa ^ (i << 5)) : "memory");
          __syncwarp();
#pragma unroll
          for (int j = 0; j < 8; j++) {
            const uint32_t x0 = bf2_mul(xv[2 * j], __float_as_uint(db[j].x)), x1 = bf2_mul(xv[2 * j + 1], __float_as_uint(db[j].x));
            pin(db[j].y);
            const float bl = bf_lo(__float_as_uint(db[j].y)), bh = bf_hi(__float_as_uint(db[j].y));
            asm volatile("st.shared.v4.f32 [%0], {%1,%2,%3,%4};" ::"r"(sb + OFF_X + 16384 + (j >> 2) * 16384 + cw * 2048 + (j & 3) * 512 + lane * 16), "f"(fmaf(bf_lo(x0), r0, bl)),
                         "f"(fmaf(bf_hi(x0), r0, bh)), "f"(fmaf(bf_lo(x1), r1, bl)), "f"(fmaf(bf_hi(x1), r1, bh)) : "memory");
          }
        }
        mbar_arrive(sb + OFF_LBAR);
        if (t == 0) TS(3, 5);
      } else {
        if (lane == 0) TG(2);
        const uint4* gwp = reinterpret_cast<const uint4*>(gate_w) + (lane & 7);
        uint4 gw[4];
#pragma unroll
        for (int i = 0; i < 4; i++) gw[i] = __ldg(gwp + i * 8);
        unsigned par;
        asm volatile("ld.relaxed.gpu.global.u32 %0, [%1];" : "=r"(par) : "l"(g_epoch + b) : "memory");
        const uint32_t dk = __ldg(reinterpret_cast<const uint32_t*>(dskip + s * 64) + lane), bb = __ldg(reinterpret_cast<const uint32_t*>(b2 + s * 64) + lane);
        asm volatile("barrier.cluster.wait.aligned;" ::: "memory");
        const int row = s * 16 + (lane >> 3);
        const uint32_t xr0 = sb + OFF_X + row * 128 + (((lane & 7) ^ (row & 7)) << 4), xr1 = (xr0 + 512) ^ 64;
        float z[4] = {0.f, 0.f, 0.f, 0.f};
#pragma unroll
        for (int kb = 0; kb < 8; kb++) {
          const uint32_t wv[4] = {gw[kb & 3].x, gw[kb & 3].y, gw[kb & 3].z, gw[kb & 3].w};
          if (kb < 4) gw[kb] = __ldg(gwp + (kb + 4) * 8);
          mbar_wait(sb + OFF_XFULL + 8 * kb, 0);
          if ((PF & 2) && kb == PFK && elect_one()) {
            l2_prefetch(pf_w1 + b * 7168, 14336);
            l2_prefetch(pf_cre + b * 2048, 4096);
            l2_prefetch(pf_cim + b * 2048, 4096);
            l2_prefetch(pf_w2 + b * 7168, 14336);
          }
          const uint32_t xo = ((kb + xrot) & 7) * 16384;
#pragma unroll
          for (int r = 0; r < 4; r++) {
            const uint4 a = lds_u4(((r & 1) ? xr1 : xr0) + xo + (r >> 1) * 1024);
            const uint32_t p = bf2_fma(a.w, wv[3], bf2_fma(a.z, wv[2], bf2_fma(a.y, wv[1], bf2_mul(a.x, wv[0]))));
            z[r] += bf_lo(p); z[r] += bf_hi(p);
          }
        }
        if (lane == 0) asm volatile("st.shared.u32 [%0], %1;" ::"r"(sb + OFF_EPOCH), "r"(par + 1) : "memory");
        par = (par + 1) & 1;
        {
          float y0 = (lane & 4) ? z[1] : z[0], y1 = (lane & 4) ? z[3] : z[2];
          y0 += __shfl_xor_sync(0xffffffffu, (lane & 4) ? z[0] : z[1], 4);
          y1 += __shfl_xor_sync(0xffffffffu, (lane & 4) ? z[2] : z[3], 4);
          float zz = (lane & 2) ? y1 : y0;
          zz += __shfl_xor_sync(0xffffffffu, (lane & 2) ? y0 : y1, 2);
          zz += __shfl_xor_sync(0xffffffffu, zz, 1);
          const float rho = 4.f * expf(zz > 40.f ? 40.f : zz);
          if ((lane & 1) == 0)
            asm volatile("st.relaxed.gpu.global.u32 [%0], %1;" ::"l"(g_gate + m * 128 + row + (lane & 4) + (lane & 2) * 4), "r"((__float_as_uint(rho) & ~1u) | par) : "memory");
        }
        if ((PF & 8) && elect_one()) {
          l2_prefetch(pf_w2 + b * 7168, 14336);
          l2_prefetch(pf_cre + b * 2048, 4096);
          l2_prefetch(pf_cim + b * 2048, 4096);
        }
        if (lane == 0) TS(3, 0);
        mbar_wait(sb + OFF_GBAR, 0);
        asm volatile("st.shared.v2.u32 [%0], {%1,%2};" ::"r"(sb + OFF_DB + lane * 8), "r"(dk), "r"(bf2_add(bb, bb)) : "memory");
        uint32_t g0, g1, g2, g3;
        int tries = 0;
#pragma unroll 1
        do {
          asm volatile("ld.relaxed.gpu.global.v4.u32 {%0,%1,%2,%3}, [%4];" : "=r"(g0), "=r"(g1), "=r"(g2), "=r"(g3) : "l"(g_gate + m * 128 + lane * 4) : "memory");
        } while ((((g0 ^ par) | (g1 ^ par) | (g2 ^ par) | (g3 ^ par)) & 1) && ++tries < 200000);
        asm volatile("st.shared.v2.u32 [%0], {%1,%2};" ::"r"(sb + OFF_GS + lane * 8), "r"(pack_bf16(__uint_as_float(g0), __uint_as_float(g1))),
                     "r"(pack_bf16(__uint_as_float(g2), __uint_as_float(g3))) : "memory");
        mbar_arrive(sb + OFF_CBAR);
        if (lane == 0) TS(3, 4);
      }
    } else {
      asm volatile("barrier.cluster.wait.aligned;" ::: "memory");
      if (elect_one()) {
        TS(2, 1);
        const uint32_t t0 = clock();
#pragma unroll 1
        for (int u = 0; u < 8; u++) {
          if (u >= 1) while ((uint32_t)clock() - t0 < D0 + (u - 1) * D1) {}
          mbar_expect_tx(sb + OFF_XFULL + 8 * u, 16384);
          tma5d_mc(sb + OFF_X + ((u + xrot) & 7) * 16384 + rank * 8192, &maps.x, u * 64, 2 * m + rank, sb + OFF_XFULL + 8 * u);
          if (u < 6) {
            mbar_expect_tx(sb + OFF_FULL + 8 * u, 16384);
            tma2d(sb + OFF_RING + u * 16384, &maps.bre, u * 64, s * 64, sb + OFF_FULL + 8 * u);
            tma2d(sb + OFF_RING + u * 16384 + 8192, &maps.bim, u * 64, s * 64, sb + OFF_FULL + 8 * u);
          } else if (PF & 4) {
            asm volatile("cp.async.bulk.prefetch.tensor.2d.L2.global [%0, {%1,%2}];" ::"l"((m & 1) ? &maps.bim : &maps.bre), "r"(u * 64), "r"(s * 64) : "memory");
          }
        }
        TS(2, 5);
        int slot = 0; uint32_t ph = 0;
#pragma unroll 1
        for (int u = 6; u < 24; u++) {
          const uint32_t fb = sb + OFF_FULL + 8 * slot, dst = sb + OFF_RING + slot * 16384;
          mbar_wait(sb + OFF_EMPTY + 8 * slot, ph);
          TS2(0, u);
          if (u < 8) {
            mbar_expect_tx(fb, 16384);
            tma2d(dst, &maps.bre, u * 64, s * 64, fb);
            tma2d(dst + 8192, &maps.bim, u * 64, s * 64, fb);
          } else if (u < 16) {
            mbar_expect_tx(fb, 12288);
            tma3d(dst, &maps.w1b, 0, (u - 8) * 64, s * 7, fb);
          } else {
            mbar_expect_tx(fb, 16384);
            tma2d(dst, &maps.w1a, s * 224 + 96, ((u - xrot) & 7) * 64, fb);
            tma2d(dst + 8192, &maps.w1a, s * 224 + 160, ((u - xrot) & 7) * 64, fb);
          }
          if (++slot == NSLOT) { slot = 0; ph ^= 1; }
        }
#pragma unroll 1
        for (int j = 0; j < 3; j++) {
          const uint32_t fb = sb + OFF_FULL + 8 * j, dst = sb + OFF_X + stage_off(0);
          const int c = ((sp + 1) & 3) * 128 + ((rank ^ 1) << 6);
          mbar_wait(sb + OFF_EMPTY + 8 + 8 * j, 1);
          mbar_expect_tx(fb, j == 1 ? 16384 : 14336);
          if (j == 1) {
            tma2d(dst + 14336, &maps.cre, s * 64, c, fb);
            tma2d(dst + 22528, &maps.cim, s * 64, c, fb);
          } else {
            tma2d(dst + j * 15360, &maps.w2, c, s * 224 + j * 56, fb);
          }
        }
#pragma unroll 1
        for (int p = 1; p < 8; p++) {
          const int c = ((sp + 1 + (p >> 1)) & 3) * 128 + (((rank ^ p ^ 1) & 1) << 6);
          const uint32_t fb = sb + OFF_XFULL + 8 * p, dst = sb + OFF_X + stage_off(p);
          if (p == 2 || p > 3) mbar_wait(sb + OFF_EMPTY + (p == 2 ? 40 : (p - 4) * 8), p == 2);
          TS2(0, 32 + p);
          mbar_expect_tx(fb, 45056);
          tma2d(dst, &maps.w2, c, s * 224, fb);
          tma2d(dst + 14336, &maps.cre, s * 64, c, fb);
          tma2d(dst + 22528, &maps.cim, s * 64, c, fb);
          tma2d(dst + 30720, &maps.w2, c, s * 224 + 112, fb);
        }
        TS(2, 2);
      }
    }
  }
}

typedef CUresult (*EncFn)(CUtensorMap*, CUtensorMapDataType, cuuint32_t, void*, const cuuint64_t*, const cuuint64_t*, const cuuint32_t*,
                          const cuuint32_t*, CUtensorMapInterleave, CUtensorMapSwizzle, CUtensorMapL2promotion, CUtensorMapFloatOOBfill);

void encode(EncFn f, CUtensorMap* mp, const void* p, int rank, const cuuint64_t* dims, const cuuint64_t* strides, const cuuint32_t* box, CUtensorMapSwizzle sw) {
  cuuint32_t es[5] = {1, 1, 1, 1, 1};
  f(mp, CU_TENSOR_MAP_DATA_TYPE_BFLOAT16, rank, const_cast<void*>(p), dims, strides, box, es, CU_TENSOR_MAP_INTERLEAVE_NONE, sw,
    CU_TENSOR_MAP_L2_PROMOTION_L2_128B, CU_TENSOR_MAP_FLOAT_OOB_FILL_NONE);
}

}

extern "C" void kernel_launch(void* const* d_in, const int* in_sizes, int n_in, void* d_out, int out_size) {
  typedef const __nv_bfloat16* bp;
  bp x = (bp)d_in[0], lre = (bp)d_in[1], lim = (bp)d_in[2], bre = (bp)d_in[3], bim = (bp)d_in[4], cre = (bp)d_in[5], cim = (bp)d_in[6],
     ldt = (bp)d_in[7], dsk = (bp)d_in[8], w1 = (bp)d_in[10], b1 = (bp)d_in[11], w2 = (bp)d_in[12], b2 = (bp)d_in[13], gw = (bp)d_in[14];
  static EncFn enc = nullptr;
  if (!enc) {
    void* f = nullptr;
    cudaDriverEntryPointQueryResult qr;
    cudaGetDriverEntryPoint("cuTensorMapEncodeTiled", &f, cudaEnableDefault, &qr);
    enc = (EncFn)f;
    cudaFuncSetAttribute(fused_kernel, cudaFuncAttributeMaxDynamicSharedMemorySize, SMEM_BYTES);
  }
  Maps maps;
  {
    cuuint64_t d[5] = {DM, 2, 4, 8, SEQ / 64}, st[4] = {DM * 2, 16 * DM * 2, 2 * DM * 2, 64 * DM * 2};
    cuuint32_t bx[5] = {64, 2, 4, 8, 1};
    encode(enc, &maps.x, x, 5, d, st, bx, CU_TENSOR_MAP_SWIZZLE_128B);
  }
  {
    cuuint64_t d[2] = {DM, DM}, st[1] = {DM * 2};
    cuuint32_t bx[2] = {64, 64};
    encode(enc, &maps.bre, bre, 2, d, st, bx, CU_TENSOR_MAP_SWIZZLE_128B);
    encode(enc, &maps.bim, bim, 2, d, st, bx, CU_TENSOR_MAP_SWIZZLE_128B);
    encode(enc, &maps.cre, cre, 2, d, st, bx, CU_TENSOR_MAP_SWIZZLE_128B);
    encode(enc, &maps.cim, cim, 2, d, st, bx, CU_TENSOR_MAP_SWIZZLE_128B);
  }
  {
    cuuint64_t d[2] = {FF, DM}, st[1] = {FF * 2};
    cuuint32_t bx[2] = {64, 64};
    encode(enc, &maps.w1a, w1, 2, d, st, bx, CU_TENSOR_MAP_SWIZZLE_128B);
    cuuint64_t d3[3] = {32, DM, FF / 32}, st3[2] = {FF * 2, 64};
    cuuint32_t bx3[3] = {32, 64, 3};
    encode(enc, &maps.w1b, w1, 3, d3, st3, bx3, CU_TENSOR_MAP_SWIZZLE_64B);
  }
  {
    cuuint64_t d[2] = {DM, FF}, st[1] = {DM * 2};
    cuuint32_t bx[2] = {64, 112};
    encode(enc, &maps.w2, w2, 2, d, st, bx, CU_TENSOR_MAP_SWIZZLE_128B);
  }
  fused_kernel<<<128, 384, SMEM_BYTES>>>(lre, lim, ldt, dsk, b1, b2, gw, w1, w2, cre, cim, (float*)d_out, maps);
}
```

```cpp
#include <cuda_runtime.h>
#include <cuda_bf16.h>
#include <cuda.h>
#include <stdint.h>

#define MAP 1
#define D0 600
#define D1 500
#define PF 4
#define PFK 5
#define GELUP 1
#define EW 2
#define K1E 1
#define K2E 0
#define QS 1
#define K2G 4
#define FINP 4
#define LBD 300
#define PFS 32
#define SB0 2
#define PFD 2
#define HOLD 0
#define GAP 14
#define FINW 0
#define K0P 33
#define K1P 53
#define TP 9
#define TW 0

namespace {

constexpr int SEQ = 2048, DM = 512, FF = 1792;
constexpr int NSLOT = 6;
constexpr uint32_t OFF_X = 0, OFF_RING = 131072, OFF_MISC = 229376;
constexpr uint32_t OFF_XFULL = OFF_MISC, OFF_FULL = OFF_XFULL + 64, OFF_RBAR = OFF_FULL + 48, OFF_EMPTY = OFF_RBAR + 16, OFF_KBAR = OFF_EMPTY + 48,
                   OFF_GBAR = OFF_KBAR + 16, OFF_LBAR = OFF_GBAR + 8, OFF_CBAR = OFF_LBAR + 8, OFF_EPOCH = OFF_CBAR + 8;
constexpr uint32_t OFF_LC = OFF_RING + 2 * 16384 + 12288;
constexpr uint32_t OFF_GS = OFF_MISC + 256;
constexpr uint32_t OFF_DB = OFF_GS + 256;
constexpr uint32_t OFF_CARRY = OFF_DB + 256;
constexpr uint32_t OFF_DBG = OFF_CARRY + 1024;
constexpr uint32_t SMEM_BYTES = OFF_DBG + 768;
static_assert(SMEM_BYTES <= 232448, "smem");

struct Maps { CUtensorMap x, bre, bim, w1b, w1a, w2, cre, cim; };
__host__ __device__ constexpr uint32_t stage_off(int p) { return 49152 + 45056 * (((p >> 1) & 1) + 2 * (p & 1)); }

__device__ uint4 g_part[16 * 8 * 3 * 1024];
__device__ float2 g_end[8 * 16 * 64];
__device__ unsigned g_gate[SEQ];
__device__ unsigned g_epoch[128];
#define TG(role) do {} while (0)
#define TS2(role, i) do {} while (0)
#define TS(role, i) do {} while (0)
#define TDUMP() do {} while (0)
#define TR(i) do {} while (0)
#define TRD() do {} while (0)

__device__ __forceinline__ void mbar_init(uint32_t bar, uint32_t cnt) { asm volatile("mbarrier.init.shared::cta.b64 [%0], %1;" ::"r"(bar), "r"(cnt)); }
__device__ __forceinline__ void mbar_expect_tx(uint32_t bar, uint32_t bytes) { asm volatile("mbarrier.arrive.expect_tx.shared::cta.b64 _, [%0], %1;" ::"r"(bar), "r"(bytes) : "memory"); }
__device__ __forceinline__ void mbar_arrive(uint32_t bar) { asm volatile("mbarrier.arrive.shared::cta.b64 _, [%0];" ::"r"(bar) : "memory"); }
__device__ __forceinline__ void mbar_arrive_cl(uint32_t cbar) { asm volatile("mbarrier.arrive.shared::cluster.b64 _, [%0];" ::"r"(cbar) : "memory"); }
__device__ __forceinline__ void mbar_wait(uint32_t bar, uint32_t parity) {
  asm volatile(
      "{\n.reg .pred p;\n.reg .u32 c;\n"
      "mbarrier.try_wait.parity.shared::cta.b64 p, [%0], %1;\n"
      "@p bra.uni LAB_DONE;\n"
      "mov.u32 c, 0;\n"
      "LAB_WAIT:\n"
      "mbarrier.try_wait.parity.shared::cta.b64 p, [%0], %1;\n"
      "@p bra.uni LAB_DONE;\n"
      "add.u32 c, c, 1;\nsetp.lt.u32 p, c, 200000;\n@p bra.uni LAB_WAIT;\n"
      "LAB_DONE:\n}" ::"r"(bar), "r"(parity) : "memory");
}
__device__ __forceinline__ void tma2d(uint32_t dst, const CUtensorMap* m, int c0, int c1, uint32_t bar) {
  asm volatile("cp.async.bulk.tensor.2d.shared::cluster.global.mbarrier::complete_tx::bytes [%0], [%1, {%3,%4}], [%2];"
               ::"r"(dst), "l"(m), "r"(bar), "r"(c0), "r"(c1) : "memory");
}
__device__ __forceinline__ void tma3d(uint32_t dst, const CUtensorMap* m, int c0, int c1, int c2, uint32_t bar) {
  asm volatile("cp.async.bulk.tensor.3d.shared::cluster.global.mbarrier::complete_tx::bytes [%0], [%1, {%3,%4,%5}], [%2];"
               ::"r"(dst), "l"(m), "r"(bar), "r"(c0), "r"(c1), "r"(c2) : "memory");
}
__device__ __forceinline__ void tma5d_mc(uint32_t dst, const CUtensorMap* m, int c0, int c4, uint32_t bar) {
  asm volatile("cp.async.bulk.tensor.5d.shared::cluster.global.mbarrier::complete_tx::bytes.multicast::cluster [%0], [%1, {%3,%5,%5,%5,%4}], [%2], %6;"
               ::"r"(dst), "l"(m), "r"(bar), "r"(c0), "r"(c4), "r"(0), "h"((uint16_t)3) : "memory");
}
__device__ __forceinline__ void l2_prefetch(const void* p, uint32_t bytes) { asm volatile("cp.async.bulk.prefetch.L2.global [%0], %1;" ::"l"(p), "r"(bytes) : "memory"); }
__device__ __forceinline__ bool elect_one() {
  uint32_t pred;
  asm volatile("{.reg .pred P; elect.sync _|P, 0xffffffff; selp.u32 %0, 1, 0, P;}" : "=r"(pred));
  return pred != 0;
}
__device__ __forceinline__ void wg_fence() { asm volatile("wgmma.fence.sync.aligned;" ::: "memory"); }
__device__ __forceinline__ void wg_commit() { asm volatile("wgmma.commit_group.sync.aligned;" ::: "memory"); }
template <int N> __device__ __forceinline__ void wg_wait() { asm volatile("wgmma.wait_group.sync.aligned %0;" ::"n"(N) : "memory"); }
__device__ __forceinline__ void pin(float& a) { asm volatile("" : "+f"(a)::"memory"); }
__device__ __forceinline__ void pin(uint32_t& a) { asm volatile("" : "+r"(a)::"memory"); }
template <int N> __device__ __forceinline__ void reg_fence(float (&d)[N]) {
#pragma unroll
  for (int i = 0; i < N; i++) pin(d[i]);
}
__device__ __forceinline__ void bar_sync(int id, int n) { asm volatile("bar.sync %0, %1;" ::"r"(id), "r"(n) : "memory"); }
__device__ __forceinline__ void bar_arrive(int id, int n) { asm volatile("bar.arrive %0, %1;" ::"r"(id), "r"(n) : "memory"); }
constexpr uint32_t DH128 = (1024 >> 4) | (1u << 30), DH64 = (512 >> 4) | (2u << 30);
__host__ __device__ constexpr uint32_t lbo(uint32_t bytes) { return (bytes >> 4) << 20; }
__device__ __forceinline__ uint32_t pack_bf16(float lo, float hi) { uint32_t r; asm("cvt.rn.bf16x2.f32 %0, %1, %2;" : "=r"(r) : "f"(hi), "f"(lo)); return r; }
__device__ __forceinline__ float bf_lo(uint32_t v) { return __uint_as_float(v << 16); }
__device__ __forceinline__ float bf_hi(uint32_t v) { return __uint_as_float(v & 0xffff0000u); }
__device__ __forceinline__ float bf_ld(const __nv_bfloat16* p) { return __bfloat162float(__ldg(p)); }
__device__ __forceinline__ uint32_t late16(uint32_t bar) {
  uint32_t r;
  asm volatile("{.reg .pred p; mbarrier.test_wait.parity.shared::cta.b64 p, [%1], 0; selp.u32 %0, 16, 0, p;}" : "=r"(r) : "r"(bar) : "memory");
  return r;
}
__device__ __forceinline__ float2 lds_f2(uint32_t a) { float2 v; asm volatile("ld.shared.v2.f32 {%0,%1}, [%2];" : "=f"(v.x), "=f"(v.y) : "r"(a)); return v; }
__device__ __forceinline__ uint32_t lds_h(uint32_t a) { uint32_t v; asm volatile("ld.shared.u16 %0, [%1];" : "=r"(v) : "r"(a)); return v; }
__device__ __forceinline__ uint32_t lds_u(uint32_t a) { uint32_t v; asm volatile("ld.shared.u32 %0, [%1];" : "=r"(v) : "r"(a)); return v; }
__device__ __forceinline__ uint4 lds_u4(uint32_t a) { uint4 v; asm volatile("ld.shared.v4.u32 {%0,%1,%2,%3}, [%4];" : "=r"(v.x), "=r"(v.y), "=r"(v.z), "=r"(v.w) : "r"(a)); return v; }
__device__ __forceinline__ void st_b128(uint4* p, uint32_t a, uint32_t b, uint32_t c, uint32_t d) {
  asm volatile("st.relaxed.gpu.global.v4.b32 [%0], {%1,%2,%3,%4};" ::"l"(p), "r"(a), "r"(b), "r"(c), "r"(d) : "memory");
}
__device__ __forceinline__ void ld_b128(const uint4* p, uint32_t& a, uint32_t& b, uint32_t& c, uint32_t& d) {
  asm volatile("{.reg .b64 l, h; .reg .b128 v; ld.relaxed.gpu.global.b128 v, [%4]; mov.b128 {l,h}, v; mov.b64 {%0,%1}, l; mov.b64 {%2,%3}, h;}"
               : "=r"(a), "=r"(b), "=r"(c), "=r"(d) : "l"(p) : "memory");
}
__device__ __forceinline__ float tanh_fast(float x) { float y; asm("tanh.approx.f32 %0, %1;" : "=f"(y) : "f"(x)); return y; }
__device__ __forceinline__ float gelu2(float v) {
  float p = fmaf(v * v, 0.0356774081363f, 0.7978845608029f);
  return fmaf(v, tanh_fast(v * p), v);
}
__device__ __forceinline__ uint32_t bf2_mul(uint32_t a, uint32_t b) { uint32_t r; asm("mul.rn.bf16x2 %0, %1, %2;" : "=r"(r) : "r"(a), "r"(b)); return r; }
__device__ __forceinline__ uint32_t bf2_add(uint32_t a, uint32_t b) { uint32_t r; asm("add.rn.bf16x2 %0, %1, %2;" : "=r"(r) : "r"(a), "r"(b)); return r; }
__device__ __forceinline__ uint32_t bf2_fma(uint32_t a, uint32_t b, uint32_t c) { uint32_t r; asm("fma.rn.bf16x2 %0, %1, %2, %3;" : "=r"(r) : "r"(a), "r"(b), "r"(c)); return r; }
__device__ __forceinline__ uint32_t gelu2_pair(float a, float b) {
  const uint32_t v = pack_bf16(a, b);
  uint32_t t;
  asm("tanh.approx.bf16x2 %0, %1;" : "=r"(t) : "r"(bf2_fma(v, bf2_fma(bf2_mul(v, v), 0x3d123d12u, 0xbe4fbe4fu), v)));
  return bf2_fma(v, t, v);
}
struct cplx { float re, im; };
__device__ __forceinline__ cplx cmul(cplx a, cplx b) { return {fmaf(a.re, b.re, -a.im * b.im), fmaf(a.re, b.im, a.im * b.re)}; }
__device__ __forceinline__ cplx cfma(cplx a, cplx b, cplx c) {
  return {fmaf(a.re, b.re, fmaf(-a.im, b.im, c.re)), fmaf(a.re, b.im, fmaf(a.im, b.re, c.im))};
}
__device__ __forceinline__ cplx make_lam(float lre, float lim, float ldt) {
  float dt = __bfloat162float(__float2bfloat16_rn(expf(ldt)));
  float mag = expf(dt * lre), sn, cs;
  sincospif(dt * lim * 0.31830988618379067f, &sn, &cs);
  return {mag * cs, mag * sn};
}

template<int TA,int TB,uint32_t AH,uint32_t BH> __device__ __forceinline__ void wgmma_n64_ss(float (&d)[32], uint32_t al, uint32_t ao, uint32_t bl, uint32_t bo, int scale_d){
  asm volatile("{.reg .pred p; .reg .b32 t, v; .reg .b64 da, db; setp.ne.b32 p, %36, 0; add.u32 t, %32, %33; mov.b64 da, {t, %39}; add.u32 v, %34, %35; mov.b64 db, {v, %40};\n"
   "wgmma.mma_async.sync.aligned.m64n64k16.f32.bf16.bf16 {%0,%1,%2,%3,%4,%5,%6,%7,%8,%9,%10,%11,%12,%13,%14,%15,%16,%17,%18,%19,%20,%21,%22,%23,%24,%25,%26,%27,%28,%29,%30,%31}, da, db, p, 1, 1, %37, %38;}"
   : "+f"(d[0]),"+f"(d[1]),"+f"(d[2]),"+f"(d[3]),"+f"(d[4]),"+f"(d[5]),"+f"(d[6]),"+f"(d[7]),"+f"(d[8]),"+f"(d[9]),"+f"(d[10]),"+f"(d[11]),"+f"(d[12]),"+f"(d[13]),"+f"(d[14]),"+f"(d[15]),"+f"(d[16]),"+f"(d[17]),"+f"(d[18]),"+f"(d[19]),"+f"(d[20]),"+f"(d[21]),"+f"(d[22]),"+f"(d[23]),"+f"(d[24]),"+f"(d[25]),"+f"(d[26]),"+f"(d[27]),"+f"(d[28]),"+f"(d[29]),"+f"(d[30]),"+f"(d[31])
   : "r"(al),"r"(ao >> 4),"r"(bl),"r"(bo >> 4),"r"(scale_d),"n"(TA),"n"(TB),"n"(AH),"n"(BH));
}
template<int TB,uint32_t BH> __device__ __forceinline__ void wgmma_n64_rs(float (&d)[32], uint32_t a0,uint32_t a1,uint32_t a2,uint32_t a3, uint32_t bl, uint32_t bo, int scale_d){
  asm volatile("{.reg .pred p; .reg .b32 t; .reg .b64 db; setp.ne.b32 p, %38, 0; add.u32 t, %36, %37; mov.b64 db, {t, %40};\n"
   "wgmma.mma_async.sync.aligned.m64n64k16.f32.bf16.bf16 {%0,%1,%2,%3,%4,%5,%6,%7,%8,%9,%10,%11,%12,%13,%14,%15,%16,%17,%18,%19,%20,%21,%22,%23,%24,%25,%26,%27,%28,%29,%30,%31}, {%32,%33,%34,%35}, db, p, 1, 1, %39;}"
   : "+f"(d[0]),"+f"(d[1]),"+f"(d[2]),"+f"(d[3]),"+f"(d[4]),"+f"(d[5]),"+f"(d[6]),"+f"(d[7]),"+f"(d[8]),"+f"(d[9]),"+f"(d[10]),"+f"(d[11]),"+f"(d[12]),"+f"(d[13]),"+f"(d[14]),"+f"(d[15]),"+f"(d[16]),"+f"(d[17]),"+f"(d[18]),"+f"(d[19]),"+f"(d[20]),"+f"(d[21]),"+f"(d[22]),"+f"(d[23]),"+f"(d[24]),"+f"(d[25]),"+f"(d[26]),"+f"(d[27]),"+f"(d[28]),"+f"(d[29]),"+f"(d[30]),"+f"(d[31])
   : "r"(a0),"r"(a1),"r"(a2),"r"(a3),"r"(bl),"r"(bo >> 4),"r"(scale_d),"n"(TB),"n"(BH));
}
template<int TA,int TB,uint32_t AH,uint32_t BH> __device__ __forceinline__ void wgmma_n96_ss(float (&d)[48], uint32_t al, uint32_t ao, uint32_t bl, uint32_t bo, int scale_d){
  asm volatile("{.reg .pred p; .reg .b32 t, v; .reg .b64 da, db; setp.ne.b32 p, %52, 0; add.u32 t, %48, %49; mov.b64 da, {t, %55}; add.u32 v, %50, %51; mov.b64 db, {v, %56};\n"
   "wgmma.mma_async.sync.aligned.m64n96k16.f32.bf16.bf16 {%0,%1,%2,%3,%4,%5,%6,%7,%8,%9,%10,%11,%12,%13,%14,%15,%16,%17,%18,%19,%20,%21,%22,%23,%24,%25,%26,%27,%28,%29,%30,%31,%32,%33,%34,%35,%36,%37,%38,%39,%40,%41,%42,%43,%44,%45,%46,%47}, da, db, p, 1, 1, %53, %54;}"
   : "+f"(d[0]),"+f"(d[1]),"+f"(d[2]),"+f"(d[3]),"+f"(d[4]),"+f"(d[5]),"+f"(d[6]),"+f"(d[7]),"+f"(d[8]),"+f"(d[9]),"+f"(d[10]),"+f"(d[11]),"+f"(d[12]),"+f"(d[13]),"+f"(d[14]),"+f"(d[15]),"+f"(d[16]),"+f"(d[17]),"+f"(d[18]),"+f"(d[19]),"+f"(d[20]),"+f"(d[21]),"+f"(d[22]),"+f"(d[23]),"+f"(d[24]),"+f"(d[25]),"+f"(d[26]),"+f"(d[27]),"+f"(d[28]),"+f"(d[29]),"+f"(d[30]),"+f"(d[31]),"+f"(d[32]),"+f"(d[33]),"+f"(d[34]),"+f"(d[35]),"+f"(d[36]),"+f"(d[37]),"+f"(d[38]),"+f"(d[39]),"+f"(d[40]),"+f"(d[41]),"+f"(d[42]),"+f"(d[43]),"+f"(d[44]),"+f"(d[45]),"+f"(d[46]),"+f"(d[47])
   : "r"(al),"r"(ao >> 4),"r"(bl),"r"(bo >> 4),"r"(scale_d),"n"(TA),"n"(TB),"n"(AH),"n"(BH));
}
template<int TA,int TB,uint32_t AH,uint32_t BH> __device__ __forceinline__ void wgmma_n128_ss(float (&d)[64], uint32_t al, uint32_t ao, uint32_t bl, uint32_t bo, int scale_d){
  asm volatile("{.reg .pred p; .reg .b32 t, v; .reg .b64 da, db; setp.ne.b32 p, %68, 0; add.u32 t, %64, %65; mov.b64 da, {t, %71}; add.u32 v, %66, %67; mov.b64 db, {v, %72};\n"
   "wgmma.mma_async.sync.aligned.m64n128k16.f32.bf16.bf16 {%0,%1,%2,%3,%4,%5,%6,%7,%8,%9,%10,%11,%12,%13,%14,%15,%16,%17,%18,%19,%20,%21,%22,%23,%24,%25,%26,%27,%28,%29,%30,%31,%32,%33,%34,%35,%36,%37,%38,%39,%40,%41,%42,%43,%44,%45,%46,%47,%48,%49,%50,%51,%52,%53,%54,%55,%56,%57,%58,%59,%60,%61,%62,%63}, da, db, p, 1, 1, %69, %70;}"
   : "+f"(d[0]),"+f"(d[1]),"+f"(d[2]),"+f"(d[3]),"+f"(d[4]),"+f"(d[5]),"+f"(d[6]),"+f"(d[7]),"+f"(d[8]),"+f"(d[9]),"+f"(d[10]),"+f"(d[11]),"+f"(d[12]),"+f"(d[13]),"+f"(d[14]),"+f"(d[15]),"+f"(d[16]),"+f"(d[17]),"+f"(d[18]),"+f"(d[19]),"+f"(d[20]),"+f"(d[21]),"+f"(d[22]),"+f"(d[23]),"+f"(d[24]),"+f"(d[25]),"+f"(d[26]),"+f"(d[27]),"+f"(d[28]),"+f"(d[29]),"+f"(d[30]),"+f"(d[31]),"+f"(d[32]),"+f"(d[33]),"+f"(d[34]),"+f"(d[35]),"+f"(d[36]),"+f"(d[37]),"+f"(d[38]),"+f"(d[39]),"+f"(d[40]),"+f"(d[41]),"+f"(d[42]),"+f"(d[43]),"+f"(d[44]),"+f"(d[45]),"+f"(d[46]),"+f"(d[47]),"+f"(d[48]),"+f"(d[49]),"+f"(d[50]),"+f"(d[51]),"+f"(d[52]),"+f"(d[53]),"+f"(d[54]),"+f"(d[55]),"+f"(d[56]),"+f"(d[57]),"+f"(d[58]),"+f"(d[59]),"+f"(d[60]),"+f"(d[61]),"+f"(d[62]),"+f"(d[63])
   : "r"(al),"r"(ao >> 4),"r"(bl),"r"(bo >> 4),"r"(scale_d),"n"(TA),"n"(TB),"n"(AH),"n"(BH));
}

__global__ void __cluster_dims__(2, 1, 1) __launch_bounds__(384, 1)
fused_kernel(const __nv_bfloat16* __restrict__ lam_re, const __nv_bfloat16* __restrict__ lam_im, const __nv_bfloat16* __restrict__ log_dt,
             const __nv_bfloat16* __restrict__ dskip, const __nv_bfloat16* __restrict__ b1, const __nv_bfloat16* __restrict__ b2,
             const __nv_bfloat16* __restrict__ gate_w, const __nv_bfloat16* __restrict__ pf_w1, const __nv_bfloat16* __restrict__ pf_w2,
             const __nv_bfloat16* __restrict__ pf_cre, const __nv_bfloat16* __restrict__ pf_cim, float* __restrict__ out,
             const __grid_constant__ Maps maps) {
  extern __shared__ __align__(1024) unsigned char smem_raw[];
  const uint32_t sb = (uint32_t)__cvta_generic_to_shared(smem_raw);
  const int b = blockIdx.x;
  const int rank = b & 1, cl = b >> 1;
  const int sp = (cl & 1) | ((cl >> 2) & 2), m = ((cl >> 1) & 3) | ((cl >> 4) << 2);
  const int s = sp * 2 + rank;
  const int warp = __shfl_sync(0xffffffffu, (int)(threadIdx.x >> 5), 0);
  const int lane = threadIdx.x & 31;
  const int xrot = 9 - 2 * sp;

  if (elect_one()) {
    if (warp == 8) TS(2, 0);
    if (warp < 3) {
      asm volatile("prefetch.tensormap [%0];" ::"l"(&maps.x + warp) : "memory");
      mbar_init(sb + OFF_GBAR + 8 * warp, warp < 2 ? 64 : 96);
    }
    const uint32_t c = warp < 8 ? 1 : warp < 11 ? 8 : 4;
    mbar_init(sb + OFF_XFULL + 16 * warp, c);
    mbar_init(sb + OFF_XFULL + 16 * warp + 8, c);
    asm volatile("fence.mbarrier_init.release.cluster;" ::: "memory");
  }
  __syncwarp();
  asm volatile("barrier.cluster.arrive.relaxed.aligned;" ::: "memory");

  if (warp < 8) {
    const int wg = warp >> 2, w = warp & 3, q = lane & 3, gr = lane >> 2;
    uint32_t bv[28];
#pragma unroll
    for (int j = 0; j < 28; j++) bv[j] = __ldg(reinterpret_cast<const uint32_t*>(b1 + s * 224 + j * 8) + q);
    asm volatile("setmaxnreg.inc.sync.aligned.u32 224;");
    asm volatile("barrier.cluster.wait.aligned;" ::: "memory");
    TS(wg, 0);
    auto release = [&](int slot) { if (lane == 0) mbar_arrive(sb + OFF_EMPTY + 8 * slot); };
    const uint32_t xw = sb + OFF_X + wg * 8192, fullb = sb + OFF_FULL;
    const uint32_t dxw = (xw & 0x3FFFF) >> 4, dring = ((sb + OFF_RING) & 0x3FFFF) >> 4;

    float ure[32], uim[32], aa[48], ab[64];
    cplx lam[2], coef[2], l16[2], l32[2], lq[2], pre[2], e[2];
    uint32_t sh16, mhi;

    auto bias = [&](int c) {
#pragma unroll
      for (int j = c * 7; j < c * 7 + 7; j++) {
        pin(bv[j]);
        float* d = j < 12 ? aa + 4 * j : ab + 4 * (j - 12);
        d[0] = d[2] = __uint_as_float(bv[j] << sh16); d[1] = d[3] = __uint_as_float(bv[j] & mhi);
        pin(d[0]); pin(d[1]); pin(d[2]); pin(d[3]);
      }
    };
    if (SB0 < 0) { sh16 = 16; mhi = 0xffff0000u; bias(0); bias(1); bias(2); bias(3); TS(wg, 27); }
#pragma unroll
    for (int kb = 0; kb < 8; kb++) {
      const int slot = kb % NSLOT;
      mbar_wait(sb + OFF_XFULL + 8 * kb, 0);
      if (kb == 0) TS(wg, 18);
      mbar_wait(fullb + 8 * slot, (kb / NSLOT) & 1);
      TS2(2, kb);
      if (kb == 0) TS(wg, 1);
      wg_fence();
      const uint32_t dxa = dxw + ((kb + xrot) & 7) * 1024;
#pragma unroll
      for (int kk = 0; kk < 4; kk++) {
        wgmma_n64_ss<0, 0, DH128, DH128>(ure, dring, slot * 16384 + kk * 32, dxa, kk * 32, (kb | kk) != 0);
        wgmma_n64_ss<0, 0, DH128, DH128>(uim, dring, slot * 16384 + 8192 + kk * 32, dxa, kk * 32, (kb | kk) != 0);
      }
      wg_commit();
      if (kb > 0) { wg_wait<1>(); release((kb - 1) % NSLOT); }
      if (SB0 >= 0) {
        if (kb == SB0) { sh16 = late16(sb + OFF_XFULL); mhi = 0xffffffffu << sh16; bias(0); }
        if (kb >= 4 && kb < 7) bias(kb - 3);
      }
    }
    TS(wg, 2);
    auto scale_u = [&](int i0, int i1) {
#pragma unroll
      for (int i = 0; i < 32; i++) if (i >= i0 && i < i1) {
        pin(ure[i]); pin(uim[i]);
        const cplx v = cmul(coef[(i >> 1) & 1], cplx{ure[i], uim[i]});
        ure[i] = v.re; uim[i] = v.im;
        pin(ure[i]); pin(uim[i]);
      }
    };
    const uint32_t lca = sb + OFF_LC + (w * 16 + gr) * 16;
#pragma unroll
    for (int kb = 0; kb < 8; kb++) {
      const int u = 8 + kb, slot = u % NSLOT;
      mbar_wait(fullb + 8 * slot, (u / NSLOT) & 1);
      wg_fence();
      const uint32_t dxa = dxw + ((kb + xrot) & 7) * 1024;
#pragma unroll
      for (int kk = 0; kk < 4; kk++)
        wgmma_n96_ss<0, 1, DH128, DH64>(aa, dxa, kk * 32, dring, slot * 16384 + kk * 1024 + lbo(4096), 1);
      wg_commit();
      if (kb == 0) {
        mbar_wait(sb + OFF_LBAR, 0);
#pragma unroll
        for (int h = 0; h < 2; h++) {
          const uint4 v = lds_u4(lca + h * 128);
          lam[h] = cplx{__uint_as_float(v.x), __uint_as_float(v.y)};
          coef[h] = cplx{__uint_as_float(v.z), __uint_as_float(v.w)};
        }
      }
      if (kb == 2) {
#pragma unroll
        for (int h = 0; h < 2; h++) {
          const uint4 v = lds_u4(lca + 1024 + h * 128);
          l16[h] = cplx{__uint_as_float(v.x), __uint_as_float(v.y)};
          l32[h] = cplx{__uint_as_float(v.z), __uint_as_float(v.w)};
        }
      }
      if (kb == 5) {
#pragma unroll
        for (int h = 0; h < 2; h++) { const float2 v = lds_f2(sb + OFF_LC + 2048 + (w * 16 + 8 * h) * 32 + lane * 8); lq[h] = cplx{v.x, v.y}; }
      }
      wg_wait<1>();
      release((u - 1) % NSLOT);
      if (kb == 0) {
        reg_fence(ure); reg_fence(uim);
#pragma unroll
        for (int h = 0; h < 2; h++) e[h] = cplx{ure[2 * h], uim[2 * h]};
      }
      if (kb == 0 || kb == 2 || kb == 3) {
        const int ch = kb ? kb - 1 : 0;
#pragma unroll
        for (int t = 1 + 5 * ch; t < 6 + 5 * ch; t++)
#pragma unroll
          for (int h = 0; h < 2; h++) { const int i = 4 * (t >> 1) + 2 * h + (t & 1); e[h] = cfma(lam[h], e[h], cplx{ure[i], uim[i]}); }
#pragma unroll
        for (int h = 0; h < 2; h++) { pin(e[h].re); pin(e[h].im); }
      } else if (kb == 4) {
#pragma unroll
        for (int h = 0; h < 2; h++) {
          cplx y = {__shfl_up_sync(0xffffffffu, e[h].re, 1, 4), __shfl_up_sync(0xffffffffu, e[h].im, 1, 4)};
          if (q >= 1) e[h] = cfma(l16[h], y, e[h]);
          y = cplx{__shfl_up_sync(0xffffffffu, e[h].re, 2, 4), __shfl_up_sync(0xffffffffu, e[h].im, 2, 4)};
          if (q >= 2) e[h] = cfma(l32[h], y, e[h]);
        }
        if (q == 3) {
#pragma unroll
          for (int h = 0; h < 2; h++)
            asm volatile("st.shared.v2.f32 [%0], {%1,%2};" ::"r"(sb + OFF_CARRY + wg * 512 + (w * 16 + gr + 8 * h) * 8), "f"(e[h].re), "f"(e[h].im) : "memory");
          mbar_arrive(sb + OFF_GBAR);
        }
#pragma unroll
        for (int h = 0; h < 2; h++) {
          const cplx y = {__shfl_up_sync(0xffffffffu, e[h].re, 1, 4), __shfl_up_sync(0xffffffffu, e[h].im, 1, 4)};
          pre[h] = (q >= 1) ? cmul(coef[h], y) : cplx{0.f, 0.f};
          pin(pre[h].re); pin(pre[h].im);
        }
        TS(wg, 3);
      } else if (kb > 4) {
        scale_u(kb == 5 ? 0 : kb == 6 ? 4 : 12, kb == 5 ? 4 : kb == 6 ? 12 : 20);
      }
    }
    TS(wg, 4);
    uint32_t H[56], hf[32];
    cplx hst[2];
    const uint32_t hst_addr = xw + (w * 16 + (lane & 15)) * 128 + (((lane >> 4) ^ (lane & 7)) << 4);
    const uint32_t him = (2 - rank) * 16384;
    uint32_t peer;
    asm volatile("mapa.shared::cluster.u32 %0, %1, %2;" : "=r"(peer) : "r"(sb), "r"(rank ^ 1));
    auto credit = [&]() { if (lane == 0) mbar_arrive_cl(peer + OFF_KBAR + wg * 8); };
#pragma unroll
    for (int kb = 0; kb < 8; kb++) {
      const int u = 16 + kb, slot = u % NSLOT;
      mbar_wait(fullb + 8 * slot, (u / NSLOT) & 1);
      wg_fence();
#pragma unroll
      for (int kk = 0; kk < 4; kk++)
        wgmma_n128_ss<0, 1, DH128, DH128>(ab, dxw, kb * 16384 + kk * 32, dring, slot * 16384 + kk * 2048 + lbo(8192), 1);
      wg_commit();
      wg_wait<1>();
      release((u - 1) % NSLOT);
      if (kb == 0) scale_u(20, 32);
      if (kb < 5 && kb != 1) {
        const int ch = kb ? kb - 1 : 0;
#pragma unroll
        for (int i = ch * 6; i < ch * 6 + 6; i++) {
          pin(aa[2 * i]); pin(aa[2 * i + 1]);
          H[i] = gelu2_pair(aa[2 * i], aa[2 * i + 1]);
          pin(H[i]);
        }
      }
      if (kb >= 4) {
        if (kb == 4) {
          TS(wg, 5);
          mbar_wait(sb + OFF_CBAR, 0);
          TS(wg, 6);
#pragma unroll
          for (int h = 0; h < 2; h++) {
            const float2 c = lds_f2(sb + OFF_CARRY + wg * 512 + (w * 16 + gr + 8 * h) * 8);
            hst[h] = cfma(lq[h], cplx{c.x, c.y}, pre[h]);
          }
        }
        const int j0 = (kb - 4) * 2;
        uint32_t rr[4], ri[4];
#pragma unroll
        for (int jj = 0; jj < 2; jj++) {
          const int j = j0 + jj;
          const uint32_t g2 = lds_u(sb + OFF_GS + (wg * 64 + j * 8 + q * 2) * 2);
#pragma unroll
          for (int h = 0; h < 2; h++) {
            const int i = 4 * j + 2 * h;
            const cplx h0 = cfma(lam[h], hst[h], cplx{ure[i], uim[i]});
            hst[h] = cfma(lam[h], h0, cplx{ure[i + 1], uim[i + 1]});
            rr[jj * 2 + h] = bf2_mul(pack_bf16(h0.re, hst[h].re), g2);
            ri[jj * 2 + h] = bf2_mul(pack_bf16(h0.im, hst[h].im), g2 ^ 0x80008000u);
          }
        }
        const uint32_t a = hst_addr ^ (j0 << 4);
        asm volatile("stmatrix.sync.aligned.m8n8.x4.shared.b16 [%0], {%1,%2,%3,%4};" ::"r"(a), "r"(rr[0]), "r"(rr[1]), "r"(rr[2]), "r"(rr[3]) : "memory");
        asm volatile("stmatrix.sync.aligned.m8n8.x4.shared.b16 [%0], {%1,%2,%3,%4};" ::"r"(a + him), "r"(ri[0]), "r"(ri[1]), "r"(ri[2]), "r"(ri[3]) : "memory");
      }
    }
    TS(wg, 7);

    uint4* const psend = g_part + (size_t)(m * 8 + rank) * 3072 + warp * 128 + lane;
    const uint4* const precv = g_part + (size_t)(m * 8 + s) * 3072 + warp * 128 + lane;
    const uint32_t pbuf = OFF_X + warp * 2048 + lane * 16;
    const uint32_t dx0 = ((sb + OFF_X) & 0x3FFFF) >> 4;
    float o[32], fin[32], rho[2];
    uint32_t tr[8];
    uint32_t r0[16], pt[16], sum[16], tag;
    auto recv_issue = [&](uint32_t (&r)[16], int k) {
#pragma unroll
      for (int i = 0; i < 4; i++) ld_b128(precv + k * 1024 + i * 32, r[4 * i], r[4 * i + 1], r[4 * i + 2], r[4 * i + 3]);
    };
    auto stale = [&](uint32_t (&r)[16]) {
      uint32_t t0, t1, r_;
      asm("lop3.b32 %0, %1, %2, %3, 0x7e;" : "=r"(t0) : "r"(r[0]), "r"(r[4]), "r"(tag));
      asm("lop3.b32 %0, %1, %2, %3, 0x7e;" : "=r"(t1) : "r"(r[8]), "r"(r[12]), "r"(tag));
      asm volatile("{.reg .pred p; .reg .b32 t; lop3.b32 t, %1, %2, 1, 0xa8; setp.ne.u32 p, t, 0; vote.sync.any.pred p, p, 0xffffffff; selp.u32 %0, 1, 0, p;}" : "=r"(r_) : "r"(t0), "r"(t1));
      return r_ != 0;
    };
    auto recv_check = [&](uint32_t (&r)[16], int k) {
      if (__builtin_expect(stale(r), 0)) {
        int tries = 0;
#pragma unroll 1
        do { recv_issue(r, k); } while (stale(r) && ++tries < 200000);
      }
    };
    auto gelu_b = [&](int i0, int i1) {
#pragma unroll
      for (int i = i0; i < i1; i++) {
        pin(ab[2 * i]); pin(ab[2 * i + 1]);
        H[24 + i] = gelu2_pair(ab[2 * i], ab[2 * i + 1]);
        pin(H[24 + i]);
      }
    };
    auto step = [&](float (&d)[32], int p, int k, int acc) {
      const uint32_t wo = stage_off(p);
      if (k >= 6 && k < 14) {
        const int kk = k - 6;
        wgmma_n64_rs<0, DH128>(d, hf[4 * kk], hf[4 * kk + 1], hf[4 * kk + 2], hf[4 * kk + 3], dx0, wo + 14336 + (kk >> 2) * 8192 + (kk & 3) * 32, 1);
      } else {
        const int kk = k < 6 ? k : k - 8;
        wgmma_n64_rs<1, DH128>(d, H[4 * kk], H[4 * kk + 1], H[4 * kk + 2], H[4 * kk + 3], dx0, wo + (kk / 7) * 30720 + (kk % 7) * 2048, k != 0 || acc);
      }
    };
    auto mma = [&](float (&d)[32], int p, int k0, int k1, int acc) {
      wg_fence();
#pragma unroll
      for (int k = k0; k < k1; k++) step(d, p, k, acc);
      wg_commit();
    };
    auto send_peer = [&]() {
#pragma unroll
      for (int i = 0; i < 4; i++)
        asm volatile("st.async.shared::cluster.mbarrier::complete_tx::bytes.v4.b32 [%0], {%1,%2,%3,%4}, [%5];" ::"r"(peer + pbuf + i * 512),
                     "r"(pack_bf16(o[8 * i], o[8 * i + 1])), "r"(pack_bf16(o[8 * i + 2], o[8 * i + 3])), "r"(pack_bf16(o[8 * i + 4], o[8 * i + 5])),
                     "r"(pack_bf16(o[8 * i + 6], o[8 * i + 7])), "r"(peer + OFF_RBAR + wg * 8) : "memory");
    };
    auto recv_peer = [&](int k) {
      mbar_wait(sb + OFF_RBAR + wg * 8, k & 1);
#pragma unroll
      for (int i = 0; i < 4; i++) { const uint4 v = lds_u4(sb + pbuf + i * 512); pt[4 * i] = v.x; pt[4 * i + 1] = v.y; pt[4 * i + 2] = v.z; pt[4 * i + 3] = v.w; }
    };
    auto send_owner = [&](float (&d)[32], int k) {
#pragma unroll
      for (int i = 0; i < 4; i++) {
#pragma unroll
        for (int c = 4 * i; c < 4 * i + 4; c++) pt[c] = bf2_add(pt[c], pack_bf16(d[2 * c], d[2 * c + 1]));
        asm("lop3.b32 %0, %0, 1, %1, 0xb8;" : "+r"(pt[4 * i]) : "r"(tag));
        st_b128(psend + (((sp + 1 + k) & 3) * 6 + k) * 1024 + i * 32, pt[4 * i], pt[4 * i + 1], pt[4 * i + 2], pt[4 * i + 3]);
      }
      __syncwarp();
      credit();
    };
    auto load_fin = [&]() {
      mbar_wait(sb + OFF_LBAR, 1);
#pragma unroll
      for (int j = 0; j < 8; j++) {
        const uint4 v = lds_u4(sb + pbuf + 16384 + (j >> 2) * 16384 + (j & 3) * 512);
        fin[4 * j] = __uint_as_float(v.x); fin[4 * j + 1] = __uint_as_float(v.y); fin[4 * j + 2] = __uint_as_float(v.z); fin[4 * j + 3] = __uint_as_float(v.w);
      }
    };
    auto ldk = [&](int pos) { if (pos == K0P) recv_issue(sum, 0); if (pos == K1P) recv_issue(r0, 1); };
    auto arm = [&]() { if ((threadIdx.x & 127) == 0) mbar_expect_tx(sb + OFF_RBAR + wg * 8, 8192); };
#pragma unroll
    for (int p = 0; p < 8; p++) {
      if (p == 0) {
        mbar_wait(fullb, 0);
        mma(o, 0, 0, 3, 0);
        wg_wait<1>(); release(5);
        gelu_b(0, 4);
        mma(o, 0, 3, 6, 0);
        bar_sync(1 + wg, 128);
        {
          const uint32_t ha = xw + ((lane >> 4) * 8 + (lane & 7)) * 128 + (((2 * w + ((lane >> 3) & 1)) ^ (lane & 7)) << 4);
#pragma unroll
          for (int kk = 0; kk < 8; kk++)
            asm volatile("ldmatrix.sync.aligned.m8n8.x4.trans.shared.b16 {%0,%1,%2,%3}, [%4];" : "=r"(hf[4 * kk]), "=r"(hf[4 * kk + 1]), "=r"(hf[4 * kk + 2]), "=r"(hf[4 * kk + 3])
                         : "r"(ha + (kk >> 2) * him + (kk & 3) * 2048) : "memory");
        }
        gelu_b(4, 10);
        mbar_wait(fullb + 8, 0);
        mma(o, 0, 6, 10, 0);
        credit();
        gelu_b(10, 16);
        mma(o, 0, 10, 15, 0);
        gelu_b(16, 24);
        mbar_wait(fullb + 16, 0);
        mma(o, 0, 15, 18, 0);
        gelu_b(24, 32);
        if (wg == 1) bar_sync(4, 256);
        mma(o, 0, 18, 22, 0);
      } else {
        TR(0);
        if (EW == 0 || (EW == 1 && (p & 1))) mbar_wait(sb + OFF_XFULL + 8 * p, 1);
        TR(1);
        bar_sync(3 + wg, 256);
        if (p < 7) mma(o, p, 0, 22, 0);
        else if (GAP == 0) mma(fin, p, 0, 22, 1);
        else {
          mma(fin, p, 0, GAP, 1);
          recv_peer(3);
          tag = lds_u(sb + OFF_EPOCH);
          mma(fin, p, GAP, 22, 1);
        }
      }
      if (p < 7 || wg == 0) bar_arrive(4 - wg, 256);
      TR(2);
      if (p != TP) TS(wg, 8 + p);
      if (p < 7 && (EW == 2 || (EW == 1 && (p & 1)))) mbar_wait(sb + OFF_XFULL + 8 * (p + 1), 1);
      ldk(10 * p);
      if ((p & 1) == 0) {
        arm();
        if (p == 6) {
          mbar_wait(sb + OFF_EMPTY + 32, 0);
          tag = lds_u(sb + OFF_EPOCH);
          recv_check(sum, 0); recv_check(r0, 1);
#pragma unroll
          for (int i = 0; i < 16; i++) sum[i] = bf2_add(sum[i], r0[i]);
        }
        TR(3);
        mbar_wait(sb + OFF_KBAR + wg * 8, (p >> 1) & 1);
        TR(4);
      } else {
        if (p == 1 || (p == 7 && GAP == 0)) tag = lds_u(sb + OFF_EPOCH);
        TR(3);
        if (p < 7 || GAP == 0) recv_peer(p >> 1);
        TR(4);
        if (p == 7) {
          recv_check(r0, 2);
#pragma unroll
          for (int i = 0; i < 16; i++) sum[i] = bf2_add(sum[i], bf2_add(r0[i], pt[i]));
        }
      }
      if (p == FINP && !FINW) load_fin();
      ldk(10 * p + 1);
      TR(5);
      wg_wait<0>();
      TR(6);
      if (p < 5) release(p);
      if (p < 7) reg_fence(o); else reg_fence(fin);
      ldk(10 * p + 2);
      if ((p & 1) == 0) {
        if (p == 6) recv_issue(r0, 2);
        send_peer();
        if (p == FINP && FINW) load_fin();
      } else if (p < 7) {
        send_owner(o, p >> 1);
      }
      ldk(10 * p + 3);
      if (p == 2) {
#pragma unroll
        for (int h = 0; h < 2; h++) { rho[h] = __fdividef(2.f, 4.f + bf_lo(lds_h(sb + OFF_GS + (wg * 64 + w * 16 + gr + 8 * h) * 2))); pin(rho[h]); }
      }
      TR(7);
    }
    {
      TS(wg, 16);
      const uint32_t tb = sb + OFF_X + stage_off(0) + warp * 4096;
      const uint32_t ta = tb + gr * 256 + ((gr & 3) << 5) + q * 8;
      const uint32_t la = tb + (lane >> 3) * 256 + (((lane & 7) << 4) ^ ((lane >> 3) << 5));
      float* op = out + (size_t)(m * 128 + wg * 64 + (lane >> 4) * 16 + w * 4 + ((lane >> 3) & 1)) * DM + s * 64 + (lane & 7) * 4;
#pragma unroll
      for (int qq = 0; qq < 4; qq += QS) {
#pragma unroll
        for (int qt = qq; qt < qq + QS; qt++) {
          const int h = qt & 1, ch = qt >> 1;
#pragma unroll
          for (int j = 0; j < 4; j++) {
            const int i = ch * 8 + j * 2 + h;
            asm volatile("st.shared.v2.f32 [%0], {%1,%2};" ::"r"((ta ^ (j << 5)) + h * 2048 + ch * 128),
                         "f"((fin[2 * i] + bf_lo(sum[i])) * rho[h]), "f"((fin[2 * i + 1] + bf_hi(sum[i])) * rho[h]) : "memory");
          }
        }
        __syncwarp();
#pragma unroll
        for (int qt = qq; qt < qq + QS; qt++) {
          const int h = qt & 1, ch = qt >> 1;
#pragma unroll
          for (int r = 0; r < 2; r++)
            *reinterpret_cast<uint4*>(op + (r * 32 + h * 2) * DM + ch * 32) = lds_u4(la + (h * 2 + r) * 1024 + ch * 128);
        }
      }
      if (threadIdx.x == 128) g_epoch[b] = tag;
      TS(wg, 17); TG(wg); TRD(); TDUMP();
    }
  } else {
    asm volatile("setmaxnreg.dec.sync.aligned.u32 56;");
    int wsel = warp;
    asm("" : "+r"(wsel));
    if (wsel > 8) {
      if (warp != 11) {
        const int t = threadIdx.x - 288;
        unsigned par;
        asm volatile("ld.relaxed.gpu.global.u32 %0, [%1];" : "=r"(par) : "l"(g_epoch + b) : "memory");
        const float pr = bf_ld(lam_re + s * 64 + t), pi = bf_ld(lam_im + s * 64 + t), pd = bf_ld(log_dt + s * 64 + t);
        asm volatile("barrier.cluster.wait.aligned;" ::: "memory");
        par = __shfl_sync(0xffffffffu, (par + 1) & 1, 0);
        cplx l64 = make_lam(pr, pi, pd);
        {
          const float inv = __fdividef(1.f, fmaf(pr, pr, pi * pi));
          const cplx l1 = l64, cf = cmul(cplx{l1.re - 1.f, l1.im}, cplx{pr * inv, -pi * inv});
          cplx l16 = cmul(l1, l1); l16 = cmul(l16, l16); l16 = cmul(l16, l16); l16 = cmul(l16, l16);
          const cplx l32 = cmul(l16, l16), c1 = cmul(cf, l16), c2 = cmul(cf, l32), c3 = cmul(c2, l16);
          l64 = cmul(l32, l32);
          mbar_wait(sb + OFF_EMPTY + 16, 0);
          asm volatile("st.shared.v4.f32 [%0], {%1,%2,%3,%4};" ::"r"(sb + OFF_LC + t * 16), "f"(l1.re), "f"(l1.im), "f"(cf.re), "f"(cf.im) : "memory");
          asm volatile("st.shared.v4.f32 [%0], {%1,%2,%3,%4};" ::"r"(sb + OFF_LC + 1024 + t * 16), "f"(l16.re), "f"(l16.im), "f"(l32.re), "f"(l32.im) : "memory");
          asm volatile("st.shared.v4.f32 [%0], {%1,%2,%3,%4};" ::"r"(sb + OFF_LC + 2048 + t * 32), "f"(cf.re), "f"(cf.im), "f"(c1.re), "f"(c1.im) : "memory");
          asm volatile("st.shared.v4.f32 [%0], {%1,%2,%3,%4};" ::"r"(sb + OFF_LC + 2064 + t * 32), "f"(c2.re), "f"(c2.im), "f"(c3.re), "f"(c3.im) : "memory");
          asm volatile("fence.proxy.async.shared::cta;" ::: "memory");
          mbar_arrive(sb + OFF_LBAR);
        }
        cplx l128 = cmul(l64, l64);
        pin(l128.re); pin(l128.im);
        uint32_t vr[15], vi[15];
#pragma unroll
        for (int i = 0; i < 15; i++) { vr[i] = par; vi[i] = 0; pin(vr[i]); pin(vi[i]); }
        mbar_wait(sb + OFF_GBAR, 0);
        const float2 e0 = lds_f2(sb + OFF_CARRY + t * 8), e1 = lds_f2(sb + OFF_CARRY + 512 + t * 8);
        float2* eb = g_end + s * 1024 + t;
        {
          const cplx e = cfma(l64, cplx{e0.x, e0.y}, cplx{e1.x, e1.y});
          const unsigned long long v = ((unsigned long long)__float_as_uint(e.im) << 32) | ((__float_as_uint(e.re) & ~1u) | par);
          asm volatile("st.relaxed.gpu.global.b64 [%0], %1;" ::"l"(eb + m * 64), "l"(v) : "memory");
        }
        if (t == 0) TS(3, 1);
        cplx S = {0.f, 0.f};
        {
          if (LBD) __nanosleep(LBD);
          const float2* e15 = eb + (m - 15) * 64;
          int tries = 0;
          bool bad;
#pragma unroll 1
          do {
#pragma unroll
            for (int i = 0; i < 15; i++)
              asm volatile("{.reg .pred p; .reg .b64 v; mov.b64 v, {%0,%1}; setp.ge.s32 p, %3, %4; @p ld.relaxed.gpu.global.b64 v, [%2]; mov.b64 {%0,%1}, v;}"
                           : "+r"(vr[i]), "+r"(vi[i]) : "l"(e15 + i * 64), "r"(m), "r"(15 - i) : "memory");
            uint32_t x = vr[0] ^ par;
#pragma unroll
            for (int i = 1; i < 15; i++) asm("lop3.b32 %0, %0, %1, %2, 0xf6;" : "+r"(x) : "r"(vr[i]), "r"(par));
            bad = __any_sync(0xffffffffu, x & 1);
          } while (bad && ++tries < 200000);
          if (t == 0) TS(3, 2);
          S = cplx{__uint_as_float(vr[0]), __uint_as_float(vi[0])};
#pragma unroll
          for (int i = 1; i < 15; i++) S = cfma(l128, S, cplx{__uint_as_float(vr[i]), __uint_as_float(vi[i])});
        }
        const cplx S1 = cfma(l64, S, cplx{e0.x, e0.y});
        asm volatile("st.shared.v2.f32 [%0], {%1,%2};" ::"r"(sb + OFF_CARRY + t * 8), "f"(S.re), "f"(S.im) : "memory");
        asm volatile("st.shared.v2.f32 [%0], {%1,%2};" ::"r"(sb + OFF_CARRY + 512 + t * 8), "f"(S1.re), "f"(S1.im) : "memory");
        mbar_arrive(sb + OFF_CBAR);
        if (t == 0) TS(3, 3);
        mbar_wait(sb + OFF_CBAR, 0);
        const int gr = lane >> 2, q = lane & 3;
        float2 db[8];
#pragma unroll
        for (int j = 0; j < 8; j++) db[j] = lds_f2(sb + OFF_DB + j * 32 + q * 8);
        mbar_wait(sb + OFF_XFULL + 16, 1);
        mbar_wait(sb + OFF_EMPTY, 0);
#pragma unroll 1
        for (int cw = warp - 9; cw < 8; cw += 2) {
          const float r0 = 0.5f * bf_lo(lds_h(sb + OFF_GS + (cw * 16 + gr) * 2)), r1 = 0.5f * bf_lo(lds_h(sb + OFF_GS + (cw * 16 + gr) * 2 + 16));
          const uint32_t xa = sb + OFF_X + (1 + rank) * 16384 + (cw * 16 + (lane & 15)) * 128 + (((lane >> 4) ^ (lane & 7)) << 4);
          uint32_t xv[16];
#pragma unroll
          for (int i = 0; i < 4; i++)
            asm volatile("ldmatrix.sync.aligned.m8n8.x4.shared.b16 {%0,%1,%2,%3}, [%4];" : "=r"(xv[4 * i]), "=r"(xv[4 * i + 1]), "=r"(xv[4 * i + 2]), "=r"(xv[4 * i + 3])
                         : "r"(xa ^ (i << 5)) : "memory");
          __syncwarp();
#pragma unroll
          for (int j = 0; j < 8; j++) {
            const uint32_t x0 = bf2_mul(xv[2 * j], __float_as_uint(db[j].x)), x1 = bf2_mul(xv[2 * j + 1], __float_as_uint(db[j].x));
            pin(db[j].y);
            const float bl = bf_lo(__float_as_uint(db[j].y)), bh = bf_hi(__float_as_uint(db[j].y));
            asm volatile("st.shared.v4.f32 [%0], {%1,%2,%3,%4};" ::"r"(sb + OFF_X + 16384 + (j >> 2) * 16384 + cw * 2048 + (j & 3) * 512 + lane * 16), "f"(fmaf(bf_lo(x0), r0, bl)),
                         "f"(fmaf(bf_hi(x0), r0, bh)), "f"(fmaf(bf_lo(x1), r1, bl)), "f"(fmaf(bf_hi(x1), r1, bh)) : "memory");
          }
        }
        mbar_arrive(sb + OFF_LBAR);
        if (t == 0) TS(3, 5);
      } else {
        if (lane == 0) TG(2);
        const uint4* gwp = reinterpret_cast<const uint4*>(gate_w) + (lane & 7);
        uint4 gw[4];
#pragma unroll
        for (int i = 0; i < 4; i++) gw[i] = __ldg(gwp + i * 8);
        unsigned par;
        asm volatile("ld.relaxed.gpu.global.u32 %0, [%1];" : "=r"(par) : "l"(g_epoch + b) : "memory");
        const uint32_t dk = __ldg(reinterpret_cast<const uint32_t*>(dskip + s * 64) + lane), bb = __ldg(reinterpret_cast<const uint32_t*>(b2 + s * 64) + lane);
        asm volatile("barrier.cluster.wait.aligned;" ::: "memory");
        const int row = s * 16 + (lane >> 3);
        const uint32_t xr0 = sb + OFF_X + row * 128 + (((lane & 7) ^ (row & 7)) << 4), xr1 = (xr0 + 512) ^ 64;
        float z[4] = {0.f, 0.f, 0.f, 0.f};
#pragma unroll
        for (int kb = 0; kb < 8; kb++) {
          const uint32_t wv[4] = {gw[kb & 3].x, gw[kb & 3].y, gw[kb & 3].z, gw[kb & 3].w};
          if (kb < 4) gw[kb] = __ldg(gwp + (kb + 4) * 8);
          mbar_wait(sb + OFF_XFULL + 8 * kb, 0);
          if ((PF & 2) && kb == PFK && elect_one()) {
            l2_prefetch(pf_w1 + b * 7168, 14336);
            l2_prefetch(pf_cre + b * 2048, 4096);
            l2_prefetch(pf_cim + b * 2048, 4096);
            l2_prefetch(pf_w2 + b * 7168, 14336);
          }
          const uint32_t xo = ((kb + xrot) & 7) * 16384;
#pragma unroll
          for (int r = 0; r < 4; r++) {
            const uint4 a = lds_u4(((r & 1) ? xr1 : xr0) + xo + (r >> 1) * 1024);
            const uint32_t p = bf2_fma(a.w, wv[3], bf2_fma(a.z, wv[2], bf2_fma(a.y, wv[1], bf2_mul(a.x, wv[0]))));
            z[r] += bf_lo(p); z[r] += bf_hi(p);
          }
        }
        if (lane == 0) asm volatile("st.shared.u32 [%0], %1;" ::"r"(sb + OFF_EPOCH), "r"(par + 1) : "memory");
        par = (par + 1) & 1;
        {
          float y0 = (lane & 4) ? z[1] : z[0], y1 = (lane & 4) ? z[3] : z[2];
          y0 += __shfl_xor_sync(0xffffffffu, (lane & 4) ? z[0] : z[1], 4);
          y1 += __shfl_xor_sync(0xffffffffu, (lane & 4) ? z[2] : z[3], 4);
          float zz = (lane & 2) ? y1 : y0;
          zz += __shfl_xor_sync(0xffffffffu, (lane & 2) ? y0 : y1, 2);
          zz += __shfl_xor_sync(0xffffffffu, zz, 1);
          const float rho = 4.f * expf(zz > 40.f ? 40.f : zz);
          if ((lane & 1) == 0)
            asm volatile("st.relaxed.gpu.global.u32 [%0], %1;" ::"l"(g_gate + m * 128 + row + (lane & 4) + (lane & 2) * 4), "r"((__float_as_uint(rho) & ~1u) | par) : "memory");
        }
        if ((PF & 8) && elect_one()) {
          l2_prefetch(pf_w2 + b * 7168, 14336);
          l2_prefetch(pf_cre + b * 2048, 4096);
          l2_prefetch(pf_cim + b * 2048, 4096);
        }
        if (lane == 0) TS(3, 0);
        mbar_wait(sb + OFF_GBAR, 0);
        asm volatile("st.shared.v2.u32 [%0], {%1,%2};" ::"r"(sb + OFF_DB + lane * 8), "r"(dk), "r"(bf2_add(bb, bb)) : "memory");
        uint32_t g0, g1, g2, g3;
        int tries = 0;
#pragma unroll 1
        do {
          asm volatile("ld.relaxed.gpu.global.v4.u32 {%0,%1,%2,%3}, [%4];" : "=r"(g0), "=r"(g1), "=r"(g2), "=r"(g3) : "l"(g_gate + m * 128 + lane * 4) : "memory");
        } while ((((g0 ^ par) | (g1 ^ par) | (g2 ^ par) | (g3 ^ par)) & 1) && ++tries < 200000);
        asm volatile("st.shared.v2.u32 [%0], {%1,%2};" ::"r"(sb + OFF_GS + lane * 8), "r"(pack_bf16(__uint_as_float(g0), __uint_as_float(g1))),
                     "r"(pack_bf16(__uint_as_float(g2), __uint_as_float(g3))) : "memory");
        mbar_arrive(sb + OFF_CBAR);
        if (lane == 0) TS(3, 4);
      }
    } else {
      asm volatile("barrier.cluster.wait.aligned;" ::: "memory");
      if (elect_one()) {
        TS(2, 1);
        const uint32_t t0 = clock();
#pragma unroll 1
        for (int u = 0; u < 8; u++) {
          if (u >= 1) while ((uint32_t)clock() - t0 < D0 + (u - 1) * D1) {}
          mbar_expect_tx(sb + OFF_XFULL + 8 * u, 16384);
          tma5d_mc(sb + OFF_X + ((u + xrot) & 7) * 16384 + rank * 8192, &maps.x, u * 64, 2 * m + rank, sb + OFF_XFULL + 8 * u);
          if (u < 6) {
            mbar_expect_tx(sb + OFF_FULL + 8 * u, 16384);
            tma2d(sb + OFF_RING + u * 16384, &maps.bre, u * 64, s * 64, sb + OFF_FULL + 8 * u);
            tma2d(sb + OFF_RING + u * 16384 + 8192, &maps.bim, u * 64, s * 64, sb + OFF_FULL + 8 * u);
          } else if (PF & 4) {
            asm volatile("cp.async.bulk.prefetch.tensor.2d.L2.global [%0, {%1,%2}];" ::"l"((m & 1) ? &maps.bim : &maps.bre), "r"(u * 64), "r"(s * 64) : "memory");
          }
        }
        TS(2, 5);
        int slot = 0; uint32_t ph = 0;
#pragma unroll 1
        for (int u = 6; u < 24; u++) {
          const uint32_t fb = sb + OFF_FULL + 8 * slot, dst = sb + OFF_RING + slot * 16384;
          mbar_wait(sb + OFF_EMPTY + 8 * slot, ph);
          TS2(0, u);
          if (u < 8) {
            mbar_expect_tx(fb, 16384);
            tma2d(dst, &maps.bre, u * 64, s * 64, fb);
            tma2d(dst + 8192, &maps.bim, u * 64, s * 64, fb);
          } else if (u < 16) {
            mbar_expect_tx(fb, 12288);
            tma3d(dst, &maps.w1b, 0, (u - 8) * 64, s * 7, fb);
          } else {
            mbar_expect_tx(fb, 16384);
            tma2d(dst, &maps.w1a, s * 224 + 96, ((u - xrot) & 7) * 64, fb);
            tma2d(dst + 8192, &maps.w1a, s * 224 + 160, ((u - xrot) & 7) * 64, fb);
          }
          if (++slot == NSLOT) { slot = 0; ph ^= 1; }
        }
#pragma unroll 1
        for (int j = 0; j < 3; j++) {
          const uint32_t fb = sb + OFF_FULL + 8 * j, dst = sb + OFF_X + stage_off(0);
          const int c = ((sp + 1) & 3) * 128 + ((rank ^ 1) << 6);
          mbar_wait(sb + OFF_EMPTY + 8 + 8 * j, 1);
          mbar_expect_tx(fb, j == 1 ? 16384 : 14336);
          if (j == 1) {
            tma2d(dst + 14336, &maps.cre, s * 64, c, fb);
            tma2d(dst + 22528, &maps.cim, s * 64, c, fb);
          } else {
            tma2d(dst + j * 15360, &maps.w2, c, s * 224 + j * 56, fb);
          }
        }
#pragma unroll 1
        for (int p = 1; p < 8; p++) {
          const int c = ((sp + 1 + (p >> 1)) & 3) * 128 + (((rank ^ p ^ 1) & 1) << 6);
          const uint32_t fb = sb + OFF_XFULL + 8 * p, dst = sb + OFF_X + stage_off(p);
          if (p == 2 || p > 3) mbar_wait(sb + OFF_EMPTY + (p == 2 ? 40 : (p - 4) * 8), p == 2);
          TS2(0, 32 + p);
          mbar_expect_tx(fb, 45056);
          tma2d(dst, &maps.w2, c, s * 224, fb);
          tma2d(dst + 14336, &maps.cre, s * 64, c, fb);
          tma2d(dst + 22528, &maps.cim, s * 64, c, fb);
          tma2d(dst + 30720, &maps.w2, c, s * 224 + 112, fb);
        }
        TS(2, 2);
      }
    }
  }
}

typedef CUresult (*EncFn)(CUtensorMap*, CUtensorMapDataType, cuuint32_t, void*, const cuuint64_t*, const cuuint64_t*, const cuuint32_t*,
                          const cuuint32_t*, CUtensorMapInterleave, CUtensorMapSwizzle, CUtensorMapL2promotion, CUtensorMapFloatOOBfill);

void encode(EncFn f, CUtensorMap* mp, const void* p, int rank, const cuuint64_t* dims, const cuuint64_t* strides, const cuuint32_t* box, CUtensorMapSwizzle sw) {
  cuuint32_t es[5] = {1, 1, 1, 1, 1};
  f(mp, CU_TENSOR_MAP_DATA_TYPE_BFLOAT16, rank, const_cast<void*>(p), dims, strides, box, es, CU_TENSOR_MAP_INTERLEAVE_NONE, sw,
    CU_TENSOR_MAP_L2_PROMOTION_L2_128B, CU_TENSOR_MAP_FLOAT_OOB_FILL_NONE);
}

}

extern "C" void kernel_launch(void* const* d_in, const int* in_sizes, int n_in, void* d_out, int out_size) {
  typedef const __nv_bfloat16* bp;
  bp x = (bp)d_in[0], lre = (bp)d_in[1], lim = (bp)d_in[2], bre = (bp)d_in[3], bim = (bp)d_in[4], cre = (bp)d_in[5], cim = (bp)d_in[6],
     ldt = (bp)d_in[7], dsk = (bp)d_in[8], w1 = (bp)d_in[10], b1 = (bp)d_in[11], w2 = (bp)d_in[12], b2 = (bp)d_in[13], gw = (bp)d_in[14];
  static EncFn enc = nullptr;
  if (!enc) {
    void* f = nullptr;
    cudaDriverEntryPointQueryResult qr;
    cudaGetDriverEntryPoint("cuTensorMapEncodeTiled", &f, cudaEnableDefault, &qr);
    enc = (EncFn)f;
    cudaFuncSetAttribute(fused_kernel, cudaFuncAttributeMaxDynamicSharedMemorySize, SMEM_BYTES);
  }
  Maps maps;
  {
    cuuint64_t d[5] = {DM, 2, 4, 8, SEQ / 64}, st[4] = {DM * 2, 16 * DM * 2, 2 * DM * 2, 64 * DM * 2};
    cuuint32_t bx[5] = {64, 2, 4, 8, 1};
    encode(enc, &maps.x, x, 5, d, st, bx, CU_TENSOR_MAP_SWIZZLE_128B);
  }
  {
    cuuint64_t d[2] = {DM, DM}, st[1] = {DM * 2};
    cuuint32_t bx[2] = {64, 64};
    encode(enc, &maps.bre, bre, 2, d, st, bx, CU_TENSOR_MAP_SWIZZLE_128B);
    encode(enc, &maps.bim, bim, 2, d, st, bx, CU_TENSOR_MAP_SWIZZLE_128B);
    encode(enc, &maps.cre, cre, 2, d, st, bx, CU_TENSOR_MAP_SWIZZLE_128B);
    encode(enc, &maps.cim, cim, 2, d, st, bx, CU_TENSOR_MAP_SWIZZLE_128B);
  }
  {
    cuuint64_t d[2] = {FF, DM}, st[1] = {FF * 2};
    cuuint32_t bx[2] = {64, 64};
    encode(enc, &maps.w1a, w1, 2, d, st, bx, CU_TENSOR_MAP_SWIZZLE_128B);
    cuuint64_t d3[3] = {32, DM, FF / 32}, st3[2] = {FF * 2, 64};
    cuuint32_t bx3[3] = {32, 64, 3};
    encode(enc, &maps.w1b, w1, 3, d3, st3, bx3, CU_TENSOR_MAP_SWIZZLE_64B);
  }
  {
    cuuint64_t d[2] = {DM, FF}, st[1] = {DM * 2};
    cuuint32_t bx[2] = {64, 112};
    encode(enc, &maps.w2, w2, 2, d, st, bx, CU_TENSOR_MAP_SWIZZLE_128B);
  }
  fused_kernel<<<128, 384, SMEM_BYTES>>>(lre, lim, ldt, dsk, b1, b2, gw, w1, w2, cre, cim, (float*)d_out, maps);
}
```

```cpp
#include <cuda_runtime.h>
#include <cuda_bf16.h>
#include <cuda.h>
#include <stdint.h>

#define MAP 1
#define D0 600
#define D1 500
#define PF 4
#define PFK 5
#define GELUP 1
#define EW 2
#define K1E 1
#define K2E 0
#define QS 1
#define K2G 4
#define FINP 4
#define LBD 300
#define PFS 32
#define SB0 2
#define PFD 2
#define HOLD 0
#define GAP 14
#define FINW 0
#define K0P 33
#define K1P 53
#define TP 9
#define TW 0

namespace {

constexpr int SEQ = 2048, DM = 512, FF = 1792;
constexpr int NSLOT = 6;
constexpr uint32_t OFF_X = 0, OFF_RING = 131072, OFF_MISC = 229376;
constexpr uint32_t OFF_XFULL = OFF_MISC, OFF_FULL = OFF_XFULL + 64, OFF_RBAR = OFF_FULL + 48, OFF_EMPTY = OFF_RBAR + 16, OFF_KBAR = OFF_EMPTY + 48,
                   OFF_GBAR = OFF_KBAR + 16, OFF_LBAR = OFF_GBAR + 8, OFF_CBAR = OFF_LBAR + 8, OFF_EPOCH = OFF_CBAR + 8;
constexpr uint32_t OFF_LC = OFF_MISC + 256;
constexpr uint32_t OFF_GS = OFF_LC;
constexpr uint32_t OFF_DB = OFF_LC + 512;
constexpr uint32_t OFF_CARRY = OFF_LC + 1024;
constexpr uint32_t OFF_DBG = OFF_CARRY + 1024;
constexpr uint32_t SMEM_BYTES = OFF_DBG + 768;
static_assert(SMEM_BYTES <= 232448, "smem");

struct Maps { CUtensorMap x, bre, bim, w1b, w1a, w2, cre, cim; };
__host__ __device__ constexpr uint32_t stage_off(int p) { return 49152 + 45056 * (((p >> 1) & 1) + 2 * (p & 1)); }

__device__ uint4 g_part[16 * 8 * 3 * 1024];
__device__ float2 g_end[8 * 16 * 64];
__device__ unsigned g_gate[SEQ];
__device__ unsigned g_epoch[128];
#define TG(role) do {} while (0)
#define TS2(role, i) do {} while (0)
#define TS(role, i) do {} while (0)
#define TDUMP() do {} while (0)
#define TR(i) do {} while (0)
#define TRD() do {} while (0)

__device__ __forceinline__ void mbar_init(uint32_t bar, uint32_t cnt) { asm volatile("mbarrier.init.shared::cta.b64 [%0], %1;" ::"r"(bar), "r"(cnt)); }
__device__ __forceinline__ void mbar_expect_tx(uint32_t bar, uint32_t bytes) { asm volatile("mbarrier.arrive.expect_tx.shared::cta.b64 _, [%0], %1;" ::"r"(bar), "r"(bytes) : "memory"); }
__device__ __forceinline__ void mbar_arrive(uint32_t bar) { asm volatile("mbarrier.arrive.shared::cta.b64 _, [%0];" ::"r"(bar) : "memory"); }
__device__ __forceinline__ void mbar_arrive_cl(uint32_t cbar) { asm volatile("mbarrier.arrive.shared::cluster.b64 _, [%0];" ::"r"(cbar) : "memory"); }
__device__ __forceinline__ void mbar_wait(uint32_t bar, uint32_t parity) {
  asm volatile(
      "{\n.reg .pred p;\n.reg .u32 c;\n"
      "mbarrier.try_wait.parity.shared::cta.b64 p, [%0], %1;\n"
      "@p bra.uni LAB_DONE;\n"
      "mov.u32 c, 0;\n"
      "LAB_WAIT:\n"
      "mbarrier.try_wait.parity.shared::cta.b64 p, [%0], %1;\n"
      "@p bra.uni LAB_DONE;\n"
      "add.u32 c, c, 1;\nsetp.lt.u32 p, c, 200000;\n@p bra.uni LAB_WAIT;\n"
      "LAB_DONE:\n}" ::"r"(bar), "r"(parity) : "memory");
}
__device__ __forceinline__ void tma2d(uint32_t dst, const CUtensorMap* m, int c0, int c1, uint32_t bar) {
  asm volatile("cp.async.bulk.tensor.2d.shared::cluster.global.mbarrier::complete_tx::bytes [%0], [%1, {%3,%4}], [%2];"
               ::"r"(dst), "l"(m), "r"(bar), "r"(c0), "r"(c1) : "memory");
}
__device__ __forceinline__ void tma3d(uint32_t dst, const CUtensorMap* m, int c0, int c1, int c2, uint32_t bar) {
  asm volatile("cp.async.bulk.tensor.3d.shared::cluster.global.mbarrier::complete_tx::bytes [%0], [%1, {%3,%4,%5}], [%2];"
               ::"r"(dst), "l"(m), "r"(bar), "r"(c0), "r"(c1), "r"(c2) : "memory");
}
__device__ __forceinline__ void tma5d_mc(uint32_t dst, const CUtensorMap* m, int c0, int c4, uint32_t bar) {
  asm volatile("cp.async.bulk.tensor.5d.shared::cluster.global.mbarrier::complete_tx::bytes.multicast::cluster [%0], [%1, {%3,%5,%5,%5,%4}], [%2], %6;"
               ::"r"(dst), "l"(m), "r"(bar), "r"(c0), "r"(c4), "r"(0), "h"((uint16_t)3) : "memory");
}
__device__ __forceinline__ void l2_prefetch(const void* p, uint32_t bytes) { asm volatile("cp.async.bulk.prefetch.L2.global [%0], %1;" ::"l"(p), "r"(bytes) : "memory"); }
__device__ __forceinline__ bool elect_one() {
  uint32_t pred;
  asm volatile("{.reg .pred P; elect.sync _|P, 0xffffffff; selp.u32 %0, 1, 0, P;}" : "=r"(pred));
  return pred != 0;
}
__device__ __forceinline__ void wg_fence() { asm volatile("wgmma.fence.sync.aligned;" ::: "memory"); }
__device__ __forceinline__ void wg_commit() { asm volatile("wgmma.commit_group.sync.aligned;" ::: "memory"); }
template <int N> __device__ __forceinline__ void wg_wait() { asm volatile("wgmma.wait_group.sync.aligned %0;" ::"n"(N) : "memory"); }
__device__ __forceinline__ void pin(float& a) { asm volatile("" : "+f"(a)::"memory"); }
__device__ __forceinline__ void pin(uint32_t& a) { asm volatile("" : "+r"(a)::"memory"); }
template <int N> __device__ __forceinline__ void reg_fence(float (&d)[N]) {
#pragma unroll
  for (int i = 0; i < N; i++) pin(d[i]);
}
__device__ __forceinline__ void bar_sync(int id, int n) { asm volatile("bar.sync %0, %1;" ::"r"(id), "r"(n) : "memory"); }
__device__ __forceinline__ void bar_arrive(int id, int n) { asm volatile("bar.arrive %0, %1;" ::"r"(id), "r"(n) : "memory"); }
constexpr uint32_t DH128 = (1024 >> 4) | (1u << 30), DH64 = (512 >> 4) | (2u << 30);
__host__ __device__ constexpr uint32_t lbo(uint32_t bytes) { return (bytes >> 4) << 20; }
__device__ __forceinline__ uint32_t pack_bf16(float lo, float hi) { uint32_t r; asm("cvt.rn.bf16x2.f32 %0, %1, %2;" : "=r"(r) : "f"(hi), "f"(lo)); return r; }
__device__ __forceinline__ float bf_lo(uint32_t v) { return __uint_as_float(v << 16); }
__device__ __forceinline__ float bf_hi(uint32_t v) { return __uint_as_float(v & 0xffff0000u); }
__device__ __forceinline__ float bf_ld(const __nv_bfloat16* p) { return __bfloat162float(__ldg(p)); }
__device__ __forceinline__ uint32_t late16(uint32_t bar) {
  uint32_t r;
  asm volatile("{.reg .pred p; mbarrier.test_wait.parity.shared::cta.b64 p, [%1], 0; selp.u32 %0, 16, 0, p;}" : "=r"(r) : "r"(bar) : "memory");
  return r;
}
__device__ __forceinline__ float2 lds_f2(uint32_t a) { float2 v; asm volatile("ld.shared.v2.f32 {%0,%1}, [%2];" : "=f"(v.x), "=f"(v.y) : "r"(a)); return v; }
__device__ __forceinline__ uint32_t lds_h(uint32_t a) { uint32_t v; asm volatile("ld.shared.u16 %0, [%1];" : "=r"(v) : "r"(a)); return v; }
__device__ __forceinline__ uint32_t lds_u(uint32_t a) { uint32_t v; asm volatile("ld.shared.u32 %0, [%1];" : "=r"(v) : "r"(a)); return v; }
__device__ __forceinline__ uint4 lds_u4(uint32_t a) { uint4 v; asm volatile("ld.shared.v4.u32 {%0,%1,%2,%3}, [%4];" : "=r"(v.x), "=r"(v.y), "=r"(v.z), "=r"(v.w) : "r"(a)); return v; }
__device__ __forceinline__ void st_b128(uint4* p, uint32_t a, uint32_t b, uint32_t c, uint32_t d) {
  asm volatile("st.relaxed.gpu.global.v4.b32 [%0], {%1,%2,%3,%4};" ::"l"(p), "r"(a), "r"(b), "r"(c), "r"(d) : "memory");
}
__device__ __forceinline__ void ld_b128(const uint4* p, uint32_t& a, uint32_t& b, uint32_t& c, uint32_t& d) {
  asm volatile("{.reg .b64 l, h; .reg .b128 v; ld.relaxed.gpu.global.b128 v, [%4]; mov.b128 {l,h}, v; mov.b64 {%0,%1}, l; mov.b64 {%2,%3}, h;}"
               : "=r"(a), "=r"(b), "=r"(c), "=r"(d) : "l"(p) : "memory");
}
__device__ __forceinline__ float tanh_fast(float x) { float y; asm("tanh.approx.f32 %0, %1;" : "=f"(y) : "f"(x)); return y; }
__device__ __forceinline__ float gelu2(float v) {
  float p = fmaf(v * v, 0.0356774081363f, 0.7978845608029f);
  return fmaf(v, tanh_fast(v * p), v);
}
__device__ __forceinline__ uint32_t bf2_mul(uint32_t a, uint32_t b) { uint32_t r; asm("mul.rn.bf16x2 %0, %1, %2;" : "=r"(r) : "r"(a), "r"(b)); return r; }
__device__ __forceinline__ uint32_t bf2_add(uint32_t a, uint32_t b) { uint32_t r; asm("add.rn.bf16x2 %0, %1, %2;" : "=r"(r) : "r"(a), "r"(b)); return r; }
__device__ __forceinline__ uint32_t bf2_fma(uint32_t a, uint32_t b, uint32_t c) { uint32_t r; asm("fma.rn.bf16x2 %0, %1, %2, %3;" : "=r"(r) : "r"(a), "r"(b), "r"(c)); return r; }
__device__ __forceinline__ uint32_t gelu2_pair(float a, float b) {
  const uint32_t v = pack_bf16(a, b);
  uint32_t t;
  asm("tanh.approx.bf16x2 %0, %1;" : "=r"(t) : "r"(bf2_fma(v, bf2_fma(bf2_mul(v, v), 0x3d123d12u, 0xbe4fbe4fu), v)));
  return bf2_fma(v, t, v);
}
struct cplx { float re, im; };
__device__ __forceinline__ cplx cmul(cplx a, cplx b) { return {fmaf(a.re, b.re, -a.im * b.im), fmaf(a.re, b.im, a.im * b.re)}; }
__device__ __forceinline__ cplx cfma(cplx a, cplx b, cplx c) {
  return {fmaf(a.re, b.re, fmaf(-a.im, b.im, c.re)), fmaf(a.re, b.im, fmaf(a.im, b.re, c.im))};
}
__device__ __forceinline__ cplx make_lam(float lre, float lim, float ldt) {
  float dt = __bfloat162float(__float2bfloat16_rn(expf(ldt)));
  float mag = expf(dt * lre), sn, cs;
  sincospif(dt * lim * 0.31830988618379067f, &sn, &cs);
  return {mag * cs, mag * sn};
}

template<int TA,int TB,uint32_t AH,uint32_t BH> __device__ __forceinline__ void wgmma_n64_ss(float (&d)[32], uint32_t al, uint32_t ao, uint32_t bl, uint32_t bo, int scale_d){
  asm volatile("{.reg .pred p; .reg .b32 t, v; .reg .b64 da, db; setp.ne.b32 p, %36, 0; add.u32 t, %32, %33; mov.b64 da, {t, %39}; add.u32 v, %34, %35; mov.b64 db, {v, %40};\n"
   "wgmma.mma_async.sync.aligned.m64n64k16.f32.bf16.bf16 {%0,%1,%2,%3,%4,%5,%6,%7,%8,%9,%10,%11,%12,%13,%14,%15,%16,%17,%18,%19,%20,%21,%22,%23,%24,%25,%26,%27,%28,%29,%30,%31}, da, db, p, 1, 1, %37, %38;}"
   : "+f"(d[0]),"+f"(d[1]),"+f"(d[2]),"+f"(d[3]),"+f"(d[4]),"+f"(d[5]),"+f"(d[6]),"+f"(d[7]),"+f"(d[8]),"+f"(d[9]),"+f"(d[10]),"+f"(d[11]),"+f"(d[12]),"+f"(d[13]),"+f"(d[14]),"+f"(d[15]),"+f"(d[16]),"+f"(d[17]),"+f"(d[18]),"+f"(d[19]),"+f"(d[20]),"+f"(d[21]),"+f"(d[22]),"+f"(d[23]),"+f"(d[24]),"+f"(d[25]),"+f"(d[26]),"+f"(d[27]),"+f"(d[28]),"+f"(d[29]),"+f"(d[30]),"+f"(d[31])
   : "r"(al),"r"(ao >> 4),"r"(bl),"r"(bo >> 4),"r"(scale_d),"n"(TA),"n"(TB),"n"(AH),"n"(BH));
}
template<int TB,uint32_t BH> __device__ __forceinline__ void wgmma_n64_rs(float (&d)[32], uint32_t a0,uint32_t a1,uint32_t a2,uint32_t a3, uint32_t bl, uint32_t bo, int scale_d){
  asm volatile("{.reg .pred p; .reg .b32 t; .reg .b64 db; setp.ne.b32 p, %38, 0; add.u32 t, %36, %37; mov.b64 db, {t, %40};\n"
   "wgmma.mma_async.sync.aligned.m64n64k16.f32.bf16.bf16 {%0,%1,%2,%3,%4,%5,%6,%7,%8,%9,%10,%11,%12,%13,%14,%15,%16,%17,%18,%19,%20,%21,%22,%23,%24,%25,%26,%27,%28,%29,%30,%31}, {%32,%33,%34,%35}, db, p, 1, 1, %39;}"
   : "+f"(d[0]),"+f"(d[1]),"+f"(d[2]),"+f"(d[3]),"+f"(d[4]),"+f"(d[5]),"+f"(d[6]),"+f"(d[7]),"+f"(d[8]),"+f"(d[9]),"+f"(d[10]),"+f"(d[11]),"+f"(d[12]),"+f"(d[13]),"+f"(d[14]),"+f"(d[15]),"+f"(d[16]),"+f"(d[17]),"+f"(d[18]),"+f"(d[19]),"+f"(d[20]),"+f"(d[21]),"+f"(d[22]),"+f"(d[23]),"+f"(d[24]),"+f"(d[25]),"+f"(d[26]),"+f"(d[27]),"+f"(d[28]),"+f"(d[29]),"+f"(d[30]),"+f"(d[31])
   : "r"(a0),"r"(a1),"r"(a2),"r"(a3),"r"(bl),"r"(bo >> 4),"r"(scale_d),"n"(TB),"n"(BH));
}
template<int TA,int TB,uint32_t AH,uint32_t BH> __device__ __forceinline__ void wgmma_n96_ss(float (&d)[48], uint32_t al, uint32_t ao, uint32_t bl, uint32_t bo, int scale_d){
  asm volatile("{.reg .pred p; .reg .b32 t, v; .reg .b64 da, db; setp.ne.b32 p, %52, 0; add.u32 t, %48, %49; mov.b64 da, {t, %55}; add.u32 v, %50, %51; mov.b64 db, {v, %56};\n"
   "wgmma.mma_async.sync.aligned.m64n96k16.f32.bf16.bf16 {%0,%1,%2,%3,%4,%5,%6,%7,%8,%9,%10,%11,%12,%13,%14,%15,%16,%17,%18,%19,%20,%21,%22,%23,%24,%25,%26,%27,%28,%29,%30,%31,%32,%33,%34,%35,%36,%37,%38,%39,%40,%41,%42,%43,%44,%45,%46,%47}, da, db, p, 1, 1, %53, %54;}"
   : "+f"(d[0]),"+f"(d[1]),"+f"(d[2]),"+f"(d[3]),"+f"(d[4]),"+f"(d[5]),"+f"(d[6]),"+f"(d[7]),"+f"(d[8]),"+f"(d[9]),"+f"(d[10]),"+f"(d[11]),"+f"(d[12]),"+f"(d[13]),"+f"(d[14]),"+f"(d[15]),"+f"(d[16]),"+f"(d[17]),"+f"(d[18]),"+f"(d[19]),"+f"(d[20]),"+f"(d[21]),"+f"(d[22]),"+f"(d[23]),"+f"(d[24]),"+f"(d[25]),"+f"(d[26]),"+f"(d[27]),"+f"(d[28]),"+f"(d[29]),"+f"(d[30]),"+f"(d[31]),"+f"(d[32]),"+f"(d[33]),"+f"(d[34]),"+f"(d[35]),"+f"(d[36]),"+f"(d[37]),"+f"(d[38]),"+f"(d[39]),"+f"(d[40]),"+f"(d[41]),"+f"(d[42]),"+f"(d[43]),"+f"(d[44]),"+f"(d[45]),"+f"(d[46]),"+f"(d[47])
   : "r"(al),"r"(ao >> 4),"r"(bl),"r"(bo >> 4),"r"(scale_d),"n"(TA),"n"(TB),"n"(AH),"n"(BH));
}
template<int TA,int TB,uint32_t AH,uint32_t BH> __device__ __forceinline__ void wgmma_n128_ss(float (&d)[64], uint32_t al, uint32_t ao, uint32_t bl, uint32_t bo, int scale_d){
  asm volatile("{.reg .pred p; .reg .b32 t, v; .reg .b64 da, db; setp.ne.b32 p, %68, 0; add.u32 t, %64, %65; mov.b64 da, {t, %71}; add.u32 v, %66, %67; mov.b64 db, {v, %72};\n"
   "wgmma.mma_async.sync.aligned.m64n128k16.f32.bf16.bf16 {%0,%1,%2,%3,%4,%5,%6,%7,%8,%9,%10,%11,%12,%13,%14,%15,%16,%17,%18,%19,%20,%21,%22,%23,%24,%25,%26,%27,%28,%29,%30,%31,%32,%33,%34,%35,%36,%37,%38,%39,%40,%41,%42,%43,%44,%45,%46,%47,%48,%49,%50,%51,%52,%53,%54,%55,%56,%57,%58,%59,%60,%61,%62,%63}, da, db, p, 1, 1, %69, %70;}"
   : "+f"(d[0]),"+f"(d[1]),"+f"(d[2]),"+f"(d[3]),"+f"(d[4]),"+f"(d[5]),"+f"(d[6]),"+f"(d[7]),"+f"(d[8]),"+f"(d[9]),"+f"(d[10]),"+f"(d[11]),"+f"(d[12]),"+f"(d[13]),"+f"(d[14]),"+f"(d[15]),"+f"(d[16]),"+f"(d[17]),"+f"(d[18]),"+f"(d[19]),"+f"(d[20]),"+f"(d[21]),"+f"(d[22]),"+f"(d[23]),"+f"(d[24]),"+f"(d[25]),"+f"(d[26]),"+f"(d[27]),"+f"(d[28]),"+f"(d[29]),"+f"(d[30]),"+f"(d[31]),"+f"(d[32]),"+f"(d[33]),"+f"(d[34]),"+f"(d[35]),"+f"(d[36]),"+f"(d[37]),"+f"(d[38]),"+f"(d[39]),"+f"(d[40]),"+f"(d[41]),"+f"(d[42]),"+f"(d[43]),"+f"(d[44]),"+f"(d[45]),"+f"(d[46]),"+f"(d[47]),"+f"(d[48]),"+f"(d[49]),"+f"(d[50]),"+f"(d[51]),"+f"(d[52]),"+f"(d[53]),"+f"(d[54]),"+f"(d[55]),"+f"(d[56]),"+f"(d[57]),"+f"(d[58]),"+f"(d[59]),"+f"(d[60]),"+f"(d[61]),"+f"(d[62]),"+f"(d[63])
   : "r"(al),"r"(ao >> 4),"r"(bl),"r"(bo >> 4),"r"(scale_d),"n"(TA),"n"(TB),"n"(AH),"n"(BH));
}

__global__ void __cluster_dims__(2, 1, 1) __launch_bounds__(384, 1)
fused_kernel(const __nv_bfloat16* __restrict__ lam_re, const __nv_bfloat16* __restrict__ lam_im, const __nv_bfloat16* __restrict__ log_dt,
             const __nv_bfloat16* __restrict__ dskip, const __nv_bfloat16* __restrict__ b1, const __nv_bfloat16* __restrict__ b2,
             const __nv_bfloat16* __restrict__ gate_w, const __nv_bfloat16* __restrict__ pf_w1, const __nv_bfloat16* __restrict__ pf_w2,
             const __nv_bfloat16* __restrict__ pf_cre, const __nv_bfloat16* __restrict__ pf_cim, float* __restrict__ out,
             const __grid_constant__ Maps maps) {
  extern __shared__ __align__(1024) unsigned char smem_raw[];
  const uint32_t sb = (uint32_t)__cvta_generic_to_shared(smem_raw);
  const int b = blockIdx.x;
  const int rank = b & 1, cl = b >> 1;
  const int sp = (cl & 1) | ((cl >> 2) & 2), m = ((cl >> 1) & 3) | ((cl >> 4) << 2);
  const int s = sp * 2 + rank;
  const int warp = __shfl_sync(0xffffffffu, (int)(threadIdx.x >> 5), 0);
  const int lane = threadIdx.x & 31;
  const int xrot = 9 - 2 * sp;

  if (elect_one()) {
    if (warp == 8) TS(2, 0);
    if (warp < 3) {
      asm volatile("prefetch.tensormap [%0];" ::"l"(&maps.x + warp) : "memory");
      mbar_init(sb + OFF_GBAR + 8 * warp, warp < 2 ? 64 : 96);
    }
    const uint32_t c = warp < 8 ? 1 : warp < 11 ? 8 : 4;
    mbar_init(sb + OFF_XFULL + 16 * warp, c);
    mbar_init(sb + OFF_XFULL + 16 * warp + 8, c);
    asm volatile("fence.mbarrier_init.release.cluster;" ::: "memory");
  }
  __syncwarp();
  asm volatile("barrier.cluster.arrive.relaxed.aligned;" ::: "memory");

  if (warp < 8) {
    const int wg = warp >> 2, w = warp & 3, q = lane & 3, gr = lane >> 2;
    uint32_t bv[28];
#pragma unroll
    for (int j = 0; j < 28; j++) bv[j] = __ldg(reinterpret_cast<const uint32_t*>(b1 + s * 224 + j * 8) + q);
    asm volatile("setmaxnreg.inc.sync.aligned.u32 224;");
    asm volatile("barrier.cluster.wait.aligned;" ::: "memory");
    TS(wg, 0);
    auto release = [&](int slot) { if (lane == 0) mbar_arrive(sb + OFF_EMPTY + 8 * slot); };
    const uint32_t xw = sb + OFF_X + wg * 8192, fullb = sb + OFF_FULL;
    const uint32_t dxw = (xw & 0x3FFFF) >> 4, dring = ((sb + OFF_RING) & 0x3FFFF) >> 4;

    float ure[32], uim[32], aa[48], ab[64];
    cplx lam[2], coef[2], l16[2], l32[2], lq[2], pre[2], e[2];
    uint32_t sh16, mhi;

    auto bias = [&](int c) {
#pragma unroll
      for (int j = c * 7; j < c * 7 + 7; j++) {
        pin(bv[j]);
        float* d = j < 12 ? aa + 4 * j : ab + 4 * (j - 12);
        d[0] = d[2] = __uint_as_float(bv[j] << sh16); d[1] = d[3] = __uint_as_float(bv[j] & mhi);
        pin(d[0]); pin(d[1]); pin(d[2]); pin(d[3]);
      }
    };
    if (SB0 < 0) { sh16 = 16; mhi = 0xffff0000u; bias(0); bias(1); bias(2); bias(3); TS(wg, 27); }
#pragma unroll
    for (int kb = 0; kb < 8; kb++) {
      const int slot = kb % NSLOT;
      mbar_wait(sb + OFF_XFULL + 8 * kb, 0);
      if (kb == 0) TS(wg, 18);
      mbar_wait(fullb + 8 * slot, (kb / NSLOT) & 1);
      TS2(2, kb);
      if (kb == 0) TS(wg, 1);
      wg_fence();
      const uint32_t dxa = dxw + ((kb + xrot) & 7) * 1024;
#pragma unroll
      for (int kk = 0; kk < 4; kk++) {
        wgmma_n64_ss<0, 0, DH128, DH128>(ure, dring, slot * 16384 + kk * 32, dxa, kk * 32, (kb | kk) != 0);
        wgmma_n64_ss<0, 0, DH128, DH128>(uim, dring, slot * 16384 + 8192 + kk * 32, dxa, kk * 32, (kb | kk) != 0);
      }
      wg_commit();
      if (kb > 0) { wg_wait<1>(); release((kb - 1) % NSLOT); }
      if (SB0 >= 0) {
        if (kb == SB0) { sh16 = late16(sb + OFF_XFULL); mhi = 0xffffffffu << sh16; bias(0); }
        if (kb == 4) bias(1);
        if (kb == 6) bias(2);
      }
      if (kb == 3) {
        mbar_wait(sb + OFF_LBAR, 0);
#pragma unroll
        for (int h = 0; h < 2; h++) {
          const uint4 v = lds_u4(sb + OFF_LC + (w * 16 + gr + 8 * h) * 16);
          lam[h] = cplx{__uint_as_float(v.x), __uint_as_float(v.y)};
          coef[h] = cplx{__uint_as_float(v.z), __uint_as_float(v.w)};
        }
      }
      if (kb == 5) {
#pragma unroll
        for (int h = 0; h < 2; h++) {
          pin(lam[h].re); pin(lam[h].im);
          cplx t = cmul(lam[h], lam[h]); t = cmul(t, t); t = cmul(t, t);
          l16[h] = cmul(t, t);
          pin(l16[h].re); pin(l16[h].im);
        }
      }
      if (kb == 7) {
#pragma unroll
        for (int h = 0; h < 2; h++) {
          pin(l16[h].re); pin(l16[h].im);
          l32[h] = cmul(l16[h], l16[h]);
          const cplx a = (q & 1) ? l16[h] : cplx{1.f, 0.f}, c = (q & 2) ? l32[h] : cplx{1.f, 0.f};
          lq[h] = cmul(cmul(a, c), coef[h]);
          pin(lq[h].re); pin(lq[h].im);
        }
      }
    }
    TS(wg, 2);
    auto scale_u = [&](int i0, int i1) {
#pragma unroll
      for (int i = 0; i < 32; i++) if (i >= i0 && i < i1) {
        pin(ure[i]); pin(uim[i]);
        const cplx v = cmul(coef[(i >> 1) & 1], cplx{ure[i], uim[i]});
        ure[i] = v.re; uim[i] = v.im;
        pin(ure[i]); pin(uim[i]);
      }
    };
#pragma unroll
    for (int kb = 0; kb < 8; kb++) {
      const int u = 8 + kb, slot = u % NSLOT;
      mbar_wait(fullb + 8 * slot, (u / NSLOT) & 1);
      wg_fence();
      const uint32_t dxa = dxw + ((kb + xrot) & 7) * 1024;
#pragma unroll
      for (int kk = 0; kk < 4; kk++)
        wgmma_n96_ss<0, 1, DH128, DH64>(aa, dxa, kk * 32, dring, slot * 16384 + kk * 1024 + lbo(4096), 1);
      wg_commit();
      if (SB0 >= 0 && kb == 0) bias(3);
      wg_wait<1>();
      release((u - 1) % NSLOT);
      if (kb == 0) {
        reg_fence(ure); reg_fence(uim);
#pragma unroll
        for (int h = 0; h < 2; h++) e[h] = cplx{ure[2 * h], uim[2 * h]};
      }
      if (kb == 0 || kb == 2 || kb == 3) {
        const int ch = kb ? kb - 1 : 0;
#pragma unroll
        for (int t = 1 + 5 * ch; t < 6 + 5 * ch; t++)
#pragma unroll
          for (int h = 0; h < 2; h++) { const int i = 4 * (t >> 1) + 2 * h + (t & 1); e[h] = cfma(lam[h], e[h], cplx{ure[i], uim[i]}); }
#pragma unroll
        for (int h = 0; h < 2; h++) { pin(e[h].re); pin(e[h].im); }
      } else if (kb == 4) {
#pragma unroll
        for (int h = 0; h < 2; h++) {
          cplx y = {__shfl_up_sync(0xffffffffu, e[h].re, 1, 4), __shfl_up_sync(0xffffffffu, e[h].im, 1, 4)};
          if (q >= 1) e[h] = cfma(l16[h], y, e[h]);
          y = cplx{__shfl_up_sync(0xffffffffu, e[h].re, 2, 4), __shfl_up_sync(0xffffffffu, e[h].im, 2, 4)};
          if (q >= 2) e[h] = cfma(l32[h], y, e[h]);
        }
        if (q == 3) {
#pragma unroll
          for (int h = 0; h < 2; h++)
            asm volatile("st.shared.v2.f32 [%0], {%1,%2};" ::"r"(sb + OFF_CARRY + wg * 512 + (w * 16 + gr + 8 * h) * 8), "f"(e[h].re), "f"(e[h].im) : "memory");
          mbar_arrive(sb + OFF_GBAR);
        }
#pragma unroll
        for (int h = 0; h < 2; h++) {
          const cplx y = {__shfl_up_sync(0xffffffffu, e[h].re, 1, 4), __shfl_up_sync(0xffffffffu, e[h].im, 1, 4)};
          pre[h] = (q >= 1) ? cmul(coef[h], y) : cplx{0.f, 0.f};
          pin(pre[h].re); pin(pre[h].im);
        }
        TS(wg, 3);
      } else if (kb > 4) {
        scale_u(kb == 5 ? 0 : kb == 6 ? 4 : 12, kb == 5 ? 4 : kb == 6 ? 12 : 20);
      }
    }
    TS(wg, 4);
    uint32_t H[56], hf[32];
    cplx hst[2];
    const uint32_t hst_addr = xw + (w * 16 + (lane & 15)) * 128 + (((lane >> 4) ^ (lane & 7)) << 4);
    const uint32_t him = (2 - rank) * 16384;
    uint32_t peer;
    asm volatile("mapa.shared::cluster.u32 %0, %1, %2;" : "=r"(peer) : "r"(sb), "r"(rank ^ 1));
    auto credit = [&]() { if (lane == 0) mbar_arrive_cl(peer + OFF_KBAR + wg * 8); };
#pragma unroll
    for (int kb = 0; kb < 8; kb++) {
      const int u = 16 + kb, slot = u % NSLOT;
      mbar_wait(fullb + 8 * slot, (u / NSLOT) & 1);
      wg_fence();
#pragma unroll
      for (int kk = 0; kk < 4; kk++)
        wgmma_n128_ss<0, 1, DH128, DH128>(ab, dxw, kb * 16384 + kk * 32, dring, slot * 16384 + kk * 2048 + lbo(8192), 1);
      wg_commit();
      wg_wait<1>();
      release((u - 1) % NSLOT);
      if (kb == 0) scale_u(20, 32);
      if (kb < 5 && kb != 1) {
        const int ch = kb ? kb - 1 : 0;
#pragma unroll
        for (int i = ch * 6; i < ch * 6 + 6; i++) {
          pin(aa[2 * i]); pin(aa[2 * i + 1]);
          H[i] = gelu2_pair(aa[2 * i], aa[2 * i + 1]);
          pin(H[i]);
        }
      }
      if (kb >= 4) {
        if (kb == 4) {
          TS(wg, 5);
          mbar_wait(sb + OFF_CBAR, 0);
          TS(wg, 6);
#pragma unroll
          for (int h = 0; h < 2; h++) {
            const float2 c = lds_f2(sb + OFF_CARRY + wg * 512 + (w * 16 + gr + 8 * h) * 8);
            hst[h] = cfma(lq[h], cplx{c.x, c.y}, pre[h]);
          }
        }
        const int j0 = (kb - 4) * 2;
        uint32_t rr[4], ri[4];
#pragma unroll
        for (int jj = 0; jj < 2; jj++) {
          const int j = j0 + jj;
          const uint32_t g2 = lds_u(sb + OFF_GS + (wg * 64 + j * 8 + q * 2) * 2);
#pragma unroll
          for (int h = 0; h < 2; h++) {
            const int i = 4 * j + 2 * h;
            const cplx h0 = cfma(lam[h], hst[h], cplx{ure[i], uim[i]});
            hst[h] = cfma(lam[h], h0, cplx{ure[i + 1], uim[i + 1]});
            rr[jj * 2 + h] = bf2_mul(pack_bf16(h0.re, hst[h].re), g2);
            ri[jj * 2 + h] = bf2_mul(pack_bf16(h0.im, hst[h].im), g2 ^ 0x80008000u);
          }
        }
        const uint32_t a = hst_addr ^ (j0 << 4);
        asm volatile("stmatrix.sync.aligned.m8n8.x4.shared.b16 [%0], {%1,%2,%3,%4};" ::"r"(a), "r"(rr[0]), "r"(rr[1]), "r"(rr[2]), "r"(rr[3]) : "memory");
        asm volatile("stmatrix.sync.aligned.m8n8.x4.shared.b16 [%0], {%1,%2,%3,%4};" ::"r"(a + him), "r"(ri[0]), "r"(ri[1]), "r"(ri[2]), "r"(ri[3]) : "memory");
      }
    }
    TS(wg, 7);

    uint4* const psend = g_part + (size_t)(m * 8 + rank) * 3072 + warp * 128 + lane;
    const uint4* const precv = g_part + (size_t)(m * 8 + s) * 3072 + warp * 128 + lane;
    const uint32_t pbuf = OFF_X + warp * 2048 + lane * 16;
    const uint32_t dx0 = ((sb + OFF_X) & 0x3FFFF) >> 4;
    float o[32], fin[32], rho[2];
    uint32_t tr[8];
    uint32_t r0[16], pt[16], sum[16], tag;
    auto recv_issue = [&](uint32_t (&r)[16], int k) {
#pragma unroll
      for (int i = 0; i < 4; i++) ld_b128(precv + k * 1024 + i * 32, r[4 * i], r[4 * i + 1], r[4 * i + 2], r[4 * i + 3]);
    };
    auto stale = [&](uint32_t (&r)[16]) {
      uint32_t t0, t1, r_;
      asm("lop3.b32 %0, %1, %2, %3, 0x7e;" : "=r"(t0) : "r"(r[0]), "r"(r[4]), "r"(tag));
      asm("lop3.b32 %0, %1, %2, %3, 0x7e;" : "=r"(t1) : "r"(r[8]), "r"(r[12]), "r"(tag));
      asm volatile("{.reg .pred p; .reg .b32 t; lop3.b32 t, %1, %2, 1, 0xa8; setp.ne.u32 p, t, 0; vote.sync.any.pred p, p, 0xffffffff; selp.u32 %0, 1, 0, p;}" : "=r"(r_) : "r"(t0), "r"(t1));
      return r_ != 0;
    };
    auto recv_check = [&](uint32_t (&r)[16], int k) {
      if (__builtin_expect(stale(r), 0)) {
        int tries = 0;
#pragma unroll 1
        do { recv_issue(r, k); } while (stale(r) && ++tries < 200000);
      }
    };
    auto gelu_b = [&](int i0, int i1) {
#pragma unroll
      for (int i = i0; i < i1; i++) {
        pin(ab[2 * i]); pin(ab[2 * i + 1]);
        H[24 + i] = gelu2_pair(ab[2 * i], ab[2 * i + 1]);
        pin(H[24 + i]);
      }
    };
    auto step = [&](float (&d)[32], int p, int k, int acc) {
      const uint32_t wo = stage_off(p);
      if (k >= 6 && k < 14) {
        const int kk = k - 6;
        wgmma_n64_rs<0, DH128>(d, hf[4 * kk], hf[4 * kk + 1], hf[4 * kk + 2], hf[4 * kk + 3], dx0, wo + 14336 + (kk >> 2) * 8192 + (kk & 3) * 32, 1);
      } else {
        const int kk = k < 6 ? k : k - 8;
        wgmma_n64_rs<1, DH128>(d, H[4 * kk], H[4 * kk + 1], H[4 * kk + 2], H[4 * kk + 3], dx0, wo + (kk / 7) * 30720 + (kk % 7) * 2048, k != 0 || acc);
      }
    };
    auto mma = [&](float (&d)[32], int p, int k0, int k1, int acc) {
      wg_fence();
#pragma unroll
      for (int k = k0; k < k1; k++) step(d, p, k, acc);
      wg_commit();
    };
    auto send_peer = [&]() {
#pragma unroll
      for (int i = 0; i < 4; i++)
        asm volatile("st.async.shared::cluster.mbarrier::complete_tx::bytes.v4.b32 [%0], {%1,%2,%3,%4}, [%5];" ::"r"(peer + pbuf + i * 512),
                     "r"(pack_bf16(o[8 * i], o[8 * i + 1])), "r"(pack_bf16(o[8 * i + 2], o[8 * i + 3])), "r"(pack_bf16(o[8 * i + 4], o[8 * i + 5])),
                     "r"(pack_bf16(o[8 * i + 6], o[8 * i + 7])), "r"(peer + OFF_RBAR + wg * 8) : "memory");
    };
    auto recv_peer = [&](int k) {
      mbar_wait(sb + OFF_RBAR + wg * 8, k & 1);
#pragma unroll
      for (int i = 0; i < 4; i++) { const uint4 v = lds_u4(sb + pbuf + i * 512); pt[4 * i] = v.x; pt[4 * i + 1] = v.y; pt[4 * i + 2] = v.z; pt[4 * i + 3] = v.w; }
    };
    auto send_owner = [&](float (&d)[32], int k) {
#pragma unroll
      for (int i = 0; i < 4; i++) {
#pragma unroll
        for (int c = 4 * i; c < 4 * i + 4; c++) pt[c] = bf2_add(pt[c], pack_bf16(d[2 * c], d[2 * c + 1]));
        asm("lop3.b32 %0, %0, 1, %1, 0xb8;" : "+r"(pt[4 * i]) : "r"(tag));
        st_b128(psend + (((sp + 1 + k) & 3) * 6 + k) * 1024 + i * 32, pt[4 * i], pt[4 * i + 1], pt[4 * i + 2], pt[4 * i + 3]);
      }
      __syncwarp();
      credit();
    };
    auto load_fin = [&]() {
      mbar_wait(sb + OFF_LBAR, 1);
#pragma unroll
      for (int j = 0; j < 8; j++) {
        const uint4 v = lds_u4(sb + pbuf + 16384 + (j >> 2) * 16384 + (j & 3) * 512);
        fin[4 * j] = __uint_as_float(v.x); fin[4 * j + 1] = __uint_as_float(v.y); fin[4 * j + 2] = __uint_as_float(v.z); fin[4 * j + 3] = __uint_as_float(v.w);
      }
    };
    auto ldk = [&](int pos) { if (pos == K0P) recv_issue(sum, 0); if (pos == K1P) recv_issue(r0, 1); };
    auto arm = [&]() { if ((threadIdx.x & 127) == 0) mbar_expect_tx(sb + OFF_RBAR + wg * 8, 8192); };
#pragma unroll
    for (int p = 0; p < 8; p++) {
      if (p == 0) {
        mbar_wait(fullb, 0);
        mma(o, 0, 0, 3, 0);
        wg_wait<1>(); release(5);
        gelu_b(0, 4);
        mma(o, 0, 3, 6, 0);
        bar_sync(1 + wg, 128);
        {
          const uint32_t ha = xw + ((lane >> 4) * 8 + (lane & 7)) * 128 + (((2 * w + ((lane >> 3) & 1)) ^ (lane & 7)) << 4);
#pragma unroll
          for (int kk = 0; kk < 8; kk++)
            asm volatile("ldmatrix.sync.aligned.m8n8.x4.trans.shared.b16 {%0,%1,%2,%3}, [%4];" : "=r"(hf[4 * kk]), "=r"(hf[4 * kk + 1]), "=r"(hf[4 * kk + 2]), "=r"(hf[4 * kk + 3])
                         : "r"(ha + (kk >> 2) * him + (kk & 3) * 2048) : "memory");
        }
        gelu_b(4, 10);
        mbar_wait(fullb + 8, 0);
        mma(o, 0, 6, 10, 0);
        credit();
        gelu_b(10, 16);
        mma(o, 0, 10, 15, 0);
        gelu_b(16, 24);
        mbar_wait(fullb + 16, 0);
        mma(o, 0, 15, 18, 0);
        gelu_b(24, 32);
        if (wg == 1) bar_sync(4, 256);
        mma(o, 0, 18, 22, 0);
      } else {
        TR(0);
        if (EW == 0 || (EW == 1 && (p & 1))) mbar_wait(sb + OFF_XFULL + 8 * p, 1);
        TR(1);
        bar_sync(3 + wg, 256);
        if (p < 7) mma(o, p, 0, 22, 0);
        else if (GAP == 0) mma(fin, p, 0, 22, 1);
        else {
          mma(fin, p, 0, GAP, 1);
          recv_peer(3);
          tag = lds_u(sb + OFF_EPOCH);
          mma(fin, p, GAP, 22, 1);
        }
      }
      if (p < 7 || wg == 0) bar_arrive(4 - wg, 256);
      TR(2);
      if (p != TP) TS(wg, 8 + p);
      if (p < 7 && (EW == 2 || (EW == 1 && (p & 1)))) mbar_wait(sb + OFF_XFULL + 8 * (p + 1), 1);
      ldk(10 * p);
      if ((p & 1) == 0) {
        arm();
        if (p == 6) {
          mbar_wait(sb + OFF_EMPTY + 32, 0);
          tag = lds_u(sb + OFF_EPOCH);
          recv_check(sum, 0); recv_check(r0, 1);
#pragma unroll
          for (int i = 0; i < 16; i++) sum[i] = bf2_add(sum[i], r0[i]);
        }
        TR(3);
        mbar_wait(sb + OFF_KBAR + wg * 8, (p >> 1) & 1);
        TR(4);
      } else {
        if (p == 1 || (p == 7 && GAP == 0)) tag = lds_u(sb + OFF_EPOCH);
        TR(3);
        if (p < 7 || GAP == 0) recv_peer(p >> 1);
        TR(4);
        if (p == 7) {
          recv_check(r0, 2);
#pragma unroll
          for (int i = 0; i < 16; i++) sum[i] = bf2_add(sum[i], bf2_add(r0[i], pt[i]));
        }
      }
      if (p == FINP && !FINW) load_fin();
      ldk(10 * p + 1);
      TR(5);
      wg_wait<0>();
      TR(6);
      if (p < 5) release(p);
      if (p < 7) reg_fence(o); else reg_fence(fin);
      ldk(10 * p + 2);
      if ((p & 1) == 0) {
        if (p == 6) recv_issue(r0, 2);
        send_peer();
        if (p == FINP && FINW) load_fin();
      } else if (p < 7) {
        send_owner(o, p >> 1);
      }
      ldk(10 * p + 3);
      if (p == 2) {
#pragma unroll
        for (int h = 0; h < 2; h++) { rho[h] = __fdividef(2.f, 4.f + bf_lo(lds_h(sb + OFF_GS + (wg * 64 + w * 16 + gr + 8 * h) * 2))); pin(rho[h]); }
      }
      TR(7);
    }
    {
      TS(wg, 16);
      const uint32_t tb = sb + OFF_X + stage_off(0) + warp * 4096;
      const uint32_t ta = tb + gr * 256 + ((gr & 3) << 5) + q * 8;
      const uint32_t la = tb + (lane >> 3) * 256 + (((lane & 7) << 4) ^ ((lane >> 3) << 5));
      float* op = out + (size_t)(m * 128 + wg * 64 + (lane >> 4) * 16 + w * 4 + ((lane >> 3) & 1)) * DM + s * 64 + (lane & 7) * 4;
#pragma unroll
      for (int qq = 0; qq < 4; qq += QS) {
#pragma unroll
        for (int qt = qq; qt < qq + QS; qt++) {
          const int h = qt & 1, ch = qt >> 1;
#pragma unroll
          for (int j = 0; j < 4; j++) {
            const int i = ch * 8 + j * 2 + h;
            asm volatile("st.shared.v2.f32 [%0], {%1,%2};" ::"r"((ta ^ (j << 5)) + h * 2048 + ch * 128),
                         "f"((fin[2 * i] + bf_lo(sum[i])) * rho[h]), "f"((fin[2 * i + 1] + bf_hi(sum[i])) * rho[h]) : "memory");
          }
        }
        __syncwarp();
#pragma unroll
        for (int qt = qq; qt < qq + QS; qt++) {
          const int h = qt & 1, ch = qt >> 1;
#pragma unroll
          for (int r = 0; r < 2; r++)
            *reinterpret_cast<uint4*>(op + (r * 32 + h * 2) * DM + ch * 32) = lds_u4(la + (h * 2 + r) * 1024 + ch * 128);
        }
      }
      if (threadIdx.x == 128) g_epoch[b] = tag;
      TS(wg, 17); TG(wg); TRD(); TDUMP();
    }
  } else {
    asm volatile("setmaxnreg.dec.sync.aligned.u32 56;");
    int wsel = warp;
    asm("" : "+r"(wsel));
    if (wsel > 8) {
      if (warp != 11) {
        const int t = threadIdx.x - 288;
        unsigned par;
        asm volatile("ld.relaxed.gpu.global.u32 %0, [%1];" : "=r"(par) : "l"(g_epoch + b) : "memory");
        const float pr = bf_ld(lam_re + s * 64 + t), pi = bf_ld(lam_im + s * 64 + t), pd = bf_ld(log_dt + s * 64 + t);
        asm volatile("barrier.cluster.wait.aligned;" ::: "memory");
        par = __shfl_sync(0xffffffffu, (par + 1) & 1, 0);
        cplx l64 = make_lam(pr, pi, pd);
        {
          const float inv = __fdividef(1.f, fmaf(pr, pr, pi * pi));
          const cplx cf = cmul(cplx{l64.re - 1.f, l64.im}, cplx{pr * inv, -pi * inv});
          asm volatile("st.shared.v4.f32 [%0], {%1,%2,%3,%4};" ::"r"(sb + OFF_LC + t * 16), "f"(l64.re), "f"(l64.im), "f"(cf.re), "f"(cf.im) : "memory");
          mbar_arrive(sb + OFF_LBAR);
        }
#pragma unroll
        for (int i = 0; i < 6; i++) l64 = cmul(l64, l64);
        cplx l128 = cmul(l64, l64);
        pin(l128.re); pin(l128.im);
        uint32_t vr[15], vi[15];
#pragma unroll
        for (int i = 0; i < 15; i++) { vr[i] = par; vi[i] = 0; pin(vr[i]); pin(vi[i]); }
        mbar_wait(sb + OFF_GBAR, 0);
        const float2 e0 = lds_f2(sb + OFF_CARRY + t * 8), e1 = lds_f2(sb + OFF_CARRY + 512 + t * 8);
        float2* eb = g_end + s * 1024 + t;
        {
          const cplx e = cfma(l64, cplx{e0.x, e0.y}, cplx{e1.x, e1.y});
          const unsigned long long v = ((unsigned long long)__float_as_uint(e.im) << 32) | ((__float_as_uint(e.re) & ~1u) | par);
          asm volatile("st.relaxed.gpu.global.b64 [%0], %1;" ::"l"(eb + m * 64), "l"(v) : "memory");
        }
        if (t == 0) TS(3, 1);
        cplx S = {0.f, 0.f};
        {
          if (LBD) __nanosleep(LBD);
          const float2* e15 = eb + (m - 15) * 64;
          int tries = 0;
          bool bad;
#pragma unroll 1
          do {
#pragma unroll
            for (int i = 0; i < 15; i++)
              asm volatile("{.reg .pred p; .reg .b64 v; mov.b64 v, {%0,%1}; setp.ge.s32 p, %3, %4; @p ld.relaxed.gpu.global.b64 v, [%2]; mov.b64 {%0,%1}, v;}"
                           : "+r"(vr[i]), "+r"(vi[i]) : "l"(e15 + i * 64), "r"(m), "r"(15 - i) : "memory");
            uint32_t x = vr[0] ^ par;
#pragma unroll
            for (int i = 1; i < 15; i++) asm("lop3.b32 %0, %0, %1, %2, 0xf6;" : "+r"(x) : "r"(vr[i]), "r"(par));
            bad = __any_sync(0xffffffffu, x & 1);
          } while (bad && ++tries < 200000);
          if (t == 0) TS(3, 2);
          S = cplx{__uint_as_float(vr[0]), __uint_as_float(vi[0])};
#pragma unroll
          for (int i = 1; i < 15; i++) S = cfma(l128, S, cplx{__uint_as_float(vr[i]), __uint_as_float(vi[i])});
        }
        const cplx S1 = cfma(l64, S, cplx{e0.x, e0.y});
        asm volatile("st.shared.v2.f32 [%0], {%1,%2};" ::"r"(sb + OFF_CARRY + t * 8), "f"(S.re), "f"(S.im) : "memory");
        asm volatile("st.shared.v2.f32 [%0], {%1,%2};" ::"r"(sb + OFF_CARRY + 512 + t * 8), "f"(S1.re), "f"(S1.im) : "memory");
        mbar_arrive(sb + OFF_CBAR);
        if (t == 0) TS(3, 3);
        mbar_wait(sb + OFF_CBAR, 0);
        const int gr = lane >> 2, q = lane & 3;
        float2 db[8];
#pragma unroll
        for (int j = 0; j < 8; j++) db[j] = lds_f2(sb + OFF_DB + j * 32 + q * 8);
        mbar_wait(sb + OFF_XFULL + 16, 1);
        mbar_wait(sb + OFF_EMPTY, 0);
#pragma unroll 1
        for (int cw = warp - 9; cw < 8; cw += 2) {
          const float r0 = 0.5f * bf_lo(lds_h(sb + OFF_GS + (cw * 16 + gr) * 2)), r1 = 0.5f * bf_lo(lds_h(sb + OFF_GS + (cw * 16 + gr) * 2 + 16));
          const uint32_t xa = sb + OFF_X + (1 + rank) * 16384 + (cw * 16 + (lane & 15)) * 128 + (((lane >> 4) ^ (lane & 7)) << 4);
          uint32_t xv[16];
#pragma unroll
          for (int i = 0; i < 4; i++)
            asm volatile("ldmatrix.sync.aligned.m8n8.x4.shared.b16 {%0,%1,%2,%3}, [%4];" : "=r"(xv[4 * i]), "=r"(xv[4 * i + 1]), "=r"(xv[4 * i + 2]), "=r"(xv[4 * i + 3])
                         : "r"(xa ^ (i << 5)) : "memory");
          __syncwarp();
#pragma unroll
          for (int j = 0; j < 8; j++) {
            const uint32_t x0 = bf2_mul(xv[2 * j], __float_as_uint(db[j].x)), x1 = bf2_mul(xv[2 * j + 1], __float_as_uint(db[j].x));
            pin(db[j].y);
            const float bl = bf_lo(__float_as_uint(db[j].y)), bh = bf_hi(__float_as_uint(db[j].y));
            asm volatile("st.shared.v4.f32 [%0], {%1,%2,%3,%4};" ::"r"(sb + OFF_X + 16384 + (j >> 2) * 16384 + cw * 2048 + (j & 3) * 512 + lane * 16), "f"(fmaf(bf_lo(x0), r0, bl)),
                         "f"(fmaf(bf_hi(x0), r0, bh)), "f"(fmaf(bf_lo(x1), r1, bl)), "f"(fmaf(bf_hi(x1), r1, bh)) : "memory");
          }
        }
        mbar_arrive(sb + OFF_LBAR);
        if (t == 0) TS(3, 5);
      } else {
        if (lane == 0) TG(2);
        const uint4* gwp = reinterpret_cast<const uint4*>(gate_w) + (lane & 7);
        uint4 gw[4];
#pragma unroll
        for (int i = 0; i < 4; i++) gw[i] = __ldg(gwp + i * 8);
        unsigned par;
        asm volatile("ld.relaxed.gpu.global.u32 %0, [%1];" : "=r"(par) : "l"(g_epoch + b) : "memory");
        const uint32_t dk = __ldg(reinterpret_cast<const uint32_t*>(dskip + s * 64) + lane), bb = __ldg(reinterpret_cast<const uint32_t*>(b2 + s * 64) + lane);
        asm volatile("barrier.cluster.wait.aligned;" ::: "memory");
        const int row = s * 16 + (lane >> 3);
        const uint32_t xr0 = sb + OFF_X + row * 128 + (((lane & 7) ^ (row & 7)) << 4), xr1 = (xr0 + 512) ^ 64;
        float z[4] = {0.f, 0.f, 0.f, 0.f};
#pragma unroll
        for (int kb = 0; kb < 8; kb++) {
          const uint32_t wv[4] = {gw[kb & 3].x, gw[kb & 3].y, gw[kb & 3].z, gw[kb & 3].w};
          if (kb < 4) gw[kb] = __ldg(gwp + (kb + 4) * 8);
          mbar_wait(sb + OFF_XFULL + 8 * kb, 0);
          if ((PF & 2) && kb == PFK && elect_one()) {
            l2_prefetch(pf_w1 + b * 7168, 14336);
            l2_prefetch(pf_cre + b * 2048, 4096);
            l2_prefetch(pf_cim + b * 2048, 4096);
            l2_prefetch(pf_w2 + b * 7168, 14336);
          }
          const uint32_t xo = ((kb + xrot) & 7) * 16384;
#pragma unroll
          for (int r = 0; r < 4; r++) {
            const uint4 a = lds_u4(((r & 1) ? xr1 : xr0) + xo + (r >> 1) * 1024);
            const uint32_t p = bf2_fma(a.w, wv[3], bf2_fma(a.z, wv[2], bf2_fma(a.y, wv[1], bf2_mul(a.x, wv[0]))));
            z[r] += bf_lo(p); z[r] += bf_hi(p);
          }
        }
        if (lane == 0) asm volatile("st.shared.u32 [%0], %1;" ::"r"(sb + OFF_EPOCH), "r"(par + 1) : "memory");
        par = (par + 1) & 1;
        {
          float y0 = (lane & 4) ? z[1] : z[0], y1 = (lane & 4) ? z[3] : z[2];
          y0 += __shfl_xor_sync(0xffffffffu, (lane & 4) ? z[0] : z[1], 4);
          y1 += __shfl_xor_sync(0xffffffffu, (lane & 4) ? z[2] : z[3], 4);
          float zz = (lane & 2) ? y1 : y0;
          zz += __shfl_xor_sync(0xffffffffu, (lane & 2) ? y0 : y1, 2);
          zz += __shfl_xor_sync(0xffffffffu, zz, 1);
          const float rho = 4.f * expf(zz > 40.f ? 40.f : zz);
          if ((lane & 1) == 0)
            asm volatile("st.relaxed.gpu.global.u32 [%0], %1;" ::"l"(g_gate + m * 128 + row + (lane & 4) + (lane & 2) * 4), "r"((__float_as_uint(rho) & ~1u) | par) : "memory");
        }
        if ((PF & 8) && elect_one()) {
          l2_prefetch(pf_w2 + b * 7168, 14336);
          l2_prefetch(pf_cre + b * 2048, 4096);
          l2_prefetch(pf_cim + b * 2048, 4096);
        }
        if (lane == 0) TS(3, 0);
        mbar_wait(sb + OFF_GBAR, 0);
        asm volatile("st.shared.v2.u32 [%0], {%1,%2};" ::"r"(sb + OFF_DB + lane * 8), "r"(dk), "r"(bf2_add(bb, bb)) : "memory");
        uint32_t g0, g1, g2, g3;
        int tries = 0;
#pragma unroll 1
        do {
          asm volatile("ld.relaxed.gpu.global.v4.u32 {%0,%1,%2,%3}, [%4];" : "=r"(g0), "=r"(g1), "=r"(g2), "=r"(g3) : "l"(g_gate + m * 128 + lane * 4) : "memory");
        } while ((((g0 ^ par) | (g1 ^ par) | (g2 ^ par) | (g3 ^ par)) & 1) && ++tries < 200000);
        asm volatile("st.shared.v2.u32 [%0], {%1,%2};" ::"r"(sb + OFF_GS + lane * 8), "r"(pack_bf16(__uint_as_float(g0), __uint_as_float(g1))),
                     "r"(pack_bf16(__uint_as_float(g2), __uint_as_float(g3))) : "memory");
        mbar_arrive(sb + OFF_CBAR);
        if (lane == 0) TS(3, 4);
      }
    } else {
      asm volatile("barrier.cluster.wait.aligned;" ::: "memory");
      if (elect_one()) {
        TS(2, 1);
        const uint32_t t0 = clock();
#pragma unroll 1
        for (int u = 0; u < 8; u++) {
          if (u >= 1) while ((uint32_t)clock() - t0 < D0 + (u - 1) * D1) {}
          mbar_expect_tx(sb + OFF_XFULL + 8 * u, 16384);
          tma5d_mc(sb + OFF_X + ((u + xrot) & 7) * 16384 + rank * 8192, &maps.x, u * 64, 2 * m + rank, sb + OFF_XFULL + 8 * u);
          if (u < 6) {
            mbar_expect_tx(sb + OFF_FULL + 8 * u, 16384);
            tma2d(sb + OFF_RING + u * 16384, &maps.bre, u * 64, s * 64, sb + OFF_FULL + 8 * u);
            tma2d(sb + OFF_RING + u * 16384 + 8192, &maps.bim, u * 64, s * 64, sb + OFF_FULL + 8 * u);
          } else if (PF & 4) {
            asm volatile("cp.async.bulk.prefetch.tensor.2d.L2.global [%0, {%1,%2}];" ::"l"((m & 1) ? &maps.bim : &maps.bre), "r"(u * 64), "r"(s * 64) : "memory");
          }
        }
        TS(2, 5);
        int slot = 0; uint32_t ph = 0;
#pragma unroll 1
        for (int u = 6; u < 24; u++) {
          const uint32_t fb = sb + OFF_FULL + 8 * slot, dst = sb + OFF_RING + slot * 16384;
          mbar_wait(sb + OFF_EMPTY + 8 * slot, ph);
          TS2(0, u);
          if (u < 8) {
            mbar_expect_tx(fb, 16384);
            tma2d(dst, &maps.bre, u * 64, s * 64, fb);
            tma2d(dst + 8192, &maps.bim, u * 64, s * 64, fb);
          } else if (u < 16) {
            mbar_expect_tx(fb, 12288);
            tma3d(dst, &maps.w1b, 0, (u - 8) * 64, s * 7, fb);
          } else {
            mbar_expect_tx(fb, 16384);
            tma2d(dst, &maps.w1a, s * 224 + 96, ((u - xrot) & 7) * 64, fb);
            tma2d(dst + 8192, &maps.w1a, s * 224 + 160, ((u - xrot) & 7) * 64, fb);
          }
          if (++slot == NSLOT) { slot = 0; ph ^= 1; }
        }
#pragma unroll 1
        for (int j = 0; j < 3; j++) {
          const uint32_t fb = sb + OFF_FULL + 8 * j, dst = sb + OFF_X + stage_off(0);
          const int c = ((sp + 1) & 3) * 128 + ((rank ^ 1) << 6);
          mbar_wait(sb + OFF_EMPTY + 8 + 8 * j, 1);
          mbar_expect_tx(fb, j == 1 ? 16384 : 14336);
          if (j == 1) {
            tma2d(dst + 14336, &maps.cre, s * 64, c, fb);
            tma2d(dst + 22528, &maps.cim, s * 64, c, fb);
          } else {
            tma2d(dst + j * 15360, &maps.w2, c, s * 224 + j * 56, fb);
          }
        }
#pragma unroll 1
        for (int p = 1; p < 8; p++) {
          const int c = ((sp + 1 + (p >> 1)) & 3) * 128 + (((rank ^ p ^ 1) & 1) << 6);
          const uint32_t fb = sb + OFF_XFULL + 8 * p, dst = sb + OFF_X + stage_off(p);
          if (p == 2 || p > 3) mbar_wait(sb + OFF_EMPTY + (p == 2 ? 40 : (p - 4) * 8), p == 2);
          TS2(0, 32 + p);
          mbar_expect_tx(fb, 45056);
          tma2d(dst, &maps.w2, c, s * 224, fb);
          tma2d(dst + 14336, &maps.cre, s * 64, c, fb);
          tma2d(dst + 22528, &maps.cim, s * 64, c, fb);
          tma2d(dst + 30720, &maps.w2, c, s * 224 + 112, fb);
        }
        TS(2, 2);
      }
    }
  }
}

typedef CUresult (*EncFn)(CUtensorMap*, CUtensorMapDataType, cuuint32_t, void*, const cuuint64_t*, const cuuint64_t*, const cuuint32_t*,
                          const cuuint32_t*, CUtensorMapInterleave, CUtensorMapSwizzle, CUtensorMapL2promotion, CUtensorMapFloatOOBfill);

void encode(EncFn f, CUtensorMap* mp, const void* p, int rank, const cuuint64_t* dims, const cuuint64_t* strides, const cuuint32_t* box, CUtensorMapSwizzle sw) {
  cuuint32_t es[5] = {1, 1, 1, 1, 1};
  f(mp, CU_TENSOR_MAP_DATA_TYPE_BFLOAT16, rank, const_cast<void*>(p), dims, strides, box, es, CU_TENSOR_MAP_INTERLEAVE_NONE, sw,
    CU_TENSOR_MAP_L2_PROMOTION_L2_128B, CU_TENSOR_MAP_FLOAT_OOB_FILL_NONE);
}

}

extern "C" void kernel_launch(void* const* d_in, const int* in_sizes, int n_in, void* d_out, int out_size) {
  typedef const __nv_bfloat16* bp;
  bp x = (bp)d_in[0], lre = (bp)d_in[1], lim = (bp)d_in[2], bre = (bp)d_in[3], bim = (bp)d_in[4], cre = (bp)d_in[5], cim = (bp)d_in[6],
     ldt = (bp)d_in[7], dsk = (bp)d_in[8], w1 = (bp)d_in[10], b1 = (bp)d_in[11], w2 = (bp)d_in[12], b2 = (bp)d_in[13], gw = (bp)d_in[14];
  static EncFn enc = nullptr;
  if (!enc) {
    void* f = nullptr;
    cudaDriverEntryPointQueryResult qr;
    cudaGetDriverEntryPoint("cuTensorMapEncodeTiled", &f, cudaEnableDefault, &qr);
    enc = (EncFn)f;
    cudaFuncSetAttribute(fused_kernel, cudaFuncAttributeMaxDynamicSharedMemorySize, SMEM_BYTES);
  }
  Maps maps;
  {
    cuuint64_t d[5] = {DM, 2, 4, 8, SEQ / 64}, st[4] = {DM * 2, 16 * DM * 2, 2 * DM * 2, 64 * DM * 2};
    cuuint32_t bx[5] = {64, 2, 4, 8, 1};
    encode(enc, &maps.x, x, 5, d, st, bx, CU_TENSOR_MAP_SWIZZLE_128B);
  }
  {
    cuuint64_t d[2] = {DM, DM}, st[1] = {DM * 2};
    cuuint32_t bx[2] = {64, 64};
    encode(enc, &maps.bre, bre, 2, d, st, bx, CU_TENSOR_MAP_SWIZZLE_128B);
    encode(enc, &maps.bim, bim, 2, d, st, bx, CU_TENSOR_MAP_SWIZZLE_128B);
    encode(enc, &maps.cre, cre, 2, d, st, bx, CU_TENSOR_MAP_SWIZZLE_128B);
    encode(enc, &maps.cim, cim, 2, d, st, bx, CU_TENSOR_MAP_SWIZZLE_128B);
  }
  {
    cuuint64_t d[2] = {FF, DM}, st[1] = {FF * 2};
    cuuint32_t bx[2] = {64, 64};
    encode(enc, &maps.w1a, w1, 2, d, st, bx, CU_TENSOR_MAP_SWIZZLE_128B);
    cuuint64_t d3[3] = {32, DM, FF / 32}, st3[2] = {FF * 2, 64};
    cuuint32_t bx3[3] = {32, 64, 3};
    encode(enc, &maps.w1b, w1, 3, d3, st3, bx3, CU_TENSOR_MAP_SWIZZLE_64B);
  }
  {
    cuuint64_t d[2] = {DM, FF}, st[1] = {DM * 2};
    cuuint32_t bx[2] = {64, 112};
    encode(enc, &maps.w2, w2, 2, d, st, bx, CU_TENSOR_MAP_SWIZZLE_128B);
  }
  fused_kernel<<<128, 384, SMEM_BYTES>>>(lre, lim, ldt, dsk, b1, b2, gw, w1, w2, cre, cim, (float*)d_out, maps);
}
```

```cpp
#include <cuda_runtime.h>
#include <cuda_bf16.h>
#include <cuda.h>
#include <stdint.h>

#define MAP 1
#define D0 600
#define D1 500
#define PF 4
#define PFK 5
#define GELUP 1
#define EW 2
#define K1E 1
#define K2E 0
#define QS 1
#define K2G 4
#define FINP 4
#define LBD 300
#define PFS 32
#define SB0 2
#define PFD 2
#define HOLD 0
#define GAP 14
#define FINW 0
#define K0P 33
#define K1P 53
#define W0 1
#define TP 9
#define TW 0

namespace {

constexpr int SEQ = 2048, DM = 512, FF = 1792;
constexpr int NSLOT = 6;
constexpr uint32_t OFF_X = 0, OFF_RING = 131072, OFF_MISC = 229376;
constexpr uint32_t OFF_XFULL = OFF_MISC, OFF_FULL = OFF_XFULL + 64, OFF_RBAR = OFF_FULL + 48, OFF_EMPTY = OFF_RBAR + 16, OFF_KBAR = OFF_EMPTY + 48,
                   OFF_GBAR = OFF_KBAR + 16, OFF_LBAR = OFF_GBAR + 8, OFF_CBAR = OFF_LBAR + 8, OFF_EPOCH = OFF_CBAR + 8;
constexpr uint32_t OFF_LC = OFF_MISC + 256;
constexpr uint32_t OFF_GS = OFF_LC;
constexpr uint32_t OFF_DB = OFF_LC + 512;
constexpr uint32_t OFF_CARRY = OFF_LC + 1024;
constexpr uint32_t OFF_DBG = OFF_CARRY + 1024;
constexpr uint32_t SMEM_BYTES = OFF_DBG + 768;
static_assert(SMEM_BYTES <= 232448, "smem");

struct Maps { CUtensorMap x, bre, bim, w1b, w1a, w2, cre, cim; };
__host__ __device__ constexpr uint32_t stage_off(int p) { return 49152 + 45056 * (((p >> 1) & 1) + 2 * (p & 1)); }

__device__ uint4 g_part[16 * 8 * 3 * 1024];
__device__ float2 g_end[8 * 16 * 64];
__device__ unsigned g_gate[SEQ];
__device__ unsigned g_epoch[128];
#define TG(role) do {} while (0)
#define TS2(role, i) do {} while (0)
#define TS(role, i) do {} while (0)
#define TDUMP() do {} while (0)
#define TR(i) do {} while (0)
#define TRD() do {} while (0)

__device__ __forceinline__ void mbar_init(uint32_t bar, uint32_t cnt) { asm volatile("mbarrier.init.shared::cta.b64 [%0], %1;" ::"r"(bar), "r"(cnt)); }
__device__ __forceinline__ void mbar_expect_tx(uint32_t bar, uint32_t bytes) { asm volatile("mbarrier.arrive.expect_tx.shared::cta.b64 _, [%0], %1;" ::"r"(bar), "r"(bytes) : "memory"); }
__device__ __forceinline__ void mbar_arrive(uint32_t bar) { asm volatile("mbarrier.arrive.shared::cta.b64 _, [%0];" ::"r"(bar) : "memory"); }
__device__ __forceinline__ void mbar_arrive_cl(uint32_t cbar) { asm volatile("mbarrier.arrive.shared::cluster.b64 _, [%0];" ::"r"(cbar) : "memory"); }
__device__ __forceinline__ void mbar_wait(uint32_t bar, uint32_t parity) {
  asm volatile(
      "{\n.reg .pred p;\n.reg .u32 c;\n"
      "mbarrier.try_wait.parity.shared::cta.b64 p, [%0], %1;\n"
      "@p bra.uni LAB_DONE;\n"
      "mov.u32 c, 0;\n"
      "LAB_WAIT:\n"
      "mbarrier.try_wait.parity.shared::cta.b64 p, [%0], %1;\n"
      "@p bra.uni LAB_DONE;\n"
      "add.u32 c, c, 1;\nsetp.lt.u32 p, c, 200000;\n@p bra.uni LAB_WAIT;\n"
      "LAB_DONE:\n}" ::"r"(bar), "r"(parity) : "memory");
}
__device__ __forceinline__ void tma2d(uint32_t dst, const CUtensorMap* m, int c0, int c1, uint32_t bar) {
  asm volatile("cp.async.bulk.tensor.2d.shared::cluster.global.mbarrier::complete_tx::bytes [%0], [%1, {%3,%4}], [%2];"
               ::"r"(dst), "l"(m), "r"(bar), "r"(c0), "r"(c1) : "memory");
}
__device__ __forceinline__ void tma3d(uint32_t dst, const CUtensorMap* m, int c0, int c1, int c2, uint32_t bar) {
  asm volatile("cp.async.bulk.tensor.3d.shared::cluster.global.mbarrier::complete_tx::bytes [%0], [%1, {%3,%4,%5}], [%2];"
               ::"r"(dst), "l"(m), "r"(bar), "r"(c0), "r"(c1), "r"(c2) : "memory");
}
__device__ __forceinline__ void tma5d_mc(uint32_t dst, const CUtensorMap* m, int c0, int c4, uint32_t bar) {
  asm volatile("cp.async.bulk.tensor.5d.shared::cluster.global.mbarrier::complete_tx::bytes.multicast::cluster [%0], [%1, {%3,%5,%5,%5,%4}], [%2], %6;"
               ::"r"(dst), "l"(m), "r"(bar), "r"(c0), "r"(c4), "r"(0), "h"((uint16_t)3) : "memory");
}
__device__ __forceinline__ void l2_prefetch(const void* p, uint32_t bytes) { asm volatile("cp.async.bulk.prefetch.L2.global [%0], %1;" ::"l"(p), "r"(bytes) : "memory"); }
__device__ __forceinline__ bool elect_one() {
  uint32_t pred;
  asm volatile("{.reg .pred P; elect.sync _|P, 0xffffffff; selp.u32 %0, 1, 0, P;}" : "=r"(pred));
  return pred != 0;
}
__device__ __forceinline__ void wg_fence() { asm volatile("wgmma.fence.sync.aligned;" ::: "memory"); }
__device__ __forceinline__ void wg_commit() { asm volatile("wgmma.commit_group.sync.aligned;" ::: "memory"); }
template <int N> __device__ __forceinline__ void wg_wait() { asm volatile("wgmma.wait_group.sync.aligned %0;" ::"n"(N) : "memory"); }
__device__ __forceinline__ void pin(float& a) { asm volatile("" : "+f"(a)::"memory"); }
__device__ __forceinline__ void pin(uint32_t& a) { asm volatile("" : "+r"(a)::"memory"); }
template <int N> __device__ __forceinline__ void reg_fence(float (&d)[N]) {
#pragma unroll
  for (int i = 0; i < N; i++) pin(d[i]);
}
__device__ __forceinline__ void bar_sync(int id, int n) { asm volatile("bar.sync %0, %1;" ::"r"(id), "r"(n) : "memory"); }
__device__ __forceinline__ void bar_arrive(int id, int n) { asm volatile("bar.arrive %0, %1;" ::"r"(id), "r"(n) : "memory"); }
constexpr uint32_t DH128 = (1024 >> 4) | (1u << 30), DH64 = (512 >> 4) | (2u << 30);
__host__ __device__ constexpr uint32_t lbo(uint32_t bytes) { return (bytes >> 4) << 20; }
__device__ __forceinline__ uint32_t pack_bf16(float lo, float hi) { uint32_t r; asm("cvt.rn.bf16x2.f32 %0, %1, %2;" : "=r"(r) : "f"(hi), "f"(lo)); return r; }
__device__ __forceinline__ float bf_lo(uint32_t v) { return __uint_as_float(v << 16); }
__device__ __forceinline__ float bf_hi(uint32_t v) { return __uint_as_float(v & 0xffff0000u); }
__device__ __forceinline__ float bf_ld(const __nv_bfloat16* p) { return __bfloat162float(__ldg(p)); }
__device__ __forceinline__ uint32_t late16(uint32_t bar) {
  uint32_t r;
  asm volatile("{.reg .pred p; mbarrier.test_wait.parity.shared::cta.b64 p, [%1], 0; selp.u32 %0, 16, 0, p;}" : "=r"(r) : "r"(bar) : "memory");
  return r;
}
__device__ __forceinline__ float2 lds_f2(uint32_t a) { float2 v; asm volatile("ld.shared.v2.f32 {%0,%1}, [%2];" : "=f"(v.x), "=f"(v.y) : "r"(a)); return v; }
__device__ __forceinline__ uint32_t lds_h(uint32_t a) { uint32_t v; asm volatile("ld.shared.u16 %0, [%1];" : "=r"(v) : "r"(a)); return v; }
__device__ __forceinline__ uint32_t lds_u(uint32_t a) { uint32_t v; asm volatile("ld.shared.u32 %0, [%1];" : "=r"(v) : "r"(a)); return v; }
__device__ __forceinline__ uint4 lds_u4(uint32_t a) { uint4 v; asm volatile("ld.shared.v4.u32 {%0,%1,%2,%3}, [%4];" : "=r"(v.x), "=r"(v.y), "=r"(v.z), "=r"(v.w) : "r"(a)); return v; }
__device__ __forceinline__ void st_b128(uint4* p, uint32_t a, uint32_t b, uint32_t c, uint32_t d) {
  asm volatile("st.relaxed.gpu.global.v4.b32 [%0], {%1,%2,%3,%4};" ::"l"(p), "r"(a), "r"(b), "r"(c), "r"(d) : "memory");
}
__device__ __forceinline__ void ld_b128(const uint4* p, uint32_t& a, uint32_t& b, uint32_t& c, uint32_t& d) {
  asm volatile("{.reg .b64 l, h; .reg .b128 v; ld.relaxed.gpu.global.b128 v, [%4]; mov.b128 {l,h}, v; mov.b64 {%0,%1}, l; mov.b64 {%2,%3}, h;}"
               : "=r"(a), "=r"(b), "=r"(c), "=r"(d) : "l"(p) : "memory");
}
__device__ __forceinline__ float tanh_fast(float x) { float y; asm("tanh.approx.f32 %0, %1;" : "=f"(y) : "f"(x)); return y; }
__device__ __forceinline__ float gelu2(float v) {
  float p = fmaf(v * v, 0.0356774081363f, 0.7978845608029f);
  return fmaf(v, tanh_fast(v * p), v);
}
__device__ __forceinline__ uint32_t bf2_mul(uint32_t a, uint32_t b) { uint32_t r; asm("mul.rn.bf16x2 %0, %1, %2;" : "=r"(r) : "r"(a), "r"(b)); return r; }
__device__ __forceinline__ uint32_t bf2_add(uint32_t a, uint32_t b) { uint32_t r; asm("add.rn.bf16x2 %0, %1, %2;" : "=r"(r) : "r"(a), "r"(b)); return r; }
__device__ __forceinline__ uint32_t bf2_fma(uint32_t a, uint32_t b, uint32_t c) { uint32_t r; asm("fma.rn.bf16x2 %0, %1, %2, %3;" : "=r"(r) : "r"(a), "r"(b), "r"(c)); return r; }
__device__ __forceinline__ uint32_t gelu2_pair(float a, float b) {
  const uint32_t v = pack_bf16(a, b);
  uint32_t t;
  asm("tanh.approx.bf16x2 %0, %1;" : "=r"(t) : "r"(bf2_fma(v, bf2_fma(bf2_mul(v, v), 0x3d123d12u, 0xbe4fbe4fu), v)));
  return bf2_fma(v, t, v);
}
struct cplx { float re, im; };
__device__ __forceinline__ cplx cmul(cplx a, cplx b) { return {fmaf(a.re, b.re, -a.im * b.im), fmaf(a.re, b.im, a.im * b.re)}; }
__device__ __forceinline__ cplx cfma(cplx a, cplx b, cplx c) {
  return {fmaf(a.re, b.re, fmaf(-a.im, b.im, c.re)), fmaf(a.re, b.im, fmaf(a.im, b.re, c.im))};
}
__device__ __forceinline__ cplx make_lam(float lre, float lim, float ldt) {
  float dt = __bfloat162float(__float2bfloat16_rn(expf(ldt)));
  float mag = expf(dt * lre), sn, cs;
  sincospif(dt * lim * 0.31830988618379067f, &sn, &cs);
  return {mag * cs, mag * sn};
}

template<int TA,int TB,uint32_t AH,uint32_t BH> __device__ __forceinline__ void wgmma_n64_ss(float (&d)[32], uint32_t al, uint32_t ao, uint32_t bl, uint32_t bo, int scale_d){
  asm volatile("{.reg .pred p; .reg .b32 t, v; .reg .b64 da, db; setp.ne.b32 p, %36, 0; add.u32 t, %32, %33; mov.b64 da, {t, %39}; add.u32 v, %34, %35; mov.b64 db, {v, %40};\n"
   "wgmma.mma_async.sync.aligned.m64n64k16.f32.bf16.bf16 {%0,%1,%2,%3,%4,%5,%6,%7,%8,%9,%10,%11,%12,%13,%14,%15,%16,%17,%18,%19,%20,%21,%22,%23,%24,%25,%26,%27,%28,%29,%30,%31}, da, db, p, 1, 1, %37, %38;}"
   : "+f"(d[0]),"+f"(d[1]),"+f"(d[2]),"+f"(d[3]),"+f"(d[4]),"+f"(d[5]),"+f"(d[6]),"+f"(d[7]),"+f"(d[8]),"+f"(d[9]),"+f"(d[10]),"+f"(d[11]),"+f"(d[12]),"+f"(d[13]),"+f"(d[14]),"+f"(d[15]),"+f"(d[16]),"+f"(d[17]),"+f"(d[18]),"+f"(d[19]),"+f"(d[20]),"+f"(d[21]),"+f"(d[22]),"+f"(d[23]),"+f"(d[24]),"+f"(d[25]),"+f"(d[26]),"+f"(d[27]),"+f"(d[28]),"+f"(d[29]),"+f"(d[30]),"+f"(d[31])
   : "r"(al),"r"(ao >> 4),"r"(bl),"r"(bo >> 4),"r"(scale_d),"n"(TA),"n"(TB),"n"(AH),"n"(BH));
}
template<int TB,uint32_t BH> __device__ __forceinline__ void wgmma_n64_rs(float (&d)[32], uint32_t a0,uint32_t a1,uint32_t a2,uint32_t a3, uint32_t bl, uint32_t bo, int scale_d){
  asm volatile("{.reg .pred p; .reg .b32 t; .reg .b64 db; setp.ne.b32 p, %38, 0; add.u32 t, %36, %37; mov.b64 db, {t, %40};\n"
   "wgmma.mma_async.sync.aligned.m64n64k16.f32.bf16.bf16 {%0,%1,%2,%3,%4,%5,%6,%7,%8,%9,%10,%11,%12,%13,%14,%15,%16,%17,%18,%19,%20,%21,%22,%23,%24,%25,%26,%27,%28,%29,%30,%31}, {%32,%33,%34,%35}, db, p, 1, 1, %39;}"
   : "+f"(d[0]),"+f"(d[1]),"+f"(d[2]),"+f"(d[3]),"+f"(d[4]),"+f"(d[5]),"+f"(d[6]),"+f"(d[7]),"+f"(d[8]),"+f"(d[9]),"+f"(d[10]),"+f"(d[11]),"+f"(d[12]),"+f"(d[13]),"+f"(d[14]),"+f"(d[15]),"+f"(d[16]),"+f"(d[17]),"+f"(d[18]),"+f"(d[19]),"+f"(d[20]),"+f"(d[21]),"+f"(d[22]),"+f"(d[23]),"+f"(d[24]),"+f"(d[25]),"+f"(d[26]),"+f"(d[27]),"+f"(d[28]),"+f"(d[29]),"+f"(d[30]),"+f"(d[31])
   : "r"(a0),"r"(a1),"r"(a2),"r"(a3),"r"(bl),"r"(bo >> 4),"r"(scale_d),"n"(TB),"n"(BH));
}
template<int TA,int TB,uint32_t AH,uint32_t BH> __device__ __forceinline__ void wgmma_n96_ss(float (&d)[48], uint32_t al, uint32_t ao, uint32_t bl, uint32_t bo, int scale_d){
  asm volatile("{.reg .pred p; .reg .b32 t, v; .reg .b64 da, db; setp.ne.b32 p, %52, 0; add.u32 t, %48, %49; mov.b64 da, {t, %55}; add.u32 v, %50, %51; mov.b64 db, {v, %56};\n"
   "wgmma.mma_async.sync.aligned.m64n96k16.f32.bf16.bf16 {%0,%1,%2,%3,%4,%5,%6,%7,%8,%9,%10,%11,%12,%13,%14,%15,%16,%17,%18,%19,%20,%21,%22,%23,%24,%25,%26,%27,%28,%29,%30,%31,%32,%33,%34,%35,%36,%37,%38,%39,%40,%41,%42,%43,%44,%45,%46,%47}, da, db, p, 1, 1, %53, %54;}"
   : "+f"(d[0]),"+f"(d[1]),"+f"(d[2]),"+f"(d[3]),"+f"(d[4]),"+f"(d[5]),"+f"(d[6]),"+f"(d[7]),"+f"(d[8]),"+f"(d[9]),"+f"(d[10]),"+f"(d[11]),"+f"(d[12]),"+f"(d[13]),"+f"(d[14]),"+f"(d[15]),"+f"(d[16]),"+f"(d[17]),"+f"(d[18]),"+f"(d[19]),"+f"(d[20]),"+f"(d[21]),"+f"(d[22]),"+f"(d[23]),"+f"(d[24]),"+f"(d[25]),"+f"(d[26]),"+f"(d[27]),"+f"(d[28]),"+f"(d[29]),"+f"(d[30]),"+f"(d[31]),"+f"(d[32]),"+f"(d[33]),"+f"(d[34]),"+f"(d[35]),"+f"(d[36]),"+f"(d[37]),"+f"(d[38]),"+f"(d[39]),"+f"(d[40]),"+f"(d[41]),"+f"(d[42]),"+f"(d[43]),"+f"(d[44]),"+f"(d[45]),"+f"(d[46]),"+f"(d[47])
   : "r"(al),"r"(ao >> 4),"r"(bl),"r"(bo >> 4),"r"(scale_d),"n"(TA),"n"(TB),"n"(AH),"n"(BH));
}
template<int TA,int TB,uint32_t AH,uint32_t BH> __device__ __forceinline__ void wgmma_n128_ss(float (&d)[64], uint32_t al, uint32_t ao, uint32_t bl, uint32_t bo, int scale_d){
  asm volatile("{.reg .pred p; .reg .b32 t, v; .reg .b64 da, db; setp.ne.b32 p, %68, 0; add.u32 t, %64, %65; mov.b64 da, {t, %71}; add.u32 v, %66, %67; mov.b64 db, {v, %72};\n"
   "wgmma.mma_async.sync.aligned.m64n128k16.f32.bf16.bf16 {%0,%1,%2,%3,%4,%5,%6,%7,%8,%9,%10,%11,%12,%13,%14,%15,%16,%17,%18,%19,%20,%21,%22,%23,%24,%25,%26,%27,%28,%29,%30,%31,%32,%33,%34,%35,%36,%37,%38,%39,%40,%41,%42,%43,%44,%45,%46,%47,%48,%49,%50,%51,%52,%53,%54,%55,%56,%57,%58,%59,%60,%61,%62,%63}, da, db, p, 1, 1, %69, %70;}"
   : "+f"(d[0]),"+f"(d[1]),"+f"(d[2]),"+f"(d[3]),"+f"(d[4]),"+f"(d[5]),"+f"(d[6]),"+f"(d[7]),"+f"(d[8]),"+f"(d[9]),"+f"(d[10]),"+f"(d[11]),"+f"(d[12]),"+f"(d[13]),"+f"(d[14]),"+f"(d[15]),"+f"(d[16]),"+f"(d[17]),"+f"(d[18]),"+f"(d[19]),"+f"(d[20]),"+f"(d[21]),"+f"(d[22]),"+f"(d[23]),"+f"(d[24]),"+f"(d[25]),"+f"(d[26]),"+f"(d[27]),"+f"(d[28]),"+f"(d[29]),"+f"(d[30]),"+f"(d[31]),"+f"(d[32]),"+f"(d[33]),"+f"(d[34]),"+f"(d[35]),"+f"(d[36]),"+f"(d[37]),"+f"(d[38]),"+f"(d[39]),"+f"(d[40]),"+f"(d[41]),"+f"(d[42]),"+f"(d[43]),"+f"(d[44]),"+f"(d[45]),"+f"(d[46]),"+f"(d[47]),"+f"(d[48]),"+f"(d[49]),"+f"(d[50]),"+f"(d[51]),"+f"(d[52]),"+f"(d[53]),"+f"(d[54]),"+f"(d[55]),"+f"(d[56]),"+f"(d[57]),"+f"(d[58]),"+f"(d[59]),"+f"(d[60]),"+f"(d[61]),"+f"(d[62]),"+f"(d[63])
   : "r"(al),"r"(ao >> 4),"r"(bl),"r"(bo >> 4),"r"(scale_d),"n"(TA),"n"(TB),"n"(AH),"n"(BH));
}

__global__ void __cluster_dims__(2, 1, 1) __launch_bounds__(384, 1)
fused_kernel(const __nv_bfloat16* __restrict__ x, const __nv_bfloat16* __restrict__ bre, const __nv_bfloat16* __restrict__ bim,
             const __nv_bfloat16* __restrict__ lam_re, const __nv_bfloat16* __restrict__ lam_im, const __nv_bfloat16* __restrict__ log_dt,
             const __nv_bfloat16* __restrict__ dskip, const __nv_bfloat16* __restrict__ b1, const __nv_bfloat16* __restrict__ b2,
             const __nv_bfloat16* __restrict__ gate_w, const __nv_bfloat16* __restrict__ pf_w1, const __nv_bfloat16* __restrict__ pf_w2,
             const __nv_bfloat16* __restrict__ pf_cre, const __nv_bfloat16* __restrict__ pf_cim, float* __restrict__ out,
             const __grid_constant__ Maps maps) {
  extern __shared__ __align__(1024) unsigned char smem_raw[];
  const uint32_t sb = (uint32_t)__cvta_generic_to_shared(smem_raw);
  const int b = blockIdx.x;
  const int rank = b & 1, cl = b >> 1;
  const int sp = (cl & 1) | ((cl >> 2) & 2), m = ((cl >> 1) & 3) | ((cl >> 4) << 2);
  const int s = sp * 2 + rank;
  const int warp = __shfl_sync(0xffffffffu, (int)(threadIdx.x >> 5), 0);
  const int lane = threadIdx.x & 31;
  const int xrot = 9 - 2 * sp;

  if (elect_one()) {
    if (warp == 8) TS(2, 0);
    if (warp < 3) {
      asm volatile("prefetch.tensormap [%0];" ::"l"(&maps.x + warp) : "memory");
      mbar_init(sb + OFF_GBAR + 8 * warp, warp < 2 ? 64 : 96);
    }
    const uint32_t c = warp < 8 ? 1 : warp < 11 ? 8 : 4;
    mbar_init(sb + OFF_XFULL + 16 * warp, c);
    mbar_init(sb + OFF_XFULL + 16 * warp + 8, c);
    asm volatile("fence.mbarrier_init.release.cluster;" ::: "memory");
  }
  __syncwarp();
  asm volatile("barrier.cluster.arrive.relaxed.aligned;" ::: "memory");
  if (warp < 8) {
    const int c = threadIdx.x & 7, r = threadIdx.x >> 3;
    const uint32_t so = sb + r * 128 + ((c ^ (r & 7)) << 4);
    const __nv_bfloat16* gx = x + (m * 128 + ((r >> 1) & 3) * 16 + (r >> 3) * 2 + (r & 1)) * DM + c * 8;
    const int go = (s * 64 + r) * DM + c * 8;
#pragma unroll
    for (int i = 0; i < 4; i++) {
      asm volatile("cp.async.cg.shared.global [%0], [%1], 16;" ::"r"(so + OFF_X + (xrot & 7) * 16384 + i * 4096), "l"(gx + ((i & 1) * 8 + (i >> 1) * 64) * DM) : "memory");
      asm volatile("cp.async.cg.shared.global [%0], [%1], 16;" ::"r"(so + OFF_RING + i * 4096), "l"((i < 2 ? bre : bim) + go + (i & 1) * 32 * DM) : "memory");
    }
    if (threadIdx.x == 0) TS(2, 3);
  }

  if (warp < 8) {
    const int wg = warp >> 2, w = warp & 3, q = lane & 3, gr = lane >> 2;
    uint32_t bv[28];
    auto load_bias = [&]() {
#pragma unroll
      for (int j = 0; j < 28; j++) asm volatile("ld.global.nc.u32 %0, [%1];" : "=r"(bv[j]) : "l"(reinterpret_cast<const uint32_t*>(b1 + s * 224 + j * 8) + q));
    };
    if (!W0) load_bias();
    asm volatile("setmaxnreg.inc.sync.aligned.u32 224;");
    asm volatile("barrier.cluster.wait.aligned;" ::: "memory");
    TS(wg, 0);
    auto release = [&](int slot) { if (lane == 0) mbar_arrive(sb + OFF_EMPTY + 8 * slot); };
    const uint32_t xw = sb + OFF_X + wg * 8192, fullb = sb + OFF_FULL;
    const uint32_t dxw = (xw & 0x3FFFF) >> 4, dring = ((sb + OFF_RING) & 0x3FFFF) >> 4;

    float ure[32], uim[32], aa[48], ab[64];
    cplx lam[2], coef[2], l16[2], l32[2], lq[2], pre[2], e[2];
    uint32_t sh16, mhi;

    auto bias = [&](int c) {
#pragma unroll
      for (int j = c * 7; j < c * 7 + 7; j++) {
        pin(bv[j]);
        float* d = j < 12 ? aa + 4 * j : ab + 4 * (j - 12);
        d[0] = d[2] = __uint_as_float(bv[j] << sh16); d[1] = d[3] = __uint_as_float(bv[j] & mhi);
        pin(d[0]); pin(d[1]); pin(d[2]); pin(d[3]);
      }
    };
    if (SB0 < 0) { sh16 = 16; mhi = 0xffff0000u; bias(0); bias(1); bias(2); bias(3); TS(wg, 27); }
#pragma unroll
    for (int kb = 0; kb < 8; kb++) {
      const int slot = kb % NSLOT;
      if (W0 && kb == 0) {
        asm volatile("cp.async.wait_all;" ::: "memory");
        TS(wg, 18);
        asm volatile("fence.proxy.async.shared::cta;" ::: "memory");
        bar_sync(5, 256);
        if (threadIdx.x < 2) mbar_arrive(sb + OFF_XFULL + threadIdx.x * 64);
      } else {
        mbar_wait(sb + OFF_XFULL + 8 * kb, 0);
        if (kb == 0) TS(wg, 18);
        mbar_wait(fullb + 8 * slot, (kb / NSLOT) & 1);
      }
      TS2(2, kb);
      if (kb == 0) TS(wg, 1);
      wg_fence();
      const uint32_t dxa = dxw + ((kb + xrot) & 7) * 1024;
#pragma unroll
      for (int kk = 0; kk < 4; kk++) {
        wgmma_n64_ss<0, 0, DH128, DH128>(ure, dring, slot * 16384 + kk * 32, dxa, kk * 32, (kb | kk) != 0);
        wgmma_n64_ss<0, 0, DH128, DH128>(uim, dring, slot * 16384 + 8192 + kk * 32, dxa, kk * 32, (kb | kk) != 0);
      }
      wg_commit();
      if (W0 && kb == 0) load_bias();
      if (kb > 0) { wg_wait<1>(); release((kb - 1) % NSLOT); }
      if (SB0 >= 0) {
        if (kb == SB0) { sh16 = late16(sb + OFF_XFULL); mhi = 0xffffffffu << sh16; bias(0); }
        if (kb == 4) bias(1);
        if (kb == 6) bias(2);
      }
      if (kb == 3) {
        mbar_wait(sb + OFF_LBAR, 0);
#pragma unroll
        for (int h = 0; h < 2; h++) {
          const uint4 v = lds_u4(sb + OFF_LC + (w * 16 + gr + 8 * h) * 16);
          lam[h] = cplx{__uint_as_float(v.x), __uint_as_float(v.y)};
          coef[h] = cplx{__uint_as_float(v.z), __uint_as_float(v.w)};
        }
      }
      if (kb == 5) {
#pragma unroll
        for (int h = 0; h < 2; h++) {
          pin(lam[h].re); pin(lam[h].im);
          cplx t = cmul(lam[h], lam[h]); t = cmul(t, t); t = cmul(t, t);
          l16[h] = cmul(t, t);
          pin(l16[h].re); pin(l16[h].im);
        }
      }
      if (kb == 7) {
#pragma unroll
        for (int h = 0; h < 2; h++) {
          pin(l16[h].re); pin(l16[h].im);
          l32[h] = cmul(l16[h], l16[h]);
          const cplx a = (q & 1) ? l16[h] : cplx{1.f, 0.f}, c = (q & 2) ? l32[h] : cplx{1.f, 0.f};
          lq[h] = cmul(cmul(a, c), coef[h]);
          pin(lq[h].re); pin(lq[h].im);
        }
      }
    }
    TS(wg, 2);
    auto scale_u = [&](int i0, int i1) {
#pragma unroll
      for (int i = 0; i < 32; i++) if (i >= i0 && i < i1) {
        pin(ure[i]); pin(uim[i]);
        const cplx v = cmul(coef[(i >> 1) & 1], cplx{ure[i], uim[i]});
        ure[i] = v.re; uim[i] = v.im;
        pin(ure[i]); pin(uim[i]);
      }
    };
#pragma unroll
    for (int kb = 0; kb < 8; kb++) {
      const int u = 8 + kb, slot = u % NSLOT;
      mbar_wait(fullb + 8 * slot, (u / NSLOT) & 1);
      wg_fence();
      const uint32_t dxa = dxw + ((kb + xrot) & 7) * 1024;
#pragma unroll
      for (int kk = 0; kk < 4; kk++)
        wgmma_n96_ss<0, 1, DH128, DH64>(aa, dxa, kk * 32, dring, slot * 16384 + kk * 1024 + lbo(4096), 1);
      wg_commit();
      if (SB0 >= 0 && kb == 0) bias(3);
      wg_wait<1>();
      release((u - 1) % NSLOT);
      if (kb == 0) {
        reg_fence(ure); reg_fence(uim);
#pragma unroll
        for (int h = 0; h < 2; h++) e[h] = cplx{ure[2 * h], uim[2 * h]};
      }
      if (kb == 0 || kb == 2 || kb == 3) {
        const int ch = kb ? kb - 1 : 0;
#pragma unroll
        for (int t = 1 + 5 * ch; t < 6 + 5 * ch; t++)
#pragma unroll
          for (int h = 0; h < 2; h++) { const int i = 4 * (t >> 1) + 2 * h + (t & 1); e[h] = cfma(lam[h], e[h], cplx{ure[i], uim[i]}); }
#pragma unroll
        for (int h = 0; h < 2; h++) { pin(e[h].re); pin(e[h].im); }
      } else if (kb == 4) {
#pragma unroll
        for (int h = 0; h < 2; h++) {
          cplx y = {__shfl_up_sync(0xffffffffu, e[h].re, 1, 4), __shfl_up_sync(0xffffffffu, e[h].im, 1, 4)};
          if (q >= 1) e[h] = cfma(l16[h], y, e[h]);
          y = cplx{__shfl_up_sync(0xffffffffu, e[h].re, 2, 4), __shfl_up_sync(0xffffffffu, e[h].im, 2, 4)};
          if (q >= 2) e[h] = cfma(l32[h], y, e[h]);
        }
        if (q == 3) {
#pragma unroll
          for (int h = 0; h < 2; h++)
            asm volatile("st.shared.v2.f32 [%0], {%1,%2};" ::"r"(sb + OFF_CARRY + wg * 512 + (w * 16 + gr + 8 * h) * 8), "f"(e[h].re), "f"(e[h].im) : "memory");
          mbar_arrive(sb + OFF_GBAR);
        }
#pragma unroll
        for (int h = 0; h < 2; h++) {
          const cplx y = {__shfl_up_sync(0xffffffffu, e[h].re, 1, 4), __shfl_up_sync(0xffffffffu, e[h].im, 1, 4)};
          pre[h] = (q >= 1) ? cmul(coef[h], y) : cplx{0.f, 0.f};
          pin(pre[h].re); pin(pre[h].im);
        }
        TS(wg, 3);
      } else if (kb > 4) {
        scale_u(kb == 5 ? 0 : kb == 6 ? 4 : 12, kb == 5 ? 4 : kb == 6 ? 12 : 20);
      }
    }
    TS(wg, 4);
    uint32_t H[56], hf[32];
    cplx hst[2];
    const uint32_t hst_addr = xw + (w * 16 + (lane & 15)) * 128 + (((lane >> 4) ^ (lane & 7)) << 4);
    const uint32_t him = (2 - rank) * 16384;
    uint32_t peer;
    asm volatile("mapa.shared::cluster.u32 %0, %1, %2;" : "=r"(peer) : "r"(sb), "r"(rank ^ 1));
    auto credit = [&]() { if (lane == 0) mbar_arrive_cl(peer + OFF_KBAR + wg * 8); };
#pragma unroll
    for (int kb = 0; kb < 8; kb++) {
      const int u = 16 + kb, slot = u % NSLOT;
      mbar_wait(fullb + 8 * slot, (u / NSLOT) & 1);
      wg_fence();
#pragma unroll
      for (int kk = 0; kk < 4; kk++)
        wgmma_n128_ss<0, 1, DH128, DH128>(ab, dxw, kb * 16384 + kk * 32, dring, slot * 16384 + kk * 2048 + lbo(8192), 1);
      wg_commit();
      wg_wait<1>();
      release((u - 1) % NSLOT);
      if (kb == 0) scale_u(20, 32);
      if (kb < 5 && kb != 1) {
        const int ch = kb ? kb - 1 : 0;
#pragma unroll
        for (int i = ch * 6; i < ch * 6 + 6; i++) {
          pin(aa[2 * i]); pin(aa[2 * i + 1]);
          H[i] = gelu2_pair(aa[2 * i], aa[2 * i + 1]);
          pin(H[i]);
        }
      }
      if (kb >= 4) {
        if (kb == 4) {
          TS(wg, 5);
          mbar_wait(sb + OFF_CBAR, 0);
          TS(wg, 6);
#pragma unroll
          for (int h = 0; h < 2; h++) {
            const float2 c = lds_f2(sb + OFF_CARRY + wg * 512 + (w * 16 + gr + 8 * h) * 8);
            hst[h] = cfma(lq[h], cplx{c.x, c.y}, pre[h]);
          }
        }
        const int j0 = (kb - 4) * 2;
        uint32_t rr[4], ri[4];
#pragma unroll
        for (int jj = 0; jj < 2; jj++) {
          const int j = j0 + jj;
          const uint32_t g2 = lds_u(sb + OFF_GS + (wg * 64 + j * 8 + q * 2) * 2);
#pragma unroll
          for (int h = 0; h < 2; h++) {
            const int i = 4 * j + 2 * h;
            const cplx h0 = cfma(lam[h], hst[h], cplx{ure[i], uim[i]});
            hst[h] = cfma(lam[h], h0, cplx{ure[i + 1], uim[i + 1]});
            rr[jj * 2 + h] = bf2_mul(pack_bf16(h0.re, hst[h].re), g2);
            ri[jj * 2 + h] = bf2_mul(pack_bf16(h0.im, hst[h].im), g2 ^ 0x80008000u);
          }
        }
        const uint32_t a = hst_addr ^ (j0 << 4);
        asm volatile("stmatrix.sync.aligned.m8n8.x4.shared.b16 [%0], {%1,%2,%3,%4};" ::"r"(a), "r"(rr[0]), "r"(rr[1]), "r"(rr[2]), "r"(rr[3]) : "memory");
        asm volatile("stmatrix.sync.aligned.m8n8.x4.shared.b16 [%0], {%1,%2,%3,%4};" ::"r"(a + him), "r"(ri[0]), "r"(ri[1]), "r"(ri[2]), "r"(ri[3]) : "memory");
      }
    }
    TS(wg, 7);

    uint4* const psend = g_part + (size_t)(m * 8 + rank) * 3072 + warp * 128 + lane;
    const uint4* const precv = g_part + (size_t)(m * 8 + s) * 3072 + warp * 128 + lane;
    const uint32_t pbuf = OFF_X + warp * 2048 + lane * 16;
    const uint32_t dx0 = ((sb + OFF_X) & 0x3FFFF) >> 4;
    float o[32], fin[32], rho[2];
    uint32_t tr[8];
    uint32_t r0[16], pt[16], sum[16], tag;
    auto recv_issue = [&](uint32_t (&r)[16], int k) {
#pragma unroll
      for (int i = 0; i < 4; i++) ld_b128(precv + k * 1024 + i * 32, r[4 * i], r[4 * i + 1], r[4 * i + 2], r[4 * i + 3]);
    };
    auto stale = [&](uint32_t (&r)[16]) {
      uint32_t t0, t1, r_;
      asm("lop3.b32 %0, %1, %2, %3, 0x7e;" : "=r"(t0) : "r"(r[0]), "r"(r[4]), "r"(tag));
      asm("lop3.b32 %0, %1, %2, %3, 0x7e;" : "=r"(t1) : "r"(r[8]), "r"(r[12]), "r"(tag));
      asm volatile("{.reg .pred p; .reg .b32 t; lop3.b32 t, %1, %2, 1, 0xa8; setp.ne.u32 p, t, 0; vote.sync.any.pred p, p, 0xffffffff; selp.u32 %0, 1, 0, p;}" : "=r"(r_) : "r"(t0), "r"(t1));
      return r_ != 0;
    };
    auto recv_check = [&](uint32_t (&r)[16], int k) {
      if (__builtin_expect(stale(r), 0)) {
        int tries = 0;
#pragma unroll 1
        do { recv_issue(r, k); } while (stale(r) && ++tries < 200000);
      }
    };
    auto gelu_b = [&](int i0, int i1) {
#pragma unroll
      for (int i = i0; i < i1; i++) {
        pin(ab[2 * i]); pin(ab[2 * i + 1]);
        H[24 + i] = gelu2_pair(ab[2 * i], ab[2 * i + 1]);
        pin(H[24 + i]);
      }
    };
    auto step = [&](float (&d)[32], int p, int k, int acc) {
      const uint32_t wo = stage_off(p);
      if (k >= 6 && k < 14) {
        const int kk = k - 6;
        wgmma_n64_rs<0, DH128>(d, hf[4 * kk], hf[4 * kk + 1], hf[4 * kk + 2], hf[4 * kk + 3], dx0, wo + 14336 + (kk >> 2) * 8192 + (kk & 3) * 32, 1);
      } else {
        const int kk = k < 6 ? k : k - 8;
        wgmma_n64_rs<1, DH128>(d, H[4 * kk], H[4 * kk + 1], H[4 * kk + 2], H[4 * kk + 3], dx0, wo + (kk / 7) * 30720 + (kk % 7) * 2048, k != 0 || acc);
      }
    };
    auto mma = [&](float (&d)[32], int p, int k0, int k1, int acc) {
      wg_fence();
#pragma unroll
      for (int k = k0; k < k1; k++) step(d, p, k, acc);
      wg_commit();
    };
    auto send_peer = [&]() {
#pragma unroll
      for (int i = 0; i < 4; i++)
        asm volatile("st.async.shared::cluster.mbarrier::complete_tx::bytes.v4.b32 [%0], {%1,%2,%3,%4}, [%5];" ::"r"(peer + pbuf + i * 512),
                     "r"(pack_bf16(o[8 * i], o[8 * i + 1])), "r"(pack_bf16(o[8 * i + 2], o[8 * i + 3])), "r"(pack_bf16(o[8 * i + 4], o[8 * i + 5])),
                     "r"(pack_bf16(o[8 * i + 6], o[8 * i + 7])), "r"(peer + OFF_RBAR + wg * 8) : "memory");
    };
    auto recv_peer = [&](int k) {
      mbar_wait(sb + OFF_RBAR + wg * 8, k & 1);
#pragma unroll
      for (int i = 0; i < 4; i++) { const uint4 v = lds_u4(sb + pbuf + i * 512); pt[4 * i] = v.x; pt[4 * i + 1] = v.y; pt[4 * i + 2] = v.z; pt[4 * i + 3] = v.w; }
    };
    auto send_owner = [&](float (&d)[32], int k) {
#pragma unroll
      for (int i = 0; i < 4; i++) {
#pragma unroll
        for (int c = 4 * i; c < 4 * i + 4; c++) pt[c] = bf2_add(pt[c], pack_bf16(d[2 * c], d[2 * c + 1]));
        asm("lop3.b32 %0, %0, 1, %1, 0xb8;" : "+r"(pt[4 * i]) : "r"(tag));
        st_b128(psend + (((sp + 1 + k) & 3) * 6 + k) * 1024 + i * 32, pt[4 * i], pt[4 * i + 1], pt[4 * i + 2], pt[4 * i + 3]);
      }
      __syncwarp();
      credit();
    };
    auto load_fin = [&]() {
      mbar_wait(sb + OFF_LBAR, 1);
#pragma unroll
      for (int j = 0; j < 8; j++) {
        const uint4 v = lds_u4(sb + pbuf + 16384 + (j >> 2) * 16384 + (j & 3) * 512);
        fin[4 * j] = __uint_as_float(v.x); fin[4 * j + 1] = __uint_as_float(v.y); fin[4 * j + 2] = __uint_as_float(v.z); fin[4 * j + 3] = __uint_as_float(v.w);
      }
    };
    auto ldk = [&](int pos) { if (pos == K0P) recv_issue(sum, 0); if (pos == K1P) recv_issue(r0, 1); };
    auto arm = [&]() { if ((threadIdx.x & 127) == 0) mbar_expect_tx(sb + OFF_RBAR + wg * 8, 8192); };
#pragma unroll
    for (int p = 0; p < 8; p++) {
      if (p == 0) {
        mbar_wait(fullb, 0);
        mma(o, 0, 0, 3, 0);
        wg_wait<1>(); release(5);
        gelu_b(0, 4);
        mma(o, 0, 3, 6, 0);
        bar_sync(1 + wg, 128);
        {
          const uint32_t ha = xw + ((lane >> 4) * 8 + (lane & 7)) * 128 + (((2 * w + ((lane >> 3) & 1)) ^ (lane & 7)) << 4);
#pragma unroll
          for (int kk = 0; kk < 8; kk++)
            asm volatile("ldmatrix.sync.aligned.m8n8.x4.trans.shared.b16 {%0,%1,%2,%3}, [%4];" : "=r"(hf[4 * kk]), "=r"(hf[4 * kk + 1]), "=r"(hf[4 * kk + 2]), "=r"(hf[4 * kk + 3])
                         : "r"(ha + (kk >> 2) * him + (kk & 3) * 2048) : "memory");
        }
        gelu_b(4, 10);
        mbar_wait(fullb + 8, 0);
        mma(o, 0, 6, 10, 0);
        credit();
        gelu_b(10, 16);
        mma(o, 0, 10, 15, 0);
        gelu_b(16, 24);
        mbar_wait(fullb + 16, 0);
        mma(o, 0, 15, 18, 0);
        gelu_b(24, 32);
        if (wg == 1) bar_sync(4, 256);
        mma(o, 0, 18, 22, 0);
      } else {
        TR(0);
        if (EW == 0 || (EW == 1 && (p & 1))) mbar_wait(sb + OFF_XFULL + 8 * p, 1);
        TR(1);
        bar_sync(3 + wg, 256);
        if (p < 7) mma(o, p, 0, 22, 0);
        else if (GAP == 0) mma(fin, p, 0, 22, 1);
        else {
          mma(fin, p, 0, GAP, 1);
          recv_peer(3);
          tag = lds_u(sb + OFF_EPOCH);
          mma(fin, p, GAP, 22, 1);
        }
      }
      if (p < 7 || wg == 0) bar_arrive(4 - wg, 256);
      TR(2);
      if (p != TP) TS(wg, 8 + p);
      if (p < 7 && (EW == 2 || (EW == 1 && (p & 1)))) mbar_wait(sb + OFF_XFULL + 8 * (p + 1), 1);
      ldk(10 * p);
      if ((p & 1) == 0) {
        arm();
        if (p == 6) {
          mbar_wait(sb + OFF_EMPTY + 32, 0);
          tag = lds_u(sb + OFF_EPOCH);
          recv_check(sum, 0); recv_check(r0, 1);
#pragma unroll
          for (int i = 0; i < 16; i++) sum[i] = bf2_add(sum[i], r0[i]);
        }
        TR(3);
        mbar_wait(sb + OFF_KBAR + wg * 8, (p >> 1) & 1);
        TR(4);
      } else {
        if (p == 1 || (p == 7 && GAP == 0)) tag = lds_u(sb + OFF_EPOCH);
        TR(3);
        if (p < 7 || GAP == 0) recv_peer(p >> 1);
        TR(4);
        if (p == 7) {
          recv_check(r0, 2);
#pragma unroll
          for (int i = 0; i < 16; i++) sum[i] = bf2_add(sum[i], bf2_add(r0[i], pt[i]));
        }
      }
      if (p == FINP && !FINW) load_fin();
      ldk(10 * p + 1);
      TR(5);
      wg_wait<0>();
      TR(6);
      if (p < 5) release(p);
      if (p < 7) reg_fence(o); else reg_fence(fin);
      ldk(10 * p + 2);
      if ((p & 1) == 0) {
        if (p == 6) recv_issue(r0, 2);
        send_peer();
        if (p == FINP && FINW) load_fin();
      } else if (p < 7) {
        send_owner(o, p >> 1);
      }
      ldk(10 * p + 3);
      if (p == 2) {
#pragma unroll
        for (int h = 0; h < 2; h++) { rho[h] = __fdividef(2.f, 4.f + bf_lo(lds_h(sb + OFF_GS + (wg * 64 + w * 16 + gr + 8 * h) * 2))); pin(rho[h]); }
      }
      TR(7);
    }
    {
      TS(wg, 16);
      const uint32_t tb = sb + OFF_X + stage_off(0) + warp * 4096;
      const uint32_t ta = tb + gr * 256 + ((gr & 3) << 5) + q * 8;
      const uint32_t la = tb + (lane >> 3) * 256 + (((lane & 7) << 4) ^ ((lane >> 3) << 5));
      float* op = out + (size_t)(m * 128 + wg * 64 + (lane >> 4) * 16 + w * 4 + ((lane >> 3) & 1)) * DM + s * 64 + (lane & 7) * 4;
#pragma unroll
      for (int qq = 0; qq < 4; qq += QS) {
#pragma unroll
        for (int qt = qq; qt < qq + QS; qt++) {
          const int h = qt & 1, ch = qt >> 1;
#pragma unroll
          for (int j = 0; j < 4; j++) {
            const int i = ch * 8 + j * 2 + h;
            asm volatile("st.shared.v2.f32 [%0], {%1,%2};" ::"r"((ta ^ (j << 5)) + h * 2048 + ch * 128),
                         "f"((fin[2 * i] + bf_lo(sum[i])) * rho[h]), "f"((fin[2 * i + 1] + bf_hi(sum[i])) * rho[h]) : "memory");
          }
        }
        __syncwarp();
#pragma unroll
        for (int qt = qq; qt < qq + QS; qt++) {
          const int h = qt & 1, ch = qt >> 1;
#pragma unroll
          for (int r = 0; r < 2; r++)
            *reinterpret_cast<uint4*>(op + (r * 32 + h * 2) * DM + ch * 32) = lds_u4(la + (h * 2 + r) * 1024 + ch * 128);
        }
      }
      if (threadIdx.x == 128) g_epoch[b] = tag;
      TS(wg, 17); TG(wg); TRD(); TDUMP();
    }
  } else {
    asm volatile("setmaxnreg.dec.sync.aligned.u32 56;");
    int wsel = warp;
    asm("" : "+r"(wsel));
    if (wsel > 8) {
      if (warp != 11) {
        const int t = threadIdx.x - 288;
        unsigned par;
        asm volatile("ld.relaxed.gpu.global.u32 %0, [%1];" : "=r"(par) : "l"(g_epoch + b) : "memory");
        const float pr = bf_ld(lam_re + s * 64 + t), pi = bf_ld(lam_im + s * 64 + t), pd = bf_ld(log_dt + s * 64 + t);
        asm volatile("barrier.cluster.wait.aligned;" ::: "memory");
        par = __shfl_sync(0xffffffffu, (par + 1) & 1, 0);
        cplx l64 = make_lam(pr, pi, pd);
        {
          const float inv = __fdividef(1.f, fmaf(pr, pr, pi * pi));
          const cplx cf = cmul(cplx{l64.re - 1.f, l64.im}, cplx{pr * inv, -pi * inv});
          asm volatile("st.shared.v4.f32 [%0], {%1,%2,%3,%4};" ::"r"(sb + OFF_LC + t * 16), "f"(l64.re), "f"(l64.im), "f"(cf.re), "f"(cf.im) : "memory");
          mbar_arrive(sb + OFF_LBAR);
        }
#pragma unroll
        for (int i = 0; i < 6; i++) l64 = cmul(l64, l64);
        cplx l128 = cmul(l64, l64);
        pin(l128.re); pin(l128.im);
        uint32_t vr[15], vi[15];
#pragma unroll
        for (int i = 0; i < 15; i++) { vr[i] = par; vi[i] = 0; pin(vr[i]); pin(vi[i]); }
        mbar_wait(sb + OFF_GBAR, 0);
        const float2 e0 = lds_f2(sb + OFF_CARRY + t * 8), e1 = lds_f2(sb + OFF_CARRY + 512 + t * 8);
        float2* eb = g_end + s * 1024 + t;
        {
          const cplx e = cfma(l64, cplx{e0.x, e0.y}, cplx{e1.x, e1.y});
          const unsigned long long v = ((unsigned long long)__float_as_uint(e.im) << 32) | ((__float_as_uint(e.re) & ~1u) | par);
          asm volatile("st.relaxed.gpu.global.b64 [%0], %1;" ::"l"(eb + m * 64), "l"(v) : "memory");
        }
        if (t == 0) TS(3, 1);
        cplx S = {0.f, 0.f};
        {
          if (LBD) __nanosleep(LBD);
          const float2* e15 = eb + (m - 15) * 64;
          int tries = 0;
          bool bad;
#pragma unroll 1
          do {
#pragma unroll
            for (int i = 0; i < 15; i++)
              asm volatile("{.reg .pred p; .reg .b64 v; mov.b64 v, {%0,%1}; setp.ge.s32 p, %3, %4; @p ld.relaxed.gpu.global.b64 v, [%2]; mov.b64 {%0,%1}, v;}"
                           : "+r"(vr[i]), "+r"(vi[i]) : "l"(e15 + i * 64), "r"(m), "r"(15 - i) : "memory");
            uint32_t x = vr[0] ^ par;
#pragma unroll
            for (int i = 1; i < 15; i++) asm("lop3.b32 %0, %0, %1, %2, 0xf6;" : "+r"(x) : "r"(vr[i]), "r"(par));
            bad = __any_sync(0xffffffffu, x & 1);
          } while (bad && ++tries < 200000);
          if (t == 0) TS(3, 2);
          S = cplx{__uint_as_float(vr[0]), __uint_as_float(vi[0])};
#pragma unroll
          for (int i = 1; i < 15; i++) S = cfma(l128, S, cplx{__uint_as_float(vr[i]), __uint_as_float(vi[i])});
        }
        const cplx S1 = cfma(l64, S, cplx{e0.x, e0.y});
        asm volatile("st.shared.v2.f32 [%0], {%1,%2};" ::"r"(sb + OFF_CARRY + t * 8), "f"(S.re), "f"(S.im) : "memory");
        asm volatile("st.shared.v2.f32 [%0], {%1,%2};" ::"r"(sb + OFF_CARRY + 512 + t * 8), "f"(S1.re), "f"(S1.im) : "memory");
        mbar_arrive(sb + OFF_CBAR);
        if (t == 0) TS(3, 3);
        mbar_wait(sb + OFF_CBAR, 0);
        const int gr = lane >> 2, q = lane & 3;
        float2 db[8];
#pragma unroll
        for (int j = 0; j < 8; j++) db[j] = lds_f2(sb + OFF_DB + j * 32 + q * 8);
        mbar_wait(sb + OFF_XFULL + 16, 1);
        mbar_wait(sb + OFF_EMPTY, 0);
#pragma unroll 1
        for (int cw = warp - 9; cw < 8; cw += 2) {
          const float r0 = 0.5f * bf_lo(lds_h(sb + OFF_GS + (cw * 16 + gr) * 2)), r1 = 0.5f * bf_lo(lds_h(sb + OFF_GS + (cw * 16 + gr) * 2 + 16));
          const uint32_t xa = sb + OFF_X + (1 + rank) * 16384 + (cw * 16 + (lane & 15)) * 128 + (((lane >> 4) ^ (lane & 7)) << 4);
          uint32_t xv[16];
#pragma unroll
          for (int i = 0; i < 4; i++)
            asm volatile("ldmatrix.sync.aligned.m8n8.x4.shared.b16 {%0,%1,%2,%3}, [%4];" : "=r"(xv[4 * i]), "=r"(xv[4 * i + 1]), "=r"(xv[4 * i + 2]), "=r"(xv[4 * i + 3])
                         : "r"(xa ^ (i << 5)) : "memory");
          __syncwarp();
#pragma unroll
          for (int j = 0; j < 8; j++) {
            const uint32_t x0 = bf2_mul(xv[2 * j], __float_as_uint(db[j].x)), x1 = bf2_mul(xv[2 * j + 1], __float_as_uint(db[j].x));
            pin(db[j].y);
            const float bl = bf_lo(__float_as_uint(db[j].y)), bh = bf_hi(__float_as_uint(db[j].y));
            asm volatile("st.shared.v4.f32 [%0], {%1,%2,%3,%4};" ::"r"(sb + OFF_X + 16384 + (j >> 2) * 16384 + cw * 2048 + (j & 3) * 512 + lane * 16), "f"(fmaf(bf_lo(x0), r0, bl)),
                         "f"(fmaf(bf_hi(x0), r0, bh)), "f"(fmaf(bf_lo(x1), r1, bl)), "f"(fmaf(bf_hi(x1), r1, bh)) : "memory");
          }
        }
        mbar_arrive(sb + OFF_LBAR);
        if (t == 0) TS(3, 5);
      } else {
        if (lane == 0) TG(2);
        const uint4* gwp = reinterpret_cast<const uint4*>(gate_w) + (lane & 7);
        uint4 gw[4];
#pragma unroll
        for (int i = 0; i < 4; i++) gw[i] = __ldg(gwp + i * 8);
        unsigned par;
        asm volatile("ld.relaxed.gpu.global.u32 %0, [%1];" : "=r"(par) : "l"(g_epoch + b) : "memory");
        const uint32_t dk = __ldg(reinterpret_cast<const uint32_t*>(dskip + s * 64) + lane), bb = __ldg(reinterpret_cast<const uint32_t*>(b2 + s * 64) + lane);
        asm volatile("barrier.cluster.wait.aligned;" ::: "memory");
        const int row = s * 16 + (lane >> 3);
        const uint32_t xr0 = sb + OFF_X + row * 128 + (((lane & 7) ^ (row & 7)) << 4), xr1 = (xr0 + 512) ^ 64;
        float z[4] = {0.f, 0.f, 0.f, 0.f};
#pragma unroll
        for (int kb = 0; kb < 8; kb++) {
          const uint32_t wv[4] = {gw[kb & 3].x, gw[kb & 3].y, gw[kb & 3].z, gw[kb & 3].w};
          if (kb < 4) gw[kb] = __ldg(gwp + (kb + 4) * 8);
          mbar_wait(sb + OFF_XFULL + 8 * kb, 0);
          if ((PF & 2) && kb == PFK && elect_one()) {
            l2_prefetch(pf_w1 + b * 7168, 14336);
            l2_prefetch(pf_cre + b * 2048, 4096);
            l2_prefetch(pf_cim + b * 2048, 4096);
            l2_prefetch(pf_w2 + b * 7168, 14336);
          }
          const uint32_t xo = ((kb + xrot) & 7) * 16384;
#pragma unroll
          for (int r = 0; r < 4; r++) {
            const uint4 a = lds_u4(((r & 1) ? xr1 : xr0) + xo + (r >> 1) * 1024);
            const uint32_t p = bf2_fma(a.w, wv[3], bf2_fma(a.z, wv[2], bf2_fma(a.y, wv[1], bf2_mul(a.x, wv[0]))));
            z[r] += bf_lo(p); z[r] += bf_hi(p);
          }
        }
        if (lane == 0) asm volatile("st.shared.u32 [%0], %1;" ::"r"(sb + OFF_EPOCH), "r"(par + 1) : "memory");
        par = (par + 1) & 1;
        {
          float y0 = (lane & 4) ? z[1] : z[0], y1 = (lane & 4) ? z[3] : z[2];
          y0 += __shfl_xor_sync(0xffffffffu, (lane & 4) ? z[0] : z[1], 4);
          y1 += __shfl_xor_sync(0xffffffffu, (lane & 4) ? z[2] : z[3], 4);
          float zz = (lane & 2) ? y1 : y0;
          zz += __shfl_xor_sync(0xffffffffu, (lane & 2) ? y0 : y1, 2);
          zz += __shfl_xor_sync(0xffffffffu, zz, 1);
          const float rho = 4.f * expf(zz > 40.f ? 40.f : zz);
          if ((lane & 1) == 0)
            asm volatile("st.relaxed.gpu.global.u32 [%0], %1;" ::"l"(g_gate + m * 128 + row + (lane & 4) + (lane & 2) * 4), "r"((__float_as_uint(rho) & ~1u) | par) : "memory");
        }
        if ((PF & 8) && elect_one()) {
          l2_prefetch(pf_w2 + b * 7168, 14336);
          l2_prefetch(pf_cre + b * 2048, 4096);
          l2_prefetch(pf_cim + b * 2048, 4096);
        }
        if (lane == 0) TS(3, 0);
        mbar_wait(sb + OFF_GBAR, 0);
        asm volatile("st.shared.v2.u32 [%0], {%1,%2};" ::"r"(sb + OFF_DB + lane * 8), "r"(dk), "r"(bf2_add(bb, bb)) : "memory");
        uint32_t g0, g1, g2, g3;
        int tries = 0;
#pragma unroll 1
        do {
          asm volatile("ld.relaxed.gpu.global.v4.u32 {%0,%1,%2,%3}, [%4];" : "=r"(g0), "=r"(g1), "=r"(g2), "=r"(g3) : "l"(g_gate + m * 128 + lane * 4) : "memory");
        } while ((((g0 ^ par) | (g1 ^ par) | (g2 ^ par) | (g3 ^ par)) & 1) && ++tries < 200000);
        asm volatile("st.shared.v2.u32 [%0], {%1,%2};" ::"r"(sb + OFF_GS + lane * 8), "r"(pack_bf16(__uint_as_float(g0), __uint_as_float(g1))),
                     "r"(pack_bf16(__uint_as_float(g2), __uint_as_float(g3))) : "memory");
        mbar_arrive(sb + OFF_CBAR);
        if (lane == 0) TS(3, 4);
      }
    } else {
      asm volatile("barrier.cluster.wait.aligned;" ::: "memory");
      if (elect_one()) {
        TS(2, 1);
        const uint32_t t0 = clock();
#pragma unroll 1
        for (int u = W0; u < 8; u++) {
          if (u > W0) while ((uint32_t)clock() - t0 < D0 + (u - 1 - W0) * D1) {}
          mbar_expect_tx(sb + OFF_XFULL + 8 * u, 16384);
          tma5d_mc(sb + OFF_X + ((u + xrot) & 7) * 16384 + rank * 8192, &maps.x, u * 64, 2 * m + rank, sb + OFF_XFULL + 8 * u);
          if (u < 6) {
            mbar_expect_tx(sb + OFF_FULL + 8 * u, 16384);
            tma2d(sb + OFF_RING + u * 16384, &maps.bre, u * 64, s * 64, sb + OFF_FULL + 8 * u);
            tma2d(sb + OFF_RING + u * 16384 + 8192, &maps.bim, u * 64, s * 64, sb + OFF_FULL + 8 * u);
          } else if (PF & 4) {
            asm volatile("cp.async.bulk.prefetch.tensor.2d.L2.global [%0, {%1,%2}];" ::"l"((m & 1) ? &maps.bim : &maps.bre), "r"(u * 64), "r"(s * 64) : "memory");
          }
        }
        TS(2, 5);
        int slot = 0; uint32_t ph = 0;
#pragma unroll 1
        for (int u = 6; u < 24; u++) {
          const uint32_t fb = sb + OFF_FULL + 8 * slot, dst = sb + OFF_RING + slot * 16384;
          mbar_wait(sb + OFF_EMPTY + 8 * slot, ph);
          TS2(0, u);
          if (u < 8) {
            mbar_expect_tx(fb, 16384);
            tma2d(dst, &maps.bre, u * 64, s * 64, fb);
            tma2d(dst + 8192, &maps.bim, u * 64, s * 64, fb);
          } else if (u < 16) {
            mbar_expect_tx(fb, 12288);
            tma3d(dst, &maps.w1b, 0, (u - 8) * 64, s * 7, fb);
          } else {
            mbar_expect_tx(fb, 16384);
            tma2d(dst, &maps.w1a, s * 224 + 96, ((u - xrot) & 7) * 64, fb);
            tma2d(dst + 8192, &maps.w1a, s * 224 + 160, ((u - xrot) & 7) * 64, fb);
          }
          if (++slot == NSLOT) { slot = 0; ph ^= 1; }
        }
#pragma unroll 1
        for (int j = 0; j < 3; j++) {
          const uint32_t fb = sb + OFF_FULL + 8 * j, dst = sb + OFF_X + stage_off(0);
          const int c = ((sp + 1) & 3) * 128 + ((rank ^ 1) << 6);
          mbar_wait(sb + OFF_EMPTY + 8 + 8 * j, 1);
          mbar_expect_tx(fb, j == 1 ? 16384 : 14336);
          if (j == 1) {
            tma2d(dst + 14336, &maps.cre, s * 64, c, fb);
            tma2d(dst + 22528, &maps.cim, s * 64, c, fb);
          } else {
            tma2d(dst + j * 15360, &maps.w2, c, s * 224 + j * 56, fb);
          }
        }
#pragma unroll 1
        for (int p = 1; p < 8; p++) {
          const int c = ((sp + 1 + (p >> 1)) & 3) * 128 + (((rank ^ p ^ 1) & 1) << 6);
          const uint32_t fb = sb + OFF_XFULL + 8 * p, dst = sb + OFF_X + stage_off(p);
          if (p == 2 || p > 3) mbar_wait(sb + OFF_EMPTY + (p == 2 ? 40 : (p - 4) * 8), p == 2);
          TS2(0, 32 + p);
          mbar_expect_tx(fb, 45056);
          tma2d(dst, &maps.w2, c, s * 224, fb);
          tma2d(dst + 14336, &maps.cre, s * 64, c, fb);
          tma2d(dst + 22528, &maps.cim, s * 64, c, fb);
          tma2d(dst + 30720, &maps.w2, c, s * 224 + 112, fb);
        }
        TS(2, 2);
      }
    }
  }
}

typedef CUresult (*EncFn)(CUtensorMap*, CUtensorMapDataType, cuuint32_t, void*, const cuuint64_t*, const cuuint64_t*, const cuuint32_t*,
                          const cuuint32_t*, CUtensorMapInterleave, CUtensorMapSwizzle, CUtensorMapL2promotion, CUtensorMapFloatOOBfill);

void encode(EncFn f, CUtensorMap* mp, const void* p, int rank, const cuuint64_t* dims, const cuuint64_t* strides, const cuuint32_t* box, CUtensorMapSwizzle sw) {
  cuuint32_t es[5] = {1, 1, 1, 1, 1};
  f(mp, CU_TENSOR_MAP_DATA_TYPE_BFLOAT16, rank, const_cast<void*>(p), dims, strides, box, es, CU_TENSOR_MAP_INTERLEAVE_NONE, sw,
    CU_TENSOR_MAP_L2_PROMOTION_L2_128B, CU_TENSOR_MAP_FLOAT_OOB_FILL_NONE);
}

}

extern "C" void kernel_launch(void* const* d_in, const int* in_sizes, int n_in, void* d_out, int out_size) {
  typedef const __nv_bfloat16* bp;
  bp x = (bp)d_in[0], lre = (bp)d_in[1], lim = (bp)d_in[2], bre = (bp)d_in[3], bim = (bp)d_in[4], cre = (bp)d_in[5], cim = (bp)d_in[6],
     ldt = (bp)d_in[7], dsk = (bp)d_in[8], w1 = (bp)d_in[10], b1 = (bp)d_in[11], w2 = (bp)d_in[12], b2 = (bp)d_in[13], gw = (bp)d_in[14];
  static EncFn enc = nullptr;
  if (!enc) {
    void* f = nullptr;
    cudaDriverEntryPointQueryResult qr;
    cudaGetDriverEntryPoint("cuTensorMapEncodeTiled", &f, cudaEnableDefault, &qr);
    enc = (EncFn)f;
    cudaFuncSetAttribute(fused_kernel, cudaFuncAttributeMaxDynamicSharedMemorySize, SMEM_BYTES);
  }
  Maps maps;
  {
    cuuint64_t d[5] = {DM, 2, 4, 8, SEQ / 64}, st[4] = {DM * 2, 16 * DM * 2, 2 * DM * 2, 64 * DM * 2};
    cuuint32_t bx[5] = {64, 2, 4, 8, 1};
    encode(enc, &maps.x, x, 5, d, st, bx, CU_TENSOR_MAP_SWIZZLE_128B);
  }
  {
    cuuint64_t d[2] = {DM, DM}, st[1] = {DM * 2};
    cuuint32_t bx[2] = {64, 64};
    encode(enc, &maps.bre, bre, 2, d, st, bx, CU_TENSOR_MAP_SWIZZLE_128B);
    encode(enc, &maps.bim, bim, 2, d, st, bx, CU_TENSOR_MAP_SWIZZLE_128B);
    encode(enc, &maps.cre, cre, 2, d, st, bx, CU_TENSOR_MAP_SWIZZLE_128B);
    encode(enc, &maps.cim, cim, 2, d, st, bx, CU_TENSOR_MAP_SWIZZLE_128B);
  }
  {
    cuuint64_t d[2] = {FF, DM}, st[1] = {FF * 2};
    cuuint32_t bx[2] = {64, 64};
    encode(enc, &maps.w1a, w1, 2, d, st, bx, CU_TENSOR_MAP_SWIZZLE_128B);
    cuuint64_t d3[3] = {32, DM, FF / 32}, st3[2] = {FF * 2, 64};
    cuuint32_t bx3[3] = {32, 64, 3};
    encode(enc, &maps.w1b, w1, 3, d3, st3, bx3, CU_TENSOR_MAP_SWIZZLE_64B);
  }
  {
    cuuint64_t d[2] = {DM, FF}, st[1] = {DM * 2};
    cuuint32_t bx[2] = {64, 112};
    encode(enc, &maps.w2, w2, 2, d, st, bx, CU_TENSOR_MAP_SWIZZLE_128B);
  }
  fused_kernel<<<128, 384, SMEM_BYTES>>>(x, bre, bim, lre, lim, ldt, dsk, b1, b2, gw, w1, w2, cre, cim, (float*)d_out, maps);
}
```

```cpp
#include <cuda_runtime.h>
#include <cuda_bf16.h>
#include <cuda.h>
#include <stdint.h>

#define MAP 1
#define D0 250
#define D1 500
#define PF 4
#define PFK 5
#define GELUP 1
#define EW 2
#define K1E 1
#define K2E 0
#define QS 1
#define K2G 4
#define FINP 4
#define LBD 300
#define PFS 32
#define SB0 2
#define PFD 2
#define HOLD 0
#define GAP 14
#define FINW 0
#define K0P 33
#define K1P 53
#define TMP2 1
#define W0 1
#define LCK 4
#define GC 0
#define GCUT {0, 8, 8, 16, 24, 32, 32, 32, 32}
#define SC0 4
#define TP 9
#define TW 0

namespace {

constexpr int SEQ = 2048, DM = 512, FF = 1792;
constexpr int NSLOT = 6;
constexpr uint32_t OFF_X = 0, OFF_RING = 131072, OFF_MISC = 229376;
constexpr uint32_t OFF_XFULL = OFF_MISC, OFF_FULL = OFF_XFULL + 64, OFF_RBAR = OFF_FULL + 48, OFF_EMPTY = OFF_RBAR + 16, OFF_KBAR = OFF_EMPTY + 48,
                   OFF_GBAR = OFF_KBAR + 16, OFF_LBAR = OFF_GBAR + 8, OFF_CBAR = OFF_LBAR + 8, OFF_EPOCH = OFF_CBAR + 8;
constexpr uint32_t OFF_LC = OFF_MISC + 256;
constexpr uint32_t OFF_GS = OFF_LC;
constexpr uint32_t OFF_DB = OFF_LC + 512;
constexpr uint32_t OFF_CARRY = OFF_LC + 1024;
constexpr uint32_t OFF_DBG = OFF_CARRY + 1024;
constexpr uint32_t SMEM_BYTES = OFF_DBG + 768;
static_assert(SMEM_BYTES <= 232448, "smem");

struct Maps { CUtensorMap x, bre, bim, w1a, w1b, w2, cre, cim; };
__host__ __device__ constexpr uint32_t stage_off(int p) { return 49152 + 45056 * (((p >> 1) & 1) + 2 * (p & 1)); }

__device__ uint4 g_part[16 * 8 * 3 * 1024];
__device__ float2 g_end[8 * 16 * 64];
__device__ unsigned g_gate[SEQ];
__device__ unsigned g_epoch[128];
#define TG(role) do {} while (0)
#define TS2(role, i) do {} while (0)
#define TS(role, i) do {} while (0)
#define TDUMP() do {} while (0)
#define TR(i) do {} while (0)
#define TRD() do {} while (0)

__device__ __forceinline__ void mbar_init(uint32_t bar, uint32_t cnt) { asm volatile("mbarrier.init.shared::cta.b64 [%0], %1;" ::"r"(bar), "r"(cnt)); }
__device__ __forceinline__ void mbar_expect_tx(uint32_t bar, uint32_t bytes) { asm volatile("mbarrier.arrive.expect_tx.shared::cta.b64 _, [%0], %1;" ::"r"(bar), "r"(bytes) : "memory"); }
__device__ __forceinline__ void mbar_arrive(uint32_t bar) { asm volatile("mbarrier.arrive.shared::cta.b64 _, [%0];" ::"r"(bar) : "memory"); }
__device__ __forceinline__ void mbar_arrive_cl(uint32_t cbar) { asm volatile("mbarrier.arrive.shared::cluster.b64 _, [%0];" ::"r"(cbar) : "memory"); }
__device__ __forceinline__ void mbar_wait(uint32_t bar, uint32_t parity) {
  asm volatile(
      "{\n.reg .pred p;\n.reg .u32 c;\n"
      "mbarrier.try_wait.parity.shared::cta.b64 p, [%0], %1;\n"
      "@p bra.uni LAB_DONE;\n"
      "mov.u32 c, 0;\n"
      "LAB_WAIT:\n"
      "mbarrier.try_wait.parity.shared::cta.b64 p, [%0], %1;\n"
      "@p bra.uni LAB_DONE;\n"
      "add.u32 c, c, 1;\nsetp.lt.u32 p, c, 200000;\n@p bra.uni LAB_WAIT;\n"
      "LAB_DONE:\n}" ::"r"(bar), "r"(parity) : "memory");
}
__device__ __forceinline__ void tma2d(uint32_t dst, const CUtensorMap* m, int c0, int c1, uint32_t bar) {
  asm volatile("cp.async.bulk.tensor.2d.shared::cluster.global.mbarrier::complete_tx::bytes [%0], [%1, {%3,%4}], [%2];"
               ::"r"(dst), "l"(m), "r"(bar), "r"(c0), "r"(c1) : "memory");
}
__device__ __forceinline__ void tma3d(uint32_t dst, const CUtensorMap* m, int c0, int c1, int c2, uint32_t bar) {
  asm volatile("cp.async.bulk.tensor.3d.shared::cluster.global.mbarrier::complete_tx::bytes [%0], [%1, {%3,%4,%5}], [%2];"
               ::"r"(dst), "l"(m), "r"(bar), "r"(c0), "r"(c1), "r"(c2) : "memory");
}
__device__ __forceinline__ void tma5d(uint32_t dst, const CUtensorMap* m, int c0, int c4, uint32_t bar) {
  asm volatile("cp.async.bulk.tensor.5d.shared::cluster.global.mbarrier::complete_tx::bytes [%0], [%1, {%3,%5,%5,%5,%4}], [%2];"
               ::"r"(dst), "l"(m), "r"(bar), "r"(c0), "r"(c4), "r"(0) : "memory");
}
__device__ __forceinline__ void tma5d_mc(uint32_t dst, const CUtensorMap* m, int c0, int c4, uint32_t bar) {
  asm volatile("cp.async.bulk.tensor.5d.shared::cluster.global.mbarrier::complete_tx::bytes.multicast::cluster [%0], [%1, {%3,%5,%5,%5,%4}], [%2], %6;"
               ::"r"(dst), "l"(m), "r"(bar), "r"(c0), "r"(c4), "r"(0), "h"((uint16_t)3) : "memory");
}
__device__ __forceinline__ void l2_prefetch(const void* p, uint32_t bytes) { asm volatile("cp.async.bulk.prefetch.L2.global [%0], %1;" ::"l"(p), "r"(bytes) : "memory"); }
__device__ __forceinline__ bool elect_one() {
  uint32_t pred;
  asm volatile("{.reg .pred P; elect.sync _|P, 0xffffffff; selp.u32 %0, 1, 0, P;}" : "=r"(pred));
  return pred != 0;
}
__device__ __forceinline__ void wg_fence() { asm volatile("wgmma.fence.sync.aligned;" ::: "memory"); }
__device__ __forceinline__ void wg_commit() { asm volatile("wgmma.commit_group.sync.aligned;" ::: "memory"); }
template <int N> __device__ __forceinline__ void wg_wait() { asm volatile("wgmma.wait_group.sync.aligned %0;" ::"n"(N) : "memory"); }
__device__ __forceinline__ void pin(float& a) { asm volatile("" : "+f"(a)::"memory"); }
__device__ __forceinline__ void pin(uint32_t& a) { asm volatile("" : "+r"(a)::"memory"); }
template <int N> __device__ __forceinline__ void reg_fence(float (&d)[N]) {
#pragma unroll
  for (int i = 0; i < N; i++) pin(d[i]);
}
__device__ __forceinline__ void bar_sync(int id, int n) { asm volatile("bar.sync %0, %1;" ::"r"(id), "r"(n) : "memory"); }
__device__ __forceinline__ void bar_arrive(int id, int n) { asm volatile("bar.arrive %0, %1;" ::"r"(id), "r"(n) : "memory"); }
constexpr uint32_t DH128 = (1024 >> 4) | (1u << 30), DH64 = (512 >> 4) | (2u << 30);
__host__ __device__ constexpr uint32_t lbo(uint32_t bytes) { return (bytes >> 4) << 20; }
__device__ __forceinline__ uint32_t pack_bf16(float lo, float hi) { uint32_t r; asm("cvt.rn.bf16x2.f32 %0, %1, %2;" : "=r"(r) : "f"(hi), "f"(lo)); return r; }
__device__ __forceinline__ float bf_lo(uint32_t v) { return __uint_as_float(v << 16); }
__device__ __forceinline__ float bf_hi(uint32_t v) { return __uint_as_float(v & 0xffff0000u); }
__device__ __forceinline__ float bf_ld(const __nv_bfloat16* p) { return __bfloat162float(__ldg(p)); }
__device__ __forceinline__ uint32_t late16(uint32_t bar) {
  uint32_t r;
  asm volatile("{.reg .pred p; mbarrier.test_wait.parity.shared::cta.b64 p, [%1], 0; selp.u32 %0, 16, 0, p;}" : "=r"(r) : "r"(bar) : "memory");
  return r;
}
__device__ __forceinline__ float2 lds_f2(uint32_t a) { float2 v; asm volatile("ld.shared.v2.f32 {%0,%1}, [%2];" : "=f"(v.x), "=f"(v.y) : "r"(a)); return v; }
__device__ __forceinline__ uint32_t lds_h(uint32_t a) { uint32_t v; asm volatile("ld.shared.u16 %0, [%1];" : "=r"(v) : "r"(a)); return v; }
__device__ __forceinline__ uint32_t lds_u(uint32_t a) { uint32_t v; asm volatile("ld.shared.u32 %0, [%1];" : "=r"(v) : "r"(a)); return v; }
__device__ __forceinline__ uint4 lds_u4(uint32_t a) { uint4 v; asm volatile("ld.shared.v4.u32 {%0,%1,%2,%3}, [%4];" : "=r"(v.x), "=r"(v.y), "=r"(v.z), "=r"(v.w) : "r"(a)); return v; }
__device__ __forceinline__ void st_b128(uint4* p, uint32_t a, uint32_t b, uint32_t c, uint32_t d) {
  asm volatile("st.relaxed.gpu.global.v4.b32 [%0], {%1,%2,%3,%4};" ::"l"(p), "r"(a), "r"(b), "r"(c), "r"(d) : "memory");
}
__device__ __forceinline__ void ld_b128(const uint4* p, uint32_t& a, uint32_t& b, uint32_t& c, uint32_t& d) {
  asm volatile("{.reg .b64 l, h; .reg .b128 v; ld.relaxed.gpu.global.b128 v, [%4]; mov.b128 {l,h}, v; mov.b64 {%0,%1}, l; mov.b64 {%2,%3}, h;}"
               : "=r"(a), "=r"(b), "=r"(c), "=r"(d) : "l"(p) : "memory");
}
__device__ __forceinline__ float tanh_fast(float x) { float y; asm("tanh.approx.f32 %0, %1;" : "=f"(y) : "f"(x)); return y; }
__device__ __forceinline__ float gelu2(float v) {
  float p = fmaf(v * v, 0.0356774081363f, 0.7978845608029f);
  return fmaf(v, tanh_fast(v * p), v);
}
__device__ __forceinline__ uint32_t bf2_mul(uint32_t a, uint32_t b) { uint32_t r; asm("mul.rn.bf16x2 %0, %1, %2;" : "=r"(r) : "r"(a), "r"(b)); return r; }
__device__ __forceinline__ uint32_t bf2_add(uint32_t a, uint32_t b) { uint32_t r; asm("add.rn.bf16x2 %0, %1, %2;" : "=r"(r) : "r"(a), "r"(b)); return r; }
__device__ __forceinline__ uint32_t bf2_fma(uint32_t a, uint32_t b, uint32_t c) { uint32_t r; asm("fma.rn.bf16x2 %0, %1, %2, %3;" : "=r"(r) : "r"(a), "r"(b), "r"(c)); return r; }
__device__ __forceinline__ uint32_t gelu2_pair(float a, float b) {
  const uint32_t v = pack_bf16(a, b);
  uint32_t t;
  asm("tanh.approx.bf16x2 %0, %1;" : "=r"(t) : "r"(bf2_fma(v, bf2_fma(bf2_mul(v, v), 0x3d123d12u, 0xbe4fbe4fu), v)));
  return bf2_fma(v, t, v);
}
struct cplx { float re, im; };
__device__ __forceinline__ cplx cmul(cplx a, cplx b) { return {fmaf(a.re, b.re, -a.im * b.im), fmaf(a.re, b.im, a.im * b.re)}; }
__device__ __forceinline__ cplx cfma(cplx a, cplx b, cplx c) {
  return {fmaf(a.re, b.re, fmaf(-a.im, b.im, c.re)), fmaf(a.re, b.im, fmaf(a.im, b.re, c.im))};
}
__device__ __forceinline__ cplx make_lam(float lre, float lim, float ldt) {
  float dt = __bfloat162float(__float2bfloat16_rn(expf(ldt)));
  float mag = expf(dt * lre), sn, cs;
  sincospif(dt * lim * 0.31830988618379067f, &sn, &cs);
  return {mag * cs, mag * sn};
}

template<int TA,int TB,uint32_t AH,uint32_t BH> __device__ __forceinline__ void wgmma_n64_ss(float (&d)[32], uint32_t al, uint32_t ao, uint32_t bl, uint32_t bo, int scale_d){
  asm volatile("{.reg .pred p; .reg .b32 t, v; .reg .b64 da, db; setp.ne.b32 p, %36, 0; add.u32 t, %32, %33; mov.b64 da, {t, %39}; add.u32 v, %34, %35; mov.b64 db, {v, %40};\n"
   "wgmma.mma_async.sync.aligned.m64n64k16.f32.bf16.bf16 {%0,%1,%2,%3,%4,%5,%6,%7,%8,%9,%10,%11,%12,%13,%14,%15,%16,%17,%18,%19,%20,%21,%22,%23,%24,%25,%26,%27,%28,%29,%30,%31}, da, db, p, 1, 1, %37, %38;}"
   : "+f"(d[0]),"+f"(d[1]),"+f"(d[2]),"+f"(d[3]),"+f"(d[4]),"+f"(d[5]),"+f"(d[6]),"+f"(d[7]),"+f"(d[8]),"+f"(d[9]),"+f"(d[10]),"+f"(d[11]),"+f"(d[12]),"+f"(d[13]),"+f"(d[14]),"+f"(d[15]),"+f"(d[16]),"+f"(d[17]),"+f"(d[18]),"+f"(d[19]),"+f"(d[20]),"+f"(d[21]),"+f"(d[22]),"+f"(d[23]),"+f"(d[24]),"+f"(d[25]),"+f"(d[26]),"+f"(d[27]),"+f"(d[28]),"+f"(d[29]),"+f"(d[30]),"+f"(d[31])
   : "r"(al),"r"(ao >> 4),"r"(bl),"r"(bo >> 4),"r"(scale_d),"n"(TA),"n"(TB),"n"(AH),"n"(BH));
}
template<int TB,uint32_t BH> __device__ __forceinline__ void wgmma_n64_rs(float (&d)[32], uint32_t a0,uint32_t a1,uint32_t a2,uint32_t a3, uint32_t bl, uint32_t bo, int scale_d){
  asm volatile("{.reg .pred p; .reg .b32 t; .reg .b64 db; setp.ne.b32 p, %38, 0; add.u32 t, %36, %37; mov.b64 db, {t, %40};\n"
   "wgmma.mma_async.sync.aligned.m64n64k16.f32.bf16.bf16 {%0,%1,%2,%3,%4,%5,%6,%7,%8,%9,%10,%11,%12,%13,%14,%15,%16,%17,%18,%19,%20,%21,%22,%23,%24,%25,%26,%27,%28,%29,%30,%31}, {%32,%33,%34,%35}, db, p, 1, 1, %39;}"
   : "+f"(d[0]),"+f"(d[1]),"+f"(d[2]),"+f"(d[3]),"+f"(d[4]),"+f"(d[5]),"+f"(d[6]),"+f"(d[7]),"+f"(d[8]),"+f"(d[9]),"+f"(d[10]),"+f"(d[11]),"+f"(d[12]),"+f"(d[13]),"+f"(d[14]),"+f"(d[15]),"+f"(d[16]),"+f"(d[17]),"+f"(d[18]),"+f"(d[19]),"+f"(d[20]),"+f"(d[21]),"+f"(d[22]),"+f"(d[23]),"+f"(d[24]),"+f"(d[25]),"+f"(d[26]),"+f"(d[27]),"+f"(d[28]),"+f"(d[29]),"+f"(d[30]),"+f"(d[31])
   : "r"(a0),"r"(a1),"r"(a2),"r"(a3),"r"(bl),"r"(bo >> 4),"r"(scale_d),"n"(TB),"n"(BH));
}
template<int TA,int TB,uint32_t AH,uint32_t BH> __device__ __forceinline__ void wgmma_n96_ss(float (&d)[48], uint32_t al, uint32_t ao, uint32_t bl, uint32_t bo, int scale_d){
  asm volatile("{.reg .pred p; .reg .b32 t, v; .reg .b64 da, db; setp.ne.b32 p, %52, 0; add.u32 t, %48, %49; mov.b64 da, {t, %55}; add.u32 v, %50, %51; mov.b64 db, {v, %56};\n"
   "wgmma.mma_async.sync.aligned.m64n96k16.f32.bf16.bf16 {%0,%1,%2,%3,%4,%5,%6,%7,%8,%9,%10,%11,%12,%13,%14,%15,%16,%17,%18,%19,%20,%21,%22,%23,%24,%25,%26,%27,%28,%29,%30,%31,%32,%33,%34,%35,%36,%37,%38,%39,%40,%41,%42,%43,%44,%45,%46,%47}, da, db, p, 1, 1, %53, %54;}"
   : "+f"(d[0]),"+f"(d[1]),"+f"(d[2]),"+f"(d[3]),"+f"(d[4]),"+f"(d[5]),"+f"(d[6]),"+f"(d[7]),"+f"(d[8]),"+f"(d[9]),"+f"(d[10]),"+f"(d[11]),"+f"(d[12]),"+f"(d[13]),"+f"(d[14]),"+f"(d[15]),"+f"(d[16]),"+f"(d[17]),"+f"(d[18]),"+f"(d[19]),"+f"(d[20]),"+f"(d[21]),"+f"(d[22]),"+f"(d[23]),"+f"(d[24]),"+f"(d[25]),"+f"(d[26]),"+f"(d[27]),"+f"(d[28]),"+f"(d[29]),"+f"(d[30]),"+f"(d[31]),"+f"(d[32]),"+f"(d[33]),"+f"(d[34]),"+f"(d[35]),"+f"(d[36]),"+f"(d[37]),"+f"(d[38]),"+f"(d[39]),"+f"(d[40]),"+f"(d[41]),"+f"(d[42]),"+f"(d[43]),"+f"(d[44]),"+f"(d[45]),"+f"(d[46]),"+f"(d[47])
   : "r"(al),"r"(ao >> 4),"r"(bl),"r"(bo >> 4),"r"(scale_d),"n"(TA),"n"(TB),"n"(AH),"n"(BH));
}
template<int TA,int TB,uint32_t AH,uint32_t BH> __device__ __forceinline__ void wgmma_n128_ss(float (&d)[64], uint32_t al, uint32_t ao, uint32_t bl, uint32_t bo, int scale_d){
  asm volatile("{.reg .pred p; .reg .b32 t, v; .reg .b64 da, db; setp.ne.b32 p, %68, 0; add.u32 t, %64, %65; mov.b64 da, {t, %71}; add.u32 v, %66, %67; mov.b64 db, {v, %72};\n"
   "wgmma.mma_async.sync.aligned.m64n128k16.f32.bf16.bf16 {%0,%1,%2,%3,%4,%5,%6,%7,%8,%9,%10,%11,%12,%13,%14,%15,%16,%17,%18,%19,%20,%21,%22,%23,%24,%25,%26,%27,%28,%29,%30,%31,%32,%33,%34,%35,%36,%37,%38,%39,%40,%41,%42,%43,%44,%45,%46,%47,%48,%49,%50,%51,%52,%53,%54,%55,%56,%57,%58,%59,%60,%61,%62,%63}, da, db, p, 1, 1, %69, %70;}"
   : "+f"(d[0]),"+f"(d[1]),"+f"(d[2]),"+f"(d[3]),"+f"(d[4]),"+f"(d[5]),"+f"(d[6]),"+f"(d[7]),"+f"(d[8]),"+f"(d[9]),"+f"(d[10]),"+f"(d[11]),"+f"(d[12]),"+f"(d[13]),"+f"(d[14]),"+f"(d[15]),"+f"(d[16]),"+f"(d[17]),"+f"(d[18]),"+f"(d[19]),"+f"(d[20]),"+f"(d[21]),"+f"(d[22]),"+f"(d[23]),"+f"(d[24]),"+f"(d[25]),"+f"(d[26]),"+f"(d[27]),"+f"(d[28]),"+f"(d[29]),"+f"(d[30]),"+f"(d[31]),"+f"(d[32]),"+f"(d[33]),"+f"(d[34]),"+f"(d[35]),"+f"(d[36]),"+f"(d[37]),"+f"(d[38]),"+f"(d[39]),"+f"(d[40]),"+f"(d[41]),"+f"(d[42]),"+f"(d[43]),"+f"(d[44]),"+f"(d[45]),"+f"(d[46]),"+f"(d[47]),"+f"(d[48]),"+f"(d[49]),"+f"(d[50]),"+f"(d[51]),"+f"(d[52]),"+f"(d[53]),"+f"(d[54]),"+f"(d[55]),"+f"(d[56]),"+f"(d[57]),"+f"(d[58]),"+f"(d[59]),"+f"(d[60]),"+f"(d[61]),"+f"(d[62]),"+f"(d[63])
   : "r"(al),"r"(ao >> 4),"r"(bl),"r"(bo >> 4),"r"(scale_d),"n"(TA),"n"(TB),"n"(AH),"n"(BH));
}

__global__ void __cluster_dims__(2, 1, 1) __launch_bounds__(384, 1)
fused_kernel(const __nv_bfloat16* __restrict__ lam_re, const __nv_bfloat16* __restrict__ lam_im, const __nv_bfloat16* __restrict__ log_dt,
             const __nv_bfloat16* __restrict__ dskip, const __nv_bfloat16* __restrict__ b1, const __nv_bfloat16* __restrict__ b2,
             const __nv_bfloat16* __restrict__ gate_w, const __nv_bfloat16* __restrict__ pf_w1, const __nv_bfloat16* __restrict__ pf_w2,
             const __nv_bfloat16* __restrict__ pf_cre, const __nv_bfloat16* __restrict__ pf_cim, float* __restrict__ out,
             const __grid_constant__ Maps maps) {
  extern __shared__ __align__(1024) unsigned char smem_raw[];
  const uint32_t sb = (uint32_t)__cvta_generic_to_shared(smem_raw);
  const int b = blockIdx.x;
  const int rank = b & 1, cl = b >> 1;
  const int sp = (cl & 1) | ((cl >> 2) & 2), m = ((cl >> 1) & 3) | ((cl >> 4) << 2);
  const int s = sp * 2 + rank;
  const int warp = __shfl_sync(0xffffffffu, (int)(threadIdx.x >> 5), 0);
  const int lane = threadIdx.x & 31;
  const int xrot = 9 - 2 * sp;

  if (elect_one()) {
    if (warp == 8) TS(2, 0);
    if (warp > 8) {
      asm volatile("prefetch.tensormap [%0];" ::"l"(&maps.x + (warp - 9)) : "memory");
      mbar_init(sb + OFF_GBAR + 8 * (warp - 9), warp < 11 ? 64 : 96);
    }
    const uint32_t c = warp < 8 ? 1 : warp < 11 ? 8 : 4, bar = sb + OFF_XFULL + 16 * warp;
    mbar_init(bar, c);
    if ((warp & 11) == 0) {
      mbar_expect_tx(bar, 16384);
      if (warp == 0) {
        tma5d(sb + OFF_X + (xrot & 7) * 16384, &maps.x, 0, 2 * m, bar);
        tma5d(sb + OFF_X + (xrot & 7) * 16384 + 8192, &maps.x, 0, 2 * m + 1, bar);
        TS(2, 3);
      } else {
        tma2d(sb + OFF_RING, &maps.bre, 0, s * 64, bar);
        tma2d(sb + OFF_RING + 8192, &maps.bim, 0, s * 64, bar);
        TS(2, 4);
      }
    }
    mbar_init(bar + 8, c);
    asm volatile("fence.mbarrier_init.release.cluster;" ::: "memory");
  }
  __syncwarp();
  asm volatile("barrier.cluster.arrive.relaxed.aligned;" ::: "memory");

  if (warp < 8) {
    const int wg = warp >> 2, w = warp & 3, q = lane & 3, gr = lane >> 2;
    uint32_t bv[28];
#pragma unroll
    for (int j = 0; j < 28; j++) bv[j] = __ldg(reinterpret_cast<const uint32_t*>(b1 + s * 224 + j * 8) + q);
    asm volatile("setmaxnreg.inc.sync.aligned.u32 224;");
    asm volatile("barrier.cluster.wait.aligned;" ::: "memory");
    TS(wg, 0);
    auto release = [&](int slot) { if (lane == 0) mbar_arrive(sb + OFF_EMPTY + 8 * slot); };
    const uint32_t xw = sb + OFF_X + wg * 8192, fullb = sb + OFF_FULL;
    const uint32_t dxw = (xw & 0x3FFFF) >> 4, dring = ((sb + OFF_RING) & 0x3FFFF) >> 4;

    float ure[32], uim[32], aa[64], ab[48];
    cplx lam[2], coef[2], l16[2], l32[2], lq[2], pre[2], e[2];
    uint32_t sh16, mhi;

    auto bias = [&](int c) {
#pragma unroll
      for (int j = c * 7; j < c * 7 + 7; j++) {
        pin(bv[j]);
        float* d = j < 16 ? aa + 4 * j : ab + 4 * (j - 16);
        d[0] = d[2] = __uint_as_float(bv[j] << sh16); d[1] = d[3] = __uint_as_float(bv[j] & mhi);
        pin(d[0]); pin(d[1]); pin(d[2]); pin(d[3]);
      }
    };
#pragma unroll
    for (int kb = 0; kb < 8; kb++) {
      const int slot = kb % NSLOT;
      mbar_wait(sb + OFF_XFULL + 8 * kb, 0);
      if (kb == 0) TS(wg, 18);
      mbar_wait(fullb + 8 * slot, (kb / NSLOT) & 1);
      TS2(2, kb);
      if (kb == 0) TS(wg, 1);
      if (kb == SB0) { sh16 = late16(sb + OFF_XFULL); mhi = 0xffffffffu << sh16; }
      if (kb == LCK) {
        mbar_wait(sb + OFF_LBAR, 0);
#pragma unroll
        for (int h = 0; h < 2; h++) {
          const uint4 v = lds_u4(sb + OFF_LC + (w * 16 + gr + 8 * h) * 16);
          lam[h] = cplx{__uint_as_float(v.x), __uint_as_float(v.y)};
          coef[h] = cplx{__uint_as_float(v.z), __uint_as_float(v.w)};
        }
      }
      wg_fence();
      const uint32_t dxa = dxw + ((kb + xrot) & 7) * 1024;
#pragma unroll
      for (int kk = 0; kk < 4; kk++) {
        wgmma_n64_ss<0, 0, DH128, DH128>(ure, dring, slot * 16384 + kk * 32, dxa, kk * 32, (kb | kk) != 0);
        wgmma_n64_ss<0, 0, DH128, DH128>(uim, dring, slot * 16384 + 8192 + kk * 32, dxa, kk * 32, (kb | kk) != 0);
      }
      wg_commit();
      if (kb > 0) { wg_wait<1>(); release((kb - 1) % NSLOT); }
      if (kb >= SB0 && kb < SB0 + 3) bias(kb - SB0);
      if (kb == 6) {
#pragma unroll
        for (int h = 0; h < 2; h++) {
          pin(lam[h].re); pin(lam[h].im);
          cplx t = cmul(lam[h], lam[h]); t = cmul(t, t); t = cmul(t, t);
          l16[h] = cmul(t, t);
          pin(l16[h].re); pin(l16[h].im);
        }
      }
      if (kb == 7) {
#pragma unroll
        for (int h = 0; h < 2; h++) {
          pin(l16[h].re); pin(l16[h].im);
          l32[h] = cmul(l16[h], l16[h]);
          const cplx a = (q & 1) ? l16[h] : cplx{1.f, 0.f}, c = (q & 2) ? l32[h] : cplx{1.f, 0.f};
          lq[h] = cmul(cmul(a, c), coef[h]);
          pin(lq[h].re); pin(lq[h].im);
        }
      }
    }
    TS(wg, 2);
    auto scale_u = [&](int i0, int i1) {
#pragma unroll
      for (int i = 0; i < 32; i++) if (i >= i0 && i < i1) {
        pin(ure[i]); pin(uim[i]);
        const cplx v = cmul(coef[(i >> 1) & 1], cplx{ure[i], uim[i]});
        ure[i] = v.re; uim[i] = v.im;
        pin(ure[i]); pin(uim[i]);
      }
    };
#pragma unroll
    for (int kb = 0; kb < 8; kb++) {
      const int u = 8 + kb, slot = u % NSLOT;
      mbar_wait(fullb + 8 * slot, (u / NSLOT) & 1);
      wg_fence();
      const uint32_t dxa = dxw + ((kb + xrot) & 7) * 1024;
#pragma unroll
      for (int kk = 0; kk < 4; kk++)
        wgmma_n128_ss<0, 1, DH128, DH128>(aa, dxa, kk * 32, dring, slot * 16384 + kk * 2048 + lbo(8192), 1);
      wg_commit();
      if (SB0 >= 0 && kb == 0) bias(3);
      wg_wait<1>();
      release((u - 1) % NSLOT);
      if (kb == 0) {
        reg_fence(ure); reg_fence(uim);
#pragma unroll
        for (int h = 0; h < 2; h++) e[h] = cplx{ure[2 * h], uim[2 * h]};
      }
      if (kb == 0 || kb == 2) {
#pragma unroll
        for (int t = 1; t < 16; t++) if ((t < 8) == (kb == 0))
#pragma unroll
          for (int h = 0; h < 2; h++) { const int i = 4 * (t >> 1) + 2 * h + (t & 1); e[h] = cfma(lam[h], e[h], cplx{ure[i], uim[i]}); }
#pragma unroll
        for (int h = 0; h < 2; h++) { pin(e[h].re); pin(e[h].im); }
      } else if (kb == 3) {
#pragma unroll
        for (int h = 0; h < 2; h++) {
          cplx y = {__shfl_up_sync(0xffffffffu, e[h].re, 1, 4), __shfl_up_sync(0xffffffffu, e[h].im, 1, 4)};
          if (q >= 1) e[h] = cfma(l16[h], y, e[h]);
          y = cplx{__shfl_up_sync(0xffffffffu, e[h].re, 2, 4), __shfl_up_sync(0xffffffffu, e[h].im, 2, 4)};
          if (q >= 2) e[h] = cfma(l32[h], y, e[h]);
        }
        if (q == 3) {
#pragma unroll
          for (int h = 0; h < 2; h++)
            asm volatile("st.shared.v2.f32 [%0], {%1,%2};" ::"r"(sb + OFF_CARRY + wg * 512 + (w * 16 + gr + 8 * h) * 8), "f"(e[h].re), "f"(e[h].im) : "memory");
          mbar_arrive(sb + OFF_GBAR);
        }
#pragma unroll
        for (int h = 0; h < 2; h++) {
          const cplx y = {__shfl_up_sync(0xffffffffu, e[h].re, 1, 4), __shfl_up_sync(0xffffffffu, e[h].im, 1, 4)};
          pre[h] = (q >= 1) ? cmul(coef[h], y) : cplx{0.f, 0.f};
          pin(pre[h].re); pin(pre[h].im);
        }
        TS(wg, 3);
      } else if (kb > 3) {
        scale_u((kb - 4) * 8, (kb - 3) * 8);
      }
    }
    TS(wg, 4);
    uint32_t H[56], hf[32];
    cplx hst[2];
    const uint32_t hst_addr = xw + (w * 16 + (lane & 15)) * 128 + (((lane >> 4) ^ (lane & 7)) << 4);
    const uint32_t him = (2 - rank) * 16384;
    uint32_t peer;
    asm volatile("mapa.shared::cluster.u32 %0, %1, %2;" : "=r"(peer) : "r"(sb), "r"(rank ^ 1));
    auto credit = [&]() { if (lane == 0) mbar_arrive_cl(peer + OFF_KBAR + wg * 8); };
#pragma unroll
    for (int kb = 0; kb < 8; kb++) {
      const int u = 16 + kb, slot = u % NSLOT;
      mbar_wait(fullb + 8 * slot, (u / NSLOT) & 1);
      wg_fence();
#pragma unroll
      for (int kk = 0; kk < 4; kk++)
        wgmma_n96_ss<0, 1, DH128, DH64>(ab, dxw, kb * 16384 + kk * 32, dring, slot * 16384 + kk * 1024 + lbo(4096), 1);
      wg_commit();
      wg_wait<1>();
      release((u - 1) % NSLOT);
      if (kb != 1) {
        constexpr int cut[9] = GCUT;
#pragma unroll
        for (int i = 0; i < 32; i++) if (i >= cut[kb] && i < cut[kb + 1]) {
          pin(aa[2 * i]); pin(aa[2 * i + 1]);
          H[i] = gelu2_pair(aa[2 * i], aa[2 * i + 1]);
          pin(H[i]);
        }
      }
      if (kb >= SC0 && kb < SC0 + 4) {
        if (kb == SC0) {
          TS(wg, 5);
          mbar_wait(sb + OFF_CBAR, 0);
          TS(wg, 6);
#pragma unroll
          for (int h = 0; h < 2; h++) {
            const float2 c = lds_f2(sb + OFF_CARRY + wg * 512 + (w * 16 + gr + 8 * h) * 8);
            hst[h] = cfma(lq[h], cplx{c.x, c.y}, pre[h]);
          }
        }
        const int j0 = (kb - SC0) * 2;
        uint32_t rr[4], ri[4];
#pragma unroll
        for (int jj = 0; jj < 2; jj++) {
          const int j = j0 + jj;
          const uint32_t g2 = lds_u(sb + OFF_GS + (wg * 64 + j * 8 + q * 2) * 2);
#pragma unroll
          for (int h = 0; h < 2; h++) {
            const int i = 4 * j + 2 * h;
            const cplx h0 = cfma(lam[h], hst[h], cplx{ure[i], uim[i]});
            hst[h] = cfma(lam[h], h0, cplx{ure[i + 1], uim[i + 1]});
            rr[jj * 2 + h] = bf2_mul(pack_bf16(h0.re, hst[h].re), g2);
            ri[jj * 2 + h] = bf2_mul(pack_bf16(h0.im, hst[h].im), g2 ^ 0x80008000u);
          }
        }
        const uint32_t a = hst_addr ^ (j0 << 4);
        asm volatile("stmatrix.sync.aligned.m8n8.x4.shared.b16 [%0], {%1,%2,%3,%4};" ::"r"(a), "r"(rr[0]), "r"(rr[1]), "r"(rr[2]), "r"(rr[3]) : "memory");
        asm volatile("stmatrix.sync.aligned.m8n8.x4.shared.b16 [%0], {%1,%2,%3,%4};" ::"r"(a + him), "r"(ri[0]), "r"(ri[1]), "r"(ri[2]), "r"(ri[3]) : "memory");
      }
    }
    TS(wg, 7);

    uint4* const psend = g_part + (size_t)(m * 8 + rank) * 3072 + warp * 128 + lane;
    const uint4* const precv = g_part + (size_t)(m * 8 + s) * 3072 + warp * 128 + lane;
    const uint32_t pbuf = OFF_X + warp * 2048 + lane * 16;
    const uint32_t dx0 = ((sb + OFF_X) & 0x3FFFF) >> 4;
    float o[32], fin[32], rho[2];
    uint32_t tr[8];
    uint32_t r0[16], pt[16], sum[16], tag;
    auto recv_issue = [&](uint32_t (&r)[16], int k) {
#pragma unroll
      for (int i = 0; i < 4; i++) ld_b128(precv + k * 1024 + i * 32, r[4 * i], r[4 * i + 1], r[4 * i + 2], r[4 * i + 3]);
    };
    auto stale = [&](uint32_t (&r)[16]) {
      uint32_t t0, t1, r_;
      asm("lop3.b32 %0, %1, %2, %3, 0x7e;" : "=r"(t0) : "r"(r[0]), "r"(r[4]), "r"(tag));
      asm("lop3.b32 %0, %1, %2, %3, 0x7e;" : "=r"(t1) : "r"(r[8]), "r"(r[12]), "r"(tag));
      asm volatile("{.reg .pred p; .reg .b32 t; lop3.b32 t, %1, %2, 1, 0xa8; setp.ne.u32 p, t, 0; vote.sync.any.pred p, p, 0xffffffff; selp.u32 %0, 1, 0, p;}" : "=r"(r_) : "r"(t0), "r"(t1));
      return r_ != 0;
    };
    auto recv_check = [&](uint32_t (&r)[16], int k) {
      if (__builtin_expect(stale(r), 0)) {
        int tries = 0;
#pragma unroll 1
        do { recv_issue(r, k); } while (stale(r) && ++tries < 200000);
      }
    };
    auto gelu_b = [&](int i0, int i1) {
#pragma unroll
      for (int i = i0; i < i1; i++) {
        pin(ab[2 * i]); pin(ab[2 * i + 1]);
        H[32 + i] = gelu2_pair(ab[2 * i], ab[2 * i + 1]);
        pin(H[32 + i]);
      }
    };
    auto step = [&](float (&d)[32], int p, int k, int acc) {
      const uint32_t wo = stage_off(p);
      if (k >= 7 && k < 15) {
        const int kk = k - 7;
        wgmma_n64_rs<0, DH128>(d, hf[4 * kk], hf[4 * kk + 1], hf[4 * kk + 2], hf[4 * kk + 3], dx0, wo + 14336 + (kk >> 2) * 8192 + (kk & 3) * 32, 1);
      } else {
        const int kk = k < 7 ? k : k - 8;
        wgmma_n64_rs<1, DH128>(d, H[4 * kk], H[4 * kk + 1], H[4 * kk + 2], H[4 * kk + 3], dx0, wo + (kk / 7) * 30720 + (kk % 7) * 2048, k != 0 || acc);
      }
    };
    auto mma = [&](float (&d)[32], int p, int k0, int k1, int acc) {
      wg_fence();
#pragma unroll
      for (int k = k0; k < k1; k++) step(d, p, k, acc);
      wg_commit();
    };
    auto send_peer = [&]() {
#pragma unroll
      for (int i = 0; i < 4; i++)
        asm volatile("st.async.shared::cluster.mbarrier::complete_tx::bytes.v4.b32 [%0], {%1,%2,%3,%4}, [%5];" ::"r"(peer + pbuf + i * 512),
                     "r"(pack_bf16(o[8 * i], o[8 * i + 1])), "r"(pack_bf16(o[8 * i + 2], o[8 * i + 3])), "r"(pack_bf16(o[8 * i + 4], o[8 * i + 5])),
                     "r"(pack_bf16(o[8 * i + 6], o[8 * i + 7])), "r"(peer + OFF_RBAR + wg * 8) : "memory");
    };
    auto recv_peer = [&](int k) {
      mbar_wait(sb + OFF_RBAR + wg * 8, k & 1);
#pragma unroll
      for (int i = 0; i < 4; i++) { const uint4 v = lds_u4(sb + pbuf + i * 512); pt[4 * i] = v.x; pt[4 * i + 1] = v.y; pt[4 * i + 2] = v.z; pt[4 * i + 3] = v.w; }
    };
    auto send_owner = [&](float (&d)[32], int k) {
#pragma unroll
      for (int i = 0; i < 4; i++) {
#pragma unroll
        for (int c = 4 * i; c < 4 * i + 4; c++) pt[c] = bf2_add(pt[c], pack_bf16(d[2 * c], d[2 * c + 1]));
        asm("lop3.b32 %0, %0, 1, %1, 0xb8;" : "+r"(pt[4 * i]) : "r"(tag));
        st_b128(psend + (((sp + 1 + k) & 3) * 6 + k) * 1024 + i * 32, pt[4 * i], pt[4 * i + 1], pt[4 * i + 2], pt[4 * i + 3]);
      }
      __syncwarp();
      credit();
    };
    auto load_fin = [&]() {
      mbar_wait(sb + OFF_LBAR, 1);
#pragma unroll
      for (int j = 0; j < 8; j++) {
        const uint4 v = lds_u4(sb + pbuf + 16384 + (j >> 2) * 16384 + (j & 3) * 512);
        fin[4 * j] = __uint_as_float(v.x); fin[4 * j + 1] = __uint_as_float(v.y); fin[4 * j + 2] = __uint_as_float(v.z); fin[4 * j + 3] = __uint_as_float(v.w);
      }
    };
    auto ldk = [&](int pos) { if (pos == K0P) recv_issue(sum, 0); if (pos == K1P) recv_issue(r0, 1); };
    auto arm = [&]() { if ((threadIdx.x & 127) == 0) mbar_expect_tx(sb + OFF_RBAR + wg * 8, 8192); };
#pragma unroll
    for (int p = 0; p < 8; p++) {
      if (p == 0) {
        mbar_wait(fullb, 0);
        mma(o, 0, 0, 4, 0);
        wg_wait<1>(); release(5);
        gelu_b(0, 4);
        mma(o, 0, 4, 7, 0);
        bar_sync(1 + wg, 128);
        {
          const uint32_t ha = xw + ((lane >> 4) * 8 + (lane & 7)) * 128 + (((2 * w + ((lane >> 3) & 1)) ^ (lane & 7)) << 4);
#pragma unroll
          for (int kk = 0; kk < 8; kk++)
            asm volatile("ldmatrix.sync.aligned.m8n8.x4.trans.shared.b16 {%0,%1,%2,%3}, [%4];" : "=r"(hf[4 * kk]), "=r"(hf[4 * kk + 1]), "=r"(hf[4 * kk + 2]), "=r"(hf[4 * kk + 3])
                         : "r"(ha + (kk >> 2) * him + (kk & 3) * 2048) : "memory");
        }
        gelu_b(4, 8);
        mbar_wait(fullb + 8, 0);
        mma(o, 0, 7, 11, 0);
        credit();
        gelu_b(8, 14);
        mma(o, 0, 11, 15, 0);
        gelu_b(14, 20);
        mbar_wait(fullb + 16, 0);
        mma(o, 0, 15, 18, 0);
        gelu_b(20, 24);
        if (wg == 1) bar_sync(4, 256);
        mma(o, 0, 18, 22, 0);
      } else {
        TR(0);
        if (EW == 0 || (EW == 1 && (p & 1))) mbar_wait(sb + OFF_XFULL + 8 * p, 1);
        TR(1);
        bar_sync(3 + wg, 256);
        if (p < 7) mma(o, p, 0, 22, 0);
        else if (GAP == 0) mma(fin, p, 0, 22, 1);
        else {
          mma(fin, p, 0, GAP, 1);
          recv_peer(3);
          tag = lds_u(sb + OFF_EPOCH);
          mma(fin, p, GAP, 22, 1);
        }
      }
      if (p < 7 || wg == 0) bar_arrive(4 - wg, 256);
      TR(2);
      if (p != TP) TS(wg, 8 + p);
      if (p < 7 && (EW == 2 || (EW == 1 && (p & 1)))) mbar_wait(sb + OFF_XFULL + 8 * (p + 1), 1);
      ldk(10 * p);
      if ((p & 1) == 0) {
        arm();
        if (p == 6) {
          mbar_wait(sb + OFF_EMPTY + 32, 0);
          tag = lds_u(sb + OFF_EPOCH);
          recv_check(sum, 0); recv_check(r0, 1);
#pragma unroll
          for (int i = 0; i < 16; i++) sum[i] = bf2_add(sum[i], r0[i]);
        }
        TR(3);
        mbar_wait(sb + OFF_KBAR + wg * 8, (p >> 1) & 1);
        TR(4);
      } else {
        if (p == 1 || (p == 7 && GAP == 0)) tag = lds_u(sb + OFF_EPOCH);
        TR(3);
        if (p < 7 || GAP == 0) recv_peer(p >> 1);
        TR(4);
        if (p == 7) {
          recv_check(r0, 2);
#pragma unroll
          for (int i = 0; i < 16; i++) sum[i] = bf2_add(sum[i], bf2_add(r0[i], pt[i]));
        }
      }
      if (p == FINP && !FINW) load_fin();
      ldk(10 * p + 1);
      TR(5);
      wg_wait<0>();
      TR(6);
      if (p < 5) release(p);
      if (p < 7) reg_fence(o); else reg_fence(fin);
      ldk(10 * p + 2);
      if ((p & 1) == 0) {
        if (p == 6) recv_issue(r0, 2);
        send_peer();
        if (p == FINP && FINW) load_fin();
      } else if (p < 7) {
        send_owner(o, p >> 1);
      }
      ldk(10 * p + 3);
      if (p == 2) {
#pragma unroll
        for (int h = 0; h < 2; h++) { rho[h] = __fdividef(2.f, 4.f + bf_lo(lds_h(sb + OFF_GS + (wg * 64 + w * 16 + gr + 8 * h) * 2))); pin(rho[h]); }
      }
      TR(7);
    }
    {
      TS(wg, 16);
      const uint32_t tb = sb + OFF_X + stage_off(0) + warp * 4096;
      const uint32_t ta = tb + gr * 256 + ((gr & 3) << 5) + q * 8;
      const uint32_t la = tb + (lane >> 3) * 256 + (((lane & 7) << 4) ^ ((lane >> 3) << 5));
      float* op = out + (size_t)(m * 128 + wg * 64 + (lane >> 4) * 16 + w * 4 + ((lane >> 3) & 1)) * DM + s * 64 + (lane & 7) * 4;
#pragma unroll
      for (int qq = 0; qq < 4; qq += QS) {
#pragma unroll
        for (int qt = qq; qt < qq + QS; qt++) {
          const int h = qt & 1, ch = qt >> 1;
#pragma unroll
          for (int j = 0; j < 4; j++) {
            const int i = ch * 8 + j * 2 + h;
            asm volatile("st.shared.v2.f32 [%0], {%1,%2};" ::"r"((ta ^ (j << 5)) + h * 2048 + ch * 128),
                         "f"((fin[2 * i] + bf_lo(sum[i])) * rho[h]), "f"((fin[2 * i + 1] + bf_hi(sum[i])) * rho[h]) : "memory");
          }
        }
        __syncwarp();
#pragma unroll
        for (int qt = qq; qt < qq + QS; qt++) {
          const int h = qt & 1, ch = qt >> 1;
#pragma unroll
          for (int r = 0; r < 2; r++)
            *reinterpret_cast<uint4*>(op + (r * 32 + h * 2) * DM + ch * 32) = lds_u4(la + (h * 2 + r) * 1024 + ch * 128);
        }
      }
      if (threadIdx.x == 128) g_epoch[b] = tag;
      TS(wg, 17); TG(wg); TRD(); TDUMP();
    }
  } else {
    asm volatile("setmaxnreg.dec.sync.aligned.u32 56;");
    int wsel = warp;
    asm("" : "+r"(wsel));
    if (wsel > 8) {
      if (warp != 11) {
        const int t = threadIdx.x - 288;
        unsigned par;
        asm volatile("ld.relaxed.gpu.global.u32 %0, [%1];" : "=r"(par) : "l"(g_epoch + b) : "memory");
        const float pr = bf_ld(lam_re + s * 64 + t), pi = bf_ld(lam_im + s * 64 + t), pd = bf_ld(log_dt + s * 64 + t);
        asm volatile("barrier.cluster.wait.aligned;" ::: "memory");
        par = __shfl_sync(0xffffffffu, (par + 1) & 1, 0);
        cplx l64 = make_lam(pr, pi, pd);
        {
          const float inv = __fdividef(1.f, fmaf(pr, pr, pi * pi));
          const cplx cf = cmul(cplx{l64.re - 1.f, l64.im}, cplx{pr * inv, -pi * inv});
          asm volatile("st.shared.v4.f32 [%0], {%1,%2,%3,%4};" ::"r"(sb + OFF_LC + t * 16), "f"(l64.re), "f"(l64.im), "f"(cf.re), "f"(cf.im) : "memory");
          mbar_arrive(sb + OFF_LBAR);
        }
#pragma unroll
        for (int i = 0; i < 6; i++) l64 = cmul(l64, l64);
        cplx l128 = cmul(l64, l64);
        pin(l128.re); pin(l128.im);
        uint32_t vr[15], vi[15];
#pragma unroll
        for (int i = 0; i < 15; i++) { vr[i] = par; vi[i] = 0; pin(vr[i]); pin(vi[i]); }
        mbar_wait(sb + OFF_GBAR, 0);
        const float2 e0 = lds_f2(sb + OFF_CARRY + t * 8), e1 = lds_f2(sb + OFF_CARRY + 512 + t * 8);
        float2* eb = g_end + s * 1024 + t;
        {
          const cplx e = cfma(l64, cplx{e0.x, e0.y}, cplx{e1.x, e1.y});
          const unsigned long long v = ((unsigned long long)__float_as_uint(e.im) << 32) | ((__float_as_uint(e.re) & ~1u) | par);
          asm volatile("st.relaxed.gpu.global.b64 [%0], %1;" ::"l"(eb + m * 64), "l"(v) : "memory");
        }
        if (t == 0) TS(3, 1);
        cplx S = {0.f, 0.f};
        {
          if (LBD) __nanosleep(LBD);
          const float2* e15 = eb + (m - 15) * 64;
          int tries = 0;
          bool bad;
#pragma unroll 1
          do {
#pragma unroll
            for (int i = 0; i < 15; i++)
              asm volatile("{.reg .pred p; .reg .b64 v; mov.b64 v, {%0,%1}; setp.ge.s32 p, %3, %4; @p ld.relaxed.gpu.global.b64 v, [%2]; mov.b64 {%0,%1}, v;}"
                           : "+r"(vr[i]), "+r"(vi[i]) : "l"(e15 + i * 64), "r"(m), "r"(15 - i) : "memory");
            uint32_t x = vr[0] ^ par;
#pragma unroll
            for (int i = 1; i < 15; i++) asm("lop3.b32 %0, %0, %1, %2, 0xf6;" : "+r"(x) : "r"(vr[i]), "r"(par));
            bad = __any_sync(0xffffffffu, x & 1);
          } while (bad && ++tries < 200000);
          if (t == 0) TS(3, 2);
          S = cplx{__uint_as_float(vr[0]), __uint_as_float(vi[0])};
#pragma unroll
          for (int i = 1; i < 15; i++) S = cfma(l128, S, cplx{__uint_as_float(vr[i]), __uint_as_float(vi[i])});
        }
        const cplx S1 = cfma(l64, S, cplx{e0.x, e0.y});
        asm volatile("st.shared.v2.f32 [%0], {%1,%2};" ::"r"(sb + OFF_CARRY + t * 8), "f"(S.re), "f"(S.im) : "memory");
        asm volatile("st.shared.v2.f32 [%0], {%1,%2};" ::"r"(sb + OFF_CARRY + 512 + t * 8), "f"(S1.re), "f"(S1.im) : "memory");
        mbar_arrive(sb + OFF_CBAR);
        if (t == 0) TS(3, 3);
        mbar_wait(sb + OFF_CBAR, 0);
        const int gr = lane >> 2, q = lane & 3;
        float2 db[8];
#pragma unroll
        for (int j = 0; j < 8; j++) db[j] = lds_f2(sb + OFF_DB + j * 32 + q * 8);
        mbar_wait(sb + OFF_XFULL + 16, 1);
        mbar_wait(sb + OFF_EMPTY, 0);
#pragma unroll 1
        for (int cw = warp - 9; cw < 8; cw += 2) {
          const float r0 = 0.5f * bf_lo(lds_h(sb + OFF_GS + (cw * 16 + gr) * 2)), r1 = 0.5f * bf_lo(lds_h(sb + OFF_GS + (cw * 16 + gr) * 2 + 16));
          const uint32_t xa = sb + OFF_X + (1 + rank) * 16384 + (cw * 16 + (lane & 15)) * 128 + (((lane >> 4) ^ (lane & 7)) << 4);
          uint32_t xv[16];
#pragma unroll
          for (int i = 0; i < 4; i++)
            asm volatile("ldmatrix.sync.aligned.m8n8.x4.shared.b16 {%0,%1,%2,%3}, [%4];" : "=r"(xv[4 * i]), "=r"(xv[4 * i + 1]), "=r"(xv[4 * i + 2]), "=r"(xv[4 * i + 3])
                         : "r"(xa ^ (i << 5)) : "memory");
          __syncwarp();
#pragma unroll
          for (int j = 0; j < 8; j++) {
            const uint32_t x0 = bf2_mul(xv[2 * j], __float_as_uint(db[j].x)), x1 = bf2_mul(xv[2 * j + 1], __float_as_uint(db[j].x));
            pin(db[j].y);
            const float bl = bf_lo(__float_as_uint(db[j].y)), bh = bf_hi(__float_as_uint(db[j].y));
            asm volatile("st.shared.v4.f32 [%0], {%1,%2,%3,%4};" ::"r"(sb + OFF_X + 16384 + (j >> 2) * 16384 + cw * 2048 + (j & 3) * 512 + lane * 16), "f"(fmaf(bf_lo(x0), r0, bl)),
                         "f"(fmaf(bf_hi(x0), r0, bh)), "f"(fmaf(bf_lo(x1), r1, bl)), "f"(fmaf(bf_hi(x1), r1, bh)) : "memory");
          }
        }
        mbar_arrive(sb + OFF_LBAR);
        if (t == 0) TS(3, 5);
      } else {
        if (lane == 0) TG(2);
        const uint4* gwp = reinterpret_cast<const uint4*>(gate_w) + (lane & 7);
        uint4 gw[4];
#pragma unroll
        for (int i = 0; i < 4; i++) gw[i] = __ldg(gwp + i * 8);
        unsigned par;
        asm volatile("ld.relaxed.gpu.global.u32 %0, [%1];" : "=r"(par) : "l"(g_epoch + b) : "memory");
        const uint32_t dk = __ldg(reinterpret_cast<const uint32_t*>(dskip + s * 64) + lane), bb = __ldg(reinterpret_cast<const uint32_t*>(b2 + s * 64) + lane);
        asm volatile("barrier.cluster.wait.aligned;" ::: "memory");
        const int row = s * 16 + (lane >> 3);
        const uint32_t xr0 = sb + OFF_X + row * 128 + (((lane & 7) ^ (row & 7)) << 4), xr1 = (xr0 + 512) ^ 64;
        float z[4] = {0.f, 0.f, 0.f, 0.f};
#pragma unroll
        for (int kb = 0; kb < 8; kb++) {
          const uint32_t wv[4] = {gw[kb & 3].x, gw[kb & 3].y, gw[kb & 3].z, gw[kb & 3].w};
          if (kb < 4) gw[kb] = __ldg(gwp + (kb + 4) * 8);
          mbar_wait(sb + OFF_XFULL + 8 * kb, 0);
          if ((PF & 2) && kb == PFK && elect_one()) {
            l2_prefetch(pf_w1 + b * 7168, 14336);
            l2_prefetch(pf_cre + b * 2048, 4096);
            l2_prefetch(pf_cim + b * 2048, 4096);
            l2_prefetch(pf_w2 + b * 7168, 14336);
          }
          const uint32_t xo = ((kb + xrot) & 7) * 16384;
#pragma unroll
          for (int r = 0; r < 4; r++) {
            const uint4 a = lds_u4(((r & 1) ? xr1 : xr0) + xo + (r >> 1) * 1024);
            const uint32_t p = bf2_fma(a.w, wv[3], bf2_fma(a.z, wv[2], bf2_fma(a.y, wv[1], bf2_mul(a.x, wv[0]))));
            z[r] += bf_lo(p); z[r] += bf_hi(p);
          }
        }
        if (lane == 0) asm volatile("st.shared.u32 [%0], %1;" ::"r"(sb + OFF_EPOCH), "r"(par + 1) : "memory");
        par = (par + 1) & 1;
        {
          float y0 = (lane & 4) ? z[1] : z[0], y1 = (lane & 4) ? z[3] : z[2];
          y0 += __shfl_xor_sync(0xffffffffu, (lane & 4) ? z[0] : z[1], 4);
          y1 += __shfl_xor_sync(0xffffffffu, (lane & 4) ? z[2] : z[3], 4);
          float zz = (lane & 2) ? y1 : y0;
          zz += __shfl_xor_sync(0xffffffffu, (lane & 2) ? y0 : y1, 2);
          zz += __shfl_xor_sync(0xffffffffu, zz, 1);
          const float rho = 4.f * expf(zz > 40.f ? 40.f : zz);
          if ((lane & 1) == 0)
            asm volatile("st.relaxed.gpu.global.u32 [%0], %1;" ::"l"(g_gate + m * 128 + row + (lane & 4) + (lane & 2) * 4), "r"((__float_as_uint(rho) & ~1u) | par) : "memory");
        }
        if ((PF & 8) && elect_one()) {
          l2_prefetch(pf_w2 + b * 7168, 14336);
          l2_prefetch(pf_cre + b * 2048, 4096);
          l2_prefetch(pf_cim + b * 2048, 4096);
        }
        if (lane == 0) TS(3, 0);
        mbar_wait(sb + OFF_GBAR, 0);
        asm volatile("st.shared.v2.u32 [%0], {%1,%2};" ::"r"(sb + OFF_DB + lane * 8), "r"(dk), "r"(bf2_add(bb, bb)) : "memory");
        uint32_t g0, g1, g2, g3;
        int tries = 0;
#pragma unroll 1
        do {
          asm volatile("ld.relaxed.gpu.global.v4.u32 {%0,%1,%2,%3}, [%4];" : "=r"(g0), "=r"(g1), "=r"(g2), "=r"(g3) : "l"(g_gate + m * 128 + lane * 4) : "memory");
        } while ((((g0 ^ par) | (g1 ^ par) | (g2 ^ par) | (g3 ^ par)) & 1) && ++tries < 200000);
        asm volatile("st.shared.v2.u32 [%0], {%1,%2};" ::"r"(sb + OFF_GS + lane * 8), "r"(pack_bf16(__uint_as_float(g0), __uint_as_float(g1))),
                     "r"(pack_bf16(__uint_as_float(g2), __uint_as_float(g3))) : "memory");
        mbar_arrive(sb + OFF_CBAR);
        if (lane == 0) TS(3, 4);
      }
    } else {
      asm volatile("barrier.cluster.wait.aligned;" ::: "memory");
      if (elect_one()) {
        TS(2, 1);
        const uint32_t t0 = clock();
#pragma unroll 1
        for (int u = W0; u < 8; u++) {
          if (u >= 1) while ((uint32_t)clock() - t0 < D0 + (u - 1) * D1) {}
          mbar_expect_tx(sb + OFF_XFULL + 8 * u, 16384);
          tma5d_mc(sb + OFF_X + ((u + xrot) & 7) * 16384 + rank * 8192, &maps.x, u * 64, 2 * m + rank, sb + OFF_XFULL + 8 * u);
          const int sl = u < 6 ? u : u - 6;
          if (u >= 6) mbar_wait(sb + OFF_EMPTY + 8 * sl, 0);
          mbar_expect_tx(sb + OFF_FULL + 8 * sl, 16384);
          tma2d(sb + OFF_RING + sl * 16384, &maps.bre, u * 64, s * 64, sb + OFF_FULL + 8 * sl);
          tma2d(sb + OFF_RING + sl * 16384 + 8192, &maps.bim, u * 64, s * 64, sb + OFF_FULL + 8 * sl);
          if (u == 2) asm volatile("prefetch.tensormap [%0];" ::"l"(&maps.w1a) : "memory");
        }
        TS(2, 5);
        int slot = 2; uint32_t ph = 0;
#pragma unroll 1
        for (int u = 8; u < 24; u++) {
          const uint32_t fb = sb + OFF_FULL + 8 * slot, dst = sb + OFF_RING + slot * 16384;
          mbar_wait(sb + OFF_EMPTY + 8 * slot, ph);
          TS2(0, u);
          if (u < 16) {
            mbar_expect_tx(fb, 16384);
            tma2d(dst, &maps.w1a, s * 224, (u - 8) * 64, fb);
            tma2d(dst + 8192, &maps.w1a, s * 224 + 64, (u - 8) * 64, fb);
            if (TMP2 && u < 12) asm volatile("prefetch.tensormap [%0];" ::"l"(&maps.w1b + (u - 8)) : "memory");
          } else {
            mbar_expect_tx(fb, 12288);
            tma3d(dst, &maps.w1b, 0, ((u - xrot) & 7) * 64, s * 7 + 4, fb);
          }
          if (++slot == NSLOT) { slot = 0; ph ^= 1; }
        }
#pragma unroll 1
        for (int j = 0; j < 3; j++) {
          const uint32_t fb = sb + OFF_FULL + 8 * j, dst = sb + OFF_X + stage_off(0);
          const int c = ((sp + 1) & 3) * 128 + ((rank ^ 1) << 6);
          mbar_wait(sb + OFF_EMPTY + 8 + 8 * j, 1);
          mbar_expect_tx(fb, j == 1 ? 16384 : 14336);
          if (j == 1) {
            tma2d(dst + 14336, &maps.cre, s * 64, c, fb);
            tma2d(dst + 22528, &maps.cim, s * 64, c, fb);
          } else {
            tma2d(dst + j * 15360, &maps.w2, c, s * 224 + j * 56, fb);
          }
        }
#pragma unroll 1
        for (int p = 1; p < 8; p++) {
          const int c = ((sp + 1 + (p >> 1)) & 3) * 128 + (((rank ^ p ^ 1) & 1) << 6);
          const uint32_t fb = sb + OFF_XFULL + 8 * p, dst = sb + OFF_X + stage_off(p);
          if (p == 2 || p > 3) mbar_wait(sb + OFF_EMPTY + (p == 2 ? 40 : (p - 4) * 8), p == 2);
          TS2(0, 32 + p);
          mbar_expect_tx(fb, 45056);
          tma2d(dst, &maps.w2, c, s * 224, fb);
          tma2d(dst + 14336, &maps.cre, s * 64, c, fb);
          tma2d(dst + 22528, &maps.cim, s * 64, c, fb);
          tma2d(dst + 30720, &maps.w2, c, s * 224 + 112, fb);
        }
        TS(2, 2);
      }
    }
  }
}

typedef CUresult (*EncFn)(CUtensorMap*, CUtensorMapDataType, cuuint32_t, void*, const cuuint64_t*, const cuuint64_t*, const cuuint32_t*,
                          const cuuint32_t*, CUtensorMapInterleave, CUtensorMapSwizzle, CUtensorMapL2promotion, CUtensorMapFloatOOBfill);

void encode(EncFn f, CUtensorMap* mp, const void* p, int rank, const cuuint64_t* dims, const cuuint64_t* strides, const cuuint32_t* box, CUtensorMapSwizzle sw) {
  cuuint32_t es[5] = {1, 1, 1, 1, 1};
  f(mp, CU_TENSOR_MAP_DATA_TYPE_BFLOAT16, rank, const_cast<void*>(p), dims, strides, box, es, CU_TENSOR_MAP_INTERLEAVE_NONE, sw,
    CU_TENSOR_MAP_L2_PROMOTION_L2_128B, CU_TENSOR_MAP_FLOAT_OOB_FILL_NONE);
}

}

extern "C" void kernel_launch(void* const* d_in, const int* in_sizes, int n_in, void* d_out, int out_size) {
  typedef const __nv_bfloat16* bp;
  bp x = (bp)d_in[0], lre = (bp)d_in[1], lim = (bp)d_in[2], bre = (bp)d_in[3], bim = (bp)d_in[4], cre = (bp)d_in[5], cim = (bp)d_in[6],
     ldt = (bp)d_in[7], dsk = (bp)d_in[8], w1 = (bp)d_in[10], b1 = (bp)d_in[11], w2 = (bp)d_in[12], b2 = (bp)d_in[13], gw = (bp)d_in[14];
  static EncFn enc = nullptr;
  if (!enc) {
    void* f = nullptr;
    cudaDriverEntryPointQueryResult qr;
    cudaGetDriverEntryPoint("cuTensorMapEncodeTiled", &f, cudaEnableDefault, &qr);
    enc = (EncFn)f;
    cudaFuncSetAttribute(fused_kernel, cudaFuncAttributeMaxDynamicSharedMemorySize, SMEM_BYTES);
  }
  Maps maps;
  {
    cuuint64_t d[5] = {DM, 2, 4, 8, SEQ / 64}, st[4] = {DM * 2, 16 * DM * 2, 2 * DM * 2, 64 * DM * 2};
    cuuint32_t bx[5] = {64, 2, 4, 8, 1};
    encode(enc, &maps.x, x, 5, d, st, bx, CU_TENSOR_MAP_SWIZZLE_128B);
  }
  {
    cuuint64_t d[2] = {DM, DM}, st[1] = {DM * 2};
    cuuint32_t bx[2] = {64, 64};
    encode(enc, &maps.bre, bre, 2, d, st, bx, CU_TENSOR_MAP_SWIZZLE_128B);
    encode(enc, &maps.bim, bim, 2, d, st, bx, CU_TENSOR_MAP_SWIZZLE_128B);
    encode(enc, &maps.cre, cre, 2, d, st, bx, CU_TENSOR_MAP_SWIZZLE_128B);
    encode(enc, &maps.cim, cim, 2, d, st, bx, CU_TENSOR_MAP_SWIZZLE_128B);
  }
  {
    cuuint64_t d[2] = {FF, DM}, st[1] = {FF * 2};
    cuuint32_t bx[2] = {64, 64};
    encode(enc, &maps.w1a, w1, 2, d, st, bx, CU_TENSOR_MAP_SWIZZLE_128B);
    cuuint64_t d3[3] = {32, DM, FF / 32}, st3[2] = {FF * 2, 64};
    cuuint32_t bx3[3] = {32, 64, 3};
    encode(enc, &maps.w1b, w1, 3, d3, st3, bx3, CU_TENSOR_MAP_SWIZZLE_64B);
  }
  {
    cuuint64_t d[2] = {DM, FF}, st[1] = {DM * 2};
    cuuint32_t bx[2] = {64, 112};
    encode(enc, &maps.w2, w2, 2, d, st, bx, CU_TENSOR_MAP_SWIZZLE_128B);
  }
  fused_kernel<<<128, 384, SMEM_BYTES>>>(lre, lim, ldt, dsk, b1, b2, gw, w1, w2, cre, cim, (float*)d_out, maps);
}
```

```cpp
#include <cuda_runtime.h>
#include <cuda_bf16.h>
#include <cuda.h>
#include <stdint.h>

#define MAP 1
#define D0 250
#define D1 500
#define PF 4
#define PFK 5
#define GELUP 1
#define EW 2
#define K1E 1
#define K2E 0
#define QS 1
#define K2G 4
#define FINP 4
#define LBD 300
#define PFS 32
#define SB0 2
#define PFD 2
#define HOLD 0
#define GAP 14
#define FINW 0
#define K0P 33
#define K1P 53
#define TMP2 1
#define W0 1
#define LCK 4
#define XS 10
#define YS 10
#define C1 6
#define C2 12
#define C3 19
#define C4 26
#define TP 9
#define TW 0

namespace {

constexpr int SEQ = 2048, DM = 512, FF = 1792;
constexpr int NSLOT = 6;
constexpr uint32_t OFF_X = 0, OFF_RING = 131072, OFF_MISC = 229376;
constexpr uint32_t OFF_XFULL = OFF_MISC, OFF_FULL = OFF_XFULL + 64, OFF_RBAR = OFF_FULL + 48, OFF_EMPTY = OFF_RBAR + 16, OFF_KBAR = OFF_EMPTY + 48,
                   OFF_GBAR = OFF_KBAR + 16, OFF_LBAR = OFF_GBAR + 8, OFF_CBAR = OFF_LBAR + 8, OFF_EPOCH = OFF_CBAR + 8;
constexpr uint32_t OFF_LC = OFF_MISC + 256;
constexpr uint32_t OFF_GS = OFF_LC;
constexpr uint32_t OFF_DB = OFF_LC + 512;
constexpr uint32_t OFF_CARRY = OFF_LC + 1024;
constexpr uint32_t OFF_DBG = OFF_CARRY + 1024;
constexpr uint32_t SMEM_BYTES = OFF_DBG + 768;
static_assert(SMEM_BYTES <= 232448, "smem");

struct Maps { CUtensorMap x, bre, bim, w1b, w1a, w2, cre, cim; };
__host__ __device__ constexpr uint32_t stage_off(int p) { return 49152 + 45056 * (((p >> 1) & 1) + 2 * (p & 1)); }

__device__ uint4 g_part[16 * 8 * 3 * 1024];
__device__ float2 g_end[8 * 16 * 64];
__device__ unsigned g_gate[SEQ];
__device__ unsigned g_epoch[128];
#define TG(role) do {} while (0)
#define TS2(role, i) do {} while (0)
#define TS(role, i) do {} while (0)
#define TDUMP() do {} while (0)
#define TR(i) do {} while (0)
#define TRD() do {} while (0)

__device__ __forceinline__ void mbar_init(uint32_t bar, uint32_t cnt) { asm volatile("mbarrier.init.shared::cta.b64 [%0], %1;" ::"r"(bar), "r"(cnt)); }
__device__ __forceinline__ void mbar_expect_tx(uint32_t bar, uint32_t bytes) { asm volatile("mbarrier.arrive.expect_tx.shared::cta.b64 _, [%0], %1;" ::"r"(bar), "r"(bytes) : "memory"); }
__device__ __forceinline__ void mbar_arrive(uint32_t bar) { asm volatile("mbarrier.arrive.shared::cta.b64 _, [%0];" ::"r"(bar) : "memory"); }
__device__ __forceinline__ void mbar_arrive_cl(uint32_t cbar) { asm volatile("mbarrier.arrive.shared::cluster.b64 _, [%0];" ::"r"(cbar) : "memory"); }
__device__ __forceinline__ void mbar_wait(uint32_t bar, uint32_t parity) {
  asm volatile(
      "{\n.reg .pred p;\n.reg .u32 c;\n"
      "mbarrier.try_wait.parity.shared::cta.b64 p, [%0], %1;\n"
      "@p bra.uni LAB_DONE;\n"
      "mov.u32 c, 0;\n"
      "LAB_WAIT:\n"
      "mbarrier.try_wait.parity.shared::cta.b64 p, [%0], %1;\n"
      "@p bra.uni LAB_DONE;\n"
      "add.u32 c, c, 1;\nsetp.lt.u32 p, c, 200000;\n@p bra.uni LAB_WAIT;\n"
      "LAB_DONE:\n}" ::"r"(bar), "r"(parity) : "memory");
}
__device__ __forceinline__ void tma2d(uint32_t dst, const CUtensorMap* m, int c0, int c1, uint32_t bar) {
  asm volatile("cp.async.bulk.tensor.2d.shared::cluster.global.mbarrier::complete_tx::bytes [%0], [%1, {%3,%4}], [%2];"
               ::"r"(dst), "l"(m), "r"(bar), "r"(c0), "r"(c1) : "memory");
}
__device__ __forceinline__ void tma3d(uint32_t dst, const CUtensorMap* m, int c0, int c1, int c2, uint32_t bar) {
  asm volatile("cp.async.bulk.tensor.3d.shared::cluster.global.mbarrier::complete_tx::bytes [%0], [%1, {%3,%4,%5}], [%2];"
               ::"r"(dst), "l"(m), "r"(bar), "r"(c0), "r"(c1), "r"(c2) : "memory");
}
__device__ __forceinline__ void tma5d(uint32_t dst, const CUtensorMap* m, int c0, int c4, uint32_t bar) {
  asm volatile("cp.async.bulk.tensor.5d.shared::cluster.global.mbarrier::complete_tx::bytes [%0], [%1, {%3,%5,%5,%5,%4}], [%2];"
               ::"r"(dst), "l"(m), "r"(bar), "r"(c0), "r"(c4), "r"(0) : "memory");
}
__device__ __forceinline__ void tma5d_mc(uint32_t dst, const CUtensorMap* m, int c0, int c4, uint32_t bar) {
  asm volatile("cp.async.bulk.tensor.5d.shared::cluster.global.mbarrier::complete_tx::bytes.multicast::cluster [%0], [%1, {%3,%5,%5,%5,%4}], [%2], %6;"
               ::"r"(dst), "l"(m), "r"(bar), "r"(c0), "r"(c4), "r"(0), "h"((uint16_t)3) : "memory");
}
__device__ __forceinline__ void l2_prefetch(const void* p, uint32_t bytes) { asm volatile("cp.async.bulk.prefetch.L2.global [%0], %1;" ::"l"(p), "r"(bytes) : "memory"); }
__device__ __forceinline__ bool elect_one() {
  uint32_t pred;
  asm volatile("{.reg .pred P; elect.sync _|P, 0xffffffff; selp.u32 %0, 1, 0, P;}" : "=r"(pred));
  return pred != 0;
}
__device__ __forceinline__ void wg_fence() { asm volatile("wgmma.fence.sync.aligned;" ::: "memory"); }
__device__ __forceinline__ void wg_commit() { asm volatile("wgmma.commit_group.sync.aligned;" ::: "memory"); }
template <int N> __device__ __forceinline__ void wg_wait() { asm volatile("wgmma.wait_group.sync.aligned %0;" ::"n"(N) : "memory"); }
__device__ __forceinline__ void pin(float& a) { asm volatile("" : "+f"(a)::"memory"); }
__device__ __forceinline__ void pin(uint32_t& a) { asm volatile("" : "+r"(a)::"memory"); }
template <int N> __device__ __forceinline__ void reg_fence(float (&d)[N]) {
#pragma unroll
  for (int i = 0; i < N; i++) pin(d[i]);
}
__device__ __forceinline__ void bar_sync(int id, int n) { asm volatile("bar.sync %0, %1;" ::"r"(id), "r"(n) : "memory"); }
__device__ __forceinline__ void bar_arrive(int id, int n) { asm volatile("bar.arrive %0, %1;" ::"r"(id), "r"(n) : "memory"); }
constexpr uint32_t DH128 = (1024 >> 4) | (1u << 30), DH64 = (512 >> 4) | (2u << 30);
__host__ __device__ constexpr uint32_t lbo(uint32_t bytes) { return (bytes >> 4) << 20; }
__device__ __forceinline__ uint32_t pack_bf16(float lo, float hi) { uint32_t r; asm("cvt.rn.bf16x2.f32 %0, %1, %2;" : "=r"(r) : "f"(hi), "f"(lo)); return r; }
__device__ __forceinline__ float bf_lo(uint32_t v) { return __uint_as_float(v << 16); }
__device__ __forceinline__ float bf_hi(uint32_t v) { return __uint_as_float(v & 0xffff0000u); }
__device__ __forceinline__ float bf_ld(const __nv_bfloat16* p) { return __bfloat162float(__ldg(p)); }
__device__ __forceinline__ uint32_t late16(uint32_t bar) {
  uint32_t r;
  asm volatile("{.reg .pred p; mbarrier.test_wait.parity.shared::cta.b64 p, [%1], 0; selp.u32 %0, 16, 0, p;}" : "=r"(r) : "r"(bar) : "memory");
  return r;
}
__device__ __forceinline__ float2 lds_f2(uint32_t a) { float2 v; asm volatile("ld.shared.v2.f32 {%0,%1}, [%2];" : "=f"(v.x), "=f"(v.y) : "r"(a)); return v; }
__device__ __forceinline__ uint32_t lds_h(uint32_t a) { uint32_t v; asm volatile("ld.shared.u16 %0, [%1];" : "=r"(v) : "r"(a)); return v; }
__device__ __forceinline__ uint32_t lds_u(uint32_t a) { uint32_t v; asm volatile("ld.shared.u32 %0, [%1];" : "=r"(v) : "r"(a)); return v; }
__device__ __forceinline__ uint4 lds_u4(uint32_t a) { uint4 v; asm volatile("ld.shared.v4.u32 {%0,%1,%2,%3}, [%4];" : "=r"(v.x), "=r"(v.y), "=r"(v.z), "=r"(v.w) : "r"(a)); return v; }
__device__ __forceinline__ void st_b128(uint4* p, uint32_t a, uint32_t b, uint32_t c, uint32_t d) {
  asm volatile("st.relaxed.gpu.global.v4.b32 [%0], {%1,%2,%3,%4};" ::"l"(p), "r"(a), "r"(b), "r"(c), "r"(d) : "memory");
}
__device__ __forceinline__ void ld_b128(const uint4* p, uint32_t& a, uint32_t& b, uint32_t& c, uint32_t& d) {
  asm volatile("{.reg .b64 l, h; .reg .b128 v; ld.relaxed.gpu.global.b128 v, [%4]; mov.b128 {l,h}, v; mov.b64 {%0,%1}, l; mov.b64 {%2,%3}, h;}"
               : "=r"(a), "=r"(b), "=r"(c), "=r"(d) : "l"(p) : "memory");
}
__device__ __forceinline__ float tanh_fast(float x) { float y; asm("tanh.approx.f32 %0, %1;" : "=f"(y) : "f"(x)); return y; }
__device__ __forceinline__ float gelu2(float v) {
  float p = fmaf(v * v, 0.0356774081363f, 0.7978845608029f);
  return fmaf(v, tanh_fast(v * p), v);
}
__device__ __forceinline__ uint32_t bf2_mul(uint32_t a, uint32_t b) { uint32_t r; asm("mul.rn.bf16x2 %0, %1, %2;" : "=r"(r) : "r"(a), "r"(b)); return r; }
__device__ __forceinline__ uint32_t bf2_add(uint32_t a, uint32_t b) { uint32_t r; asm("add.rn.bf16x2 %0, %1, %2;" : "=r"(r) : "r"(a), "r"(b)); return r; }
__device__ __forceinline__ uint32_t bf2_fma(uint32_t a, uint32_t b, uint32_t c) { uint32_t r; asm("fma.rn.bf16x2 %0, %1, %2, %3;" : "=r"(r) : "r"(a), "r"(b), "r"(c)); return r; }
__device__ __forceinline__ uint32_t gelu2_pair(float a, float b) {
  const uint32_t v = pack_bf16(a, b);
  uint32_t t;
  asm("tanh.approx.bf16x2 %0, %1;" : "=r"(t) : "r"(bf2_fma(v, bf2_fma(bf2_mul(v, v), 0x3d123d12u, 0xbe4fbe4fu), v)));
  return bf2_fma(v, t, v);
}
struct cplx { float re, im; };
__device__ __forceinline__ cplx cmul(cplx a, cplx b) { return {fmaf(a.re, b.re, -a.im * b.im), fmaf(a.re, b.im, a.im * b.re)}; }
__device__ __forceinline__ cplx cfma(cplx a, cplx b, cplx c) {
  return {fmaf(a.re, b.re, fmaf(-a.im, b.im, c.re)), fmaf(a.re, b.im, fmaf(a.im, b.re, c.im))};
}
__device__ __forceinline__ cplx make_lam(float lre, float lim, float ldt) {
  float dt = __bfloat162float(__float2bfloat16_rn(expf(ldt)));
  float mag = expf(dt * lre), sn, cs;
  sincospif(dt * lim * 0.31830988618379067f, &sn, &cs);
  return {mag * cs, mag * sn};
}

template<int TA,int TB,uint32_t AH,uint32_t BH> __device__ __forceinline__ void wgmma_n64_ss(float (&d)[32], uint32_t al, uint32_t ao, uint32_t bl, uint32_t bo, int scale_d){
  asm volatile("{.reg .pred p; .reg .b32 t, v; .reg .b64 da, db; setp.ne.b32 p, %36, 0; add.u32 t, %32, %33; mov.b64 da, {t, %39}; add.u32 v, %34, %35; mov.b64 db, {v, %40};\n"
   "wgmma.mma_async.sync.aligned.m64n64k16.f32.bf16.bf16 {%0,%1,%2,%3,%4,%5,%6,%7,%8,%9,%10,%11,%12,%13,%14,%15,%16,%17,%18,%19,%20,%21,%22,%23,%24,%25,%26,%27,%28,%29,%30,%31}, da, db, p, 1, 1, %37, %38;}"
   : "+f"(d[0]),"+f"(d[1]),"+f"(d[2]),"+f"(d[3]),"+f"(d[4]),"+f"(d[5]),"+f"(d[6]),"+f"(d[7]),"+f"(d[8]),"+f"(d[9]),"+f"(d[10]),"+f"(d[11]),"+f"(d[12]),"+f"(d[13]),"+f"(d[14]),"+f"(d[15]),"+f"(d[16]),"+f"(d[17]),"+f"(d[18]),"+f"(d[19]),"+f"(d[20]),"+f"(d[21]),"+f"(d[22]),"+f"(d[23]),"+f"(d[24]),"+f"(d[25]),"+f"(d[26]),"+f"(d[27]),"+f"(d[28]),"+f"(d[29]),"+f"(d[30]),"+f"(d[31])
   : "r"(al),"r"(ao >> 4),"r"(bl),"r"(bo >> 4),"r"(scale_d),"n"(TA),"n"(TB),"n"(AH),"n"(BH));
}
template<int TB,uint32_t BH> __device__ __forceinline__ void wgmma_n64_rs(float (&d)[32], uint32_t a0,uint32_t a1,uint32_t a2,uint32_t a3, uint32_t bl, uint32_t bo, int scale_d){
  asm volatile("{.reg .pred p; .reg .b32 t; .reg .b64 db; setp.ne.b32 p, %38, 0; add.u32 t, %36, %37; mov.b64 db, {t, %40};\n"
   "wgmma.mma_async.sync.aligned.m64n64k16.f32.bf16.bf16 {%0,%1,%2,%3,%4,%5,%6,%7,%8,%9,%10,%11,%12,%13,%14,%15,%16,%17,%18,%19,%20,%21,%22,%23,%24,%25,%26,%27,%28,%29,%30,%31}, {%32,%33,%34,%35}, db, p, 1, 1, %39;}"
   : "+f"(d[0]),"+f"(d[1]),"+f"(d[2]),"+f"(d[3]),"+f"(d[4]),"+f"(d[5]),"+f"(d[6]),"+f"(d[7]),"+f"(d[8]),"+f"(d[9]),"+f"(d[10]),"+f"(d[11]),"+f"(d[12]),"+f"(d[13]),"+f"(d[14]),"+f"(d[15]),"+f"(d[16]),"+f"(d[17]),"+f"(d[18]),"+f"(d[19]),"+f"(d[20]),"+f"(d[21]),"+f"(d[22]),"+f"(d[23]),"+f"(d[24]),"+f"(d[25]),"+f"(d[26]),"+f"(d[27]),"+f"(d[28]),"+f"(d[29]),"+f"(d[30]),"+f"(d[31])
   : "r"(a0),"r"(a1),"r"(a2),"r"(a3),"r"(bl),"r"(bo >> 4),"r"(scale_d),"n"(TB),"n"(BH));
}
template<int TA,int TB,uint32_t AH,uint32_t BH> __device__ __forceinline__ void wgmma_n96_ss(float (&d)[48], uint32_t al, uint32_t ao, uint32_t bl, uint32_t bo, int scale_d){
  asm volatile("{.reg .pred p; .reg .b32 t, v; .reg .b64 da, db; setp.ne.b32 p, %52, 0; add.u32 t, %48, %49; mov.b64 da, {t, %55}; add.u32 v, %50, %51; mov.b64 db, {v, %56};\n"
   "wgmma.mma_async.sync.aligned.m64n96k16.f32.bf16.bf16 {%0,%1,%2,%3,%4,%5,%6,%7,%8,%9,%10,%11,%12,%13,%14,%15,%16,%17,%18,%19,%20,%21,%22,%23,%24,%25,%26,%27,%28,%29,%30,%31,%32,%33,%34,%35,%36,%37,%38,%39,%40,%41,%42,%43,%44,%45,%46,%47}, da, db, p, 1, 1, %53, %54;}"
   : "+f"(d[0]),"+f"(d[1]),"+f"(d[2]),"+f"(d[3]),"+f"(d[4]),"+f"(d[5]),"+f"(d[6]),"+f"(d[7]),"+f"(d[8]),"+f"(d[9]),"+f"(d[10]),"+f"(d[11]),"+f"(d[12]),"+f"(d[13]),"+f"(d[14]),"+f"(d[15]),"+f"(d[16]),"+f"(d[17]),"+f"(d[18]),"+f"(d[19]),"+f"(d[20]),"+f"(d[21]),"+f"(d[22]),"+f"(d[23]),"+f"(d[24]),"+f"(d[25]),"+f"(d[26]),"+f"(d[27]),"+f"(d[28]),"+f"(d[29]),"+f"(d[30]),"+f"(d[31]),"+f"(d[32]),"+f"(d[33]),"+f"(d[34]),"+f"(d[35]),"+f"(d[36]),"+f"(d[37]),"+f"(d[38]),"+f"(d[39]),"+f"(d[40]),"+f"(d[41]),"+f"(d[42]),"+f"(d[43]),"+f"(d[44]),"+f"(d[45]),"+f"(d[46]),"+f"(d[47])
   : "r"(al),"r"(ao >> 4),"r"(bl),"r"(bo >> 4),"r"(scale_d),"n"(TA),"n"(TB),"n"(AH),"n"(BH));
}
template<int TA,int TB,uint32_t AH,uint32_t BH> __device__ __forceinline__ void wgmma_n128_ss(float (&d)[64], uint32_t al, uint32_t ao, uint32_t bl, uint32_t bo, int scale_d){
  asm volatile("{.reg .pred p; .reg .b32 t, v; .reg .b64 da, db; setp.ne.b32 p, %68, 0; add.u32 t, %64, %65; mov.b64 da, {t, %71}; add.u32 v, %66, %67; mov.b64 db, {v, %72};\n"
   "wgmma.mma_async.sync.aligned.m64n128k16.f32.bf16.bf16 {%0,%1,%2,%3,%4,%5,%6,%7,%8,%9,%10,%11,%12,%13,%14,%15,%16,%17,%18,%19,%20,%21,%22,%23,%24,%25,%26,%27,%28,%29,%30,%31,%32,%33,%34,%35,%36,%37,%38,%39,%40,%41,%42,%43,%44,%45,%46,%47,%48,%49,%50,%51,%52,%53,%54,%55,%56,%57,%58,%59,%60,%61,%62,%63}, da, db, p, 1, 1, %69, %70;}"
   : "+f"(d[0]),"+f"(d[1]),"+f"(d[2]),"+f"(d[3]),"+f"(d[4]),"+f"(d[5]),"+f"(d[6]),"+f"(d[7]),"+f"(d[8]),"+f"(d[9]),"+f"(d[10]),"+f"(d[11]),"+f"(d[12]),"+f"(d[13]),"+f"(d[14]),"+f"(d[15]),"+f"(d[16]),"+f"(d[17]),"+f"(d[18]),"+f"(d[19]),"+f"(d[20]),"+f"(d[21]),"+f"(d[22]),"+f"(d[23]),"+f"(d[24]),"+f"(d[25]),"+f"(d[26]),"+f"(d[27]),"+f"(d[28]),"+f"(d[29]),"+f"(d[30]),"+f"(d[31]),"+f"(d[32]),"+f"(d[33]),"+f"(d[34]),"+f"(d[35]),"+f"(d[36]),"+f"(d[37]),"+f"(d[38]),"+f"(d[39]),"+f"(d[40]),"+f"(d[41]),"+f"(d[42]),"+f"(d[43]),"+f"(d[44]),"+f"(d[45]),"+f"(d[46]),"+f"(d[47]),"+f"(d[48]),"+f"(d[49]),"+f"(d[50]),"+f"(d[51]),"+f"(d[52]),"+f"(d[53]),"+f"(d[54]),"+f"(d[55]),"+f"(d[56]),"+f"(d[57]),"+f"(d[58]),"+f"(d[59]),"+f"(d[60]),"+f"(d[61]),"+f"(d[62]),"+f"(d[63])
   : "r"(al),"r"(ao >> 4),"r"(bl),"r"(bo >> 4),"r"(scale_d),"n"(TA),"n"(TB),"n"(AH),"n"(BH));
}

__global__ void __cluster_dims__(2, 1, 1) __launch_bounds__(384, 1)
fused_kernel(const __nv_bfloat16* __restrict__ lam_re, const __nv_bfloat16* __restrict__ lam_im, const __nv_bfloat16* __restrict__ log_dt,
             const __nv_bfloat16* __restrict__ dskip, const __nv_bfloat16* __restrict__ b1, const __nv_bfloat16* __restrict__ b2,
             const __nv_bfloat16* __restrict__ gate_w, const __nv_bfloat16* __restrict__ pf_w1, const __nv_bfloat16* __restrict__ pf_w2,
             const __nv_bfloat16* __restrict__ pf_cre, const __nv_bfloat16* __restrict__ pf_cim, float* __restrict__ out,
             const __grid_constant__ Maps maps) {
  extern __shared__ __align__(1024) unsigned char smem_raw[];
  const uint32_t sb = (uint32_t)__cvta_generic_to_shared(smem_raw);
  const int b = blockIdx.x;
  const int rank = b & 1, cl = b >> 1;
  const int sp = (cl & 1) | ((cl >> 2) & 2), m = ((cl >> 1) & 3) | ((cl >> 4) << 2);
  const int s = sp * 2 + rank;
  const int warp = __shfl_sync(0xffffffffu, (int)(threadIdx.x >> 5), 0);
  const int lane = threadIdx.x & 31;
  const int xrot = 9 - 2 * sp;

  if (elect_one()) {
    if (warp == 8) TS(2, 0);
    if (warp > 8) {
      asm volatile("prefetch.tensormap [%0];" ::"l"(&maps.x + (warp - 9)) : "memory");
      mbar_init(sb + OFF_GBAR + 8 * (warp - 9), warp < 11 ? 64 : 96);
    }
    const uint32_t c = warp < 8 ? 1 : warp < 11 ? 8 : 4, bar = sb + OFF_XFULL + 16 * warp;
    mbar_init(bar, c);
    if ((warp & 11) == 0) {
      mbar_expect_tx(bar, 16384);
      if (warp == 0) {
        tma5d(sb + OFF_X + (xrot & 7) * 16384, &maps.x, 0, 2 * m, bar);
        tma5d(sb + OFF_X + (xrot & 7) * 16384 + 8192, &maps.x, 0, 2 * m + 1, bar);
        TS(2, 3);
      } else {
        tma2d(sb + OFF_RING, &maps.bre, 0, s * 64, bar);
        tma2d(sb + OFF_RING + 8192, &maps.bim, 0, s * 64, bar);
        TS(2, 4);
      }
    }
    mbar_init(bar + 8, c);
    asm volatile("fence.mbarrier_init.release.cluster;" ::: "memory");
  }
  __syncwarp();
  asm volatile("barrier.cluster.arrive.relaxed.aligned;" ::: "memory");

  if (warp < 8) {
    const int wg = warp >> 2, w = warp & 3, q = lane & 3, gr = lane >> 2;
    uint32_t bv[28];
#pragma unroll
    for (int j = 0; j < 28; j++) bv[j] = __ldg(reinterpret_cast<const uint32_t*>(b1 + s * 224 + j * 8) + q);
    asm volatile("setmaxnreg.inc.sync.aligned.u32 224;");
    asm volatile("barrier.cluster.wait.aligned;" ::: "memory");
    TS(wg, 0);
    auto release = [&](int slot) { if (lane == 0) mbar_arrive(sb + OFF_EMPTY + 8 * slot); };
    const uint32_t xw = sb + OFF_X + wg * 8192, fullb = sb + OFF_FULL;
    const uint32_t dxw = (xw & 0x3FFFF) >> 4, dring = ((sb + OFF_RING) & 0x3FFFF) >> 4;

    float ure[32], uim[32], aa[48], ab[64];
    cplx lam[2], coef[2], l16[2], l32[2], lq[2], pre[2], e[2];
    uint32_t sh16, mhi;

    auto bias = [&](int c) {
#pragma unroll
      for (int j = c * 7; j < c * 7 + 7; j++) {
        pin(bv[j]);
        float* d = j < 12 ? aa + 4 * j : ab + 4 * (j - 12);
        d[0] = d[2] = __uint_as_float(bv[j] << sh16); d[1] = d[3] = __uint_as_float(bv[j] & mhi);
        pin(d[0]); pin(d[1]); pin(d[2]); pin(d[3]);
      }
    };
#pragma unroll
    for (int kb = 0; kb < 8; kb++) {
      const int slot = kb % NSLOT;
      mbar_wait(sb + OFF_XFULL + 8 * kb, 0);
      if (kb == 0) TS(wg, 18);
      mbar_wait(fullb + 8 * slot, (kb / NSLOT) & 1);
      TS2(2, kb);
      if (kb == 0) TS(wg, 1);
      if (kb == SB0) { sh16 = late16(sb + OFF_XFULL); mhi = 0xffffffffu << sh16; }
      if (kb == LCK) {
        mbar_wait(sb + OFF_LBAR, 0);
#pragma unroll
        for (int h = 0; h < 2; h++) {
          const uint4 v = lds_u4(sb + OFF_LC + (w * 16 + gr + 8 * h) * 16);
          lam[h] = cplx{__uint_as_float(v.x), __uint_as_float(v.y)};
          coef[h] = cplx{__uint_as_float(v.z), __uint_as_float(v.w)};
        }
      }
      wg_fence();
      const uint32_t dxa = dxw + ((kb + xrot) & 7) * 1024;
#pragma unroll
      for (int kk = 0; kk < 4; kk++) {
        wgmma_n64_ss<0, 0, DH128, DH128>(ure, dring, slot * 16384 + kk * 32, dxa, kk * 32, (kb | kk) != 0);
        wgmma_n64_ss<0, 0, DH128, DH128>(uim, dring, slot * 16384 + 8192 + kk * 32, dxa, kk * 32, (kb | kk) != 0);
      }
      wg_commit();
      if (kb > 0) { wg_wait<1>(); release((kb - 1) % NSLOT); }
      if (kb >= SB0 && kb < SB0 + 3) bias(kb - SB0);
      if (kb == 6) {
#pragma unroll
        for (int h = 0; h < 2; h++) {
          pin(lam[h].re); pin(lam[h].im);
          cplx t = cmul(lam[h], lam[h]); t = cmul(t, t); t = cmul(t, t);
          l16[h] = cmul(t, t);
          pin(l16[h].re); pin(l16[h].im);
        }
      }
      if (kb == 7) {
#pragma unroll
        for (int h = 0; h < 2; h++) {
          pin(l16[h].re); pin(l16[h].im);
          l32[h] = cmul(l16[h], l16[h]);
          const cplx a = (q & 1) ? l16[h] : cplx{1.f, 0.f}, c = (q & 2) ? l32[h] : cplx{1.f, 0.f};
          lq[h] = cmul(cmul(a, c), coef[h]);
          pin(lq[h].re); pin(lq[h].im);
        }
      }
    }
    TS(wg, 2);
    auto scale_u = [&](int i0, int i1) {
#pragma unroll
      for (int i = 0; i < 32; i++) if (i >= i0 && i < i1) {
        pin(ure[i]); pin(uim[i]);
        const cplx v = cmul(coef[(i >> 1) & 1], cplx{ure[i], uim[i]});
        ure[i] = v.re; uim[i] = v.im;
        pin(ure[i]); pin(uim[i]);
      }
    };
#pragma unroll
    for (int kb = 0; kb < 8; kb++) {
      const int u = 8 + kb, slot = u % NSLOT;
      mbar_wait(fullb + 8 * slot, (u / NSLOT) & 1);
      wg_fence();
      const uint32_t dxa = dxw + ((kb + xrot) & 7) * 1024;
#pragma unroll
      for (int kk = 0; kk < 4; kk++)
        wgmma_n96_ss<0, 1, DH128, DH64>(aa, dxa, kk * 32, dring, slot * 16384 + kk * 1024 + lbo(4096), 1);
      wg_commit();
      if (SB0 >= 0 && kb == 0) bias(3);
      wg_wait<1>();
      release((u - 1) % NSLOT);
      if (kb == 0) {
        reg_fence(ure); reg_fence(uim);
#pragma unroll
        for (int h = 0; h < 2; h++) e[h] = cplx{ure[2 * h], uim[2 * h]};
      }
      if (kb == 0 || kb == 2 || kb == 3) {
        const int ch = kb ? kb - 1 : 0;
#pragma unroll
        for (int t = 1 + 5 * ch; t < 6 + 5 * ch; t++)
#pragma unroll
          for (int h = 0; h < 2; h++) { const int i = 4 * (t >> 1) + 2 * h + (t & 1); e[h] = cfma(lam[h], e[h], cplx{ure[i], uim[i]}); }
#pragma unroll
        for (int h = 0; h < 2; h++) { pin(e[h].re); pin(e[h].im); }
      } else if (kb == 4) {
#pragma unroll
        for (int h = 0; h < 2; h++) {
          cplx y = {__shfl_up_sync(0xffffffffu, e[h].re, 1, 4), __shfl_up_sync(0xffffffffu, e[h].im, 1, 4)};
          if (q >= 1) e[h] = cfma(l16[h], y, e[h]);
          y = cplx{__shfl_up_sync(0xffffffffu, e[h].re, 2, 4), __shfl_up_sync(0xffffffffu, e[h].im, 2, 4)};
          if (q >= 2) e[h] = cfma(l32[h], y, e[h]);
        }
        if (q == 3) {
#pragma unroll
          for (int h = 0; h < 2; h++)
            asm volatile("st.shared.v2.f32 [%0], {%1,%2};" ::"r"(sb + OFF_CARRY + wg * 512 + (w * 16 + gr + 8 * h) * 8), "f"(e[h].re), "f"(e[h].im) : "memory");
          mbar_arrive(sb + OFF_GBAR);
        }
#pragma unroll
        for (int h = 0; h < 2; h++) {
          const cplx y = {__shfl_up_sync(0xffffffffu, e[h].re, 1, 4), __shfl_up_sync(0xffffffffu, e[h].im, 1, 4)};
          pre[h] = (q >= 1) ? cmul(coef[h], y) : cplx{0.f, 0.f};
          pin(pre[h].re); pin(pre[h].im);
        }
        TS(wg, 3);
      } else if (kb > 4) {
        scale_u(kb == 5 ? 0 : kb == 6 ? 4 : 12, kb == 5 ? 4 : kb == 6 ? 12 : 20);
      }
    }
    TS(wg, 4);
    uint32_t H[56], hf[32];
    cplx hst[2];
    const uint32_t hst_addr = xw + (w * 16 + (lane & 15)) * 128 + (((lane >> 4) ^ (lane & 7)) << 4);
    const uint32_t him = (2 - rank) * 16384;
    uint32_t peer;
    asm volatile("mapa.shared::cluster.u32 %0, %1, %2;" : "=r"(peer) : "r"(sb), "r"(rank ^ 1));
    auto credit = [&]() { if (lane == 0) mbar_arrive_cl(peer + OFF_KBAR + wg * 8); };
#pragma unroll
    for (int kb = 0; kb < 8; kb++) {
      const int u = 16 + kb, slot = u % NSLOT;
      mbar_wait(fullb + 8 * slot, (u / NSLOT) & 1);
      wg_fence();
#pragma unroll
      for (int kk = 0; kk < 4; kk++)
        wgmma_n128_ss<0, 1, DH128, DH128>(ab, dxw, kb * 16384 + kk * 32, dring, slot * 16384 + kk * 2048 + lbo(8192), 1);
      wg_commit();
      wg_wait<1>();
      release((u - 1) % NSLOT);
      if (kb == 0) scale_u(20, 32);
      if (kb < 5 && kb != 1) {
        const int ch = kb ? kb - 1 : 0;
#pragma unroll
        for (int i = ch * 6; i < ch * 6 + 6; i++) {
          pin(aa[2 * i]); pin(aa[2 * i + 1]);
          H[i] = gelu2_pair(aa[2 * i], aa[2 * i + 1]);
          pin(H[i]);
        }
      }
      if (kb >= 4) {
        if (kb == 4) {
          TS(wg, 5);
          mbar_wait(sb + OFF_CBAR, 0);
          TS(wg, 6);
#pragma unroll
          for (int h = 0; h < 2; h++) {
            const float2 c = lds_f2(sb + OFF_CARRY + wg * 512 + (w * 16 + gr + 8 * h) * 8);
            hst[h] = cfma(lq[h], cplx{c.x, c.y}, pre[h]);
          }
        }
        const int j0 = (kb - 4) * 2;
        uint32_t rr[4], ri[4];
#pragma unroll
        for (int jj = 0; jj < 2; jj++) {
          const int j = j0 + jj;
          const uint32_t g2 = lds_u(sb + OFF_GS + (wg * 64 + j * 8 + q * 2) * 2);
#pragma unroll
          for (int h = 0; h < 2; h++) {
            const int i = 4 * j + 2 * h;
            const cplx h0 = cfma(lam[h], hst[h], cplx{ure[i], uim[i]});
            hst[h] = cfma(lam[h], h0, cplx{ure[i + 1], uim[i + 1]});
            rr[jj * 2 + h] = bf2_mul(pack_bf16(h0.re, hst[h].re), g2);
            ri[jj * 2 + h] = bf2_mul(pack_bf16(h0.im, hst[h].im), g2 ^ 0x80008000u);
          }
        }
        const uint32_t a = hst_addr ^ (j0 << 4);
        asm volatile("stmatrix.sync.aligned.m8n8.x4.shared.b16 [%0], {%1,%2,%3,%4};" ::"r"(a), "r"(rr[0]), "r"(rr[1]), "r"(rr[2]), "r"(rr[3]) : "memory");
        asm volatile("stmatrix.sync.aligned.m8n8.x4.shared.b16 [%0], {%1,%2,%3,%4};" ::"r"(a + him), "r"(ri[0]), "r"(ri[1]), "r"(ri[2]), "r"(ri[3]) : "memory");
      }
    }
    TS(wg, 7);

    uint4* const psend = g_part + (size_t)(m * 8 + rank) * 3072 + warp * 128 + lane;
    const uint4* const precv = g_part + (size_t)(m * 8 + s) * 3072 + warp * 128 + lane;
    const uint32_t pbuf = OFF_X + warp * 2048 + lane * 16;
    const uint32_t dx0 = ((sb + OFF_X) & 0x3FFFF) >> 4;
    float o[32], fin[32], rho[2];
    uint32_t tr[8];
    uint32_t r0[16], pt[16], sum[16], tag;
    auto recv_issue = [&](uint32_t (&r)[16], int k) {
#pragma unroll
      for (int i = 0; i < 4; i++) ld_b128(precv + k * 1024 + i * 32, r[4 * i], r[4 * i + 1], r[4 * i + 2], r[4 * i + 3]);
    };
    auto stale = [&](uint32_t (&r)[16]) {
      uint32_t t0, t1, r_;
      asm("lop3.b32 %0, %1, %2, %3, 0x7e;" : "=r"(t0) : "r"(r[0]), "r"(r[4]), "r"(tag));
      asm("lop3.b32 %0, %1, %2, %3, 0x7e;" : "=r"(t1) : "r"(r[8]), "r"(r[12]), "r"(tag));
      asm volatile("{.reg .pred p; .reg .b32 t; lop3.b32 t, %1, %2, 1, 0xa8; setp.ne.u32 p, t, 0; vote.sync.any.pred p, p, 0xffffffff; selp.u32 %0, 1, 0, p;}" : "=r"(r_) : "r"(t0), "r"(t1));
      return r_ != 0;
    };
    auto recv_check = [&](uint32_t (&r)[16], int k) {
      if (__builtin_expect(stale(r), 0)) {
        int tries = 0;
#pragma unroll 1
        do { recv_issue(r, k); } while (stale(r) && ++tries < 200000);
      }
    };
    auto gelu_b = [&](int i0, int i1) {
#pragma unroll
      for (int i = i0; i < i1; i++) {
        pin(ab[2 * i]); pin(ab[2 * i + 1]);
        H[24 + i] = gelu2_pair(ab[2 * i], ab[2 * i + 1]);
        pin(H[24 + i]);
      }
    };
    auto step = [&](float (&d)[32], int p, int k, int acc) {
      const uint32_t wo = stage_off(p);
      if (k >= 6 && k < 14) {
        const int kk = k - 6;
        wgmma_n64_rs<0, DH128>(d, hf[4 * kk], hf[4 * kk + 1], hf[4 * kk + 2], hf[4 * kk + 3], dx0, wo + 14336 + (kk >> 2) * 8192 + (kk & 3) * 32, 1);
      } else {
        const int kk = k < 6 ? k : k - 8;
        wgmma_n64_rs<1, DH128>(d, H[4 * kk], H[4 * kk + 1], H[4 * kk + 2], H[4 * kk + 3], dx0, wo + (kk / 7) * 30720 + (kk % 7) * 2048, k != 0 || acc);
      }
    };
    auto mma = [&](float (&d)[32], int p, int k0, int k1, int acc) {
      wg_fence();
#pragma unroll
      for (int k = k0; k < k1; k++) step(d, p, k, acc);
      wg_commit();
    };
    auto send_peer = [&]() {
#pragma unroll
      for (int i = 0; i < 4; i++)
        asm volatile("st.async.shared::cluster.mbarrier::complete_tx::bytes.v4.b32 [%0], {%1,%2,%3,%4}, [%5];" ::"r"(peer + pbuf + i * 512),
                     "r"(pack_bf16(o[8 * i], o[8 * i + 1])), "r"(pack_bf16(o[8 * i + 2], o[8 * i + 3])), "r"(pack_bf16(o[8 * i + 4], o[8 * i + 5])),
                     "r"(pack_bf16(o[8 * i + 6], o[8 * i + 7])), "r"(peer + OFF_RBAR + wg * 8) : "memory");
    };
    auto recv_peer = [&](int k) {
      mbar_wait(sb + OFF_RBAR + wg * 8, k & 1);
#pragma unroll
      for (int i = 0; i < 4; i++) { const uint4 v = lds_u4(sb + pbuf + i * 512); pt[4 * i] = v.x; pt[4 * i + 1] = v.y; pt[4 * i + 2] = v.z; pt[4 * i + 3] = v.w; }
    };
    auto send_owner = [&](float (&d)[32], int k) {
#pragma unroll
      for (int i = 0; i < 4; i++) {
#pragma unroll
        for (int c = 4 * i; c < 4 * i + 4; c++) pt[c] = bf2_add(pt[c], pack_bf16(d[2 * c], d[2 * c + 1]));
        asm("lop3.b32 %0, %0, 1, %1, 0xb8;" : "+r"(pt[4 * i]) : "r"(tag));
        st_b128(psend + (((sp + 1 + k) & 3) * 6 + k) * 1024 + i * 32, pt[4 * i], pt[4 * i + 1], pt[4 * i + 2], pt[4 * i + 3]);
      }
      __syncwarp();
      credit();
    };
    auto load_fin = [&]() {
      mbar_wait(sb + OFF_LBAR, 1);
#pragma unroll
      for (int j = 0; j < 8; j++) {
        const uint4 v = lds_u4(sb + pbuf + 16384 + (j >> 2) * 16384 + (j & 3) * 512);
        fin[4 * j] = __uint_as_float(v.x); fin[4 * j + 1] = __uint_as_float(v.y); fin[4 * j + 2] = __uint_as_float(v.z); fin[4 * j + 3] = __uint_as_float(v.w);
      }
    };
    auto ldk = [&](int pos) { if (pos == K0P) recv_issue(sum, 0); if (pos == K1P) recv_issue(r0, 1); };
    auto arm = [&]() { if ((threadIdx.x & 127) == 0) mbar_expect_tx(sb + OFF_RBAR + wg * 8, 8192); };
#pragma unroll
    for (int p = 0; p < 8; p++) {
      if (p == 0) {
        mbar_wait(fullb, 0);
        mma(o, 0, 0, 4, 0);
        wg_wait<1>(); release(5);
        gelu_b(0, C1);
        mma(fin, 1, 0, 4, 0);
        bar_sync(1 + wg, 128);
        {
          const uint32_t ha = xw + ((lane >> 4) * 8 + (lane & 7)) * 128 + (((2 * w + ((lane >> 3) & 1)) ^ (lane & 7)) << 4);
#pragma unroll
          for (int kk = 0; kk < 8; kk++)
            asm volatile("ldmatrix.sync.aligned.m8n8.x4.trans.shared.b16 {%0,%1,%2,%3}, [%4];" : "=r"(hf[4 * kk]), "=r"(hf[4 * kk + 1]), "=r"(hf[4 * kk + 2]), "=r"(hf[4 * kk + 3])
                         : "r"(ha + (kk >> 2) * him + (kk & 3) * 2048) : "memory");
        }
        gelu_b(C1, C2);
        mma(o, 0, 4, 6, 0); mma(fin, 1, 4, 6, 0);
        gelu_b(C2, C3);
        mbar_wait(fullb + 8, 0);
        mma(o, 0, 6, XS, 0);
        credit();
        gelu_b(C3, C4);
        if (YS > 6) mma(fin, 1, 6, YS, 0);
        gelu_b(C4, 32);
        mbar_wait(fullb + 16, 0);
        if (wg == 1) bar_sync(4, 256);
        mma(o, 0, XS, 22, 0);
      } else {
        TR(0);
        if (EW == 0 || (EW == 1 && (p & 1))) mbar_wait(sb + OFF_XFULL + 8 * p, 1);
        TR(1);
        bar_sync(3 + wg, 256);
        if (p == 1) mma(fin, 1, YS, 22, 0);
        else if (p < 7) mma(o, p, 0, 22, 0);
        else if (GAP == 0) mma(fin, p, 0, 22, 1);
        else {
          mma(fin, p, 0, GAP, 1);
          recv_peer(3);
          tag = lds_u(sb + OFF_EPOCH);
          mma(fin, p, GAP, 22, 1);
        }
      }
      if (p < 7 || wg == 0) bar_arrive(4 - wg, 256);
      TR(2);
      if (p != TP) TS(wg, 8 + p);
      if (p > 0 && p < 7 && (EW == 2 || (EW == 1 && (p & 1)))) mbar_wait(sb + OFF_XFULL + 8 * (p + 1), 1);
      ldk(10 * p);
      if ((p & 1) == 0) {
        arm();
        if (p == 6) {
          mbar_wait(sb + OFF_EMPTY + 32, 0);
          tag = lds_u(sb + OFF_EPOCH);
          recv_check(sum, 0); recv_check(r0, 1);
#pragma unroll
          for (int i = 0; i < 16; i++) sum[i] = bf2_add(sum[i], r0[i]);
        }
        TR(3);
        mbar_wait(sb + OFF_KBAR + wg * 8, (p >> 1) & 1);
        TR(4);
      } else {
        if (p == 1 || (p == 7 && GAP == 0)) tag = lds_u(sb + OFF_EPOCH);
        TR(3);
        if (p < 7 || GAP == 0) recv_peer(p >> 1);
        TR(4);
        if (p == 7) {
          recv_check(r0, 2);
#pragma unroll
          for (int i = 0; i < 16; i++) sum[i] = bf2_add(sum[i], bf2_add(r0[i], pt[i]));
        }
      }
      if (p == FINP && !FINW) load_fin();
      ldk(10 * p + 1);
      TR(5);
      wg_wait<0>();
      TR(6);
      if (p < 5) release(p);
      if (p < 7 && p != 1) reg_fence(o); else reg_fence(fin);
      ldk(10 * p + 2);
      if ((p & 1) == 0) {
        if (p == 6) recv_issue(r0, 2);
        send_peer();
        if (p == FINP && FINW) load_fin();
      } else if (p < 7) {
        if (p == 1) send_owner(fin, 0); else send_owner(o, p >> 1);
      }
      ldk(10 * p + 3);
      if (p == 2) {
#pragma unroll
        for (int h = 0; h < 2; h++) { rho[h] = __fdividef(2.f, 4.f + bf_lo(lds_h(sb + OFF_GS + (wg * 64 + w * 16 + gr + 8 * h) * 2))); pin(rho[h]); }
      }
      TR(7);
    }
    {
      TS(wg, 16);
      const uint32_t tb = sb + OFF_X + stage_off(0) + warp * 4096;
      const uint32_t ta = tb + gr * 256 + ((gr & 3) << 5) + q * 8;
      const uint32_t la = tb + (lane >> 3) * 256 + (((lane & 7) << 4) ^ ((lane >> 3) << 5));
      float* op = out + (size_t)(m * 128 + wg * 64 + (lane >> 4) * 16 + w * 4 + ((lane >> 3) & 1)) * DM + s * 64 + (lane & 7) * 4;
#pragma unroll
      for (int qq = 0; qq < 4; qq += QS) {
#pragma unroll
        for (int qt = qq; qt < qq + QS; qt++) {
          const int h = qt & 1, ch = qt >> 1;
#pragma unroll
          for (int j = 0; j < 4; j++) {
            const int i = ch * 8 + j * 2 + h;
            asm volatile("st.shared.v2.f32 [%0], {%1,%2};" ::"r"((ta ^ (j << 5)) + h * 2048 + ch * 128),
                         "f"((fin[2 * i] + bf_lo(sum[i])) * rho[h]), "f"((fin[2 * i + 1] + bf_hi(sum[i])) * rho[h]) : "memory");
          }
        }
        __syncwarp();
#pragma unroll
        for (int qt = qq; qt < qq + QS; qt++) {
          const int h = qt & 1, ch = qt >> 1;
#pragma unroll
          for (int r = 0; r < 2; r++)
            *reinterpret_cast<uint4*>(op + (r * 32 + h * 2) * DM + ch * 32) = lds_u4(la + (h * 2 + r) * 1024 + ch * 128);
        }
      }
      if (threadIdx.x == 128) g_epoch[b] = tag;
      TS(wg, 17); TG(wg); TRD(); TDUMP();
    }
  } else {
    asm volatile("setmaxnreg.dec.sync.aligned.u32 56;");
    int wsel = warp;
    asm("" : "+r"(wsel));
    if (wsel > 8) {
      if (warp != 11) {
        const int t = threadIdx.x - 288;
        unsigned par;
        asm volatile("ld.relaxed.gpu.global.u32 %0, [%1];" : "=r"(par) : "l"(g_epoch + b) : "memory");
        const float pr = bf_ld(lam_re + s * 64 + t), pi = bf_ld(lam_im + s * 64 + t), pd = bf_ld(log_dt + s * 64 + t);
        asm volatile("barrier.cluster.wait.aligned;" ::: "memory");
        par = __shfl_sync(0xffffffffu, (par + 1) & 1, 0);
        cplx l64 = make_lam(pr, pi, pd);
        {
          const float inv = __fdividef(1.f, fmaf(pr, pr, pi * pi));
          const cplx cf = cmul(cplx{l64.re - 1.f, l64.im}, cplx{pr * inv, -pi * inv});
          asm volatile("st.shared.v4.f32 [%0], {%1,%2,%3,%4};" ::"r"(sb + OFF_LC + t * 16), "f"(l64.re), "f"(l64.im), "f"(cf.re), "f"(cf.im) : "memory");
          mbar_arrive(sb + OFF_LBAR);
        }
#pragma unroll
        for (int i = 0; i < 6; i++) l64 = cmul(l64, l64);
        cplx l128 = cmul(l64, l64);
        pin(l128.re); pin(l128.im);
        uint32_t vr[15], vi[15];
#pragma unroll
        for (int i = 0; i < 15; i++) { vr[i] = par; vi[i] = 0; pin(vr[i]); pin(vi[i]); }
        mbar_wait(sb + OFF_GBAR, 0);
        const float2 e0 = lds_f2(sb + OFF_CARRY + t * 8), e1 = lds_f2(sb + OFF_CARRY + 512 + t * 8);
        float2* eb = g_end + s * 1024 + t;
        {
          const cplx e = cfma(l64, cplx{e0.x, e0.y}, cplx{e1.x, e1.y});
          const unsigned long long v = ((unsigned long long)__float_as_uint(e.im) << 32) | ((__float_as_uint(e.re) & ~1u) | par);
          asm volatile("st.relaxed.gpu.global.b64 [%0], %1;" ::"l"(eb + m * 64), "l"(v) : "memory");
        }
        if (t == 0) TS(3, 1);
        cplx S = {0.f, 0.f};
        {
          if (LBD) __nanosleep(LBD);
          const float2* e15 = eb + (m - 15) * 64;
          int tries = 0;
          bool bad;
#pragma unroll 1
          do {
#pragma unroll
            for (int i = 0; i < 15; i++)
              asm volatile("{.reg .pred p; .reg .b64 v; mov.b64 v, {%0,%1}; setp.ge.s32 p, %3, %4; @p ld.relaxed.gpu.global.b64 v, [%2]; mov.b64 {%0,%1}, v;}"
                           : "+r"(vr[i]), "+r"(vi[i]) : "l"(e15 + i * 64), "r"(m), "r"(15 - i) : "memory");
            uint32_t x = vr[0] ^ par;
#pragma unroll
            for (int i = 1; i < 15; i++) asm("lop3.b32 %0, %0, %1, %2, 0xf6;" : "+r"(x) : "r"(vr[i]), "r"(par));
            bad = __any_sync(0xffffffffu, x & 1);
          } while (bad && ++tries < 200000);
          if (t == 0) TS(3, 2);
          S = cplx{__uint_as_float(vr[0]), __uint_as_float(vi[0])};
#pragma unroll
          for (int i = 1; i < 15; i++) S = cfma(l128, S, cplx{__uint_as_float(vr[i]), __uint_as_float(vi[i])});
        }
        const cplx S1 = cfma(l64, S, cplx{e0.x, e0.y});
        asm volatile("st.shared.v2.f32 [%0], {%1,%2};" ::"r"(sb + OFF_CARRY + t * 8), "f"(S.re), "f"(S.im) : "memory");
        asm volatile("st.shared.v2.f32 [%0], {%1,%2};" ::"r"(sb + OFF_CARRY + 512 + t * 8), "f"(S1.re), "f"(S1.im) : "memory");
        mbar_arrive(sb + OFF_CBAR);
        if (t == 0) TS(3, 3);
        mbar_wait(sb + OFF_CBAR, 0);
        const int gr = lane >> 2, q = lane & 3;
        float2 db[8];
#pragma unroll
        for (int j = 0; j < 8; j++) db[j] = lds_f2(sb + OFF_DB + j * 32 + q * 8);
        mbar_wait(sb + OFF_XFULL + 16, 1);
        mbar_wait(sb + OFF_EMPTY, 0);
#pragma unroll 1
        for (int cw = warp - 9; cw < 8; cw += 2) {
          const float r0 = 0.5f * bf_lo(lds_h(sb + OFF_GS + (cw * 16 + gr) * 2)), r1 = 0.5f * bf_lo(lds_h(sb + OFF_GS + (cw * 16 + gr) * 2 + 16));
          const uint32_t xa = sb + OFF_X + (1 + rank) * 16384 + (cw * 16 + (lane & 15)) * 128 + (((lane >> 4) ^ (lane & 7)) << 4);
          uint32_t xv[16];
#pragma unroll
          for (int i = 0; i < 4; i++)
            asm volatile("ldmatrix.sync.aligned.m8n8.x4.shared.b16 {%0,%1,%2,%3}, [%4];" : "=r"(xv[4 * i]), "=r"(xv[4 * i + 1]), "=r"(xv[4 * i + 2]), "=r"(xv[4 * i + 3])
                         : "r"(xa ^ (i << 5)) : "memory");
          __syncwarp();
#pragma unroll
          for (int j = 0; j < 8; j++) {
            const uint32_t x0 = bf2_mul(xv[2 * j], __float_as_uint(db[j].x)), x1 = bf2_mul(xv[2 * j + 1], __float_as_uint(db[j].x));
            pin(db[j].y);
            const float bl = bf_lo(__float_as_uint(db[j].y)), bh = bf_hi(__float_as_uint(db[j].y));
            asm volatile("st.shared.v4.f32 [%0], {%1,%2,%3,%4};" ::"r"(sb + OFF_X + 16384 + (j >> 2) * 16384 + cw * 2048 + (j & 3) * 512 + lane * 16), "f"(fmaf(bf_lo(x0), r0, bl)),
                         "f"(fmaf(bf_hi(x0), r0, bh)), "f"(fmaf(bf_lo(x1), r1, bl)), "f"(fmaf(bf_hi(x1), r1, bh)) : "memory");
          }
        }
        mbar_arrive(sb + OFF_LBAR);
        if (t == 0) TS(3, 5);
      } else {
        if (lane == 0) TG(2);
        const uint4* gwp = reinterpret_cast<const uint4*>(gate_w) + (lane & 7);
        uint4 gw[4];
#pragma unroll
        for (int i = 0; i < 4; i++) gw[i] = __ldg(gwp + i * 8);
        unsigned par;
        asm volatile("ld.relaxed.gpu.global.u32 %0, [%1];" : "=r"(par) : "l"(g_epoch + b) : "memory");
        const uint32_t dk = __ldg(reinterpret_cast<const uint32_t*>(dskip + s * 64) + lane), bb = __ldg(reinterpret_cast<const uint32_t*>(b2 + s * 64) + lane);
        asm volatile("barrier.cluster.wait.aligned;" ::: "memory");
        const int row = s * 16 + (lane >> 3);
        const uint32_t xr0 = sb + OFF_X + row * 128 + (((lane & 7) ^ (row & 7)) << 4), xr1 = (xr0 + 512) ^ 64;
        float z[4] = {0.f, 0.f, 0.f, 0.f};
#pragma unroll
        for (int kb = 0; kb < 8; kb++) {
          const uint32_t wv[4] = {gw[kb & 3].x, gw[kb & 3].y, gw[kb & 3].z, gw[kb & 3].w};
          if (kb < 4) gw[kb] = __ldg(gwp + (kb + 4) * 8);
          mbar_wait(sb + OFF_XFULL + 8 * kb, 0);
          if ((PF & 2) && kb == PFK && elect_one()) {
            l2_prefetch(pf_w1 + b * 7168, 14336);
            l2_prefetch(pf_cre + b * 2048, 4096);
            l2_prefetch(pf_cim + b * 2048, 4096);
            l2_prefetch(pf_w2 + b * 7168, 14336);
          }
          const uint32_t xo = ((kb + xrot) & 7) * 16384;
#pragma unroll
          for (int r = 0; r < 4; r++) {
            const uint4 a = lds_u4(((r & 1) ? xr1 : xr0) + xo + (r >> 1) * 1024);
            const uint32_t p = bf2_fma(a.w, wv[3], bf2_fma(a.z, wv[2], bf2_fma(a.y, wv[1], bf2_mul(a.x, wv[0]))));
            z[r] += bf_lo(p); z[r] += bf_hi(p);
          }
        }
        if (lane == 0) asm volatile("st.shared.u32 [%0], %1;" ::"r"(sb + OFF_EPOCH), "r"(par + 1) : "memory");
        par = (par + 1) & 1;
        {
          float y0 = (lane & 4) ? z[1] : z[0], y1 = (lane & 4) ? z[3] : z[2];
          y0 += __shfl_xor_sync(0xffffffffu, (lane & 4) ? z[0] : z[1], 4);
          y1 += __shfl_xor_sync(0xffffffffu, (lane & 4) ? z[2] : z[3], 4);
          float zz = (lane & 2) ? y1 : y0;
          zz += __shfl_xor_sync(0xffffffffu, (lane & 2) ? y0 : y1, 2);
          zz += __shfl_xor_sync(0xffffffffu, zz, 1);
          const float rho = 4.f * expf(zz > 40.f ? 40.f : zz);
          if ((lane & 1) == 0)
            asm volatile("st.relaxed.gpu.global.u32 [%0], %1;" ::"l"(g_gate + m * 128 + row + (lane & 4) + (lane & 2) * 4), "r"((__float_as_uint(rho) & ~1u) | par) : "memory");
        }
        if ((PF & 8) && elect_one()) {
          l2_prefetch(pf_w2 + b * 7168, 14336);
          l2_prefetch(pf_cre + b * 2048, 4096);
          l2_prefetch(pf_cim + b * 2048, 4096);
        }
        if (lane == 0) TS(3, 0);
        mbar_wait(sb + OFF_GBAR, 0);
        asm volatile("st.shared.v2.u32 [%0], {%1,%2};" ::"r"(sb + OFF_DB + lane * 8), "r"(dk), "r"(bf2_add(bb, bb)) : "memory");
        uint32_t g0, g1, g2, g3;
        int tries = 0;
#pragma unroll 1
        do {
          asm volatile("ld.relaxed.gpu.global.v4.u32 {%0,%1,%2,%3}, [%4];" : "=r"(g0), "=r"(g1), "=r"(g2), "=r"(g3) : "l"(g_gate + m * 128 + lane * 4) : "memory");
        } while ((((g0 ^ par) | (g1 ^ par) | (g2 ^ par) | (g3 ^ par)) & 1) && ++tries < 200000);
        asm volatile("st.shared.v2.u32 [%0], {%1,%2};" ::"r"(sb + OFF_GS + lane * 8), "r"(pack_bf16(__uint_as_float(g0), __uint_as_float(g1))),
                     "r"(pack_bf16(__uint_as_float(g2), __uint_as_float(g3))) : "memory");
        mbar_arrive(sb + OFF_CBAR);
        if (lane == 0) TS(3, 4);
      }
    } else {
      asm volatile("barrier.cluster.wait.aligned;" ::: "memory");
      if (elect_one()) {
        TS(2, 1);
        const uint32_t t0 = clock();
#pragma unroll 1
        for (int u = W0; u < 8; u++) {
          if (u >= 1) while ((uint32_t)clock() - t0 < D0 + (u - 1) * D1) {}
          mbar_expect_tx(sb + OFF_XFULL + 8 * u, 16384);
          tma5d_mc(sb + OFF_X + ((u + xrot) & 7) * 16384 + rank * 8192, &maps.x, u * 64, 2 * m + rank, sb + OFF_XFULL + 8 * u);
          const int sl = u < 6 ? u : u - 6;
          if (u >= 6) mbar_wait(sb + OFF_EMPTY + 8 * sl, 0);
          mbar_expect_tx(sb + OFF_FULL + 8 * sl, 16384);
          tma2d(sb + OFF_RING + sl * 16384, &maps.bre, u * 64, s * 64, sb + OFF_FULL + 8 * sl);
          tma2d(sb + OFF_RING + sl * 16384 + 8192, &maps.bim, u * 64, s * 64, sb + OFF_FULL + 8 * sl);
          if (u == 2) asm volatile("prefetch.tensormap [%0];" ::"l"(&maps.w1b) : "memory");
        }
        TS(2, 5);
        int slot = 2; uint32_t ph = 0;
#pragma unroll 1
        for (int u = 8; u < 24; u++) {
          const uint32_t fb = sb + OFF_FULL + 8 * slot, dst = sb + OFF_RING + slot * 16384;
          mbar_wait(sb + OFF_EMPTY + 8 * slot, ph);
          TS2(0, u);
          if (u < 16) {
            mbar_expect_tx(fb, 12288);
            tma3d(dst, &maps.w1b, 0, (u - 8) * 64, s * 7, fb);
            if (TMP2 && u < 12) asm volatile("prefetch.tensormap [%0];" ::"l"(&maps.w1a + (u - 8)) : "memory");
          } else {
            mbar_expect_tx(fb, 16384);
            tma2d(dst, &maps.w1a, s * 224 + 96, ((u - xrot) & 7) * 64, fb);
            tma2d(dst + 8192, &maps.w1a, s * 224 + 160, ((u - xrot) & 7) * 64, fb);
          }
          if (++slot == NSLOT) { slot = 0; ph ^= 1; }
        }
#pragma unroll 1
        for (int j = 0; j < 3; j++) {
          const uint32_t fb = sb + OFF_FULL + 8 * j;
          mbar_wait(sb + OFF_EMPTY + 8 + 8 * j, 1);
          mbar_expect_tx(fb, j == 1 ? 32768 : 28672);
#pragma unroll
          for (int e = 0; e < 2; e++) {
            const int c = ((sp + 1) & 3) * 128 + ((rank ^ e ^ 1) << 6);
            const uint32_t dst = sb + OFF_X + stage_off(e);
            if (j == 1) {
              tma2d(dst + 14336, &maps.cre, s * 64, c, fb);
              tma2d(dst + 22528, &maps.cim, s * 64, c, fb);
            } else {
              tma2d(dst + j * 15360, &maps.w2, c, s * 224 + j * 56, fb);
            }
          }
        }
#pragma unroll 1
        for (int p = 2; p < 8; p++) {
          const int c = ((sp + 1 + (p >> 1)) & 3) * 128 + (((rank ^ p ^ 1) & 1) << 6);
          const uint32_t fb = sb + OFF_XFULL + 8 * p, dst = sb + OFF_X + stage_off(p);
          if (p == 2 || p > 3) mbar_wait(sb + OFF_EMPTY + (p == 2 ? 40 : (p - 4) * 8), p == 2);
          TS2(0, 32 + p);
          mbar_expect_tx(fb, 45056);
          tma2d(dst, &maps.w2, c, s * 224, fb);
          tma2d(dst + 14336, &maps.cre, s * 64, c, fb);
          tma2d(dst + 22528, &maps.cim, s * 64, c, fb);
          tma2d(dst + 30720, &maps.w2, c, s * 224 + 112, fb);
        }
        TS(2, 2);
      }
    }
  }
}

typedef CUresult (*EncFn)(CUtensorMap*, CUtensorMapDataType, cuuint32_t, void*, const cuuint64_t*, const cuuint64_t*, const cuuint32_t*,
                          const cuuint32_t*, CUtensorMapInterleave, CUtensorMapSwizzle, CUtensorMapL2promotion, CUtensorMapFloatOOBfill);

void encode(EncFn f, CUtensorMap* mp, const void* p, int rank, const cuuint64_t* dims, const cuuint64_t* strides, const cuuint32_t* box, CUtensorMapSwizzle sw) {
  cuuint32_t es[5] = {1, 1, 1, 1, 1};
  f(mp, CU_TENSOR_MAP_DATA_TYPE_BFLOAT16, rank, const_cast<void*>(p), dims, strides, box, es, CU_TENSOR_MAP_INTERLEAVE_NONE, sw,
    CU_TENSOR_MAP_L2_PROMOTION_L2_128B, CU_TENSOR_MAP_FLOAT_OOB_FILL_NONE);
}

}

extern "C" void kernel_launch(void* const* d_in, const int* in_sizes, int n_in, void* d_out, int out_size) {
  typedef const __nv_bfloat16* bp;
  bp x = (bp)d_in[0], lre = (bp)d_in[1], lim = (bp)d_in[2], bre = (bp)d_in[3], bim = (bp)d_in[4], cre = (bp)d_in[5], cim = (bp)d_in[6],
     ldt = (bp)d_in[7], dsk = (bp)d_in[8], w1 = (bp)d_in[10], b1 = (bp)d_in[11], w2 = (bp)d_in[12], b2 = (bp)d_in[13], gw = (bp)d_in[14];
  static EncFn enc = nullptr;
  if (!enc) {
    void* f = nullptr;
    cudaDriverEntryPointQueryResult qr;
    cudaGetDriverEntryPoint("cuTensorMapEncodeTiled", &f, cudaEnableDefault, &qr);
    enc = (EncFn)f;
    cudaFuncSetAttribute(fused_kernel, cudaFuncAttributeMaxDynamicSharedMemorySize, SMEM_BYTES);
  }
  Maps maps;
  {
    cuuint64_t d[5] = {DM, 2, 4, 8, SEQ / 64}, st[4] = {DM * 2, 16 * DM * 2, 2 * DM * 2, 64 * DM * 2};
    cuuint32_t bx[5] = {64, 2, 4, 8, 1};
    encode(enc, &maps.x, x, 5, d, st, bx, CU_TENSOR_MAP_SWIZZLE_128B);
  }
  {
    cuuint64_t d[2] = {DM, DM}, st[1] = {DM * 2};
    cuuint32_t bx[2] = {64, 64};
    encode(enc, &maps.bre, bre, 2, d, st, bx, CU_TENSOR_MAP_SWIZZLE_128B);
    encode(enc, &maps.bim, bim, 2, d, st, bx, CU_TENSOR_MAP_SWIZZLE_128B);
    encode(enc, &maps.cre, cre, 2, d, st, bx, CU_TENSOR_MAP_SWIZZLE_128B);
    encode(enc, &maps.cim, cim, 2, d, st, bx, CU_TENSOR_MAP_SWIZZLE_128B);
  }
  {
    cuuint64_t d[2] = {FF, DM}, st[1] = {FF * 2};
    cuuint32_t bx[2] = {64, 64};
    encode(enc, &maps.w1a, w1, 2, d, st, bx, CU_TENSOR_MAP_SWIZZLE_128B);
    cuuint64_t d3[3] = {32, DM, FF / 32}, st3[2] = {FF * 2, 64};
    cuuint32_t bx3[3] = {32, 64, 3};
    encode(enc, &maps.w1b, w1, 3, d3, st3, bx3, CU_TENSOR_MAP_SWIZZLE_64B);
  }
  {
    cuuint64_t d[2] = {DM, FF}, st[1] = {DM * 2};
    cuuint32_t bx[2] = {64, 112};
    encode(enc, &maps.w2, w2, 2, d, st, bx, CU_TENSOR_MAP_SWIZZLE_128B);
  }
  fused_kernel<<<128, 384, SMEM_BYTES>>>(lre, lim, ldt, dsk, b1, b2, gw, w1, w2, cre, cim, (float*)d_out, maps);
}
```

```cpp
#include <cuda_runtime.h>
#include <cuda_bf16.h>
#include <cuda.h>
#include <stdint.h>

#define MAP 1
#define D0 250
#define D1 500
#define PF 4
#define PFK 5
#define GELUP 1
#define EW 2
#define K1E 1
#define K2E 0
#define QS 1
#define K2G 4
#define FINP 4
#define LBD 300
#define PFS 32
#define SB0 2
#define PFD 2
#define HOLD 0
#define GAP 14
#define FINW 0
#define K0P 33
#define K1P 53
#define TMP2 1
#define W0 1
#define LCK 4
#define GC 3
#define GCUT {0, 6, 6, 12, 18, 24, 26, 29, 32}
#define SC0 4
#define XS 11
#define YS 7
#define C1 5
#define C2 10
#define C3 18
#define TP 9
#define TW 0

namespace {

constexpr int SEQ = 2048, DM = 512, FF = 1792;
constexpr int NSLOT = 6;
constexpr uint32_t OFF_X = 0, OFF_RING = 131072, OFF_MISC = 229376;
constexpr uint32_t OFF_XFULL = OFF_MISC, OFF_FULL = OFF_XFULL + 64, OFF_RBAR = OFF_FULL + 48, OFF_EMPTY = OFF_RBAR + 16, OFF_KBAR = OFF_EMPTY + 48,
                   OFF_GBAR = OFF_KBAR + 16, OFF_LBAR = OFF_GBAR + 8, OFF_CBAR = OFF_LBAR + 8, OFF_EPOCH = OFF_CBAR + 8;
constexpr uint32_t OFF_LC = OFF_MISC + 256;
constexpr uint32_t OFF_GS = OFF_LC;
constexpr uint32_t OFF_DB = OFF_LC + 512;
constexpr uint32_t OFF_CARRY = OFF_LC + 1024;
constexpr uint32_t OFF_DBG = OFF_CARRY + 1024;
constexpr uint32_t SMEM_BYTES = OFF_DBG + 768;
static_assert(SMEM_BYTES <= 232448, "smem");

struct Maps { CUtensorMap x, bre, bim, w1a, w1b, w2, cre, cim; };
__host__ __device__ constexpr uint32_t stage_off(int p) { return 49152 + 45056 * (((p >> 1) & 1) + 2 * (p & 1)); }

__device__ uint4 g_part[16 * 8 * 3 * 1024];
__device__ float2 g_end[8 * 16 * 64];
__device__ unsigned g_gate[SEQ];
__device__ unsigned g_epoch[128];
#define TG(role) do {} while (0)
#define TS2(role, i) do {} while (0)
#define TS(role, i) do {} while (0)
#define TDUMP() do {} while (0)
#define TR(i) do {} while (0)
#define TRD() do {} while (0)

__device__ __forceinline__ void mbar_init(uint32_t bar, uint32_t cnt) { asm volatile("mbarrier.init.shared::cta.b64 [%0], %1;" ::"r"(bar), "r"(cnt)); }
__device__ __forceinline__ void mbar_expect_tx(uint32_t bar, uint32_t bytes) { asm volatile("mbarrier.arrive.expect_tx.shared::cta.b64 _, [%0], %1;" ::"r"(bar), "r"(bytes) : "memory"); }
__device__ __forceinline__ void mbar_arrive(uint32_t bar) { asm volatile("mbarrier.arrive.shared::cta.b64 _, [%0];" ::"r"(bar) : "memory"); }
__device__ __forceinline__ void mbar_arrive_cl(uint32_t cbar) { asm volatile("mbarrier.arrive.shared::cluster.b64 _, [%0];" ::"r"(cbar) : "memory"); }
__device__ __forceinline__ void mbar_wait(uint32_t bar, uint32_t parity) {
  asm volatile(
      "{\n.reg .pred p;\n.reg .u32 c;\n"
      "mbarrier.try_wait.parity.shared::cta.b64 p, [%0], %1;\n"
      "@p bra.uni LAB_DONE;\n"
      "mov.u32 c, 0;\n"
      "LAB_WAIT:\n"
      "mbarrier.try_wait.parity.shared::cta.b64 p, [%0], %1;\n"
      "@p bra.uni LAB_DONE;\n"
      "add.u32 c, c, 1;\nsetp.lt.u32 p, c, 200000;\n@p bra.uni LAB_WAIT;\n"
      "LAB_DONE:\n}" ::"r"(bar), "r"(parity) : "memory");
}
__device__ __forceinline__ void tma2d(uint32_t dst, const CUtensorMap* m, int c0, int c1, uint32_t bar) {
  asm volatile("cp.async.bulk.tensor.2d.shared::cluster.global.mbarrier::complete_tx::bytes [%0], [%1, {%3,%4}], [%2];"
               ::"r"(dst), "l"(m), "r"(bar), "r"(c0), "r"(c1) : "memory");
}
__device__ __forceinline__ void tma3d(uint32_t dst, const CUtensorMap* m, int c0, int c1, int c2, uint32_t bar) {
  asm volatile("cp.async.bulk.tensor.3d.shared::cluster.global.mbarrier::complete_tx::bytes [%0], [%1, {%3,%4,%5}], [%2];"
               ::"r"(dst), "l"(m), "r"(bar), "r"(c0), "r"(c1), "r"(c2) : "memory");
}
__device__ __forceinline__ void tma5d(uint32_t dst, const CUtensorMap* m, int c0, int c4, uint32_t bar) {
  asm volatile("cp.async.bulk.tensor.5d.shared::cluster.global.mbarrier::complete_tx::bytes [%0], [%1, {%3,%5,%5,%5,%4}], [%2];"
               ::"r"(dst), "l"(m), "r"(bar), "r"(c0), "r"(c4), "r"(0) : "memory");
}
__device__ __forceinline__ void tma5d_mc(uint32_t dst, const CUtensorMap* m, int c0, int c4, uint32_t bar) {
  asm volatile("cp.async.bulk.tensor.5d.shared::cluster.global.mbarrier::complete_tx::bytes.multicast::cluster [%0], [%1, {%3,%5,%5,%5,%4}], [%2], %6;"
               ::"r"(dst), "l"(m), "r"(bar), "r"(c0), "r"(c4), "r"(0), "h"((uint16_t)3) : "memory");
}
__device__ __forceinline__ void l2_prefetch(const void* p, uint32_t bytes) { asm volatile("cp.async.bulk.prefetch.L2.global [%0], %1;" ::"l"(p), "r"(bytes) : "memory"); }
__device__ __forceinline__ bool elect_one() {
  uint32_t pred;
  asm volatile("{.reg .pred P; elect.sync _|P, 0xffffffff; selp.u32 %0, 1, 0, P;}" : "=r"(pred));
  return pred != 0;
}
__device__ __forceinline__ void wg_fence() { asm volatile("wgmma.fence.sync.aligned;" ::: "memory"); }
__device__ __forceinline__ void wg_commit() { asm volatile("wgmma.commit_group.sync.aligned;" ::: "memory"); }
template <int N> __device__ __forceinline__ void wg_wait() { asm volatile("wgmma.wait_group.sync.aligned %0;" ::"n"(N) : "memory"); }
__device__ __forceinline__ void pin(float& a) { asm volatile("" : "+f"(a)::"memory"); }
__device__ __forceinline__ void pin(uint32_t& a) { asm volatile("" : "+r"(a)::"memory"); }
template <int N> __device__ __forceinline__ void reg_fence(float (&d)[N]) {
#pragma unroll
  for (int i = 0; i < N; i++) pin(d[i]);
}
__device__ __forceinline__ void bar_sync(int id, int n) { asm volatile("bar.sync %0, %1;" ::"r"(id), "r"(n) : "memory"); }
__device__ __forceinline__ void bar_arrive(int id, int n) { asm volatile("bar.arrive %0, %1;" ::"r"(id), "r"(n) : "memory"); }
constexpr uint32_t DH128 = (1024 >> 4) | (1u << 30), DH64 = (512 >> 4) | (2u << 30);
__host__ __device__ constexpr uint32_t lbo(uint32_t bytes) { return (bytes >> 4) << 20; }
__device__ __forceinline__ uint32_t pack_bf16(float lo, float hi) { uint32_t r; asm("cvt.rn.bf16x2.f32 %0, %1, %2;" : "=r"(r) : "f"(hi), "f"(lo)); return r; }
__device__ __forceinline__ float bf_lo(uint32_t v) { return __uint_as_float(v << 16); }
__device__ __forceinline__ float bf_hi(uint32_t v) { return __uint_as_float(v & 0xffff0000u); }
__device__ __forceinline__ float bf_ld(const __nv_bfloat16* p) { return __bfloat162float(__ldg(p)); }
__device__ __forceinline__ uint32_t late16(uint32_t bar) {
  uint32_t r;
  asm volatile("{.reg .pred p; mbarrier.test_wait.parity.shared::cta.b64 p, [%1], 0; selp.u32 %0, 16, 0, p;}" : "=r"(r) : "r"(bar) : "memory");
  return r;
}
__device__ __forceinline__ float2 lds_f2(uint32_t a) { float2 v; asm volatile("ld.shared.v2.f32 {%0,%1}, [%2];" : "=f"(v.x), "=f"(v.y) : "r"(a)); return v; }
__device__ __forceinline__ uint32_t lds_h(uint32_t a) { uint32_t v; asm volatile("ld.shared.u16 %0, [%1];" : "=r"(v) : "r"(a)); return v; }
__device__ __forceinline__ uint32_t lds_u(uint32_t a) { uint32_t v; asm volatile("ld.shared.u32 %0, [%1];" : "=r"(v) : "r"(a)); return v; }
__device__ __forceinline__ uint4 lds_u4(uint32_t a) { uint4 v; asm volatile("ld.shared.v4.u32 {%0,%1,%2,%3}, [%4];" : "=r"(v.x), "=r"(v.y), "=r"(v.z), "=r"(v.w) : "r"(a)); return v; }
__device__ __forceinline__ void st_b128(uint4* p, uint32_t a, uint32_t b, uint32_t c, uint32_t d) {
  asm volatile("st.relaxed.gpu.global.v4.b32 [%0], {%1,%2,%3,%4};" ::"l"(p), "r"(a), "r"(b), "r"(c), "r"(d) : "memory");
}
__device__ __forceinline__ void ld_b128(const uint4* p, uint32_t& a, uint32_t& b, uint32_t& c, uint32_t& d) {
  asm volatile("{.reg .b64 l, h; .reg .b128 v; ld.relaxed.gpu.global.b128 v, [%4]; mov.b128 {l,h}, v; mov.b64 {%0,%1}, l; mov.b64 {%2,%3}, h;}"
               : "=r"(a), "=r"(b), "=r"(c), "=r"(d) : "l"(p) : "memory");
}
__device__ __forceinline__ float tanh_fast(float x) { float y; asm("tanh.approx.f32 %0, %1;" : "=f"(y) : "f"(x)); return y; }
__device__ __forceinline__ float gelu2(float v) {
  float p = fmaf(v * v, 0.0356774081363f, 0.7978845608029f);
  return fmaf(v, tanh_fast(v * p), v);
}
__device__ __forceinline__ uint32_t bf2_mul(uint32_t a, uint32_t b) { uint32_t r; asm("mul.rn.bf16x2 %0, %1, %2;" : "=r"(r) : "r"(a), "r"(b)); return r; }
__device__ __forceinline__ uint32_t bf2_add(uint32_t a, uint32_t b) { uint32_t r; asm("add.rn.bf16x2 %0, %1, %2;" : "=r"(r) : "r"(a), "r"(b)); return r; }
__device__ __forceinline__ uint32_t bf2_fma(uint32_t a, uint32_t b, uint32_t c) { uint32_t r; asm("fma.rn.bf16x2 %0, %1, %2, %3;" : "=r"(r) : "r"(a), "r"(b), "r"(c)); return r; }
__device__ __forceinline__ uint32_t gelu2_pair(float a, float b) {
  const uint32_t v = pack_bf16(a, b);
  uint32_t t;
  asm("tanh.approx.bf16x2 %0, %1;" : "=r"(t) : "r"(bf2_fma(v, bf2_fma(bf2_mul(v, v), 0x3d123d12u, 0xbe4fbe4fu), v)));
  return bf2_fma(v, t, v);
}
struct cplx { float re, im; };
__device__ __forceinline__ cplx cmul(cplx a, cplx b) { return {fmaf(a.re, b.re, -a.im * b.im), fmaf(a.re, b.im, a.im * b.re)}; }
__device__ __forceinline__ cplx cfma(cplx a, cplx b, cplx c) {
  return {fmaf(a.re, b.re, fmaf(-a.im, b.im, c.re)), fmaf(a.re, b.im, fmaf(a.im, b.re, c.im))};
}
__device__ __forceinline__ cplx make_lam(float lre, float lim, float ldt) {
  float dt = __bfloat162float(__float2bfloat16_rn(expf(ldt)));
  float mag = expf(dt * lre), sn, cs;
  sincospif(dt * lim * 0.31830988618379067f, &sn, &cs);
  return {mag * cs, mag * sn};
}

template<int TA,int TB,uint32_t AH,uint32_t BH> __device__ __forceinline__ void wgmma_n64_ss(float (&d)[32], uint32_t al, uint32_t ao, uint32_t bl, uint32_t bo, int scale_d){
  asm volatile("{.reg .pred p; .reg .b32 t, v; .reg .b64 da, db; setp.ne.b32 p, %36, 0; add.u32 t, %32, %33; mov.b64 da, {t, %39}; add.u32 v, %34, %35; mov.b64 db, {v, %40};\n"
   "wgmma.mma_async.sync.aligned.m64n64k16.f32.bf16.bf16 {%0,%1,%2,%3,%4,%5,%6,%7,%8,%9,%10,%11,%12,%13,%14,%15,%16,%17,%18,%19,%20,%21,%22,%23,%24,%25,%26,%27,%28,%29,%30,%31}, da, db, p, 1, 1, %37, %38;}"
   : "+f"(d[0]),"+f"(d[1]),"+f"(d[2]),"+f"(d[3]),"+f"(d[4]),"+f"(d[5]),"+f"(d[6]),"+f"(d[7]),"+f"(d[8]),"+f"(d[9]),"+f"(d[10]),"+f"(d[11]),"+f"(d[12]),"+f"(d[13]),"+f"(d[14]),"+f"(d[15]),"+f"(d[16]),"+f"(d[17]),"+f"(d[18]),"+f"(d[19]),"+f"(d[20]),"+f"(d[21]),"+f"(d[22]),"+f"(d[23]),"+f"(d[24]),"+f"(d[25]),"+f"(d[26]),"+f"(d[27]),"+f"(d[28]),"+f"(d[29]),"+f"(d[30]),"+f"(d[31])
   : "r"(al),"r"(ao >> 4),"r"(bl),"r"(bo >> 4),"r"(scale_d),"n"(TA),"n"(TB),"n"(AH),"n"(BH));
}
template<int TB,uint32_t BH> __device__ __forceinline__ void wgmma_n64_rs(float (&d)[32], uint32_t a0,uint32_t a1,uint32_t a2,uint32_t a3, uint32_t bl, uint32_t bo, int scale_d){
  asm volatile("{.reg .pred p; .reg .b32 t; .reg .b64 db; setp.ne.b32 p, %38, 0; add.u32 t, %36, %37; mov.b64 db, {t, %40};\n"
   "wgmma.mma_async.sync.aligned.m64n64k16.f32.bf16.bf16 {%0,%1,%2,%3,%4,%5,%6,%7,%8,%9,%10,%11,%12,%13,%14,%15,%16,%17,%18,%19,%20,%21,%22,%23,%24,%25,%26,%27,%28,%29,%30,%31}, {%32,%33,%34,%35}, db, p, 1, 1, %39;}"
   : "+f"(d[0]),"+f"(d[1]),"+f"(d[2]),"+f"(d[3]),"+f"(d[4]),"+f"(d[5]),"+f"(d[6]),"+f"(d[7]),"+f"(d[8]),"+f"(d[9]),"+f"(d[10]),"+f"(d[11]),"+f"(d[12]),"+f"(d[13]),"+f"(d[14]),"+f"(d[15]),"+f"(d[16]),"+f"(d[17]),"+f"(d[18]),"+f"(d[19]),"+f"(d[20]),"+f"(d[21]),"+f"(d[22]),"+f"(d[23]),"+f"(d[24]),"+f"(d[25]),"+f"(d[26]),"+f"(d[27]),"+f"(d[28]),"+f"(d[29]),"+f"(d[30]),"+f"(d[31])
   : "r"(a0),"r"(a1),"r"(a2),"r"(a3),"r"(bl),"r"(bo >> 4),"r"(scale_d),"n"(TB),"n"(BH));
}
template<int TA,int TB,uint32_t AH,uint32_t BH> __device__ __forceinline__ void wgmma_n96_ss(float (&d)[48], uint32_t al, uint32_t ao, uint32_t bl, uint32_t bo, int scale_d){
  asm volatile("{.reg .pred p; .reg .b32 t, v; .reg .b64 da, db; setp.ne.b32 p, %52, 0; add.u32 t, %48, %49; mov.b64 da, {t, %55}; add.u32 v, %50, %51; mov.b64 db, {v, %56};\n"
   "wgmma.mma_async.sync.aligned.m64n96k16.f32.bf16.bf16 {%0,%1,%2,%3,%4,%5,%6,%7,%8,%9,%10,%11,%12,%13,%14,%15,%16,%17,%18,%19,%20,%21,%22,%23,%24,%25,%26,%27,%28,%29,%30,%31,%32,%33,%34,%35,%36,%37,%38,%39,%40,%41,%42,%43,%44,%45,%46,%47}, da, db, p, 1, 1, %53, %54;}"
   : "+f"(d[0]),"+f"(d[1]),"+f"(d[2]),"+f"(d[3]),"+f"(d[4]),"+f"(d[5]),"+f"(d[6]),"+f"(d[7]),"+f"(d[8]),"+f"(d[9]),"+f"(d[10]),"+f"(d[11]),"+f"(d[12]),"+f"(d[13]),"+f"(d[14]),"+f"(d[15]),"+f"(d[16]),"+f"(d[17]),"+f"(d[18]),"+f"(d[19]),"+f"(d[20]),"+f"(d[21]),"+f"(d[22]),"+f"(d[23]),"+f"(d[24]),"+f"(d[25]),"+f"(d[26]),"+f"(d[27]),"+f"(d[28]),"+f"(d[29]),"+f"(d[30]),"+f"(d[31]),"+f"(d[32]),"+f"(d[33]),"+f"(d[34]),"+f"(d[35]),"+f"(d[36]),"+f"(d[37]),"+f"(d[38]),"+f"(d[39]),"+f"(d[40]),"+f"(d[41]),"+f"(d[42]),"+f"(d[43]),"+f"(d[44]),"+f"(d[45]),"+f"(d[46]),"+f"(d[47])
   : "r"(al),"r"(ao >> 4),"r"(bl),"r"(bo >> 4),"r"(scale_d),"n"(TA),"n"(TB),"n"(AH),"n"(BH));
}
template<int TA,int TB,uint32_t AH,uint32_t BH> __device__ __forceinline__ void wgmma_n128_ss(float (&d)[64], uint32_t al, uint32_t ao, uint32_t bl, uint32_t bo, int scale_d){
  asm volatile("{.reg .pred p; .reg .b32 t, v; .reg .b64 da, db; setp.ne.b32 p, %68, 0; add.u32 t, %64, %65; mov.b64 da, {t, %71}; add.u32 v, %66, %67; mov.b64 db, {v, %72};\n"
   "wgmma.mma_async.sync.aligned.m64n128k16.f32.bf16.bf16 {%0,%1,%2,%3,%4,%5,%6,%7,%8,%9,%10,%11,%12,%13,%14,%15,%16,%17,%18,%19,%20,%21,%22,%23,%24,%25,%26,%27,%28,%29,%30,%31,%32,%33,%34,%35,%36,%37,%38,%39,%40,%41,%42,%43,%44,%45,%46,%47,%48,%49,%50,%51,%52,%53,%54,%55,%56,%57,%58,%59,%60,%61,%62,%63}, da, db, p, 1, 1, %69, %70;}"
   : "+f"(d[0]),"+f"(d[1]),"+f"(d[2]),"+f"(d[3]),"+f"(d[4]),"+f"(d[5]),"+f"(d[6]),"+f"(d[7]),"+f"(d[8]),"+f"(d[9]),"+f"(d[10]),"+f"(d[11]),"+f"(d[12]),"+f"(d[13]),"+f"(d[14]),"+f"(d[15]),"+f"(d[16]),"+f"(d[17]),"+f"(d[18]),"+f"(d[19]),"+f"(d[20]),"+f"(d[21]),"+f"(d[22]),"+f"(d[23]),"+f"(d[24]),"+f"(d[25]),"+f"(d[26]),"+f"(d[27]),"+f"(d[28]),"+f"(d[29]),"+f"(d[30]),"+f"(d[31]),"+f"(d[32]),"+f"(d[33]),"+f"(d[34]),"+f"(d[35]),"+f"(d[36]),"+f"(d[37]),"+f"(d[38]),"+f"(d[39]),"+f"(d[40]),"+f"(d[41]),"+f"(d[42]),"+f"(d[43]),"+f"(d[44]),"+f"(d[45]),"+f"(d[46]),"+f"(d[47]),"+f"(d[48]),"+f"(d[49]),"+f"(d[50]),"+f"(d[51]),"+f"(d[52]),"+f"(d[53]),"+f"(d[54]),"+f"(d[55]),"+f"(d[56]),"+f"(d[57]),"+f"(d[58]),"+f"(d[59]),"+f"(d[60]),"+f"(d[61]),"+f"(d[62]),"+f"(d[63])
   : "r"(al),"r"(ao >> 4),"r"(bl),"r"(bo >> 4),"r"(scale_d),"n"(TA),"n"(TB),"n"(AH),"n"(BH));
}

__global__ void __cluster_dims__(2, 1, 1) __launch_bounds__(384, 1)
fused_kernel(const __nv_bfloat16* __restrict__ lam_re, const __nv_bfloat16* __restrict__ lam_im, const __nv_bfloat16* __restrict__ log_dt,
             const __nv_bfloat16* __restrict__ dskip, const __nv_bfloat16* __restrict__ b1, const __nv_bfloat16* __restrict__ b2,
             const __nv_bfloat16* __restrict__ gate_w, const __nv_bfloat16* __restrict__ pf_w1, const __nv_bfloat16* __restrict__ pf_w2,
             const __nv_bfloat16* __restrict__ pf_cre, const __nv_bfloat16* __restrict__ pf_cim, float* __restrict__ out,
             const __grid_constant__ Maps maps) {
  extern __shared__ __align__(1024) unsigned char smem_raw[];
  const uint32_t sb = (uint32_t)__cvta_generic_to_shared(smem_raw);
  const int b = blockIdx.x;
  const int rank = b & 1, cl = b >> 1;
  const int sp = (cl & 1) | ((cl >> 2) & 2), m = ((cl >> 1) & 3) | ((cl >> 4) << 2);
  const int s = sp * 2 + rank;
  const int warp = __shfl_sync(0xffffffffu, (int)(threadIdx.x >> 5), 0);
  const int lane = threadIdx.x & 31;
  const int xrot = 9 - 2 * sp;

  if (elect_one()) {
    if (warp == 8) TS(2, 0);
    if (warp > 8) {
      asm volatile("prefetch.tensormap [%0];" ::"l"(&maps.x + (warp - 9)) : "memory");
      mbar_init(sb + OFF_GBAR + 8 * (warp - 9), warp < 11 ? 64 : 96);
    }
    const uint32_t c = warp < 8 ? 1 : warp < 11 ? 8 : 4, bar = sb + OFF_XFULL + 16 * warp;
    mbar_init(bar, c);
    if ((warp & 11) == 0) {
      mbar_expect_tx(bar, 16384);
      if (warp == 0) {
        tma5d(sb + OFF_X + (xrot & 7) * 16384, &maps.x, 0, 2 * m, bar);
        tma5d(sb + OFF_X + (xrot & 7) * 16384 + 8192, &maps.x, 0, 2 * m + 1, bar);
        TS(2, 3);
      } else {
        tma2d(sb + OFF_RING, &maps.bre, 0, s * 64, bar);
        tma2d(sb + OFF_RING + 8192, &maps.bim, 0, s * 64, bar);
        TS(2, 4);
      }
    }
    mbar_init(bar + 8, c);
    asm volatile("fence.mbarrier_init.release.cluster;" ::: "memory");
  }
  __syncwarp();
  asm volatile("barrier.cluster.arrive.relaxed.aligned;" ::: "memory");

  if (warp < 8) {
    const int wg = warp >> 2, w = warp & 3, q = lane & 3, gr = lane >> 2;
    uint32_t bv[28];
#pragma unroll
    for (int j = 0; j < 28; j++) bv[j] = __ldg(reinterpret_cast<const uint32_t*>(b1 + s * 224 + j * 8) + q);
    asm volatile("setmaxnreg.inc.sync.aligned.u32 224;");
    asm volatile("barrier.cluster.wait.aligned;" ::: "memory");
    TS(wg, 0);
    auto release = [&](int slot) { if (lane == 0) mbar_arrive(sb + OFF_EMPTY + 8 * slot); };
    const uint32_t xw = sb + OFF_X + wg * 8192, fullb = sb + OFF_FULL;
    const uint32_t dxw = (xw & 0x3FFFF) >> 4, dring = ((sb + OFF_RING) & 0x3FFFF) >> 4;

    float ure[32], uim[32], aa[64], ab[48];
    cplx lam[2], coef[2], l16[2], l32[2], lq[2], pre[2], e[2];
    uint32_t sh16, mhi;

    auto bias = [&](int c) {
#pragma unroll
      for (int j = c * 7; j < c * 7 + 7; j++) {
        pin(bv[j]);
        float* d = j < 16 ? aa + 4 * j : ab + 4 * (j - 16);
        d[0] = d[2] = __uint_as_float(bv[j] << sh16); d[1] = d[3] = __uint_as_float(bv[j] & mhi);
        pin(d[0]); pin(d[1]); pin(d[2]); pin(d[3]);
      }
    };
#pragma unroll
    for (int kb = 0; kb < 8; kb++) {
      const int slot = kb % NSLOT;
      mbar_wait(sb + OFF_XFULL + 8 * kb, 0);
      if (kb == 0) TS(wg, 18);
      mbar_wait(fullb + 8 * slot, (kb / NSLOT) & 1);
      TS2(2, kb);
      if (kb == 0) TS(wg, 1);
      if (kb == SB0) { sh16 = late16(sb + OFF_XFULL); mhi = 0xffffffffu << sh16; }
      if (kb == LCK) {
        mbar_wait(sb + OFF_LBAR, 0);
#pragma unroll
        for (int h = 0; h < 2; h++) {
          const uint4 v = lds_u4(sb + OFF_LC + (w * 16 + gr + 8 * h) * 16);
          lam[h] = cplx{__uint_as_float(v.x), __uint_as_float(v.y)};
          coef[h] = cplx{__uint_as_float(v.z), __uint_as_float(v.w)};
        }
      }
      wg_fence();
      const uint32_t dxa = dxw + ((kb + xrot) & 7) * 1024;
#pragma unroll
      for (int kk = 0; kk < 4; kk++) {
        wgmma_n64_ss<0, 0, DH128, DH128>(ure, dring, slot * 16384 + kk * 32, dxa, kk * 32, (kb | kk) != 0);
        wgmma_n64_ss<0, 0, DH128, DH128>(uim, dring, slot * 16384 + 8192 + kk * 32, dxa, kk * 32, (kb | kk) != 0);
      }
      wg_commit();
      if (kb > 0) { wg_wait<1>(); release((kb - 1) % NSLOT); }
      if (kb >= SB0 && kb < SB0 + 3) bias(kb - SB0);
      if (kb == 6) {
#pragma unroll
        for (int h = 0; h < 2; h++) {
          pin(lam[h].re); pin(lam[h].im);
          cplx t = cmul(lam[h], lam[h]); t = cmul(t, t); t = cmul(t, t);
          l16[h] = cmul(t, t);
          pin(l16[h].re); pin(l16[h].im);
        }
      }
      if (kb == 7) {
#pragma unroll
        for (int h = 0; h < 2; h++) {
          pin(l16[h].re); pin(l16[h].im);
          l32[h] = cmul(l16[h], l16[h]);
          const cplx a = (q & 1) ? l16[h] : cplx{1.f, 0.f}, c = (q & 2) ? l32[h] : cplx{1.f, 0.f};
          lq[h] = cmul(cmul(a, c), coef[h]);
          pin(lq[h].re); pin(lq[h].im);
        }
      }
    }
    TS(wg, 2);
    auto scale_u = [&](int i0, int i1) {
#pragma unroll
      for (int i = 0; i < 32; i++) if (i >= i0 && i < i1) {
        pin(ure[i]); pin(uim[i]);
        const cplx v = cmul(coef[(i >> 1) & 1], cplx{ure[i], uim[i]});
        ure[i] = v.re; uim[i] = v.im;
        pin(ure[i]); pin(uim[i]);
      }
    };
#pragma unroll
    for (int kb = 0; kb < 8; kb++) {
      const int u = 8 + kb, slot = u % NSLOT;
      mbar_wait(fullb + 8 * slot, (u / NSLOT) & 1);
      wg_fence();
      const uint32_t dxa = dxw + ((kb + xrot) & 7) * 1024;
#pragma unroll
      for (int kk = 0; kk < 4; kk++)
        wgmma_n128_ss<0, 1, DH128, DH128>(aa, dxa, kk * 32, dring, slot * 16384 + kk * 2048 + lbo(8192), 1);
      wg_commit();
      if (SB0 >= 0 && kb == 0) bias(3);
      wg_wait<1>();
      release((u - 1) % NSLOT);
      if (kb == 0) {
        reg_fence(ure); reg_fence(uim);
#pragma unroll
        for (int h = 0; h < 2; h++) e[h] = cplx{ure[2 * h], uim[2 * h]};
      }
      if (kb == 0 || kb == 2) {
#pragma unroll
        for (int t = 1; t < 16; t++) if ((t < 8) == (kb == 0))
#pragma unroll
          for (int h = 0; h < 2; h++) { const int i = 4 * (t >> 1) + 2 * h + (t & 1); e[h] = cfma(lam[h], e[h], cplx{ure[i], uim[i]}); }
#pragma unroll
        for (int h = 0; h < 2; h++) { pin(e[h].re); pin(e[h].im); }
      } else if (kb == 3) {
#pragma unroll
        for (int h = 0; h < 2; h++) {
          cplx y = {__shfl_up_sync(0xffffffffu, e[h].re, 1, 4), __shfl_up_sync(0xffffffffu, e[h].im, 1, 4)};
          if (q >= 1) e[h] = cfma(l16[h], y, e[h]);
          y = cplx{__shfl_up_sync(0xffffffffu, e[h].re, 2, 4), __shfl_up_sync(0xffffffffu, e[h].im, 2, 4)};
          if (q >= 2) e[h] = cfma(l32[h], y, e[h]);
        }
        if (q == 3) {
#pragma unroll
          for (int h = 0; h < 2; h++)
            asm volatile("st.shared.v2.f32 [%0], {%1,%2};" ::"r"(sb + OFF_CARRY + wg * 512 + (w * 16 + gr + 8 * h) * 8), "f"(e[h].re), "f"(e[h].im) : "memory");
          mbar_arrive(sb + OFF_GBAR);
        }
#pragma unroll
        for (int h = 0; h < 2; h++) {
          const cplx y = {__shfl_up_sync(0xffffffffu, e[h].re, 1, 4), __shfl_up_sync(0xffffffffu, e[h].im, 1, 4)};
          pre[h] = (q >= 1) ? cmul(coef[h], y) : cplx{0.f, 0.f};
          pin(pre[h].re); pin(pre[h].im);
        }
        TS(wg, 3);
      } else if (kb > 3) {
        scale_u((kb - 4) * 8, (kb - 3) * 8);
      }
    }
    TS(wg, 4);
    uint32_t H[56], hf[32];
    cplx hst[2];
    const uint32_t hst_addr = xw + (w * 16 + (lane & 15)) * 128 + (((lane >> 4) ^ (lane & 7)) << 4);
    const uint32_t him = (2 - rank) * 16384;
    uint32_t peer;
    asm volatile("mapa.shared::cluster.u32 %0, %1, %2;" : "=r"(peer) : "r"(sb), "r"(rank ^ 1));
    auto credit = [&]() { if (lane == 0) mbar_arrive_cl(peer + OFF_KBAR + wg * 8); };
#pragma unroll
    for (int kb = 0; kb < 8; kb++) {
      const int u = 16 + kb, slot = u % NSLOT;
      mbar_wait(fullb + 8 * slot, (u / NSLOT) & 1);
      wg_fence();
#pragma unroll
      for (int kk = 0; kk < 4; kk++)
        wgmma_n96_ss<0, 1, DH128, DH64>(ab, dxw, kb * 16384 + kk * 32, dring, slot * 16384 + kk * 1024 + lbo(4096), 1);
      wg_commit();
      wg_wait<1>();
      release((u - 1) % NSLOT);
      if (kb != 1) {
        constexpr int cut[9] = GCUT;
#pragma unroll
        for (int i = 0; i < 32; i++) if (i >= cut[kb] && i < cut[kb + 1]) {
          pin(aa[2 * i]); pin(aa[2 * i + 1]);
          H[i] = gelu2_pair(aa[2 * i], aa[2 * i + 1]);
          pin(H[i]);
        }
      }
      if (kb >= SC0 && kb < SC0 + 4) {
        if (kb == SC0) {
          TS(wg, 5);
          mbar_wait(sb + OFF_CBAR, 0);
          TS(wg, 6);
#pragma unroll
          for (int h = 0; h < 2; h++) {
            const float2 c = lds_f2(sb + OFF_CARRY + wg * 512 + (w * 16 + gr + 8 * h) * 8);
            hst[h] = cfma(lq[h], cplx{c.x, c.y}, pre[h]);
          }
        }
        const int j0 = (kb - SC0) * 2;
        uint32_t rr[4], ri[4];
#pragma unroll
        for (int jj = 0; jj < 2; jj++) {
          const int j = j0 + jj;
          const uint32_t g2 = lds_u(sb + OFF_GS + (wg * 64 + j * 8 + q * 2) * 2);
#pragma unroll
          for (int h = 0; h < 2; h++) {
            const int i = 4 * j + 2 * h;
            const cplx h0 = cfma(lam[h], hst[h], cplx{ure[i], uim[i]});
            hst[h] = cfma(lam[h], h0, cplx{ure[i + 1], uim[i + 1]});
            rr[jj * 2 + h] = bf2_mul(pack_bf16(h0.re, hst[h].re), g2);
            ri[jj * 2 + h] = bf2_mul(pack_bf16(h0.im, hst[h].im), g2 ^ 0x80008000u);
          }
        }
        const uint32_t a = hst_addr ^ (j0 << 4);
        asm volatile("stmatrix.sync.aligned.m8n8.x4.shared.b16 [%0], {%1,%2,%3,%4};" ::"r"(a), "r"(rr[0]), "r"(rr[1]), "r"(rr[2]), "r"(rr[3]) : "memory");
        asm volatile("stmatrix.sync.aligned.m8n8.x4.shared.b16 [%0], {%1,%2,%3,%4};" ::"r"(a + him), "r"(ri[0]), "r"(ri[1]), "r"(ri[2]), "r"(ri[3]) : "memory");
      }
    }
    TS(wg, 7);

    uint4* const psend = g_part + (size_t)(m * 8 + rank) * 3072 + warp * 128 + lane;
    const uint4* const precv = g_part + (size_t)(m * 8 + s) * 3072 + warp * 128 + lane;
    const uint32_t pbuf = OFF_X + warp * 2048 + lane * 16;
    const uint32_t dx0 = ((sb + OFF_X) & 0x3FFFF) >> 4;
    float o[32], fin[32], rho[2];
    uint32_t tr[8];
    uint32_t r0[16], pt[16], sum[16], tag;
    auto recv_issue = [&](uint32_t (&r)[16], int k) {
#pragma unroll
      for (int i = 0; i < 4; i++) ld_b128(precv + k * 1024 + i * 32, r[4 * i], r[4 * i + 1], r[4 * i + 2], r[4 * i + 3]);
    };
    auto stale = [&](uint32_t (&r)[16]) {
      uint32_t t0, t1, r_;
      asm("lop3.b32 %0, %1, %2, %3, 0x7e;" : "=r"(t0) : "r"(r[0]), "r"(r[4]), "r"(tag));
      asm("lop3.b32 %0, %1, %2, %3, 0x7e;" : "=r"(t1) : "r"(r[8]), "r"(r[12]), "r"(tag));
      asm volatile("{.reg .pred p; .reg .b32 t; lop3.b32 t, %1, %2, 1, 0xa8; setp.ne.u32 p, t, 0; vote.sync.any.pred p, p, 0xffffffff; selp.u32 %0, 1, 0, p;}" : "=r"(r_) : "r"(t0), "r"(t1));
      return r_ != 0;
    };
    auto recv_check = [&](uint32_t (&r)[16], int k) {
      if (__builtin_expect(stale(r), 0)) {
        int tries = 0;
#pragma unroll 1
        do { recv_issue(r, k); } while (stale(r) && ++tries < 200000);
      }
    };
    auto gelu_b = [&](int i0, int i1) {
#pragma unroll
      for (int i = i0; i < i1; i++) {
        pin(ab[2 * i]); pin(ab[2 * i + 1]);
        H[32 + i] = gelu2_pair(ab[2 * i], ab[2 * i + 1]);
        pin(H[32 + i]);
      }
    };
    auto step = [&](float (&d)[32], int p, int k, int acc) {
      const uint32_t wo = stage_off(p);
      if (k >= 7 && k < 15) {
        const int kk = k - 7;
        wgmma_n64_rs<0, DH128>(d, hf[4 * kk], hf[4 * kk + 1], hf[4 * kk + 2], hf[4 * kk + 3], dx0, wo + 14336 + (kk >> 2) * 8192 + (kk & 3) * 32, 1);
      } else {
        const int kk = k < 7 ? k : k - 8;
        wgmma_n64_rs<1, DH128>(d, H[4 * kk], H[4 * kk + 1], H[4 * kk + 2], H[4 * kk + 3], dx0, wo + (kk / 7) * 30720 + (kk % 7) * 2048, k != 0 || acc);
      }
    };
    auto mma = [&](float (&d)[32], int p, int k0, int k1, int acc) {
      wg_fence();
#pragma unroll
      for (int k = k0; k < k1; k++) step(d, p, k, acc);
      wg_commit();
    };
    auto send_peer = [&]() {
#pragma unroll
      for (int i = 0; i < 4; i++)
        asm volatile("st.async.shared::cluster.mbarrier::complete_tx::bytes.v4.b32 [%0], {%1,%2,%3,%4}, [%5];" ::"r"(peer + pbuf + i * 512),
                     "r"(pack_bf16(o[8 * i], o[8 * i + 1])), "r"(pack_bf16(o[8 * i + 2], o[8 * i + 3])), "r"(pack_bf16(o[8 * i + 4], o[8 * i + 5])),
                     "r"(pack_bf16(o[8 * i + 6], o[8 * i + 7])), "r"(peer + OFF_RBAR + wg * 8) : "memory");
    };
    auto recv_peer = [&](int k) {
      mbar_wait(sb + OFF_RBAR + wg * 8, k & 1);
#pragma unroll
      for (int i = 0; i < 4; i++) { const uint4 v = lds_u4(sb + pbuf + i * 512); pt[4 * i] = v.x; pt[4 * i + 1] = v.y; pt[4 * i + 2] = v.z; pt[4 * i + 3] = v.w; }
    };
    auto send_owner = [&](float (&d)[32], int k) {
#pragma unroll
      for (int i = 0; i < 4; i++) {
#pragma unroll
        for (int c = 4 * i; c < 4 * i + 4; c++) pt[c] = bf2_add(pt[c], pack_bf16(d[2 * c], d[2 * c + 1]));
        asm("lop3.b32 %0, %0, 1, %1, 0xb8;" : "+r"(pt[4 * i]) : "r"(tag));
        st_b128(psend + (((sp + 1 + k) & 3) * 6 + k) * 1024 + i * 32, pt[4 * i], pt[4 * i + 1], pt[4 * i + 2], pt[4 * i + 3]);
      }
      __syncwarp();
      credit();
    };
    auto load_fin = [&]() {
      mbar_wait(sb + OFF_LBAR, 1);
#pragma unroll
      for (int j = 0; j < 8; j++) {
        const uint4 v = lds_u4(sb + pbuf + 16384 + (j >> 2) * 16384 + (j & 3) * 512);
        fin[4 * j] = __uint_as_float(v.x); fin[4 * j + 1] = __uint_as_float(v.y); fin[4 * j + 2] = __uint_as_float(v.z); fin[4 * j + 3] = __uint_as_float(v.w);
      }
    };
    auto ldk = [&](int pos) { if (pos == K0P) recv_issue(sum, 0); if (pos == K1P) recv_issue(r0, 1); };
    auto arm = [&]() { if ((threadIdx.x & 127) == 0) mbar_expect_tx(sb + OFF_RBAR + wg * 8, 8192); };
#pragma unroll
    for (int p = 0; p < 8; p++) {
      if (p == 0) {
        mbar_wait(fullb, 0);
        mma(o, 0, 0, 4, 0);
        wg_wait<1>(); release(5);
        gelu_b(0, C1);
        mma(fin, 1, 0, 4, 0);
        bar_sync(1 + wg, 128);
        {
          const uint32_t ha = xw + ((lane >> 4) * 8 + (lane & 7)) * 128 + (((2 * w + ((lane >> 3) & 1)) ^ (lane & 7)) << 4);
#pragma unroll
          for (int kk = 0; kk < 8; kk++)
            asm volatile("ldmatrix.sync.aligned.m8n8.x4.trans.shared.b16 {%0,%1,%2,%3}, [%4];" : "=r"(hf[4 * kk]), "=r"(hf[4 * kk + 1]), "=r"(hf[4 * kk + 2]), "=r"(hf[4 * kk + 3])
                         : "r"(ha + (kk >> 2) * him + (kk & 3) * 2048) : "memory");
        }
        gelu_b(C1, C2);
        mma(o, 0, 4, 7, 0); if (YS > 4) mma(fin, 1, 4, YS, 0);
        gelu_b(C2, C3);
        mbar_wait(fullb + 8, 0);
        mma(o, 0, 7, XS, 0);
        credit();
        gelu_b(C3, 24);
        mbar_wait(fullb + 16, 0);
        if (wg == 1) bar_sync(4, 256);
        mma(o, 0, XS, 22, 0);
      } else {
        TR(0);
        if (EW == 0 || (EW == 1 && (p & 1))) mbar_wait(sb + OFF_XFULL + 8 * p, 1);
        TR(1);
        bar_sync(3 + wg, 256);
        if (p == 1) mma(fin, 1, YS, 22, 0);
        else if (p < 7) mma(o, p, 0, 22, 0);
        else if (GAP == 0) mma(fin, p, 0, 22, 1);
        else {
          mma(fin, p, 0, GAP, 1);
          recv_peer(3);
          tag = lds_u(sb + OFF_EPOCH);
          mma(fin, p, GAP, 22, 1);
        }
      }
      if (p < 7 || wg == 0) bar_arrive(4 - wg, 256);
      TR(2);
      if (p != TP) TS(wg, 8 + p);
      if (p > 0 && p < 7 && (EW == 2 || (EW == 1 && (p & 1)))) mbar_wait(sb + OFF_XFULL + 8 * (p + 1), 1);
      ldk(10 * p);
      if ((p & 1) == 0) {
        arm();
        if (p == 6) {
          mbar_wait(sb + OFF_EMPTY + 32, 0);
          tag = lds_u(sb + OFF_EPOCH);
          recv_check(sum, 0); recv_check(r0, 1);
#pragma unroll
          for (int i = 0; i < 16; i++) sum[i] = bf2_add(sum[i], r0[i]);
        }
        TR(3);
        mbar_wait(sb + OFF_KBAR + wg * 8, (p >> 1) & 1);
        TR(4);
      } else {
        if (p == 1 || (p == 7 && GAP == 0)) tag = lds_u(sb + OFF_EPOCH);
        TR(3);
        if (p < 7 || GAP == 0) recv_peer(p >> 1);
        TR(4);
        if (p == 7) {
          recv_check(r0, 2);
#pragma unroll
          for (int i = 0; i < 16; i++) sum[i] = bf2_add(sum[i], bf2_add(r0[i], pt[i]));
        }
      }
      if (p == FINP && !FINW) load_fin();
      ldk(10 * p + 1);
      TR(5);
      wg_wait<0>();
      TR(6);
      if (p < 5) release(p);
      if (p < 7 && p != 1) reg_fence(o); else reg_fence(fin);
      ldk(10 * p + 2);
      if ((p & 1) == 0) {
        if (p == 6) recv_issue(r0, 2);
        send_peer();
        if (p == FINP && FINW) load_fin();
      } else if (p < 7) {
        if (p == 1) send_owner(fin, 0); else send_owner(o, p >> 1);
      }
      ldk(10 * p + 3);
      if (p == 2) {
#pragma unroll
        for (int h = 0; h < 2; h++) { rho[h] = __fdividef(2.f, 4.f + bf_lo(lds_h(sb + OFF_GS + (wg * 64 + w * 16 + gr + 8 * h) * 2))); pin(rho[h]); }
      }
      TR(7);
    }
    {
      TS(wg, 16);
      const uint32_t tb = sb + OFF_X + stage_off(0) + warp * 4096;
      const uint32_t ta = tb + gr * 256 + ((gr & 3) << 5) + q * 8;
      const uint32_t la = tb + (lane >> 3) * 256 + (((lane & 7) << 4) ^ ((lane >> 3) << 5));
      float* op = out + (size_t)(m * 128 + wg * 64 + (lane >> 4) * 16 + w * 4 + ((lane >> 3) & 1)) * DM + s * 64 + (lane & 7) * 4;
#pragma unroll
      for (int qq = 0; qq < 4; qq += QS) {
#pragma unroll
        for (int qt = qq; qt < qq + QS; qt++) {
          const int h = qt & 1, ch = qt >> 1;
#pragma unroll
          for (int j = 0; j < 4; j++) {
            const int i = ch * 8 + j * 2 + h;
            asm volatile("st.shared.v2.f32 [%0], {%1,%2};" ::"r"((ta ^ (j << 5)) + h * 2048 + ch * 128),
                         "f"((fin[2 * i] + bf_lo(sum[i])) * rho[h]), "f"((fin[2 * i + 1] + bf_hi(sum[i])) * rho[h]) : "memory");
          }
        }
        __syncwarp();
#pragma unroll
        for (int qt = qq; qt < qq + QS; qt++) {
          const int h = qt & 1, ch = qt >> 1;
#pragma unroll
          for (int r = 0; r < 2; r++)
            *reinterpret_cast<uint4*>(op + (r * 32 + h * 2) * DM + ch * 32) = lds_u4(la + (h * 2 + r) * 1024 + ch * 128);
        }
      }
      if (threadIdx.x == 128) g_epoch[b] = tag;
      TS(wg, 17); TG(wg); TRD(); TDUMP();
    }
  } else {
    asm volatile("setmaxnreg.dec.sync.aligned.u32 56;");
    int wsel = warp;
    asm("" : "+r"(wsel));
    if (wsel > 8) {
      if (warp != 11) {
        const int t = threadIdx.x - 288;
        unsigned par;
        asm volatile("ld.relaxed.gpu.global.u32 %0, [%1];" : "=r"(par) : "l"(g_epoch + b) : "memory");
        const float pr = bf_ld(lam_re + s * 64 + t), pi = bf_ld(lam_im + s * 64 + t), pd = bf_ld(log_dt + s * 64 + t);
        asm volatile("barrier.cluster.wait.aligned;" ::: "memory");
        par = __shfl_sync(0xffffffffu, (par + 1) & 1, 0);
        cplx l64 = make_lam(pr, pi, pd);
        {
          const float inv = __fdividef(1.f, fmaf(pr, pr, pi * pi));
          const cplx cf = cmul(cplx{l64.re - 1.f, l64.im}, cplx{pr * inv, -pi * inv});
          asm volatile("st.shared.v4.f32 [%0], {%1,%2,%3,%4};" ::"r"(sb + OFF_LC + t * 16), "f"(l64.re), "f"(l64.im), "f"(cf.re), "f"(cf.im) : "memory");
          mbar_arrive(sb + OFF_LBAR);
        }
#pragma unroll
        for (int i = 0; i < 6; i++) l64 = cmul(l64, l64);
        cplx l128 = cmul(l64, l64);
        pin(l128.re); pin(l128.im);
        uint32_t vr[15], vi[15];
#pragma unroll
        for (int i = 0; i < 15; i++) { vr[i] = par; vi[i] = 0; pin(vr[i]); pin(vi[i]); }
        mbar_wait(sb + OFF_GBAR, 0);
        const float2 e0 = lds_f2(sb + OFF_CARRY + t * 8), e1 = lds_f2(sb + OFF_CARRY + 512 + t * 8);
        float2* eb = g_end + s * 1024 + t;
        {
          const cplx e = cfma(l64, cplx{e0.x, e0.y}, cplx{e1.x, e1.y});
          const unsigned long long v = ((unsigned long long)__float_as_uint(e.im) << 32) | ((__float_as_uint(e.re) & ~1u) | par);
          asm volatile("st.relaxed.gpu.global.b64 [%0], %1;" ::"l"(eb + m * 64), "l"(v) : "memory");
        }
        if (t == 0) TS(3, 1);
        cplx S = {0.f, 0.f};
        {
          if (LBD) __nanosleep(LBD);
          const float2* e15 = eb + (m - 15) * 64;
          int tries = 0;
          bool bad;
#pragma unroll 1
          do {
#pragma unroll
            for (int i = 0; i < 15; i++)
              asm volatile("{.reg .pred p; .reg .b64 v; mov.b64 v, {%0,%1}; setp.ge.s32 p, %3, %4; @p ld.relaxed.gpu.global.b64 v, [%2]; mov.b64 {%0,%1}, v;}"
                           : "+r"(vr[i]), "+r"(vi[i]) : "l"(e15 + i * 64), "r"(m), "r"(15 - i) : "memory");
            uint32_t x = vr[0] ^ par;
#pragma unroll
            for (int i = 1; i < 15; i++) asm("lop3.b32 %0, %0, %1, %2, 0xf6;" : "+r"(x) : "r"(vr[i]), "r"(par));
            bad = __any_sync(0xffffffffu, x & 1);
          } while (bad && ++tries < 200000);
          if (t == 0) TS(3, 2);
          S = cplx{__uint_as_float(vr[0]), __uint_as_float(vi[0])};
#pragma unroll
          for (int i = 1; i < 15; i++) S = cfma(l128, S, cplx{__uint_as_float(vr[i]), __uint_as_float(vi[i])});
        }
        const cplx S1 = cfma(l64, S, cplx{e0.x, e0.y});
        asm volatile("st.shared.v2.f32 [%0], {%1,%2};" ::"r"(sb + OFF_CARRY + t * 8), "f"(S.re), "f"(S.im) : "memory");
        asm volatile("st.shared.v2.f32 [%0], {%1,%2};" ::"r"(sb + OFF_CARRY + 512 + t * 8), "f"(S1.re), "f"(S1.im) : "memory");
        mbar_arrive(sb + OFF_CBAR);
        if (t == 0) TS(3, 3);
        mbar_wait(sb + OFF_CBAR, 0);
        const int gr = lane >> 2, q = lane & 3;
        float2 db[8];
#pragma unroll
        for (int j = 0; j < 8; j++) db[j] = lds_f2(sb + OFF_DB + j * 32 + q * 8);
        mbar_wait(sb + OFF_XFULL + 16, 1);
        mbar_wait(sb + OFF_EMPTY, 0);
#pragma unroll 1
        for (int cw = warp - 9; cw < 8; cw += 2) {
          const float r0 = 0.5f * bf_lo(lds_h(sb + OFF_GS + (cw * 16 + gr) * 2)), r1 = 0.5f * bf_lo(lds_h(sb + OFF_GS + (cw * 16 + gr) * 2 + 16));
          const uint32_t xa = sb + OFF_X + (1 + rank) * 16384 + (cw * 16 + (lane & 15)) * 128 + (((lane >> 4) ^ (lane & 7)) << 4);
          uint32_t xv[16];
#pragma unroll
          for (int i = 0; i < 4; i++)
            asm volatile("ldmatrix.sync.aligned.m8n8.x4.shared.b16 {%0,%1,%2,%3}, [%4];" : "=r"(xv[4 * i]), "=r"(xv[4 * i + 1]), "=r"(xv[4 * i + 2]), "=r"(xv[4 * i + 3])
                         : "r"(xa ^ (i << 5)) : "memory");
          __syncwarp();
#pragma unroll
          for (int j = 0; j < 8; j++) {
            const uint32_t x0 = bf2_mul(xv[2 * j], __float_as_uint(db[j].x)), x1 = bf2_mul(xv[2 * j + 1], __float_as_uint(db[j].x));
            pin(db[j].y);
            const float bl = bf_lo(__float_as_uint(db[j].y)), bh = bf_hi(__float_as_uint(db[j].y));
            asm volatile("st.shared.v4.f32 [%0], {%1,%2,%3,%4};" ::"r"(sb + OFF_X + 16384 + (j >> 2) * 16384 + cw * 2048 + (j & 3) * 512 + lane * 16), "f"(fmaf(bf_lo(x0), r0, bl)),
                         "f"(fmaf(bf_hi(x0), r0, bh)), "f"(fmaf(bf_lo(x1), r1, bl)), "f"(fmaf(bf_hi(x1), r1, bh)) : "memory");
          }
        }
        mbar_arrive(sb + OFF_LBAR);
        if (t == 0) TS(3, 5);
      } else {
        if (lane == 0) TG(2);
        const uint4* gwp = reinterpret_cast<const uint4*>(gate_w) + (lane & 7);
        uint4 gw[4];
#pragma unroll
        for (int i = 0; i < 4; i++) gw[i] = __ldg(gwp + i * 8);
        unsigned par;
        asm volatile("ld.relaxed.gpu.global.u32 %0, [%1];" : "=r"(par) : "l"(g_epoch + b) : "memory");
        const uint32_t dk = __ldg(reinterpret_cast<const uint32_t*>(dskip + s * 64) + lane), bb = __ldg(reinterpret_cast<const uint32_t*>(b2 + s * 64) + lane);
        asm volatile("barrier.cluster.wait.aligned;" ::: "memory");
        const int row = s * 16 + (lane >> 3);
        const uint32_t xr0 = sb + OFF_X + row * 128 + (((lane & 7) ^ (row & 7)) << 4), xr1 = (xr0 + 512) ^ 64;
        float z[4] = {0.f, 0.f, 0.f, 0.f};
#pragma unroll
        for (int kb = 0; kb < 8; kb++) {
          const uint32_t wv[4] = {gw[kb & 3].x, gw[kb & 3].y, gw[kb & 3].z, gw[kb & 3].w};
          if (kb < 4) gw[kb] = __ldg(gwp + (kb + 4) * 8);
          mbar_wait(sb + OFF_XFULL + 8 * kb, 0);
          if ((PF & 2) && kb == PFK && elect_one()) {
            l2_prefetch(pf_w1 + b * 7168, 14336);
            l2_prefetch(pf_cre + b * 2048, 4096);
            l2_prefetch(pf_cim + b * 2048, 4096);
            l2_prefetch(pf_w2 + b * 7168, 14336);
          }
          const uint32_t xo = ((kb + xrot) & 7) * 16384;
#pragma unroll
          for (int r = 0; r < 4; r++) {
            const uint4 a = lds_u4(((r & 1) ? xr1 : xr0) + xo + (r >> 1) * 1024);
            const uint32_t p = bf2_fma(a.w, wv[3], bf2_fma(a.z, wv[2], bf2_fma(a.y, wv[1], bf2_mul(a.x, wv[0]))));
            z[r] += bf_lo(p); z[r] += bf_hi(p);
          }
        }
        if (lane == 0) asm volatile("st.shared.u32 [%0], %1;" ::"r"(sb + OFF_EPOCH), "r"(par + 1) : "memory");
        par = (par + 1) & 1;
        {
          float y0 = (lane & 4) ? z[1] : z[0], y1 = (lane & 4) ? z[3] : z[2];
          y0 += __shfl_xor_sync(0xffffffffu, (lane & 4) ? z[0] : z[1], 4);
          y1 += __shfl_xor_sync(0xffffffffu, (lane & 4) ? z[2] : z[3], 4);
          float zz = (lane & 2) ? y1 : y0;
          zz += __shfl_xor_sync(0xffffffffu, (lane & 2) ? y0 : y1, 2);
          zz += __shfl_xor_sync(0xffffffffu, zz, 1);
          const float rho = 4.f * expf(zz > 40.f ? 40.f : zz);
          if ((lane & 1) == 0)
            asm volatile("st.relaxed.gpu.global.u32 [%0], %1;" ::"l"(g_gate + m * 128 + row + (lane & 4) + (lane & 2) * 4), "r"((__float_as_uint(rho) & ~1u) | par) : "memory");
        }
        if ((PF & 8) && elect_one()) {
          l2_prefetch(pf_w2 + b * 7168, 14336);
          l2_prefetch(pf_cre + b * 2048, 4096);
          l2_prefetch(pf_cim + b * 2048, 4096);
        }
        if (lane == 0) TS(3, 0);
        mbar_wait(sb + OFF_GBAR, 0);
        asm volatile("st.shared.v2.u32 [%0], {%1,%2};" ::"r"(sb + OFF_DB + lane * 8), "r"(dk), "r"(bf2_add(bb, bb)) : "memory");
        uint32_t g0, g1, g2, g3;
        int tries = 0;
#pragma unroll 1
        do {
          asm volatile("ld.relaxed.gpu.global.v4.u32 {%0,%1,%2,%3}, [%4];" : "=r"(g0), "=r"(g1), "=r"(g2), "=r"(g3) : "l"(g_gate + m * 128 + lane * 4) : "memory");
        } while ((((g0 ^ par) | (g1 ^ par) | (g2 ^ par) | (g3 ^ par)) & 1) && ++tries < 200000);
        asm volatile("st.shared.v2.u32 [%0], {%1,%2};" ::"r"(sb + OFF_GS + lane * 8), "r"(pack_bf16(__uint_as_float(g0), __uint_as_float(g1))),
                     "r"(pack_bf16(__uint_as_float(g2), __uint_as_float(g3))) : "memory");
        mbar_arrive(sb + OFF_CBAR);
        if (lane == 0) TS(3, 4);
      }
    } else {
      asm volatile("barrier.cluster.wait.aligned;" ::: "memory");
      if (elect_one()) {
        TS(2, 1);
        const uint32_t t0 = clock();
#pragma unroll 1
        for (int u = W0; u < 8; u++) {
          if (u >= 1) while ((uint32_t)clock() - t0 < D0 + (u - 1) * D1) {}
          mbar_expect_tx(sb + OFF_XFULL + 8 * u, 16384);
          tma5d_mc(sb + OFF_X + ((u + xrot) & 7) * 16384 + rank * 8192, &maps.x, u * 64, 2 * m + rank, sb + OFF_XFULL + 8 * u);
          const int sl = u < 6 ? u : u - 6;
          if (u >= 6) mbar_wait(sb + OFF_EMPTY + 8 * sl, 0);
          mbar_expect_tx(sb + OFF_FULL + 8 * sl, 16384);
          tma2d(sb + OFF_RING + sl * 16384, &maps.bre, u * 64, s * 64, sb + OFF_FULL + 8 * sl);
          tma2d(sb + OFF_RING + sl * 16384 + 8192, &maps.bim, u * 64, s * 64, sb + OFF_FULL + 8 * sl);
          if (u == 2) asm volatile("prefetch.tensormap [%0];" ::"l"(&maps.w1a) : "memory");
        }
        TS(2, 5);
        int slot = 2; uint32_t ph = 0;
#pragma unroll 1
        for (int u = 8; u < 24; u++) {
          const uint32_t fb = sb + OFF_FULL + 8 * slot, dst = sb + OFF_RING + slot * 16384;
          mbar_wait(sb + OFF_EMPTY + 8 * slot, ph);
          TS2(0, u);
          if (u < 16) {
            mbar_expect_tx(fb, 16384);
            tma2d(dst, &maps.w1a, s * 224, (u - 8) * 64, fb);
            tma2d(dst + 8192, &maps.w1a, s * 224 + 64, (u - 8) * 64, fb);
            if (TMP2 && u < 12) asm volatile("prefetch.tensormap [%0];" ::"l"(&maps.w1b + (u - 8)) : "memory");
          } else {
            mbar_expect_tx(fb, 12288);
            tma3d(dst, &maps.w1b, 0, ((u - xrot) & 7) * 64, s * 7 + 4, fb);
          }
          if (++slot == NSLOT) { slot = 0; ph ^= 1; }
        }
#pragma unroll 1
        for (int j = 0; j < 3; j++) {
          const uint32_t fb = sb + OFF_FULL + 8 * j;
          mbar_wait(sb + OFF_EMPTY + 8 + 8 * j, 1);
          mbar_expect_tx(fb, j == 1 ? 32768 : 28672);
#pragma unroll
          for (int e = 0; e < 2; e++) {
            const int c = ((sp + 1) & 3) * 128 + ((rank ^ e ^ 1) << 6);
            const uint32_t dst = sb + OFF_X + stage_off(e);
            if (j == 1) {
              tma2d(dst + 14336, &maps.cre, s * 64, c, fb);
              tma2d(dst + 22528, &maps.cim, s * 64, c, fb);
            } else {
              tma2d(dst + j * 15360, &maps.w2, c, s * 224 + j * 56, fb);
            }
          }
        }
#pragma unroll 1
        for (int p = 2; p < 8; p++) {
          const int c = ((sp + 1 + (p >> 1)) & 3) * 128 + (((rank ^ p ^ 1) & 1) << 6);
          const uint32_t fb = sb + OFF_XFULL + 8 * p, dst = sb + OFF_X + stage_off(p);
          if (p == 2 || p > 3) mbar_wait(sb + OFF_EMPTY + (p == 2 ? 40 : (p - 4) * 8), p == 2);
          TS2(0, 32 + p);
          mbar_expect_tx(fb, 45056);
          tma2d(dst, &maps.w2, c, s * 224, fb);
          tma2d(dst + 14336, &maps.cre, s * 64, c, fb);
          tma2d(dst + 22528, &maps.cim, s * 64, c, fb);
          tma2d(dst + 30720, &maps.w2, c, s * 224 + 112, fb);
        }
        TS(2, 2);
      }
    }
  }
}

typedef CUresult (*EncFn)(CUtensorMap*, CUtensorMapDataType, cuuint32_t, void*, const cuuint64_t*, const cuuint64_t*, const cuuint32_t*,
                          const cuuint32_t*, CUtensorMapInterleave, CUtensorMapSwizzle, CUtensorMapL2promotion, CUtensorMapFloatOOBfill);

void encode(EncFn f, CUtensorMap* mp, const void* p, int rank, const cuuint64_t* dims, const cuuint64_t* strides, const cuuint32_t* box, CUtensorMapSwizzle sw) {
  cuuint32_t es[5] = {1, 1, 1, 1, 1};
  f(mp, CU_TENSOR_MAP_DATA_TYPE_BFLOAT16, rank, const_cast<void*>(p), dims, strides, box, es, CU_TENSOR_MAP_INTERLEAVE_NONE, sw,
    CU_TENSOR_MAP_L2_PROMOTION_L2_128B, CU_TENSOR_MAP_FLOAT_OOB_FILL_NONE);
}

}

extern "C" void kernel_launch(void* const* d_in, const int* in_sizes, int n_in, void* d_out, int out_size) {
  typedef const __nv_bfloat16* bp;
  bp x = (bp)d_in[0], lre = (bp)d_in[1], lim = (bp)d_in[2], bre = (bp)d_in[3], bim = (bp)d_in[4], cre = (bp)d_in[5], cim = (bp)d_in[6],
     ldt = (bp)d_in[7], dsk = (bp)d_in[8], w1 = (bp)d_in[10], b1 = (bp)d_in[11], w2 = (bp)d_in[12], b2 = (bp)d_in[13], gw = (bp)d_in[14];
  static EncFn enc = nullptr;
  if (!enc) {
    void* f = nullptr;
    cudaDriverEntryPointQueryResult qr;
    cudaGetDriverEntryPoint("cuTensorMapEncodeTiled", &f, cudaEnableDefault, &qr);
    enc = (EncFn)f;
    cudaFuncSetAttribute(fused_kernel, cudaFuncAttributeMaxDynamicSharedMemorySize, SMEM_BYTES);
  }
  Maps maps;
  {
    cuuint64_t d[5] = {DM, 2, 4, 8, SEQ / 64}, st[4] = {DM * 2, 16 * DM * 2, 2 * DM * 2, 64 * DM * 2};
    cuuint32_t bx[5] = {64, 2, 4, 8, 1};
    encode(enc, &maps.x, x, 5, d, st, bx, CU_TENSOR_MAP_SWIZZLE_128B);
  }
  {
    cuuint64_t d[2] = {DM, DM}, st[1] = {DM * 2};
    cuuint32_t bx[2] = {64, 64};
    encode(enc, &maps.bre, bre, 2, d, st, bx, CU_TENSOR_MAP_SWIZZLE_128B);
    encode(enc, &maps.bim, bim, 2, d, st, bx, CU_TENSOR_MAP_SWIZZLE_128B);
    encode(enc, &maps.cre, cre, 2, d, st, bx, CU_TENSOR_MAP_SWIZZLE_128B);
    encode(enc, &maps.cim, cim, 2, d, st, bx, CU_TENSOR_MAP_SWIZZLE_128B);
  }
  {
    cuuint64_t d[2] = {FF, DM}, st[1] = {FF * 2};
    cuuint32_t bx[2] = {64, 64};
    encode(enc, &maps.w1a, w1, 2, d, st, bx, CU_TENSOR_MAP_SWIZZLE_128B);
    cuuint64_t d3[3] = {32, DM, FF / 32}, st3[2] = {FF * 2, 64};
    cuuint32_t bx3[3] = {32, 64, 3};
    encode(enc, &maps.w1b, w1, 3, d3, st3, bx3, CU_TENSOR_MAP_SWIZZLE_64B);
  }
  {
    cuuint64_t d[2] = {DM, FF}, st[1] = {DM * 2};
    cuuint32_t bx[2] = {64, 112};
    encode(enc, &maps.w2, w2, 2, d, st, bx, CU_TENSOR_MAP_SWIZZLE_128B);
  }
  fused_kernel<<<128, 384, SMEM_BYTES>>>(lre, lim, ldt, dsk, b1, b2, gw, w1, w2, cre, cim, (float*)d_out, maps);
}
```

```cpp
#include <cuda_runtime.h>
#include <cuda_bf16.h>
#include <cuda.h>
#include <stdint.h>

#define MAP 1
#define D0 250
#define D1 500
#define PF 4
#define PFK 5
#define GELUP 1
#define EW 2
#define K1E 1
#define K2E 0
#define QS 1
#define K2G 4
#define FINP 4
#define LBD 300
#define PFS 32
#define SB0 2
#define PFD 2
#define HOLD 0
#define GAP 14
#define FINW 0
#define K0P 33
#define K1P 53
#define TMP2 1
#define W0 1
#define LCK 4
#define TOKA 0
#define TOKB 2
#define TOKD 0
#define TKT 999
#define AV 0
#define QK 4
#define TCUT {1, 6, 6, 11, 16}
#define SCUT {0, 0, 0, 0, 0, 0, 10, 21, 32}
#define TP 9
#define TW 0

namespace {

constexpr int SEQ = 2048, DM = 512, FF = 1792;
constexpr int NSLOT = 6;
constexpr uint32_t OFF_X = 0, OFF_RING = 131072, OFF_MISC = 229376;
constexpr uint32_t OFF_XFULL = OFF_MISC, OFF_FULL = OFF_XFULL + 64, OFF_RBAR = OFF_FULL + 48, OFF_EMPTY = OFF_RBAR + 16, OFF_KBAR = OFF_EMPTY + 48,
                   OFF_GBAR = OFF_KBAR + 16, OFF_LBAR = OFF_GBAR + 8, OFF_CBAR = OFF_LBAR + 8, OFF_EPOCH = OFF_CBAR + 8;
constexpr uint32_t OFF_LC = OFF_MISC + 256;
constexpr uint32_t OFF_GS = OFF_LC;
constexpr uint32_t OFF_GT = OFF_LC + 256;
constexpr uint32_t OFF_DB = OFF_LC + 512;
constexpr uint32_t OFF_CARRY = OFF_LC + 1024;
constexpr uint32_t OFF_DBG = OFF_CARRY + 1024;
constexpr uint32_t SMEM_BYTES = OFF_DBG + 768;
static_assert(SMEM_BYTES <= 232448, "smem");

struct Maps { CUtensorMap x, bre, bim, w1b, w1a, w2, cre, cim; };
__host__ __device__ constexpr uint32_t stage_off(int p) { return 49152 + 45056 * (((p >> 1) & 1) + 2 * (p & 1)); }

__device__ uint4 g_part[16 * 8 * 3 * 1024];
__device__ float2 g_end[8 * 16 * 64];
__device__ unsigned g_gate[SEQ];
__device__ unsigned g_epoch[128];
#define TG(role) do {} while (0)
#define TS2(role, i) do {} while (0)
#define TS(role, i) do {} while (0)
#define TDUMP() do {} while (0)
#define TR(i) do {} while (0)
#define TK(i) do {} while (0)
#define TRD() do {} while (0)

__device__ __forceinline__ void mbar_init(uint32_t bar, uint32_t cnt) { asm volatile("mbarrier.init.shared::cta.b64 [%0], %1;" ::"r"(bar), "r"(cnt)); }
__device__ __forceinline__ void mbar_expect_tx(uint32_t bar, uint32_t bytes) { asm volatile("mbarrier.arrive.expect_tx.shared::cta.b64 _, [%0], %1;" ::"r"(bar), "r"(bytes) : "memory"); }
__device__ __forceinline__ void mbar_arrive(uint32_t bar) { asm volatile("mbarrier.arrive.shared::cta.b64 _, [%0];" ::"r"(bar) : "memory"); }
__device__ __forceinline__ void mbar_arrive_cl(uint32_t cbar) { asm volatile("mbarrier.arrive.shared::cluster.b64 _, [%0];" ::"r"(cbar) : "memory"); }
__device__ __forceinline__ void mbar_wait(uint32_t bar, uint32_t parity) {
  asm volatile(
      "{\n.reg .pred p;\n.reg .u32 c;\n"
      "mbarrier.try_wait.parity.shared::cta.b64 p, [%0], %1;\n"
      "@p bra.uni LAB_DONE;\n"
      "mov.u32 c, 0;\n"
      "LAB_WAIT:\n"
      "mbarrier.try_wait.parity.shared::cta.b64 p, [%0], %1;\n"
      "@p bra.uni LAB_DONE;\n"
      "add.u32 c, c, 1;\nsetp.lt.u32 p, c, 200000;\n@p bra.uni LAB_WAIT;\n"
      "LAB_DONE:\n}" ::"r"(bar), "r"(parity) : "memory");
}
__device__ __forceinline__ void tma2d(uint32_t dst, const CUtensorMap* m, int c0, int c1, uint32_t bar) {
  asm volatile("cp.async.bulk.tensor.2d.shared::cluster.global.mbarrier::complete_tx::bytes [%0], [%1, {%3,%4}], [%2];"
               ::"r"(dst), "l"(m), "r"(bar), "r"(c0), "r"(c1) : "memory");
}
__device__ __forceinline__ void tma3d(uint32_t dst, const CUtensorMap* m, int c0, int c1, int c2, uint32_t bar) {
  asm volatile("cp.async.bulk.tensor.3d.shared::cluster.global.mbarrier::complete_tx::bytes [%0], [%1, {%3,%4,%5}], [%2];"
               ::"r"(dst), "l"(m), "r"(bar), "r"(c0), "r"(c1), "r"(c2) : "memory");
}
__device__ __forceinline__ void tma5d(uint32_t dst, const CUtensorMap* m, int c0, int c4, uint32_t bar) {
  asm volatile("cp.async.bulk.tensor.5d.shared::cluster.global.mbarrier::complete_tx::bytes [%0], [%1, {%3,%5,%5,%5,%4}], [%2];"
               ::"r"(dst), "l"(m), "r"(bar), "r"(c0), "r"(c4), "r"(0) : "memory");
}
__device__ __forceinline__ void tma5d_mc(uint32_t dst, const CUtensorMap* m, int c0, int c4, uint32_t bar) {
  asm volatile("cp.async.bulk.tensor.5d.shared::cluster.global.mbarrier::complete_tx::bytes.multicast::cluster [%0], [%1, {%3,%5,%5,%5,%4}], [%2], %6;"
               ::"r"(dst), "l"(m), "r"(bar), "r"(c0), "r"(c4), "r"(0), "h"((uint16_t)3) : "memory");
}
__device__ __forceinline__ void l2_prefetch(const void* p, uint32_t bytes) { asm volatile("cp.async.bulk.prefetch.L2.global [%0], %1;" ::"l"(p), "r"(bytes) : "memory"); }
__device__ __forceinline__ bool elect_one() {
  uint32_t pred;
  asm volatile("{.reg .pred P; elect.sync _|P, 0xffffffff; selp.u32 %0, 1, 0, P;}" : "=r"(pred));
  return pred != 0;
}
__device__ __forceinline__ void wg_fence() { asm volatile("wgmma.fence.sync.aligned;" ::: "memory"); }
__device__ __forceinline__ void wg_commit() { asm volatile("wgmma.commit_group.sync.aligned;" ::: "memory"); }
template <int N> __device__ __forceinline__ void wg_wait() { asm volatile("wgmma.wait_group.sync.aligned %0;" ::"n"(N) : "memory"); }
__device__ __forceinline__ void pin(float& a) { asm volatile("" : "+f"(a)::"memory"); }
__device__ __forceinline__ void pin(uint32_t& a) { asm volatile("" : "+r"(a)::"memory"); }
template <int N> __device__ __forceinline__ void reg_fence(float (&d)[N]) {
#pragma unroll
  for (int i = 0; i < N; i++) pin(d[i]);
}
__device__ __forceinline__ void bar_sync(int id, int n) { asm volatile("bar.sync %0, %1;" ::"r"(id), "r"(n) : "memory"); }
__device__ __forceinline__ void bar_arrive(int id, int n) { asm volatile("bar.arrive %0, %1;" ::"r"(id), "r"(n) : "memory"); }
constexpr uint32_t DH128 = (1024 >> 4) | (1u << 30), DH64 = (512 >> 4) | (2u << 30);
__host__ __device__ constexpr uint32_t lbo(uint32_t bytes) { return (bytes >> 4) << 20; }
__device__ __forceinline__ uint32_t pack_bf16(float lo, float hi) { uint32_t r; asm("cvt.rn.bf16x2.f32 %0, %1, %2;" : "=r"(r) : "f"(hi), "f"(lo)); return r; }
__device__ __forceinline__ float bf_lo(uint32_t v) { return __uint_as_float(v << 16); }
__device__ __forceinline__ float bf_hi(uint32_t v) { return __uint_as_float(v & 0xffff0000u); }
__device__ __forceinline__ float bf_ld(const __nv_bfloat16* p) { return __bfloat162float(__ldg(p)); }
__device__ __forceinline__ uint32_t late16(uint32_t bar) {
  uint32_t r;
  asm volatile("{.reg .pred p; mbarrier.test_wait.parity.shared::cta.b64 p, [%1], 0; selp.u32 %0, 16, 0, p;}" : "=r"(r) : "r"(bar) : "memory");
  return r;
}
__device__ __forceinline__ float2 lds_f2(uint32_t a) { float2 v; asm volatile("ld.shared.v2.f32 {%0,%1}, [%2];" : "=f"(v.x), "=f"(v.y) : "r"(a)); return v; }
__device__ __forceinline__ uint32_t lds_h(uint32_t a) { uint32_t v; asm volatile("ld.shared.u16 %0, [%1];" : "=r"(v) : "r"(a)); return v; }
__device__ __forceinline__ uint32_t lds_u(uint32_t a) { uint32_t v; asm volatile("ld.shared.u32 %0, [%1];" : "=r"(v) : "r"(a)); return v; }
__device__ __forceinline__ uint4 lds_u4(uint32_t a) { uint4 v; asm volatile("ld.shared.v4.u32 {%0,%1,%2,%3}, [%4];" : "=r"(v.x), "=r"(v.y), "=r"(v.z), "=r"(v.w) : "r"(a)); return v; }
__device__ __forceinline__ void st_b128(uint4* p, uint32_t a, uint32_t b, uint32_t c, uint32_t d) {
  asm volatile("st.relaxed.gpu.global.v4.b32 [%0], {%1,%2,%3,%4};" ::"l"(p), "r"(a), "r"(b), "r"(c), "r"(d) : "memory");
}
__device__ __forceinline__ void ld_b128(const uint4* p, uint32_t& a, uint32_t& b, uint32_t& c, uint32_t& d) {
  asm volatile("{.reg .b64 l, h; .reg .b128 v; ld.relaxed.gpu.global.b128 v, [%4]; mov.b128 {l,h}, v; mov.b64 {%0,%1}, l; mov.b64 {%2,%3}, h;}"
               : "=r"(a), "=r"(b), "=r"(c), "=r"(d) : "l"(p) : "memory");
}
__device__ __forceinline__ float tanh_fast(float x) { float y; asm("tanh.approx.f32 %0, %1;" : "=f"(y) : "f"(x)); return y; }
__device__ __forceinline__ float gelu2(float v) {
  float p = fmaf(v * v, 0.0356774081363f, 0.7978845608029f);
  return fmaf(v, tanh_fast(v * p), v);
}
__device__ __forceinline__ void sched_fence(uint32_t& ck) { asm volatile("{.reg .b32 c; mov.u32 c, %%clock; xor.b32 %0, %0, c;}" : "+r"(ck)::"memory"); }
__device__ __forceinline__ uint32_t bf2_mul(uint32_t a, uint32_t b) { uint32_t r; asm("mul.rn.bf16x2 %0, %1, %2;" : "=r"(r) : "r"(a), "r"(b)); return r; }
__device__ __forceinline__ uint32_t bf2_add(uint32_t a, uint32_t b) { uint32_t r; asm("add.rn.bf16x2 %0, %1, %2;" : "=r"(r) : "r"(a), "r"(b)); return r; }
__device__ __forceinline__ uint32_t bf2_fma(uint32_t a, uint32_t b, uint32_t c) { uint32_t r; asm("fma.rn.bf16x2 %0, %1, %2, %3;" : "=r"(r) : "r"(a), "r"(b), "r"(c)); return r; }
__device__ __forceinline__ uint32_t gelu2_pair(float a, float b) {
  const uint32_t v = pack_bf16(a, b);
  uint32_t t;
  asm("tanh.approx.bf16x2 %0, %1;" : "=r"(t) : "r"(bf2_fma(v, bf2_fma(bf2_mul(v, v), 0x3d123d12u, 0xbe4fbe4fu), v)));
  return bf2_fma(v, t, v);
}
struct cplx { float re, im; };
__device__ __forceinline__ cplx cmul(cplx a, cplx b) { return {fmaf(a.re, b.re, -a.im * b.im), fmaf(a.re, b.im, a.im * b.re)}; }
__device__ __forceinline__ cplx cfma(cplx a, cplx b, cplx c) {
  return {fmaf(a.re, b.re, fmaf(-a.im, b.im, c.re)), fmaf(a.re, b.im, fmaf(a.im, b.re, c.im))};
}
__device__ __forceinline__ cplx make_lam(float lre, float lim, float ldt) {
  float dt = __bfloat162float(__float2bfloat16_rn(expf(ldt)));
  float mag = expf(dt * lre), sn, cs;
  sincospif(dt * lim * 0.31830988618379067f, &sn, &cs);
  return {mag * cs, mag * sn};
}

template<int TA,int TB,uint32_t AH,uint32_t BH> __device__ __forceinline__ void wgmma_n64_ss(float (&d)[32], uint32_t al, uint32_t ao, uint32_t bl, uint32_t bo, int scale_d){
  asm volatile("{.reg .pred p; .reg .b32 t, v; .reg .b64 da, db; setp.ne.b32 p, %36, 0; add.u32 t, %32, %33; mov.b64 da, {t, %39}; add.u32 v, %34, %35; mov.b64 db, {v, %40};\n"
   "wgmma.mma_async.sync.aligned.m64n64k16.f32.bf16.bf16 {%0,%1,%2,%3,%4,%5,%6,%7,%8,%9,%10,%11,%12,%13,%14,%15,%16,%17,%18,%19,%20,%21,%22,%23,%24,%25,%26,%27,%28,%29,%30,%31}, da, db, p, 1, 1, %37, %38;}"
   : "+f"(d[0]),"+f"(d[1]),"+f"(d[2]),"+f"(d[3]),"+f"(d[4]),"+f"(d[5]),"+f"(d[6]),"+f"(d[7]),"+f"(d[8]),"+f"(d[9]),"+f"(d[10]),"+f"(d[11]),"+f"(d[12]),"+f"(d[13]),"+f"(d[14]),"+f"(d[15]),"+f"(d[16]),"+f"(d[17]),"+f"(d[18]),"+f"(d[19]),"+f"(d[20]),"+f"(d[21]),"+f"(d[22]),"+f"(d[23]),"+f"(d[24]),"+f"(d[25]),"+f"(d[26]),"+f"(d[27]),"+f"(d[28]),"+f"(d[29]),"+f"(d[30]),"+f"(d[31])
   : "r"(al),"r"(ao >> 4),"r"(bl),"r"(bo >> 4),"r"(scale_d),"n"(TA),"n"(TB),"n"(AH),"n"(BH));
}
template<int TB,uint32_t BH,int SA=1> __device__ __forceinline__ void wgmma_n64_rs(float (&d)[32], uint32_t a0,uint32_t a1,uint32_t a2,uint32_t a3, uint32_t bl, uint32_t bo, int scale_d){
  asm volatile("{.reg .pred p; .reg .b32 t; .reg .b64 db; setp.ne.b32 p, %38, 0; add.u32 t, %36, %37; mov.b64 db, {t, %40};\n"
   "wgmma.mma_async.sync.aligned.m64n64k16.f32.bf16.bf16 {%0,%1,%2,%3,%4,%5,%6,%7,%8,%9,%10,%11,%12,%13,%14,%15,%16,%17,%18,%19,%20,%21,%22,%23,%24,%25,%26,%27,%28,%29,%30,%31}, {%32,%33,%34,%35}, db, p, %41, 1, %39;}"
   : "+f"(d[0]),"+f"(d[1]),"+f"(d[2]),"+f"(d[3]),"+f"(d[4]),"+f"(d[5]),"+f"(d[6]),"+f"(d[7]),"+f"(d[8]),"+f"(d[9]),"+f"(d[10]),"+f"(d[11]),"+f"(d[12]),"+f"(d[13]),"+f"(d[14]),"+f"(d[15]),"+f"(d[16]),"+f"(d[17]),"+f"(d[18]),"+f"(d[19]),"+f"(d[20]),"+f"(d[21]),"+f"(d[22]),"+f"(d[23]),"+f"(d[24]),"+f"(d[25]),"+f"(d[26]),"+f"(d[27]),"+f"(d[28]),"+f"(d[29]),"+f"(d[30]),"+f"(d[31])
   : "r"(a0),"r"(a1),"r"(a2),"r"(a3),"r"(bl),"r"(bo >> 4),"r"(scale_d),"n"(TB),"n"(BH),"n"(SA));
}
template<int TA,int TB,uint32_t AH,uint32_t BH> __device__ __forceinline__ void wgmma_n96_ss(float (&d)[48], uint32_t al, uint32_t ao, uint32_t bl, uint32_t bo, int scale_d){
  asm volatile("{.reg .pred p; .reg .b32 t, v; .reg .b64 da, db; setp.ne.b32 p, %52, 0; add.u32 t, %48, %49; mov.b64 da, {t, %55}; add.u32 v, %50, %51; mov.b64 db, {v, %56};\n"
   "wgmma.mma_async.sync.aligned.m64n96k16.f32.bf16.bf16 {%0,%1,%2,%3,%4,%5,%6,%7,%8,%9,%10,%11,%12,%13,%14,%15,%16,%17,%18,%19,%20,%21,%22,%23,%24,%25,%26,%27,%28,%29,%30,%31,%32,%33,%34,%35,%36,%37,%38,%39,%40,%41,%42,%43,%44,%45,%46,%47}, da, db, p, 1, 1, %53, %54;}"
   : "+f"(d[0]),"+f"(d[1]),"+f"(d[2]),"+f"(d[3]),"+f"(d[4]),"+f"(d[5]),"+f"(d[6]),"+f"(d[7]),"+f"(d[8]),"+f"(d[9]),"+f"(d[10]),"+f"(d[11]),"+f"(d[12]),"+f"(d[13]),"+f"(d[14]),"+f"(d[15]),"+f"(d[16]),"+f"(d[17]),"+f"(d[18]),"+f"(d[19]),"+f"(d[20]),"+f"(d[21]),"+f"(d[22]),"+f"(d[23]),"+f"(d[24]),"+f"(d[25]),"+f"(d[26]),"+f"(d[27]),"+f"(d[28]),"+f"(d[29]),"+f"(d[30]),"+f"(d[31]),"+f"(d[32]),"+f"(d[33]),"+f"(d[34]),"+f"(d[35]),"+f"(d[36]),"+f"(d[37]),"+f"(d[38]),"+f"(d[39]),"+f"(d[40]),"+f"(d[41]),"+f"(d[42]),"+f"(d[43]),"+f"(d[44]),"+f"(d[45]),"+f"(d[46]),"+f"(d[47])
   : "r"(al),"r"(ao >> 4),"r"(bl),"r"(bo >> 4),"r"(scale_d),"n"(TA),"n"(TB),"n"(AH),"n"(BH));
}
template<int TA,int TB,uint32_t AH,uint32_t BH> __device__ __forceinline__ void wgmma_n128_ss(float (&d)[64], uint32_t al, uint32_t ao, uint32_t bl, uint32_t bo, int scale_d){
  asm volatile("{.reg .pred p; .reg .b32 t, v; .reg .b64 da, db; setp.ne.b32 p, %68, 0; add.u32 t, %64, %65; mov.b64 da, {t, %71}; add.u32 v, %66, %67; mov.b64 db, {v, %72};\n"
   "wgmma.mma_async.sync.aligned.m64n128k16.f32.bf16.bf16 {%0,%1,%2,%3,%4,%5,%6,%7,%8,%9,%10,%11,%12,%13,%14,%15,%16,%17,%18,%19,%20,%21,%22,%23,%24,%25,%26,%27,%28,%29,%30,%31,%32,%33,%34,%35,%36,%37,%38,%39,%40,%41,%42,%43,%44,%45,%46,%47,%48,%49,%50,%51,%52,%53,%54,%55,%56,%57,%58,%59,%60,%61,%62,%63}, da, db, p, 1, 1, %69, %70;}"
   : "+f"(d[0]),"+f"(d[1]),"+f"(d[2]),"+f"(d[3]),"+f"(d[4]),"+f"(d[5]),"+f"(d[6]),"+f"(d[7]),"+f"(d[8]),"+f"(d[9]),"+f"(d[10]),"+f"(d[11]),"+f"(d[12]),"+f"(d[13]),"+f"(d[14]),"+f"(d[15]),"+f"(d[16]),"+f"(d[17]),"+f"(d[18]),"+f"(d[19]),"+f"(d[20]),"+f"(d[21]),"+f"(d[22]),"+f"(d[23]),"+f"(d[24]),"+f"(d[25]),"+f"(d[26]),"+f"(d[27]),"+f"(d[28]),"+f"(d[29]),"+f"(d[30]),"+f"(d[31]),"+f"(d[32]),"+f"(d[33]),"+f"(d[34]),"+f"(d[35]),"+f"(d[36]),"+f"(d[37]),"+f"(d[38]),"+f"(d[39]),"+f"(d[40]),"+f"(d[41]),"+f"(d[42]),"+f"(d[43]),"+f"(d[44]),"+f"(d[45]),"+f"(d[46]),"+f"(d[47]),"+f"(d[48]),"+f"(d[49]),"+f"(d[50]),"+f"(d[51]),"+f"(d[52]),"+f"(d[53]),"+f"(d[54]),"+f"(d[55]),"+f"(d[56]),"+f"(d[57]),"+f"(d[58]),"+f"(d[59]),"+f"(d[60]),"+f"(d[61]),"+f"(d[62]),"+f"(d[63])
   : "r"(al),"r"(ao >> 4),"r"(bl),"r"(bo >> 4),"r"(scale_d),"n"(TA),"n"(TB),"n"(AH),"n"(BH));
}

__global__ void __cluster_dims__(2, 1, 1) __launch_bounds__(384, 1)
fused_kernel(const __nv_bfloat16* __restrict__ lam_re, const __nv_bfloat16* __restrict__ lam_im, const __nv_bfloat16* __restrict__ log_dt,
             const __nv_bfloat16* __restrict__ dskip, const __nv_bfloat16* __restrict__ b1, const __nv_bfloat16* __restrict__ b2,
             const __nv_bfloat16* __restrict__ gate_w, const __nv_bfloat16* __restrict__ pf_w1, const __nv_bfloat16* __restrict__ pf_w2,
             const __nv_bfloat16* __restrict__ pf_cre, const __nv_bfloat16* __restrict__ pf_cim, float* __restrict__ out,
             const __grid_constant__ Maps maps) {
  extern __shared__ __align__(1024) unsigned char smem_raw[];
  const uint32_t sb = (uint32_t)__cvta_generic_to_shared(smem_raw);
  const int b = blockIdx.x;
  const int rank = b & 1, cl = b >> 1;
  const int sp = (cl & 1) | ((cl >> 2) & 2), m = ((cl >> 1) & 3) | ((cl >> 4) << 2);
  const int s = sp * 2 + rank;
  const int warp = __shfl_sync(0xffffffffu, (int)(threadIdx.x >> 5), 0);
  const int lane = threadIdx.x & 31;
  const int xrot = 9 - 2 * sp;

  if (elect_one()) {
    if (warp == 8) TS(2, 0);
    if (warp > 8) {
      asm volatile("prefetch.tensormap [%0];" ::"l"(&maps.x + (warp - 9)) : "memory");
      mbar_init(sb + OFF_GBAR + 8 * (warp - 9), warp < 11 ? 64 : 96);
    }
    const uint32_t c = warp < 8 ? 1 : warp < 11 ? 8 : 4, bar = sb + OFF_XFULL + 16 * warp;
    mbar_init(bar, c);
    if ((warp & 11) == 0) {
      mbar_expect_tx(bar, 16384);
      if (warp == 0) {
        tma5d(sb + OFF_X + (xrot & 7) * 16384, &maps.x, 0, 2 * m, bar);
        tma5d(sb + OFF_X + (xrot & 7) * 16384 + 8192, &maps.x, 0, 2 * m + 1, bar);
        TS(2, 3);
      } else {
        tma2d(sb + OFF_RING, &maps.bre, 0, s * 64, bar);
        tma2d(sb + OFF_RING + 8192, &maps.bim, 0, s * 64, bar);
        TS(2, 4);
      }
    }
    mbar_init(bar + 8, c);
    asm volatile("fence.mbarrier_init.release.cluster;" ::: "memory");
  }
  __syncwarp();
  asm volatile("barrier.cluster.arrive.relaxed.aligned;" ::: "memory");

  if (warp < 8) {
    const int wg = warp >> 2, w = warp & 3, q = lane & 3, gr = lane >> 2;
    uint32_t bv[28];
#pragma unroll
    for (int j = 0; j < 28; j++) bv[j] = __ldg(reinterpret_cast<const uint32_t*>(b1 + s * 224 + j * 8) + q);
    asm volatile("setmaxnreg.inc.sync.aligned.u32 224;");
    asm volatile("barrier.cluster.wait.aligned;" ::: "memory");
    TS(wg, 0);
    auto release = [&](int slot) { if (lane == 0) mbar_arrive(sb + OFF_EMPTY + 8 * slot); };
    const uint32_t xw = sb + OFF_X + wg * 8192, fullb = sb + OFF_FULL;
    const uint32_t dxw = (xw & 0x3FFFF) >> 4, dring = ((sb + OFF_RING) & 0x3FFFF) >> 4;

    float ure[32], uim[32], aa[48], ab[64];
    cplx lam[2], coef[2], l16[2], l32[2], lq[2], pre[2], e[2];
    uint32_t sh16, mhi, ck = 0;

    auto bias = [&](int c) {
#pragma unroll
      for (int j = c * 7; j < c * 7 + 7; j++) {
        pin(bv[j]);
        float* d = j < 12 ? aa + 4 * j : ab + 4 * (j - 12);
        d[0] = d[2] = __uint_as_float(bv[j] << sh16); d[1] = d[3] = __uint_as_float(bv[j] & mhi);
        pin(d[0]); pin(d[1]); pin(d[2]); pin(d[3]);
      }
    };
#pragma unroll
    for (int kb = 0; kb < 8; kb++) {
      const int slot = kb % NSLOT;
      mbar_wait(sb + OFF_XFULL + 8 * kb, 0);
      if (kb == 0) TS(wg, 18);
      mbar_wait(fullb + 8 * slot, (kb / NSLOT) & 1);
      TS2(2, kb);
      if (kb == 0) TS(wg, 1);
      if (kb == SB0) { sh16 = late16(sb + OFF_XFULL); mhi = 0xffffffffu << sh16; }
      if (kb == LCK) {
        mbar_wait(sb + OFF_LBAR, 0);
#pragma unroll
        for (int h = 0; h < 2; h++) {
          const uint4 v = lds_u4(sb + OFF_LC + (w * 16 + gr + 8 * h) * 16);
          lam[h] = cplx{__uint_as_float(v.x), __uint_as_float(v.y)};
          coef[h] = cplx{__uint_as_float(v.z), __uint_as_float(v.w)};
        }
      }
      wg_fence();
      const uint32_t dxa = dxw + ((kb + xrot) & 7) * 1024;
#pragma unroll
      for (int kk = 0; kk < 4; kk++) {
        wgmma_n64_ss<0, 0, DH128, DH128>(ure, dring, slot * 16384 + kk * 32, dxa, kk * 32, (kb | kk) != 0);
        wgmma_n64_ss<0, 0, DH128, DH128>(uim, dring, slot * 16384 + 8192 + kk * 32, dxa, kk * 32, (kb | kk) != 0);
      }
      wg_commit();
      if (kb > 0) { wg_wait<1>(); release((kb - 1) % NSLOT); }
      if (kb >= SB0 && kb < SB0 + 3) bias(kb - SB0);
      if (kb == 6) {
#pragma unroll
        for (int h = 0; h < 2; h++) {
          pin(lam[h].re); pin(lam[h].im);
          cplx t = cmul(lam[h], lam[h]); t = cmul(t, t); t = cmul(t, t);
          l16[h] = cmul(t, t);
          pin(l16[h].re); pin(l16[h].im);
        }
      }
      if (kb == 7) {
#pragma unroll
        for (int h = 0; h < 2; h++) {
          pin(l16[h].re); pin(l16[h].im);
          l32[h] = cmul(l16[h], l16[h]);
          const cplx a = (q & 1) ? l16[h] : cplx{1.f, 0.f}, c = (q & 2) ? l32[h] : cplx{1.f, 0.f};
          lq[h] = cmul(cmul(a, c), coef[h]);
          pin(lq[h].re); pin(lq[h].im);
        }
      }
    }
    TS(wg, 2);
    auto scale_u = [&](int i0, int i1) {
#pragma unroll
      for (int i = 0; i < 32; i++) if (i >= i0 && i < i1) {
        pin(ure[i]); pin(uim[i]);
        const cplx v = cmul(coef[(i >> 1) & 1], cplx{ure[i], uim[i]});
        ure[i] = v.re; uim[i] = v.im;
        pin(ure[i]); pin(uim[i]);
      }
    };
#pragma unroll
    for (int kb = 0; kb < 8; kb++) {
      const int u = 8 + kb, slot = u % NSLOT;
      mbar_wait(fullb + 8 * slot, (u / NSLOT) & 1);
      TK(kb);
      wg_fence();
      const uint32_t dxa = dxw + ((kb + xrot) & 7) * 1024;
#pragma unroll
      for (int kk = 0; kk < 4; kk++)
        wgmma_n96_ss<0, 1, DH128, DH64>(aa, dxa, kk * 32, dring, slot * 16384 + kk * 1024 + lbo(4096), 1);
      wg_commit();
      if (kb == 0) bias(3);
      if (kb != QK) { wg_wait<1>(); release((u - 1) % NSLOT); }
      if (kb == 0) {
        reg_fence(ure); reg_fence(uim);
#pragma unroll
        for (int h = 0; h < 2; h++) e[h] = cplx{ure[2 * h], uim[2 * h]};
      }
      if (kb == 0 || (kb >= 2 && kb <= QK && kb < 4)) {
        constexpr int tc[5] = TCUT;
#pragma unroll
        for (int t = 1; t < 16; t++) if (t >= tc[kb] && t < tc[kb + 1]) {
#pragma unroll
          for (int h = 0; h < 2; h++) { const int i = 4 * (t >> 1) + 2 * h + (t & 1); e[h] = cfma(lam[h], e[h], cplx{ure[i], uim[i]}); }
        }
#pragma unroll
        for (int h = 0; h < 2; h++) { pin(e[h].re); pin(e[h].im); }
      }
      if (kb == QK) {
        sched_fence(ck);
#pragma unroll
        for (int h = 0; h < 2; h++) {
          cplx y = {__shfl_up_sync(0xffffffffu, e[h].re, 1, 4), __shfl_up_sync(0xffffffffu, e[h].im, 1, 4)};
          if (q >= 1) e[h] = cfma(l16[h], y, e[h]);
          y = cplx{__shfl_up_sync(0xffffffffu, e[h].re, 2, 4), __shfl_up_sync(0xffffffffu, e[h].im, 2, 4)};
          if (q >= 2) e[h] = cfma(l32[h], y, e[h]);
        }
        if (q == 3) {
#pragma unroll
          for (int h = 0; h < 2; h++)
            asm volatile("st.shared.v2.f32 [%0], {%1,%2};" ::"r"(sb + OFF_CARRY + wg * 512 + (w * 16 + gr + 8 * h) * 8), "f"(e[h].re), "f"(e[h].im) : "memory");
          mbar_arrive(sb + OFF_GBAR);
        }
#pragma unroll
        for (int h = 0; h < 2; h++) e[h] = cplx{__shfl_up_sync(0xffffffffu, e[h].re, 1, 4), __shfl_up_sync(0xffffffffu, e[h].im, 1, 4)};
        wg_wait<1>(); release((u - 1) % NSLOT);
        TS(wg, 3);
      }
      if (kb == QK + 1) {
#pragma unroll
        for (int h = 0; h < 2; h++) {
          pre[h] = (q >= 1) ? cmul(coef[h], e[h]) : cplx{0.f, 0.f};
          pin(pre[h].re); pin(pre[h].im);
        }
      }
      if (kb > QK) { constexpr int sc[9] = SCUT; scale_u(sc[kb], sc[kb + 1]); }
    }
    TS(wg, 4);
    uint32_t H[56], hf[32];
    cplx hst[2];
    const uint32_t hst_addr = xw + (w * 16 + (lane & 15)) * 128 + (((lane >> 4) ^ (lane & 7)) << 4);
    const uint32_t him = (2 - rank) * 16384;
    uint32_t peer;
    asm volatile("mapa.shared::cluster.u32 %0, %1, %2;" : "=r"(peer) : "r"(sb), "r"(rank ^ 1));
    auto credit = [&]() { if (lane == 0) mbar_arrive_cl(peer + OFF_KBAR + wg * 8); };
    uint32_t g2[8];
#pragma unroll
    for (int kb = 0; kb < 8; kb++) {
      const int u = 16 + kb, slot = u % NSLOT;
      mbar_wait(fullb + 8 * slot, (u / NSLOT) & 1);
      TK(kb < 7 ? 24 + kb : 32);
      wg_fence();
#pragma unroll
      for (int kk = 0; kk < 4; kk++)
        wgmma_n128_ss<0, 1, DH128, DH128>(ab, dxw, kb * 16384 + kk * 32, dring, slot * 16384 + kk * 2048 + lbo(8192), 1);
      wg_commit();
      if (kb == 0) { constexpr int sc[9] = SCUT; scale_u(sc[8], 32); }
      if (kb == 4) {
        TS(wg, 5);
        mbar_wait(sb + OFF_CBAR, 0);
        TS(wg, 6);
#pragma unroll
        for (int h = 0; h < 2; h++) {
          const float2 c = lds_f2(sb + OFF_CARRY + wg * 512 + (w * 16 + gr + 8 * h) * 8);
          hst[h] = cfma(lq[h], cplx{c.x, c.y}, pre[h]);
        }
#pragma unroll
        for (int i = 0; i < 2; i++) {
          const uint4 v = lds_u4(sb + OFF_GT + wg * 128 + q * 32 + i * 16);
          g2[4 * i] = v.x; g2[4 * i + 1] = v.y; g2[4 * i + 2] = v.z; g2[4 * i + 3] = v.w;
        }
      }
      if (kb == 0 || TOKB != 1) { wg_wait<1>(); release((u - 1) % NSLOT); }
      if (kb) sched_fence(ck);
      if (kb < 4) {
#pragma unroll
        for (int i = kb * 6; i < kb * 6 + 6; i++) {
          pin(aa[2 * i]); pin(aa[2 * i + 1]);
          H[i] = gelu2_pair(aa[2 * i], aa[2 * i + 1]);
          pin(H[i]);
        }
      } else {
        const int j0 = (kb - 4) * 2;
        uint32_t rr[4], ri[4];
#pragma unroll
        for (int jj = 0; jj < 2; jj++) {
          const int j = j0 + jj;
#pragma unroll
          for (int h = 0; h < 2; h++) {
            const int i = 4 * j + 2 * h;
            const cplx h0 = cfma(lam[h], hst[h], cplx{ure[i], uim[i]});
            hst[h] = cfma(lam[h], h0, cplx{ure[i + 1], uim[i + 1]});
            rr[jj * 2 + h] = bf2_mul(pack_bf16(h0.re, hst[h].re), g2[j]);
            ri[jj * 2 + h] = bf2_mul(pack_bf16(h0.im, hst[h].im), g2[j]);
          }
        }
        const uint32_t a = hst_addr ^ (j0 << 4);
        asm volatile("stmatrix.sync.aligned.m8n8.x4.shared.b16 [%0], {%1,%2,%3,%4};" ::"r"(a), "r"(rr[0]), "r"(rr[1]), "r"(rr[2]), "r"(rr[3]) : "memory");
        asm volatile("stmatrix.sync.aligned.m8n8.x4.shared.b16 [%0], {%1,%2,%3,%4};" ::"r"(a + him), "r"(ri[0]), "r"(ri[1]), "r"(ri[2]), "r"(ri[3]) : "memory");
      }
      if (kb && TOKB == 1) { wg_wait<1>(); release((u - 1) % NSLOT); }
    }
    TS(wg, 7);

    uint4* const psend = g_part + (size_t)(m * 8 + rank) * 3072 + warp * 128 + lane;
    const uint4* const precv = g_part + (size_t)(m * 8 + s) * 3072 + warp * 128 + lane;
    const uint32_t pbuf = OFF_X + warp * 2048 + lane * 16;
    const uint32_t dx0 = ((sb + OFF_X) & 0x3FFFF) >> 4;
    float o[32], fin[32], rho[2];
    uint32_t tr[8];
    uint32_t r0[16], pt[16], sum[16], tag;
    auto recv_issue = [&](uint32_t (&r)[16], int k) {
#pragma unroll
      for (int i = 0; i < 4; i++) ld_b128(precv + k * 1024 + i * 32, r[4 * i], r[4 * i + 1], r[4 * i + 2], r[4 * i + 3]);
    };
    auto stale = [&](uint32_t (&r)[16]) {
      uint32_t t0, t1, r_;
      asm("lop3.b32 %0, %1, %2, %3, 0x7e;" : "=r"(t0) : "r"(r[0]), "r"(r[4]), "r"(tag));
      asm("lop3.b32 %0, %1, %2, %3, 0x7e;" : "=r"(t1) : "r"(r[8]), "r"(r[12]), "r"(tag));
      asm volatile("{.reg .pred p; .reg .b32 t; lop3.b32 t, %1, %2, 1, 0xa8; setp.ne.u32 p, t, 0; vote.sync.any.pred p, p, 0xffffffff; selp.u32 %0, 1, 0, p;}" : "=r"(r_) : "r"(t0), "r"(t1));
      return r_ != 0;
    };
    auto recv_check = [&](uint32_t (&r)[16], int k) {
      if (__builtin_expect(stale(r), 0)) {
        int tries = 0;
#pragma unroll 1
        do { recv_issue(r, k); } while (stale(r) && ++tries < 200000);
      }
    };
    auto gelu_b = [&](int i0, int i1) {
      if (TOKD && i0) sched_fence(ck);
#pragma unroll
      for (int i = i0; i < i1; i++) {
        pin(ab[2 * i]); pin(ab[2 * i + 1]);
        H[24 + i] = gelu2_pair(ab[2 * i], ab[2 * i + 1]);
        pin(H[24 + i]);
      }
      if (TOKD == 2) sched_fence(ck);
    };
    auto step = [&](float (&d)[32], int p, int k, int acc) {
      const uint32_t wo = stage_off(p);
      if (k >= 6 && k < 14) {
        const int kk = k - 6;
        if (kk < 4) wgmma_n64_rs<0, DH128, 1>(d, hf[4 * kk], hf[4 * kk + 1], hf[4 * kk + 2], hf[4 * kk + 3], dx0, wo + 14336 + kk * 32, 1);
        else wgmma_n64_rs<0, DH128, -1>(d, hf[4 * kk], hf[4 * kk + 1], hf[4 * kk + 2], hf[4 * kk + 3], dx0, wo + 22528 + (kk - 4) * 32, 1);
      } else {
        const int kk = k < 6 ? k : k - 8;
        wgmma_n64_rs<1, DH128>(d, H[4 * kk], H[4 * kk + 1], H[4 * kk + 2], H[4 * kk + 3], dx0, wo + (kk / 7) * 30720 + (kk % 7) * 2048, k != 0 || acc);
      }
    };
    auto mma = [&](float (&d)[32], int p, int k0, int k1, int acc) {
      wg_fence();
#pragma unroll
      for (int k = k0; k < k1; k++) step(d, p, k, acc);
      wg_commit();
    };
    auto send_peer = [&]() {
#pragma unroll
      for (int i = 0; i < 4; i++)
        asm volatile("st.async.shared::cluster.mbarrier::complete_tx::bytes.v4.b32 [%0], {%1,%2,%3,%4}, [%5];" ::"r"(peer + pbuf + i * 512),
                     "r"(pack_bf16(o[8 * i], o[8 * i + 1])), "r"(pack_bf16(o[8 * i + 2], o[8 * i + 3])), "r"(pack_bf16(o[8 * i + 4], o[8 * i + 5])),
                     "r"(pack_bf16(o[8 * i + 6], o[8 * i + 7])), "r"(peer + OFF_RBAR + wg * 8) : "memory");
    };
    auto recv_peer = [&](int k) {
      mbar_wait(sb + OFF_RBAR + wg * 8, k & 1);
#pragma unroll
      for (int i = 0; i < 4; i++) { const uint4 v = lds_u4(sb + pbuf + i * 512); pt[4 * i] = v.x; pt[4 * i + 1] = v.y; pt[4 * i + 2] = v.z; pt[4 * i + 3] = v.w; }
    };
    auto send_owner = [&](float (&d)[32], int k) {
#pragma unroll
      for (int i = 0; i < 4; i++) {
#pragma unroll
        for (int c = 4 * i; c < 4 * i + 4; c++) pt[c] = bf2_add(pt[c], pack_bf16(d[2 * c], d[2 * c + 1]));
        asm("lop3.b32 %0, %0, 1, %1, 0xb8;" : "+r"(pt[4 * i]) : "r"(tag));
        st_b128(psend + (((sp + 1 + k) & 3) * 6 + k) * 1024 + i * 32, pt[4 * i], pt[4 * i + 1], pt[4 * i + 2], pt[4 * i + 3]);
      }
      __syncwarp();
      credit();
    };
    auto load_fin = [&]() {
      mbar_wait(sb + OFF_LBAR, 1);
#pragma unroll
      for (int j = 0; j < 8; j++) {
        const uint4 v = lds_u4(sb + pbuf + 16384 + (j >> 2) * 16384 + (j & 3) * 512);
        fin[4 * j] = __uint_as_float(v.x); fin[4 * j + 1] = __uint_as_float(v.y); fin[4 * j + 2] = __uint_as_float(v.z); fin[4 * j + 3] = __uint_as_float(v.w);
      }
    };
    auto ldk = [&](int pos) { if (pos == K0P) recv_issue(sum, 0); if (pos == K1P) recv_issue(r0, 1); };
    auto arm = [&]() { if ((threadIdx.x & 127) == 0) mbar_expect_tx(sb + OFF_RBAR + wg * 8, 8192); };
#pragma unroll
    for (int p = 0; p < 8; p++) {
      if (p == 0) {
        TK(40);
        mbar_wait(fullb, 0);
        TK(41);
        mma(o, 0, 0, 3, 0);
        wg_wait<1>(); release(5);
        gelu_b(0, 4);
        mma(o, 0, 3, 6, 0);
        bar_sync(1 + wg, 128);
        {
          const uint32_t ha = xw + ((lane >> 4) * 8 + (lane & 7)) * 128 + (((2 * w + ((lane >> 3) & 1)) ^ (lane & 7)) << 4);
#pragma unroll
          for (int kk = 0; kk < 8; kk++)
            asm volatile("ldmatrix.sync.aligned.m8n8.x4.trans.shared.b16 {%0,%1,%2,%3}, [%4];" : "=r"(hf[4 * kk]), "=r"(hf[4 * kk + 1]), "=r"(hf[4 * kk + 2]), "=r"(hf[4 * kk + 3])
                         : "r"(ha + (kk >> 2) * him + (kk & 3) * 2048) : "memory");
        }
        gelu_b(4, 10);
        TK(42);
        mbar_wait(fullb + 8, 0);
        TK(43);
        mma(o, 0, 6, 10, 0);
        credit();
        gelu_b(10, 16);
        mma(o, 0, 10, 15, 0);
        gelu_b(16, 24);
        TK(44);
        mbar_wait(fullb + 16, 0);
        TK(45);
        mma(o, 0, 15, 18, 0);
        gelu_b(24, 32);
        if (wg == 1) bar_sync(4, 256);
        mma(o, 0, 18, 22, 0);
      } else {
        TR(0);
        if (EW == 0 || (EW == 1 && (p & 1))) mbar_wait(sb + OFF_XFULL + 8 * p, 1);
        TR(1);
        bar_sync(3 + wg, 256);
        if (p < 7) mma(o, p, 0, 22, 0);
        else if (GAP == 0) mma(fin, p, 0, 22, 1);
        else {
          mma(fin, p, 0, GAP, 1);
          recv_peer(3);
          tag = lds_u(sb + OFF_EPOCH);
          mma(fin, p, GAP, 22, 1);
        }
      }
      if (p < 7 || wg == 0) bar_arrive(4 - wg, 256);
      TR(2);
      if (p != TP) TS(wg, 8 + p);
      if (p < 7 && (EW == 2 || (EW == 1 && (p & 1)))) mbar_wait(sb + OFF_XFULL + 8 * (p + 1), 1);
      ldk(10 * p);
      if (p == 2) asm volatile("st.shared.u32 [%0], %1;" ::"r"(sb + OFF_EPOCH + 4), "r"(ck) : "memory");
      if ((p & 1) == 0) {
        arm();
        if (p == 6) {
          mbar_wait(sb + OFF_EMPTY + 32, 0);
          tag = lds_u(sb + OFF_EPOCH);
          recv_check(sum, 0); recv_check(r0, 1);
#pragma unroll
          for (int i = 0; i < 16; i++) sum[i] = bf2_add(sum[i], r0[i]);
        }
        TR(3);
        mbar_wait(sb + OFF_KBAR + wg * 8, (p >> 1) & 1);
        TR(4);
      } else {
        if (p == 1 || (p == 7 && GAP == 0)) tag = lds_u(sb + OFF_EPOCH);
        TR(3);
        if (p < 7 || GAP == 0) recv_peer(p >> 1);
        TR(4);
        if (p == 7) {
          recv_check(r0, 2);
#pragma unroll
          for (int i = 0; i < 16; i++) sum[i] = bf2_add(sum[i], bf2_add(r0[i], pt[i]));
        }
      }
      if (p == FINP && !FINW) load_fin();
      ldk(10 * p + 1);
      TR(5);
      wg_wait<0>();
      TR(6);
      if (p < 5) release(p);
      if (p < 7) reg_fence(o); else reg_fence(fin);
      ldk(10 * p + 2);
      if ((p & 1) == 0) {
        if (p == 6) recv_issue(r0, 2);
        send_peer();
        if (p == FINP && FINW) load_fin();
      } else if (p < 7) {
        send_owner(o, p >> 1);
      }
      ldk(10 * p + 3);
      if (p == 2) {
#pragma unroll
        for (int h = 0; h < 2; h++) { rho[h] = __fdividef(2.f, 4.f + bf_lo(lds_h(sb + OFF_GS + (wg * 64 + w * 16 + gr + 8 * h) * 2))); pin(rho[h]); }
      }
      TR(7);
    }
    {
      TS(wg, 16);
      const uint32_t tb = sb + OFF_X + stage_off(0) + warp * 4096;
      const uint32_t ta = tb + gr * 256 + ((gr & 3) << 5) + q * 8;
      const uint32_t la = tb + (lane >> 3) * 256 + (((lane & 7) << 4) ^ ((lane >> 3) << 5));
      float* op = out + (size_t)(m * 128 + wg * 64 + (lane >> 4) * 16 + w * 4 + ((lane >> 3) & 1)) * DM + s * 64 + (lane & 7) * 4;
#pragma unroll
      for (int qq = 0; qq < 4; qq += QS) {
#pragma unroll
        for (int qt = qq; qt < qq + QS; qt++) {
          const int h = qt & 1, ch = qt >> 1;
#pragma unroll
          for (int j = 0; j < 4; j++) {
            const int i = ch * 8 + j * 2 + h;
            asm volatile("st.shared.v2.f32 [%0], {%1,%2};" ::"r"((ta ^ (j << 5)) + h * 2048 + ch * 128),
                         "f"((fin[2 * i] + bf_lo(sum[i])) * rho[h]), "f"((fin[2 * i + 1] + bf_hi(sum[i])) * rho[h]) : "memory");
          }
        }
        __syncwarp();
#pragma unroll
        for (int qt = qq; qt < qq + QS; qt++) {
          const int h = qt & 1, ch = qt >> 1;
#pragma unroll
          for (int r = 0; r < 2; r++)
            *reinterpret_cast<uint4*>(op + (r * 32 + h * 2) * DM + ch * 32) = lds_u4(la + (h * 2 + r) * 1024 + ch * 128);
        }
      }
      if (threadIdx.x == 128) g_epoch[b] = tag;
      TS(wg, 17); TG(wg); TRD(); TDUMP();
    }
  } else {
    asm volatile("setmaxnreg.dec.sync.aligned.u32 56;");
    int wsel = warp;
    asm("" : "+r"(wsel));
    if (wsel > 8) {
      if (warp != 11) {
        const int t = threadIdx.x - 288;
        unsigned par;
        asm volatile("ld.relaxed.gpu.global.u32 %0, [%1];" : "=r"(par) : "l"(g_epoch + b) : "memory");
        const float pr = bf_ld(lam_re + s * 64 + t), pi = bf_ld(lam_im + s * 64 + t), pd = bf_ld(log_dt + s * 64 + t);
        asm volatile("barrier.cluster.wait.aligned;" ::: "memory");
        par = __shfl_sync(0xffffffffu, (par + 1) & 1, 0);
        cplx l64 = make_lam(pr, pi, pd);
        {
          const float inv = __fdividef(1.f, fmaf(pr, pr, pi * pi));
          const cplx cf = cmul(cplx{l64.re - 1.f, l64.im}, cplx{pr * inv, -pi * inv});
          asm volatile("st.shared.v4.f32 [%0], {%1,%2,%3,%4};" ::"r"(sb + OFF_LC + t * 16), "f"(l64.re), "f"(l64.im), "f"(cf.re), "f"(cf.im) : "memory");
          mbar_arrive(sb + OFF_LBAR);
        }
#pragma unroll
        for (int i = 0; i < 6; i++) l64 = cmul(l64, l64);
        cplx l128 = cmul(l64, l64);
        pin(l128.re); pin(l128.im);
        uint32_t vr[15], vi[15];
#pragma unroll
        for (int i = 0; i < 15; i++) { vr[i] = par; vi[i] = 0; pin(vr[i]); pin(vi[i]); }
        mbar_wait(sb + OFF_GBAR, 0);
        const float2 e0 = lds_f2(sb + OFF_CARRY + t * 8), e1 = lds_f2(sb + OFF_CARRY + 512 + t * 8);
        float2* eb = g_end + s * 1024 + t;
        {
          const cplx e = cfma(l64, cplx{e0.x, e0.y}, cplx{e1.x, e1.y});
          const unsigned long long v = ((unsigned long long)__float_as_uint(e.im) << 32) | ((__float_as_uint(e.re) & ~1u) | par);
          asm volatile("st.relaxed.gpu.global.b64 [%0], %1;" ::"l"(eb + m * 64), "l"(v) : "memory");
        }
        if (t == 0) TS(3, 1);
        cplx S = {0.f, 0.f};
        {
          if (LBD) __nanosleep(LBD);
          const float2* e15 = eb + (m - 15) * 64;
          int tries = 0;
          bool bad;
#pragma unroll 1
          do {
#pragma unroll
            for (int i = 0; i < 15; i++)
              asm volatile("{.reg .pred p; .reg .b64 v; mov.b64 v, {%0,%1}; setp.ge.s32 p, %3, %4; @p ld.relaxed.gpu.global.b64 v, [%2]; mov.b64 {%0,%1}, v;}"
                           : "+r"(vr[i]), "+r"(vi[i]) : "l"(e15 + i * 64), "r"(m), "r"(15 - i) : "memory");
            uint32_t x = vr[0] ^ par;
#pragma unroll
            for (int i = 1; i < 15; i++) asm("lop3.b32 %0, %0, %1, %2, 0xf6;" : "+r"(x) : "r"(vr[i]), "r"(par));
            bad = __any_sync(0xffffffffu, x & 1);
          } while (bad && ++tries < 200000);
          if (t == 0) TS(3, 2);
          S = cplx{__uint_as_float(vr[0]), __uint_as_float(vi[0])};
#pragma unroll
          for (int i = 1; i < 15; i++) S = cfma(l128, S, cplx{__uint_as_float(vr[i]), __uint_as_float(vi[i])});
        }
        const cplx S1 = cfma(l64, S, cplx{e0.x, e0.y});
        asm volatile("st.shared.v2.f32 [%0], {%1,%2};" ::"r"(sb + OFF_CARRY + t * 8), "f"(S.re), "f"(S.im) : "memory");
        asm volatile("st.shared.v2.f32 [%0], {%1,%2};" ::"r"(sb + OFF_CARRY + 512 + t * 8), "f"(S1.re), "f"(S1.im) : "memory");
        mbar_arrive(sb + OFF_CBAR);
        if (t == 0) TS(3, 3);
        mbar_wait(sb + OFF_CBAR, 0);
        const int gr = lane >> 2, q = lane & 3;
        float2 db[8];
#pragma unroll
        for (int j = 0; j < 8; j++) db[j] = lds_f2(sb + OFF_DB + j * 32 + q * 8);
        mbar_wait(sb + OFF_XFULL + 16, 1);
        mbar_wait(sb + OFF_EMPTY, 0);
#pragma unroll 1
        for (int cw = warp - 9; cw < 8; cw += 2) {
          const float r0 = 0.5f * bf_lo(lds_h(sb + OFF_GS + (cw * 16 + gr) * 2)), r1 = 0.5f * bf_lo(lds_h(sb + OFF_GS + (cw * 16 + gr) * 2 + 16));
          const uint32_t xa = sb + OFF_X + (1 + rank) * 16384 + (cw * 16 + (lane & 15)) * 128 + (((lane >> 4) ^ (lane & 7)) << 4);
          uint32_t xv[16];
#pragma unroll
          for (int i = 0; i < 4; i++)
            asm volatile("ldmatrix.sync.aligned.m8n8.x4.shared.b16 {%0,%1,%2,%3}, [%4];" : "=r"(xv[4 * i]), "=r"(xv[4 * i + 1]), "=r"(xv[4 * i + 2]), "=r"(xv[4 * i + 3])
                         : "r"(xa ^ (i << 5)) : "memory");
          __syncwarp();
#pragma unroll
          for (int j = 0; j < 8; j++) {
            const uint32_t x0 = bf2_mul(xv[2 * j], __float_as_uint(db[j].x)), x1 = bf2_mul(xv[2 * j + 1], __float_as_uint(db[j].x));
            pin(db[j].y);
            const float bl = bf_lo(__float_as_uint(db[j].y)), bh = bf_hi(__float_as_uint(db[j].y));
            asm volatile("st.shared.v4.f32 [%0], {%1,%2,%3,%4};" ::"r"(sb + OFF_X + 16384 + (j >> 2) * 16384 + cw * 2048 + (j & 3) * 512 + lane * 16), "f"(fmaf(bf_lo(x0), r0, bl)),
                         "f"(fmaf(bf_hi(x0), r0, bh)), "f"(fmaf(bf_lo(x1), r1, bl)), "f"(fmaf(bf_hi(x1), r1, bh)) : "memory");
          }
        }
        mbar_arrive(sb + OFF_LBAR);
        if (t == 0) TS(3, 5);
      } else {
        if (lane == 0) TG(2);
        const uint4* gwp = reinterpret_cast<const uint4*>(gate_w) + (lane & 7);
        uint4 gw[4];
#pragma unroll
        for (int i = 0; i < 4; i++) gw[i] = __ldg(gwp + i * 8);
        unsigned par;
        asm volatile("ld.relaxed.gpu.global.u32 %0, [%1];" : "=r"(par) : "l"(g_epoch + b) : "memory");
        const uint32_t dk = __ldg(reinterpret_cast<const uint32_t*>(dskip + s * 64) + lane), bb = __ldg(reinterpret_cast<const uint32_t*>(b2 + s * 64) + lane);
        asm volatile("barrier.cluster.wait.aligned;" ::: "memory");
        const int row = s * 16 + (lane >> 3);
        const uint32_t xr0 = sb + OFF_X + row * 128 + (((lane & 7) ^ (row & 7)) << 4), xr1 = (xr0 + 512) ^ 64;
        float z[4] = {0.f, 0.f, 0.f, 0.f};
#pragma unroll
        for (int kb = 0; kb < 8; kb++) {
          const uint32_t wv[4] = {gw[kb & 3].x, gw[kb & 3].y, gw[kb & 3].z, gw[kb & 3].w};
          if (kb < 4) gw[kb] = __ldg(gwp + (kb + 4) * 8);
          mbar_wait(sb + OFF_XFULL + 8 * kb, 0);
          if ((PF & 2) && kb == PFK && elect_one()) {
            l2_prefetch(pf_w1 + b * 7168, 14336);
            l2_prefetch(pf_cre + b * 2048, 4096);
            l2_prefetch(pf_cim + b * 2048, 4096);
            l2_prefetch(pf_w2 + b * 7168, 14336);
          }
          const uint32_t xo = ((kb + xrot) & 7) * 16384;
#pragma unroll
          for (int r = 0; r < 4; r++) {
            const uint4 a = lds_u4(((r & 1) ? xr1 : xr0) + xo + (r >> 1) * 1024);
            const uint32_t p = bf2_fma(a.w, wv[3], bf2_fma(a.z, wv[2], bf2_fma(a.y, wv[1], bf2_mul(a.x, wv[0]))));
            z[r] += bf_lo(p); z[r] += bf_hi(p);
          }
        }
        if (lane == 0) asm volatile("st.shared.u32 [%0], %1;" ::"r"(sb + OFF_EPOCH), "r"(par + 1) : "memory");
        par = (par + 1) & 1;
        {
          float y0 = (lane & 4) ? z[1] : z[0], y1 = (lane & 4) ? z[3] : z[2];
          y0 += __shfl_xor_sync(0xffffffffu, (lane & 4) ? z[0] : z[1], 4);
          y1 += __shfl_xor_sync(0xffffffffu, (lane & 4) ? z[2] : z[3], 4);
          float zz = (lane & 2) ? y1 : y0;
          zz += __shfl_xor_sync(0xffffffffu, (lane & 2) ? y0 : y1, 2);
          zz += __shfl_xor_sync(0xffffffffu, zz, 1);
          const float rho = 4.f * expf(zz > 40.f ? 40.f : zz);
          if ((lane & 1) == 0)
            asm volatile("st.relaxed.gpu.global.u32 [%0], %1;" ::"l"(g_gate + m * 128 + row + (lane & 4) + (lane & 2) * 4), "r"((__float_as_uint(rho) & ~1u) | par) : "memory");
        }
        if ((PF & 8) && elect_one()) {
          l2_prefetch(pf_w2 + b * 7168, 14336);
          l2_prefetch(pf_cre + b * 2048, 4096);
          l2_prefetch(pf_cim + b * 2048, 4096);
        }
        if (lane == 0) TS(3, 0);
        mbar_wait(sb + OFF_GBAR, 0);
        asm volatile("st.shared.v2.u32 [%0], {%1,%2};" ::"r"(sb + OFF_DB + lane * 8), "r"(dk), "r"(bf2_add(bb, bb)) : "memory");
        uint32_t g0, g1, g2, g3;
        int tries = 0;
#pragma unroll 1
        do {
          asm volatile("ld.relaxed.gpu.global.v4.u32 {%0,%1,%2,%3}, [%4];" : "=r"(g0), "=r"(g1), "=r"(g2), "=r"(g3) : "l"(g_gate + m * 128 + lane * 4) : "memory");
        } while ((((g0 ^ par) | (g1 ^ par) | (g2 ^ par) | (g3 ^ par)) & 1) && ++tries < 200000);
        asm volatile("st.shared.v2.u32 [%0], {%1,%2};" ::"r"(sb + OFF_GS + lane * 8), "r"(pack_bf16(__uint_as_float(g0), __uint_as_float(g1))),
                     "r"(pack_bf16(__uint_as_float(g2), __uint_as_float(g3))) : "memory");
        const uint32_t gt = sb + OFF_GT + (lane >> 4) * 128 + (lane & 1) * 64 + ((lane >> 1) & 7) * 4;
        asm volatile("st.shared.u32 [%0], %1;" ::"r"(gt), "r"(pack_bf16(__uint_as_float(g0), __uint_as_float(g1))) : "memory");
        asm volatile("st.shared.u32 [%0], %1;" ::"r"(gt + 32), "r"(pack_bf16(__uint_as_float(g2), __uint_as_float(g3))) : "memory");
        mbar_arrive(sb + OFF_CBAR);
        if (lane == 0) TS(3, 4);
      }
    } else {
      asm volatile("barrier.cluster.wait.aligned;" ::: "memory");
      if (elect_one()) {
        TS(2, 1);
        const uint32_t t0 = clock();
#pragma unroll 1
        for (int u = W0; u < 8; u++) {
          if (u >= 1) while ((uint32_t)clock() - t0 < D0 + (u - 1) * D1) {}
          mbar_expect_tx(sb + OFF_XFULL + 8 * u, 16384);
          tma5d_mc(sb + OFF_X + ((u + xrot) & 7) * 16384 + rank * 8192, &maps.x, u * 64, 2 * m + rank, sb + OFF_XFULL + 8 * u);
          const int sl = u < 6 ? u : u - 6;
          if (u >= 6) mbar_wait(sb + OFF_EMPTY + 8 * sl, 0);
          mbar_expect_tx(sb + OFF_FULL + 8 * sl, 16384);
          tma2d(sb + OFF_RING + sl * 16384, &maps.bre, u * 64, s * 64, sb + OFF_FULL + 8 * sl);
          tma2d(sb + OFF_RING + sl * 16384 + 8192, &maps.bim, u * 64, s * 64, sb + OFF_FULL + 8 * sl);
          if (u == 2) asm volatile("prefetch.tensormap [%0];" ::"l"(&maps.w1b) : "memory");
        }
        TS(2, 5);
        int slot = 2; uint32_t ph = 0;
#pragma unroll 1
        for (int u = 8; u < 24; u++) {
          const uint32_t fb = sb + OFF_FULL + 8 * slot, dst = sb + OFF_RING + slot * 16384;
          mbar_wait(sb + OFF_EMPTY + 8 * slot, ph);
          TS2(0, u);
          if (u < 16) {
            mbar_expect_tx(fb, 12288);
            tma3d(dst, &maps.w1b, 0, (u - 8) * 64, s * 7, fb);
            if (TMP2 && u < 12) asm volatile("prefetch.tensormap [%0];" ::"l"(&maps.w1a + (u - 8)) : "memory");
          } else {
            mbar_expect_tx(fb, 16384);
            tma2d(dst, &maps.w1a, s * 224 + 96, ((u - xrot) & 7) * 64, fb);
            tma2d(dst + 8192, &maps.w1a, s * 224 + 160, ((u - xrot) & 7) * 64, fb);
          }
          if (++slot == NSLOT) { slot = 0; ph ^= 1; }
        }
#pragma unroll 1
        for (int j = 0; j < 3; j++) {
          const uint32_t fb = sb + OFF_FULL + 8 * j, dst = sb + OFF_X + stage_off(0);
          const int c = ((sp + 1) & 3) * 128 + ((rank ^ 1) << 6);
          mbar_wait(sb + OFF_EMPTY + 8 + 8 * j, 1);
          mbar_expect_tx(fb, j == 1 ? 16384 : 14336);
          if (j == 1) {
            tma2d(dst + 14336, &maps.cre, s * 64, c, fb);
            tma2d(dst + 22528, &maps.cim, s * 64, c, fb);
          } else {
            tma2d(dst + j * 15360, &maps.w2, c, s * 224 + j * 56, fb);
          }
        }
#pragma unroll 1
        for (int p = 1; p < 8; p++) {
          const int c = ((sp + 1 + (p >> 1)) & 3) * 128 + (((rank ^ p ^ 1) & 1) << 6);
          const uint32_t fb = sb + OFF_XFULL + 8 * p, dst = sb + OFF_X + stage_off(p);
          if (p == 2 || p > 3) mbar_wait(sb + OFF_EMPTY + (p == 2 ? 40 : (p - 4) * 8), p == 2);
          TS2(0, 32 + p);
          mbar_expect_tx(fb, 45056);
          tma2d(dst, &maps.w2, c, s * 224, fb);
          tma2d(dst + 14336, &maps.cre, s * 64, c, fb);
          tma2d(dst + 22528, &maps.cim, s * 64, c, fb);
          tma2d(dst + 30720, &maps.w2, c, s * 224 + 112, fb);
        }
        TS(2, 2);
      }
    }
  }
}

typedef CUresult (*EncFn)(CUtensorMap*, CUtensorMapDataType, cuuint32_t, void*, const cuuint64_t*, const cuuint64_t*, const cuuint32_t*,
                          const cuuint32_t*, CUtensorMapInterleave, CUtensorMapSwizzle, CUtensorMapL2promotion, CUtensorMapFloatOOBfill);

void encode(EncFn f, CUtensorMap* mp, const void* p, int rank, const cuuint64_t* dims, const cuuint64_t* strides, const cuuint32_t* box, CUtensorMapSwizzle sw) {
  cuuint32_t es[5] = {1, 1, 1, 1, 1};
  f(mp, CU_TENSOR_MAP_DATA_TYPE_BFLOAT16, rank, const_cast<void*>(p), dims, strides, box, es, CU_TENSOR_MAP_INTERLEAVE_NONE, sw,
    CU_TENSOR_MAP_L2_PROMOTION_L2_128B, CU_TENSOR_MAP_FLOAT_OOB_FILL_NONE);
}

}

extern "C" void kernel_launch(void* const* d_in, const int* in_sizes, int n_in, void* d_out, int out_size) {
  typedef const __nv_bfloat16* bp;
  bp x = (bp)d_in[0], lre = (bp)d_in[1], lim = (bp)d_in[2], bre = (bp)d_in[3], bim = (bp)d_in[4], cre = (bp)d_in[5], cim = (bp)d_in[6],
     ldt = (bp)d_in[7], dsk = (bp)d_in[8], w1 = (bp)d_in[10], b1 = (bp)d_in[11], w2 = (bp)d_in[12], b2 = (bp)d_in[13], gw = (bp)d_in[14];
  static EncFn enc = nullptr;
  if (!enc) {
    void* f = nullptr;
    cudaDriverEntryPointQueryResult qr;
    cudaGetDriverEntryPoint("cuTensorMapEncodeTiled", &f, cudaEnableDefault, &qr);
    enc = (EncFn)f;
    cudaFuncSetAttribute(fused_kernel, cudaFuncAttributeMaxDynamicSharedMemorySize, SMEM_BYTES);
  }
  Maps maps;
  {
    cuuint64_t d[5] = {DM, 2, 4, 8, SEQ / 64}, st[4] = {DM * 2, 16 * DM * 2, 2 * DM * 2, 64 * DM * 2};
    cuuint32_t bx[5] = {64, 2, 4, 8, 1};
    encode(enc, &maps.x, x, 5, d, st, bx, CU_TENSOR_MAP_SWIZZLE_128B);
  }
  {
    cuuint64_t d[2] = {DM, DM}, st[1] = {DM * 2};
    cuuint32_t bx[2] = {64, 64};
    encode(enc, &maps.bre, bre, 2, d, st, bx, CU_TENSOR_MAP_SWIZZLE_128B);
    encode(enc, &maps.bim, bim, 2, d, st, bx, CU_TENSOR_MAP_SWIZZLE_128B);
    encode(enc, &maps.cre, cre, 2, d, st, bx, CU_TENSOR_MAP_SWIZZLE_128B);
    encode(enc, &maps.cim, cim, 2, d, st, bx, CU_TENSOR_MAP_SWIZZLE_128B);
  }
  {
    cuuint64_t d[2] = {FF, DM}, st[1] = {FF * 2};
    cuuint32_t bx[2] = {64, 64};
    encode(enc, &maps.w1a, w1, 2, d, st, bx, CU_TENSOR_MAP_SWIZZLE_128B);
    cuuint64_t d3[3] = {32, DM, FF / 32}, st3[2] = {FF * 2, 64};
    cuuint32_t bx3[3] = {32, 64, 3};
    encode(enc, &maps.w1b, w1, 3, d3, st3, bx3, CU_TENSOR_MAP_SWIZZLE_64B);
  }
  {
    cuuint64_t d[2] = {DM, FF}, st[1] = {DM * 2};
    cuuint32_t bx[2] = {64, 112};
    encode(enc, &maps.w2, w2, 2, d, st, bx, CU_TENSOR_MAP_SWIZZLE_128B);
  }
  fused_kernel<<<128, 384, SMEM_BYTES>>>(lre, lim, ldt, dsk, b1, b2, gw, w1, w2, cre, cim, (float*)d_out, maps);
}
```

```cpp
#include <cuda_runtime.h>
#include <cuda_bf16.h>
#include <cuda.h>
#include <stdint.h>

#define MAP 1
#define D0 250
#define D1 500
#define PF 4
#define PFK 5
#define GELUP 1
#define EW 2
#define K1E 1
#define K2E 0
#define QS 1
#define K2G 4
#define FINP 4
#define LBD 300
#define PFS 32
#define SB0 2
#define PFD 2
#define HOLD 0
#define GAP 14
#define FINW 0
#define K0P 33
#define K1P 53
#define TMP2 1
#define W0 1
#define LCK 4
#define TOKA 0
#define TOKB 2
#define TOKD 0
#define TKT 999
#define AV 3
#define QK 4
#define TCUT {1, 6, 6, 11, 16}
#define SCUT {0, 0, 0, 0, 0, 0, 8, 16, 24}
#define QF 1
#define TP 9
#define TW 0

namespace {

constexpr int SEQ = 2048, DM = 512, FF = 1792;
constexpr int NSLOT = 6;
constexpr uint32_t OFF_X = 0, OFF_RING = 131072, OFF_MISC = 229376;
constexpr uint32_t OFF_XFULL = OFF_MISC, OFF_FULL = OFF_XFULL + 64, OFF_RBAR = OFF_FULL + 48, OFF_EMPTY = OFF_RBAR + 16, OFF_KBAR = OFF_EMPTY + 48,
                   OFF_GBAR = OFF_KBAR + 16, OFF_LBAR = OFF_GBAR + 8, OFF_CBAR = OFF_LBAR + 8, OFF_EPOCH = OFF_CBAR + 8;
constexpr uint32_t OFF_LC = OFF_MISC + 256;
constexpr uint32_t OFF_GS = OFF_LC;
constexpr uint32_t OFF_GT = OFF_LC + 256;
constexpr uint32_t OFF_DB = OFF_LC + 512;
constexpr uint32_t OFF_CARRY = OFF_LC + 1024;
constexpr uint32_t OFF_DBG = OFF_CARRY + 1024;
constexpr uint32_t SMEM_BYTES = OFF_DBG + 768;
static_assert(SMEM_BYTES <= 232448, "smem");

struct Maps { CUtensorMap x, bre, bim, w1b, w1a, w2, cre, cim; };
__host__ __device__ constexpr uint32_t stage_off(int p) { return 49152 + 45056 * (((p >> 1) & 1) + 2 * (p & 1)); }

__device__ uint4 g_part[16 * 8 * 3 * 1024];
__device__ float2 g_end[8 * 16 * 64];
__device__ unsigned g_gate[SEQ];
__device__ unsigned g_epoch[128];
#define TG(role) do {} while (0)
#define TS2(role, i) do {} while (0)
#define TS(role, i) do {} while (0)
#define TDUMP() do {} while (0)
#define TR(i) do {} while (0)
#define TK(i) do {} while (0)
#define TRD() do {} while (0)

__device__ __forceinline__ void mbar_init(uint32_t bar, uint32_t cnt) { asm volatile("mbarrier.init.shared::cta.b64 [%0], %1;" ::"r"(bar), "r"(cnt)); }
__device__ __forceinline__ void mbar_expect_tx(uint32_t bar, uint32_t bytes) { asm volatile("mbarrier.arrive.expect_tx.shared::cta.b64 _, [%0], %1;" ::"r"(bar), "r"(bytes) : "memory"); }
__device__ __forceinline__ void mbar_arrive(uint32_t bar) { asm volatile("mbarrier.arrive.shared::cta.b64 _, [%0];" ::"r"(bar) : "memory"); }
__device__ __forceinline__ void mbar_arrive_cl(uint32_t cbar) { asm volatile("mbarrier.arrive.shared::cluster.b64 _, [%0];" ::"r"(cbar) : "memory"); }
__device__ __forceinline__ void mbar_wait(uint32_t bar, uint32_t parity) {
  asm volatile(
      "{\n.reg .pred p;\n.reg .u32 c;\n"
      "mbarrier.try_wait.parity.shared::cta.b64 p, [%0], %1;\n"
      "@p bra.uni LAB_DONE;\n"
      "mov.u32 c, 0;\n"
      "LAB_WAIT:\n"
      "mbarrier.try_wait.parity.shared::cta.b64 p, [%0], %1;\n"
      "@p bra.uni LAB_DONE;\n"
      "add.u32 c, c, 1;\nsetp.lt.u32 p, c, 200000;\n@p bra.uni LAB_WAIT;\n"
      "LAB_DONE:\n}" ::"r"(bar), "r"(parity) : "memory");
}
__device__ __forceinline__ void tma2d(uint32_t dst, const CUtensorMap* m, int c0, int c1, uint32_t bar) {
  asm volatile("cp.async.bulk.tensor.2d.shared::cluster.global.mbarrier::complete_tx::bytes [%0], [%1, {%3,%4}], [%2];"
               ::"r"(dst), "l"(m), "r"(bar), "r"(c0), "r"(c1) : "memory");
}
__device__ __forceinline__ void tma3d(uint32_t dst, const CUtensorMap* m, int c0, int c1, int c2, uint32_t bar) {
  asm volatile("cp.async.bulk.tensor.3d.shared::cluster.global.mbarrier::complete_tx::bytes [%0], [%1, {%3,%4,%5}], [%2];"
               ::"r"(dst), "l"(m), "r"(bar), "r"(c0), "r"(c1), "r"(c2) : "memory");
}
__device__ __forceinline__ void tma5d(uint32_t dst, const CUtensorMap* m, int c0, int c4, uint32_t bar) {
  asm volatile("cp.async.bulk.tensor.5d.shared::cluster.global.mbarrier::complete_tx::bytes [%0], [%1, {%3,%5,%5,%5,%4}], [%2];"
               ::"r"(dst), "l"(m), "r"(bar), "r"(c0), "r"(c4), "r"(0) : "memory");
}
__device__ __forceinline__ void tma5d_mc(uint32_t dst, const CUtensorMap* m, int c0, int c4, uint32_t bar) {
  asm volatile("cp.async.bulk.tensor.5d.shared::cluster.global.mbarrier::complete_tx::bytes.multicast::cluster [%0], [%1, {%3,%5,%5,%5,%4}], [%2], %6;"
               ::"r"(dst), "l"(m), "r"(bar), "r"(c0), "r"(c4), "r"(0), "h"((uint16_t)3) : "memory");
}
__device__ __forceinline__ void l2_prefetch(const void* p, uint32_t bytes) { asm volatile("cp.async.bulk.prefetch.L2.global [%0], %1;" ::"l"(p), "r"(bytes) : "memory"); }
__device__ __forceinline__ bool elect_one() {
  uint32_t pred;
  asm volatile("{.reg .pred P; elect.sync _|P, 0xffffffff; selp.u32 %0, 1, 0, P;}" : "=r"(pred));
  return pred != 0;
}
__device__ __forceinline__ void wg_fence() { asm volatile("wgmma.fence.sync.aligned;" ::: "memory"); }
__device__ __forceinline__ void wg_commit() { asm volatile("wgmma.commit_group.sync.aligned;" ::: "memory"); }
template <int N> __device__ __forceinline__ void wg_wait() { asm volatile("wgmma.wait_group.sync.aligned %0;" ::"n"(N) : "memory"); }
__device__ __forceinline__ void pin(float& a) { asm volatile("" : "+f"(a)::"memory"); }
__device__ __forceinline__ void pin(uint32_t& a) { asm volatile("" : "+r"(a)::"memory"); }
template <int N> __device__ __forceinline__ void reg_fence(float (&d)[N]) {
#pragma unroll
  for (int i = 0; i < N; i++) pin(d[i]);
}
__device__ __forceinline__ void bar_sync(int id, int n) { asm volatile("bar.sync %0, %1;" ::"r"(id), "r"(n) : "memory"); }
__device__ __forceinline__ void bar_arrive(int id, int n) { asm volatile("bar.arrive %0, %1;" ::"r"(id), "r"(n) : "memory"); }
constexpr uint32_t DH128 = (1024 >> 4) | (1u << 30), DH64 = (512 >> 4) | (2u << 30);
__host__ __device__ constexpr uint32_t lbo(uint32_t bytes) { return (bytes >> 4) << 20; }
__device__ __forceinline__ uint32_t pack_bf16(float lo, float hi) { uint32_t r; asm("cvt.rn.bf16x2.f32 %0, %1, %2;" : "=r"(r) : "f"(hi), "f"(lo)); return r; }
__device__ __forceinline__ float bf_lo(uint32_t v) { return __uint_as_float(v << 16); }
__device__ __forceinline__ float bf_hi(uint32_t v) { return __uint_as_float(v & 0xffff0000u); }
__device__ __forceinline__ float bf_ld(const __nv_bfloat16* p) { return __bfloat162float(__ldg(p)); }
__device__ __forceinline__ uint32_t late16(uint32_t bar) {
  uint32_t r;
  asm volatile("{.reg .pred p; mbarrier.test_wait.parity.shared::cta.b64 p, [%1], 0; selp.u32 %0, 16, 0, p;}" : "=r"(r) : "r"(bar) : "memory");
  return r;
}
__device__ __forceinline__ float2 lds_f2(uint32_t a) { float2 v; asm volatile("ld.shared.v2.f32 {%0,%1}, [%2];" : "=f"(v.x), "=f"(v.y) : "r"(a)); return v; }
__device__ __forceinline__ uint32_t lds_h(uint32_t a) { uint32_t v; asm volatile("ld.shared.u16 %0, [%1];" : "=r"(v) : "r"(a)); return v; }
__device__ __forceinline__ uint32_t lds_u(uint32_t a) { uint32_t v; asm volatile("ld.shared.u32 %0, [%1];" : "=r"(v) : "r"(a)); return v; }
__device__ __forceinline__ uint4 lds_u4(uint32_t a) { uint4 v; asm volatile("ld.shared.v4.u32 {%0,%1,%2,%3}, [%4];" : "=r"(v.x), "=r"(v.y), "=r"(v.z), "=r"(v.w) : "r"(a)); return v; }
__device__ __forceinline__ void st_b128(uint4* p, uint32_t a, uint32_t b, uint32_t c, uint32_t d) {
  asm volatile("st.relaxed.gpu.global.v4.b32 [%0], {%1,%2,%3,%4};" ::"l"(p), "r"(a), "r"(b), "r"(c), "r"(d) : "memory");
}
__device__ __forceinline__ void ld_b128(const uint4* p, uint32_t& a, uint32_t& b, uint32_t& c, uint32_t& d) {
  asm volatile("{.reg .b64 l, h; .reg .b128 v; ld.relaxed.gpu.global.b128 v, [%4]; mov.b128 {l,h}, v; mov.b64 {%0,%1}, l; mov.b64 {%2,%3}, h;}"
               : "=r"(a), "=r"(b), "=r"(c), "=r"(d) : "l"(p) : "memory");
}
__device__ __forceinline__ float tanh_fast(float x) { float y; asm("tanh.approx.f32 %0, %1;" : "=f"(y) : "f"(x)); return y; }
__device__ __forceinline__ float gelu2(float v) {
  float p = fmaf(v * v, 0.0356774081363f, 0.7978845608029f);
  return fmaf(v, tanh_fast(v * p), v);
}
__device__ __forceinline__ void sched_fence(uint32_t& ck) { asm volatile("{.reg .b32 c; mov.u32 c, %%clock; xor.b32 %0, %0, c;}" : "+r"(ck)::"memory"); }
__device__ __forceinline__ uint32_t bf2_mul(uint32_t a, uint32_t b) { uint32_t r; asm("mul.rn.bf16x2 %0, %1, %2;" : "=r"(r) : "r"(a), "r"(b)); return r; }
__device__ __forceinline__ uint32_t bf2_add(uint32_t a, uint32_t b) { uint32_t r; asm("add.rn.bf16x2 %0, %1, %2;" : "=r"(r) : "r"(a), "r"(b)); return r; }
__device__ __forceinline__ uint32_t bf2_fma(uint32_t a, uint32_t b, uint32_t c) { uint32_t r; asm("fma.rn.bf16x2 %0, %1, %2, %3;" : "=r"(r) : "r"(a), "r"(b), "r"(c)); return r; }
__device__ __forceinline__ uint32_t gelu2_pair(float a, float b) {
  const uint32_t v = pack_bf16(a, b);
  uint32_t t;
  asm("tanh.approx.bf16x2 %0, %1;" : "=r"(t) : "r"(bf2_fma(v, bf2_fma(bf2_mul(v, v), 0x3d123d12u, 0xbe4fbe4fu), v)));
  return bf2_fma(v, t, v);
}
struct cplx { float re, im; };
__device__ __forceinline__ cplx cmul(cplx a, cplx b) { return {fmaf(a.re, b.re, -a.im * b.im), fmaf(a.re, b.im, a.im * b.re)}; }
__device__ __forceinline__ cplx cfma(cplx a, cplx b, cplx c) {
  return {fmaf(a.re, b.re, fmaf(-a.im, b.im, c.re)), fmaf(a.re, b.im, fmaf(a.im, b.re, c.im))};
}
__device__ __forceinline__ cplx make_lam(float lre, float lim, float ldt) {
  float dt = __bfloat162float(__float2bfloat16_rn(expf(ldt)));
  float mag = expf(dt * lre), sn, cs;
  sincospif(dt * lim * 0.31830988618379067f, &sn, &cs);
  return {mag * cs, mag * sn};
}

template<int TA,int TB,uint32_t AH,uint32_t BH> __device__ __forceinline__ void wgmma_n64_ss(float (&d)[32], uint32_t al, uint32_t ao, uint32_t bl, uint32_t bo, int scale_d){
  asm volatile("{.reg .pred p; .reg .b32 t, v; .reg .b64 da, db; setp.ne.b32 p, %36, 0; add.u32 t, %32, %33; mov.b64 da, {t, %39}; add.u32 v, %34, %35; mov.b64 db, {v, %40};\n"
   "wgmma.mma_async.sync.aligned.m64n64k16.f32.bf16.bf16 {%0,%1,%2,%3,%4,%5,%6,%7,%8,%9,%10,%11,%12,%13,%14,%15,%16,%17,%18,%19,%20,%21,%22,%23,%24,%25,%26,%27,%28,%29,%30,%31}, da, db, p, 1, 1, %37, %38;}"
   : "+f"(d[0]),"+f"(d[1]),"+f"(d[2]),"+f"(d[3]),"+f"(d[4]),"+f"(d[5]),"+f"(d[6]),"+f"(d[7]),"+f"(d[8]),"+f"(d[9]),"+f"(d[10]),"+f"(d[11]),"+f"(d[12]),"+f"(d[13]),"+f"(d[14]),"+f"(d[15]),"+f"(d[16]),"+f"(d[17]),"+f"(d[18]),"+f"(d[19]),"+f"(d[20]),"+f"(d[21]),"+f"(d[22]),"+f"(d[23]),"+f"(d[24]),"+f"(d[25]),"+f"(d[26]),"+f"(d[27]),"+f"(d[28]),"+f"(d[29]),"+f"(d[30]),"+f"(d[31])
   : "r"(al),"r"(ao >> 4),"r"(bl),"r"(bo >> 4),"r"(scale_d),"n"(TA),"n"(TB),"n"(AH),"n"(BH));
}
template<int TB,uint32_t BH,int SA=1> __device__ __forceinline__ void wgmma_n64_rs(float (&d)[32], uint32_t a0,uint32_t a1,uint32_t a2,uint32_t a3, uint32_t bl, uint32_t bo, int scale_d){
  asm volatile("{.reg .pred p; .reg .b32 t; .reg .b64 db; setp.ne.b32 p, %38, 0; add.u32 t, %36, %37; mov.b64 db, {t, %40};\n"
   "wgmma.mma_async.sync.aligned.m64n64k16.f32.bf16.bf16 {%0,%1,%2,%3,%4,%5,%6,%7,%8,%9,%10,%11,%12,%13,%14,%15,%16,%17,%18,%19,%20,%21,%22,%23,%24,%25,%26,%27,%28,%29,%30,%31}, {%32,%33,%34,%35}, db, p, %41, 1, %39;}"
   : "+f"(d[0]),"+f"(d[1]),"+f"(d[2]),"+f"(d[3]),"+f"(d[4]),"+f"(d[5]),"+f"(d[6]),"+f"(d[7]),"+f"(d[8]),"+f"(d[9]),"+f"(d[10]),"+f"(d[11]),"+f"(d[12]),"+f"(d[13]),"+f"(d[14]),"+f"(d[15]),"+f"(d[16]),"+f"(d[17]),"+f"(d[18]),"+f"(d[19]),"+f"(d[20]),"+f"(d[21]),"+f"(d[22]),"+f"(d[23]),"+f"(d[24]),"+f"(d[25]),"+f"(d[26]),"+f"(d[27]),"+f"(d[28]),"+f"(d[29]),"+f"(d[30]),"+f"(d[31])
   : "r"(a0),"r"(a1),"r"(a2),"r"(a3),"r"(bl),"r"(bo >> 4),"r"(scale_d),"n"(TB),"n"(BH),"n"(SA));
}
template<int TA,int TB,uint32_t AH,uint32_t BH> __device__ __forceinline__ void wgmma_n96_ss(float (&d)[48], uint32_t al, uint32_t ao, uint32_t bl, uint32_t bo, int scale_d){
  asm volatile("{.reg .pred p; .reg .b32 t, v; .reg .b64 da, db; setp.ne.b32 p, %52, 0; add.u32 t, %48, %49; mov.b64 da, {t, %55}; add.u32 v, %50, %51; mov.b64 db, {v, %56};\n"
   "wgmma.mma_async.sync.aligned.m64n96k16.f32.bf16.bf16 {%0,%1,%2,%3,%4,%5,%6,%7,%8,%9,%10,%11,%12,%13,%14,%15,%16,%17,%18,%19,%20,%21,%22,%23,%24,%25,%26,%27,%28,%29,%30,%31,%32,%33,%34,%35,%36,%37,%38,%39,%40,%41,%42,%43,%44,%45,%46,%47}, da, db, p, 1, 1, %53, %54;}"
   : "+f"(d[0]),"+f"(d[1]),"+f"(d[2]),"+f"(d[3]),"+f"(d[4]),"+f"(d[5]),"+f"(d[6]),"+f"(d[7]),"+f"(d[8]),"+f"(d[9]),"+f"(d[10]),"+f"(d[11]),"+f"(d[12]),"+f"(d[13]),"+f"(d[14]),"+f"(d[15]),"+f"(d[16]),"+f"(d[17]),"+f"(d[18]),"+f"(d[19]),"+f"(d[20]),"+f"(d[21]),"+f"(d[22]),"+f"(d[23]),"+f"(d[24]),"+f"(d[25]),"+f"(d[26]),"+f"(d[27]),"+f"(d[28]),"+f"(d[29]),"+f"(d[30]),"+f"(d[31]),"+f"(d[32]),"+f"(d[33]),"+f"(d[34]),"+f"(d[35]),"+f"(d[36]),"+f"(d[37]),"+f"(d[38]),"+f"(d[39]),"+f"(d[40]),"+f"(d[41]),"+f"(d[42]),"+f"(d[43]),"+f"(d[44]),"+f"(d[45]),"+f"(d[46]),"+f"(d[47])
   : "r"(al),"r"(ao >> 4),"r"(bl),"r"(bo >> 4),"r"(scale_d),"n"(TA),"n"(TB),"n"(AH),"n"(BH));
}
template<int TA,int TB,uint32_t AH,uint32_t BH> __device__ __forceinline__ void wgmma_n128_ss(float (&d)[64], uint32_t al, uint32_t ao, uint32_t bl, uint32_t bo, int scale_d){
  asm volatile("{.reg .pred p; .reg .b32 t, v; .reg .b64 da, db; setp.ne.b32 p, %68, 0; add.u32 t, %64, %65; mov.b64 da, {t, %71}; add.u32 v, %66, %67; mov.b64 db, {v, %72};\n"
   "wgmma.mma_async.sync.aligned.m64n128k16.f32.bf16.bf16 {%0,%1,%2,%3,%4,%5,%6,%7,%8,%9,%10,%11,%12,%13,%14,%15,%16,%17,%18,%19,%20,%21,%22,%23,%24,%25,%26,%27,%28,%29,%30,%31,%32,%33,%34,%35,%36,%37,%38,%39,%40,%41,%42,%43,%44,%45,%46,%47,%48,%49,%50,%51,%52,%53,%54,%55,%56,%57,%58,%59,%60,%61,%62,%63}, da, db, p, 1, 1, %69, %70;}"
   : "+f"(d[0]),"+f"(d[1]),"+f"(d[2]),"+f"(d[3]),"+f"(d[4]),"+f"(d[5]),"+f"(d[6]),"+f"(d[7]),"+f"(d[8]),"+f"(d[9]),"+f"(d[10]),"+f"(d[11]),"+f"(d[12]),"+f"(d[13]),"+f"(d[14]),"+f"(d[15]),"+f"(d[16]),"+f"(d[17]),"+f"(d[18]),"+f"(d[19]),"+f"(d[20]),"+f"(d[21]),"+f"(d[22]),"+f"(d[23]),"+f"(d[24]),"+f"(d[25]),"+f"(d[26]),"+f"(d[27]),"+f"(d[28]),"+f"(d[29]),"+f"(d[30]),"+f"(d[31]),"+f"(d[32]),"+f"(d[33]),"+f"(d[34]),"+f"(d[35]),"+f"(d[36]),"+f"(d[37]),"+f"(d[38]),"+f"(d[39]),"+f"(d[40]),"+f"(d[41]),"+f"(d[42]),"+f"(d[43]),"+f"(d[44]),"+f"(d[45]),"+f"(d[46]),"+f"(d[47]),"+f"(d[48]),"+f"(d[49]),"+f"(d[50]),"+f"(d[51]),"+f"(d[52]),"+f"(d[53]),"+f"(d[54]),"+f"(d[55]),"+f"(d[56]),"+f"(d[57]),"+f"(d[58]),"+f"(d[59]),"+f"(d[60]),"+f"(d[61]),"+f"(d[62]),"+f"(d[63])
   : "r"(al),"r"(ao >> 4),"r"(bl),"r"(bo >> 4),"r"(scale_d),"n"(TA),"n"(TB),"n"(AH),"n"(BH));
}

__global__ void __cluster_dims__(2, 1, 1) __launch_bounds__(384, 1)
fused_kernel(const __nv_bfloat16* __restrict__ lam_re, const __nv_bfloat16* __restrict__ lam_im, const __nv_bfloat16* __restrict__ log_dt,
             const __nv_bfloat16* __restrict__ dskip, const __nv_bfloat16* __restrict__ b1, const __nv_bfloat16* __restrict__ b2,
             const __nv_bfloat16* __restrict__ gate_w, const __nv_bfloat16* __restrict__ pf_w1, const __nv_bfloat16* __restrict__ pf_w2,
             const __nv_bfloat16* __restrict__ pf_cre, const __nv_bfloat16* __restrict__ pf_cim, float* __restrict__ out,
             const __grid_constant__ Maps maps) {
  extern __shared__ __align__(1024) unsigned char smem_raw[];
  const uint32_t sb = (uint32_t)__cvta_generic_to_shared(smem_raw);
  const int b = blockIdx.x;
  const int rank = b & 1, cl = b >> 1;
  const int sp = (cl & 1) | ((cl >> 2) & 2), m = ((cl >> 1) & 3) | ((cl >> 4) << 2);
  const int s = sp * 2 + rank;
  const int warp = __shfl_sync(0xffffffffu, (int)(threadIdx.x >> 5), 0);
  const int lane = threadIdx.x & 31;
  const int xrot = 9 - 2 * sp;

  if (elect_one()) {
    if (warp == 8) TS(2, 0);
    if (warp > 8) {
      asm volatile("prefetch.tensormap [%0];" ::"l"(&maps.x + (warp - 9)) : "memory");
      mbar_init(sb + OFF_GBAR + 8 * (warp - 9), warp < 11 ? 64 : 96);
    }
    const uint32_t c = warp < 8 ? 1 : warp < 11 ? 8 : 4, bar = sb + OFF_XFULL + 16 * warp;
    mbar_init(bar, c);
    if ((warp & 11) == 0) {
      mbar_expect_tx(bar, 16384);
      if (warp == 0) {
        tma5d(sb + OFF_X + (xrot & 7) * 16384, &maps.x, 0, 2 * m, bar);
        tma5d(sb + OFF_X + (xrot & 7) * 16384 + 8192, &maps.x, 0, 2 * m + 1, bar);
        TS(2, 3);
      } else {
        tma2d(sb + OFF_RING, &maps.bre, 0, s * 64, bar);
        tma2d(sb + OFF_RING + 8192, &maps.bim, 0, s * 64, bar);
        TS(2, 4);
      }
    }
    mbar_init(bar + 8, c);
    asm volatile("fence.mbarrier_init.release.cluster;" ::: "memory");
  }
  __syncwarp();
  asm volatile("barrier.cluster.arrive.relaxed.aligned;" ::: "memory");

  if (warp < 8) {
    const int wg = warp >> 2, w = warp & 3, q = lane & 3, gr = lane >> 2;
    uint32_t bv[28];
#pragma unroll
    for (int j = 0; j < 28; j++) bv[j] = __ldg(reinterpret_cast<const uint32_t*>(b1 + s * 224 + j * 8) + q);
    asm volatile("setmaxnreg.inc.sync.aligned.u32 224;");
    asm volatile("barrier.cluster.wait.aligned;" ::: "memory");
    TS(wg, 0);
    auto release = [&](int slot) { if (lane == 0) mbar_arrive(sb + OFF_EMPTY + 8 * slot); };
    const uint32_t xw = sb + OFF_X + wg * 8192, fullb = sb + OFF_FULL;
    const uint32_t dxw = (xw & 0x3FFFF) >> 4, dring = ((sb + OFF_RING) & 0x3FFFF) >> 4;

    float ure[32], uim[32], aa[48], ab[64];
    cplx lam[2], coef[2], l16[2], l32[2], lq[2], pre[2], e[2];
    uint32_t sh16, mhi, ck = 0;

    auto bias = [&](int c) {
#pragma unroll
      for (int j = c * 7; j < c * 7 + 7; j++) {
        pin(bv[j]);
        float* d = j < 12 ? aa + 4 * j : ab + 4 * (j - 12);
        d[0] = d[2] = __uint_as_float(bv[j] << sh16); d[1] = d[3] = __uint_as_float(bv[j] & mhi);
        pin(d[0]); pin(d[1]); pin(d[2]); pin(d[3]);
      }
    };
#pragma unroll
    for (int kb = 0; kb < 8; kb++) {
      const int slot = kb % NSLOT;
      mbar_wait(sb + OFF_XFULL + 8 * kb, 0);
      if (kb == 0) TS(wg, 18);
      mbar_wait(fullb + 8 * slot, (kb / NSLOT) & 1);
      TS2(2, kb);
      if (kb == 0) TS(wg, 1);
      if (kb == SB0) { sh16 = late16(sb + OFF_XFULL); mhi = 0xffffffffu << sh16; }
      if (kb == LCK) {
        mbar_wait(sb + OFF_LBAR, 0);
#pragma unroll
        for (int h = 0; h < 2; h++) {
          const uint4 v = lds_u4(sb + OFF_LC + (w * 16 + gr + 8 * h) * 16);
          lam[h] = cplx{__uint_as_float(v.x), __uint_as_float(v.y)};
          coef[h] = cplx{__uint_as_float(v.z), __uint_as_float(v.w)};
        }
      }
      wg_fence();
      const uint32_t dxa = dxw + ((kb + xrot) & 7) * 1024;
#pragma unroll
      for (int kk = 0; kk < 4; kk++) {
        wgmma_n64_ss<0, 0, DH128, DH128>(ure, dring, slot * 16384 + kk * 32, dxa, kk * 32, (kb | kk) != 0);
        wgmma_n64_ss<0, 0, DH128, DH128>(uim, dring, slot * 16384 + 8192 + kk * 32, dxa, kk * 32, (kb | kk) != 0);
      }
      wg_commit();
      if (kb > 0) { wg_wait<1>(); release((kb - 1) % NSLOT); }
      if (kb >= SB0 && kb < SB0 + 3) bias(kb - SB0);
      if (kb == 6) {
#pragma unroll
        for (int h = 0; h < 2; h++) {
          pin(lam[h].re); pin(lam[h].im);
          cplx t = cmul(lam[h], lam[h]); t = cmul(t, t); t = cmul(t, t);
          l16[h] = cmul(t, t);
          pin(l16[h].re); pin(l16[h].im);
        }
      }
      if (kb == 7) {
#pragma unroll
        for (int h = 0; h < 2; h++) {
          pin(l16[h].re); pin(l16[h].im);
          l32[h] = cmul(l16[h], l16[h]);
          const cplx a = (q & 1) ? l16[h] : cplx{1.f, 0.f}, c = (q & 2) ? l32[h] : cplx{1.f, 0.f};
          lq[h] = cmul(cmul(a, c), coef[h]);
          if (q < 2) l16[h] = cplx{0.f, 0.f};
          if (q < 3) l32[h] = cplx{0.f, 0.f};
          pin(lq[h].re); pin(lq[h].im); pin(l16[h].re); pin(l16[h].im); pin(l32[h].re); pin(l32[h].im);
        }
      }
    }
    TS(wg, 2);
    auto scale_u = [&](int i0, int i1) {
#pragma unroll
      for (int i = 0; i < 32; i++) if (i >= i0 && i < i1) {
        pin(ure[i]); pin(uim[i]);
        const cplx v = cmul(coef[(i >> 1) & 1], cplx{ure[i], uim[i]});
        ure[i] = v.re; uim[i] = v.im;
        pin(ure[i]); pin(uim[i]);
      }
    };
#pragma unroll
    for (int kb = 0; kb < 8; kb++) {
      const int u = 8 + kb, slot = u % NSLOT;
      mbar_wait(fullb + 8 * slot, (u / NSLOT) & 1);
      TK(kb);
      wg_fence();
      const uint32_t dxa = dxw + ((kb + xrot) & 7) * 1024;
#pragma unroll
      for (int kk = 0; kk < 4; kk++)
        wgmma_n96_ss<0, 1, DH128, DH64>(aa, dxa, kk * 32, dring, slot * 16384 + kk * 1024 + lbo(4096), 1);
      wg_commit();
      if (kb == 0) bias(3);
      if (kb != QK) { wg_wait<1>(); release((u - 1) % NSLOT); }
      if (kb == 0) {
        reg_fence(ure); reg_fence(uim);
#pragma unroll
        for (int h = 0; h < 2; h++) e[h] = cplx{ure[2 * h], uim[2 * h]};
      }
      if (kb == 0 || (kb >= 2 && kb <= QK && kb < 4)) {
        constexpr int tc[5] = TCUT;
#pragma unroll
        for (int t = 1; t < 16; t++) if (t >= tc[kb] && t < tc[kb + 1]) {
#pragma unroll
          for (int h = 0; h < 2; h++) { const int i = 4 * (t >> 1) + 2 * h + (t & 1); e[h] = cfma(lam[h], e[h], cplx{ure[i], uim[i]}); }
        }
#pragma unroll
        for (int h = 0; h < 2; h++) { pin(e[h].re); pin(e[h].im); }
      }
      if (kb == QK) {
        if (QF) sched_fence(ck);
#pragma unroll
        for (int h = 0; h < 2; h++) {
          cplx y[3];
#pragma unroll
          for (int d = 0; d < 3; d++) y[d] = cplx{__shfl_up_sync(0xffffffffu, e[h].re, d + 1, 4), __shfl_up_sync(0xffffffffu, e[h].im, d + 1, 4)};
          pre[h] = cfma(l32[h], y[2], cfma(l16[h], y[1], q ? y[0] : cplx{0.f, 0.f}));
          e[h] = cfma(l16[h], pre[h], e[h]);
        }
        if (q == 3) {
#pragma unroll
          for (int h = 0; h < 2; h++)
            asm volatile("st.shared.v2.f32 [%0], {%1,%2};" ::"r"(sb + OFF_CARRY + wg * 512 + (w * 16 + gr + 8 * h) * 8), "f"(e[h].re), "f"(e[h].im) : "memory");
          mbar_arrive(sb + OFF_GBAR);
        }
        wg_wait<1>(); release((u - 1) % NSLOT);
        if (TKT > 500) TS(wg, 3);
      }
      if (kb == QK + 1) {
#pragma unroll
        for (int h = 0; h < 2; h++) {
          pre[h] = cmul(coef[h], pre[h]);
          pin(pre[h].re); pin(pre[h].im);
        }
      }
      if (kb > QK) { constexpr int sc[9] = SCUT; scale_u(sc[kb], sc[kb + 1]); }
    }
    TS(wg, 4);
    uint32_t H[56], hf[32];
    cplx hst[2];
    const uint32_t hst_addr = xw + (w * 16 + (lane & 15)) * 128 + (((lane >> 4) ^ (lane & 7)) << 4);
    const uint32_t him = (2 - rank) * 16384;
    uint32_t peer;
    asm volatile("mapa.shared::cluster.u32 %0, %1, %2;" : "=r"(peer) : "r"(sb), "r"(rank ^ 1));
    auto credit = [&]() { if (lane == 0) mbar_arrive_cl(peer + OFF_KBAR + wg * 8); };
    uint32_t g2[8];
#pragma unroll
    for (int kb = 0; kb < 8; kb++) {
      const int u = 16 + kb, slot = u % NSLOT;
      mbar_wait(fullb + 8 * slot, (u / NSLOT) & 1);
      TK(kb < 7 ? 24 + kb : 32);
      wg_fence();
#pragma unroll
      for (int kk = 0; kk < 4; kk++)
        wgmma_n128_ss<0, 1, DH128, DH128>(ab, dxw, kb * 16384 + kk * 32, dring, slot * 16384 + kk * 2048 + lbo(8192), 1);
      wg_commit();
      if (kb == 0) { constexpr int sc[9] = SCUT; scale_u(sc[8], 32); }
      if (kb == 4) {
        if (TKT > 500) TS(wg, 5);
        mbar_wait(sb + OFF_CBAR, 0);
        if (TKT > 500) TS(wg, 6);
#pragma unroll
        for (int h = 0; h < 2; h++) {
          const float2 c = lds_f2(sb + OFF_CARRY + wg * 512 + (w * 16 + gr + 8 * h) * 8);
          hst[h] = cfma(lq[h], cplx{c.x, c.y}, pre[h]);
        }
#pragma unroll
        for (int i = 0; i < 2; i++) {
          const uint4 v = lds_u4(sb + OFF_GT + wg * 128 + q * 32 + i * 16);
          g2[4 * i] = v.x; g2[4 * i + 1] = v.y; g2[4 * i + 2] = v.z; g2[4 * i + 3] = v.w;
        }
      }
      if (kb == 0 || TOKB != 1) { wg_wait<1>(); release((u - 1) % NSLOT); }
      if (kb) sched_fence(ck);
      if (kb < 4) {
#pragma unroll
        for (int i = kb * 6; i < kb * 6 + 6; i++) {
          pin(aa[2 * i]); pin(aa[2 * i + 1]);
          H[i] = gelu2_pair(aa[2 * i], aa[2 * i + 1]);
          pin(H[i]);
        }
      } else {
        const int j0 = (kb - 4) * 2;
        uint32_t rr[4], ri[4];
#pragma unroll
        for (int jj = 0; jj < 2; jj++) {
          const int j = j0 + jj;
#pragma unroll
          for (int h = 0; h < 2; h++) {
            const int i = 4 * j + 2 * h;
            const cplx h0 = cfma(lam[h], hst[h], cplx{ure[i], uim[i]});
            hst[h] = cfma(lam[h], h0, cplx{ure[i + 1], uim[i + 1]});
            rr[jj * 2 + h] = bf2_mul(pack_bf16(h0.re, hst[h].re), g2[j]);
            ri[jj * 2 + h] = bf2_mul(pack_bf16(h0.im, hst[h].im), g2[j]);
          }
        }
        const uint32_t a = hst_addr ^ (j0 << 4);
        asm volatile("stmatrix.sync.aligned.m8n8.x4.shared.b16 [%0], {%1,%2,%3,%4};" ::"r"(a), "r"(rr[0]), "r"(rr[1]), "r"(rr[2]), "r"(rr[3]) : "memory");
        asm volatile("stmatrix.sync.aligned.m8n8.x4.shared.b16 [%0], {%1,%2,%3,%4};" ::"r"(a + him), "r"(ri[0]), "r"(ri[1]), "r"(ri[2]), "r"(ri[3]) : "memory");
      }
      if (kb && TOKB == 1) { wg_wait<1>(); release((u - 1) % NSLOT); }
    }
    TS(wg, 7);

    uint4* const psend = g_part + (size_t)(m * 8 + rank) * 3072 + warp * 128 + lane;
    const uint4* const precv = g_part + (size_t)(m * 8 + s) * 3072 + warp * 128 + lane;
    const uint32_t pbuf = OFF_X + warp * 2048 + lane * 16;
    const uint32_t dx0 = ((sb + OFF_X) & 0x3FFFF) >> 4;
    float o[32], fin[32], rho[2];
    uint32_t tr[8];
    uint32_t r0[16], pt[16], sum[16], tag;
    auto recv_issue = [&](uint32_t (&r)[16], int k) {
#pragma unroll
      for (int i = 0; i < 4; i++) ld_b128(precv + k * 1024 + i * 32, r[4 * i], r[4 * i + 1], r[4 * i + 2], r[4 * i + 3]);
    };
    auto stale = [&](uint32_t (&r)[16]) {
      uint32_t t0, t1, r_;
      asm("lop3.b32 %0, %1, %2, %3, 0x7e;" : "=r"(t0) : "r"(r[0]), "r"(r[4]), "r"(tag));
      asm("lop3.b32 %0, %1, %2, %3, 0x7e;" : "=r"(t1) : "r"(r[8]), "r"(r[12]), "r"(tag));
      asm volatile("{.reg .pred p; .reg .b32 t; lop3.b32 t, %1, %2, 1, 0xa8; setp.ne.u32 p, t, 0; vote.sync.any.pred p, p, 0xffffffff; selp.u32 %0, 1, 0, p;}" : "=r"(r_) : "r"(t0), "r"(t1));
      return r_ != 0;
    };
    auto recv_check = [&](uint32_t (&r)[16], int k) {
      if (__builtin_expect(stale(r), 0)) {
        int tries = 0;
#pragma unroll 1
        do { recv_issue(r, k); } while (stale(r) && ++tries < 200000);
      }
    };
    auto gelu_b = [&](int i0, int i1) {
      if (TOKD && i0) sched_fence(ck);
#pragma unroll
      for (int i = i0; i < i1; i++) {
        pin(ab[2 * i]); pin(ab[2 * i + 1]);
        H[24 + i] = gelu2_pair(ab[2 * i], ab[2 * i + 1]);
        pin(H[24 + i]);
      }
      if (TOKD == 2) sched_fence(ck);
    };
    auto step = [&](float (&d)[32], int p, int k, int acc) {
      const uint32_t wo = stage_off(p);
      if (k >= 6 && k < 14) {
        const int kk = k - 6;
        if (kk < 4) wgmma_n64_rs<0, DH128, 1>(d, hf[4 * kk], hf[4 * kk + 1], hf[4 * kk + 2], hf[4 * kk + 3], dx0, wo + 14336 + kk * 32, 1);
        else wgmma_n64_rs<0, DH128, -1>(d, hf[4 * kk], hf[4 * kk + 1], hf[4 * kk + 2], hf[4 * kk + 3], dx0, wo + 22528 + (kk - 4) * 32, 1);
      } else {
        const int kk = k < 6 ? k : k - 8;
        wgmma_n64_rs<1, DH128>(d, H[4 * kk], H[4 * kk + 1], H[4 * kk + 2], H[4 * kk + 3], dx0, wo + (kk / 7) * 30720 + (kk % 7) * 2048, k != 0 || acc);
      }
    };
    auto mma = [&](float (&d)[32], int p, int k0, int k1, int acc) {
      wg_fence();
#pragma unroll
      for (int k = k0; k < k1; k++) step(d, p, k, acc);
      wg_commit();
    };
    auto send_peer = [&]() {
#pragma unroll
      for (int i = 0; i < 4; i++)
        asm volatile("st.async.shared::cluster.mbarrier::complete_tx::bytes.v4.b32 [%0], {%1,%2,%3,%4}, [%5];" ::"r"(peer + pbuf + i * 512),
                     "r"(pack_bf16(o[8 * i], o[8 * i + 1])), "r"(pack_bf16(o[8 * i + 2], o[8 * i + 3])), "r"(pack_bf16(o[8 * i + 4], o[8 * i + 5])),
                     "r"(pack_bf16(o[8 * i + 6], o[8 * i + 7])), "r"(peer + OFF_RBAR + wg * 8) : "memory");
    };
    auto recv_peer = [&](int k) {
      mbar_wait(sb + OFF_RBAR + wg * 8, k & 1);
#pragma unroll
      for (int i = 0; i < 4; i++) { const uint4 v = lds_u4(sb + pbuf + i * 512); pt[4 * i] = v.x; pt[4 * i + 1] = v.y; pt[4 * i + 2] = v.z; pt[4 * i + 3] = v.w; }
    };
    auto send_owner = [&](float (&d)[32], int k) {
#pragma unroll
      for (int i = 0; i < 4; i++) {
#pragma unroll
        for (int c = 4 * i; c < 4 * i + 4; c++) pt[c] = bf2_add(pt[c], pack_bf16(d[2 * c], d[2 * c + 1]));
        asm("lop3.b32 %0, %0, 1, %1, 0xb8;" : "+r"(pt[4 * i]) : "r"(tag));
        st_b128(psend + (((sp + 1 + k) & 3) * 6 + k) * 1024 + i * 32, pt[4 * i], pt[4 * i + 1], pt[4 * i + 2], pt[4 * i + 3]);
      }
      __syncwarp();
      credit();
    };
    auto load_fin = [&]() {
      mbar_wait(sb + OFF_LBAR, 1);
#pragma unroll
      for (int j = 0; j < 8; j++) {
        const uint4 v = lds_u4(sb + pbuf + 16384 + (j >> 2) * 16384 + (j & 3) * 512);
        fin[4 * j] = __uint_as_float(v.x); fin[4 * j + 1] = __uint_as_float(v.y); fin[4 * j + 2] = __uint_as_float(v.z); fin[4 * j + 3] = __uint_as_float(v.w);
      }
    };
    auto ldk = [&](int pos) { if (pos == K0P) recv_issue(sum, 0); if (pos == K1P) recv_issue(r0, 1); };
    auto arm = [&]() { if ((threadIdx.x & 127) == 0) mbar_expect_tx(sb + OFF_RBAR + wg * 8, 8192); };
#pragma unroll
    for (int p = 0; p < 8; p++) {
      if (p == 0) {
        TK(40);
        mbar_wait(fullb, 0);
        TK(41);
        mma(o, 0, 0, 3, 0);
        wg_wait<1>(); release(5);
        gelu_b(0, 4);
        mma(o, 0, 3, 6, 0);
        bar_sync(1 + wg, 128);
        {
          const uint32_t ha = xw + ((lane >> 4) * 8 + (lane & 7)) * 128 + (((2 * w + ((lane >> 3) & 1)) ^ (lane & 7)) << 4);
#pragma unroll
          for (int kk = 0; kk < 8; kk++)
            asm volatile("ldmatrix.sync.aligned.m8n8.x4.trans.shared.b16 {%0,%1,%2,%3}, [%4];" : "=r"(hf[4 * kk]), "=r"(hf[4 * kk + 1]), "=r"(hf[4 * kk + 2]), "=r"(hf[4 * kk + 3])
                         : "r"(ha + (kk >> 2) * him + (kk & 3) * 2048) : "memory");
        }
        gelu_b(4, 10);
        TK(42);
        mbar_wait(fullb + 8, 0);
        TK(43);
        mma(o, 0, 6, 10, 0);
        credit();
        gelu_b(10, 16);
        mma(o, 0, 10, 15, 0);
        gelu_b(16, 24);
        TK(44);
        mbar_wait(fullb + 16, 0);
        TK(45);
        mma(o, 0, 15, 18, 0);
        gelu_b(24, 32);
        if (wg == 1) bar_sync(4, 256);
        mma(o, 0, 18, 22, 0);
      } else {
        TR(0);
        if (EW == 0 || (EW == 1 && (p & 1))) mbar_wait(sb + OFF_XFULL + 8 * p, 1);
        TR(1);
        bar_sync(3 + wg, 256);
        if (p < 7) mma(o, p, 0, 22, 0);
        else if (GAP == 0) mma(fin, p, 0, 22, 1);
        else {
          mma(fin, p, 0, GAP, 1);
          recv_peer(3);
          tag = lds_u(sb + OFF_EPOCH);
          mma(fin, p, GAP, 22, 1);
        }
      }
      if (p < 7 || wg == 0) bar_arrive(4 - wg, 256);
      TR(2);
      if (p != TP) TS(wg, 8 + p);
      if (p < 7 && (EW == 2 || (EW == 1 && (p & 1)))) mbar_wait(sb + OFF_XFULL + 8 * (p + 1), 1);
      ldk(10 * p);
      if (p == 2) asm volatile("st.shared.u32 [%0], %1;" ::"r"(sb + OFF_EPOCH + 4), "r"(ck) : "memory");
      if ((p & 1) == 0) {
        arm();
        if (p == 6) {
          mbar_wait(sb + OFF_EMPTY + 32, 0);
          tag = lds_u(sb + OFF_EPOCH);
          recv_check(sum, 0); recv_check(r0, 1);
#pragma unroll
          for (int i = 0; i < 16; i++) sum[i] = bf2_add(sum[i], r0[i]);
        }
        TR(3);
        mbar_wait(sb + OFF_KBAR + wg * 8, (p >> 1) & 1);
        TR(4);
      } else {
        if (p == 1 || (p == 7 && GAP == 0)) tag = lds_u(sb + OFF_EPOCH);
        TR(3);
        if (p < 7 || GAP == 0) recv_peer(p >> 1);
        TR(4);
        if (p == 7) {
          recv_check(r0, 2);
#pragma unroll
          for (int i = 0; i < 16; i++) sum[i] = bf2_add(sum[i], bf2_add(r0[i], pt[i]));
        }
      }
      if (p == FINP && !FINW) load_fin();
      ldk(10 * p + 1);
      TR(5);
      wg_wait<0>();
      TR(6);
      if (p < 5) release(p);
      if (p < 7) reg_fence(o); else reg_fence(fin);
      ldk(10 * p + 2);
      if ((p & 1) == 0) {
        if (p == 6) recv_issue(r0, 2);
        send_peer();
        if (p == FINP && FINW) load_fin();
      } else if (p < 7) {
        send_owner(o, p >> 1);
      }
      ldk(10 * p + 3);
      if (p == 2) {
#pragma unroll
        for (int h = 0; h < 2; h++) { rho[h] = __fdividef(2.f, 4.f + bf_lo(lds_h(sb + OFF_GS + (wg * 64 + w * 16 + gr + 8 * h) * 2))); pin(rho[h]); }
      }
      TR(7);
    }
    {
      TS(wg, 16);
      const uint32_t tb = sb + OFF_X + stage_off(0) + warp * 4096;
      const uint32_t ta = tb + gr * 256 + ((gr & 3) << 5) + q * 8;
      const uint32_t la = tb + (lane >> 3) * 256 + (((lane & 7) << 4) ^ ((lane >> 3) << 5));
      float* op = out + (size_t)(m * 128 + wg * 64 + (lane >> 4) * 16 + w * 4 + ((lane >> 3) & 1)) * DM + s * 64 + (lane & 7) * 4;
#pragma unroll
      for (int qq = 0; qq < 4; qq += QS) {
#pragma unroll
        for (int qt = qq; qt < qq + QS; qt++) {
          const int h = qt & 1, ch = qt >> 1;
#pragma unroll
          for (int j = 0; j < 4; j++) {
            const int i = ch * 8 + j * 2 + h;
            asm volatile("st.shared.v2.f32 [%0], {%1,%2};" ::"r"((ta ^ (j << 5)) + h * 2048 + ch * 128),
                         "f"((fin[2 * i] + bf_lo(sum[i])) * rho[h]), "f"((fin[2 * i + 1] + bf_hi(sum[i])) * rho[h]) : "memory");
          }
        }
        __syncwarp();
#pragma unroll
        for (int qt = qq; qt < qq + QS; qt++) {
          const int h = qt & 1, ch = qt >> 1;
#pragma unroll
          for (int r = 0; r < 2; r++)
            *reinterpret_cast<uint4*>(op + (r * 32 + h * 2) * DM + ch * 32) = lds_u4(la + (h * 2 + r) * 1024 + ch * 128);
        }
      }
      if (threadIdx.x == 128) g_epoch[b] = tag;
      TS(wg, 17); TG(wg); TRD(); TDUMP();
    }
  } else {
    asm volatile("setmaxnreg.dec.sync.aligned.u32 56;");
    int wsel = warp;
    asm("" : "+r"(wsel));
    if (wsel > 8) {
      if (warp != 11) {
        const int t = threadIdx.x - 288;
        unsigned par;
        asm volatile("ld.relaxed.gpu.global.u32 %0, [%1];" : "=r"(par) : "l"(g_epoch + b) : "memory");
        const float pr = bf_ld(lam_re + s * 64 + t), pi = bf_ld(lam_im + s * 64 + t), pd = bf_ld(log_dt + s * 64 + t);
        asm volatile("barrier.cluster.wait.aligned;" ::: "memory");
        par = __shfl_sync(0xffffffffu, (par + 1) & 1, 0);
        cplx l64 = make_lam(pr, pi, pd);
        {
          const float inv = __fdividef(1.f, fmaf(pr, pr, pi * pi));
          const cplx cf = cmul(cplx{l64.re - 1.f, l64.im}, cplx{pr * inv, -pi * inv});
          asm volatile("st.shared.v4.f32 [%0], {%1,%2,%3,%4};" ::"r"(sb + OFF_LC + t * 16), "f"(l64.re), "f"(l64.im), "f"(cf.re), "f"(cf.im) : "memory");
          mbar_arrive(sb + OFF_LBAR);
        }
#pragma unroll
        for (int i = 0; i < 6; i++) l64 = cmul(l64, l64);
        cplx l128 = cmul(l64, l64);
        pin(l128.re); pin(l128.im);
        uint32_t vr[15], vi[15];
#pragma unroll
        for (int i = 0; i < 15; i++) { vr[i] = par; vi[i] = 0; pin(vr[i]); pin(vi[i]); }
        mbar_wait(sb + OFF_GBAR, 0);
        const float2 e0 = lds_f2(sb + OFF_CARRY + t * 8), e1 = lds_f2(sb + OFF_CARRY + 512 + t * 8);
        float2* eb = g_end + s * 1024 + t;
        {
          const cplx e = cfma(l64, cplx{e0.x, e0.y}, cplx{e1.x, e1.y});
          const unsigned long long v = ((unsigned long long)__float_as_uint(e.im) << 32) | ((__float_as_uint(e.re) & ~1u) | par);
          asm volatile("st.relaxed.gpu.global.b64 [%0], %1;" ::"l"(eb + m * 64), "l"(v) : "memory");
        }
        if (t == 0) TS(3, 1);
        cplx S = {0.f, 0.f};
        {
          if (LBD) __nanosleep(LBD);
          const float2* e15 = eb + (m - 15) * 64;
          int tries = 0;
          bool bad;
#pragma unroll 1
          do {
#pragma unroll
            for (int i = 0; i < 15; i++)
              asm volatile("{.reg .pred p; .reg .b64 v; mov.b64 v, {%0,%1}; setp.ge.s32 p, %3, %4; @p ld.relaxed.gpu.global.b64 v, [%2]; mov.b64 {%0,%1}, v;}"
                           : "+r"(vr[i]), "+r"(vi[i]) : "l"(e15 + i * 64), "r"(m), "r"(15 - i) : "memory");
            uint32_t x = vr[0] ^ par;
#pragma unroll
            for (int i = 1; i < 15; i++) asm("lop3.b32 %0, %0, %1, %2, 0xf6;" : "+r"(x) : "r"(vr[i]), "r"(par));
            bad = __any_sync(0xffffffffu, x & 1);
          } while (bad && ++tries < 200000);
          if (t == 0) TS(3, 2);
          S = cplx{__uint_as_float(vr[0]), __uint_as_float(vi[0])};
#pragma unroll
          for (int i = 1; i < 15; i++) S = cfma(l128, S, cplx{__uint_as_float(vr[i]), __uint_as_float(vi[i])});
        }
        const cplx S1 = cfma(l64, S, cplx{e0.x, e0.y});
        asm volatile("st.shared.v2.f32 [%0], {%1,%2};" ::"r"(sb + OFF_CARRY + t * 8), "f"(S.re), "f"(S.im) : "memory");
        asm volatile("st.shared.v2.f32 [%0], {%1,%2};" ::"r"(sb + OFF_CARRY + 512 + t * 8), "f"(S1.re), "f"(S1.im) : "memory");
        mbar_arrive(sb + OFF_CBAR);
        if (t == 0) TS(3, 3);
        mbar_wait(sb + OFF_CBAR, 0);
        const int gr = lane >> 2, q = lane & 3;
        float2 db[8];
#pragma unroll
        for (int j = 0; j < 8; j++) db[j] = lds_f2(sb + OFF_DB + j * 32 + q * 8);
        mbar_wait(sb + OFF_XFULL + 16, 1);
        mbar_wait(sb + OFF_EMPTY, 0);
#pragma unroll 1
        for (int cw = warp - 9; cw < 8; cw += 2) {
          const float r0 = 0.5f * bf_lo(lds_h(sb + OFF_GS + (cw * 16 + gr) * 2)), r1 = 0.5f * bf_lo(lds_h(sb + OFF_GS + (cw * 16 + gr) * 2 + 16));
          const uint32_t xa = sb + OFF_X + (1 + rank) * 16384 + (cw * 16 + (lane & 15)) * 128 + (((lane >> 4) ^ (lane & 7)) << 4);
          uint32_t xv[16];
#pragma unroll
          for (int i = 0; i < 4; i++)
            asm volatile("ldmatrix.sync.aligned.m8n8.x4.shared.b16 {%0,%1,%2,%3}, [%4];" : "=r"(xv[4 * i]), "=r"(xv[4 * i + 1]), "=r"(xv[4 * i + 2]), "=r"(xv[4 * i + 3])
                         : "r"(xa ^ (i << 5)) : "memory");
          __syncwarp();
#pragma unroll
          for (int j = 0; j < 8; j++) {
            const uint32_t x0 = bf2_mul(xv[2 * j], __float_as_uint(db[j].x)), x1 = bf2_mul(xv[2 * j + 1], __float_as_uint(db[j].x));
            pin(db[j].y);
            const float bl = bf_lo(__float_as_uint(db[j].y)), bh = bf_hi(__float_as_uint(db[j].y));
            asm volatile("st.shared.v4.f32 [%0], {%1,%2,%3,%4};" ::"r"(sb + OFF_X + 16384 + (j >> 2) * 16384 + cw * 2048 + (j & 3) * 512 + lane * 16), "f"(fmaf(bf_lo(x0), r0, bl)),
                         "f"(fmaf(bf_hi(x0), r0, bh)), "f"(fmaf(bf_lo(x1), r1, bl)), "f"(fmaf(bf_hi(x1), r1, bh)) : "memory");
          }
        }
        mbar_arrive(sb + OFF_LBAR);
        if (t == 0) TS(3, 5);
      } else {
        if (lane == 0) TG(2);
        const uint4* gwp = reinterpret_cast<const uint4*>(gate_w) + (lane & 7);
        uint4 gw[4];
#pragma unroll
        for (int i = 0; i < 4; i++) gw[i] = __ldg(gwp + i * 8);
        unsigned par;
        asm volatile("ld.relaxed.gpu.global.u32 %0, [%1];" : "=r"(par) : "l"(g_epoch + b) : "memory");
        const uint32_t dk = __ldg(reinterpret_cast<const uint32_t*>(dskip + s * 64) + lane), bb = __ldg(reinterpret_cast<const uint32_t*>(b2 + s * 64) + lane);
        asm volatile("barrier.cluster.wait.aligned;" ::: "memory");
        const int row = s * 16 + (lane >> 3);
        const uint32_t xr0 = sb + OFF_X + row * 128 + (((lane & 7) ^ (row & 7)) << 4), xr1 = (xr0 + 512) ^ 64;
        float z[4] = {0.f, 0.f, 0.f, 0.f};
#pragma unroll
        for (int kb = 0; kb < 8; kb++) {
          const uint32_t wv[4] = {gw[kb & 3].x, gw[kb & 3].y, gw[kb & 3].z, gw[kb & 3].w};
          if (kb < 4) gw[kb] = __ldg(gwp + (kb + 4) * 8);
          mbar_wait(sb + OFF_XFULL + 8 * kb, 0);
          if ((PF & 2) && kb == PFK && elect_one()) {
            l2_prefetch(pf_w1 + b * 7168, 14336);
            l2_prefetch(pf_cre + b * 2048, 4096);
            l2_prefetch(pf_cim + b * 2048, 4096);
            l2_prefetch(pf_w2 + b * 7168, 14336);
          }
          const uint32_t xo = ((kb + xrot) & 7) * 16384;
#pragma unroll
          for (int r = 0; r < 4; r++) {
            const uint4 a = lds_u4(((r & 1) ? xr1 : xr0) + xo + (r >> 1) * 1024);
            const uint32_t p = bf2_fma(a.w, wv[3], bf2_fma(a.z, wv[2], bf2_fma(a.y, wv[1], bf2_mul(a.x, wv[0]))));
            z[r] += bf_lo(p); z[r] += bf_hi(p);
          }
        }
        if (lane == 0) asm volatile("st.shared.u32 [%0], %1;" ::"r"(sb + OFF_EPOCH), "r"(par + 1) : "memory");
        par = (par + 1) & 1;
        {
          float y0 = (lane & 4) ? z[1] : z[0], y1 = (lane & 4) ? z[3] : z[2];
          y0 += __shfl_xor_sync(0xffffffffu, (lane & 4) ? z[0] : z[1], 4);
          y1 += __shfl_xor_sync(0xffffffffu, (lane & 4) ? z[2] : z[3], 4);
          float zz = (lane & 2) ? y1 : y0;
          zz += __shfl_xor_sync(0xffffffffu, (lane & 2) ? y0 : y1, 2);
          zz += __shfl_xor_sync(0xffffffffu, zz, 1);
          const float rho = 4.f * expf(zz > 40.f ? 40.f : zz);
          if ((lane & 1) == 0)
            asm volatile("st.relaxed.gpu.global.u32 [%0], %1;" ::"l"(g_gate + m * 128 + row + (lane & 4) + (lane & 2) * 4), "r"((__float_as_uint(rho) & ~1u) | par) : "memory");
        }
        if ((PF & 8) && elect_one()) {
          l2_prefetch(pf_w2 + b * 7168, 14336);
          l2_prefetch(pf_cre + b * 2048, 4096);
          l2_prefetch(pf_cim + b * 2048, 4096);
        }
        if (lane == 0) TS(3, 0);
        mbar_wait(sb + OFF_GBAR, 0);
        asm volatile("st.shared.v2.u32 [%0], {%1,%2};" ::"r"(sb + OFF_DB + lane * 8), "r"(dk), "r"(bf2_add(bb, bb)) : "memory");
        uint32_t g0, g1, g2, g3;
        int tries = 0;
#pragma unroll 1
        do {
          asm volatile("ld.relaxed.gpu.global.v4.u32 {%0,%1,%2,%3}, [%4];" : "=r"(g0), "=r"(g1), "=r"(g2), "=r"(g3) : "l"(g_gate + m * 128 + lane * 4) : "memory");
        } while ((((g0 ^ par) | (g1 ^ par) | (g2 ^ par) | (g3 ^ par)) & 1) && ++tries < 200000);
        asm volatile("st.shared.v2.u32 [%0], {%1,%2};" ::"r"(sb + OFF_GS + lane * 8), "r"(pack_bf16(__uint_as_float(g0), __uint_as_float(g1))),
                     "r"(pack_bf16(__uint_as_float(g2), __uint_as_float(g3))) : "memory");
        const uint32_t gt = sb + OFF_GT + (lane >> 4) * 128 + (lane & 1) * 64 + ((lane >> 1) & 7) * 4;
        asm volatile("st.shared.u32 [%0], %1;" ::"r"(gt), "r"(pack_bf16(__uint_as_float(g0), __uint_as_float(g1))) : "memory");
        asm volatile("st.shared.u32 [%0], %1;" ::"r"(gt + 32), "r"(pack_bf16(__uint_as_float(g2), __uint_as_float(g3))) : "memory");
        mbar_arrive(sb + OFF_CBAR);
        if (lane == 0) TS(3, 4);
      }
    } else {
      asm volatile("barrier.cluster.wait.aligned;" ::: "memory");
      if (elect_one()) {
        TS(2, 1);
        const uint32_t t0 = clock();
#pragma unroll 1
        for (int u = W0; u < 8; u++) {
          if (u >= 1) while ((uint32_t)clock() - t0 < D0 + (u - 1) * D1) {}
          mbar_expect_tx(sb + OFF_XFULL + 8 * u, 16384);
          tma5d_mc(sb + OFF_X + ((u + xrot) & 7) * 16384 + rank * 8192, &maps.x, u * 64, 2 * m + rank, sb + OFF_XFULL + 8 * u);
          const int sl = u < 6 ? u : u - 6;
          if (u >= 6) mbar_wait(sb + OFF_EMPTY + 8 * sl, 0);
          mbar_expect_tx(sb + OFF_FULL + 8 * sl, 16384);
          tma2d(sb + OFF_RING + sl * 16384, &maps.bre, u * 64, s * 64, sb + OFF_FULL + 8 * sl);
          tma2d(sb + OFF_RING + sl * 16384 + 8192, &maps.bim, u * 64, s * 64, sb + OFF_FULL + 8 * sl);
          if (u == 2) asm volatile("prefetch.tensormap [%0];" ::"l"(&maps.w1b) : "memory");
        }
        TS(2, 5);
        int slot = 2; uint32_t ph = 0;
#pragma unroll 1
        for (int u = 8; u < 24; u++) {
          const uint32_t fb = sb + OFF_FULL + 8 * slot, dst = sb + OFF_RING + slot * 16384;
          mbar_wait(sb + OFF_EMPTY + 8 * slot, ph);
          TS2(0, u);
          if (u < 16) {
            mbar_expect_tx(fb, 12288);
            tma3d(dst, &maps.w1b, 0, (u - 8) * 64, s * 7, fb);
            if (TMP2 && u < 12) asm volatile("prefetch.tensormap [%0];" ::"l"(&maps.w1a + (u - 8)) : "memory");
          } else {
            mbar_expect_tx(fb, 16384);
            tma2d(dst, &maps.w1a, s * 224 + 96, ((u - xrot) & 7) * 64, fb);
            tma2d(dst + 8192, &maps.w1a, s * 224 + 160, ((u - xrot) & 7) * 64, fb);
          }
          if (++slot == NSLOT) { slot = 0; ph ^= 1; }
        }
#pragma unroll 1
        for (int j = 0; j < 3; j++) {
          const uint32_t fb = sb + OFF_FULL + 8 * j, dst = sb + OFF_X + stage_off(0);
          const int c = ((sp + 1) & 3) * 128 + ((rank ^ 1) << 6);
          mbar_wait(sb + OFF_EMPTY + 8 + 8 * j, 1);
          mbar_expect_tx(fb, j == 1 ? 16384 : 14336);
          if (j == 1) {
            tma2d(dst + 14336, &maps.cre, s * 64, c, fb);
            tma2d(dst + 22528, &maps.cim, s * 64, c, fb);
          } else {
            tma2d(dst + j * 15360, &maps.w2, c, s * 224 + j * 56, fb);
          }
        }
#pragma unroll 1
        for (int p = 1; p < 8; p++) {
          const int c = ((sp + 1 + (p >> 1)) & 3) * 128 + (((rank ^ p ^ 1) & 1) << 6);
          const uint32_t fb = sb + OFF_XFULL + 8 * p, dst = sb + OFF_X + stage_off(p);
          if (p == 2 || p > 3) mbar_wait(sb + OFF_EMPTY + (p == 2 ? 40 : (p - 4) * 8), p == 2);
          TS2(0, 32 + p);
          mbar_expect_tx(fb, 45056);
          tma2d(dst, &maps.w2, c, s * 224, fb);
          tma2d(dst + 14336, &maps.cre, s * 64, c, fb);
          tma2d(dst + 22528, &maps.cim, s * 64, c, fb);
          tma2d(dst + 30720, &maps.w2, c, s * 224 + 112, fb);
        }
        TS(2, 2);
      }
    }
  }
}

typedef CUresult (*EncFn)(CUtensorMap*, CUtensorMapDataType, cuuint32_t, void*, const cuuint64_t*, const cuuint64_t*, const cuuint32_t*,
                          const cuuint32_t*, CUtensorMapInterleave, CUtensorMapSwizzle, CUtensorMapL2promotion, CUtensorMapFloatOOBfill);

void encode(EncFn f, CUtensorMap* mp, const void* p, int rank, const cuuint64_t* dims, const cuuint64_t* strides, const cuuint32_t* box, CUtensorMapSwizzle sw) {
  cuuint32_t es[5] = {1, 1, 1, 1, 1};
  f(mp, CU_TENSOR_MAP_DATA_TYPE_BFLOAT16, rank, const_cast<void*>(p), dims, strides, box, es, CU_TENSOR_MAP_INTERLEAVE_NONE, sw,
    CU_TENSOR_MAP_L2_PROMOTION_L2_128B, CU_TENSOR_MAP_FLOAT_OOB_FILL_NONE);
}

}

extern "C" void kernel_launch(void* const* d_in, const int* in_sizes, int n_in, void* d_out, int out_size) {
  typedef const __nv_bfloat16* bp;
  bp x = (bp)d_in[0], lre = (bp)d_in[1], lim = (bp)d_in[2], bre = (bp)d_in[3], bim = (bp)d_in[4], cre = (bp)d_in[5], cim = (bp)d_in[6],
     ldt = (bp)d_in[7], dsk = (bp)d_in[8], w1 = (bp)d_in[10], b1 = (bp)d_in[11], w2 = (bp)d_in[12], b2 = (bp)d_in[13], gw = (bp)d_in[14];
  static EncFn enc = nullptr;
  if (!enc) {
    void* f = nullptr;
    cudaDriverEntryPointQueryResult qr;
    cudaGetDriverEntryPoint("cuTensorMapEncodeTiled", &f, cudaEnableDefault, &qr);
    enc = (EncFn)f;
    cudaFuncSetAttribute(fused_kernel, cudaFuncAttributeMaxDynamicSharedMemorySize, SMEM_BYTES);
  }
  Maps maps;
  {
    cuuint64_t d[5] = {DM, 2, 4, 8, SEQ / 64}, st[4] = {DM * 2, 16 * DM * 2, 2 * DM * 2, 64 * DM * 2};
    cuuint32_t bx[5] = {64, 2, 4, 8, 1};
    encode(enc, &maps.x, x, 5, d, st, bx, CU_TENSOR_MAP_SWIZZLE_128B);
  }
  {
    cuuint64_t d[2] = {DM, DM}, st[1] = {DM * 2};
    cuuint32_t bx[2] = {64, 64};
    encode(enc, &maps.bre, bre, 2, d, st, bx, CU_TENSOR_MAP_SWIZZLE_128B);
    encode(enc, &maps.bim, bim, 2, d, st, bx, CU_TENSOR_MAP_SWIZZLE_128B);
    encode(enc, &maps.cre, cre, 2, d, st, bx, CU_TENSOR_MAP_SWIZZLE_128B);
    encode(enc, &maps.cim, cim, 2, d, st, bx, CU_TENSOR_MAP_SWIZZLE_128B);
  }
  {
    cuuint64_t d[2] = {FF, DM}, st[1] = {FF * 2};
    cuuint32_t bx[2] = {64, 64};
    encode(enc, &maps.w1a, w1, 2, d, st, bx, CU_TENSOR_MAP_SWIZZLE_128B);
    cuuint64_t d3[3] = {32, DM, FF / 32}, st3[2] = {FF * 2, 64};
    cuuint32_t bx3[3] = {32, 64, 3};
    encode(enc, &maps.w1b, w1, 3, d3, st3, bx3, CU_TENSOR_MAP_SWIZZLE_64B);
  }
  {
    cuuint64_t d[2] = {DM, FF}, st[1] = {DM * 2};
    cuuint32_t bx[2] = {64, 112};
    encode(enc, &maps.w2, w2, 2, d, st, bx, CU_TENSOR_MAP_SWIZZLE_128B);
  }
  fused_kernel<<<128, 384, SMEM_BYTES>>>(lre, lim, ldt, dsk, b1, b2, gw, w1, w2, cre, cim, (float*)d_out, maps);
}
```

```cpp
#include <cuda_runtime.h>
#include <cuda_bf16.h>
#include <cuda.h>
#include <stdint.h>

#define MAP 1
#define D0 250
#define D1 500
#define PF 4
#define PFK 5
#define GELUP 1
#define EW 2
#define K1E 1
#define K2E 0
#define QS 1
#define K2G 4
#define FINP 4
#define LBD 300
#define PFS 32
#define SB0 2
#define PFD 2
#define HOLD 0
#define GAP 14
#define FINW 0
#define K0P 33
#define K1P 53
#define TMP2 1
#define W0 1
#define LCK 4
#define TOKA 0
#define TOKB 2
#define TOKD 0
#define TKT 999
#define AV 3
#define QK 4
#define TCUT {1, 6, 6, 11, 16}
#define SCUT {0, 0, 0, 0, 0, 0, 8, 16, 24}
#define TP 9
#define TW 0

namespace {

constexpr int SEQ = 2048, DM = 512, FF = 1792;
constexpr int NSLOT = 6;
constexpr uint32_t OFF_X = 0, OFF_RING = 131072, OFF_MISC = 229376;
constexpr uint32_t OFF_XFULL = OFF_MISC, OFF_FULL = OFF_XFULL + 64, OFF_RBAR = OFF_FULL + 48, OFF_EMPTY = OFF_RBAR + 16, OFF_KBAR = OFF_EMPTY + 48,
                   OFF_GBAR = OFF_KBAR + 16, OFF_LBAR = OFF_GBAR + 8, OFF_CBAR = OFF_LBAR + 8, OFF_EPOCH = OFF_CBAR + 8;
constexpr uint32_t OFF_LC = OFF_MISC + 256;
constexpr uint32_t OFF_GS = OFF_LC;
constexpr uint32_t OFF_GT = OFF_LC + 256;
constexpr uint32_t OFF_DB = OFF_LC + 512;
constexpr uint32_t OFF_CARRY = OFF_LC + 1024;
constexpr uint32_t OFF_DBG = OFF_CARRY + 1024;
constexpr uint32_t SMEM_BYTES = OFF_DBG + 768;
static_assert(SMEM_BYTES <= 232448, "smem");

struct Maps { CUtensorMap x, bre, bim, w1b, w1a, w2, cre, cim; };
__host__ __device__ constexpr uint32_t stage_off(int p) { return 49152 + 45056 * (((p >> 1) & 1) + 2 * (p & 1)); }

__host__ __device__ constexpr uint32_t full_par(int u) { return ((u - 8) / 6 + (u % 6 == 0)) & 1; }

__device__ uint4 g_part[16 * 8 * 3 * 1024];
__device__ float2 g_end[8 * 16 * 64];
__device__ unsigned g_gate[SEQ];
__device__ unsigned g_epoch[128];
#define TG(role) do {} while (0)
#define TS2(role, i) do {} while (0)
#define TS(role, i) do {} while (0)
#define TDUMP() do {} while (0)
#define TR(i) do {} while (0)
#define TK(i) do {} while (0)
#define TRD() do {} while (0)

__device__ __forceinline__ void mbar_init(uint32_t bar, uint32_t cnt) { asm volatile("mbarrier.init.shared::cta.b64 [%0], %1;" ::"r"(bar), "r"(cnt)); }
__device__ __forceinline__ void mbar_expect_tx(uint32_t bar, uint32_t bytes) { asm volatile("mbarrier.arrive.expect_tx.shared::cta.b64 _, [%0], %1;" ::"r"(bar), "r"(bytes) : "memory"); }
__device__ __forceinline__ void mbar_arrive(uint32_t bar) { asm volatile("mbarrier.arrive.shared::cta.b64 _, [%0];" ::"r"(bar) : "memory"); }
__device__ __forceinline__ void mbar_arrive_cl(uint32_t cbar) { asm volatile("mbarrier.arrive.shared::cluster.b64 _, [%0];" ::"r"(cbar) : "memory"); }
__device__ __forceinline__ void mbar_wait(uint32_t bar, uint32_t parity) {
  asm volatile(
      "{\n.reg .pred p;\n.reg .u32 c;\n"
      "mbarrier.try_wait.parity.shared::cta.b64 p, [%0], %1;\n"
      "@p bra.uni LAB_DONE;\n"
      "mov.u32 c, 0;\n"
      "LAB_WAIT:\n"
      "mbarrier.try_wait.parity.shared::cta.b64 p, [%0], %1;\n"
      "@p bra.uni LAB_DONE;\n"
      "add.u32 c, c, 1;\nsetp.lt.u32 p, c, 200000;\n@p bra.uni LAB_WAIT;\n"
      "LAB_DONE:\n}" ::"r"(bar), "r"(parity) : "memory");
}
__device__ __forceinline__ void tma2d(uint32_t dst, const CUtensorMap* m, int c0, int c1, uint32_t bar) {
  asm volatile("cp.async.bulk.tensor.2d.shared::cluster.global.mbarrier::complete_tx::bytes [%0], [%1, {%3,%4}], [%2];"
               ::"r"(dst), "l"(m), "r"(bar), "r"(c0), "r"(c1) : "memory");
}
__device__ __forceinline__ void tma3d(uint32_t dst, const CUtensorMap* m, int c0, int c1, int c2, uint32_t bar) {
  asm volatile("cp.async.bulk.tensor.3d.shared::cluster.global.mbarrier::complete_tx::bytes [%0], [%1, {%3,%4,%5}], [%2];"
               ::"r"(dst), "l"(m), "r"(bar), "r"(c0), "r"(c1), "r"(c2) : "memory");
}
__device__ __forceinline__ void tma5d(uint32_t dst, const CUtensorMap* m, int c0, int c4, uint32_t bar) {
  asm volatile("cp.async.bulk.tensor.5d.shared::cluster.global.mbarrier::complete_tx::bytes [%0], [%1, {%3,%5,%5,%5,%4}], [%2];"
               ::"r"(dst), "l"(m), "r"(bar), "r"(c0), "r"(c4), "r"(0) : "memory");
}
__device__ __forceinline__ void tma5d_mc(uint32_t dst, const CUtensorMap* m, int c0, int c4, uint32_t bar) {
  asm volatile("cp.async.bulk.tensor.5d.shared::cluster.global.mbarrier::complete_tx::bytes.multicast::cluster [%0], [%1, {%3,%5,%5,%5,%4}], [%2], %6;"
               ::"r"(dst), "l"(m), "r"(bar), "r"(c0), "r"(c4), "r"(0), "h"((uint16_t)3) : "memory");
}
__device__ __forceinline__ void l2_prefetch(const void* p, uint32_t bytes) { asm volatile("cp.async.bulk.prefetch.L2.global [%0], %1;" ::"l"(p), "r"(bytes) : "memory"); }
__device__ __forceinline__ bool elect_one() {
  uint32_t pred;
  asm volatile("{.reg .pred P; elect.sync _|P, 0xffffffff; selp.u32 %0, 1, 0, P;}" : "=r"(pred));
  return pred != 0;
}
__device__ __forceinline__ void wg_fence() { asm volatile("wgmma.fence.sync.aligned;" ::: "memory"); }
__device__ __forceinline__ void wg_commit() { asm volatile("wgmma.commit_group.sync.aligned;" ::: "memory"); }
template <int N> __device__ __forceinline__ void wg_wait() { asm volatile("wgmma.wait_group.sync.aligned %0;" ::"n"(N) : "memory"); }
__device__ __forceinline__ void pin(float& a) { asm volatile("" : "+f"(a)::"memory"); }
__device__ __forceinline__ void pin(uint32_t& a) { asm volatile("" : "+r"(a)::"memory"); }
template <int N> __device__ __forceinline__ void reg_fence(float (&d)[N]) {
#pragma unroll
  for (int i = 0; i < N; i++) pin(d[i]);
}
__device__ __forceinline__ void bar_sync(int id, int n) { asm volatile("bar.sync %0, %1;" ::"r"(id), "r"(n) : "memory"); }
__device__ __forceinline__ void bar_arrive(int id, int n) { asm volatile("bar.arrive %0, %1;" ::"r"(id), "r"(n) : "memory"); }
constexpr uint32_t DH128 = (1024 >> 4) | (1u << 30), DH64 = (512 >> 4) | (2u << 30);
__host__ __device__ constexpr uint32_t lbo(uint32_t bytes) { return (bytes >> 4) << 20; }
__device__ __forceinline__ uint32_t pack_bf16(float lo, float hi) { uint32_t r; asm("cvt.rn.bf16x2.f32 %0, %1, %2;" : "=r"(r) : "f"(hi), "f"(lo)); return r; }
__device__ __forceinline__ float bf_lo(uint32_t v) { return __uint_as_float(v << 16); }
__device__ __forceinline__ float bf_hi(uint32_t v) { return __uint_as_float(v & 0xffff0000u); }
__device__ __forceinline__ float bf_ld(const __nv_bfloat16* p) { return __bfloat162float(__ldg(p)); }
__device__ __forceinline__ uint32_t late16(uint32_t bar) {
  uint32_t r;
  asm volatile("{.reg .pred p; mbarrier.test_wait.parity.shared::cta.b64 p, [%1], 0; selp.u32 %0, 16, 0, p;}" : "=r"(r) : "r"(bar) : "memory");
  return r;
}
__device__ __forceinline__ float2 lds_f2(uint32_t a) { float2 v; asm volatile("ld.shared.v2.f32 {%0,%1}, [%2];" : "=f"(v.x), "=f"(v.y) : "r"(a)); return v; }
__device__ __forceinline__ uint32_t lds_h(uint32_t a) { uint32_t v; asm volatile("ld.shared.u16 %0, [%1];" : "=r"(v) : "r"(a)); return v; }
__device__ __forceinline__ uint32_t lds_u(uint32_t a) { uint32_t v; asm volatile("ld.shared.u32 %0, [%1];" : "=r"(v) : "r"(a)); return v; }
__device__ __forceinline__ uint4 lds_u4(uint32_t a) { uint4 v; asm volatile("ld.shared.v4.u32 {%0,%1,%2,%3}, [%4];" : "=r"(v.x), "=r"(v.y), "=r"(v.z), "=r"(v.w) : "r"(a)); return v; }
__device__ __forceinline__ void st_b128(uint4* p, uint32_t a, uint32_t b, uint32_t c, uint32_t d) {
  asm volatile("st.relaxed.gpu.global.v4.b32 [%0], {%1,%2,%3,%4};" ::"l"(p), "r"(a), "r"(b), "r"(c), "r"(d) : "memory");
}
__device__ __forceinline__ void ld_b128(const uint4* p, uint32_t& a, uint32_t& b, uint32_t& c, uint32_t& d) {
  asm volatile("{.reg .b64 l, h; .reg .b128 v; ld.relaxed.gpu.global.b128 v, [%4]; mov.b128 {l,h}, v; mov.b64 {%0,%1}, l; mov.b64 {%2,%3}, h;}"
               : "=r"(a), "=r"(b), "=r"(c), "=r"(d) : "l"(p) : "memory");
}
__device__ __forceinline__ float tanh_fast(float x) { float y; asm("tanh.approx.f32 %0, %1;" : "=f"(y) : "f"(x)); return y; }
__device__ __forceinline__ float gelu2(float v) {
  float p = fmaf(v * v, 0.0356774081363f, 0.7978845608029f);
  return fmaf(v, tanh_fast(v * p), v);
}
__device__ __forceinline__ void sched_fence(uint32_t& ck) { asm volatile("{.reg .b32 c; mov.u32 c, %%clock; xor.b32 %0, %0, c;}" : "+r"(ck)::"memory"); }
__device__ __forceinline__ uint32_t bf2_mul(uint32_t a, uint32_t b) { uint32_t r; asm("mul.rn.bf16x2 %0, %1, %2;" : "=r"(r) : "r"(a), "r"(b)); return r; }
__device__ __forceinline__ uint32_t bf2_add(uint32_t a, uint32_t b) { uint32_t r; asm("add.rn.bf16x2 %0, %1, %2;" : "=r"(r) : "r"(a), "r"(b)); return r; }
__device__ __forceinline__ uint32_t bf2_fma(uint32_t a, uint32_t b, uint32_t c) { uint32_t r; asm("fma.rn.bf16x2 %0, %1, %2, %3;" : "=r"(r) : "r"(a), "r"(b), "r"(c)); return r; }
__device__ __forceinline__ uint32_t gelu2_pair(float a, float b) {
  const uint32_t v = pack_bf16(a, b);
  uint32_t t;
  asm("tanh.approx.bf16x2 %0, %1;" : "=r"(t) : "r"(bf2_fma(v, bf2_fma(bf2_mul(v, v), 0x3d123d12u, 0xbe4fbe4fu), v)));
  return bf2_fma(v, t, v);
}
struct cplx { float re, im; };
__device__ __forceinline__ cplx cmul(cplx a, cplx b) { return {fmaf(a.re, b.re, -a.im * b.im), fmaf(a.re, b.im, a.im * b.re)}; }
__device__ __forceinline__ cplx cfma(cplx a, cplx b, cplx c) {
  return {fmaf(a.re, b.re, fmaf(-a.im, b.im, c.re)), fmaf(a.re, b.im, fmaf(a.im, b.re, c.im))};
}
__device__ __forceinline__ cplx make_lam(float lre, float lim, float ldt) {
  float dt = __bfloat162float(__float2bfloat16_rn(expf(ldt)));
  float mag = expf(dt * lre), sn, cs;
  sincospif(dt * lim * 0.31830988618379067f, &sn, &cs);
  return {mag * cs, mag * sn};
}

template<int TA,int TB,uint32_t AH,uint32_t BH> __device__ __forceinline__ void wgmma_n64_ss(float (&d)[32], uint32_t al, uint32_t ao, uint32_t bl, uint32_t bo, int scale_d){
  asm volatile("{.reg .pred p; .reg .b32 t, v; .reg .b64 da, db; setp.ne.b32 p, %36, 0; add.u32 t, %32, %33; mov.b64 da, {t, %39}; add.u32 v, %34, %35; mov.b64 db, {v, %40};\n"
   "wgmma.mma_async.sync.aligned.m64n64k16.f32.bf16.bf16 {%0,%1,%2,%3,%4,%5,%6,%7,%8,%9,%10,%11,%12,%13,%14,%15,%16,%17,%18,%19,%20,%21,%22,%23,%24,%25,%26,%27,%28,%29,%30,%31}, da, db, p, 1, 1, %37, %38;}"
   : "+f"(d[0]),"+f"(d[1]),"+f"(d[2]),"+f"(d[3]),"+f"(d[4]),"+f"(d[5]),"+f"(d[6]),"+f"(d[7]),"+f"(d[8]),"+f"(d[9]),"+f"(d[10]),"+f"(d[11]),"+f"(d[12]),"+f"(d[13]),"+f"(d[14]),"+f"(d[15]),"+f"(d[16]),"+f"(d[17]),"+f"(d[18]),"+f"(d[19]),"+f"(d[20]),"+f"(d[21]),"+f"(d[22]),"+f"(d[23]),"+f"(d[24]),"+f"(d[25]),"+f"(d[26]),"+f"(d[27]),"+f"(d[28]),"+f"(d[29]),"+f"(d[30]),"+f"(d[31])
   : "r"(al),"r"(ao >> 4),"r"(bl),"r"(bo >> 4),"r"(scale_d),"n"(TA),"n"(TB),"n"(AH),"n"(BH));
}
template<int TB,uint32_t BH,int SA=1> __device__ __forceinline__ void wgmma_n64_rs(float (&d)[32], uint32_t a0,uint32_t a1,uint32_t a2,uint32_t a3, uint32_t bl, uint32_t bo, int scale_d){
  asm volatile("{.reg .pred p; .reg .b32 t; .reg .b64 db; setp.ne.b32 p, %38, 0; add.u32 t, %36, %37; mov.b64 db, {t, %40};\n"
   "wgmma.mma_async.sync.aligned.m64n64k16.f32.bf16.bf16 {%0,%1,%2,%3,%4,%5,%6,%7,%8,%9,%10,%11,%12,%13,%14,%15,%16,%17,%18,%19,%20,%21,%22,%23,%24,%25,%26,%27,%28,%29,%30,%31}, {%32,%33,%34,%35}, db, p, %41, 1, %39;}"
   : "+f"(d[0]),"+f"(d[1]),"+f"(d[2]),"+f"(d[3]),"+f"(d[4]),"+f"(d[5]),"+f"(d[6]),"+f"(d[7]),"+f"(d[8]),"+f"(d[9]),"+f"(d[10]),"+f"(d[11]),"+f"(d[12]),"+f"(d[13]),"+f"(d[14]),"+f"(d[15]),"+f"(d[16]),"+f"(d[17]),"+f"(d[18]),"+f"(d[19]),"+f"(d[20]),"+f"(d[21]),"+f"(d[22]),"+f"(d[23]),"+f"(d[24]),"+f"(d[25]),"+f"(d[26]),"+f"(d[27]),"+f"(d[28]),"+f"(d[29]),"+f"(d[30]),"+f"(d[31])
   : "r"(a0),"r"(a1),"r"(a2),"r"(a3),"r"(bl),"r"(bo >> 4),"r"(scale_d),"n"(TB),"n"(BH),"n"(SA));
}
template<int TA,int TB,uint32_t AH,uint32_t BH> __device__ __forceinline__ void wgmma_n96_ss(float (&d)[48], uint32_t al, uint32_t ao, uint32_t bl, uint32_t bo, int scale_d){
  asm volatile("{.reg .pred p; .reg .b32 t, v; .reg .b64 da, db; setp.ne.b32 p, %52, 0; add.u32 t, %48, %49; mov.b64 da, {t, %55}; add.u32 v, %50, %51; mov.b64 db, {v, %56};\n"
   "wgmma.mma_async.sync.aligned.m64n96k16.f32.bf16.bf16 {%0,%1,%2,%3,%4,%5,%6,%7,%8,%9,%10,%11,%12,%13,%14,%15,%16,%17,%18,%19,%20,%21,%22,%23,%24,%25,%26,%27,%28,%29,%30,%31,%32,%33,%34,%35,%36,%37,%38,%39,%40,%41,%42,%43,%44,%45,%46,%47}, da, db, p, 1, 1, %53, %54;}"
   : "+f"(d[0]),"+f"(d[1]),"+f"(d[2]),"+f"(d[3]),"+f"(d[4]),"+f"(d[5]),"+f"(d[6]),"+f"(d[7]),"+f"(d[8]),"+f"(d[9]),"+f"(d[10]),"+f"(d[11]),"+f"(d[12]),"+f"(d[13]),"+f"(d[14]),"+f"(d[15]),"+f"(d[16]),"+f"(d[17]),"+f"(d[18]),"+f"(d[19]),"+f"(d[20]),"+f"(d[21]),"+f"(d[22]),"+f"(d[23]),"+f"(d[24]),"+f"(d[25]),"+f"(d[26]),"+f"(d[27]),"+f"(d[28]),"+f"(d[29]),"+f"(d[30]),"+f"(d[31]),"+f"(d[32]),"+f"(d[33]),"+f"(d[34]),"+f"(d[35]),"+f"(d[36]),"+f"(d[37]),"+f"(d[38]),"+f"(d[39]),"+f"(d[40]),"+f"(d[41]),"+f"(d[42]),"+f"(d[43]),"+f"(d[44]),"+f"(d[45]),"+f"(d[46]),"+f"(d[47])
   : "r"(al),"r"(ao >> 4),"r"(bl),"r"(bo >> 4),"r"(scale_d),"n"(TA),"n"(TB),"n"(AH),"n"(BH));
}
template<int TA,int TB,uint32_t AH,uint32_t BH> __device__ __forceinline__ void wgmma_n128_ss(float (&d)[64], uint32_t al, uint32_t ao, uint32_t bl, uint32_t bo, int scale_d){
  asm volatile("{.reg .pred p; .reg .b32 t, v; .reg .b64 da, db; setp.ne.b32 p, %68, 0; add.u32 t, %64, %65; mov.b64 da, {t, %71}; add.u32 v, %66, %67; mov.b64 db, {v, %72};\n"
   "wgmma.mma_async.sync.aligned.m64n128k16.f32.bf16.bf16 {%0,%1,%2,%3,%4,%5,%6,%7,%8,%9,%10,%11,%12,%13,%14,%15,%16,%17,%18,%19,%20,%21,%22,%23,%24,%25,%26,%27,%28,%29,%30,%31,%32,%33,%34,%35,%36,%37,%38,%39,%40,%41,%42,%43,%44,%45,%46,%47,%48,%49,%50,%51,%52,%53,%54,%55,%56,%57,%58,%59,%60,%61,%62,%63}, da, db, p, 1, 1, %69, %70;}"
   : "+f"(d[0]),"+f"(d[1]),"+f"(d[2]),"+f"(d[3]),"+f"(d[4]),"+f"(d[5]),"+f"(d[6]),"+f"(d[7]),"+f"(d[8]),"+f"(d[9]),"+f"(d[10]),"+f"(d[11]),"+f"(d[12]),"+f"(d[13]),"+f"(d[14]),"+f"(d[15]),"+f"(d[16]),"+f"(d[17]),"+f"(d[18]),"+f"(d[19]),"+f"(d[20]),"+f"(d[21]),"+f"(d[22]),"+f"(d[23]),"+f"(d[24]),"+f"(d[25]),"+f"(d[26]),"+f"(d[27]),"+f"(d[28]),"+f"(d[29]),"+f"(d[30]),"+f"(d[31]),"+f"(d[32]),"+f"(d[33]),"+f"(d[34]),"+f"(d[35]),"+f"(d[36]),"+f"(d[37]),"+f"(d[38]),"+f"(d[39]),"+f"(d[40]),"+f"(d[41]),"+f"(d[42]),"+f"(d[43]),"+f"(d[44]),"+f"(d[45]),"+f"(d[46]),"+f"(d[47]),"+f"(d[48]),"+f"(d[49]),"+f"(d[50]),"+f"(d[51]),"+f"(d[52]),"+f"(d[53]),"+f"(d[54]),"+f"(d[55]),"+f"(d[56]),"+f"(d[57]),"+f"(d[58]),"+f"(d[59]),"+f"(d[60]),"+f"(d[61]),"+f"(d[62]),"+f"(d[63])
   : "r"(al),"r"(ao >> 4),"r"(bl),"r"(bo >> 4),"r"(scale_d),"n"(TA),"n"(TB),"n"(AH),"n"(BH));
}

__global__ void __cluster_dims__(2, 1, 1) __launch_bounds__(384, 1)
fused_kernel(const __nv_bfloat16* __restrict__ lam_re, const __nv_bfloat16* __restrict__ lam_im, const __nv_bfloat16* __restrict__ log_dt,
             const __nv_bfloat16* __restrict__ dskip, const __nv_bfloat16* __restrict__ b1, const __nv_bfloat16* __restrict__ b2,
             const __nv_bfloat16* __restrict__ gate_w, const __nv_bfloat16* __restrict__ pf_w1, const __nv_bfloat16* __restrict__ pf_w2,
             const __nv_bfloat16* __restrict__ pf_cre, const __nv_bfloat16* __restrict__ pf_cim, float* __restrict__ out,
             const __grid_constant__ Maps maps) {
  extern __shared__ __align__(1024) unsigned char smem_raw[];
  const uint32_t sb = (uint32_t)__cvta_generic_to_shared(smem_raw);
  const int b = blockIdx.x;
  const int rank = b & 1, cl = b >> 1;
  const int sp = (cl & 1) | ((cl >> 2) & 2), m = ((cl >> 1) & 3) | ((cl >> 4) << 2);
  const int s = sp * 2 + rank;
  const int warp = __shfl_sync(0xffffffffu, (int)(threadIdx.x >> 5), 0);
  const int lane = threadIdx.x & 31;
  const int xrot = 9 - 2 * sp;

  if (elect_one()) {
    if (warp == 8) TS(2, 0);
    if (warp > 8) {
      asm volatile("prefetch.tensormap [%0];" ::"l"(&maps.x + (warp - 9)) : "memory");
      mbar_init(sb + OFF_GBAR + 8 * (warp - 9), warp < 11 ? 64 : 96);
    }
    const uint32_t c = warp < 8 ? 1 : warp < 11 ? 8 : 4, bar = sb + OFF_XFULL + 16 * warp;
    mbar_init(bar, c);
    if ((warp & 11) == 0) {
      mbar_expect_tx(bar, 16384);
      if (warp == 0) {
        tma5d(sb + OFF_X + (xrot & 7) * 16384, &maps.x, 0, 2 * m, bar);
        tma5d(sb + OFF_X + (xrot & 7) * 16384 + 8192, &maps.x, 0, 2 * m + 1, bar);
        TS(2, 3);
      } else {
        tma2d(sb + OFF_RING, &maps.bre, 0, s * 64, bar);
        tma2d(sb + OFF_RING + 8192, &maps.bim, 0, s * 64, bar);
        TS(2, 4);
      }
    }
    mbar_init(bar + 8, c);
    asm volatile("fence.mbarrier_init.release.cluster;" ::: "memory");
  }
  __syncwarp();
  asm volatile("barrier.cluster.arrive.relaxed.aligned;" ::: "memory");

  if (warp < 8) {
    const int wg = warp >> 2, w = warp & 3, q = lane & 3, gr = lane >> 2;
    uint32_t bv[28];
#pragma unroll
    for (int j = 0; j < 28; j++) bv[j] = __ldg(reinterpret_cast<const uint32_t*>(b1 + s * 224 + j * 8) + q);
    asm volatile("setmaxnreg.inc.sync.aligned.u32 224;");
    asm volatile("barrier.cluster.wait.aligned;" ::: "memory");
    TS(wg, 0);
    auto release = [&](int slot) { if (lane == 0) mbar_arrive(sb + OFF_EMPTY + 8 * slot); };
    const uint32_t xw = sb + OFF_X + wg * 8192, fullb = sb + OFF_FULL;
    const uint32_t dxw = (xw & 0x3FFFF) >> 4, dring = ((sb + OFF_RING) & 0x3FFFF) >> 4;

    float ure[32], uim[32], aa[48], ab[64];
    cplx lam[2], coef[2], l16[2], l32[2], lq[2], pre[2], e[2];
    uint32_t sh16, mhi, ck = 0;

    auto bias = [&](int c) {
#pragma unroll
      for (int j = c * 7; j < c * 7 + 7; j++) {
        pin(bv[j]);
        float* d = j < 12 ? aa + 4 * j : ab + 4 * (j - 12);
        d[0] = d[2] = __uint_as_float(bv[j] << sh16); d[1] = d[3] = __uint_as_float(bv[j] & mhi);
        pin(d[0]); pin(d[1]); pin(d[2]); pin(d[3]);
      }
    };
#pragma unroll
    for (int kb = 0; kb < 8; kb++) {
      const int slot = kb % NSLOT;
      mbar_wait(sb + OFF_XFULL + 8 * kb, 0);
      if (kb == 0) TS(wg, 18);
      if (kb == 0) mbar_wait(fullb, 0);
      TS2(2, kb);
      if (kb == 0) TS(wg, 1);
      if (kb == SB0) { sh16 = late16(sb + OFF_XFULL); mhi = 0xffffffffu << sh16; }
      if (kb == LCK) {
        mbar_wait(sb + OFF_LBAR, 0);
#pragma unroll
        for (int h = 0; h < 2; h++) {
          const uint4 v = lds_u4(sb + OFF_LC + (w * 16 + gr + 8 * h) * 16);
          lam[h] = cplx{__uint_as_float(v.x), __uint_as_float(v.y)};
          coef[h] = cplx{__uint_as_float(v.z), __uint_as_float(v.w)};
        }
      }
      wg_fence();
      const uint32_t dxa = dxw + ((kb + xrot) & 7) * 1024;
#pragma unroll
      for (int kk = 0; kk < 4; kk++) {
        wgmma_n64_ss<0, 0, DH128, DH128>(ure, dring, slot * 16384 + kk * 32, dxa, kk * 32, (kb | kk) != 0);
        wgmma_n64_ss<0, 0, DH128, DH128>(uim, dring, slot * 16384 + 8192 + kk * 32, dxa, kk * 32, (kb | kk) != 0);
      }
      wg_commit();
      if (kb > 0) { wg_wait<1>(); release((kb - 1) % NSLOT); }
      if (kb >= SB0 && kb < SB0 + 3) bias(kb - SB0);
      if (kb == 6) {
#pragma unroll
        for (int h = 0; h < 2; h++) {
          pin(lam[h].re); pin(lam[h].im);
          cplx t = cmul(lam[h], lam[h]); t = cmul(t, t); t = cmul(t, t);
          l16[h] = cmul(t, t);
          pin(l16[h].re); pin(l16[h].im);
        }
      }
      if (kb == 7) {
#pragma unroll
        for (int h = 0; h < 2; h++) {
          pin(l16[h].re); pin(l16[h].im);
          l32[h] = cmul(l16[h], l16[h]);
          const cplx a = (q & 1) ? l16[h] : cplx{1.f, 0.f}, c = (q & 2) ? l32[h] : cplx{1.f, 0.f};
          lq[h] = cmul(cmul(a, c), coef[h]);
          pin(lq[h].re); pin(lq[h].im);
        }
      }
    }
    TS(wg, 2);
    auto scale_u = [&](int i0, int i1) {
#pragma unroll
      for (int i = 0; i < 32; i++) if (i >= i0 && i < i1) {
        pin(ure[i]); pin(uim[i]);
        const cplx v = cmul(coef[(i >> 1) & 1], cplx{ure[i], uim[i]});
        ure[i] = v.re; uim[i] = v.im;
        pin(ure[i]); pin(uim[i]);
      }
    };
#pragma unroll
    for (int kb = 0; kb < 8; kb++) {
      const int u = 8 + kb, slot = u % NSLOT;
      mbar_wait(fullb + 8 * slot, full_par(u));
      TK(kb);
      wg_fence();
      const uint32_t dxa = dxw + ((kb + xrot) & 7) * 1024;
#pragma unroll
      for (int kk = 0; kk < 4; kk++)
        wgmma_n96_ss<0, 1, DH128, DH64>(aa, dxa, kk * 32, dring, slot * 16384 + kk * 1024 + lbo(4096), 1);
      wg_commit();
      if (kb == 0) bias(3);
      if (kb != QK) { wg_wait<1>(); release((u - 1) % NSLOT); }
      if (kb == 0) {
        reg_fence(ure); reg_fence(uim);
#pragma unroll
        for (int h = 0; h < 2; h++) e[h] = cplx{ure[2 * h], uim[2 * h]};
      }
      if (kb == 0 || (kb >= 2 && kb <= QK && kb < 4)) {
        constexpr int tc[5] = TCUT;
#pragma unroll
        for (int t = 1; t < 16; t++) if (t >= tc[kb] && t < tc[kb + 1]) {
#pragma unroll
          for (int h = 0; h < 2; h++) { const int i = 4 * (t >> 1) + 2 * h + (t & 1); e[h] = cfma(lam[h], e[h], cplx{ure[i], uim[i]}); }
        }
#pragma unroll
        for (int h = 0; h < 2; h++) { pin(e[h].re); pin(e[h].im); }
      }
      if (kb == QK) {
        sched_fence(ck);
#pragma unroll
        for (int h = 0; h < 2; h++) {
          cplx y = {__shfl_up_sync(0xffffffffu, e[h].re, 1, 4), __shfl_up_sync(0xffffffffu, e[h].im, 1, 4)};
          if (q >= 1) e[h] = cfma(l16[h], y, e[h]);
          y = cplx{__shfl_up_sync(0xffffffffu, e[h].re, 2, 4), __shfl_up_sync(0xffffffffu, e[h].im, 2, 4)};
          if (q >= 2) e[h] = cfma(l32[h], y, e[h]);
        }
        if (q == 3) {
#pragma unroll
          for (int h = 0; h < 2; h++)
            asm volatile("st.shared.v2.f32 [%0], {%1,%2};" ::"r"(sb + OFF_CARRY + wg * 512 + (w * 16 + gr + 8 * h) * 8), "f"(e[h].re), "f"(e[h].im) : "memory");
          mbar_arrive(sb + OFF_GBAR);
        }
#pragma unroll
        for (int h = 0; h < 2; h++) e[h] = cplx{__shfl_up_sync(0xffffffffu, e[h].re, 1, 4), __shfl_up_sync(0xffffffffu, e[h].im, 1, 4)};
        wg_wait<1>(); release((u - 1) % NSLOT);
        if (TKT > 500) TS(wg, 3);
      }
      if (kb == QK + 1) {
#pragma unroll
        for (int h = 0; h < 2; h++) {
          pre[h] = (q >= 1) ? cmul(coef[h], e[h]) : cplx{0.f, 0.f};
          pin(pre[h].re); pin(pre[h].im);
        }
      }
      if (kb > QK) { constexpr int sc[9] = SCUT; scale_u(sc[kb], sc[kb + 1]); }
    }
    TS(wg, 4);
    uint32_t H[56], hf[32];
    cplx hst[2];
    const uint32_t hst_addr = xw + (w * 16 + (lane & 15)) * 128 + (((lane >> 4) ^ (lane & 7)) << 4);
    const uint32_t him = (2 - rank) * 16384;
    uint32_t peer;
    asm volatile("mapa.shared::cluster.u32 %0, %1, %2;" : "=r"(peer) : "r"(sb), "r"(rank ^ 1));
    auto credit = [&]() { if (lane == 0) mbar_arrive_cl(peer + OFF_KBAR + wg * 8); };
    uint32_t g2[8];
#pragma unroll
    for (int kb = 0; kb < 8; kb++) {
      const int u = 16 + kb, slot = u % NSLOT;
      mbar_wait(fullb + 8 * slot, full_par(u));
      TK(kb < 7 ? 24 + kb : 32);
      wg_fence();
#pragma unroll
      for (int kk = 0; kk < 4; kk++)
        wgmma_n128_ss<0, 1, DH128, DH128>(ab, dxw, kb * 16384 + kk * 32, dring, slot * 16384 + kk * 2048 + lbo(8192), 1);
      wg_commit();
      if (kb == 0) { constexpr int sc[9] = SCUT; scale_u(sc[8], 32); }
      if (kb == 4) {
        if (TKT > 500) TS(wg, 5);
        mbar_wait(sb + OFF_CBAR, 0);
        if (TKT > 500) TS(wg, 6);
#pragma unroll
        for (int h = 0; h < 2; h++) {
          const float2 c = lds_f2(sb + OFF_CARRY + wg * 512 + (w * 16 + gr + 8 * h) * 8);
          hst[h] = cfma(lq[h], cplx{c.x, c.y}, pre[h]);
        }
#pragma unroll
        for (int i = 0; i < 2; i++) {
          const uint4 v = lds_u4(sb + OFF_GT + wg * 128 + q * 32 + i * 16);
          g2[4 * i] = v.x; g2[4 * i + 1] = v.y; g2[4 * i + 2] = v.z; g2[4 * i + 3] = v.w;
        }
      }
      if (kb == 0 || TOKB != 1) { wg_wait<1>(); release((u - 1) % NSLOT); }
      if (kb) sched_fence(ck);
      if (kb < 4) {
#pragma unroll
        for (int i = kb * 6; i < kb * 6 + 6; i++) {
          pin(aa[2 * i]); pin(aa[2 * i + 1]);
          H[i] = gelu2_pair(aa[2 * i], aa[2 * i + 1]);
          pin(H[i]);
        }
      } else {
        const int j0 = (kb - 4) * 2;
        uint32_t rr[4], ri[4];
#pragma unroll
        for (int jj = 0; jj < 2; jj++) {
          const int j = j0 + jj;
#pragma unroll
          for (int h = 0; h < 2; h++) {
            const int i = 4 * j + 2 * h;
            const cplx h0 = cfma(lam[h], hst[h], cplx{ure[i], uim[i]});
            hst[h] = cfma(lam[h], h0, cplx{ure[i + 1], uim[i + 1]});
            rr[jj * 2 + h] = bf2_mul(pack_bf16(h0.re, hst[h].re), g2[j]);
            ri[jj * 2 + h] = bf2_mul(pack_bf16(h0.im, hst[h].im), g2[j]);
          }
        }
        const uint32_t a = hst_addr ^ (j0 << 4);
        asm volatile("stmatrix.sync.aligned.m8n8.x4.shared.b16 [%0], {%1,%2,%3,%4};" ::"r"(a), "r"(rr[0]), "r"(rr[1]), "r"(rr[2]), "r"(rr[3]) : "memory");
        asm volatile("stmatrix.sync.aligned.m8n8.x4.shared.b16 [%0], {%1,%2,%3,%4};" ::"r"(a + him), "r"(ri[0]), "r"(ri[1]), "r"(ri[2]), "r"(ri[3]) : "memory");
      }
      if (kb && TOKB == 1) { wg_wait<1>(); release((u - 1) % NSLOT); }
    }
    TS(wg, 7);

    uint4* const psend = g_part + (size_t)(m * 8 + rank) * 3072 + warp * 128 + lane;
    const uint4* const precv = g_part + (size_t)(m * 8 + s) * 3072 + warp * 128 + lane;
    const uint32_t pbuf = OFF_X + warp * 2048 + lane * 16;
    const uint32_t dx0 = ((sb + OFF_X) & 0x3FFFF) >> 4;
    float o[32], fin[32], rho[2];
    uint32_t tr[8];
    uint32_t r0[16], pt[16], sum[16], tag;
    auto recv_issue = [&](uint32_t (&r)[16], int k) {
#pragma unroll
      for (int i = 0; i < 4; i++) ld_b128(precv + k * 1024 + i * 32, r[4 * i], r[4 * i + 1], r[4 * i + 2], r[4 * i + 3]);
    };
    auto stale = [&](uint32_t (&r)[16]) {
      uint32_t t0, t1, r_;
      asm("lop3.b32 %0, %1, %2, %3, 0x7e;" : "=r"(t0) : "r"(r[0]), "r"(r[4]), "r"(tag));
      asm("lop3.b32 %0, %1, %2, %3, 0x7e;" : "=r"(t1) : "r"(r[8]), "r"(r[12]), "r"(tag));
      asm volatile("{.reg .pred p; .reg .b32 t; lop3.b32 t, %1, %2, 1, 0xa8; setp.ne.u32 p, t, 0; vote.sync.any.pred p, p, 0xffffffff; selp.u32 %0, 1, 0, p;}" : "=r"(r_) : "r"(t0), "r"(t1));
      return r_ != 0;
    };
    auto recv_check = [&](uint32_t (&r)[16], int k) {
      if (__builtin_expect(stale(r), 0)) {
        int tries = 0;
#pragma unroll 1
        do { recv_issue(r, k); } while (stale(r) && ++tries < 200000);
      }
    };
    auto gelu_b = [&](int i0, int i1) {
      if (TOKD && i0) sched_fence(ck);
#pragma unroll
      for (int i = i0; i < i1; i++) {
        pin(ab[2 * i]); pin(ab[2 * i + 1]);
        H[24 + i] = gelu2_pair(ab[2 * i], ab[2 * i + 1]);
        pin(H[24 + i]);
      }
      if (TOKD == 2) sched_fence(ck);
    };
    auto step = [&](float (&d)[32], int p, int k, int acc) {
      const uint32_t wo = stage_off(p);
      if (k >= 6 && k < 14) {
        const int kk = k - 6;
        if (kk < 4) wgmma_n64_rs<0, DH128, 1>(d, hf[4 * kk], hf[4 * kk + 1], hf[4 * kk + 2], hf[4 * kk + 3], dx0, wo + 14336 + kk * 32, 1);
        else wgmma_n64_rs<0, DH128, -1>(d, hf[4 * kk], hf[4 * kk + 1], hf[4 * kk + 2], hf[4 * kk + 3], dx0, wo + 22528 + (kk - 4) * 32, 1);
      } else {
        const int kk = k < 6 ? k : k - 8;
        wgmma_n64_rs<1, DH128>(d, H[4 * kk], H[4 * kk + 1], H[4 * kk + 2], H[4 * kk + 3], dx0, wo + (kk / 7) * 30720 + (kk % 7) * 2048, k != 0 || acc);
      }
    };
    auto mma = [&](float (&d)[32], int p, int k0, int k1, int acc) {
      wg_fence();
#pragma unroll
      for (int k = k0; k < k1; k++) step(d, p, k, acc);
      wg_commit();
    };
    auto send_peer = [&]() {
#pragma unroll
      for (int i = 0; i < 4; i++)
        asm volatile("st.async.shared::cluster.mbarrier::complete_tx::bytes.v4.b32 [%0], {%1,%2,%3,%4}, [%5];" ::"r"(peer + pbuf + i * 512),
                     "r"(pack_bf16(o[8 * i], o[8 * i + 1])), "r"(pack_bf16(o[8 * i + 2], o[8 * i + 3])), "r"(pack_bf16(o[8 * i + 4], o[8 * i + 5])),
                     "r"(pack_bf16(o[8 * i + 6], o[8 * i + 7])), "r"(peer + OFF_RBAR + wg * 8) : "memory");
    };
    auto recv_peer = [&](int k) {
      mbar_wait(sb + OFF_RBAR + wg * 8, k & 1);
#pragma unroll
      for (int i = 0; i < 4; i++) { const uint4 v = lds_u4(sb + pbuf + i * 512); pt[4 * i] = v.x; pt[4 * i + 1] = v.y; pt[4 * i + 2] = v.z; pt[4 * i + 3] = v.w; }
    };
    auto send_owner = [&](float (&d)[32], int k) {
#pragma unroll
      for (int i = 0; i < 4; i++) {
#pragma unroll
        for (int c = 4 * i; c < 4 * i + 4; c++) pt[c] = bf2_add(pt[c], pack_bf16(d[2 * c], d[2 * c + 1]));
        asm("lop3.b32 %0, %0, 1, %1, 0xb8;" : "+r"(pt[4 * i]) : "r"(tag));
        st_b128(psend + (((sp + 1 + k) & 3) * 6 + k) * 1024 + i * 32, pt[4 * i], pt[4 * i + 1], pt[4 * i + 2], pt[4 * i + 3]);
      }
      __syncwarp();
      credit();
    };
    auto load_fin = [&]() {
      mbar_wait(sb + OFF_LBAR, 1);
#pragma unroll
      for (int j = 0; j < 8; j++) {
        const uint4 v = lds_u4(sb + pbuf + 16384 + (j >> 2) * 16384 + (j & 3) * 512);
        fin[4 * j] = __uint_as_float(v.x); fin[4 * j + 1] = __uint_as_float(v.y); fin[4 * j + 2] = __uint_as_float(v.z); fin[4 * j + 3] = __uint_as_float(v.w);
      }
    };
    auto ldk = [&](int pos) { if (pos == K0P) recv_issue(sum, 0); if (pos == K1P) recv_issue(r0, 1); };
    auto arm = [&]() { if ((threadIdx.x & 127) == 0) mbar_expect_tx(sb + OFF_RBAR + wg * 8, 8192); };
#pragma unroll
    for (int p = 0; p < 8; p++) {
      if (p == 0) {
        TK(40);
        mbar_wait(fullb, full_par(24));
        TK(41);
        mma(o, 0, 0, 3, 0);
        wg_wait<1>(); release(5);
        gelu_b(0, 4);
        mma(o, 0, 3, 6, 0);
        bar_sync(1 + wg, 128);
        {
          const uint32_t ha = xw + ((lane >> 4) * 8 + (lane & 7)) * 128 + (((2 * w + ((lane >> 3) & 1)) ^ (lane & 7)) << 4);
#pragma unroll
          for (int kk = 0; kk < 8; kk++)
            asm volatile("ldmatrix.sync.aligned.m8n8.x4.trans.shared.b16 {%0,%1,%2,%3}, [%4];" : "=r"(hf[4 * kk]), "=r"(hf[4 * kk + 1]), "=r"(hf[4 * kk + 2]), "=r"(hf[4 * kk + 3])
                         : "r"(ha + (kk >> 2) * him + (kk & 3) * 2048) : "memory");
        }
        gelu_b(4, 10);
        TK(42);
        mbar_wait(fullb + 8, full_par(25));
        TK(43);
        mma(o, 0, 6, 10, 0);
        credit();
        gelu_b(10, 16);
        mma(o, 0, 10, 15, 0);
        gelu_b(16, 24);
        TK(44);
        mbar_wait(fullb + 16, full_par(26));
        TK(45);
        mma(o, 0, 15, 18, 0);
        gelu_b(24, 32);
        if (wg == 1) bar_sync(4, 256);
        mma(o, 0, 18, 22, 0);
      } else {
        TR(0);
        if (EW == 0 || (EW == 1 && (p & 1))) mbar_wait(sb + OFF_XFULL + 8 * p, 1);
        TR(1);
        bar_sync(3 + wg, 256);
        if (p < 7) mma(o, p, 0, 22, 0);
        else if (GAP == 0) mma(fin, p, 0, 22, 1);
        else {
          mma(fin, p, 0, GAP, 1);
          recv_peer(3);
          tag = lds_u(sb + OFF_EPOCH);
          mma(fin, p, GAP, 22, 1);
        }
      }
      if (p < 7 || wg == 0) bar_arrive(4 - wg, 256);
      TR(2);
      if (p != TP) TS(wg, 8 + p);
      if (p < 7 && (EW == 2 || (EW == 1 && (p & 1)))) mbar_wait(sb + OFF_XFULL + 8 * (p + 1), 1);
      ldk(10 * p);
      if (p == 2) asm volatile("st.shared.u32 [%0], %1;" ::"r"(sb + OFF_EPOCH + 4), "r"(ck) : "memory");
      if ((p & 1) == 0) {
        arm();
        if (p == 6) {
          mbar_wait(sb + OFF_EMPTY + 32, 0);
          tag = lds_u(sb + OFF_EPOCH);
          recv_check(sum, 0); recv_check(r0, 1);
#pragma unroll
          for (int i = 0; i < 16; i++) sum[i] = bf2_add(sum[i], r0[i]);
        }
        TR(3);
        mbar_wait(sb + OFF_KBAR + wg * 8, (p >> 1) & 1);
        TR(4);
      } else {
        if (p == 1 || (p == 7 && GAP == 0)) tag = lds_u(sb + OFF_EPOCH);
        TR(3);
        if (p < 7 || GAP == 0) recv_peer(p >> 1);
        TR(4);
        if (p == 7) {
          recv_check(r0, 2);
#pragma unroll
          for (int i = 0; i < 16; i++) sum[i] = bf2_add(sum[i], bf2_add(r0[i], pt[i]));
        }
      }
      if (p == FINP && !FINW) load_fin();
      ldk(10 * p + 1);
      TR(5);
      wg_wait<0>();
      TR(6);
      if (p < 5) release(p);
      if (p < 7) reg_fence(o); else reg_fence(fin);
      ldk(10 * p + 2);
      if ((p & 1) == 0) {
        if (p == 6) recv_issue(r0, 2);
        send_peer();
        if (p == FINP && FINW) load_fin();
      } else if (p < 7) {
        send_owner(o, p >> 1);
      }
      ldk(10 * p + 3);
      if (p == 2) {
#pragma unroll
        for (int h = 0; h < 2; h++) { rho[h] = __fdividef(2.f, 4.f + bf_lo(lds_h(sb + OFF_GS + (wg * 64 + w * 16 + gr + 8 * h) * 2))); pin(rho[h]); }
      }
      TR(7);
    }
    {
      TS(wg, 16);
      const uint32_t tb = sb + OFF_X + stage_off(0) + warp * 4096;
      const uint32_t ta = tb + gr * 256 + ((gr & 3) << 5) + q * 8;
      const uint32_t la = tb + (lane >> 3) * 256 + (((lane & 7) << 4) ^ ((lane >> 3) << 5));
      float* op = out + (size_t)(m * 128 + wg * 64 + (lane >> 4) * 16 + w * 4 + ((lane >> 3) & 1)) * DM + s * 64 + (lane & 7) * 4;
#pragma unroll
      for (int qq = 0; qq < 4; qq += QS) {
#pragma unroll
        for (int qt = qq; qt < qq + QS; qt++) {
          const int h = qt & 1, ch = qt >> 1;
#pragma unroll
          for (int j = 0; j < 4; j++) {
            const int i = ch * 8 + j * 2 + h;
            asm volatile("st.shared.v2.f32 [%0], {%1,%2};" ::"r"((ta ^ (j << 5)) + h * 2048 + ch * 128),
                         "f"((fin[2 * i] + bf_lo(sum[i])) * rho[h]), "f"((fin[2 * i + 1] + bf_hi(sum[i])) * rho[h]) : "memory");
          }
        }
        __syncwarp();
#pragma unroll
        for (int qt = qq; qt < qq + QS; qt++) {
          const int h = qt & 1, ch = qt >> 1;
#pragma unroll
          for (int r = 0; r < 2; r++)
            *reinterpret_cast<uint4*>(op + (r * 32 + h * 2) * DM + ch * 32) = lds_u4(la + (h * 2 + r) * 1024 + ch * 128);
        }
      }
      if (threadIdx.x == 128) g_epoch[b] = tag;
      TS(wg, 17); TG(wg); TRD(); TDUMP();
    }
  } else {
    asm volatile("setmaxnreg.dec.sync.aligned.u32 56;");
    int wsel = warp;
    asm("" : "+r"(wsel));
    if (wsel > 8) {
      if (warp != 11) {
        const int t = threadIdx.x - 288;
        unsigned par;
        asm volatile("ld.relaxed.gpu.global.u32 %0, [%1];" : "=r"(par) : "l"(g_epoch + b) : "memory");
        const float pr = bf_ld(lam_re + s * 64 + t), pi = bf_ld(lam_im + s * 64 + t), pd = bf_ld(log_dt + s * 64 + t);
        asm volatile("barrier.cluster.wait.aligned;" ::: "memory");
        par = __shfl_sync(0xffffffffu, (par + 1) & 1, 0);
        cplx l64 = make_lam(pr, pi, pd);
        {
          const float inv = __fdividef(1.f, fmaf(pr, pr, pi * pi));
          const cplx cf = cmul(cplx{l64.re - 1.f, l64.im}, cplx{pr * inv, -pi * inv});
          asm volatile("st.shared.v4.f32 [%0], {%1,%2,%3,%4};" ::"r"(sb + OFF_LC + t * 16), "f"(l64.re), "f"(l64.im), "f"(cf.re), "f"(cf.im) : "memory");
          mbar_arrive(sb + OFF_LBAR);
        }
#pragma unroll
        for (int i = 0; i < 6; i++) l64 = cmul(l64, l64);
        cplx l128 = cmul(l64, l64);
        pin(l128.re); pin(l128.im);
        uint32_t vr[15], vi[15];
#pragma unroll
        for (int i = 0; i < 15; i++) { vr[i] = par; vi[i] = 0; pin(vr[i]); pin(vi[i]); }
        mbar_wait(sb + OFF_GBAR, 0);
        const float2 e0 = lds_f2(sb + OFF_CARRY + t * 8), e1 = lds_f2(sb + OFF_CARRY + 512 + t * 8);
        float2* eb = g_end + s * 1024 + t;
        {
          const cplx e = cfma(l64, cplx{e0.x, e0.y}, cplx{e1.x, e1.y});
          const unsigned long long v = ((unsigned long long)__float_as_uint(e.im) << 32) | ((__float_as_uint(e.re) & ~1u) | par);
          asm volatile("st.relaxed.gpu.global.b64 [%0], %1;" ::"l"(eb + m * 64), "l"(v) : "memory");
        }
        if (t == 0) TS(3, 1);
        cplx S = {0.f, 0.f};
        {
          if (LBD) __nanosleep(LBD);
          const float2* e15 = eb + (m - 15) * 64;
          int tries = 0;
          bool bad;
#pragma unroll 1
          do {
#pragma unroll
            for (int i = 0; i < 15; i++)
              asm volatile("{.reg .pred p; .reg .b64 v; mov.b64 v, {%0,%1}; setp.ge.s32 p, %3, %4; @p ld.relaxed.gpu.global.b64 v, [%2]; mov.b64 {%0,%1}, v;}"
                           : "+r"(vr[i]), "+r"(vi[i]) : "l"(e15 + i * 64), "r"(m), "r"(15 - i) : "memory");
            uint32_t x = vr[0] ^ par;
#pragma unroll
            for (int i = 1; i < 15; i++) asm("lop3.b32 %0, %0, %1, %2, 0xf6;" : "+r"(x) : "r"(vr[i]), "r"(par));
            bad = __any_sync(0xffffffffu, x & 1);
          } while (bad && ++tries < 200000);
          if (t == 0) TS(3, 2);
          S = cplx{__uint_as_float(vr[0]), __uint_as_float(vi[0])};
#pragma unroll
          for (int i = 1; i < 15; i++) S = cfma(l128, S, cplx{__uint_as_float(vr[i]), __uint_as_float(vi[i])});
        }
        const cplx S1 = cfma(l64, S, cplx{e0.x, e0.y});
        asm volatile("st.shared.v2.f32 [%0], {%1,%2};" ::"r"(sb + OFF_CARRY + t * 8), "f"(S.re), "f"(S.im) : "memory");
        asm volatile("st.shared.v2.f32 [%0], {%1,%2};" ::"r"(sb + OFF_CARRY + 512 + t * 8), "f"(S1.re), "f"(S1.im) : "memory");
        mbar_arrive(sb + OFF_CBAR);
        if (t == 0) TS(3, 3);
        mbar_wait(sb + OFF_CBAR, 0);
        const int gr = lane >> 2, q = lane & 3;
        float2 db[8];
#pragma unroll
        for (int j = 0; j < 8; j++) db[j] = lds_f2(sb + OFF_DB + j * 32 + q * 8);
        mbar_wait(sb + OFF_XFULL + 16, 1);
        mbar_wait(sb + OFF_EMPTY, 0);
#pragma unroll 1
        for (int cw = warp - 9; cw < 8; cw += 2) {
          const float r0 = 0.5f * bf_lo(lds_h(sb + OFF_GS + (cw * 16 + gr) * 2)), r1 = 0.5f * bf_lo(lds_h(sb + OFF_GS + (cw * 16 + gr) * 2 + 16));
          const uint32_t xa = sb + OFF_X + (1 + rank) * 16384 + (cw * 16 + (lane & 15)) * 128 + (((lane >> 4) ^ (lane & 7)) << 4);
          uint32_t xv[16];
#pragma unroll
          for (int i = 0; i < 4; i++)
            asm volatile("ldmatrix.sync.aligned.m8n8.x4.shared.b16 {%0,%1,%2,%3}, [%4];" : "=r"(xv[4 * i]), "=r"(xv[4 * i + 1]), "=r"(xv[4 * i + 2]), "=r"(xv[4 * i + 3])
                         : "r"(xa ^ (i << 5)) : "memory");
          __syncwarp();
#pragma unroll
          for (int j = 0; j < 8; j++) {
            const uint32_t x0 = bf2_mul(xv[2 * j], __float_as_uint(db[j].x)), x1 = bf2_mul(xv[2 * j + 1], __float_as_uint(db[j].x));
            pin(db[j].y);
            const float bl = bf_lo(__float_as_uint(db[j].y)), bh = bf_hi(__float_as_uint(db[j].y));
            asm volatile("st.shared.v4.f32 [%0], {%1,%2,%3,%4};" ::"r"(sb + OFF_X + 16384 + (j >> 2) * 16384 + cw * 2048 + (j & 3) * 512 + lane * 16), "f"(fmaf(bf_lo(x0), r0, bl)),
                         "f"(fmaf(bf_hi(x0), r0, bh)), "f"(fmaf(bf_lo(x1), r1, bl)), "f"(fmaf(bf_hi(x1), r1, bh)) : "memory");
          }
        }
        mbar_arrive(sb + OFF_LBAR);
        if (t == 0) TS(3, 5);
      } else {
        if (lane == 0) TG(2);
        const uint4* gwp = reinterpret_cast<const uint4*>(gate_w) + (lane & 7);
        uint4 gw[4];
#pragma unroll
        for (int i = 0; i < 4; i++) gw[i] = __ldg(gwp + i * 8);
        unsigned par;
        asm volatile("ld.relaxed.gpu.global.u32 %0, [%1];" : "=r"(par) : "l"(g_epoch + b) : "memory");
        const uint32_t dk = __ldg(reinterpret_cast<const uint32_t*>(dskip + s * 64) + lane), bb = __ldg(reinterpret_cast<const uint32_t*>(b2 + s * 64) + lane);
        asm volatile("barrier.cluster.wait.aligned;" ::: "memory");
        const int row = s * 16 + (lane >> 3);
        const uint32_t xr0 = sb + OFF_X + row * 128 + (((lane & 7) ^ (row & 7)) << 4), xr1 = (xr0 + 512) ^ 64;
        float z[4] = {0.f, 0.f, 0.f, 0.f};
#pragma unroll
        for (int kb = 0; kb < 8; kb++) {
          const uint32_t wv[4] = {gw[kb & 3].x, gw[kb & 3].y, gw[kb & 3].z, gw[kb & 3].w};
          if (kb < 4) gw[kb] = __ldg(gwp + (kb + 4) * 8);
          mbar_wait(sb + OFF_XFULL + 8 * kb, 0);
          if ((PF & 2) && kb == PFK && elect_one()) {
            l2_prefetch(pf_w1 + b * 7168, 14336);
            l2_prefetch(pf_cre + b * 2048, 4096);
            l2_prefetch(pf_cim + b * 2048, 4096);
            l2_prefetch(pf_w2 + b * 7168, 14336);
          }
          const uint32_t xo = ((kb + xrot) & 7) * 16384;
#pragma unroll
          for (int r = 0; r < 4; r++) {
            const uint4 a = lds_u4(((r & 1) ? xr1 : xr0) + xo + (r >> 1) * 1024);
            const uint32_t p = bf2_fma(a.w, wv[3], bf2_fma(a.z, wv[2], bf2_fma(a.y, wv[1], bf2_mul(a.x, wv[0]))));
            z[r] += bf_lo(p); z[r] += bf_hi(p);
          }
        }
        if (lane == 0) asm volatile("st.shared.u32 [%0], %1;" ::"r"(sb + OFF_EPOCH), "r"(par + 1) : "memory");
        par = (par + 1) & 1;
        {
          float y0 = (lane & 4) ? z[1] : z[0], y1 = (lane & 4) ? z[3] : z[2];
          y0 += __shfl_xor_sync(0xffffffffu, (lane & 4) ? z[0] : z[1], 4);
          y1 += __shfl_xor_sync(0xffffffffu, (lane & 4) ? z[2] : z[3], 4);
          float zz = (lane & 2) ? y1 : y0;
          zz += __shfl_xor_sync(0xffffffffu, (lane & 2) ? y0 : y1, 2);
          zz += __shfl_xor_sync(0xffffffffu, zz, 1);
          const float rho = 4.f * expf(zz > 40.f ? 40.f : zz);
          if ((lane & 1) == 0)
            asm volatile("st.relaxed.gpu.global.u32 [%0], %1;" ::"l"(g_gate + m * 128 + row + (lane & 4) + (lane & 2) * 4), "r"((__float_as_uint(rho) & ~1u) | par) : "memory");
        }
        if ((PF & 8) && elect_one()) {
          l2_prefetch(pf_w2 + b * 7168, 14336);
          l2_prefetch(pf_cre + b * 2048, 4096);
          l2_prefetch(pf_cim + b * 2048, 4096);
        }
        if (lane == 0) TS(3, 0);
        mbar_wait(sb + OFF_GBAR, 0);
        asm volatile("st.shared.v2.u32 [%0], {%1,%2};" ::"r"(sb + OFF_DB + lane * 8), "r"(dk), "r"(bf2_add(bb, bb)) : "memory");
        uint32_t g0, g1, g2, g3;
        int tries = 0;
#pragma unroll 1
        do {
          asm volatile("ld.relaxed.gpu.global.v4.u32 {%0,%1,%2,%3}, [%4];" : "=r"(g0), "=r"(g1), "=r"(g2), "=r"(g3) : "l"(g_gate + m * 128 + lane * 4) : "memory");
        } while ((((g0 ^ par) | (g1 ^ par) | (g2 ^ par) | (g3 ^ par)) & 1) && ++tries < 200000);
        asm volatile("st.shared.v2.u32 [%0], {%1,%2};" ::"r"(sb + OFF_GS + lane * 8), "r"(pack_bf16(__uint_as_float(g0), __uint_as_float(g1))),
                     "r"(pack_bf16(__uint_as_float(g2), __uint_as_float(g3))) : "memory");
        const uint32_t gt = sb + OFF_GT + (lane >> 4) * 128 + (lane & 1) * 64 + ((lane >> 1) & 7) * 4;
        asm volatile("st.shared.u32 [%0], %1;" ::"r"(gt), "r"(pack_bf16(__uint_as_float(g0), __uint_as_float(g1))) : "memory");
        asm volatile("st.shared.u32 [%0], %1;" ::"r"(gt + 32), "r"(pack_bf16(__uint_as_float(g2), __uint_as_float(g3))) : "memory");
        mbar_arrive(sb + OFF_CBAR);
        if (lane == 0) TS(3, 4);
      }
    } else {
      asm volatile("barrier.cluster.wait.aligned;" ::: "memory");
      if (elect_one()) {
        TS(2, 1);
        const uint32_t t0 = clock();
#pragma unroll 1
        for (int u = W0; u < 8; u++) {
          if (u >= 1) while ((uint32_t)clock() - t0 < D0 + (u - 1) * D1) {}
          mbar_expect_tx(sb + OFF_XFULL + 8 * u, 32768);
          tma5d_mc(sb + OFF_X + ((u + xrot) & 7) * 16384 + rank * 8192, &maps.x, u * 64, 2 * m + rank, sb + OFF_XFULL + 8 * u);
          const int sl = u < 6 ? u : u - 6;
          if (u >= 6) mbar_wait(sb + OFF_EMPTY + 8 * sl, 0);
          tma2d(sb + OFF_RING + sl * 16384, &maps.bre, u * 64, s * 64, sb + OFF_XFULL + 8 * u);
          tma2d(sb + OFF_RING + sl * 16384 + 8192, &maps.bim, u * 64, s * 64, sb + OFF_XFULL + 8 * u);
          if (u == 2) asm volatile("prefetch.tensormap [%0];" ::"l"(&maps.w1b) : "memory");
        }
        TS(2, 5);
        int slot = 2; uint32_t ph = 0;
#pragma unroll 1
        for (int u = 8; u < 24; u++) {
          const uint32_t fb = sb + OFF_FULL + 8 * slot, dst = sb + OFF_RING + slot * 16384;
          mbar_wait(sb + OFF_EMPTY + 8 * slot, ph);
          TS2(0, u);
          if (u < 16) {
            mbar_expect_tx(fb, 12288);
            tma3d(dst, &maps.w1b, 0, (u - 8) * 64, s * 7, fb);
            if (TMP2 && u < 12) asm volatile("prefetch.tensormap [%0];" ::"l"(&maps.w1a + (u - 8)) : "memory");
          } else {
            mbar_expect_tx(fb, 16384);
            tma2d(dst, &maps.w1a, s * 224 + 96, ((u - xrot) & 7) * 64, fb);
            tma2d(dst + 8192, &maps.w1a, s * 224 + 160, ((u - xrot) & 7) * 64, fb);
          }
          if (++slot == NSLOT) { slot = 0; ph ^= 1; }
        }
#pragma unroll 1
        for (int j = 0; j < 3; j++) {
          const uint32_t fb = sb + OFF_FULL + 8 * j, dst = sb + OFF_X + stage_off(0);
          const int c = ((sp + 1) & 3) * 128 + ((rank ^ 1) << 6);
          mbar_wait(sb + OFF_EMPTY + 8 + 8 * j, 1);
          mbar_expect_tx(fb, j == 1 ? 16384 : 14336);
          if (j == 1) {
            tma2d(dst + 14336, &maps.cre, s * 64, c, fb);
            tma2d(dst + 22528, &maps.cim, s * 64, c, fb);
          } else {
            tma2d(dst + j * 15360, &maps.w2, c, s * 224 + j * 56, fb);
          }
        }
#pragma unroll 1
        for (int p = 1; p < 8; p++) {
          const int c = ((sp + 1 + (p >> 1)) & 3) * 128 + (((rank ^ p ^ 1) & 1) << 6);
          const uint32_t fb = sb + OFF_XFULL + 8 * p, dst = sb + OFF_X + stage_off(p);
          if (p == 2 || p > 3) mbar_wait(sb + OFF_EMPTY + (p == 2 ? 40 : (p - 4) * 8), p == 2);
          TS2(0, 32 + p);
          mbar_expect_tx(fb, 45056);
          tma2d(dst, &maps.w2, c, s * 224, fb);
          tma2d(dst + 14336, &maps.cre, s * 64, c, fb);
          tma2d(dst + 22528, &maps.cim, s * 64, c, fb);
          tma2d(dst + 30720, &maps.w2, c, s * 224 + 112, fb);
        }
        TS(2, 2);
      }
    }
  }
}

typedef CUresult (*EncFn)(CUtensorMap*, CUtensorMapDataType, cuuint32_t, void*, const cuuint64_t*, const cuuint64_t*, const cuuint32_t*,
                          const cuuint32_t*, CUtensorMapInterleave, CUtensorMapSwizzle, CUtensorMapL2promotion, CUtensorMapFloatOOBfill);

void encode(EncFn f, CUtensorMap* mp, const void* p, int rank, const cuuint64_t* dims, const cuuint64_t* strides, const cuuint32_t* box, CUtensorMapSwizzle sw) {
  cuuint32_t es[5] = {1, 1, 1, 1, 1};
  f(mp, CU_TENSOR_MAP_DATA_TYPE_BFLOAT16, rank, const_cast<void*>(p), dims, strides, box, es, CU_TENSOR_MAP_INTERLEAVE_NONE, sw,
    CU_TENSOR_MAP_L2_PROMOTION_L2_128B, CU_TENSOR_MAP_FLOAT_OOB_FILL_NONE);
}

}

extern "C" void kernel_launch(void* const* d_in, const int* in_sizes, int n_in, void* d_out, int out_size) {
  typedef const __nv_bfloat16* bp;
  bp x = (bp)d_in[0], lre = (bp)d_in[1], lim = (bp)d_in[2], bre = (bp)d_in[3], bim = (bp)d_in[4], cre = (bp)d_in[5], cim = (bp)d_in[6],
     ldt = (bp)d_in[7], dsk = (bp)d_in[8], w1 = (bp)d_in[10], b1 = (bp)d_in[11], w2 = (bp)d_in[12], b2 = (bp)d_in[13], gw = (bp)d_in[14];
  static EncFn enc = nullptr;
  if (!enc) {
    void* f = nullptr;
    cudaDriverEntryPointQueryResult qr;
    cudaGetDriverEntryPoint("cuTensorMapEncodeTiled", &f, cudaEnableDefault, &qr);
    enc = (EncFn)f;
    cudaFuncSetAttribute(fused_kernel, cudaFuncAttributeMaxDynamicSharedMemorySize, SMEM_BYTES);
  }
  Maps maps;
  {
    cuuint64_t d[5] = {DM, 2, 4, 8, SEQ / 64}, st[4] = {DM * 2, 16 * DM * 2, 2 * DM * 2, 64 * DM * 2};
    cuuint32_t bx[5] = {64, 2, 4, 8, 1};
    encode(enc, &maps.x, x, 5, d, st, bx, CU_TENSOR_MAP_SWIZZLE_128B);
  }
  {
    cuuint64_t d[2] = {DM, DM}, st[1] = {DM * 2};
    cuuint32_t bx[2] = {64, 64};
    encode(enc, &maps.bre, bre, 2, d, st, bx, CU_TENSOR_MAP_SWIZZLE_128B);
    encode(enc, &maps.bim, bim, 2, d, st, bx, CU_TENSOR_MAP_SWIZZLE_128B);
    encode(enc, &maps.cre, cre, 2, d, st, bx, CU_TENSOR_MAP_SWIZZLE_128B);
    encode(enc, &maps.cim, cim, 2, d, st, bx, CU_TENSOR_MAP_SWIZZLE_128B);
  }
  {
    cuuint64_t d[2] = {FF, DM}, st[1] = {FF * 2};
    cuuint32_t bx[2] = {64, 64};
    encode(enc, &maps.w1a, w1, 2, d, st, bx, CU_TENSOR_MAP_SWIZZLE_128B);
    cuuint64_t d3[3] = {32, DM, FF / 32}, st3[2] = {FF * 2, 64};
    cuuint32_t bx3[3] = {32, 64, 3};
    encode(enc, &maps.w1b, w1, 3, d3, st3, bx3, CU_TENSOR_MAP_SWIZZLE_64B);
  }
  {
    cuuint64_t d[2] = {DM, FF}, st[1] = {DM * 2};
    cuuint32_t bx[2] = {64, 112};
    encode(enc, &maps.w2, w2, 2, d, st, bx, CU_TENSOR_MAP_SWIZZLE_128B);
  }
  fused_kernel<<<128, 384, SMEM_BYTES>>>(lre, lim, ldt, dsk, b1, b2, gw, w1, w2, cre, cim, (float*)d_out, maps);
}
```

```cpp
#include <cuda_runtime.h>
#include <cuda_bf16.h>
#include <cuda.h>
#include <stdint.h>

#define MAP 1
#define D0 200
#define D1 480
#define PF 4
#define PFK 5
#define GELUP 1
#define EW 2
#define K1E 1
#define K2E 0
#define QS 1
#define K2G 4
#define FINP 4
#define LBD 300
#define PFS 32
#define SB0 2
#define PFD 2
#define HOLD 0
#define GAP 14
#define FINW 0
#define K0P 33
#define K1P 53
#define TMP2 1
#define W0 1
#define LCK 4
#define TOKA 0
#define TOKB 2
#define TOKD 0
#define TKT 999
#define AV 3
#define QK 4
#define TCUT {1, 6, 6, 11, 16}
#define SCUT {0, 0, 0, 0, 0, 0, 8, 16, 24}
#define PV 0
#define KCUT {3, 5, 8, 10, 13, 15, 17, 19}
#define E1L 1
#define TP 9
#define TW 0

namespace {

constexpr int SEQ = 2048, DM = 512, FF = 1792;
constexpr int NSLOT = 6;
constexpr uint32_t OFF_X = 0, OFF_RING = 131072, OFF_MISC = 229376;
constexpr uint32_t OFF_XFULL = OFF_MISC, OFF_FULL = OFF_XFULL + 64, OFF_RBAR = OFF_FULL + 48, OFF_EMPTY = OFF_RBAR + 16, OFF_KBAR = OFF_EMPTY + 48,
                   OFF_GBAR = OFF_KBAR + 16, OFF_LBAR = OFF_GBAR + 8, OFF_CBAR = OFF_LBAR + 8, OFF_EPOCH = OFF_CBAR + 8;
constexpr uint32_t OFF_LC = OFF_MISC + 256;
constexpr uint32_t OFF_GS = OFF_LC;
constexpr uint32_t OFF_GT = OFF_LC + 256;
constexpr uint32_t OFF_DB = OFF_LC + 512;
constexpr uint32_t OFF_CARRY = OFF_LC + 1024;
constexpr uint32_t OFF_DBG = OFF_CARRY + 1024;
constexpr uint32_t SMEM_BYTES = OFF_DBG + 768;
static_assert(SMEM_BYTES <= 232448, "smem");

struct Maps { CUtensorMap x, bre, bim, w1b, w1a, w2, cre, cim; };
__host__ __device__ constexpr uint32_t stage_off(int p) { return 49152 + 45056 * (((p >> 1) & 1) + 2 * (p & 1)); }

__host__ __device__ constexpr uint32_t full_par(int u) { return ((u - 8) / 6 + (u % 6 == 0)) & 1; }

__device__ uint4 g_part[16 * 8 * 3 * 1024];
__device__ float2 g_end[8 * 16 * 64];
__device__ unsigned g_gate[SEQ];
__device__ unsigned g_epoch[128];
#define TG(role) do {} while (0)
#define TS2(role, i) do {} while (0)
#define TS(role, i) do {} while (0)
#define TDUMP() do {} while (0)
#define TR(i) do {} while (0)
#define TK(i) do {} while (0)
#define TRD() do {} while (0)

__device__ __forceinline__ void mbar_init(uint32_t bar, uint32_t cnt) { asm volatile("mbarrier.init.shared::cta.b64 [%0], %1;" ::"r"(bar), "r"(cnt)); }
__device__ __forceinline__ void mbar_expect_tx(uint32_t bar, uint32_t bytes) { asm volatile("mbarrier.arrive.expect_tx.shared::cta.b64 _, [%0], %1;" ::"r"(bar), "r"(bytes) : "memory"); }
__device__ __forceinline__ void mbar_arrive(uint32_t bar) { asm volatile("mbarrier.arrive.shared::cta.b64 _, [%0];" ::"r"(bar) : "memory"); }
__device__ __forceinline__ void mbar_arrive_cl(uint32_t cbar) { asm volatile("mbarrier.arrive.shared::cluster.b64 _, [%0];" ::"r"(cbar) : "memory"); }
__device__ __forceinline__ void mbar_wait(uint32_t bar, uint32_t parity) {
  asm volatile(
      "{\n.reg .pred p;\n.reg .u32 c;\n"
      "mbarrier.try_wait.parity.shared::cta.b64 p, [%0], %1;\n"
      "@p bra.uni LAB_DONE;\n"
      "mov.u32 c, 0;\n"
      "LAB_WAIT:\n"
      "mbarrier.try_wait.parity.shared::cta.b64 p, [%0], %1;\n"
      "@p bra.uni LAB_DONE;\n"
      "add.u32 c, c, 1;\nsetp.lt.u32 p, c, 200000;\n@p bra.uni LAB_WAIT;\n"
      "LAB_DONE:\n}" ::"r"(bar), "r"(parity) : "memory");
}
__device__ __forceinline__ void tma2d(uint32_t dst, const CUtensorMap* m, int c0, int c1, uint32_t bar) {
  asm volatile("cp.async.bulk.tensor.2d.shared::cluster.global.mbarrier::complete_tx::bytes [%0], [%1, {%3,%4}], [%2];"
               ::"r"(dst), "l"(m), "r"(bar), "r"(c0), "r"(c1) : "memory");
}
__device__ __forceinline__ void tma3d(uint32_t dst, const CUtensorMap* m, int c0, int c1, int c2, uint32_t bar) {
  asm volatile("cp.async.bulk.tensor.3d.shared::cluster.global.mbarrier::complete_tx::bytes [%0], [%1, {%3,%4,%5}], [%2];"
               ::"r"(dst), "l"(m), "r"(bar), "r"(c0), "r"(c1), "r"(c2) : "memory");
}
__device__ __forceinline__ void tma5d(uint32_t dst, const CUtensorMap* m, int c0, int c4, uint32_t bar) {
  asm volatile("cp.async.bulk.tensor.5d.shared::cluster.global.mbarrier::complete_tx::bytes [%0], [%1, {%3,%5,%5,%5,%4}], [%2];"
               ::"r"(dst), "l"(m), "r"(bar), "r"(c0), "r"(c4), "r"(0) : "memory");
}
__device__ __forceinline__ void tma5d_mc(uint32_t dst, const CUtensorMap* m, int c0, int c4, uint32_t bar) {
  asm volatile("cp.async.bulk.tensor.5d.shared::cluster.global.mbarrier::complete_tx::bytes.multicast::cluster [%0], [%1, {%3,%5,%5,%5,%4}], [%2], %6;"
               ::"r"(dst), "l"(m), "r"(bar), "r"(c0), "r"(c4), "r"(0), "h"((uint16_t)3) : "memory");
}
__device__ __forceinline__ void l2_prefetch(const void* p, uint32_t bytes) { asm volatile("cp.async.bulk.prefetch.L2.global [%0], %1;" ::"l"(p), "r"(bytes) : "memory"); }
__device__ __forceinline__ bool elect_one() {
  uint32_t pred;
  asm volatile("{.reg .pred P; elect.sync _|P, 0xffffffff; selp.u32 %0, 1, 0, P;}" : "=r"(pred));
  return pred != 0;
}
__device__ __forceinline__ void wg_fence() { asm volatile("wgmma.fence.sync.aligned;" ::: "memory"); }
__device__ __forceinline__ void wg_commit() { asm volatile("wgmma.commit_group.sync.aligned;" ::: "memory"); }
template <int N> __device__ __forceinline__ void wg_wait() { asm volatile("wgmma.wait_group.sync.aligned %0;" ::"n"(N) : "memory"); }
__device__ __forceinline__ void pin(float& a) { asm volatile("" : "+f"(a)::"memory"); }
__device__ __forceinline__ void pin(uint32_t& a) { asm volatile("" : "+r"(a)::"memory"); }
template <int N> __device__ __forceinline__ void reg_fence(float (&d)[N]) {
#pragma unroll
  for (int i = 0; i < N; i++) pin(d[i]);
}
__device__ __forceinline__ void bar_sync(int id, int n) { asm volatile("bar.sync %0, %1;" ::"r"(id), "r"(n) : "memory"); }
__device__ __forceinline__ void bar_arrive(int id, int n) { asm volatile("bar.arrive %0, %1;" ::"r"(id), "r"(n) : "memory"); }
constexpr uint32_t DH128 = (1024 >> 4) | (1u << 30), DH64 = (512 >> 4) | (2u << 30);
__host__ __device__ constexpr uint32_t lbo(uint32_t bytes) { return (bytes >> 4) << 20; }
__device__ __forceinline__ uint32_t pack_bf16(float lo, float hi) { uint32_t r; asm("cvt.rn.bf16x2.f32 %0, %1, %2;" : "=r"(r) : "f"(hi), "f"(lo)); return r; }
__device__ __forceinline__ float bf_lo(uint32_t v) { return __uint_as_float(v << 16); }
__device__ __forceinline__ float bf_hi(uint32_t v) { return __uint_as_float(v & 0xffff0000u); }
__device__ __forceinline__ float bf_ld(const __nv_bfloat16* p) { return __bfloat162float(__ldg(p)); }
__device__ __forceinline__ uint32_t late16(uint32_t bar) {
  uint32_t r;
  asm volatile("{.reg .pred p; mbarrier.test_wait.parity.shared::cta.b64 p, [%1], 0; selp.u32 %0, 16, 0, p;}" : "=r"(r) : "r"(bar) : "memory");
  return r;
}
__device__ __forceinline__ float2 lds_f2(uint32_t a) { float2 v; asm volatile("ld.shared.v2.f32 {%0,%1}, [%2];" : "=f"(v.x), "=f"(v.y) : "r"(a)); return v; }
__device__ __forceinline__ uint32_t lds_h(uint32_t a) { uint32_t v; asm volatile("ld.shared.u16 %0, [%1];" : "=r"(v) : "r"(a)); return v; }
__device__ __forceinline__ uint32_t lds_u(uint32_t a) { uint32_t v; asm volatile("ld.shared.u32 %0, [%1];" : "=r"(v) : "r"(a)); return v; }
__device__ __forceinline__ uint4 lds_u4(uint32_t a) { uint4 v; asm volatile("ld.shared.v4.u32 {%0,%1,%2,%3}, [%4];" : "=r"(v.x), "=r"(v.y), "=r"(v.z), "=r"(v.w) : "r"(a)); return v; }
__device__ __forceinline__ void st_b128(uint4* p, uint32_t a, uint32_t b, uint32_t c, uint32_t d) {
  asm volatile("st.relaxed.gpu.global.v4.b32 [%0], {%1,%2,%3,%4};" ::"l"(p), "r"(a), "r"(b), "r"(c), "r"(d) : "memory");
}
__device__ __forceinline__ void ld_b128(const uint4* p, uint32_t& a, uint32_t& b, uint32_t& c, uint32_t& d) {
  asm volatile("{.reg .b64 l, h; .reg .b128 v; ld.relaxed.gpu.global.b128 v, [%4]; mov.b128 {l,h}, v; mov.b64 {%0,%1}, l; mov.b64 {%2,%3}, h;}"
               : "=r"(a), "=r"(b), "=r"(c), "=r"(d) : "l"(p) : "memory");
}
__device__ __forceinline__ float tanh_fast(float x) { float y; asm("tanh.approx.f32 %0, %1;" : "=f"(y) : "f"(x)); return y; }
__device__ __forceinline__ float gelu2(float v) {
  float p = fmaf(v * v, 0.0356774081363f, 0.7978845608029f);
  return fmaf(v, tanh_fast(v * p), v);
}
__device__ __forceinline__ void sched_fence(uint32_t& ck) { asm volatile("{.reg .b32 c; mov.u32 c, %%clock; xor.b32 %0, %0, c;}" : "+r"(ck)::"memory"); }
__device__ __forceinline__ uint32_t bf2_mul(uint32_t a, uint32_t b) { uint32_t r; asm("mul.rn.bf16x2 %0, %1, %2;" : "=r"(r) : "r"(a), "r"(b)); return r; }
__device__ __forceinline__ uint32_t bf2_add(uint32_t a, uint32_t b) { uint32_t r; asm("add.rn.bf16x2 %0, %1, %2;" : "=r"(r) : "r"(a), "r"(b)); return r; }
__device__ __forceinline__ uint32_t bf2_fma(uint32_t a, uint32_t b, uint32_t c) { uint32_t r; asm("fma.rn.bf16x2 %0, %1, %2, %3;" : "=r"(r) : "r"(a), "r"(b), "r"(c)); return r; }
__device__ __forceinline__ uint32_t gelu2_pair(float a, float b) {
  const uint32_t v = pack_bf16(a, b);
  uint32_t t;
  asm("tanh.approx.bf16x2 %0, %1;" : "=r"(t) : "r"(bf2_fma(v, bf2_fma(bf2_mul(v, v), 0x3d123d12u, 0xbe4fbe4fu), v)));
  return bf2_fma(v, t, v);
}
struct cplx { float re, im; };
__device__ __forceinline__ cplx cmul(cplx a, cplx b) { return {fmaf(a.re, b.re, -a.im * b.im), fmaf(a.re, b.im, a.im * b.re)}; }
__device__ __forceinline__ cplx cfma(cplx a, cplx b, cplx c) {
  return {fmaf(a.re, b.re, fmaf(-a.im, b.im, c.re)), fmaf(a.re, b.im, fmaf(a.im, b.re, c.im))};
}
__device__ __forceinline__ cplx make_lam(float lre, float lim, float ldt) {
  float dt = __bfloat162float(__float2bfloat16_rn(expf(ldt)));
  float mag = expf(dt * lre), sn, cs;
  sincospif(dt * lim * 0.31830988618379067f, &sn, &cs);
  return {mag * cs, mag * sn};
}

template<int TA,int TB,uint32_t AH,uint32_t BH> __device__ __forceinline__ void wgmma_n64_ss(float (&d)[32], uint32_t al, uint32_t ao, uint32_t bl, uint32_t bo, int scale_d){
  asm volatile("{.reg .pred p; .reg .b32 t, v; .reg .b64 da, db; setp.ne.b32 p, %36, 0; add.u32 t, %32, %33; mov.b64 da, {t, %39}; add.u32 v, %34, %35; mov.b64 db, {v, %40};\n"
   "wgmma.mma_async.sync.aligned.m64n64k16.f32.bf16.bf16 {%0,%1,%2,%3,%4,%5,%6,%7,%8,%9,%10,%11,%12,%13,%14,%15,%16,%17,%18,%19,%20,%21,%22,%23,%24,%25,%26,%27,%28,%29,%30,%31}, da, db, p, 1, 1, %37, %38;}"
   : "+f"(d[0]),"+f"(d[1]),"+f"(d[2]),"+f"(d[3]),"+f"(d[4]),"+f"(d[5]),"+f"(d[6]),"+f"(d[7]),"+f"(d[8]),"+f"(d[9]),"+f"(d[10]),"+f"(d[11]),"+f"(d[12]),"+f"(d[13]),"+f"(d[14]),"+f"(d[15]),"+f"(d[16]),"+f"(d[17]),"+f"(d[18]),"+f"(d[19]),"+f"(d[20]),"+f"(d[21]),"+f"(d[22]),"+f"(d[23]),"+f"(d[24]),"+f"(d[25]),"+f"(d[26]),"+f"(d[27]),"+f"(d[28]),"+f"(d[29]),"+f"(d[30]),"+f"(d[31])
   : "r"(al),"r"(ao >> 4),"r"(bl),"r"(bo >> 4),"r"(scale_d),"n"(TA),"n"(TB),"n"(AH),"n"(BH));
}
template<int TB,uint32_t BH,int SA=1> __device__ __forceinline__ void wgmma_n64_rs(float (&d)[32], uint32_t a0,uint32_t a1,uint32_t a2,uint32_t a3, uint32_t bl, uint32_t bo, int scale_d){
  asm volatile("{.reg .pred p; .reg .b32 t; .reg .b64 db; setp.ne.b32 p, %38, 0; add.u32 t, %36, %37; mov.b64 db, {t, %40};\n"
   "wgmma.mma_async.sync.aligned.m64n64k16.f32.bf16.bf16 {%0,%1,%2,%3,%4,%5,%6,%7,%8,%9,%10,%11,%12,%13,%14,%15,%16,%17,%18,%19,%20,%21,%22,%23,%24,%25,%26,%27,%28,%29,%30,%31}, {%32,%33,%34,%35}, db, p, %41, 1, %39;}"
   : "+f"(d[0]),"+f"(d[1]),"+f"(d[2]),"+f"(d[3]),"+f"(d[4]),"+f"(d[5]),"+f"(d[6]),"+f"(d[7]),"+f"(d[8]),"+f"(d[9]),"+f"(d[10]),"+f"(d[11]),"+f"(d[12]),"+f"(d[13]),"+f"(d[14]),"+f"(d[15]),"+f"(d[16]),"+f"(d[17]),"+f"(d[18]),"+f"(d[19]),"+f"(d[20]),"+f"(d[21]),"+f"(d[22]),"+f"(d[23]),"+f"(d[24]),"+f"(d[25]),"+f"(d[26]),"+f"(d[27]),"+f"(d[28]),"+f"(d[29]),"+f"(d[30]),"+f"(d[31])
   : "r"(a0),"r"(a1),"r"(a2),"r"(a3),"r"(bl),"r"(bo >> 4),"r"(scale_d),"n"(TB),"n"(BH),"n"(SA));
}
template<int TA,int TB,uint32_t AH,uint32_t BH> __device__ __forceinline__ void wgmma_n96_ss(float (&d)[48], uint32_t al, uint32_t ao, uint32_t bl, uint32_t bo, int scale_d){
  asm volatile("{.reg .pred p; .reg .b32 t, v; .reg .b64 da, db; setp.ne.b32 p, %52, 0; add.u32 t, %48, %49; mov.b64 da, {t, %55}; add.u32 v, %50, %51; mov.b64 db, {v, %56};\n"
   "wgmma.mma_async.sync.aligned.m64n96k16.f32.bf16.bf16 {%0,%1,%2,%3,%4,%5,%6,%7,%8,%9,%10,%11,%12,%13,%14,%15,%16,%17,%18,%19,%20,%21,%22,%23,%24,%25,%26,%27,%28,%29,%30,%31,%32,%33,%34,%35,%36,%37,%38,%39,%40,%41,%42,%43,%44,%45,%46,%47}, da, db, p, 1, 1, %53, %54;}"
   : "+f"(d[0]),"+f"(d[1]),"+f"(d[2]),"+f"(d[3]),"+f"(d[4]),"+f"(d[5]),"+f"(d[6]),"+f"(d[7]),"+f"(d[8]),"+f"(d[9]),"+f"(d[10]),"+f"(d[11]),"+f"(d[12]),"+f"(d[13]),"+f"(d[14]),"+f"(d[15]),"+f"(d[16]),"+f"(d[17]),"+f"(d[18]),"+f"(d[19]),"+f"(d[20]),"+f"(d[21]),"+f"(d[22]),"+f"(d[23]),"+f"(d[24]),"+f"(d[25]),"+f"(d[26]),"+f"(d[27]),"+f"(d[28]),"+f"(d[29]),"+f"(d[30]),"+f"(d[31]),"+f"(d[32]),"+f"(d[33]),"+f"(d[34]),"+f"(d[35]),"+f"(d[36]),"+f"(d[37]),"+f"(d[38]),"+f"(d[39]),"+f"(d[40]),"+f"(d[41]),"+f"(d[42]),"+f"(d[43]),"+f"(d[44]),"+f"(d[45]),"+f"(d[46]),"+f"(d[47])
   : "r"(al),"r"(ao >> 4),"r"(bl),"r"(bo >> 4),"r"(scale_d),"n"(TA),"n"(TB),"n"(AH),"n"(BH));
}
template<int TA,int TB,uint32_t AH,uint32_t BH> __device__ __forceinline__ void wgmma_n128_ss(float (&d)[64], uint32_t al, uint32_t ao, uint32_t bl, uint32_t bo, int scale_d){
  asm volatile("{.reg .pred p; .reg .b32 t, v; .reg .b64 da, db; setp.ne.b32 p, %68, 0; add.u32 t, %64, %65; mov.b64 da, {t, %71}; add.u32 v, %66, %67; mov.b64 db, {v, %72};\n"
   "wgmma.mma_async.sync.aligned.m64n128k16.f32.bf16.bf16 {%0,%1,%2,%3,%4,%5,%6,%7,%8,%9,%10,%11,%12,%13,%14,%15,%16,%17,%18,%19,%20,%21,%22,%23,%24,%25,%26,%27,%28,%29,%30,%31,%32,%33,%34,%35,%36,%37,%38,%39,%40,%41,%42,%43,%44,%45,%46,%47,%48,%49,%50,%51,%52,%53,%54,%55,%56,%57,%58,%59,%60,%61,%62,%63}, da, db, p, 1, 1, %69, %70;}"
   : "+f"(d[0]),"+f"(d[1]),"+f"(d[2]),"+f"(d[3]),"+f"(d[4]),"+f"(d[5]),"+f"(d[6]),"+f"(d[7]),"+f"(d[8]),"+f"(d[9]),"+f"(d[10]),"+f"(d[11]),"+f"(d[12]),"+f"(d[13]),"+f"(d[14]),"+f"(d[15]),"+f"(d[16]),"+f"(d[17]),"+f"(d[18]),"+f"(d[19]),"+f"(d[20]),"+f"(d[21]),"+f"(d[22]),"+f"(d[23]),"+f"(d[24]),"+f"(d[25]),"+f"(d[26]),"+f"(d[27]),"+f"(d[28]),"+f"(d[29]),"+f"(d[30]),"+f"(d[31]),"+f"(d[32]),"+f"(d[33]),"+f"(d[34]),"+f"(d[35]),"+f"(d[36]),"+f"(d[37]),"+f"(d[38]),"+f"(d[39]),"+f"(d[40]),"+f"(d[41]),"+f"(d[42]),"+f"(d[43]),"+f"(d[44]),"+f"(d[45]),"+f"(d[46]),"+f"(d[47]),"+f"(d[48]),"+f"(d[49]),"+f"(d[50]),"+f"(d[51]),"+f"(d[52]),"+f"(d[53]),"+f"(d[54]),"+f"(d[55]),"+f"(d[56]),"+f"(d[57]),"+f"(d[58]),"+f"(d[59]),"+f"(d[60]),"+f"(d[61]),"+f"(d[62]),"+f"(d[63])
   : "r"(al),"r"(ao >> 4),"r"(bl),"r"(bo >> 4),"r"(scale_d),"n"(TA),"n"(TB),"n"(AH),"n"(BH));
}

__global__ void __cluster_dims__(2, 1, 1) __launch_bounds__(384, 1)
fused_kernel(const __nv_bfloat16* __restrict__ lam_re, const __nv_bfloat16* __restrict__ lam_im, const __nv_bfloat16* __restrict__ log_dt,
             const __nv_bfloat16* __restrict__ dskip, const __nv_bfloat16* __restrict__ b1, const __nv_bfloat16* __restrict__ b2,
             const __nv_bfloat16* __restrict__ gate_w, const __nv_bfloat16* __restrict__ pf_w1, const __nv_bfloat16* __restrict__ pf_w2,
             const __nv_bfloat16* __restrict__ pf_cre, const __nv_bfloat16* __restrict__ pf_cim, float* __restrict__ out,
             const __grid_constant__ Maps maps) {
  extern __shared__ __align__(1024) unsigned char smem_raw[];
  const uint32_t sb = (uint32_t)__cvta_generic_to_shared(smem_raw);
  const int b = blockIdx.x;
  const int rank = b & 1, cl = b >> 1;
  const int sp = (cl & 1) | ((cl >> 2) & 2), m = ((cl >> 1) & 3) | ((cl >> 4) << 2);
  const int s = sp * 2 + rank;
  const int warp = __shfl_sync(0xffffffffu, (int)(threadIdx.x >> 5), 0);
  const int lane = threadIdx.x & 31;
  const int xrot = 9 - 2 * sp;

  if (elect_one()) {
    if (warp == 8) TS(2, 0);
    if (warp > 8) {
      asm volatile("prefetch.tensormap [%0];" ::"l"(&maps.x + (warp - 9)) : "memory");
      mbar_init(sb + OFF_GBAR + 8 * (warp - 9), warp < 11 ? 64 : 96);
    }
    const uint32_t c = warp < 8 ? 1 : warp < 11 ? 8 : 4, bar = sb + OFF_XFULL + 16 * warp;
    mbar_init(bar, c);
    if ((warp & 11) == 0) {
      mbar_expect_tx(bar, 16384);
      if (warp == 0) {
        tma5d(sb + OFF_X + (xrot & 7) * 16384, &maps.x, 0, 2 * m, bar);
        tma5d(sb + OFF_X + (xrot & 7) * 16384 + 8192, &maps.x, 0, 2 * m + 1, bar);
        TS(2, 3);
      } else {
        tma2d(sb + OFF_RING, &maps.bre, 0, s * 64, bar);
        tma2d(sb + OFF_RING + 8192, &maps.bim, 0, s * 64, bar);
        TS(2, 4);
      }
    }
    mbar_init(bar + 8, c);
    asm volatile("fence.mbarrier_init.release.cluster;" ::: "memory");
  }
  __syncwarp();
  asm volatile("barrier.cluster.arrive.relaxed.aligned;" ::: "memory");

  if (warp < 8) {
    const int wg = warp >> 2, w = warp & 3, q = lane & 3, gr = lane >> 2;
    uint32_t bv[28];
#pragma unroll
    for (int j = 0; j < 28; j++) bv[j] = __ldg(reinterpret_cast<const uint32_t*>(b1 + s * 224 + j * 8) + q);
    asm volatile("setmaxnreg.inc.sync.aligned.u32 224;");
    asm volatile("barrier.cluster.wait.aligned;" ::: "memory");
    TS(wg, 0);
    auto release = [&](int slot) { if (lane == 0) mbar_arrive(sb + OFF_EMPTY + 8 * slot); };
    const uint32_t xw = sb + OFF_X + wg * 8192, fullb = sb + OFF_FULL;
    const uint32_t dxw = (xw & 0x3FFFF) >> 4, dring = ((sb + OFF_RING) & 0x3FFFF) >> 4;

    float ure[32], uim[32], aa[48], ab[64];
    cplx lam[2], coef[2], l16[2], l32[2], lq[2], pre[2], e[2];
    uint32_t sh16, mhi, ck = 0;

    auto bias = [&](int c) {
#pragma unroll
      for (int j = c * 7; j < c * 7 + 7; j++) {
        pin(bv[j]);
        float* d = j < 12 ? aa + 4 * j : ab + 4 * (j - 12);
        d[0] = d[2] = __uint_as_float(bv[j] << sh16); d[1] = d[3] = __uint_as_float(bv[j] & mhi);
        pin(d[0]); pin(d[1]); pin(d[2]); pin(d[3]);
      }
    };
#pragma unroll
    for (int kb = 0; kb < 8; kb++) {
      const int slot = kb % NSLOT;
      mbar_wait(sb + OFF_XFULL + 8 * kb, 0);
      if (kb == 0) TS(wg, 18);
      if (kb == 0) mbar_wait(fullb, 0);
      TS2(2, kb);
      if (kb == 0) TS(wg, 1);
      if (kb == SB0) { sh16 = late16(sb + OFF_XFULL); mhi = 0xffffffffu << sh16; }
      if (kb == LCK) {
        mbar_wait(sb + OFF_LBAR, 0);
#pragma unroll
        for (int h = 0; h < 2; h++) {
          const uint4 v = lds_u4(sb + OFF_LC + (w * 16 + gr + 8 * h) * 16);
          lam[h] = cplx{__uint_as_float(v.x), __uint_as_float(v.y)};
          coef[h] = cplx{__uint_as_float(v.z), __uint_as_float(v.w)};
        }
      }
      wg_fence();
      const uint32_t dxa = dxw + ((kb + xrot) & 7) * 1024;
#pragma unroll
      for (int kk = 0; kk < 4; kk++) {
        wgmma_n64_ss<0, 0, DH128, DH128>(ure, dring, slot * 16384 + kk * 32, dxa, kk * 32, (kb | kk) != 0);
        wgmma_n64_ss<0, 0, DH128, DH128>(uim, dring, slot * 16384 + 8192 + kk * 32, dxa, kk * 32, (kb | kk) != 0);
      }
      wg_commit();
      if (kb > 0) { wg_wait<1>(); release((kb - 1) % NSLOT); }
      if (kb >= SB0 && kb < SB0 + 3) bias(kb - SB0);
      if (kb == 6) {
#pragma unroll
        for (int h = 0; h < 2; h++) {
          pin(lam[h].re); pin(lam[h].im);
          cplx t = cmul(lam[h], lam[h]); t = cmul(t, t); t = cmul(t, t);
          l16[h] = cmul(t, t);
          pin(l16[h].re); pin(l16[h].im);
        }
      }
      if (kb == 7) {
#pragma unroll
        for (int h = 0; h < 2; h++) {
          pin(l16[h].re); pin(l16[h].im);
          l32[h] = cmul(l16[h], l16[h]);
          const cplx a = (q & 1) ? l16[h] : cplx{1.f, 0.f}, c = (q & 2) ? l32[h] : cplx{1.f, 0.f};
          lq[h] = cmul(cmul(a, c), coef[h]);
          pin(lq[h].re); pin(lq[h].im);
        }
      }
    }
    TS(wg, 2);
    auto scale_u = [&](int i0, int i1) {
#pragma unroll
      for (int i = 0; i < 32; i++) if (i >= i0 && i < i1) {
        pin(ure[i]); pin(uim[i]);
        const cplx v = cmul(coef[(i >> 1) & 1], cplx{ure[i], uim[i]});
        ure[i] = v.re; uim[i] = v.im;
        pin(ure[i]); pin(uim[i]);
      }
    };
#pragma unroll
    for (int kb = 0; kb < 8; kb++) {
      const int u = 8 + kb, slot = u % NSLOT;
      mbar_wait(fullb + 8 * slot, full_par(u));
      TK(kb);
      wg_fence();
      const uint32_t dxa = dxw + ((kb + xrot) & 7) * 1024;
#pragma unroll
      for (int kk = 0; kk < 4; kk++)
        wgmma_n96_ss<0, 1, DH128, DH64>(aa, dxa, kk * 32, dring, slot * 16384 + kk * 1024 + lbo(4096), 1);
      wg_commit();
      if (kb == 0) bias(3);
      if (kb != QK) { wg_wait<1>(); release((u - 1) % NSLOT); }
      if (kb == 0) {
        reg_fence(ure); reg_fence(uim);
#pragma unroll
        for (int h = 0; h < 2; h++) e[h] = cplx{ure[2 * h], uim[2 * h]};
      }
      if (kb == 0 || (kb >= 2 && kb <= QK && kb < 4)) {
        constexpr int tc[5] = TCUT;
#pragma unroll
        for (int t = 1; t < 16; t++) if (t >= tc[kb] && t < tc[kb + 1]) {
#pragma unroll
          for (int h = 0; h < 2; h++) { const int i = 4 * (t >> 1) + 2 * h + (t & 1); e[h] = cfma(lam[h], e[h], cplx{ure[i], uim[i]}); }
        }
#pragma unroll
        for (int h = 0; h < 2; h++) { pin(e[h].re); pin(e[h].im); }
      }
      if (kb == QK) {
        sched_fence(ck);
#pragma unroll
        for (int h = 0; h < 2; h++) {
          cplx y = {__shfl_up_sync(0xffffffffu, e[h].re, 1, 4), __shfl_up_sync(0xffffffffu, e[h].im, 1, 4)};
          if (q >= 1) e[h] = cfma(l16[h], y, e[h]);
          y = cplx{__shfl_up_sync(0xffffffffu, e[h].re, 2, 4), __shfl_up_sync(0xffffffffu, e[h].im, 2, 4)};
          if (q >= 2) e[h] = cfma(l32[h], y, e[h]);
        }
        if (q == 3) {
#pragma unroll
          for (int h = 0; h < 2; h++)
            asm volatile("st.shared.v2.f32 [%0], {%1,%2};" ::"r"(sb + OFF_CARRY + wg * 512 + (w * 16 + gr + 8 * h) * 8), "f"(e[h].re), "f"(e[h].im) : "memory");
          mbar_arrive(sb + OFF_GBAR);
        }
#pragma unroll
        for (int h = 0; h < 2; h++) e[h] = cplx{__shfl_up_sync(0xffffffffu, e[h].re, 1, 4), __shfl_up_sync(0xffffffffu, e[h].im, 1, 4)};
        wg_wait<1>(); release((u - 1) % NSLOT);
        if (TKT > 500) TS(wg, 3);
      }
      if (kb == QK + 1) {
#pragma unroll
        for (int h = 0; h < 2; h++) {
          pre[h] = (q >= 1) ? cmul(coef[h], e[h]) : cplx{0.f, 0.f};
          pin(pre[h].re); pin(pre[h].im);
        }
      }
      if (kb > QK) { constexpr int sc[9] = SCUT; scale_u(sc[kb], sc[kb + 1]); }
    }
    TS(wg, 4);
    uint32_t H[56], hf[32];
    cplx hst[2];
    const uint32_t hst_addr = xw + (w * 16 + (lane & 15)) * 128 + (((lane >> 4) ^ (lane & 7)) << 4);
    const uint32_t him = (2 - rank) * 16384;
    uint32_t peer;
    asm volatile("mapa.shared::cluster.u32 %0, %1, %2;" : "=r"(peer) : "r"(sb), "r"(rank ^ 1));
    auto credit = [&]() { if (lane == 0) mbar_arrive_cl(peer + OFF_KBAR + wg * 8); };
    uint32_t g2[8];
#pragma unroll
    for (int kb = 0; kb < 8; kb++) {
      const int u = 16 + kb, slot = u % NSLOT;
      mbar_wait(fullb + 8 * slot, full_par(u));
      TK(kb < 7 ? 24 + kb : 32);
      wg_fence();
#pragma unroll
      for (int kk = 0; kk < 4; kk++)
        wgmma_n128_ss<0, 1, DH128, DH128>(ab, dxw, kb * 16384 + kk * 32, dring, slot * 16384 + kk * 2048 + lbo(8192), 1);
      wg_commit();
      if (kb == 0) { constexpr int sc[9] = SCUT; scale_u(sc[8], 32); }
      if (kb == 4) {
        if (TKT > 500) TS(wg, 5);
        mbar_wait(sb + OFF_CBAR, 0);
        if (TKT > 500) TS(wg, 6);
#pragma unroll
        for (int h = 0; h < 2; h++) {
          const float2 c = lds_f2(sb + OFF_CARRY + wg * 512 + (w * 16 + gr + 8 * h) * 8);
          hst[h] = cfma(lq[h], cplx{c.x, c.y}, pre[h]);
        }
#pragma unroll
        for (int i = 0; i < 2; i++) {
          const uint4 v = lds_u4(sb + OFF_GT + wg * 128 + q * 32 + i * 16);
          g2[4 * i] = v.x; g2[4 * i + 1] = v.y; g2[4 * i + 2] = v.z; g2[4 * i + 3] = v.w;
        }
      }
      if (kb == 0 || TOKB != 1) { wg_wait<1>(); release((u - 1) % NSLOT); }
      if (kb) sched_fence(ck);
      if (kb < 4) {
#pragma unroll
        for (int i = kb * 6; i < kb * 6 + 6; i++) {
          pin(aa[2 * i]); pin(aa[2 * i + 1]);
          H[i] = gelu2_pair(aa[2 * i], aa[2 * i + 1]);
          pin(H[i]);
        }
      } else {
        const int j0 = (kb - 4) * 2;
        uint32_t rr[4], ri[4];
#pragma unroll
        for (int jj = 0; jj < 2; jj++) {
          const int j = j0 + jj;
#pragma unroll
          for (int h = 0; h < 2; h++) {
            const int i = 4 * j + 2 * h;
            const cplx h0 = cfma(lam[h], hst[h], cplx{ure[i], uim[i]});
            hst[h] = cfma(lam[h], h0, cplx{ure[i + 1], uim[i + 1]});
            rr[jj * 2 + h] = bf2_mul(pack_bf16(h0.re, hst[h].re), g2[j]);
            ri[jj * 2 + h] = bf2_mul(pack_bf16(h0.im, hst[h].im), g2[j]);
          }
        }
        const uint32_t a = hst_addr ^ (j0 << 4);
        asm volatile("stmatrix.sync.aligned.m8n8.x4.shared.b16 [%0], {%1,%2,%3,%4};" ::"r"(a), "r"(rr[0]), "r"(rr[1]), "r"(rr[2]), "r"(rr[3]) : "memory");
        asm volatile("stmatrix.sync.aligned.m8n8.x4.shared.b16 [%0], {%1,%2,%3,%4};" ::"r"(a + him), "r"(ri[0]), "r"(ri[1]), "r"(ri[2]), "r"(ri[3]) : "memory");
      }
      if (kb && TOKB == 1) { wg_wait<1>(); release((u - 1) % NSLOT); }
    }
    TS(wg, 7);

    uint4* const psend = g_part + (size_t)(m * 8 + rank) * 3072 + warp * 128 + lane;
    const uint4* const precv = g_part + (size_t)(m * 8 + s) * 3072 + warp * 128 + lane;
    const uint32_t pbuf = OFF_X + warp * 2048 + lane * 16;
    const uint32_t dx0 = ((sb + OFF_X) & 0x3FFFF) >> 4;
    float o[32], fin[32], rho[2];
    uint32_t tr[8];
    uint32_t r0[16], pt[16], sum[16], tag;
    auto recv_issue = [&](uint32_t (&r)[16], int k) {
#pragma unroll
      for (int i = 0; i < 4; i++) ld_b128(precv + k * 1024 + i * 32, r[4 * i], r[4 * i + 1], r[4 * i + 2], r[4 * i + 3]);
    };
    auto stale = [&](uint32_t (&r)[16]) {
      uint32_t t0, t1, r_;
      asm("lop3.b32 %0, %1, %2, %3, 0x7e;" : "=r"(t0) : "r"(r[0]), "r"(r[4]), "r"(tag));
      asm("lop3.b32 %0, %1, %2, %3, 0x7e;" : "=r"(t1) : "r"(r[8]), "r"(r[12]), "r"(tag));
      asm volatile("{.reg .pred p; .reg .b32 t; lop3.b32 t, %1, %2, 1, 0xa8; setp.ne.u32 p, t, 0; vote.sync.any.pred p, p, 0xffffffff; selp.u32 %0, 1, 0, p;}" : "=r"(r_) : "r"(t0), "r"(t1));
      return r_ != 0;
    };
    auto recv_check = [&](uint32_t (&r)[16], int k) {
      if (__builtin_expect(stale(r), 0)) {
        int tries = 0;
#pragma unroll 1
        do { recv_issue(r, k); } while (stale(r) && ++tries < 200000);
      }
    };
    auto gelu_b = [&](int i0, int i1) {
      if (TOKD && i0) sched_fence(ck);
#pragma unroll
      for (int i = i0; i < i1; i++) {
        pin(ab[2 * i]); pin(ab[2 * i + 1]);
        H[24 + i] = gelu2_pair(ab[2 * i], ab[2 * i + 1]);
        pin(H[24 + i]);
      }
      if (TOKD == 2) sched_fence(ck);
    };
    auto step = [&](float (&d)[32], int p, int k, int acc) {
      const uint32_t wo = stage_off(p);
      if (k >= 6 && k < 14) {
        const int kk = k - 6;
        if (kk < 4) wgmma_n64_rs<0, DH128, 1>(d, hf[4 * kk], hf[4 * kk + 1], hf[4 * kk + 2], hf[4 * kk + 3], dx0, wo + 14336 + kk * 32, 1);
        else wgmma_n64_rs<0, DH128, -1>(d, hf[4 * kk], hf[4 * kk + 1], hf[4 * kk + 2], hf[4 * kk + 3], dx0, wo + 22528 + (kk - 4) * 32, 1);
      } else {
        const int kk = k < 6 ? k : k - 8;
        wgmma_n64_rs<1, DH128>(d, H[4 * kk], H[4 * kk + 1], H[4 * kk + 2], H[4 * kk + 3], dx0, wo + (kk / 7) * 30720 + (kk % 7) * 2048, k != 0 || acc);
      }
    };
    auto mma = [&](float (&d)[32], int p, int k0, int k1, int acc) {
      wg_fence();
#pragma unroll
      for (int k = k0; k < k1; k++) step(d, p, k, acc);
      wg_commit();
    };
    auto send_peer = [&]() {
#pragma unroll
      for (int i = 0; i < 4; i++)
        asm volatile("st.async.shared::cluster.mbarrier::complete_tx::bytes.v4.b32 [%0], {%1,%2,%3,%4}, [%5];" ::"r"(peer + pbuf + i * 512),
                     "r"(pack_bf16(o[8 * i], o[8 * i + 1])), "r"(pack_bf16(o[8 * i + 2], o[8 * i + 3])), "r"(pack_bf16(o[8 * i + 4], o[8 * i + 5])),
                     "r"(pack_bf16(o[8 * i + 6], o[8 * i + 7])), "r"(peer + OFF_RBAR + wg * 8) : "memory");
    };
    auto recv_peer = [&](int k) {
      mbar_wait(sb + OFF_RBAR + wg * 8, k & 1);
#pragma unroll
      for (int i = 0; i < 4; i++) { const uint4 v = lds_u4(sb + pbuf + i * 512); pt[4 * i] = v.x; pt[4 * i + 1] = v.y; pt[4 * i + 2] = v.z; pt[4 * i + 3] = v.w; }
    };
    auto send_owner = [&](float (&d)[32], int k) {
#pragma unroll
      for (int i = 0; i < 4; i++) {
#pragma unroll
        for (int c = 4 * i; c < 4 * i + 4; c++) pt[c] = bf2_add(pt[c], pack_bf16(d[2 * c], d[2 * c + 1]));
        asm("lop3.b32 %0, %0, 1, %1, 0xb8;" : "+r"(pt[4 * i]) : "r"(tag));
        st_b128(psend + (((sp + 1 + k) & 3) * 6 + k) * 1024 + i * 32, pt[4 * i], pt[4 * i + 1], pt[4 * i + 2], pt[4 * i + 3]);
      }
      __syncwarp();
      credit();
    };
    auto load_fin = [&]() {
      mbar_wait(sb + OFF_LBAR, 1);
#pragma unroll
      for (int j = 0; j < 8; j++) {
        const uint4 v = lds_u4(sb + pbuf + 16384 + (j >> 2) * 16384 + (j & 3) * 512);
        fin[4 * j] = __uint_as_float(v.x); fin[4 * j + 1] = __uint_as_float(v.y); fin[4 * j + 2] = __uint_as_float(v.z); fin[4 * j + 3] = __uint_as_float(v.w);
      }
    };
    auto ldk = [&](int pos) { if (pos == K0P) recv_issue(sum, 0); if (pos == K1P) recv_issue(r0, 1); };
    auto arm = [&]() { if ((threadIdx.x & 127) == 0) mbar_expect_tx(sb + OFF_RBAR + wg * 8, 8192); };
    auto mma2 = [&](int k0, int k1) {
      wg_fence();
#pragma unroll
      for (int k = k0; k < k1; k++) { step(o, 0, k, 0); step(fin, 1, k, 0); }
      wg_commit();
    };
    {
        constexpr int kc[8] = KCUT;
        mbar_wait(fullb, full_par(24));
        mma2(0, kc[0]);
        bar_sync(1 + wg, 128);
        {
          const uint32_t ha = xw + ((lane >> 4) * 8 + (lane & 7)) * 128 + (((2 * w + ((lane >> 3) & 1)) ^ (lane & 7)) << 4);
#pragma unroll
          for (int kk = 0; kk < 8; kk++)
            asm volatile("ldmatrix.sync.aligned.m8n8.x4.trans.shared.b16 {%0,%1,%2,%3}, [%4];" : "=r"(hf[4 * kk]), "=r"(hf[4 * kk + 1]), "=r"(hf[4 * kk + 2]), "=r"(hf[4 * kk + 3])
                         : "r"(ha + (kk >> 2) * him + (kk & 3) * 2048) : "memory");
        }
        tag = lds_u(sb + OFF_EPOCH);
        arm();
        mbar_wait(fullb + 8, full_par(25));
        wg_wait<1>(); release(5);
        gelu_b(0, 4);   mma2(kc[0], kc[1]);
        gelu_b(4, 8);   mma2(kc[1], kc[2]);
        gelu_b(8, 12);  mma2(kc[2], kc[3]); credit();
        gelu_b(12, 16); mma2(kc[3], kc[4]);
        gelu_b(16, 20);
        mbar_wait(fullb + 16, full_par(26));
        mma2(kc[4], kc[5]);
        gelu_b(20, 24); mma2(kc[5], kc[6]);
        gelu_b(24, 28); mma2(kc[6], kc[7]);
        mbar_wait(sb + OFF_KBAR + wg * 8, 0);
        mbar_wait(sb + OFF_XFULL + 16, 1);
        gelu_b(28, 32);
        if (wg == 1) bar_sync(4, 256);
        mma(o, 0, kc[7], 22, 0);
        mma(fin, 1, kc[7], 22, 0);
        bar_arrive(4 - wg, 256);
        TS(wg, 9);
        wg_wait<1>();
        reg_fence(o);
        send_peer();
        if (E1L == 0 || (E1L == 1 && wg == 1)) { recv_peer(0); wg_wait<0>(); release(0); release(1); reg_fence(fin); send_owner(fin, 0); }
    }
#pragma unroll
    for (int p = 2; p < 8; p++) {
      {
        TR(0);
        if (EW == 0 || (EW == 1 && (p & 1))) mbar_wait(sb + OFF_XFULL + 8 * p, 1);
        TR(1);
        bar_sync(3 + wg, 256);
        if (p < 7) mma(o, p, 0, 22, 0);
        else if (GAP == 0) mma(fin, p, 0, 22, 1);
        else {
          mma(fin, p, 0, GAP, 1);
          recv_peer(3);
          tag = lds_u(sb + OFF_EPOCH);
          mma(fin, p, GAP, 22, 1);
        }
      }
      if (p < 7 || wg == 0) bar_arrive(4 - wg, 256);
      TR(2);
      if (p != TP) TS(wg, 8 + p);
      if (p < 7 && (EW == 2 || (EW == 1 && (p & 1)))) mbar_wait(sb + OFF_XFULL + 8 * (p + 1), 1);
      ldk(10 * p);
      if (p == 2) asm volatile("st.shared.u32 [%0], %1;" ::"r"(sb + OFF_EPOCH + 4), "r"(ck) : "memory");
      if ((p & 1) == 0) {
        if (p == 2 && (E1L == 2 || (E1L == 1 && wg == 0))) { recv_peer(0); wg_wait<1>(); release(0); release(1); reg_fence(fin); send_owner(fin, 0); }
        arm();
        if (p == 6) {
          mbar_wait(sb + OFF_EMPTY + 32, 0);
          tag = lds_u(sb + OFF_EPOCH);
          recv_check(sum, 0); recv_check(r0, 1);
#pragma unroll
          for (int i = 0; i < 16; i++) sum[i] = bf2_add(sum[i], r0[i]);
        }
        TR(3);
        mbar_wait(sb + OFF_KBAR + wg * 8, (p >> 1) & 1);
        TR(4);
      } else {
        if (p == 1 || (p == 7 && GAP == 0)) tag = lds_u(sb + OFF_EPOCH);
        TR(3);
        if (p < 7 || GAP == 0) recv_peer(p >> 1);
        TR(4);
        if (p == 7) {
          recv_check(r0, 2);
#pragma unroll
          for (int i = 0; i < 16; i++) sum[i] = bf2_add(sum[i], bf2_add(r0[i], pt[i]));
        }
      }
      if (p == FINP && !FINW) load_fin();
      ldk(10 * p + 1);
      TR(5);
      wg_wait<0>();
      TR(6);
      if (p < 5) release(p);
      if (p < 7) reg_fence(o); else reg_fence(fin);
      ldk(10 * p + 2);
      if ((p & 1) == 0) {
        if (p == 6) recv_issue(r0, 2);
        send_peer();
        if (p == FINP && FINW) load_fin();
      } else if (p < 7) {
        send_owner(o, p >> 1);
      }
      ldk(10 * p + 3);
      if (p == 2) {
#pragma unroll
        for (int h = 0; h < 2; h++) { rho[h] = __fdividef(2.f, 4.f + bf_lo(lds_h(sb + OFF_GS + (wg * 64 + w * 16 + gr + 8 * h) * 2))); pin(rho[h]); }
      }
      TR(7);
    }
    {
      TS(wg, 16);
      const uint32_t tb = sb + OFF_X + stage_off(0) + warp * 4096;
      const uint32_t ta = tb + gr * 256 + ((gr & 3) << 5) + q * 8;
      const uint32_t la = tb + (lane >> 3) * 256 + (((lane & 7) << 4) ^ ((lane >> 3) << 5));
      float* op = out + (size_t)(m * 128 + wg * 64 + (lane >> 4) * 16 + w * 4 + ((lane >> 3) & 1)) * DM + s * 64 + (lane & 7) * 4;
#pragma unroll
      for (int qq = 0; qq < 4; qq += QS) {
#pragma unroll
        for (int qt = qq; qt < qq + QS; qt++) {
          const int h = qt & 1, ch = qt >> 1;
#pragma unroll
          for (int j = 0; j < 4; j++) {
            const int i = ch * 8 + j * 2 + h;
            asm volatile("st.shared.v2.f32 [%0], {%1,%2};" ::"r"((ta ^ (j << 5)) + h * 2048 + ch * 128),
                         "f"((fin[2 * i] + bf_lo(sum[i])) * rho[h]), "f"((fin[2 * i + 1] + bf_hi(sum[i])) * rho[h]) : "memory");
          }
        }
        __syncwarp();
#pragma unroll
        for (int qt = qq; qt < qq + QS; qt++) {
          const int h = qt & 1, ch = qt >> 1;
#pragma unroll
          for (int r = 0; r < 2; r++)
            *reinterpret_cast<uint4*>(op + (r * 32 + h * 2) * DM + ch * 32) = lds_u4(la + (h * 2 + r) * 1024 + ch * 128);
        }
      }
      if (threadIdx.x == 128) g_epoch[b] = tag;
      TS(wg, 17); TG(wg); TRD(); TDUMP();
    }
  } else {
    asm volatile("setmaxnreg.dec.sync.aligned.u32 56;");
    int wsel = warp;
    asm("" : "+r"(wsel));
    if (wsel > 8) {
      if (warp != 11) {
        const int t = threadIdx.x - 288;
        unsigned par;
        asm volatile("ld.relaxed.gpu.global.u32 %0, [%1];" : "=r"(par) : "l"(g_epoch + b) : "memory");
        const float pr = bf_ld(lam_re + s * 64 + t), pi = bf_ld(lam_im + s * 64 + t), pd = bf_ld(log_dt + s * 64 + t);
        asm volatile("barrier.cluster.wait.aligned;" ::: "memory");
        par = __shfl_sync(0xffffffffu, (par + 1) & 1, 0);
        cplx l64 = make_lam(pr, pi, pd);
        {
          const float inv = __fdividef(1.f, fmaf(pr, pr, pi * pi));
          const cplx cf = cmul(cplx{l64.re - 1.f, l64.im}, cplx{pr * inv, -pi * inv});
          asm volatile("st.shared.v4.f32 [%0], {%1,%2,%3,%4};" ::"r"(sb + OFF_LC + t * 16), "f"(l64.re), "f"(l64.im), "f"(cf.re), "f"(cf.im) : "memory");
          mbar_arrive(sb + OFF_LBAR);
        }
#pragma unroll
        for (int i = 0; i < 6; i++) l64 = cmul(l64, l64);
        cplx l128 = cmul(l64, l64);
        pin(l128.re); pin(l128.im);
        uint32_t vr[15], vi[15];
#pragma unroll
        for (int i = 0; i < 15; i++) { vr[i] = par; vi[i] = 0; pin(vr[i]); pin(vi[i]); }
        mbar_wait(sb + OFF_GBAR, 0);
        const float2 e0 = lds_f2(sb + OFF_CARRY + t * 8), e1 = lds_f2(sb + OFF_CARRY + 512 + t * 8);
        float2* eb = g_end + s * 1024 + t;
        {
          const cplx e = cfma(l64, cplx{e0.x, e0.y}, cplx{e1.x, e1.y});
          const unsigned long long v = ((unsigned long long)__float_as_uint(e.im) << 32) | ((__float_as_uint(e.re) & ~1u) | par);
          asm volatile("st.relaxed.gpu.global.b64 [%0], %1;" ::"l"(eb + m * 64), "l"(v) : "memory");
        }
        if (t == 0) TS(3, 1);
        cplx S = {0.f, 0.f};
        {
          if (LBD) __nanosleep(LBD);
          const float2* e15 = eb + (m - 15) * 64;
          int tries = 0;
          bool bad;
#pragma unroll 1
          do {
#pragma unroll
            for (int i = 0; i < 15; i++)
              asm volatile("{.reg .pred p; .reg .b64 v; mov.b64 v, {%0,%1}; setp.ge.s32 p, %3, %4; @p ld.relaxed.gpu.global.b64 v, [%2]; mov.b64 {%0,%1}, v;}"
                           : "+r"(vr[i]), "+r"(vi[i]) : "l"(e15 + i * 64), "r"(m), "r"(15 - i) : "memory");
            uint32_t x = vr[0] ^ par;
#pragma unroll
            for (int i = 1; i < 15; i++) asm("lop3.b32 %0, %0, %1, %2, 0xf6;" : "+r"(x) : "r"(vr[i]), "r"(par));
            bad = __any_sync(0xffffffffu, x & 1);
          } while (bad && ++tries < 200000);
          if (t == 0) TS(3, 2);
          S = cplx{__uint_as_float(vr[0]), __uint_as_float(vi[0])};
#pragma unroll
          for (int i = 1; i < 15; i++) S = cfma(l128, S, cplx{__uint_as_float(vr[i]), __uint_as_float(vi[i])});
        }
        const cplx S1 = cfma(l64, S, cplx{e0.x, e0.y});
        asm volatile("st.shared.v2.f32 [%0], {%1,%2};" ::"r"(sb + OFF_CARRY + t * 8), "f"(S.re), "f"(S.im) : "memory");
        asm volatile("st.shared.v2.f32 [%0], {%1,%2};" ::"r"(sb + OFF_CARRY + 512 + t * 8), "f"(S1.re), "f"(S1.im) : "memory");
        mbar_arrive(sb + OFF_CBAR);
        if (t == 0) TS(3, 3);
        mbar_wait(sb + OFF_CBAR, 0);
        const int gr = lane >> 2, q = lane & 3;
        float2 db[8];
#pragma unroll
        for (int j = 0; j < 8; j++) db[j] = lds_f2(sb + OFF_DB + j * 32 + q * 8);
        mbar_wait(sb + OFF_XFULL + 16, 1);
        mbar_wait(sb + OFF_EMPTY, 0);
#pragma unroll 1
        for (int cw = warp - 9; cw < 8; cw += 2) {
          const float r0 = 0.5f * bf_lo(lds_h(sb + OFF_GS + (cw * 16 + gr) * 2)), r1 = 0.5f * bf_lo(lds_h(sb + OFF_GS + (cw * 16 + gr) * 2 + 16));
          const uint32_t xa = sb + OFF_X + (1 + rank) * 16384 + (cw * 16 + (lane & 15)) * 128 + (((lane >> 4) ^ (lane & 7)) << 4);
          uint32_t xv[16];
#pragma unroll
          for (int i = 0; i < 4; i++)
            asm volatile("ldmatrix.sync.aligned.m8n8.x4.shared.b16 {%0,%1,%2,%3}, [%4];" : "=r"(xv[4 * i]), "=r"(xv[4 * i + 1]), "=r"(xv[4 * i + 2]), "=r"(xv[4 * i + 3])
                         : "r"(xa ^ (i << 5)) : "memory");
          __syncwarp();
#pragma unroll
          for (int j = 0; j < 8; j++) {
            const uint32_t x0 = bf2_mul(xv[2 * j], __float_as_uint(db[j].x)), x1 = bf2_mul(xv[2 * j + 1], __float_as_uint(db[j].x));
            pin(db[j].y);
            const float bl = bf_lo(__float_as_uint(db[j].y)), bh = bf_hi(__float_as_uint(db[j].y));
            asm volatile("st.shared.v4.f32 [%0], {%1,%2,%3,%4};" ::"r"(sb + OFF_X + 16384 + (j >> 2) * 16384 + cw * 2048 + (j & 3) * 512 + lane * 16), "f"(fmaf(bf_lo(x0), r0, bl)),
                         "f"(fmaf(bf_hi(x0), r0, bh)), "f"(fmaf(bf_lo(x1), r1, bl)), "f"(fmaf(bf_hi(x1), r1, bh)) : "memory");
          }
        }
        mbar_arrive(sb + OFF_LBAR);
        if (t == 0) TS(3, 5);
      } else {
        if (lane == 0) TG(2);
        const uint4* gwp = reinterpret_cast<const uint4*>(gate_w) + (lane & 7);
        uint4 gw[4];
#pragma unroll
        for (int i = 0; i < 4; i++) gw[i] = __ldg(gwp + i * 8);
        unsigned par;
        asm volatile("ld.relaxed.gpu.global.u32 %0, [%1];" : "=r"(par) : "l"(g_epoch + b) : "memory");
        const uint32_t dk = __ldg(reinterpret_cast<const uint32_t*>(dskip + s * 64) + lane), bb = __ldg(reinterpret_cast<const uint32_t*>(b2 + s * 64) + lane);
        asm volatile("barrier.cluster.wait.aligned;" ::: "memory");
        const int row = s * 16 + (lane >> 3);
        const uint32_t xr0 = sb + OFF_X + row * 128 + (((lane & 7) ^ (row & 7)) << 4), xr1 = (xr0 + 512) ^ 64;
        float z[4] = {0.f, 0.f, 0.f, 0.f};
#pragma unroll
        for (int kb = 0; kb < 8; kb++) {
          const uint32_t wv[4] = {gw[kb & 3].x, gw[kb & 3].y, gw[kb & 3].z, gw[kb & 3].w};
          if (kb < 4) gw[kb] = __ldg(gwp + (kb + 4) * 8);
          mbar_wait(sb + OFF_XFULL + 8 * kb, 0);
          if ((PF & 2) && kb == PFK && elect_one()) {
            l2_prefetch(pf_w1 + b * 7168, 14336);
            l2_prefetch(pf_cre + b * 2048, 4096);
            l2_prefetch(pf_cim + b * 2048, 4096);
            l2_prefetch(pf_w2 + b * 7168, 14336);
          }
          const uint32_t xo = ((kb + xrot) & 7) * 16384;
#pragma unroll
          for (int r = 0; r < 4; r++) {
            const uint4 a = lds_u4(((r & 1) ? xr1 : xr0) + xo + (r >> 1) * 1024);
            const uint32_t p = bf2_fma(a.w, wv[3], bf2_fma(a.z, wv[2], bf2_fma(a.y, wv[1], bf2_mul(a.x, wv[0]))));
            z[r] += bf_lo(p); z[r] += bf_hi(p);
          }
        }
        if (lane == 0) asm volatile("st.shared.u32 [%0], %1;" ::"r"(sb + OFF_EPOCH), "r"(par + 1) : "memory");
        par = (par + 1) & 1;
        {
          float y0 = (lane & 4) ? z[1] : z[0], y1 = (lane & 4) ? z[3] : z[2];
          y0 += __shfl_xor_sync(0xffffffffu, (lane & 4) ? z[0] : z[1], 4);
          y1 += __shfl_xor_sync(0xffffffffu, (lane & 4) ? z[2] : z[3], 4);
          float zz = (lane & 2) ? y1 : y0;
          zz += __shfl_xor_sync(0xffffffffu, (lane & 2) ? y0 : y1, 2);
          zz += __shfl_xor_sync(0xffffffffu, zz, 1);
          const float rho = 4.f * expf(zz > 40.f ? 40.f : zz);
          if ((lane & 1) == 0)
            asm volatile("st.relaxed.gpu.global.u32 [%0], %1;" ::"l"(g_gate + m * 128 + row + (lane & 4) + (lane & 2) * 4), "r"((__float_as_uint(rho) & ~1u) | par) : "memory");
        }
        if ((PF & 8) && elect_one()) {
          l2_prefetch(pf_w2 + b * 7168, 14336);
          l2_prefetch(pf_cre + b * 2048, 4096);
          l2_prefetch(pf_cim + b * 2048, 4096);
        }
        if (lane == 0) TS(3, 0);
        mbar_wait(sb + OFF_GBAR, 0);
        asm volatile("st.shared.v2.u32 [%0], {%1,%2};" ::"r"(sb + OFF_DB + lane * 8), "r"(dk), "r"(bf2_add(bb, bb)) : "memory");
        uint32_t g0, g1, g2, g3;
        int tries = 0;
#pragma unroll 1
        do {
          asm volatile("ld.relaxed.gpu.global.v4.u32 {%0,%1,%2,%3}, [%4];" : "=r"(g0), "=r"(g1), "=r"(g2), "=r"(g3) : "l"(g_gate + m * 128 + lane * 4) : "memory");
        } while ((((g0 ^ par) | (g1 ^ par) | (g2 ^ par) | (g3 ^ par)) & 1) && ++tries < 200000);
        asm volatile("st.shared.v2.u32 [%0], {%1,%2};" ::"r"(sb + OFF_GS + lane * 8), "r"(pack_bf16(__uint_as_float(g0), __uint_as_float(g1))),
                     "r"(pack_bf16(__uint_as_float(g2), __uint_as_float(g3))) : "memory");
        const uint32_t gt = sb + OFF_GT + (lane >> 4) * 128 + (lane & 1) * 64 + ((lane >> 1) & 7) * 4;
        asm volatile("st.shared.u32 [%0], %1;" ::"r"(gt), "r"(pack_bf16(__uint_as_float(g0), __uint_as_float(g1))) : "memory");
        asm volatile("st.shared.u32 [%0], %1;" ::"r"(gt + 32), "r"(pack_bf16(__uint_as_float(g2), __uint_as_float(g3))) : "memory");
        mbar_arrive(sb + OFF_CBAR);
        if (lane == 0) TS(3, 4);
      }
    } else {
      asm volatile("barrier.cluster.wait.aligned;" ::: "memory");
      if (elect_one()) {
        TS(2, 1);
        const uint32_t t0 = clock();
#pragma unroll 1
        for (int u = W0; u < 8; u++) {
          if (u >= 1) while ((uint32_t)clock() - t0 < D0 + (u - 1) * D1) {}
          mbar_expect_tx(sb + OFF_XFULL + 8 * u, 32768);
          tma5d_mc(sb + OFF_X + ((u + xrot) & 7) * 16384 + rank * 8192, &maps.x, u * 64, 2 * m + rank, sb + OFF_XFULL + 8 * u);
          const int sl = u < 6 ? u : u - 6;
          if (u >= 6) mbar_wait(sb + OFF_EMPTY + 8 * sl, 0);
          tma2d(sb + OFF_RING + sl * 16384, &maps.bre, u * 64, s * 64, sb + OFF_XFULL + 8 * u);
          tma2d(sb + OFF_RING + sl * 16384 + 8192, &maps.bim, u * 64, s * 64, sb + OFF_XFULL + 8 * u);
          if (u == 2) asm volatile("prefetch.tensormap [%0];" ::"l"(&maps.w1b) : "memory");
        }
        TS(2, 5);
        int slot = 2; uint32_t ph = 0;
#pragma unroll 1
        for (int u = 8; u < 24; u++) {
          const uint32_t fb = sb + OFF_FULL + 8 * slot, dst = sb + OFF_RING + slot * 16384;
          mbar_wait(sb + OFF_EMPTY + 8 * slot, ph);
          TS2(0, u);
          if (u < 16) {
            mbar_expect_tx(fb, 12288);
            tma3d(dst, &maps.w1b, 0, (u - 8) * 64, s * 7, fb);
            if (TMP2 && u < 12) asm volatile("prefetch.tensormap [%0];" ::"l"(&maps.w1a + (u - 8)) : "memory");
          } else {
            mbar_expect_tx(fb, 16384);
            tma2d(dst, &maps.w1a, s * 224 + 96, ((u - xrot) & 7) * 64, fb);
            tma2d(dst + 8192, &maps.w1a, s * 224 + 160, ((u - xrot) & 7) * 64, fb);
          }
          if (++slot == NSLOT) { slot = 0; ph ^= 1; }
        }
#pragma unroll 1
        for (int j = 0; j < 3; j++) {
          const uint32_t fb = sb + OFF_FULL + 8 * j;
          mbar_wait(sb + OFF_EMPTY + 8 + 8 * j, 1);
          mbar_expect_tx(fb, j == 1 ? 32768 : 28672);
#pragma unroll
          for (int e = 0; e < 2; e++) {
            const int c = ((sp + 1) & 3) * 128 + ((rank ^ e ^ 1) << 6);
            const uint32_t dst = sb + OFF_X + stage_off(e);
            if (j == 1) {
              tma2d(dst + 14336, &maps.cre, s * 64, c, fb);
              tma2d(dst + 22528, &maps.cim, s * 64, c, fb);
            } else {
              tma2d(dst + j * 15360, &maps.w2, c, s * 224 + j * 56, fb);
            }
          }
        }
#pragma unroll 1
        for (int p = 2; p < 8; p++) {
          const int c = ((sp + 1 + (p >> 1)) & 3) * 128 + (((rank ^ p ^ 1) & 1) << 6);
          const uint32_t fb = sb + OFF_XFULL + 8 * p, dst = sb + OFF_X + stage_off(p);
          if (p == 2 || p > 3) mbar_wait(sb + OFF_EMPTY + (p == 2 ? 40 : (p - 4) * 8), p == 2);
          TS2(0, 32 + p);
          mbar_expect_tx(fb, 45056);
          tma2d(dst, &maps.w2, c, s * 224, fb);
          tma2d(dst + 14336, &maps.cre, s * 64, c, fb);
          tma2d(dst + 22528, &maps.cim, s * 64, c, fb);
          tma2d(dst + 30720, &maps.w2, c, s * 224 + 112, fb);
        }
        TS(2, 2);
      }
    }
  }
}

typedef CUresult (*EncFn)(CUtensorMap*, CUtensorMapDataType, cuuint32_t, void*, const cuuint64_t*, const cuuint64_t*, const cuuint32_t*,
                          const cuuint32_t*, CUtensorMapInterleave, CUtensorMapSwizzle, CUtensorMapL2promotion, CUtensorMapFloatOOBfill);

void encode(EncFn f, CUtensorMap* mp, const void* p, int rank, const cuuint64_t* dims, const cuuint64_t* strides, const cuuint32_t* box, CUtensorMapSwizzle sw) {
  cuuint32_t es[5] = {1, 1, 1, 1, 1};
  f(mp, CU_TENSOR_MAP_DATA_TYPE_BFLOAT16, rank, const_cast<void*>(p), dims, strides, box, es, CU_TENSOR_MAP_INTERLEAVE_NONE, sw,
    CU_TENSOR_MAP_L2_PROMOTION_L2_128B, CU_TENSOR_MAP_FLOAT_OOB_FILL_NONE);
}

}

extern "C" void kernel_launch(void* const* d_in, const int* in_sizes, int n_in, void* d_out, int out_size) {
  typedef const __nv_bfloat16* bp;
  bp x = (bp)d_in[0], lre = (bp)d_in[1], lim = (bp)d_in[2], bre = (bp)d_in[3], bim = (bp)d_in[4], cre = (bp)d_in[5], cim = (bp)d_in[6],
     ldt = (bp)d_in[7], dsk = (bp)d_in[8], w1 = (bp)d_in[10], b1 = (bp)d_in[11], w2 = (bp)d_in[12], b2 = (bp)d_in[13], gw = (bp)d_in[14];
  static EncFn enc = nullptr;
  if (!enc) {
    void* f = nullptr;
    cudaDriverEntryPointQueryResult qr;
    cudaGetDriverEntryPoint("cuTensorMapEncodeTiled", &f, cudaEnableDefault, &qr);
    enc = (EncFn)f;
    cudaFuncSetAttribute(fused_kernel, cudaFuncAttributeMaxDynamicSharedMemorySize, SMEM_BYTES);
  }
  Maps maps;
  {
    cuuint64_t d[5] = {DM, 2, 4, 8, SEQ / 64}, st[4] = {DM * 2, 16 * DM * 2, 2 * DM * 2, 64 * DM * 2};
    cuuint32_t bx[5] = {64, 2, 4, 8, 1};
    encode(enc, &maps.x, x, 5, d, st, bx, CU_TENSOR_MAP_SWIZZLE_128B);
  }
  {
    cuuint64_t d[2] = {DM, DM}, st[1] = {DM * 2};
    cuuint32_t bx[2] = {64, 64};
    encode(enc, &maps.bre, bre, 2, d, st, bx, CU_TENSOR_MAP_SWIZZLE_128B);
    encode(enc, &maps.bim, bim, 2, d, st, bx, CU_TENSOR_MAP_SWIZZLE_128B);
    encode(enc, &maps.cre, cre, 2, d, st, bx, CU_TENSOR_MAP_SWIZZLE_128B);
    encode(enc, &maps.cim, cim, 2, d, st, bx, CU_TENSOR_MAP_SWIZZLE_128B);
  }
  {
    cuuint64_t d[2] = {FF, DM}, st[1] = {FF * 2};
    cuuint32_t bx[2] = {64, 64};
    encode(enc, &maps.w1a, w1, 2, d, st, bx, CU_TENSOR_MAP_SWIZZLE_128B);
    cuuint64_t d3[3] = {32, DM, FF / 32}, st3[2] = {FF * 2, 64};
    cuuint32_t bx3[3] = {32, 64, 3};
    encode(enc, &maps.w1b, w1, 3, d3, st3, bx3, CU_TENSOR_MAP_SWIZZLE_64B);
  }
  {
    cuuint64_t d[2] = {DM, FF}, st[1] = {DM * 2};
    cuuint32_t bx[2] = {64, 112};
    encode(enc, &maps.w2, w2, 2, d, st, bx, CU_TENSOR_MAP_SWIZZLE_128B);
  }
  fused_kernel<<<128, 384, SMEM_BYTES>>>(lre, lim, ldt, dsk, b1, b2, gw, w1, w2, cre, cim, (float*)d_out, maps);
}
```

```cpp
#include <cuda_runtime.h>
#include <cuda_bf16.h>
#include <cuda.h>
#include <stdint.h>

#define MAP 1
#define D0 200
#define D1 480
#define PF 4
#define PFK 5
#define GELUP 1
#define EW 2
#define K1E 1
#define K2E 0
#define QS 1
#define K2G 4
#define FINP 4
#define LBD 300
#define PFS 32
#define SB0 2
#define PFD 2
#define HOLD 0
#define GAP 14
#define FINW 0
#define K0P 33
#define K1P 53
#define TMP2 1
#define W0 1
#define LCK 4
#define TOKA 0
#define TOKB 2
#define TOKD 0
#define TKT 999
#define AV 3
#define QK 4
#define TCUT {1, 6, 6, 11, 16}
#define SCUT {0, 0, 0, 0, 0, 0, 8, 16, 24}
#define PV 2
#define KCUT {4, 8, 12, 15, 18}
#define GCUT {6, 12, 18, 24}
#define TP 9
#define TW 0

namespace {

constexpr int SEQ = 2048, DM = 512, FF = 1792;
constexpr int NSLOT = 6;
constexpr uint32_t OFF_X = 0, OFF_RING = 131072, OFF_MISC = 229376;
constexpr uint32_t OFF_XFULL = OFF_MISC, OFF_FULL = OFF_XFULL + 64, OFF_RBAR = OFF_FULL + 48, OFF_EMPTY = OFF_RBAR + 16, OFF_KBAR = OFF_EMPTY + 48,
                   OFF_GBAR = OFF_KBAR + 16, OFF_LBAR = OFF_GBAR + 8, OFF_CBAR = OFF_LBAR + 8, OFF_EPOCH = OFF_CBAR + 8;
constexpr uint32_t OFF_LC = OFF_MISC + 256;
constexpr uint32_t OFF_GS = OFF_LC;
constexpr uint32_t OFF_GT = OFF_LC + 256;
constexpr uint32_t OFF_DB = OFF_LC + 512;
constexpr uint32_t OFF_CARRY = OFF_LC + 1024;
constexpr uint32_t OFF_DBG = OFF_CARRY + 1024;
constexpr uint32_t SMEM_BYTES = OFF_DBG + 768;
static_assert(SMEM_BYTES <= 232448, "smem");

struct Maps { CUtensorMap x, bre, bim, w1b, w1a, w2, cre, cim; };
__host__ __device__ constexpr uint32_t stage_off(int p) { return 49152 + 45056 * (((p >> 1) & 1) + 2 * (p & 1)); }

__host__ __device__ constexpr uint32_t full_par(int u) { return ((u - 8) / 6 + (u % 6 == 0)) & 1; }

__device__ uint4 g_part[16 * 8 * 3 * 1024];
__device__ float2 g_end[8 * 16 * 64];
__device__ unsigned g_gate[SEQ];
__device__ unsigned g_epoch[128];
#define TG(role) do {} while (0)
#define TS2(role, i) do {} while (0)
#define TS(role, i) do {} while (0)
#define TDUMP() do {} while (0)
#define TR(i) do {} while (0)
#define TK(i) do {} while (0)
#define TRD() do {} while (0)

__device__ __forceinline__ void mbar_init(uint32_t bar, uint32_t cnt) { asm volatile("mbarrier.init.shared::cta.b64 [%0], %1;" ::"r"(bar), "r"(cnt)); }
__device__ __forceinline__ void mbar_expect_tx(uint32_t bar, uint32_t bytes) { asm volatile("mbarrier.arrive.expect_tx.shared::cta.b64 _, [%0], %1;" ::"r"(bar), "r"(bytes) : "memory"); }
__device__ __forceinline__ void mbar_arrive(uint32_t bar) { asm volatile("mbarrier.arrive.shared::cta.b64 _, [%0];" ::"r"(bar) : "memory"); }
__device__ __forceinline__ void mbar_arrive_cl(uint32_t cbar) { asm volatile("mbarrier.arrive.shared::cluster.b64 _, [%0];" ::"r"(cbar) : "memory"); }
__device__ __forceinline__ void mbar_wait(uint32_t bar, uint32_t parity) {
  asm volatile(
      "{\n.reg .pred p;\n.reg .u32 c;\n"
      "mbarrier.try_wait.parity.shared::cta.b64 p, [%0], %1;\n"
      "@p bra.uni LAB_DONE;\n"
      "mov.u32 c, 0;\n"
      "LAB_WAIT:\n"
      "mbarrier.try_wait.parity.shared::cta.b64 p, [%0], %1;\n"
      "@p bra.uni LAB_DONE;\n"
      "add.u32 c, c, 1;\nsetp.lt.u32 p, c, 200000;\n@p bra.uni LAB_WAIT;\n"
      "LAB_DONE:\n}" ::"r"(bar), "r"(parity) : "memory");
}
__device__ __forceinline__ void tma2d(uint32_t dst, const CUtensorMap* m, int c0, int c1, uint32_t bar) {
  asm volatile("cp.async.bulk.tensor.2d.shared::cluster.global.mbarrier::complete_tx::bytes [%0], [%1, {%3,%4}], [%2];"
               ::"r"(dst), "l"(m), "r"(bar), "r"(c0), "r"(c1) : "memory");
}
__device__ __forceinline__ void tma3d(uint32_t dst, const CUtensorMap* m, int c0, int c1, int c2, uint32_t bar) {
  asm volatile("cp.async.bulk.tensor.3d.shared::cluster.global.mbarrier::complete_tx::bytes [%0], [%1, {%3,%4,%5}], [%2];"
               ::"r"(dst), "l"(m), "r"(bar), "r"(c0), "r"(c1), "r"(c2) : "memory");
}
__device__ __forceinline__ void tma5d(uint32_t dst, const CUtensorMap* m, int c0, int c4, uint32_t bar) {
  asm volatile("cp.async.bulk.tensor.5d.shared::cluster.global.mbarrier::complete_tx::bytes [%0], [%1, {%3,%5,%5,%5,%4}], [%2];"
               ::"r"(dst), "l"(m), "r"(bar), "r"(c0), "r"(c4), "r"(0) : "memory");
}
__device__ __forceinline__ void tma5d_mc(uint32_t dst, const CUtensorMap* m, int c0, int c4, uint32_t bar) {
  asm volatile("cp.async.bulk.tensor.5d.shared::cluster.global.mbarrier::complete_tx::bytes.multicast::cluster [%0], [%1, {%3,%5,%5,%5,%4}], [%2], %6;"
               ::"r"(dst), "l"(m), "r"(bar), "r"(c0), "r"(c4), "r"(0), "h"((uint16_t)3) : "memory");
}
__device__ __forceinline__ void l2_prefetch(const void* p, uint32_t bytes) { asm volatile("cp.async.bulk.prefetch.L2.global [%0], %1;" ::"l"(p), "r"(bytes) : "memory"); }
__device__ __forceinline__ bool elect_one() {
  uint32_t pred;
  asm volatile("{.reg .pred P; elect.sync _|P, 0xffffffff; selp.u32 %0, 1, 0, P;}" : "=r"(pred));
  return pred != 0;
}
__device__ __forceinline__ void wg_fence() { asm volatile("wgmma.fence.sync.aligned;" ::: "memory"); }
__device__ __forceinline__ void wg_commit() { asm volatile("wgmma.commit_group.sync.aligned;" ::: "memory"); }
template <int N> __device__ __forceinline__ void wg_wait() { asm volatile("wgmma.wait_group.sync.aligned %0;" ::"n"(N) : "memory"); }
__device__ __forceinline__ void pin(float& a) { asm volatile("" : "+f"(a)::"memory"); }
__device__ __forceinline__ void pin(uint32_t& a) { asm volatile("" : "+r"(a)::"memory"); }
template <int N> __device__ __forceinline__ void reg_fence(float (&d)[N]) {
#pragma unroll
  for (int i = 0; i < N; i++) pin(d[i]);
}
__device__ __forceinline__ void bar_sync(int id, int n) { asm volatile("bar.sync %0, %1;" ::"r"(id), "r"(n) : "memory"); }
__device__ __forceinline__ void bar_arrive(int id, int n) { asm volatile("bar.arrive %0, %1;" ::"r"(id), "r"(n) : "memory"); }
constexpr uint32_t DH128 = (1024 >> 4) | (1u << 30), DH64 = (512 >> 4) | (2u << 30);
__host__ __device__ constexpr uint32_t lbo(uint32_t bytes) { return (bytes >> 4) << 20; }
__device__ __forceinline__ uint32_t pack_bf16(float lo, float hi) { uint32_t r; asm("cvt.rn.bf16x2.f32 %0, %1, %2;" : "=r"(r) : "f"(hi), "f"(lo)); return r; }
__device__ __forceinline__ float bf_lo(uint32_t v) { return __uint_as_float(v << 16); }
__device__ __forceinline__ float bf_hi(uint32_t v) { return __uint_as_float(v & 0xffff0000u); }
__device__ __forceinline__ float bf_ld(const __nv_bfloat16* p) { return __bfloat162float(__ldg(p)); }
__device__ __forceinline__ uint32_t late16(uint32_t bar) {
  uint32_t r;
  asm volatile("{.reg .pred p; mbarrier.test_wait.parity.shared::cta.b64 p, [%1], 0; selp.u32 %0, 16, 0, p;}" : "=r"(r) : "r"(bar) : "memory");
  return r;
}
__device__ __forceinline__ float2 lds_f2(uint32_t a) { float2 v; asm volatile("ld.shared.v2.f32 {%0,%1}, [%2];" : "=f"(v.x), "=f"(v.y) : "r"(a)); return v; }
__device__ __forceinline__ uint32_t lds_h(uint32_t a) { uint32_t v; asm volatile("ld.shared.u16 %0, [%1];" : "=r"(v) : "r"(a)); return v; }
__device__ __forceinline__ uint32_t lds_u(uint32_t a) { uint32_t v; asm volatile("ld.shared.u32 %0, [%1];" : "=r"(v) : "r"(a)); return v; }
__device__ __forceinline__ uint4 lds_u4(uint32_t a) { uint4 v; asm volatile("ld.shared.v4.u32 {%0,%1,%2,%3}, [%4];" : "=r"(v.x), "=r"(v.y), "=r"(v.z), "=r"(v.w) : "r"(a)); return v; }
__device__ __forceinline__ void st_b128(uint4* p, uint32_t a, uint32_t b, uint32_t c, uint32_t d) {
  asm volatile("st.relaxed.gpu.global.v4.b32 [%0], {%1,%2,%3,%4};" ::"l"(p), "r"(a), "r"(b), "r"(c), "r"(d) : "memory");
}
__device__ __forceinline__ void ld_b128(const uint4* p, uint32_t& a, uint32_t& b, uint32_t& c, uint32_t& d) {
  asm volatile("{.reg .b64 l, h; .reg .b128 v; ld.relaxed.gpu.global.b128 v, [%4]; mov.b128 {l,h}, v; mov.b64 {%0,%1}, l; mov.b64 {%2,%3}, h;}"
               : "=r"(a), "=r"(b), "=r"(c), "=r"(d) : "l"(p) : "memory");
}
__device__ __forceinline__ float tanh_fast(float x) { float y; asm("tanh.approx.f32 %0, %1;" : "=f"(y) : "f"(x)); return y; }
__device__ __forceinline__ float gelu2(float v) {
  float p = fmaf(v * v, 0.0356774081363f, 0.7978845608029f);
  return fmaf(v, tanh_fast(v * p), v);
}
__device__ __forceinline__ void sched_fence(uint32_t& ck) { asm volatile("{.reg .b32 c; mov.u32 c, %%clock; xor.b32 %0, %0, c;}" : "+r"(ck)::"memory"); }
__device__ __forceinline__ uint32_t bf2_mul(uint32_t a, uint32_t b) { uint32_t r; asm("mul.rn.bf16x2 %0, %1, %2;" : "=r"(r) : "r"(a), "r"(b)); return r; }
__device__ __forceinline__ uint32_t bf2_add(uint32_t a, uint32_t b) { uint32_t r; asm("add.rn.bf16x2 %0, %1, %2;" : "=r"(r) : "r"(a), "r"(b)); return r; }
__device__ __forceinline__ uint32_t bf2_fma(uint32_t a, uint32_t b, uint32_t c) { uint32_t r; asm("fma.rn.bf16x2 %0, %1, %2, %3;" : "=r"(r) : "r"(a), "r"(b), "r"(c)); return r; }
__device__ __forceinline__ uint32_t gelu2_pair(float a, float b) {
  const uint32_t v = pack_bf16(a, b);
  uint32_t t;
  asm("tanh.approx.bf16x2 %0, %1;" : "=r"(t) : "r"(bf2_fma(v, bf2_fma(bf2_mul(v, v), 0x3d123d12u, 0xbe4fbe4fu), v)));
  return bf2_fma(v, t, v);
}
struct cplx { float re, im; };
__device__ __forceinline__ cplx cmul(cplx a, cplx b) { return {fmaf(a.re, b.re, -a.im * b.im), fmaf(a.re, b.im, a.im * b.re)}; }
__device__ __forceinline__ cplx cfma(cplx a, cplx b, cplx c) {
  return {fmaf(a.re, b.re, fmaf(-a.im, b.im, c.re)), fmaf(a.re, b.im, fmaf(a.im, b.re, c.im))};
}
__device__ __forceinline__ cplx make_lam(float lre, float lim, float ldt) {
  float dt = __bfloat162float(__float2bfloat16_rn(expf(ldt)));
  float mag = expf(dt * lre), sn, cs;
  sincospif(dt * lim * 0.31830988618379067f, &sn, &cs);
  return {mag * cs, mag * sn};
}

template<int TA,int TB,uint32_t AH,uint32_t BH> __device__ __forceinline__ void wgmma_n64_ss(float (&d)[32], uint32_t al, uint32_t ao, uint32_t bl, uint32_t bo, int scale_d){
  asm volatile("{.reg .pred p; .reg .b32 t, v; .reg .b64 da, db; setp.ne.b32 p, %36, 0; add.u32 t, %32, %33; mov.b64 da, {t, %39}; add.u32 v, %34, %35; mov.b64 db, {v, %40};\n"
   "wgmma.mma_async.sync.aligned.m64n64k16.f32.bf16.bf16 {%0,%1,%2,%3,%4,%5,%6,%7,%8,%9,%10,%11,%12,%13,%14,%15,%16,%17,%18,%19,%20,%21,%22,%23,%24,%25,%26,%27,%28,%29,%30,%31}, da, db, p, 1, 1, %37, %38;}"
   : "+f"(d[0]),"+f"(d[1]),"+f"(d[2]),"+f"(d[3]),"+f"(d[4]),"+f"(d[5]),"+f"(d[6]),"+f"(d[7]),"+f"(d[8]),"+f"(d[9]),"+f"(d[10]),"+f"(d[11]),"+f"(d[12]),"+f"(d[13]),"+f"(d[14]),"+f"(d[15]),"+f"(d[16]),"+f"(d[17]),"+f"(d[18]),"+f"(d[19]),"+f"(d[20]),"+f"(d[21]),"+f"(d[22]),"+f"(d[23]),"+f"(d[24]),"+f"(d[25]),"+f"(d[26]),"+f"(d[27]),"+f"(d[28]),"+f"(d[29]),"+f"(d[30]),"+f"(d[31])
   : "r"(al),"r"(ao >> 4),"r"(bl),"r"(bo >> 4),"r"(scale_d),"n"(TA),"n"(TB),"n"(AH),"n"(BH));
}
template<int TB,uint32_t BH,int SA=1> __device__ __forceinline__ void wgmma_n64_rs(float (&d)[32], uint32_t a0,uint32_t a1,uint32_t a2,uint32_t a3, uint32_t bl, uint32_t bo, int scale_d){
  asm volatile("{.reg .pred p; .reg .b32 t; .reg .b64 db; setp.ne.b32 p, %38, 0; add.u32 t, %36, %37; mov.b64 db, {t, %40};\n"
   "wgmma.mma_async.sync.aligned.m64n64k16.f32.bf16.bf16 {%0,%1,%2,%3,%4,%5,%6,%7,%8,%9,%10,%11,%12,%13,%14,%15,%16,%17,%18,%19,%20,%21,%22,%23,%24,%25,%26,%27,%28,%29,%30,%31}, {%32,%33,%34,%35}, db, p, %41, 1, %39;}"
   : "+f"(d[0]),"+f"(d[1]),"+f"(d[2]),"+f"(d[3]),"+f"(d[4]),"+f"(d[5]),"+f"(d[6]),"+f"(d[7]),"+f"(d[8]),"+f"(d[9]),"+f"(d[10]),"+f"(d[11]),"+f"(d[12]),"+f"(d[13]),"+f"(d[14]),"+f"(d[15]),"+f"(d[16]),"+f"(d[17]),"+f"(d[18]),"+f"(d[19]),"+f"(d[20]),"+f"(d[21]),"+f"(d[22]),"+f"(d[23]),"+f"(d[24]),"+f"(d[25]),"+f"(d[26]),"+f"(d[27]),"+f"(d[28]),"+f"(d[29]),"+f"(d[30]),"+f"(d[31])
   : "r"(a0),"r"(a1),"r"(a2),"r"(a3),"r"(bl),"r"(bo >> 4),"r"(scale_d),"n"(TB),"n"(BH),"n"(SA));
}
template<int TA,int TB,uint32_t AH,uint32_t BH> __device__ __forceinline__ void wgmma_n96_ss(float (&d)[48], uint32_t al, uint32_t ao, uint32_t bl, uint32_t bo, int scale_d){
  asm volatile("{.reg .pred p; .reg .b32 t, v; .reg .b64 da, db; setp.ne.b32 p, %52, 0; add.u32 t, %48, %49; mov.b64 da, {t, %55}; add.u32 v, %50, %51; mov.b64 db, {v, %56};\n"
   "wgmma.mma_async.sync.aligned.m64n96k16.f32.bf16.bf16 {%0,%1,%2,%3,%4,%5,%6,%7,%8,%9,%10,%11,%12,%13,%14,%15,%16,%17,%18,%19,%20,%21,%22,%23,%24,%25,%26,%27,%28,%29,%30,%31,%32,%33,%34,%35,%36,%37,%38,%39,%40,%41,%42,%43,%44,%45,%46,%47}, da, db, p, 1, 1, %53, %54;}"
   : "+f"(d[0]),"+f"(d[1]),"+f"(d[2]),"+f"(d[3]),"+f"(d[4]),"+f"(d[5]),"+f"(d[6]),"+f"(d[7]),"+f"(d[8]),"+f"(d[9]),"+f"(d[10]),"+f"(d[11]),"+f"(d[12]),"+f"(d[13]),"+f"(d[14]),"+f"(d[15]),"+f"(d[16]),"+f"(d[17]),"+f"(d[18]),"+f"(d[19]),"+f"(d[20]),"+f"(d[21]),"+f"(d[22]),"+f"(d[23]),"+f"(d[24]),"+f"(d[25]),"+f"(d[26]),"+f"(d[27]),"+f"(d[28]),"+f"(d[29]),"+f"(d[30]),"+f"(d[31]),"+f"(d[32]),"+f"(d[33]),"+f"(d[34]),"+f"(d[35]),"+f"(d[36]),"+f"(d[37]),"+f"(d[38]),"+f"(d[39]),"+f"(d[40]),"+f"(d[41]),"+f"(d[42]),"+f"(d[43]),"+f"(d[44]),"+f"(d[45]),"+f"(d[46]),"+f"(d[47])
   : "r"(al),"r"(ao >> 4),"r"(bl),"r"(bo >> 4),"r"(scale_d),"n"(TA),"n"(TB),"n"(AH),"n"(BH));
}
template<int TA,int TB,uint32_t AH,uint32_t BH> __device__ __forceinline__ void wgmma_n128_ss(float (&d)[64], uint32_t al, uint32_t ao, uint32_t bl, uint32_t bo, int scale_d){
  asm volatile("{.reg .pred p; .reg .b32 t, v; .reg .b64 da, db; setp.ne.b32 p, %68, 0; add.u32 t, %64, %65; mov.b64 da, {t, %71}; add.u32 v, %66, %67; mov.b64 db, {v, %72};\n"
   "wgmma.mma_async.sync.aligned.m64n128k16.f32.bf16.bf16 {%0,%1,%2,%3,%4,%5,%6,%7,%8,%9,%10,%11,%12,%13,%14,%15,%16,%17,%18,%19,%20,%21,%22,%23,%24,%25,%26,%27,%28,%29,%30,%31,%32,%33,%34,%35,%36,%37,%38,%39,%40,%41,%42,%43,%44,%45,%46,%47,%48,%49,%50,%51,%52,%53,%54,%55,%56,%57,%58,%59,%60,%61,%62,%63}, da, db, p, 1, 1, %69, %70;}"
   : "+f"(d[0]),"+f"(d[1]),"+f"(d[2]),"+f"(d[3]),"+f"(d[4]),"+f"(d[5]),"+f"(d[6]),"+f"(d[7]),"+f"(d[8]),"+f"(d[9]),"+f"(d[10]),"+f"(d[11]),"+f"(d[12]),"+f"(d[13]),"+f"(d[14]),"+f"(d[15]),"+f"(d[16]),"+f"(d[17]),"+f"(d[18]),"+f"(d[19]),"+f"(d[20]),"+f"(d[21]),"+f"(d[22]),"+f"(d[23]),"+f"(d[24]),"+f"(d[25]),"+f"(d[26]),"+f"(d[27]),"+f"(d[28]),"+f"(d[29]),"+f"(d[30]),"+f"(d[31]),"+f"(d[32]),"+f"(d[33]),"+f"(d[34]),"+f"(d[35]),"+f"(d[36]),"+f"(d[37]),"+f"(d[38]),"+f"(d[39]),"+f"(d[40]),"+f"(d[41]),"+f"(d[42]),"+f"(d[43]),"+f"(d[44]),"+f"(d[45]),"+f"(d[46]),"+f"(d[47]),"+f"(d[48]),"+f"(d[49]),"+f"(d[50]),"+f"(d[51]),"+f"(d[52]),"+f"(d[53]),"+f"(d[54]),"+f"(d[55]),"+f"(d[56]),"+f"(d[57]),"+f"(d[58]),"+f"(d[59]),"+f"(d[60]),"+f"(d[61]),"+f"(d[62]),"+f"(d[63])
   : "r"(al),"r"(ao >> 4),"r"(bl),"r"(bo >> 4),"r"(scale_d),"n"(TA),"n"(TB),"n"(AH),"n"(BH));
}

__global__ void __cluster_dims__(2, 1, 1) __launch_bounds__(384, 1)
fused_kernel(const __nv_bfloat16* __restrict__ lam_re, const __nv_bfloat16* __restrict__ lam_im, const __nv_bfloat16* __restrict__ log_dt,
             const __nv_bfloat16* __restrict__ dskip, const __nv_bfloat16* __restrict__ b1, const __nv_bfloat16* __restrict__ b2,
             const __nv_bfloat16* __restrict__ gate_w, const __nv_bfloat16* __restrict__ pf_w1, const __nv_bfloat16* __restrict__ pf_w2,
             const __nv_bfloat16* __restrict__ pf_cre, const __nv_bfloat16* __restrict__ pf_cim, float* __restrict__ out,
             const __grid_constant__ Maps maps) {
  extern __shared__ __align__(1024) unsigned char smem_raw[];
  const uint32_t sb = (uint32_t)__cvta_generic_to_shared(smem_raw);
  const int b = blockIdx.x;
  const int rank = b & 1, cl = b >> 1;
  const int sp = (cl & 1) | ((cl >> 2) & 2), m = ((cl >> 1) & 3) | ((cl >> 4) << 2);
  const int s = sp * 2 + rank;
  const int warp = __shfl_sync(0xffffffffu, (int)(threadIdx.x >> 5), 0);
  const int lane = threadIdx.x & 31;
  const int xrot = 9 - 2 * sp;

  if (elect_one()) {
    if (warp == 8) TS(2, 0);
    if (warp > 8) {
      asm volatile("prefetch.tensormap [%0];" ::"l"(&maps.x + (warp - 9)) : "memory");
      mbar_init(sb + OFF_GBAR + 8 * (warp - 9), warp < 11 ? 64 : 96);
    }
    const uint32_t c = warp < 8 ? 1 : warp < 11 ? 8 : 4, bar = sb + OFF_XFULL + 16 * warp;
    mbar_init(bar, c);
    if ((warp & 11) == 0) {
      mbar_expect_tx(bar, 16384);
      if (warp == 0) {
        tma5d(sb + OFF_X + (xrot & 7) * 16384, &maps.x, 0, 2 * m, bar);
        tma5d(sb + OFF_X + (xrot & 7) * 16384 + 8192, &maps.x, 0, 2 * m + 1, bar);
        TS(2, 3);
      } else {
        tma2d(sb + OFF_RING, &maps.bre, 0, s * 64, bar);
        tma2d(sb + OFF_RING + 8192, &maps.bim, 0, s * 64, bar);
        TS(2, 4);
      }
    }
    mbar_init(bar + 8, c);
    asm volatile("fence.mbarrier_init.release.cluster;" ::: "memory");
  }
  __syncwarp();
  asm volatile("barrier.cluster.arrive.relaxed.aligned;" ::: "memory");

  if (warp < 8) {
    const int wg = warp >> 2, w = warp & 3, q = lane & 3, gr = lane >> 2;
    uint32_t bv[28];
#pragma unroll
    for (int j = 0; j < 28; j++) bv[j] = __ldg(reinterpret_cast<const uint32_t*>(b1 + s * 224 + j * 8) + q);
    asm volatile("setmaxnreg.inc.sync.aligned.u32 224;");
    asm volatile("barrier.cluster.wait.aligned;" ::: "memory");
    TS(wg, 0);
    auto release = [&](int slot) { if (lane == 0) mbar_arrive(sb + OFF_EMPTY + 8 * slot); };
    const uint32_t xw = sb + OFF_X + wg * 8192, fullb = sb + OFF_FULL;
    const uint32_t dxw = (xw & 0x3FFFF) >> 4, dring = ((sb + OFF_RING) & 0x3FFFF) >> 4;

    float ure[32], uim[32], aa[48], ab[64];
    cplx lam[2], coef[2], l16[2], l32[2], lq[2], pre[2], e[2];
    uint32_t sh16, mhi, ck = 0;

    auto bias = [&](int c) {
#pragma unroll
      for (int j = c * 7; j < c * 7 + 7; j++) {
        pin(bv[j]);
        float* d = j < 12 ? aa + 4 * j : ab + 4 * (j - 12);
        d[0] = d[2] = __uint_as_float(bv[j] << sh16); d[1] = d[3] = __uint_as_float(bv[j] & mhi);
        pin(d[0]); pin(d[1]); pin(d[2]); pin(d[3]);
      }
    };
#pragma unroll
    for (int kb = 0; kb < 8; kb++) {
      const int slot = kb % NSLOT;
      mbar_wait(sb + OFF_XFULL + 8 * kb, 0);
      if (kb == 0) TS(wg, 18);
      if (kb == 0) mbar_wait(fullb, 0);
      TS2(2, kb);
      if (kb == 0) TS(wg, 1);
      if (kb == SB0) { sh16 = late16(sb + OFF_XFULL); mhi = 0xffffffffu << sh16; }
      if (kb == LCK) {
        mbar_wait(sb + OFF_LBAR, 0);
#pragma unroll
        for (int h = 0; h < 2; h++) {
          const uint4 v = lds_u4(sb + OFF_LC + (w * 16 + gr + 8 * h) * 16);
          lam[h] = cplx{__uint_as_float(v.x), __uint_as_float(v.y)};
          coef[h] = cplx{__uint_as_float(v.z), __uint_as_float(v.w)};
        }
      }
      wg_fence();
      const uint32_t dxa = dxw + ((kb + xrot) & 7) * 1024;
#pragma unroll
      for (int kk = 0; kk < 4; kk++) {
        wgmma_n64_ss<0, 0, DH128, DH128>(ure, dring, slot * 16384 + kk * 32, dxa, kk * 32, (kb | kk) != 0);
        wgmma_n64_ss<0, 0, DH128, DH128>(uim, dring, slot * 16384 + 8192 + kk * 32, dxa, kk * 32, (kb | kk) != 0);
      }
      wg_commit();
      if (kb > 0) { wg_wait<1>(); release((kb - 1) % NSLOT); }
      if (kb >= SB0 && kb < SB0 + 3) bias(kb - SB0);
      if (kb == 6) {
#pragma unroll
        for (int h = 0; h < 2; h++) {
          pin(lam[h].re); pin(lam[h].im);
          cplx t = cmul(lam[h], lam[h]); t = cmul(t, t); t = cmul(t, t);
          l16[h] = cmul(t, t);
          pin(l16[h].re); pin(l16[h].im);
        }
      }
      if (kb == 7) {
#pragma unroll
        for (int h = 0; h < 2; h++) {
          pin(l16[h].re); pin(l16[h].im);
          l32[h] = cmul(l16[h], l16[h]);
          const cplx a = (q & 1) ? l16[h] : cplx{1.f, 0.f}, c = (q & 2) ? l32[h] : cplx{1.f, 0.f};
          lq[h] = cmul(cmul(a, c), coef[h]);
          pin(lq[h].re); pin(lq[h].im);
        }
      }
    }
    TS(wg, 2);
    auto scale_u = [&](int i0, int i1) {
#pragma unroll
      for (int i = 0; i < 32; i++) if (i >= i0 && i < i1) {
        pin(ure[i]); pin(uim[i]);
        const cplx v = cmul(coef[(i >> 1) & 1], cplx{ure[i], uim[i]});
        ure[i] = v.re; uim[i] = v.im;
        pin(ure[i]); pin(uim[i]);
      }
    };
#pragma unroll
    for (int kb = 0; kb < 8; kb++) {
      const int u = 8 + kb, slot = u % NSLOT;
      mbar_wait(fullb + 8 * slot, full_par(u));
      TK(kb);
      wg_fence();
      const uint32_t dxa = dxw + ((kb + xrot) & 7) * 1024;
#pragma unroll
      for (int kk = 0; kk < 4; kk++)
        wgmma_n96_ss<0, 1, DH128, DH64>(aa, dxa, kk * 32, dring, slot * 16384 + kk * 1024 + lbo(4096), 1);
      wg_commit();
      if (kb == 0) bias(3);
      if (kb != QK) { wg_wait<1>(); release((u - 1) % NSLOT); }
      if (kb == 0) {
        reg_fence(ure); reg_fence(uim);
#pragma unroll
        for (int h = 0; h < 2; h++) e[h] = cplx{ure[2 * h], uim[2 * h]};
      }
      if (kb == 0 || (kb >= 2 && kb <= QK && kb < 4)) {
        constexpr int tc[5] = TCUT;
#pragma unroll
        for (int t = 1; t < 16; t++) if (t >= tc[kb] && t < tc[kb + 1]) {
#pragma unroll
          for (int h = 0; h < 2; h++) { const int i = 4 * (t >> 1) + 2 * h + (t & 1); e[h] = cfma(lam[h], e[h], cplx{ure[i], uim[i]}); }
        }
#pragma unroll
        for (int h = 0; h < 2; h++) { pin(e[h].re); pin(e[h].im); }
      }
      if (kb == QK) {
        sched_fence(ck);
#pragma unroll
        for (int h = 0; h < 2; h++) {
          cplx y = {__shfl_up_sync(0xffffffffu, e[h].re, 1, 4), __shfl_up_sync(0xffffffffu, e[h].im, 1, 4)};
          if (q >= 1) e[h] = cfma(l16[h], y, e[h]);
          y = cplx{__shfl_up_sync(0xffffffffu, e[h].re, 2, 4), __shfl_up_sync(0xffffffffu, e[h].im, 2, 4)};
          if (q >= 2) e[h] = cfma(l32[h], y, e[h]);
        }
        if (q == 3) {
#pragma unroll
          for (int h = 0; h < 2; h++)
            asm volatile("st.shared.v2.f32 [%0], {%1,%2};" ::"r"(sb + OFF_CARRY + wg * 512 + (w * 16 + gr + 8 * h) * 8), "f"(e[h].re), "f"(e[h].im) : "memory");
          mbar_arrive(sb + OFF_GBAR);
        }
#pragma unroll
        for (int h = 0; h < 2; h++) e[h] = cplx{__shfl_up_sync(0xffffffffu, e[h].re, 1, 4), __shfl_up_sync(0xffffffffu, e[h].im, 1, 4)};
        wg_wait<1>(); release((u - 1) % NSLOT);
        if (TKT > 500) TS(wg, 3);
      }
      if (kb == QK + 1) {
#pragma unroll
        for (int h = 0; h < 2; h++) {
          pre[h] = (q >= 1) ? cmul(coef[h], e[h]) : cplx{0.f, 0.f};
          pin(pre[h].re); pin(pre[h].im);
        }
      }
      if (kb > QK) { constexpr int sc[9] = SCUT; scale_u(sc[kb], sc[kb + 1]); }
    }
    TS(wg, 4);
    uint32_t H[56], hf[32];
    cplx hst[2];
    const uint32_t hst_addr = xw + (w * 16 + (lane & 15)) * 128 + (((lane >> 4) ^ (lane & 7)) << 4);
    const uint32_t him = (2 - rank) * 16384;
    uint32_t peer;
    asm volatile("mapa.shared::cluster.u32 %0, %1, %2;" : "=r"(peer) : "r"(sb), "r"(rank ^ 1));
    auto credit = [&]() { if (lane == 0) mbar_arrive_cl(peer + OFF_KBAR + wg * 8); };
    uint32_t g2[8];
#pragma unroll
    for (int kb = 0; kb < 8; kb++) {
      const int u = 16 + kb, slot = u % NSLOT;
      mbar_wait(fullb + 8 * slot, full_par(u));
      TK(kb < 7 ? 24 + kb : 32);
      wg_fence();
#pragma unroll
      for (int kk = 0; kk < 4; kk++)
        wgmma_n128_ss<0, 1, DH128, DH128>(ab, dxw, kb * 16384 + kk * 32, dring, slot * 16384 + kk * 2048 + lbo(8192), 1);
      wg_commit();
      if (kb == 0) { constexpr int sc[9] = SCUT; scale_u(sc[8], 32); }
      if (kb == 4) {
        if (TKT > 500) TS(wg, 5);
        mbar_wait(sb + OFF_CBAR, 0);
        if (TKT > 500) TS(wg, 6);
#pragma unroll
        for (int h = 0; h < 2; h++) {
          const float2 c = lds_f2(sb + OFF_CARRY + wg * 512 + (w * 16 + gr + 8 * h) * 8);
          hst[h] = cfma(lq[h], cplx{c.x, c.y}, pre[h]);
        }
#pragma unroll
        for (int i = 0; i < 2; i++) {
          const uint4 v = lds_u4(sb + OFF_GT + wg * 128 + q * 32 + i * 16);
          g2[4 * i] = v.x; g2[4 * i + 1] = v.y; g2[4 * i + 2] = v.z; g2[4 * i + 3] = v.w;
        }
      }
      if (kb == 0 || TOKB != 1) { wg_wait<1>(); release((u - 1) % NSLOT); }
      if (kb) sched_fence(ck);
      if (kb < 4) {
#pragma unroll
        for (int i = kb * 6; i < kb * 6 + 6; i++) {
          pin(aa[2 * i]); pin(aa[2 * i + 1]);
          H[i] = gelu2_pair(aa[2 * i], aa[2 * i + 1]);
          pin(H[i]);
        }
      } else {
        const int j0 = (kb - 4) * 2;
        uint32_t rr[4], ri[4];
#pragma unroll
        for (int jj = 0; jj < 2; jj++) {
          const int j = j0 + jj;
#pragma unroll
          for (int h = 0; h < 2; h++) {
            const int i = 4 * j + 2 * h;
            const cplx h0 = cfma(lam[h], hst[h], cplx{ure[i], uim[i]});
            hst[h] = cfma(lam[h], h0, cplx{ure[i + 1], uim[i + 1]});
            rr[jj * 2 + h] = bf2_mul(pack_bf16(h0.re, hst[h].re), g2[j]);
            ri[jj * 2 + h] = bf2_mul(pack_bf16(h0.im, hst[h].im), g2[j]);
          }
        }
        const uint32_t a = hst_addr ^ (j0 << 4);
        asm volatile("stmatrix.sync.aligned.m8n8.x4.shared.b16 [%0], {%1,%2,%3,%4};" ::"r"(a), "r"(rr[0]), "r"(rr[1]), "r"(rr[2]), "r"(rr[3]) : "memory");
        asm volatile("stmatrix.sync.aligned.m8n8.x4.shared.b16 [%0], {%1,%2,%3,%4};" ::"r"(a + him), "r"(ri[0]), "r"(ri[1]), "r"(ri[2]), "r"(ri[3]) : "memory");
      }
      if (kb && TOKB == 1) { wg_wait<1>(); release((u - 1) % NSLOT); }
    }
    TS(wg, 7);

    uint4* const psend = g_part + (size_t)(m * 8 + rank) * 3072 + warp * 128 + lane;
    const uint4* const precv = g_part + (size_t)(m * 8 + s) * 3072 + warp * 128 + lane;
    const uint32_t pbuf = OFF_X + warp * 2048 + lane * 16;
    const uint32_t dx0 = ((sb + OFF_X) & 0x3FFFF) >> 4;
    float o[32], fin[32], rho[2];
    uint32_t tr[8];
    uint32_t r0[16], pt[16], sum[16], tag;
    auto recv_issue = [&](uint32_t (&r)[16], int k) {
#pragma unroll
      for (int i = 0; i < 4; i++) ld_b128(precv + k * 1024 + i * 32, r[4 * i], r[4 * i + 1], r[4 * i + 2], r[4 * i + 3]);
    };
    auto stale = [&](uint32_t (&r)[16]) {
      uint32_t t0, t1, r_;
      asm("lop3.b32 %0, %1, %2, %3, 0x7e;" : "=r"(t0) : "r"(r[0]), "r"(r[4]), "r"(tag));
      asm("lop3.b32 %0, %1, %2, %3, 0x7e;" : "=r"(t1) : "r"(r[8]), "r"(r[12]), "r"(tag));
      asm volatile("{.reg .pred p; .reg .b32 t; lop3.b32 t, %1, %2, 1, 0xa8; setp.ne.u32 p, t, 0; vote.sync.any.pred p, p, 0xffffffff; selp.u32 %0, 1, 0, p;}" : "=r"(r_) : "r"(t0), "r"(t1));
      return r_ != 0;
    };
    auto recv_check = [&](uint32_t (&r)[16], int k) {
      if (__builtin_expect(stale(r), 0)) {
        int tries = 0;
#pragma unroll 1
        do { recv_issue(r, k); } while (stale(r) && ++tries < 200000);
      }
    };
    auto gelu_b = [&](int i0, int i1) {
      if (TOKD && i0) sched_fence(ck);
#pragma unroll
      for (int i = i0; i < i1; i++) {
        pin(ab[2 * i]); pin(ab[2 * i + 1]);
        H[24 + i] = gelu2_pair(ab[2 * i], ab[2 * i + 1]);
        pin(H[24 + i]);
      }
      if (TOKD == 2) sched_fence(ck);
    };
    auto step = [&](float (&d)[32], int p, int k, int acc) {
      const uint32_t wo = stage_off(p);
      if (k >= 6 && k < 14) {
        const int kk = k - 6;
        if (kk < 4) wgmma_n64_rs<0, DH128, 1>(d, hf[4 * kk], hf[4 * kk + 1], hf[4 * kk + 2], hf[4 * kk + 3], dx0, wo + 14336 + kk * 32, 1);
        else wgmma_n64_rs<0, DH128, -1>(d, hf[4 * kk], hf[4 * kk + 1], hf[4 * kk + 2], hf[4 * kk + 3], dx0, wo + 22528 + (kk - 4) * 32, 1);
      } else {
        const int kk = k < 6 ? k : k - 8;
        wgmma_n64_rs<1, DH128>(d, H[4 * kk], H[4 * kk + 1], H[4 * kk + 2], H[4 * kk + 3], dx0, wo + (kk / 7) * 30720 + (kk % 7) * 2048, k != 0 || acc);
      }
    };
    auto mma = [&](float (&d)[32], int p, int k0, int k1, int acc) {
      wg_fence();
#pragma unroll
      for (int k = k0; k < k1; k++) step(d, p, k, acc);
      wg_commit();
    };
    auto send_peer = [&]() {
#pragma unroll
      for (int i = 0; i < 4; i++)
        asm volatile("st.async.shared::cluster.mbarrier::complete_tx::bytes.v4.b32 [%0], {%1,%2,%3,%4}, [%5];" ::"r"(peer + pbuf + i * 512),
                     "r"(pack_bf16(o[8 * i], o[8 * i + 1])), "r"(pack_bf16(o[8 * i + 2], o[8 * i + 3])), "r"(pack_bf16(o[8 * i + 4], o[8 * i + 5])),
                     "r"(pack_bf16(o[8 * i + 6], o[8 * i + 7])), "r"(peer + OFF_RBAR + wg * 8) : "memory");
    };
    auto recv_peer = [&](int k) {
      mbar_wait(sb + OFF_RBAR + wg * 8, k & 1);
#pragma unroll
      for (int i = 0; i < 4; i++) { const uint4 v = lds_u4(sb + pbuf + i * 512); pt[4 * i] = v.x; pt[4 * i + 1] = v.y; pt[4 * i + 2] = v.z; pt[4 * i + 3] = v.w; }
    };
    auto send_owner = [&](float (&d)[32], int k) {
#pragma unroll
      for (int i = 0; i < 4; i++) {
#pragma unroll
        for (int c = 4 * i; c < 4 * i + 4; c++) pt[c] = bf2_add(pt[c], pack_bf16(d[2 * c], d[2 * c + 1]));
        asm("lop3.b32 %0, %0, 1, %1, 0xb8;" : "+r"(pt[4 * i]) : "r"(tag));
        st_b128(psend + (((sp + 1 + k) & 3) * 6 + k) * 1024 + i * 32, pt[4 * i], pt[4 * i + 1], pt[4 * i + 2], pt[4 * i + 3]);
      }
      __syncwarp();
      credit();
    };
    auto load_fin = [&]() {
      mbar_wait(sb + OFF_LBAR, 1);
#pragma unroll
      for (int j = 0; j < 8; j++) {
        const uint4 v = lds_u4(sb + pbuf + 16384 + (j >> 2) * 16384 + (j & 3) * 512);
        fin[4 * j] = __uint_as_float(v.x); fin[4 * j + 1] = __uint_as_float(v.y); fin[4 * j + 2] = __uint_as_float(v.z); fin[4 * j + 3] = __uint_as_float(v.w);
      }
    };
    auto ldk = [&](int pos) { if (pos == K0P) recv_issue(sum, 0); if (pos == K1P) recv_issue(r0, 1); };
    auto arm = [&]() { if ((threadIdx.x & 127) == 0) mbar_expect_tx(sb + OFF_RBAR + wg * 8, 8192); };
#pragma unroll
    for (int p = 0; p < 8; p++) {
      if (p == 0) {
        TK(40);
        mbar_wait(fullb, full_par(24));
        TK(41);
        constexpr int kc[7] = KCUT, gc[6] = GCUT;
        mma(o, 0, 0, kc[0], 0);
        bar_sync(1 + wg, 128);
        {
          const uint32_t ha = xw + ((lane >> 4) * 8 + (lane & 7)) * 128 + (((2 * w + ((lane >> 3) & 1)) ^ (lane & 7)) << 4);
#pragma unroll
          for (int kk = 0; kk < 8; kk++)
            asm volatile("ldmatrix.sync.aligned.m8n8.x4.trans.shared.b16 {%0,%1,%2,%3}, [%4];" : "=r"(hf[4 * kk]), "=r"(hf[4 * kk + 1]), "=r"(hf[4 * kk + 2]), "=r"(hf[4 * kk + 3])
                         : "r"(ha + (kk >> 2) * him + (kk & 3) * 2048) : "memory");
        }
        mbar_wait(fullb + 8, full_par(25));
        wg_wait<1>(); release(5);
        gelu_b(0, gc[0]);
        mma(o, 0, kc[0], kc[1], 0);
        gelu_b(gc[0], gc[1]);
        mma(o, 0, kc[1], kc[2], 0);
        credit();
        gelu_b(gc[1], gc[2]);
        mbar_wait(fullb + 16, full_par(26));
        mma(o, 0, kc[2], kc[3], 0);
        gelu_b(gc[2], gc[3]);
        if (kc[4] > kc[3]) mma(o, 0, kc[3], kc[4], 0);
        gelu_b(gc[3], 32);
        if (wg == 1) bar_sync(4, 256);
        mma(o, 0, kc[4], 22, 0);
      } else {
        TR(0);
        if (EW == 0 || (EW == 1 && (p & 1))) mbar_wait(sb + OFF_XFULL + 8 * p, 1);
        TR(1);
        bar_sync(3 + wg, 256);
        if (p < 7) mma(o, p, 0, 22, 0);
        else if (GAP == 0) mma(fin, p, 0, 22, 1);
        else {
          mma(fin, p, 0, GAP, 1);
          recv_peer(3);
          tag = lds_u(sb + OFF_EPOCH);
          mma(fin, p, GAP, 22, 1);
        }
      }
      if (p < 7 || wg == 0) bar_arrive(4 - wg, 256);
      TR(2);
      if (p != TP) TS(wg, 8 + p);
      if (p < 7 && (EW == 2 || (EW == 1 && (p & 1)))) mbar_wait(sb + OFF_XFULL + 8 * (p + 1), 1);
      ldk(10 * p);
      if (p == 2) asm volatile("st.shared.u32 [%0], %1;" ::"r"(sb + OFF_EPOCH + 4), "r"(ck) : "memory");
      if ((p & 1) == 0) {
        arm();
        if (p == 6) {
          mbar_wait(sb + OFF_EMPTY + 32, 0);
          tag = lds_u(sb + OFF_EPOCH);
          recv_check(sum, 0); recv_check(r0, 1);
#pragma unroll
          for (int i = 0; i < 16; i++) sum[i] = bf2_add(sum[i], r0[i]);
        }
        TR(3);
        mbar_wait(sb + OFF_KBAR + wg * 8, (p >> 1) & 1);
        TR(4);
      } else {
        if (p == 1 || (p == 7 && GAP == 0)) tag = lds_u(sb + OFF_EPOCH);
        TR(3);
        if (p < 7 || GAP == 0) recv_peer(p >> 1);
        TR(4);
        if (p == 7) {
          recv_check(r0, 2);
#pragma unroll
          for (int i = 0; i < 16; i++) sum[i] = bf2_add(sum[i], bf2_add(r0[i], pt[i]));
        }
      }
      if (p == FINP && !FINW) load_fin();
      ldk(10 * p + 1);
      TR(5);
      wg_wait<0>();
      TR(6);
      if (p < 5) release(p);
      if (p < 7) reg_fence(o); else reg_fence(fin);
      ldk(10 * p + 2);
      if ((p & 1) == 0) {
        if (p == 6) recv_issue(r0, 2);
        send_peer();
        if (p == FINP && FINW) load_fin();
      } else if (p < 7) {
        send_owner(o, p >> 1);
      }
      ldk(10 * p + 3);
      if (p == 2) {
#pragma unroll
        for (int h = 0; h < 2; h++) { rho[h] = __fdividef(2.f, 4.f + bf_lo(lds_h(sb + OFF_GS + (wg * 64 + w * 16 + gr + 8 * h) * 2))); pin(rho[h]); }
      }
      TR(7);
    }
    {
      TS(wg, 16);
      const uint32_t tb = sb + OFF_X + stage_off(0) + warp * 4096;
      const uint32_t ta = tb + gr * 256 + ((gr & 3) << 5) + q * 8;
      const uint32_t la = tb + (lane >> 3) * 256 + (((lane & 7) << 4) ^ ((lane >> 3) << 5));
      float* op = out + (size_t)(m * 128 + wg * 64 + (lane >> 4) * 16 + w * 4 + ((lane >> 3) & 1)) * DM + s * 64 + (lane & 7) * 4;
#pragma unroll
      for (int qq = 0; qq < 4; qq += QS) {
#pragma unroll
        for (int qt = qq; qt < qq + QS; qt++) {
          const int h = qt & 1, ch = qt >> 1;
#pragma unroll
          for (int j = 0; j < 4; j++) {
            const int i = ch * 8 + j * 2 + h;
            asm volatile("st.shared.v2.f32 [%0], {%1,%2};" ::"r"((ta ^ (j << 5)) + h * 2048 + ch * 128),
                         "f"((fin[2 * i] + bf_lo(sum[i])) * rho[h]), "f"((fin[2 * i + 1] + bf_hi(sum[i])) * rho[h]) : "memory");
          }
        }
        __syncwarp();
#pragma unroll
        for (int qt = qq; qt < qq + QS; qt++) {
          const int h = qt & 1, ch = qt >> 1;
#pragma unroll
          for (int r = 0; r < 2; r++)
            *reinterpret_cast<uint4*>(op + (r * 32 + h * 2) * DM + ch * 32) = lds_u4(la + (h * 2 + r) * 1024 + ch * 128);
        }
      }
      if (threadIdx.x == 128) g_epoch[b] = tag;
      TS(wg, 17); TG(wg); TRD(); TDUMP();
    }
  } else {
    asm volatile("setmaxnreg.dec.sync.aligned.u32 56;");
    int wsel = warp;
    asm("" : "+r"(wsel));
    if (wsel > 8) {
      if (warp != 11) {
        const int t = threadIdx.x - 288;
        unsigned par;
        asm volatile("ld.relaxed.gpu.global.u32 %0, [%1];" : "=r"(par) : "l"(g_epoch + b) : "memory");
        const float pr = bf_ld(lam_re + s * 64 + t), pi = bf_ld(lam_im + s * 64 + t), pd = bf_ld(log_dt + s * 64 + t);
        asm volatile("barrier.cluster.wait.aligned;" ::: "memory");
        par = __shfl_sync(0xffffffffu, (par + 1) & 1, 0);
        cplx l64 = make_lam(pr, pi, pd);
        {
          const float inv = __fdividef(1.f, fmaf(pr, pr, pi * pi));
          const cplx cf = cmul(cplx{l64.re - 1.f, l64.im}, cplx{pr * inv, -pi * inv});
          asm volatile("st.shared.v4.f32 [%0], {%1,%2,%3,%4};" ::"r"(sb + OFF_LC + t * 16), "f"(l64.re), "f"(l64.im), "f"(cf.re), "f"(cf.im) : "memory");
          mbar_arrive(sb + OFF_LBAR);
        }
#pragma unroll
        for (int i = 0; i < 6; i++) l64 = cmul(l64, l64);
        cplx l128 = cmul(l64, l64);
        pin(l128.re); pin(l128.im);
        uint32_t vr[15], vi[15];
#pragma unroll
        for (int i = 0; i < 15; i++) { vr[i] = par; vi[i] = 0; pin(vr[i]); pin(vi[i]); }
        mbar_wait(sb + OFF_GBAR, 0);
        const float2 e0 = lds_f2(sb + OFF_CARRY + t * 8), e1 = lds_f2(sb + OFF_CARRY + 512 + t * 8);
        float2* eb = g_end + s * 1024 + t;
        {
          const cplx e = cfma(l64, cplx{e0.x, e0.y}, cplx{e1.x, e1.y});
          const unsigned long long v = ((unsigned long long)__float_as_uint(e.im) << 32) | ((__float_as_uint(e.re) & ~1u) | par);
          asm volatile("st.relaxed.gpu.global.b64 [%0], %1;" ::"l"(eb + m * 64), "l"(v) : "memory");
        }
        if (t == 0) TS(3, 1);
        cplx S = {0.f, 0.f};
        {
          if (LBD) __nanosleep(LBD);
          const float2* e15 = eb + (m - 15) * 64;
          int tries = 0;
          bool bad;
#pragma unroll 1
          do {
#pragma unroll
            for (int i = 0; i < 15; i++)
              asm volatile("{.reg .pred p; .reg .b64 v; mov.b64 v, {%0,%1}; setp.ge.s32 p, %3, %4; @p ld.relaxed.gpu.global.b64 v, [%2]; mov.b64 {%0,%1}, v;}"
                           : "+r"(vr[i]), "+r"(vi[i]) : "l"(e15 + i * 64), "r"(m), "r"(15 - i) : "memory");
            uint32_t x = vr[0] ^ par;
#pragma unroll
            for (int i = 1; i < 15; i++) asm("lop3.b32 %0, %0, %1, %2, 0xf6;" : "+r"(x) : "r"(vr[i]), "r"(par));
            bad = __any_sync(0xffffffffu, x & 1);
          } while (bad && ++tries < 200000);
          if (t == 0) TS(3, 2);
          S = cplx{__uint_as_float(vr[0]), __uint_as_float(vi[0])};
#pragma unroll
          for (int i = 1; i < 15; i++) S = cfma(l128, S, cplx{__uint_as_float(vr[i]), __uint_as_float(vi[i])});
        }
        const cplx S1 = cfma(l64, S, cplx{e0.x, e0.y});
        asm volatile("st.shared.v2.f32 [%0], {%1,%2};" ::"r"(sb + OFF_CARRY + t * 8), "f"(S.re), "f"(S.im) : "memory");
        asm volatile("st.shared.v2.f32 [%0], {%1,%2};" ::"r"(sb + OFF_CARRY + 512 + t * 8), "f"(S1.re), "f"(S1.im) : "memory");
        mbar_arrive(sb + OFF_CBAR);
        if (t == 0) TS(3, 3);
        mbar_wait(sb + OFF_CBAR, 0);
        const int gr = lane >> 2, q = lane & 3;
        float2 db[8];
#pragma unroll
        for (int j = 0; j < 8; j++) db[j] = lds_f2(sb + OFF_DB + j * 32 + q * 8);
        mbar_wait(sb + OFF_XFULL + 16, 1);
        mbar_wait(sb + OFF_EMPTY, 0);
#pragma unroll 1
        for (int cw = warp - 9; cw < 8; cw += 2) {
          const float r0 = 0.5f * bf_lo(lds_h(sb + OFF_GS + (cw * 16 + gr) * 2)), r1 = 0.5f * bf_lo(lds_h(sb + OFF_GS + (cw * 16 + gr) * 2 + 16));
          const uint32_t xa = sb + OFF_X + (1 + rank) * 16384 + (cw * 16 + (lane & 15)) * 128 + (((lane >> 4) ^ (lane & 7)) << 4);
          uint32_t xv[16];
#pragma unroll
          for (int i = 0; i < 4; i++)
            asm volatile("ldmatrix.sync.aligned.m8n8.x4.shared.b16 {%0,%1,%2,%3}, [%4];" : "=r"(xv[4 * i]), "=r"(xv[4 * i + 1]), "=r"(xv[4 * i + 2]), "=r"(xv[4 * i + 3])
                         : "r"(xa ^ (i << 5)) : "memory");
          __syncwarp();
#pragma unroll
          for (int j = 0; j < 8; j++) {
            const uint32_t x0 = bf2_mul(xv[2 * j], __float_as_uint(db[j].x)), x1 = bf2_mul(xv[2 * j + 1], __float_as_uint(db[j].x));
            pin(db[j].y);
            const float bl = bf_lo(__float_as_uint(db[j].y)), bh = bf_hi(__float_as_uint(db[j].y));
            asm volatile("st.shared.v4.f32 [%0], {%1,%2,%3,%4};" ::"r"(sb + OFF_X + 16384 + (j >> 2) * 16384 + cw * 2048 + (j & 3) * 512 + lane * 16), "f"(fmaf(bf_lo(x0), r0, bl)),
                         "f"(fmaf(bf_hi(x0), r0, bh)), "f"(fmaf(bf_lo(x1), r1, bl)), "f"(fmaf(bf_hi(x1), r1, bh)) : "memory");
          }
        }
        mbar_arrive(sb + OFF_LBAR);
        if (t == 0) TS(3, 5);
      } else {
        if (lane == 0) TG(2);
        const uint4* gwp = reinterpret_cast<const uint4*>(gate_w) + (lane & 7);
        uint4 gw[4];
#pragma unroll
        for (int i = 0; i < 4; i++) gw[i] = __ldg(gwp + i * 8);
        unsigned par;
        asm volatile("ld.relaxed.gpu.global.u32 %0, [%1];" : "=r"(par) : "l"(g_epoch + b) : "memory");
        const uint32_t dk = __ldg(reinterpret_cast<const uint32_t*>(dskip + s * 64) + lane), bb = __ldg(reinterpret_cast<const uint32_t*>(b2 + s * 64) + lane);
        asm volatile("barrier.cluster.wait.aligned;" ::: "memory");
        const int row = s * 16 + (lane >> 3);
        const uint32_t xr0 = sb + OFF_X + row * 128 + (((lane & 7) ^ (row & 7)) << 4), xr1 = (xr0 + 512) ^ 64;
        float z[4] = {0.f, 0.f, 0.f, 0.f};
#pragma unroll
        for (int kb = 0; kb < 8; kb++) {
          const uint32_t wv[4] = {gw[kb & 3].x, gw[kb & 3].y, gw[kb & 3].z, gw[kb & 3].w};
          if (kb < 4) gw[kb] = __ldg(gwp + (kb + 4) * 8);
          mbar_wait(sb + OFF_XFULL + 8 * kb, 0);
          if ((PF & 2) && kb == PFK && elect_one()) {
            l2_prefetch(pf_w1 + b * 7168, 14336);
            l2_prefetch(pf_cre + b * 2048, 4096);
            l2_prefetch(pf_cim + b * 2048, 4096);
            l2_prefetch(pf_w2 + b * 7168, 14336);
          }
          const uint32_t xo = ((kb + xrot) & 7) * 16384;
#pragma unroll
          for (int r = 0; r < 4; r++) {
            const uint4 a = lds_u4(((r & 1) ? xr1 : xr0) + xo + (r >> 1) * 1024);
            const uint32_t p = bf2_fma(a.w, wv[3], bf2_fma(a.z, wv[2], bf2_fma(a.y, wv[1], bf2_mul(a.x, wv[0]))));
            z[r] += bf_lo(p); z[r] += bf_hi(p);
          }
        }
        if (lane == 0) asm volatile("st.shared.u32 [%0], %1;" ::"r"(sb + OFF_EPOCH), "r"(par + 1) : "memory");
        par = (par + 1) & 1;
        {
          float y0 = (lane & 4) ? z[1] : z[0], y1 = (lane & 4) ? z[3] : z[2];
          y0 += __shfl_xor_sync(0xffffffffu, (lane & 4) ? z[0] : z[1], 4);
          y1 += __shfl_xor_sync(0xffffffffu, (lane & 4) ? z[2] : z[3], 4);
          float zz = (lane & 2) ? y1 : y0;
          zz += __shfl_xor_sync(0xffffffffu, (lane & 2) ? y0 : y1, 2);
          zz += __shfl_xor_sync(0xffffffffu, zz, 1);
          const float rho = 4.f * expf(zz > 40.f ? 40.f : zz);
          if ((lane & 1) == 0)
            asm volatile("st.relaxed.gpu.global.u32 [%0], %1;" ::"l"(g_gate + m * 128 + row + (lane & 4) + (lane & 2) * 4), "r"((__float_as_uint(rho) & ~1u) | par) : "memory");
        }
        if ((PF & 8) && elect_one()) {
          l2_prefetch(pf_w2 + b * 7168, 14336);
          l2_prefetch(pf_cre + b * 2048, 4096);
          l2_prefetch(pf_cim + b * 2048, 4096);
        }
        if (lane == 0) TS(3, 0);
        mbar_wait(sb + OFF_GBAR, 0);
        asm volatile("st.shared.v2.u32 [%0], {%1,%2};" ::"r"(sb + OFF_DB + lane * 8), "r"(dk), "r"(bf2_add(bb, bb)) : "memory");
        uint32_t g0, g1, g2, g3;
        int tries = 0;
#pragma unroll 1
        do {
          asm volatile("ld.relaxed.gpu.global.v4.u32 {%0,%1,%2,%3}, [%4];" : "=r"(g0), "=r"(g1), "=r"(g2), "=r"(g3) : "l"(g_gate + m * 128 + lane * 4) : "memory");
        } while ((((g0 ^ par) | (g1 ^ par) | (g2 ^ par) | (g3 ^ par)) & 1) && ++tries < 200000);
        asm volatile("st.shared.v2.u32 [%0], {%1,%2};" ::"r"(sb + OFF_GS + lane * 8), "r"(pack_bf16(__uint_as_float(g0), __uint_as_float(g1))),
                     "r"(pack_bf16(__uint_as_float(g2), __uint_as_float(g3))) : "memory");
        const uint32_t gt = sb + OFF_GT + (lane >> 4) * 128 + (lane & 1) * 64 + ((lane >> 1) & 7) * 4;
        asm volatile("st.shared.u32 [%0], %1;" ::"r"(gt), "r"(pack_bf16(__uint_as_float(g0), __uint_as_float(g1))) : "memory");
        asm volatile("st.shared.u32 [%0], %1;" ::"r"(gt + 32), "r"(pack_bf16(__uint_as_float(g2), __uint_as_float(g3))) : "memory");
        mbar_arrive(sb + OFF_CBAR);
        if (lane == 0) TS(3, 4);
      }
    } else {
      asm volatile("barrier.cluster.wait.aligned;" ::: "memory");
      if (elect_one()) {
        TS(2, 1);
        const uint32_t t0 = clock();
#pragma unroll 1
        for (int u = W0; u < 8; u++) {
          if (u >= 1) while ((uint32_t)clock() - t0 < D0 + (u - 1) * D1) {}
          mbar_expect_tx(sb + OFF_XFULL + 8 * u, 32768);
          tma5d_mc(sb + OFF_X + ((u + xrot) & 7) * 16384 + rank * 8192, &maps.x, u * 64, 2 * m + rank, sb + OFF_XFULL + 8 * u);
          const int sl = u < 6 ? u : u - 6;
          if (u >= 6) mbar_wait(sb + OFF_EMPTY + 8 * sl, 0);
          tma2d(sb + OFF_RING + sl * 16384, &maps.bre, u * 64, s * 64, sb + OFF_XFULL + 8 * u);
          tma2d(sb + OFF_RING + sl * 16384 + 8192, &maps.bim, u * 64, s * 64, sb + OFF_XFULL + 8 * u);
          if (u == 2) asm volatile("prefetch.tensormap [%0];" ::"l"(&maps.w1b) : "memory");
        }
        TS(2, 5);
        int slot = 2; uint32_t ph = 0;
#pragma unroll 1
        for (int u = 8; u < 24; u++) {
          const uint32_t fb = sb + OFF_FULL + 8 * slot, dst = sb + OFF_RING + slot * 16384;
          mbar_wait(sb + OFF_EMPTY + 8 * slot, ph);
          TS2(0, u);
          if (u < 16) {
            mbar_expect_tx(fb, 12288);
            tma3d(dst, &maps.w1b, 0, (u - 8) * 64, s * 7, fb);
            if (TMP2 && u < 12) asm volatile("prefetch.tensormap [%0];" ::"l"(&maps.w1a + (u - 8)) : "memory");
          } else {
            mbar_expect_tx(fb, 16384);
            tma2d(dst, &maps.w1a, s * 224 + 96, ((u - xrot) & 7) * 64, fb);
            tma2d(dst + 8192, &maps.w1a, s * 224 + 160, ((u - xrot) & 7) * 64, fb);
          }
          if (++slot == NSLOT) { slot = 0; ph ^= 1; }
        }
#pragma unroll 1
        for (int j = 0; j < 3; j++) {
          const uint32_t fb = sb + OFF_FULL + 8 * j, dst = sb + OFF_X + stage_off(0);
          const int c = ((sp + 1) & 3) * 128 + ((rank ^ 1) << 6);
          mbar_wait(sb + OFF_EMPTY + 8 + 8 * j, 1);
          mbar_expect_tx(fb, j == 1 ? 16384 : 14336);
          if (j == 1) {
            tma2d(dst + 14336, &maps.cre, s * 64, c, fb);
            tma2d(dst + 22528, &maps.cim, s * 64, c, fb);
          } else {
            tma2d(dst + j * 15360, &maps.w2, c, s * 224 + j * 56, fb);
          }
        }
#pragma unroll 1
        for (int p = 1; p < 8; p++) {
          const int c = ((sp + 1 + (p >> 1)) & 3) * 128 + (((rank ^ p ^ 1) & 1) << 6);
          const uint32_t fb = sb + OFF_XFULL + 8 * p, dst = sb + OFF_X + stage_off(p);
          if (p == 2 || p > 3) mbar_wait(sb + OFF_EMPTY + (p == 2 ? 40 : (p - 4) * 8), p == 2);
          TS2(0, 32 + p);
          mbar_expect_tx(fb, 45056);
          tma2d(dst, &maps.w2, c, s * 224, fb);
          tma2d(dst + 14336, &maps.cre, s * 64, c, fb);
          tma2d(dst + 22528, &maps.cim, s * 64, c, fb);
          tma2d(dst + 30720, &maps.w2, c, s * 224 + 112, fb);
        }
        TS(2, 2);
      }
    }
  }
}

typedef CUresult (*EncFn)(CUtensorMap*, CUtensorMapDataType, cuuint32_t, void*, const cuuint64_t*, const cuuint64_t*, const cuuint32_t*,
                          const cuuint32_t*, CUtensorMapInterleave, CUtensorMapSwizzle, CUtensorMapL2promotion, CUtensorMapFloatOOBfill);

void encode(EncFn f, CUtensorMap* mp, const void* p, int rank, const cuuint64_t* dims, const cuuint64_t* strides, const cuuint32_t* box, CUtensorMapSwizzle sw) {
  cuuint32_t es[5] = {1, 1, 1, 1, 1};
  f(mp, CU_TENSOR_MAP_DATA_TYPE_BFLOAT16, rank, const_cast<void*>(p), dims, strides, box, es, CU_TENSOR_MAP_INTERLEAVE_NONE, sw,
    CU_TENSOR_MAP_L2_PROMOTION_L2_128B, CU_TENSOR_MAP_FLOAT_OOB_FILL_NONE);
}

}

extern "C" void kernel_launch(void* const* d_in, const int* in_sizes, int n_in, void* d_out, int out_size) {
  typedef const __nv_bfloat16* bp;
  bp x = (bp)d_in[0], lre = (bp)d_in[1], lim = (bp)d_in[2], bre = (bp)d_in[3], bim = (bp)d_in[4], cre = (bp)d_in[5], cim = (bp)d_in[6],
     ldt = (bp)d_in[7], dsk = (bp)d_in[8], w1 = (bp)d_in[10], b1 = (bp)d_in[11], w2 = (bp)d_in[12], b2 = (bp)d_in[13], gw = (bp)d_in[14];
  static EncFn enc = nullptr;
  if (!enc) {
    void* f = nullptr;
    cudaDriverEntryPointQueryResult qr;
    cudaGetDriverEntryPoint("cuTensorMapEncodeTiled", &f, cudaEnableDefault, &qr);
    enc = (EncFn)f;
    cudaFuncSetAttribute(fused_kernel, cudaFuncAttributeMaxDynamicSharedMemorySize, SMEM_BYTES);
  }
  Maps maps;
  {
    cuuint64_t d[5] = {DM, 2, 4, 8, SEQ / 64}, st[4] = {DM * 2, 16 * DM * 2, 2 * DM * 2, 64 * DM * 2};
    cuuint32_t bx[5] = {64, 2, 4, 8, 1};
    encode(enc, &maps.x, x, 5, d, st, bx, CU_TENSOR_MAP_SWIZZLE_128B);
  }
  {
    cuuint64_t d[2] = {DM, DM}, st[1] = {DM * 2};
    cuuint32_t bx[2] = {64, 64};
    encode(enc, &maps.bre, bre, 2, d, st, bx, CU_TENSOR_MAP_SWIZZLE_128B);
    encode(enc, &maps.bim, bim, 2, d, st, bx, CU_TENSOR_MAP_SWIZZLE_128B);
    encode(enc, &maps.cre, cre, 2, d, st, bx, CU_TENSOR_MAP_SWIZZLE_128B);
    encode(enc, &maps.cim, cim, 2, d, st, bx, CU_TENSOR_MAP_SWIZZLE_128B);
  }
  {
    cuuint64_t d[2] = {FF, DM}, st[1] = {FF * 2};
    cuuint32_t bx[2] = {64, 64};
    encode(enc, &maps.w1a, w1, 2, d, st, bx, CU_TENSOR_MAP_SWIZZLE_128B);
    cuuint64_t d3[3] = {32, DM, FF / 32}, st3[2] = {FF * 2, 64};
    cuuint32_t bx3[3] = {32, 64, 3};
    encode(enc, &maps.w1b, w1, 3, d3, st3, bx3, CU_TENSOR_MAP_SWIZZLE_64B);
  }
  {
    cuuint64_t d[2] = {DM, FF}, st[1] = {DM * 2};
    cuuint32_t bx[2] = {64, 112};
    encode(enc, &maps.w2, w2, 2, d, st, bx, CU_TENSOR_MAP_SWIZZLE_128B);
  }
  fused_kernel<<<128, 384, SMEM_BYTES>>>(lre, lim, ldt, dsk, b1, b2, gw, w1, w2, cre, cim, (float*)d_out, maps);
}
```

```cpp
#include <cuda_runtime.h>
#include <cuda_bf16.h>
#include <cuda.h>
#include <stdint.h>

namespace {

constexpr int SEQ = 2048, DM = 512, FF = 1792;
constexpr int NSLOT = 6;
constexpr uint32_t OFF_X = 0, OFF_RING = 131072, OFF_MISC = 229376;
constexpr uint32_t OFF_XFULL = OFF_MISC, OFF_FULL = OFF_XFULL + 64, OFF_RBAR = OFF_FULL + 48, OFF_EMPTY = OFF_RBAR + 16, OFF_KBAR = OFF_EMPTY + 48,
                   OFF_GBAR = OFF_KBAR + 16, OFF_LBAR = OFF_GBAR + 8, OFF_CBAR = OFF_LBAR + 8, OFF_EPOCH = OFF_CBAR + 8;
constexpr uint32_t OFF_LC = OFF_MISC + 256;
constexpr uint32_t OFF_GS = OFF_LC;
constexpr uint32_t OFF_GT = OFF_LC + 256;
constexpr uint32_t OFF_DB = OFF_LC + 512;
constexpr uint32_t OFF_CARRY = OFF_LC + 1024;
constexpr uint32_t SMEM_BYTES = OFF_CARRY + 1024;
static_assert(SMEM_BYTES <= 232448, "smem");

struct Maps { CUtensorMap x, bre, bim, w1b, w1a, w2, cre, cim; };
__host__ __device__ constexpr uint32_t stage_off(int p) { return 49152 + 45056 * (((p >> 1) & 1) + 2 * (p & 1)); }
__host__ __device__ constexpr uint32_t full_par(int u) { return ((u - 8) / 6 + (u % 6 == 0)) & 1; }

__device__ uint4 g_part[16 * 8 * 3 * 1024];
__device__ float2 g_end[8 * 16 * 64];
__device__ unsigned g_gate[SEQ];
__device__ unsigned g_epoch[128];

__device__ __forceinline__ void mbar_init(uint32_t bar, uint32_t cnt) { asm volatile("mbarrier.init.shared::cta.b64 [%0], %1;" ::"r"(bar), "r"(cnt)); }
__device__ __forceinline__ void mbar_expect_tx(uint32_t bar, uint32_t bytes) { asm volatile("mbarrier.arrive.expect_tx.shared::cta.b64 _, [%0], %1;" ::"r"(bar), "r"(bytes) : "memory"); }
__device__ __forceinline__ void mbar_arrive(uint32_t bar) { asm volatile("mbarrier.arrive.shared::cta.b64 _, [%0];" ::"r"(bar) : "memory"); }
__device__ __forceinline__ void mbar_arrive_cl(uint32_t cbar) { asm volatile("mbarrier.arrive.shared::cluster.b64 _, [%0];" ::"r"(cbar) : "memory"); }
__device__ __forceinline__ void mbar_wait(uint32_t bar, uint32_t parity) {
  asm volatile(
      "{\n.reg .pred p;\n.reg .u32 c;\n"
      "mbarrier.try_wait.parity.shared::cta.b64 p, [%0], %1;\n"
      "@p bra.uni LAB_DONE;\n"
      "mov.u32 c, 0;\n"
      "LAB_WAIT:\n"
      "mbarrier.try_wait.parity.shared::cta.b64 p, [%0], %1;\n"
      "@p bra.uni LAB_DONE;\n"
      "add.u32 c, c, 1;\nsetp.lt.u32 p, c, 200000;\n@p bra.uni LAB_WAIT;\n"
      "LAB_DONE:\n}" ::"r"(bar), "r"(parity) : "memory");
}
__device__ __forceinline__ void tma2d(uint32_t dst, const CUtensorMap* m, int c0, int c1, uint32_t bar) {
  asm volatile("cp.async.bulk.tensor.2d.shared::cluster.global.mbarrier::complete_tx::bytes [%0], [%1, {%3,%4}], [%2];"
               ::"r"(dst), "l"(m), "r"(bar), "r"(c0), "r"(c1) : "memory");
}
__device__ __forceinline__ void tma3d(uint32_t dst, const CUtensorMap* m, int c0, int c1, int c2, uint32_t bar) {
  asm volatile("cp.async.bulk.tensor.3d.shared::cluster.global.mbarrier::complete_tx::bytes [%0], [%1, {%3,%4,%5}], [%2];"
               ::"r"(dst), "l"(m), "r"(bar), "r"(c0), "r"(c1), "r"(c2) : "memory");
}
__device__ __forceinline__ void tma5d(uint32_t dst, const CUtensorMap* m, int c0, int c4, uint32_t bar) {
  asm volatile("cp.async.bulk.tensor.5d.shared::cluster.global.mbarrier::complete_tx::bytes [%0], [%1, {%3,%5,%5,%5,%4}], [%2];"
               ::"r"(dst), "l"(m), "r"(bar), "r"(c0), "r"(c4), "r"(0) : "memory");
}
__device__ __forceinline__ void tma5d_mc(uint32_t dst, const CUtensorMap* m, int c0, int c4, uint32_t bar) {
  asm volatile("cp.async.bulk.tensor.5d.shared::cluster.global.mbarrier::complete_tx::bytes.multicast::cluster [%0], [%1, {%3,%5,%5,%5,%4}], [%2], %6;"
               ::"r"(dst), "l"(m), "r"(bar), "r"(c0), "r"(c4), "r"(0), "h"((uint16_t)3) : "memory");
}
__device__ __forceinline__ void map_prefetch(const CUtensorMap* m) { asm volatile("prefetch.tensormap [%0];" ::"l"(m) : "memory"); }
__device__ __forceinline__ bool elect_one() {
  uint32_t pred;
  asm volatile("{.reg .pred P; elect.sync _|P, 0xffffffff; selp.u32 %0, 1, 0, P;}" : "=r"(pred));
  return pred != 0;
}
__device__ __forceinline__ void cluster_wait() { asm volatile("barrier.cluster.wait.aligned;" ::: "memory"); }
__device__ __forceinline__ void wg_fence() { asm volatile("wgmma.fence.sync.aligned;" ::: "memory"); }
__device__ __forceinline__ void wg_commit() { asm volatile("wgmma.commit_group.sync.aligned;" ::: "memory"); }
template <int N> __device__ __forceinline__ void wg_wait() { asm volatile("wgmma.wait_group.sync.aligned %0;" ::"n"(N) : "memory"); }
__device__ __forceinline__ void pin(float& a) { asm volatile("" : "+f"(a)::"memory"); }
__device__ __forceinline__ void pin(uint32_t& a) { asm volatile("" : "+r"(a)::"memory"); }
template <int N> __device__ __forceinline__ void reg_fence(float (&d)[N]) {
#pragma unroll
  for (int i = 0; i < N; i++) pin(d[i]);
}
__device__ __forceinline__ void sched_fence(uint32_t& ck) { asm volatile("{.reg .b32 c; mov.u32 c, %%clock; xor.b32 %0, %0, c;}" : "+r"(ck)::"memory"); }
__device__ __forceinline__ void bar_sync(int id, int n) { asm volatile("bar.sync %0, %1;" ::"r"(id), "r"(n) : "memory"); }
__device__ __forceinline__ void bar_arrive(int id, int n) { asm volatile("bar.arrive %0, %1;" ::"r"(id), "r"(n) : "memory"); }
constexpr uint32_t DH128 = (1024 >> 4) | (1u << 30), DH64 = (512 >> 4) | (2u << 30);
__host__ __device__ constexpr uint32_t lbo(uint32_t bytes) { return (bytes >> 4) << 20; }
__device__ __forceinline__ uint32_t pack_bf16(float lo, float hi) { uint32_t r; asm("cvt.rn.bf16x2.f32 %0, %1, %2;" : "=r"(r) : "f"(hi), "f"(lo)); return r; }
__device__ __forceinline__ float bf_lo(uint32_t v) { return __uint_as_float(v << 16); }
__device__ __forceinline__ float bf_hi(uint32_t v) { return __uint_as_float(v & 0xffff0000u); }
__device__ __forceinline__ float bf_ld(const __nv_bfloat16* p) { return __bfloat162float(__ldg(p)); }
__device__ __forceinline__ uint32_t late16(uint32_t bar) {
  uint32_t r;
  asm volatile("{.reg .pred p; mbarrier.test_wait.parity.shared::cta.b64 p, [%1], 0; selp.u32 %0, 16, 0, p;}" : "=r"(r) : "r"(bar) : "memory");
  return r;
}
__device__ __forceinline__ float2 lds_f2(uint32_t a) { float2 v; asm volatile("ld.shared.v2.f32 {%0,%1}, [%2];" : "=f"(v.x), "=f"(v.y) : "r"(a)); return v; }
__device__ __forceinline__ uint32_t lds_h(uint32_t a) { uint32_t v; asm volatile("ld.shared.u16 %0, [%1];" : "=r"(v) : "r"(a)); return v; }
__device__ __forceinline__ uint32_t lds_u(uint32_t a) { uint32_t v; asm volatile("ld.shared.u32 %0, [%1];" : "=r"(v) : "r"(a)); return v; }
__device__ __forceinline__ uint4 lds_u4(uint32_t a) { uint4 v; asm volatile("ld.shared.v4.u32 {%0,%1,%2,%3}, [%4];" : "=r"(v.x), "=r"(v.y), "=r"(v.z), "=r"(v.w) : "r"(a)); return v; }
__device__ __forceinline__ void sts_u(uint32_t a, uint32_t v) { asm volatile("st.shared.u32 [%0], %1;" ::"r"(a), "r"(v) : "memory"); }
__device__ __forceinline__ void sts_u2(uint32_t a, uint32_t x, uint32_t y) { asm volatile("st.shared.v2.u32 [%0], {%1,%2};" ::"r"(a), "r"(x), "r"(y) : "memory"); }
__device__ __forceinline__ void sts_f2(uint32_t a, float x, float y) { asm volatile("st.shared.v2.f32 [%0], {%1,%2};" ::"r"(a), "f"(x), "f"(y) : "memory"); }
__device__ __forceinline__ void sts_f4(uint32_t a, float x, float y, float z, float w) {
  asm volatile("st.shared.v4.f32 [%0], {%1,%2,%3,%4};" ::"r"(a), "f"(x), "f"(y), "f"(z), "f"(w) : "memory");
}
__device__ __forceinline__ void st_b128(uint4* p, uint32_t a, uint32_t b, uint32_t c, uint32_t d) {
  asm volatile("st.relaxed.gpu.global.v4.b32 [%0], {%1,%2,%3,%4};" ::"l"(p), "r"(a), "r"(b), "r"(c), "r"(d) : "memory");
}
__device__ __forceinline__ void ld_b128(const uint4* p, uint32_t& a, uint32_t& b, uint32_t& c, uint32_t& d) {
  asm volatile("{.reg .b64 l, h; .reg .b128 v; ld.relaxed.gpu.global.b128 v, [%4]; mov.b128 {l,h}, v; mov.b64 {%0,%1}, l; mov.b64 {%2,%3}, h;}"
               : "=r"(a), "=r"(b), "=r"(c), "=r"(d) : "l"(p) : "memory");
}
__device__ __forceinline__ uint32_t bf2_mul(uint32_t a, uint32_t b) { uint32_t r; asm("mul.rn.bf16x2 %0, %1, %2;" : "=r"(r) : "r"(a), "r"(b)); return r; }
__device__ __forceinline__ uint32_t bf2_add(uint32_t a, uint32_t b) { uint32_t r; asm("add.rn.bf16x2 %0, %1, %2;" : "=r"(r) : "r"(a), "r"(b)); return r; }
__device__ __forceinline__ uint32_t bf2_fma(uint32_t a, uint32_t b, uint32_t c) { uint32_t r; asm("fma.rn.bf16x2 %0, %1, %2, %3;" : "=r"(r) : "r"(a), "r"(b), "r"(c)); return r; }
__device__ __forceinline__ uint32_t gelu2_pair(float a, float b) {
  const uint32_t v = pack_bf16(a, b);
  uint32_t t;
  asm("tanh.approx.bf16x2 %0, %1;" : "=r"(t) : "r"(bf2_fma(v, bf2_fma(bf2_mul(v, v), 0x3d123d12u, 0xbe4fbe4fu), v)));
  return bf2_fma(v, t, v);
}
struct cplx { float re, im; };
__device__ __forceinline__ cplx cmul(cplx a, cplx b) { return {fmaf(a.re, b.re, -a.im * b.im), fmaf(a.re, b.im, a.im * b.re)}; }
__device__ __forceinline__ cplx cfma(cplx a, cplx b, cplx c) {
  return {fmaf(a.re, b.re, fmaf(-a.im, b.im, c.re)), fmaf(a.re, b.im, fmaf(a.im, b.re, c.im))};
}
__device__ __forceinline__ cplx make_lam(float lre, float lim, float ldt) {
  float dt = __bfloat162float(__float2bfloat16_rn(expf(ldt)));
  float mag = expf(dt * lre), sn, cs;
  sincospif(dt * lim * 0.31830988618379067f, &sn, &cs);
  return {mag * cs, mag * sn};
}

template <int NG>
__device__ __forceinline__ void gate_rows(uint32_t sb, int xrot, int row0, uint4 (&gw)[4], const uint4* gwp, unsigned* dst, unsigned par) {
  const int lane = threadIdx.x & 31, row = row0 + (lane >> 3);
  const uint32_t xr0 = sb + OFF_X + row * 128 + (((lane & 7) ^ (row & 7)) << 4), xr1 = (xr0 + 512) ^ 64;
  float z[NG], y[NG];
#pragma unroll
  for (int r = 0; r < NG; r++) z[r] = y[r] = 0.f;
#pragma unroll
  for (int kb = 0; kb < 8; kb++) {
    const uint4 w = gw[kb & 3];
    if (kb < 4) gw[kb] = __ldg(gwp + (kb + 4) * 8);
    mbar_wait(sb + OFF_XFULL + 8 * kb, 0);
#pragma unroll
    for (int r = 0; r < NG; r++) {
      const uint4 a = lds_u4((r ? xr1 : xr0) + ((kb + xrot) & 7) * 16384);
      const uint32_t p[4] = {bf2_mul(a.x, w.x), bf2_mul(a.y, w.y), bf2_mul(a.z, w.z), bf2_mul(a.w, w.w)};
#pragma unroll
      for (int c = 0; c < 4; c++) { z[r] += bf_lo(p[c]); y[r] += bf_hi(p[c]); }
    }
  }
  float zz = z[0] + y[0];
  if (NG == 2) {
    const float z1 = z[NG - 1] + y[NG - 1];
    zz = ((lane & 4) ? z1 : zz) + __shfl_xor_sync(0xffffffffu, (lane & 4) ? zz : z1, 4);
  } else {
    zz += __shfl_xor_sync(0xffffffffu, zz, 4);
  }
  zz += __shfl_xor_sync(0xffffffffu, zz, 2);
  zz += __shfl_xor_sync(0xffffffffu, zz, 1);
  zz = bf_lo(pack_bf16(zz, 0.f));
  const float rho = 4.f * expf(zz > 40.f ? 40.f : zz);
  if ((lane & (NG == 2 ? 3 : 7)) == 0)
    asm volatile("st.relaxed.gpu.global.u32 [%0], %1;" ::"l"(dst + row + (lane & 4)), "r"((__float_as_uint(rho) & ~1u) | par) : "memory");
}

template<int TA,int TB,uint32_t AH,uint32_t BH> __device__ __forceinline__ void wgmma_n64_ss(float (&d)[32], uint32_t al, uint32_t ao, uint32_t bl, uint32_t bo, int scale_d){
  asm volatile("{.reg .pred p; .reg .b32 t, v; .reg .b64 da, db; setp.ne.b32 p, %36, 0; add.u32 t, %32, %33; mov.b64 da, {t, %39}; add.u32 v, %34, %35; mov.b64 db, {v, %40};\n"
   "wgmma.mma_async.sync.aligned.m64n64k16.f32.bf16.bf16 {%0,%1,%2,%3,%4,%5,%6,%7,%8,%9,%10,%11,%12,%13,%14,%15,%16,%17,%18,%19,%20,%21,%22,%23,%24,%25,%26,%27,%28,%29,%30,%31}, da, db, p, 1, 1, %37, %38;}"
   : "+f"(d[0]),"+f"(d[1]),"+f"(d[2]),"+f"(d[3]),"+f"(d[4]),"+f"(d[5]),"+f"(d[6]),"+f"(d[7]),"+f"(d[8]),"+f"(d[9]),"+f"(d[10]),"+f"(d[11]),"+f"(d[12]),"+f"(d[13]),"+f"(d[14]),"+f"(d[15]),"+f"(d[16]),"+f"(d[17]),"+f"(d[18]),"+f"(d[19]),"+f"(d[20]),"+f"(d[21]),"+f"(d[22]),"+f"(d[23]),"+f"(d[24]),"+f"(d[25]),"+f"(d[26]),"+f"(d[27]),"+f"(d[28]),"+f"(d[29]),"+f"(d[30]),"+f"(d[31])
   : "r"(al),"r"(ao >> 4),"r"(bl),"r"(bo >> 4),"r"(scale_d),"n"(TA),"n"(TB),"n"(AH),"n"(BH));
}
template<int TB,uint32_t BH,int SA=1> __device__ __forceinline__ void wgmma_n64_rs(float (&d)[32], uint32_t a0,uint32_t a1,uint32_t a2,uint32_t a3, uint32_t bl, uint32_t bo, int scale_d){
  asm volatile("{.reg .pred p; .reg .b32 t; .reg .b64 db; setp.ne.b32 p, %38, 0; add.u32 t, %36, %37; mov.b64 db, {t, %40};\n"
   "wgmma.mma_async.sync.aligned.m64n64k16.f32.bf16.bf16 {%0,%1,%2,%3,%4,%5,%6,%7,%8,%9,%10,%11,%12,%13,%14,%15,%16,%17,%18,%19,%20,%21,%22,%23,%24,%25,%26,%27,%28,%29,%30,%31}, {%32,%33,%34,%35}, db, p, %41, 1, %39;}"
   : "+f"(d[0]),"+f"(d[1]),"+f"(d[2]),"+f"(d[3]),"+f"(d[4]),"+f"(d[5]),"+f"(d[6]),"+f"(d[7]),"+f"(d[8]),"+f"(d[9]),"+f"(d[10]),"+f"(d[11]),"+f"(d[12]),"+f"(d[13]),"+f"(d[14]),"+f"(d[15]),"+f"(d[16]),"+f"(d[17]),"+f"(d[18]),"+f"(d[19]),"+f"(d[20]),"+f"(d[21]),"+f"(d[22]),"+f"(d[23]),"+f"(d[24]),"+f"(d[25]),"+f"(d[26]),"+f"(d[27]),"+f"(d[28]),"+f"(d[29]),"+f"(d[30]),"+f"(d[31])
   : "r"(a0),"r"(a1),"r"(a2),"r"(a3),"r"(bl),"r"(bo >> 4),"r"(scale_d),"n"(TB),"n"(BH),"n"(SA));
}
template<int TA,int TB,uint32_t AH,uint32_t BH> __device__ __forceinline__ void wgmma_n96_ss(float (&d)[48], uint32_t al, uint32_t ao, uint32_t bl, uint32_t bo, int scale_d){
  asm volatile("{.reg .pred p; .reg .b32 t, v; .reg .b64 da, db; setp.ne.b32 p, %52, 0; add.u32 t, %48, %49; mov.b64 da, {t, %55}; add.u32 v, %50, %51; mov.b64 db, {v, %56};\n"
   "wgmma.mma_async.sync.aligned.m64n96k16.f32.bf16.bf16 {%0,%1,%2,%3,%4,%5,%6,%7,%8,%9,%10,%11,%12,%13,%14,%15,%16,%17,%18,%19,%20,%21,%22,%23,%24,%25,%26,%27,%28,%29,%30,%31,%32,%33,%34,%35,%36,%37,%38,%39,%40,%41,%42,%43,%44,%45,%46,%47}, da, db, p, 1, 1, %53, %54;}"
   : "+f"(d[0]),"+f"(d[1]),"+f"(d[2]),"+f"(d[3]),"+f"(d[4]),"+f"(d[5]),"+f"(d[6]),"+f"(d[7]),"+f"(d[8]),"+f"(d[9]),"+f"(d[10]),"+f"(d[11]),"+f"(d[12]),"+f"(d[13]),"+f"(d[14]),"+f"(d[15]),"+f"(d[16]),"+f"(d[17]),"+f"(d[18]),"+f"(d[19]),"+f"(d[20]),"+f"(d[21]),"+f"(d[22]),"+f"(d[23]),"+f"(d[24]),"+f"(d[25]),"+f"(d[26]),"+f"(d[27]),"+f"(d[28]),"+f"(d[29]),"+f"(d[30]),"+f"(d[31]),"+f"(d[32]),"+f"(d[33]),"+f"(d[34]),"+f"(d[35]),"+f"(d[36]),"+f"(d[37]),"+f"(d[38]),"+f"(d[39]),"+f"(d[40]),"+f"(d[41]),"+f"(d[42]),"+f"(d[43]),"+f"(d[44]),"+f"(d[45]),"+f"(d[46]),"+f"(d[47])
   : "r"(al),"r"(ao >> 4),"r"(bl),"r"(bo >> 4),"r"(scale_d),"n"(TA),"n"(TB),"n"(AH),"n"(BH));
}
template<int TA,int TB,uint32_t AH,uint32_t BH> __device__ __forceinline__ void wgmma_n128_ss(float (&d)[64], uint32_t al, uint32_t ao, uint32_t bl, uint32_t bo, int scale_d){
  asm volatile("{.reg .pred p; .reg .b32 t, v; .reg .b64 da, db; setp.ne.b32 p, %68, 0; add.u32 t, %64, %65; mov.b64 da, {t, %71}; add.u32 v, %66, %67; mov.b64 db, {v, %72};\n"
   "wgmma.mma_async.sync.aligned.m64n128k16.f32.bf16.bf16 {%0,%1,%2,%3,%4,%5,%6,%7,%8,%9,%10,%11,%12,%13,%14,%15,%16,%17,%18,%19,%20,%21,%22,%23,%24,%25,%26,%27,%28,%29,%30,%31,%32,%33,%34,%35,%36,%37,%38,%39,%40,%41,%42,%43,%44,%45,%46,%47,%48,%49,%50,%51,%52,%53,%54,%55,%56,%57,%58,%59,%60,%61,%62,%63}, da, db, p, 1, 1, %69, %70;}"
   : "+f"(d[0]),"+f"(d[1]),"+f"(d[2]),"+f"(d[3]),"+f"(d[4]),"+f"(d[5]),"+f"(d[6]),"+f"(d[7]),"+f"(d[8]),"+f"(d[9]),"+f"(d[10]),"+f"(d[11]),"+f"(d[12]),"+f"(d[13]),"+f"(d[14]),"+f"(d[15]),"+f"(d[16]),"+f"(d[17]),"+f"(d[18]),"+f"(d[19]),"+f"(d[20]),"+f"(d[21]),"+f"(d[22]),"+f"(d[23]),"+f"(d[24]),"+f"(d[25]),"+f"(d[26]),"+f"(d[27]),"+f"(d[28]),"+f"(d[29]),"+f"(d[30]),"+f"(d[31]),"+f"(d[32]),"+f"(d[33]),"+f"(d[34]),"+f"(d[35]),"+f"(d[36]),"+f"(d[37]),"+f"(d[38]),"+f"(d[39]),"+f"(d[40]),"+f"(d[41]),"+f"(d[42]),"+f"(d[43]),"+f"(d[44]),"+f"(d[45]),"+f"(d[46]),"+f"(d[47]),"+f"(d[48]),"+f"(d[49]),"+f"(d[50]),"+f"(d[51]),"+f"(d[52]),"+f"(d[53]),"+f"(d[54]),"+f"(d[55]),"+f"(d[56]),"+f"(d[57]),"+f"(d[58]),"+f"(d[59]),"+f"(d[60]),"+f"(d[61]),"+f"(d[62]),"+f"(d[63])
   : "r"(al),"r"(ao >> 4),"r"(bl),"r"(bo >> 4),"r"(scale_d),"n"(TA),"n"(TB),"n"(AH),"n"(BH));
}

__global__ void __cluster_dims__(2, 1, 1) __launch_bounds__(384, 1)
fused_kernel(const __nv_bfloat16* __restrict__ lam_re, const __nv_bfloat16* __restrict__ lam_im, const __nv_bfloat16* __restrict__ log_dt,
             const __nv_bfloat16* __restrict__ dskip, const __nv_bfloat16* __restrict__ b1, const __nv_bfloat16* __restrict__ b2,
             const __nv_bfloat16* __restrict__ gate_w, float* __restrict__ out, const __grid_constant__ Maps maps) {
  extern __shared__ __align__(1024) unsigned char smem_raw[];
  const uint32_t sb = (uint32_t)__cvta_generic_to_shared(smem_raw);
  const int b = blockIdx.x;
  const int rank = b & 1, cl = b >> 1;
  const int sp = (cl & 1) | ((cl >> 2) & 2), m = ((cl >> 1) & 3) | ((cl >> 4) << 2);
  const int s = sp * 2 + rank;
  const int warp = __shfl_sync(0xffffffffu, (int)(threadIdx.x >> 5), 0);
  const int lane = threadIdx.x & 31;
  const int xrot = 9 - 2 * sp;

  if (elect_one()) {
    if (warp > 8) {
      map_prefetch(&maps.x + (warp - 9));
      mbar_init(sb + OFF_GBAR + 8 * (warp - 9), warp < 11 ? 64 : 96);
    }
    const uint32_t c = warp < 8 ? 1 : warp < 11 ? 8 : 4, bar = sb + OFF_XFULL + 16 * warp;
    mbar_init(bar, c);
    if ((warp & 11) == 0) {
      mbar_expect_tx(bar, 16384);
      if (warp == 0) {
        tma5d(sb + OFF_X + (xrot & 7) * 16384, &maps.x, 0, 2 * m, bar);
        tma5d(sb + OFF_X + (xrot & 7) * 16384 + 8192, &maps.x, 0, 2 * m + 1, bar);
      } else {
        tma2d(sb + OFF_RING, &maps.bre, 0, s * 64, bar);
        tma2d(sb + OFF_RING + 8192, &maps.bim, 0, s * 64, bar);
      }
    }
    mbar_init(bar + 8, c);
    asm volatile("fence.mbarrier_init.release.cluster;" ::: "memory");
  }
  __syncwarp();
  asm volatile("barrier.cluster.arrive.relaxed.aligned;" ::: "memory");

  if (warp < 8) {
    const int wg = warp >> 2, w = warp & 3, q = lane & 3, gr = lane >> 2;
    uint32_t bv[28];
#pragma unroll
    for (int j = 0; j < 28; j++) bv[j] = __ldg(reinterpret_cast<const uint32_t*>(b1 + s * 224 + j * 8) + q);
    asm volatile("setmaxnreg.inc.sync.aligned.u32 224;");
    cluster_wait();
    auto release = [&](int slot) { if (lane == 0) mbar_arrive(sb + OFF_EMPTY + 8 * slot); };
    const uint32_t xw = sb + OFF_X + wg * 8192, fullb = sb + OFF_FULL;
    const uint32_t dxw = (xw & 0x3FFFF) >> 4, dring = ((sb + OFF_RING) & 0x3FFFF) >> 4;

    float ure[32], uim[32], aa[48], ab[64];
    cplx lam[2], coef[2], l16[2], l32[2], lq[2], pre[2], e[2];
    uint32_t sh16, mhi, ck = 0;

    auto bias = [&](int c) {
#pragma unroll
      for (int j = c * 7; j < c * 7 + 7; j++) {
        pin(bv[j]);
        float* d = j < 12 ? aa + 4 * j : ab + 4 * (j - 12);
        d[0] = d[2] = __uint_as_float(bv[j] << sh16); d[1] = d[3] = __uint_as_float(bv[j] & mhi);
        pin(d[0]); pin(d[1]); pin(d[2]); pin(d[3]);
      }
    };
#pragma unroll
    for (int kb = 0; kb < 8; kb++) {
      const int slot = kb % NSLOT;
      mbar_wait(sb + OFF_XFULL + 8 * kb, 0);
      if (kb == 0) mbar_wait(fullb, 0);
      if (kb == 2) { sh16 = late16(sb + OFF_XFULL); mhi = 0xffffffffu << sh16; }
      if (kb == 4) {
        mbar_wait(sb + OFF_LBAR, 0);
#pragma unroll
        for (int h = 0; h < 2; h++) {
          const uint4 v = lds_u4(sb + OFF_LC + (w * 16 + gr + 8 * h) * 16);
          lam[h] = cplx{__uint_as_float(v.x), __uint_as_float(v.y)};
          coef[h] = cplx{__uint_as_float(v.z), __uint_as_float(v.w)};
        }
      }
      wg_fence();
      const uint32_t dxa = dxw + ((kb + xrot) & 7) * 1024;
#pragma unroll
      for (int kk = 0; kk < 4; kk++) {
        wgmma_n64_ss<0, 0, DH128, DH128>(ure, dring, slot * 16384 + kk * 32, dxa, kk * 32, (kb | kk) != 0);
        wgmma_n64_ss<0, 0, DH128, DH128>(uim, dring, slot * 16384 + 8192 + kk * 32, dxa, kk * 32, (kb | kk) != 0);
      }
      wg_commit();
      if (kb > 0) { wg_wait<1>(); release((kb - 1) % NSLOT); }
      if (kb >= 2 && kb < 5) bias(kb - 2);
      if (kb == 6) {
#pragma unroll
        for (int h = 0; h < 2; h++) {
          pin(lam[h].re); pin(lam[h].im);
          cplx t = cmul(lam[h], lam[h]); t = cmul(t, t); t = cmul(t, t);
          l16[h] = cmul(t, t);
          pin(l16[h].re); pin(l16[h].im);
        }
      }
      if (kb == 7) {
#pragma unroll
        for (int h = 0; h < 2; h++) {
          pin(l16[h].re); pin(l16[h].im);
          l32[h] = cmul(l16[h], l16[h]);
          const cplx a = (q & 1) ? l16[h] : cplx{1.f, 0.f}, c = (q & 2) ? l32[h] : cplx{1.f, 0.f};
          lq[h] = cmul(cmul(a, c), coef[h]);
          pin(lq[h].re); pin(lq[h].im);
        }
      }
    }
    auto scale_u = [&](int i0) {
#pragma unroll
      for (int i = i0; i < i0 + 8; i++) {
        pin(ure[i]); pin(uim[i]);
        const cplx v = cmul(coef[(i >> 1) & 1], cplx{ure[i], uim[i]});
        ure[i] = v.re; uim[i] = v.im;
        pin(ure[i]); pin(uim[i]);
      }
    };
#pragma unroll
    for (int kb = 0; kb < 8; kb++) {
      const int u = 8 + kb, slot = u % NSLOT;
      mbar_wait(fullb + 8 * slot, full_par(u));
      wg_fence();
      const uint32_t dxa = dxw + ((kb + xrot) & 7) * 1024;
#pragma unroll
      for (int kk = 0; kk < 4; kk++)
        wgmma_n96_ss<0, 1, DH128, DH64>(aa, dxa, kk * 32, dring, slot * 16384 + kk * 1024 + lbo(4096), 1);
      wg_commit();
      if (kb == 0) bias(3);
      if (kb != 4) { wg_wait<1>(); release((u - 1) % NSLOT); }
      if (kb == 0) {
        reg_fence(ure); reg_fence(uim);
#pragma unroll
        for (int h = 0; h < 2; h++) e[h] = cplx{ure[2 * h], uim[2 * h]};
      }
      if (kb == 0 || kb == 2 || kb == 3) {
        const int t0 = kb ? 5 * kb - 4 : 1;
#pragma unroll
        for (int t = t0; t < t0 + 5; t++) {
#pragma unroll
          for (int h = 0; h < 2; h++) { const int i = 4 * (t >> 1) + 2 * h + (t & 1); e[h] = cfma(lam[h], e[h], cplx{ure[i], uim[i]}); }
        }
#pragma unroll
        for (int h = 0; h < 2; h++) { pin(e[h].re); pin(e[h].im); }
      }
      if (kb == 4) {
        scale_u(0);
        sched_fence(ck);
#pragma unroll
        for (int h = 0; h < 2; h++) {
          cplx y = {__shfl_up_sync(0xffffffffu, e[h].re, 1, 4), __shfl_up_sync(0xffffffffu, e[h].im, 1, 4)};
          if (q >= 1) e[h] = cfma(l16[h], y, e[h]);
          y = cplx{__shfl_up_sync(0xffffffffu, e[h].re, 2, 4), __shfl_up_sync(0xffffffffu, e[h].im, 2, 4)};
          if (q >= 2) e[h] = cfma(l32[h], y, e[h]);
        }
        if (q == 3) {
#pragma unroll
          for (int h = 0; h < 2; h++) sts_f2(sb + OFF_CARRY + wg * 512 + (w * 16 + gr + 8 * h) * 8, e[h].re, e[h].im);
          mbar_arrive(sb + OFF_GBAR);
        }
#pragma unroll
        for (int h = 0; h < 2; h++) e[h] = cplx{__shfl_up_sync(0xffffffffu, e[h].re, 1, 4), __shfl_up_sync(0xffffffffu, e[h].im, 1, 4)};
        wg_wait<1>(); release((u - 1) % NSLOT);
      }
      if (kb == 5) {
#pragma unroll
        for (int h = 0; h < 2; h++) {
          pre[h] = (q >= 1) ? cmul(coef[h], e[h]) : cplx{0.f, 0.f};
          pin(pre[h].re); pin(pre[h].im);
        }
      }
      if (kb > 5) scale_u((kb - 5) * 8);
    }
    uint32_t H[56], hf[32];
    cplx hst[2];
    const uint32_t hst_addr = xw + (w * 16 + (lane & 15)) * 128 + (((lane >> 4) ^ (lane & 7)) << 4);
    const uint32_t him = (2 - rank) * 16384;
    uint32_t peer;
    asm volatile("mapa.shared::cluster.u32 %0, %1, %2;" : "=r"(peer) : "r"(sb), "r"(rank ^ 1));
    auto credit = [&]() { if (lane == 0) mbar_arrive_cl(peer + OFF_KBAR + wg * 8); };
    uint32_t g2[8];
#pragma unroll
    for (int kb = 0; kb < 8; kb++) {
      const int u = 16 + kb, slot = u % NSLOT;
      mbar_wait(fullb + 8 * slot, full_par(u));
      wg_fence();
#pragma unroll
      for (int kk = 0; kk < 4; kk++)
        wgmma_n128_ss<0, 1, DH128, DH128>(ab, dxw, kb * 16384 + kk * 32, dring, slot * 16384 + kk * 2048 + lbo(8192), 1);
      wg_commit();
      if (kb == 0) scale_u(24);
      if (kb == 4) {
        mbar_wait(sb + OFF_CBAR, 0);
#pragma unroll
        for (int h = 0; h < 2; h++) {
          const float2 c = lds_f2(sb + OFF_CARRY + wg * 512 + (w * 16 + gr + 8 * h) * 8);
          hst[h] = cfma(lq[h], cplx{c.x, c.y}, pre[h]);
        }
#pragma unroll
        for (int i = 0; i < 2; i++) {
          const uint4 v = lds_u4(sb + OFF_GT + wg * 128 + q * 32 + i * 16);
          g2[4 * i] = v.x; g2[4 * i + 1] = v.y; g2[4 * i + 2] = v.z; g2[4 * i + 3] = v.w;
        }
      }
      wg_wait<1>(); release((u - 1) % NSLOT);
      if (kb) sched_fence(ck);
      if (kb < 4) {
#pragma unroll
        for (int i = kb * 6; i < kb * 6 + 6; i++) {
          pin(aa[2 * i]); pin(aa[2 * i + 1]);
          H[i] = gelu2_pair(aa[2 * i], aa[2 * i + 1]);
          pin(H[i]);
        }
      } else {
        const int j0 = (kb - 4) * 2;
        uint32_t rr[4], ri[4];
#pragma unroll
        for (int jj = 0; jj < 2; jj++) {
          const int j = j0 + jj;
#pragma unroll
          for (int h = 0; h < 2; h++) {
            const int i = 4 * j + 2 * h;
            const cplx h0 = cfma(lam[h], hst[h], cplx{ure[i], uim[i]});
            hst[h] = cfma(lam[h], h0, cplx{ure[i + 1], uim[i + 1]});
            rr[jj * 2 + h] = bf2_mul(pack_bf16(h0.re, hst[h].re), g2[j]);
            ri[jj * 2 + h] = bf2_mul(pack_bf16(h0.im, hst[h].im), g2[j]);
          }
        }
        const uint32_t a = hst_addr ^ (j0 << 4);
        asm volatile("stmatrix.sync.aligned.m8n8.x4.shared.b16 [%0], {%1,%2,%3,%4};" ::"r"(a), "r"(rr[0]), "r"(rr[1]), "r"(rr[2]), "r"(rr[3]) : "memory");
        asm volatile("stmatrix.sync.aligned.m8n8.x4.shared.b16 [%0], {%1,%2,%3,%4};" ::"r"(a + him), "r"(ri[0]), "r"(ri[1]), "r"(ri[2]), "r"(ri[3]) : "memory");
      }
    }

    uint4* const psend = g_part + (size_t)(m * 8 + rank) * 3072 + warp * 128 + lane;
    const uint4* const precv = g_part + (size_t)(m * 8 + s) * 3072 + warp * 128 + lane;
    const uint32_t pbuf = OFF_X + warp * 2048 + lane * 16;
    const uint32_t dx0 = ((sb + OFF_X) & 0x3FFFF) >> 4;
    float o[32], fin[32], fs[2];
    uint32_t r0[16], pt[16], sum[16], tag;
    auto recv_issue = [&](uint32_t (&r)[16], int k) {
#pragma unroll
      for (int i = 0; i < 4; i++) ld_b128(precv + k * 1024 + i * 32, r[4 * i], r[4 * i + 1], r[4 * i + 2], r[4 * i + 3]);
    };
    auto stale = [&](uint32_t (&r)[16]) {
      uint32_t t0, t1, r_;
      asm("lop3.b32 %0, %1, %2, %3, 0x7e;" : "=r"(t0) : "r"(r[0]), "r"(r[4]), "r"(tag));
      asm("lop3.b32 %0, %1, %2, %3, 0x7e;" : "=r"(t1) : "r"(r[8]), "r"(r[12]), "r"(tag));
      asm volatile("{.reg .pred p; .reg .b32 t; lop3.b32 t, %1, %2, 1, 0xa8; setp.ne.u32 p, t, 0; vote.sync.any.pred p, p, 0xffffffff; selp.u32 %0, 1, 0, p;}" : "=r"(r_) : "r"(t0), "r"(t1));
      return r_ != 0;
    };
    auto recv_check = [&](uint32_t (&r)[16], int k) {
      if (__builtin_expect(stale(r), 0)) {
        int tries = 0;
#pragma unroll 1
        do { recv_issue(r, k); } while (stale(r) && ++tries < 200000);
      }
    };
    auto gelu_b = [&](int i0, int i1) {
#pragma unroll
      for (int i = i0; i < i1; i++) {
        pin(ab[2 * i]); pin(ab[2 * i + 1]);
        H[24 + i] = gelu2_pair(ab[2 * i], ab[2 * i + 1]);
        pin(H[24 + i]);
      }
    };
    auto mma = [&](float (&d)[32], int p, int k0, int k1, int acc) {
      const uint32_t wo = stage_off(p);
      wg_fence();
#pragma unroll
      for (int k = k0; k < k1; k++) {
        if (k >= 6 && k < 14) {
          const int kk = k - 6;
          if (kk < 4) wgmma_n64_rs<0, DH128, 1>(d, hf[4 * kk], hf[4 * kk + 1], hf[4 * kk + 2], hf[4 * kk + 3], dx0, wo + 14336 + kk * 32, 1);
          else wgmma_n64_rs<0, DH128, -1>(d, hf[4 * kk], hf[4 * kk + 1], hf[4 * kk + 2], hf[4 * kk + 3], dx0, wo + 22528 + (kk - 4) * 32, 1);
        } else {
          const int kk = k < 6 ? k : k - 8;
          wgmma_n64_rs<1, DH128>(d, H[4 * kk], H[4 * kk + 1], H[4 * kk + 2], H[4 * kk + 3], dx0, wo + (kk / 7) * 30720 + (kk % 7) * 2048, k != 0 || acc);
        }
      }
      wg_commit();
    };
    auto recv_peer = [&](int k) {
      mbar_wait(sb + OFF_RBAR + wg * 8, k & 1);
#pragma unroll
      for (int i = 0; i < 4; i++) { const uint4 v = lds_u4(sb + pbuf + i * 512); pt[4 * i] = v.x; pt[4 * i + 1] = v.y; pt[4 * i + 2] = v.z; pt[4 * i + 3] = v.w; }
    };
#pragma unroll
    for (int p = 0; p < 8; p++) {
      if (p == 0) {
        mbar_wait(fullb, full_par(24));
        mma(o, 0, 0, 4, 0);
        bar_sync(1 + wg, 128);
        {
          const uint32_t ha = xw + ((lane >> 4) * 8 + (lane & 7)) * 128 + (((2 * w + ((lane >> 3) & 1)) ^ (lane & 7)) << 4);
#pragma unroll
          for (int kk = 0; kk < 8; kk++)
            asm volatile("ldmatrix.sync.aligned.m8n8.x4.trans.shared.b16 {%0,%1,%2,%3}, [%4];" : "=r"(hf[4 * kk]), "=r"(hf[4 * kk + 1]), "=r"(hf[4 * kk + 2]), "=r"(hf[4 * kk + 3])
                         : "r"(ha + (kk >> 2) * him + (kk & 3) * 2048) : "memory");
        }
        mbar_wait(fullb + 8, full_par(25));
        wg_wait<1>(); release(5);
        gelu_b(0, 6);
        mma(o, 0, 4, 8, 0);
        gelu_b(6, 12);
        mma(o, 0, 8, 12, 0);
        credit();
        gelu_b(12, 18);
        mbar_wait(fullb + 16, full_par(26));
        mma(o, 0, 12, 15, 0);
        gelu_b(18, 24);
        mma(o, 0, 15, 18, 0);
        gelu_b(24, 32);
        if (wg == 1) bar_sync(4, 256);
        mma(o, 0, 18, 22, 0);
      } else {
        bar_sync(3 + wg, 256);
        if (p < 7) mma(o, p, 0, 22, 0);
        else {
          mma(fin, p, 0, 14, 1);
          recv_peer(3);
          tag = lds_u(sb + OFF_EPOCH);
          mma(fin, p, 14, 22, 1);
        }
      }
      if (p < 7 || wg == 0) bar_arrive(4 - wg, 256);
      if (p < 7) mbar_wait(sb + OFF_XFULL + 8 * (p + 1), 1);
      if (p == 2) sts_u(sb + OFF_EPOCH + 4, ck);
      if ((p & 1) == 0) {
        if ((threadIdx.x & 127) == 0) mbar_expect_tx(sb + OFF_RBAR + wg * 8, 8192);
        if (p == 6) {
          mbar_wait(sb + OFF_EMPTY + 32, 0);
          tag = lds_u(sb + OFF_EPOCH);
          recv_check(sum, 0); recv_check(r0, 1);
#pragma unroll
          for (int i = 0; i < 16; i++) sum[i] = bf2_add(sum[i], r0[i]);
        }
        mbar_wait(sb + OFF_KBAR + wg * 8, (p >> 1) & 1);
      } else if (p < 7) {
        if (p == 1) tag = lds_u(sb + OFF_EPOCH);
        recv_peer(p >> 1);
      } else {
        recv_check(r0, 2);
#pragma unroll
        for (int i = 0; i < 16; i++) sum[i] = bf2_add(sum[i], bf2_add(r0[i], pt[i]));
      }
      if (p == 4) {
        mbar_wait(sb + OFF_LBAR, 1);
#pragma unroll
        for (int j = 0; j < 8; j++) {
          const uint4 v = lds_u4(sb + pbuf + 16384 + (j >> 2) * 16384 + (j & 3) * 512);
          fin[4 * j] = __uint_as_float(v.x); fin[4 * j + 1] = __uint_as_float(v.y); fin[4 * j + 2] = __uint_as_float(v.z); fin[4 * j + 3] = __uint_as_float(v.w);
        }
      }
      wg_wait<0>();
      if (p < 5) release(p);
      if (p < 7) reg_fence(o); else reg_fence(fin);
      if ((p & 1) == 0) {
        if (p == 6) recv_issue(r0, 2);
#pragma unroll
        for (int i = 0; i < 4; i++)
          asm volatile("st.async.shared::cluster.mbarrier::complete_tx::bytes.v4.b32 [%0], {%1,%2,%3,%4}, [%5];" ::"r"(peer + pbuf + i * 512),
                       "r"(pack_bf16(o[8 * i], o[8 * i + 1])), "r"(pack_bf16(o[8 * i + 2], o[8 * i + 3])), "r"(pack_bf16(o[8 * i + 4], o[8 * i + 5])),
                       "r"(pack_bf16(o[8 * i + 6], o[8 * i + 7])), "r"(peer + OFF_RBAR + wg * 8) : "memory");
      } else if (p < 7) {
        const int k = p >> 1;
#pragma unroll
        for (int i = 0; i < 4; i++) {
#pragma unroll
          for (int c = 4 * i; c < 4 * i + 4; c++) pt[c] = bf2_add(pt[c], pack_bf16(o[2 * c], o[2 * c + 1]));
          asm("lop3.b32 %0, %0, 1, %1, 0xb8;" : "+r"(pt[4 * i]) : "r"(tag));
          st_b128(psend + (((sp + 1 + k) & 3) * 6 + k) * 1024 + i * 32, pt[4 * i], pt[4 * i + 1], pt[4 * i + 2], pt[4 * i + 3]);
        }
        __syncwarp();
        credit();
        if (p == 3) recv_issue(sum, 0);
        if (p == 5) recv_issue(r0, 1);
      }
      if (p == 2) {
#pragma unroll
        for (int h = 0; h < 2; h++) { fs[h] = __fdividef(2.f, 4.f + bf_lo(lds_h(sb + OFF_GS + (wg * 64 + w * 16 + gr + 8 * h) * 2))); pin(fs[h]); }
      }
    }
    {
      const uint32_t tb = sb + OFF_X + stage_off(0) + warp * 4096;
      const uint32_t ta = tb + gr * 256 + ((gr & 3) << 5) + q * 8;
      const uint32_t la = tb + (lane >> 3) * 256 + (((lane & 7) << 4) ^ ((lane >> 3) << 5));
      float* op = out + (size_t)(m * 128 + wg * 64 + (lane >> 4) * 16 + w * 4 + ((lane >> 3) & 1)) * DM + s * 64 + (lane & 7) * 4;
#pragma unroll
      for (int qt = 0; qt < 4; qt++) {
        const int h = qt & 1, ch = qt >> 1;
#pragma unroll
        for (int j = 0; j < 4; j++) {
          const int i = ch * 8 + j * 2 + h;
          sts_f2((ta ^ (j << 5)) + h * 2048 + ch * 128, (fin[2 * i] + bf_lo(sum[i])) * fs[h], (fin[2 * i + 1] + bf_hi(sum[i])) * fs[h]);
        }
        __syncwarp();
#pragma unroll
        for (int r = 0; r < 2; r++)
          *reinterpret_cast<uint4*>(op + (r * 32 + h * 2) * DM + ch * 32) = lds_u4(la + (h * 2 + r) * 1024 + ch * 128);
      }
      if (threadIdx.x == 128) g_epoch[b] = tag;
    }
  } else {
    asm volatile("setmaxnreg.dec.sync.aligned.u32 56;");
    int wsel = warp;
    asm("" : "+r"(wsel));
    if (wsel > 8) {
      const uint4* gwp = reinterpret_cast<const uint4*>(gate_w) + (lane & 7);
      uint4 gw[4];
      if (warp != 11) {
        const int t = threadIdx.x - 288;
        unsigned par;
        asm volatile("ld.relaxed.gpu.global.u32 %0, [%1];" : "=r"(par) : "l"(g_epoch + b) : "memory");
        const float pr = bf_ld(lam_re + s * 64 + t), pi = bf_ld(lam_im + s * 64 + t), pd = bf_ld(log_dt + s * 64 + t);
#pragma unroll
        for (int i = 0; i < 4; i++) gw[i] = __ldg(gwp + i * 8);
        cluster_wait();
        par = __shfl_sync(0xffffffffu, (par + 1) & 1, 0);
        cplx l64 = make_lam(pr, pi, pd);
        {
          const float inv = __fdividef(1.f, fmaf(pr, pr, pi * pi));
          const cplx cf = cmul(cplx{l64.re - 1.f, l64.im}, cplx{pr * inv, -pi * inv});
          sts_f4(sb + OFF_LC + t * 16, l64.re, l64.im, cf.re, cf.im);
          mbar_arrive(sb + OFF_LBAR);
        }
#pragma unroll
        for (int i = 0; i < 6; i++) l64 = cmul(l64, l64);
        cplx l128 = cmul(l64, l64);
        pin(l128.re); pin(l128.im);
        gate_rows<1>(sb, xrot, s * 16 + (warp - 9) * 4, gw, gwp, g_gate + m * 128, par);
        uint32_t vr[15], vi[15];
#pragma unroll
        for (int i = 0; i < 15; i++) { vr[i] = par; vi[i] = 0; pin(vr[i]); pin(vi[i]); }
        mbar_wait(sb + OFF_GBAR, 0);
        const float2 e0 = lds_f2(sb + OFF_CARRY + t * 8), e1 = lds_f2(sb + OFF_CARRY + 512 + t * 8);
        float2* eb = g_end + s * 1024 + t;
        {
          const cplx e = cfma(l64, cplx{e0.x, e0.y}, cplx{e1.x, e1.y});
          const unsigned long long v = ((unsigned long long)__float_as_uint(e.im) << 32) | ((__float_as_uint(e.re) & ~1u) | par);
          asm volatile("st.relaxed.gpu.global.b64 [%0], %1;" ::"l"(eb + m * 64), "l"(v) : "memory");
        }
        __nanosleep(300);
        const float2* e15 = eb + (m - 15) * 64;
        int tries = 0;
        bool bad;
#pragma unroll 1
        do {
#pragma unroll
          for (int i = 0; i < 15; i++)
            asm volatile("{.reg .pred p; .reg .b64 v; mov.b64 v, {%0,%1}; setp.ge.s32 p, %3, %4; @p ld.relaxed.gpu.global.b64 v, [%2]; mov.b64 {%0,%1}, v;}"
                         : "+r"(vr[i]), "+r"(vi[i]) : "l"(e15 + i * 64), "r"(m), "r"(15 - i) : "memory");
          uint32_t x = vr[0] ^ par;
#pragma unroll
          for (int i = 1; i < 15; i++) asm("lop3.b32 %0, %0, %1, %2, 0xf6;" : "+r"(x) : "r"(vr[i]), "r"(par));
          bad = __any_sync(0xffffffffu, x & 1);
        } while (bad && ++tries < 200000);
        cplx S = {__uint_as_float(vr[0]), __uint_as_float(vi[0])};
#pragma unroll
        for (int i = 1; i < 15; i++) S = cfma(l128, S, cplx{__uint_as_float(vr[i]), __uint_as_float(vi[i])});
        const cplx S1 = cfma(l64, S, cplx{e0.x, e0.y});
        sts_f2(sb + OFF_CARRY + t * 8, S.re, S.im);
        sts_f2(sb + OFF_CARRY + 512 + t * 8, S1.re, S1.im);
        mbar_arrive(sb + OFF_CBAR);
        mbar_wait(sb + OFF_CBAR, 0);
        const int gr = lane >> 2, q = lane & 3;
        float2 db[8];
#pragma unroll
        for (int j = 0; j < 8; j++) db[j] = lds_f2(sb + OFF_DB + j * 32 + q * 8);
        mbar_wait(sb + OFF_XFULL + 16, 1);
        mbar_wait(sb + OFF_EMPTY, 0);
#pragma unroll 1
        for (int cw = warp - 9; cw < 8; cw += 2) {
          const float r0 = 0.5f * bf_lo(lds_h(sb + OFF_GS + (cw * 16 + gr) * 2)), r1 = 0.5f * bf_lo(lds_h(sb + OFF_GS + (cw * 16 + gr) * 2 + 16));
          const uint32_t xa = sb + OFF_X + (1 + rank) * 16384 + (cw * 16 + (lane & 15)) * 128 + (((lane >> 4) ^ (lane & 7)) << 4);
          uint32_t xv[16];
#pragma unroll
          for (int i = 0; i < 4; i++)
            asm volatile("ldmatrix.sync.aligned.m8n8.x4.shared.b16 {%0,%1,%2,%3}, [%4];" : "=r"(xv[4 * i]), "=r"(xv[4 * i + 1]), "=r"(xv[4 * i + 2]), "=r"(xv[4 * i + 3])
                         : "r"(xa ^ (i << 5)) : "memory");
          __syncwarp();
#pragma unroll
          for (int j = 0; j < 8; j++) {
            const uint32_t x0 = bf2_mul(xv[2 * j], __float_as_uint(db[j].x)), x1 = bf2_mul(xv[2 * j + 1], __float_as_uint(db[j].x));
            pin(db[j].y);
            const float bl = bf_lo(__float_as_uint(db[j].y)), bh = bf_hi(__float_as_uint(db[j].y));
            sts_f4(sb + OFF_X + 16384 + (j >> 2) * 16384 + cw * 2048 + (j & 3) * 512 + lane * 16, fmaf(bf_lo(x0), r0, bl), fmaf(bf_hi(x0), r0, bh),
                   fmaf(bf_lo(x1), r1, bl), fmaf(bf_hi(x1), r1, bh));
          }
        }
        mbar_arrive(sb + OFF_LBAR);
      } else {
#pragma unroll
        for (int i = 0; i < 4; i++) gw[i] = __ldg(gwp + i * 8);
        unsigned par;
        asm volatile("ld.relaxed.gpu.global.u32 %0, [%1];" : "=r"(par) : "l"(g_epoch + b) : "memory");
        const uint32_t dk = __ldg(reinterpret_cast<const uint32_t*>(dskip + s * 64) + lane), bb = __ldg(reinterpret_cast<const uint32_t*>(b2 + s * 64) + lane);
        cluster_wait();
        if (lane == 0) sts_u(sb + OFF_EPOCH, par + 1);
        par = (par + 1) & 1;
        gate_rows<2>(sb, xrot, s * 16 + 8, gw, gwp, g_gate + m * 128, par);
        mbar_wait(sb + OFF_GBAR, 0);
        sts_u2(sb + OFF_DB + lane * 8, dk, bf2_add(bb, bb));
        uint32_t g0, g1, g2, g3;
        int tries = 0;
#pragma unroll 1
        do {
          asm volatile("ld.relaxed.gpu.global.v4.u32 {%0,%1,%2,%3}, [%4];" : "=r"(g0), "=r"(g1), "=r"(g2), "=r"(g3) : "l"(g_gate + m * 128 + lane * 4) : "memory");
        } while ((((g0 ^ par) | (g1 ^ par) | (g2 ^ par) | (g3 ^ par)) & 1) && ++tries < 200000);
        const uint32_t p01 = pack_bf16(__uint_as_float(g0), __uint_as_float(g1)), p23 = pack_bf16(__uint_as_float(g2), __uint_as_float(g3));
        sts_u2(sb + OFF_GS + lane * 8, p01, p23);
        const uint32_t gt = sb + OFF_GT + (lane >> 4) * 128 + (lane & 1) * 64 + ((lane >> 1) & 7) * 4;
        sts_u(gt, p01);
        sts_u(gt + 32, p23);
        mbar_arrive(sb + OFF_CBAR);
      }
    } else {
      cluster_wait();
      if (elect_one()) {
        const uint32_t t0 = clock();
#pragma unroll 1
        for (int u = 1; u < 8; u++) {
          while ((uint32_t)clock() - t0 < 200 + (u - 1) * 480) {}
          const uint32_t fb = sb + OFF_XFULL + 8 * u;
          mbar_expect_tx(fb, 32768);
          tma5d_mc(sb + OFF_X + ((u + xrot) & 7) * 16384 + rank * 8192, &maps.x, u * 64, 2 * m + rank, fb);
          const int sl = u < 6 ? u : u - 6;
          if (u >= 6) mbar_wait(sb + OFF_EMPTY + 8 * sl, 0);
          tma2d(sb + OFF_RING + sl * 16384, &maps.bre, u * 64, s * 64, fb);
          tma2d(sb + OFF_RING + sl * 16384 + 8192, &maps.bim, u * 64, s * 64, fb);
          if (u == 2) map_prefetch(&maps.w1b);
        }
        int slot = 2; uint32_t ph = 0;
#pragma unroll 1
        for (int u = 8; u < 24; u++) {
          const uint32_t fb = sb + OFF_FULL + 8 * slot, dst = sb + OFF_RING + slot * 16384;
          mbar_wait(sb + OFF_EMPTY + 8 * slot, ph);
          if (u < 16) {
            mbar_expect_tx(fb, 12288);
            tma3d(dst, &maps.w1b, 0, (u - 8) * 64, s * 7, fb);
            if (u < 12) map_prefetch(&maps.w1a + (u - 8));
          } else {
            mbar_expect_tx(fb, 16384);
            tma2d(dst, &maps.w1a, s * 224 + 96, ((u - xrot) & 7) * 64, fb);
            tma2d(dst + 8192, &maps.w1a, s * 224 + 160, ((u - xrot) & 7) * 64, fb);
          }
          if (++slot == NSLOT) { slot = 0; ph ^= 1; }
        }
#pragma unroll 1
        for (int j = 0; j < 3; j++) {
          const uint32_t fb = sb + OFF_FULL + 8 * j, dst = sb + OFF_X + stage_off(0);
          const int c = ((sp + 1) & 3) * 128 + ((rank ^ 1) << 6);
          mbar_wait(sb + OFF_EMPTY + 8 + 8 * j, 1);
          mbar_expect_tx(fb, j == 1 ? 16384 : 14336);
          if (j == 1) {
            tma2d(dst + 14336, &maps.cre, s * 64, c, fb);
            tma2d(dst + 22528, &maps.cim, s * 64, c, fb);
          } else {
            tma2d(dst + j * 15360, &maps.w2, c, s * 224 + j * 56, fb);
          }
        }
#pragma unroll 1
        for (int p = 1; p < 8; p++) {
          const int c = ((sp + 1 + (p >> 1)) & 3) * 128 + (((rank ^ p ^ 1) & 1) << 6);
          const uint32_t fb = sb + OFF_XFULL + 8 * p, dst = sb + OFF_X + stage_off(p);
          if (p == 2 || p > 3) mbar_wait(sb + OFF_EMPTY + (p == 2 ? 40 : (p - 4) * 8), p == 2);
          mbar_expect_tx(fb, 45056);
          tma2d(dst, &maps.w2, c, s * 224, fb);
          tma2d(dst + 14336, &maps.cre, s * 64, c, fb);
          tma2d(dst + 22528, &maps.cim, s * 64, c, fb);
          tma2d(dst + 30720, &maps.w2, c, s * 224 + 112, fb);
        }
      }
    }
  }
}

typedef CUresult (*EncFn)(CUtensorMap*, CUtensorMapDataType, cuuint32_t, void*, const cuuint64_t*, const cuuint64_t*, const cuuint32_t*,
                          const cuuint32_t*, CUtensorMapInterleave, CUtensorMapSwizzle, CUtensorMapL2promotion, CUtensorMapFloatOOBfill);

void encode(EncFn f, CUtensorMap* mp, const void* p, int rank, const cuuint64_t* dims, const cuuint64_t* strides, const cuuint32_t* box, CUtensorMapSwizzle sw) {
  cuuint32_t es[5] = {1, 1, 1, 1, 1};
  f(mp, CU_TENSOR_MAP_DATA_TYPE_BFLOAT16, rank, const_cast<void*>(p), dims, strides, box, es, CU_TENSOR_MAP_INTERLEAVE_NONE, sw,
    CU_TENSOR_MAP_L2_PROMOTION_L2_128B, CU_TENSOR_MAP_FLOAT_OOB_FILL_NONE);
}

}

extern "C" void kernel_launch(void* const* d_in, const int* in_sizes, int n_in, void* d_out, int out_size) {
  typedef const __nv_bfloat16* bp;
  bp x = (bp)d_in[0], lre = (bp)d_in[1], lim = (bp)d_in[2], bre = (bp)d_in[3], bim = (bp)d_in[4], cre = (bp)d_in[5], cim = (bp)d_in[6],
     ldt = (bp)d_in[7], dsk = (bp)d_in[8], w1 = (bp)d_in[10], b1 = (bp)d_in[11], w2 = (bp)d_in[12], b2 = (bp)d_in[13], gw = (bp)d_in[14];
  static EncFn enc = nullptr;
  if (!enc) {
    void* f = nullptr;
    cudaDriverEntryPointQueryResult qr;
    cudaGetDriverEntryPoint("cuTensorMapEncodeTiled", &f, cudaEnableDefault, &qr);
    enc = (EncFn)f;
    cudaFuncSetAttribute(fused_kernel, cudaFuncAttributeMaxDynamicSharedMemorySize, SMEM_BYTES);
  }
  Maps maps;
  {
    cuuint64_t d[5] = {DM, 2, 4, 8, SEQ / 64}, st[4] = {DM * 2, 16 * DM * 2, 2 * DM * 2, 64 * DM * 2};
    cuuint32_t bx[5] = {64, 2, 4, 8, 1};
    encode(enc, &maps.x, x, 5, d, st, bx, CU_TENSOR_MAP_SWIZZLE_128B);
  }
  {
    cuuint64_t d[2] = {DM, DM}, st[1] = {DM * 2};
    cuuint32_t bx[2] = {64, 64};
    encode(enc, &maps.bre, bre, 2, d, st, bx, CU_TENSOR_MAP_SWIZZLE_128B);
    encode(enc, &maps.bim, bim, 2, d, st, bx, CU_TENSOR_MAP_SWIZZLE_128B);
    encode(enc, &maps.cre, cre, 2, d, st, bx, CU_TENSOR_MAP_SWIZZLE_128B);
    encode(enc, &maps.cim, cim, 2, d, st, bx, CU_TENSOR_MAP_SWIZZLE_128B);
  }
  {
    cuuint64_t d[2] = {FF, DM}, st[1] = {FF * 2};
    cuuint32_t bx[2] = {64, 64};
    encode(enc, &maps.w1a, w1, 2, d, st, bx, CU_TENSOR_MAP_SWIZZLE_128B);
    cuuint64_t d3[3] = {32, DM, FF / 32}, st3[2] = {FF * 2, 64};
    cuuint32_t bx3[3] = {32, 64, 3};
    encode(enc, &maps.w1b, w1, 3, d3, st3, bx3, CU_TENSOR_MAP_SWIZZLE_64B);
  }
  {
    cuuint64_t d[2] = {DM, FF}, st[1] = {DM * 2};
    cuuint32_t bx[2] = {64, 112};
    encode(enc, &maps.w2, w2, 2, d, st, bx, CU_TENSOR_MAP_SWIZZLE_128B);
  }
  fused_kernel<<<128, 384, SMEM_BYTES>>>(lre, lim, ldt, dsk, b1, b2, gw, (float*)d_out, maps);
}
```

```cpp
#include <cuda_runtime.h>
#include <cuda_bf16.h>
#include <cuda.h>
#include <stdint.h>

namespace {

constexpr int SEQ = 2048, DM = 512, FF = 1792;
constexpr int NSLOT = 6;
constexpr uint32_t OFF_X = 0, OFF_RING = 131072, OFF_MISC = 229376;
constexpr uint32_t OFF_XFULL = OFF_MISC, OFF_FULL = OFF_XFULL + 64, OFF_RBAR = OFF_FULL + 48, OFF_EMPTY = OFF_RBAR + 16, OFF_KBAR = OFF_EMPTY + 48,
                   OFF_GBAR = OFF_KBAR + 16, OFF_LBAR = OFF_GBAR + 8, OFF_CBAR = OFF_LBAR + 8, OFF_EPOCH = OFF_CBAR + 8;
constexpr uint32_t OFF_LC = OFF_MISC + 256;
constexpr uint32_t OFF_GS = OFF_LC;
constexpr uint32_t OFF_GT = OFF_LC + 256;
constexpr uint32_t OFF_DB = OFF_LC + 512;
constexpr uint32_t OFF_CARRY = OFF_LC + 1024;
constexpr uint32_t SMEM_BYTES = OFF_CARRY + 1024;
static_assert(SMEM_BYTES <= 232448, "smem");

struct Maps { CUtensorMap x, bre, bim, w1b, w1a, w2, cre, cim; };
__host__ __device__ constexpr uint32_t stage_off(int p) { return 49152 + 45056 * (((p >> 1) & 1) + 2 * (p & 1)); }
__host__ __device__ constexpr uint32_t full_par(int u) { return ((u - 8) / 6 + (u % 6 == 0)) & 1; }

__device__ uint4 g_part[16 * 8 * 3 * 1024];
__device__ float2 g_end[8 * 16 * 64];
__device__ unsigned g_gate[SEQ];
__device__ unsigned g_epoch[128];

__device__ __forceinline__ void mbar_init(uint32_t bar, uint32_t cnt) { asm volatile("mbarrier.init.shared::cta.b64 [%0], %1;" ::"r"(bar), "r"(cnt)); }
__device__ __forceinline__ void mbar_expect_tx(uint32_t bar, uint32_t bytes) { asm volatile("mbarrier.arrive.expect_tx.shared::cta.b64 _, [%0], %1;" ::"r"(bar), "r"(bytes) : "memory"); }
__device__ __forceinline__ void mbar_arrive(uint32_t bar) { asm volatile("mbarrier.arrive.shared::cta.b64 _, [%0];" ::"r"(bar) : "memory"); }
__device__ __forceinline__ void mbar_arrive_cl(uint32_t cbar) { asm volatile("mbarrier.arrive.shared::cluster.b64 _, [%0];" ::"r"(cbar) : "memory"); }
__device__ __forceinline__ void mbar_wait(uint32_t bar, uint32_t parity) {
  asm volatile(
      "{\n.reg .pred p;\n.reg .u32 c;\n"
      "mbarrier.try_wait.parity.shared::cta.b64 p, [%0], %1;\n"
      "@p bra.uni LAB_DONE;\n"
      "mov.u32 c, 0;\n"
      "LAB_WAIT:\n"
      "mbarrier.try_wait.parity.shared::cta.b64 p, [%0], %1;\n"
      "@p bra.uni LAB_DONE;\n"
      "add.u32 c, c, 1;\nsetp.lt.u32 p, c, 200000;\n@p bra.uni LAB_WAIT;\n"
      "LAB_DONE:\n}" ::"r"(bar), "r"(parity) : "memory");
}
__device__ __forceinline__ void tma2d(uint32_t dst, const CUtensorMap* m, int c0, int c1, uint32_t bar) {
  asm volatile("cp.async.bulk.tensor.2d.shared::cluster.global.mbarrier::complete_tx::bytes [%0], [%1, {%3,%4}], [%2];"
               ::"r"(dst), "l"(m), "r"(bar), "r"(c0), "r"(c1) : "memory");
}
__device__ __forceinline__ void tma3d(uint32_t dst, const CUtensorMap* m, int c0, int c1, int c2, uint32_t bar) {
  asm volatile("cp.async.bulk.tensor.3d.shared::cluster.global.mbarrier::complete_tx::bytes [%0], [%1, {%3,%4,%5}], [%2];"
               ::"r"(dst), "l"(m), "r"(bar), "r"(c0), "r"(c1), "r"(c2) : "memory");
}
__device__ __forceinline__ void tma5d(uint32_t dst, const CUtensorMap* m, int c0, int c4, uint32_t bar) {
  asm volatile("cp.async.bulk.tensor.5d.shared::cluster.global.mbarrier::complete_tx::bytes [%0], [%1, {%3,%5,%5,%5,%4}], [%2];"
               ::"r"(dst), "l"(m), "r"(bar), "r"(c0), "r"(c4), "r"(0) : "memory");
}
__device__ __forceinline__ void tma5d_mc(uint32_t dst, const CUtensorMap* m, int c0, int c4, uint32_t bar) {
  asm volatile("cp.async.bulk.tensor.5d.shared::cluster.global.mbarrier::complete_tx::bytes.multicast::cluster [%0], [%1, {%3,%5,%5,%5,%4}], [%2], %6;"
               ::"r"(dst), "l"(m), "r"(bar), "r"(c0), "r"(c4), "r"(0), "h"((uint16_t)3) : "memory");
}
__device__ __forceinline__ void map_prefetch(const CUtensorMap* m) { asm volatile("prefetch.tensormap [%0];" ::"l"(m) : "memory"); }
__device__ __forceinline__ bool elect_one() {
  uint32_t pred;
  asm volatile("{.reg .pred P; elect.sync _|P, 0xffffffff; selp.u32 %0, 1, 0, P;}" : "=r"(pred));
  return pred != 0;
}
__device__ __forceinline__ void cluster_wait() { asm volatile("barrier.cluster.wait.aligned;" ::: "memory"); }
__device__ __forceinline__ void wg_fence() { asm volatile("wgmma.fence.sync.aligned;" ::: "memory"); }
__device__ __forceinline__ void wg_commit() { asm volatile("wgmma.commit_group.sync.aligned;" ::: "memory"); }
template <int N> __device__ __forceinline__ void wg_wait() { asm volatile("wgmma.wait_group.sync.aligned %0;" ::"n"(N) : "memory"); }
__device__ __forceinline__ void pin(float& a) { asm volatile("" : "+f"(a)::"memory"); }
__device__ __forceinline__ void pin(uint32_t& a) { asm volatile("" : "+r"(a)::"memory"); }
template <int N> __device__ __forceinline__ void reg_fence(float (&d)[N]) {
#pragma unroll
  for (int i = 0; i < N; i++) pin(d[i]);
}
__device__ __forceinline__ void sched_fence(uint32_t& ck) { asm volatile("{.reg .b32 c; mov.u32 c, %%clock; xor.b32 %0, %0, c;}" : "+r"(ck)::"memory"); }
__device__ __forceinline__ void bar_sync(int id, int n) { asm volatile("bar.sync %0, %1;" ::"r"(id), "r"(n) : "memory"); }
__device__ __forceinline__ void bar_arrive(int id, int n) { asm volatile("bar.arrive %0, %1;" ::"r"(id), "r"(n) : "memory"); }
constexpr uint32_t DH128 = (1024 >> 4) | (1u << 30), DH64 = (512 >> 4) | (2u << 30);
__host__ __device__ constexpr uint32_t lbo(uint32_t bytes) { return (bytes >> 4) << 20; }
__device__ __forceinline__ uint32_t pack_bf16(float lo, float hi) { uint32_t r; asm("cvt.rn.bf16x2.f32 %0, %1, %2;" : "=r"(r) : "f"(hi), "f"(lo)); return r; }
__device__ __forceinline__ float bf_lo(uint32_t v) { return __uint_as_float(v << 16); }
__device__ __forceinline__ float bf_hi(uint32_t v) { return __uint_as_float(v & 0xffff0000u); }
__device__ __forceinline__ float bf_ld(const __nv_bfloat16* p) { return __bfloat162float(__ldg(p)); }
__device__ __forceinline__ uint32_t late16(uint32_t bar) {
  uint32_t r;
  asm volatile("{.reg .pred p; mbarrier.test_wait.parity.shared::cta.b64 p, [%1], 0; selp.u32 %0, 16, 0, p;}" : "=r"(r) : "r"(bar) : "memory");
  return r;
}
__device__ __forceinline__ float2 lds_f2(uint32_t a) { float2 v; asm volatile("ld.shared.v2.f32 {%0,%1}, [%2];" : "=f"(v.x), "=f"(v.y) : "r"(a)); return v; }
__device__ __forceinline__ uint32_t lds_h(uint32_t a) { uint32_t v; asm volatile("ld.shared.u16 %0, [%1];" : "=r"(v) : "r"(a)); return v; }
__device__ __forceinline__ uint32_t lds_u(uint32_t a) { uint32_t v; asm volatile("ld.shared.u32 %0, [%1];" : "=r"(v) : "r"(a)); return v; }
__device__ __forceinline__ uint4 lds_u4(uint32_t a) { uint4 v; asm volatile("ld.shared.v4.u32 {%0,%1,%2,%3}, [%4];" : "=r"(v.x), "=r"(v.y), "=r"(v.z), "=r"(v.w) : "r"(a)); return v; }
__device__ __forceinline__ void sts_u(uint32_t a, uint32_t v) { asm volatile("st.shared.u32 [%0], %1;" ::"r"(a), "r"(v) : "memory"); }
__device__ __forceinline__ void sts_u2(uint32_t a, uint32_t x, uint32_t y) { asm volatile("st.shared.v2.u32 [%0], {%1,%2};" ::"r"(a), "r"(x), "r"(y) : "memory"); }
__device__ __forceinline__ void sts_f2(uint32_t a, float x, float y) { asm volatile("st.shared.v2.f32 [%0], {%1,%2};" ::"r"(a), "f"(x), "f"(y) : "memory"); }
__device__ __forceinline__ void sts_f4(uint32_t a, float x, float y, float z, float w) {
  asm volatile("st.shared.v4.f32 [%0], {%1,%2,%3,%4};" ::"r"(a), "f"(x), "f"(y), "f"(z), "f"(w) : "memory");
}
__device__ __forceinline__ void st_b128(uint4* p, uint32_t a, uint32_t b, uint32_t c, uint32_t d) {
  asm volatile("st.relaxed.gpu.global.v4.b32 [%0], {%1,%2,%3,%4};" ::"l"(p), "r"(a), "r"(b), "r"(c), "r"(d) : "memory");
}
__device__ __forceinline__ void ld_b128(const uint4* p, uint32_t& a, uint32_t& b, uint32_t& c, uint32_t& d) {
  asm volatile("{.reg .b64 l, h; .reg .b128 v; ld.relaxed.gpu.global.b128 v, [%4]; mov.b128 {l,h}, v; mov.b64 {%0,%1}, l; mov.b64 {%2,%3}, h;}"
               : "=r"(a), "=r"(b), "=r"(c), "=r"(d) : "l"(p) : "memory");
}
__device__ __forceinline__ uint32_t bf2_mul(uint32_t a, uint32_t b) { uint32_t r; asm("mul.rn.bf16x2 %0, %1, %2;" : "=r"(r) : "r"(a), "r"(b)); return r; }
__device__ __forceinline__ uint32_t bf2_add(uint32_t a, uint32_t b) { uint32_t r; asm("add.rn.bf16x2 %0, %1, %2;" : "=r"(r) : "r"(a), "r"(b)); return r; }
__device__ __forceinline__ uint32_t bf2_fma(uint32_t a, uint32_t b, uint32_t c) { uint32_t r; asm("fma.rn.bf16x2 %0, %1, %2, %3;" : "=r"(r) : "r"(a), "r"(b), "r"(c)); return r; }
__device__ __forceinline__ uint32_t gelu2_pair(float a, float b) {
  const uint32_t v = pack_bf16(a, b);
  uint32_t t;
  asm("tanh.approx.bf16x2 %0, %1;" : "=r"(t) : "r"(bf2_fma(v, bf2_fma(bf2_mul(v, v), 0x3d123d12u, 0xbe4fbe4fu), v)));
  return bf2_fma(v, t, v);
}
struct cplx { float re, im; };
__device__ __forceinline__ cplx cmul(cplx a, cplx b) { return {fmaf(a.re, b.re, -a.im * b.im), fmaf(a.re, b.im, a.im * b.re)}; }
__device__ __forceinline__ cplx cfma(cplx a, cplx b, cplx c) {
  return {fmaf(a.re, b.re, fmaf(-a.im, b.im, c.re)), fmaf(a.re, b.im, fmaf(a.im, b.re, c.im))};
}
__device__ __forceinline__ cplx make_lam(float lre, float lim, float ldt) {
  float dt = __bfloat162float(__float2bfloat16_rn(expf(ldt)));
  float mag = expf(dt * lre), sn, cs;
  sincospif(dt * lim * 0.31830988618379067f, &sn, &cs);
  return {mag * cs, mag * sn};
}

template <int NG>
__device__ __forceinline__ void gate_rows(uint32_t sb, int lane, int xrot, int row0, uint4 (&gw)[4], const uint4* gwp, unsigned* dst, unsigned par) {
  const int row = row0 + (lane >> 3);
  const uint32_t xr0 = sb + OFF_X + row * 128 + (((lane & 7) ^ (row & 7)) << 4), xr1 = (xr0 + 512) ^ 64;
  float z[NG], y[NG];
#pragma unroll
  for (int r = 0; r < NG; r++) z[r] = y[r] = 0.f;
#pragma unroll
  for (int kb = 0; kb < 8; kb++) {
    const uint4 w = gw[kb & 3];
    if (kb < 4) gw[kb] = __ldg(gwp + (kb + 4) * 8);
    mbar_wait(sb + OFF_XFULL + 8 * kb, 0);
#pragma unroll
    for (int r = 0; r < NG; r++) {
      const uint4 a = lds_u4((r ? xr1 : xr0) + ((kb + xrot) & 7) * 16384);
      const uint32_t p[4] = {bf2_mul(a.x, w.x), bf2_mul(a.y, w.y), bf2_mul(a.z, w.z), bf2_mul(a.w, w.w)};
#pragma unroll
      for (int c = 0; c < 4; c++) { z[r] += bf_lo(p[c]); y[r] += bf_hi(p[c]); }
    }
  }
  float zz = z[0] + y[0];
  if (NG == 2) {
    const float z1 = z[NG - 1] + y[NG - 1];
    zz = ((lane & 4) ? z1 : zz) + __shfl_xor_sync(0xffffffffu, (lane & 4) ? zz : z1, 4);
  } else {
    zz += __shfl_xor_sync(0xffffffffu, zz, 4);
  }
  zz += __shfl_xor_sync(0xffffffffu, zz, 2);
  zz += __shfl_xor_sync(0xffffffffu, zz, 1);
  zz = bf_lo(pack_bf16(zz, 0.f));
  const float rho = 4.f * expf(zz > 40.f ? 40.f : zz);
  if ((lane & (NG == 2 ? 3 : 7)) == 0)
    asm volatile("st.relaxed.gpu.global.u32 [%0], %1;" ::"l"(dst + row + (lane & 4)), "r"((__float_as_uint(rho) & ~1u) | par) : "memory");
}

template<int TA,int TB,uint32_t AH,uint32_t BH> __device__ __forceinline__ void wgmma_n64_ss(float (&d)[32], uint32_t al, uint32_t ao, uint32_t bl, uint32_t bo, int scale_d){
  asm volatile("{.reg .pred p; .reg .b32 t, v; .reg .b64 da, db; setp.ne.b32 p, %36, 0; add.u32 t, %32, %33; mov.b64 da, {t, %39}; add.u32 v, %34, %35; mov.b64 db, {v, %40};\n"
   "wgmma.mma_async.sync.aligned.m64n64k16.f32.bf16.bf16 {%0,%1,%2,%3,%4,%5,%6,%7,%8,%9,%10,%11,%12,%13,%14,%15,%16,%17,%18,%19,%20,%21,%22,%23,%24,%25,%26,%27,%28,%29,%30,%31}, da, db, p, 1, 1, %37, %38;}"
   : "+f"(d[0]),"+f"(d[1]),"+f"(d[2]),"+f"(d[3]),"+f"(d[4]),"+f"(d[5]),"+f"(d[6]),"+f"(d[7]),"+f"(d[8]),"+f"(d[9]),"+f"(d[10]),"+f"(d[11]),"+f"(d[12]),"+f"(d[13]),"+f"(d[14]),"+f"(d[15]),"+f"(d[16]),"+f"(d[17]),"+f"(d[18]),"+f"(d[19]),"+f"(d[20]),"+f"(d[21]),"+f"(d[22]),"+f"(d[23]),"+f"(d[24]),"+f"(d[25]),"+f"(d[26]),"+f"(d[27]),"+f"(d[28]),"+f"(d[29]),"+f"(d[30]),"+f"(d[31])
   : "r"(al),"r"(ao >> 4),"r"(bl),"r"(bo >> 4),"r"(scale_d),"n"(TA),"n"(TB),"n"(AH),"n"(BH));
}
template<int TB,uint32_t BH,int SA=1> __device__ __forceinline__ void wgmma_n64_rs(float (&d)[32], uint32_t a0,uint32_t a1,uint32_t a2,uint32_t a3, uint32_t bl, uint32_t bo, int scale_d){
  asm volatile("{.reg .pred p; .reg .b32 t; .reg .b64 db; setp.ne.b32 p, %38, 0; add.u32 t, %36, %37; mov.b64 db, {t, %40};\n"
   "wgmma.mma_async.sync.aligned.m64n64k16.f32.bf16.bf16 {%0,%1,%2,%3,%4,%5,%6,%7,%8,%9,%10,%11,%12,%13,%14,%15,%16,%17,%18,%19,%20,%21,%22,%23,%24,%25,%26,%27,%28,%29,%30,%31}, {%32,%33,%34,%35}, db, p, %41, 1, %39;}"
   : "+f"(d[0]),"+f"(d[1]),"+f"(d[2]),"+f"(d[3]),"+f"(d[4]),"+f"(d[5]),"+f"(d[6]),"+f"(d[7]),"+f"(d[8]),"+f"(d[9]),"+f"(d[10]),"+f"(d[11]),"+f"(d[12]),"+f"(d[13]),"+f"(d[14]),"+f"(d[15]),"+f"(d[16]),"+f"(d[17]),"+f"(d[18]),"+f"(d[19]),"+f"(d[20]),"+f"(d[21]),"+f"(d[22]),"+f"(d[23]),"+f"(d[24]),"+f"(d[25]),"+f"(d[26]),"+f"(d[27]),"+f"(d[28]),"+f"(d[29]),"+f"(d[30]),"+f"(d[31])
   : "r"(a0),"r"(a1),"r"(a2),"r"(a3),"r"(bl),"r"(bo >> 4),"r"(scale_d),"n"(TB),"n"(BH),"n"(SA));
}
template<int TA,int TB,uint32_t AH,uint32_t BH> __device__ __forceinline__ void wgmma_n96_ss(float (&d)[48], uint32_t al, uint32_t ao, uint32_t bl, uint32_t bo, int scale_d){
  asm volatile("{.reg .pred p; .reg .b32 t, v; .reg .b64 da, db; setp.ne.b32 p, %52, 0; add.u32 t, %48, %49; mov.b64 da, {t, %55}; add.u32 v, %50, %51; mov.b64 db, {v, %56};\n"
   "wgmma.mma_async.sync.aligned.m64n96k16.f32.bf16.bf16 {%0,%1,%2,%3,%4,%5,%6,%7,%8,%9,%10,%11,%12,%13,%14,%15,%16,%17,%18,%19,%20,%21,%22,%23,%24,%25,%26,%27,%28,%29,%30,%31,%32,%33,%34,%35,%36,%37,%38,%39,%40,%41,%42,%43,%44,%45,%46,%47}, da, db, p, 1, 1, %53, %54;}"
   : "+f"(d[0]),"+f"(d[1]),"+f"(d[2]),"+f"(d[3]),"+f"(d[4]),"+f"(d[5]),"+f"(d[6]),"+f"(d[7]),"+f"(d[8]),"+f"(d[9]),"+f"(d[10]),"+f"(d[11]),"+f"(d[12]),"+f"(d[13]),"+f"(d[14]),"+f"(d[15]),"+f"(d[16]),"+f"(d[17]),"+f"(d[18]),"+f"(d[19]),"+f"(d[20]),"+f"(d[21]),"+f"(d[22]),"+f"(d[23]),"+f"(d[24]),"+f"(d[25]),"+f"(d[26]),"+f"(d[27]),"+f"(d[28]),"+f"(d[29]),"+f"(d[30]),"+f"(d[31]),"+f"(d[32]),"+f"(d[33]),"+f"(d[34]),"+f"(d[35]),"+f"(d[36]),"+f"(d[37]),"+f"(d[38]),"+f"(d[39]),"+f"(d[40]),"+f"(d[41]),"+f"(d[42]),"+f"(d[43]),"+f"(d[44]),"+f"(d[45]),"+f"(d[46]),"+f"(d[47])
   : "r"(al),"r"(ao >> 4),"r"(bl),"r"(bo >> 4),"r"(scale_d),"n"(TA),"n"(TB),"n"(AH),"n"(BH));
}
template<int TA,int TB,uint32_t AH,uint32_t BH> __device__ __forceinline__ void wgmma_n128_ss(float (&d)[64], uint32_t al, uint32_t ao, uint32_t bl, uint32_t bo, int scale_d){
  asm volatile("{.reg .pred p; .reg .b32 t, v; .reg .b64 da, db; setp.ne.b32 p, %68, 0; add.u32 t, %64, %65; mov.b64 da, {t, %71}; add.u32 v, %66, %67; mov.b64 db, {v, %72};\n"
   "wgmma.mma_async.sync.aligned.m64n128k16.f32.bf16.bf16 {%0,%1,%2,%3,%4,%5,%6,%7,%8,%9,%10,%11,%12,%13,%14,%15,%16,%17,%18,%19,%20,%21,%22,%23,%24,%25,%26,%27,%28,%29,%30,%31,%32,%33,%34,%35,%36,%37,%38,%39,%40,%41,%42,%43,%44,%45,%46,%47,%48,%49,%50,%51,%52,%53,%54,%55,%56,%57,%58,%59,%60,%61,%62,%63}, da, db, p, 1, 1, %69, %70;}"
   : "+f"(d[0]),"+f"(d[1]),"+f"(d[2]),"+f"(d[3]),"+f"(d[4]),"+f"(d[5]),"+f"(d[6]),"+f"(d[7]),"+f"(d[8]),"+f"(d[9]),"+f"(d[10]),"+f"(d[11]),"+f"(d[12]),"+f"(d[13]),"+f"(d[14]),"+f"(d[15]),"+f"(d[16]),"+f"(d[17]),"+f"(d[18]),"+f"(d[19]),"+f"(d[20]),"+f"(d[21]),"+f"(d[22]),"+f"(d[23]),"+f"(d[24]),"+f"(d[25]),"+f"(d[26]),"+f"(d[27]),"+f"(d[28]),"+f"(d[29]),"+f"(d[30]),"+f"(d[31]),"+f"(d[32]),"+f"(d[33]),"+f"(d[34]),"+f"(d[35]),"+f"(d[36]),"+f"(d[37]),"+f"(d[38]),"+f"(d[39]),"+f"(d[40]),"+f"(d[41]),"+f"(d[42]),"+f"(d[43]),"+f"(d[44]),"+f"(d[45]),"+f"(d[46]),"+f"(d[47]),"+f"(d[48]),"+f"(d[49]),"+f"(d[50]),"+f"(d[51]),"+f"(d[52]),"+f"(d[53]),"+f"(d[54]),"+f"(d[55]),"+f"(d[56]),"+f"(d[57]),"+f"(d[58]),"+f"(d[59]),"+f"(d[60]),"+f"(d[61]),"+f"(d[62]),"+f"(d[63])
   : "r"(al),"r"(ao >> 4),"r"(bl),"r"(bo >> 4),"r"(scale_d),"n"(TA),"n"(TB),"n"(AH),"n"(BH));
}

__global__ void __cluster_dims__(2, 1, 1) __launch_bounds__(384, 1)
fused_kernel(const __nv_bfloat16* __restrict__ lam_re, const __nv_bfloat16* __restrict__ lam_im, const __nv_bfloat16* __restrict__ log_dt,
             const __nv_bfloat16* __restrict__ dskip, const __nv_bfloat16* __restrict__ b1, const __nv_bfloat16* __restrict__ b2,
             const __nv_bfloat16* __restrict__ gate_w, float* __restrict__ out, const __grid_constant__ Maps maps) {
  extern __shared__ __align__(1024) unsigned char smem_raw[];
  const uint32_t sb = (uint32_t)__cvta_generic_to_shared(smem_raw);
  if (threadIdx.x == 352) { map_prefetch(&maps.x); map_prefetch(&maps.bre); map_prefetch(&maps.bim); }
  const int b = blockIdx.x;
  const int rank = b & 1, cl = b >> 1;
  const int sp = (cl & 1) | ((cl >> 2) & 2), m = ((cl >> 1) & 3) | ((cl >> 4) << 2);
  const int s = sp * 2 + rank;
  const int xrot = 9 - 2 * sp;
  if (threadIdx.x < 32 && elect_one()) {
    mbar_init(sb + OFF_XFULL, 1);
    mbar_expect_tx(sb + OFF_XFULL, 16384);
    tma5d(sb + OFF_X + (xrot & 7) * 16384, &maps.x, 0, 2 * m, sb + OFF_XFULL);
    tma5d(sb + OFF_X + (xrot & 7) * 16384 + 8192, &maps.x, 0, 2 * m + 1, sb + OFF_XFULL);
  }
  if ((threadIdx.x >> 5) == 4 && elect_one()) {
    mbar_init(sb + OFF_FULL, 1);
    mbar_expect_tx(sb + OFF_FULL, 16384);
    tma2d(sb + OFF_RING, &maps.bre, 0, s * 64, sb + OFF_FULL);
    tma2d(sb + OFF_RING + 8192, &maps.bim, 0, s * 64, sb + OFF_FULL);
  }
  const int warp = __shfl_sync(0xffffffffu, (int)(threadIdx.x >> 5), 0);
  const int lane0 = threadIdx.x & 31;

  if (elect_one()) {
    if (warp > 8) mbar_init(sb + OFF_GBAR + 8 * (warp - 9), warp < 11 ? 64 : 96);
    const uint32_t c = warp < 8 ? 1 : warp < 11 ? 8 : 4, bar = sb + OFF_XFULL + 16 * warp;
    if ((warp & 11) != 0) mbar_init(bar, c);
    mbar_init(bar + 8, c);
    asm volatile("fence.mbarrier_init.release.cluster;" ::: "memory");
  }
  __syncwarp();
  asm volatile("barrier.cluster.arrive.relaxed.aligned;" ::: "memory");

  if (warp < 8) {
    const int lane = __shfl_sync(0xffffffffu, lane0, lane0);
    const int wg = warp >> 2, w = warp & 3, q = lane & 3, gr = lane >> 2;
    uint32_t bv[28];
#pragma unroll
    for (int j = 0; j < 28; j++) bv[j] = __ldg(reinterpret_cast<const uint32_t*>(b1 + s * 224 + j * 8) + q);
    asm volatile("setmaxnreg.inc.sync.aligned.u32 224;");
    cluster_wait();
    auto release = [&](int slot) { if (lane == 0) mbar_arrive(sb + OFF_EMPTY + 8 * slot); };
    const uint32_t xw = sb + OFF_X + wg * 8192, fullb = sb + OFF_FULL;
    const uint32_t dxw = (xw & 0x3FFFF) >> 4, dring = ((sb + OFF_RING) & 0x3FFFF) >> 4;

    float ure[32], uim[32], aa[48], ab[64];
    cplx lam[2], coef[2], l16[2], l32[2], lq[2], pre[2], e[2];
    uint32_t sh16, mhi, ck = 0;

    auto bias = [&](int c) {
#pragma unroll
      for (int j = c * 7; j < c * 7 + 7; j++) {
        pin(bv[j]);
        float* d = j < 12 ? aa + 4 * j : ab + 4 * (j - 12);
        d[0] = d[2] = __uint_as_float(bv[j] << sh16); d[1] = d[3] = __uint_as_float(bv[j] & mhi);
        pin(d[0]); pin(d[1]); pin(d[2]); pin(d[3]);
      }
    };
#pragma unroll
    for (int kb = 0; kb < 8; kb++) {
      const int slot = kb % NSLOT;
      mbar_wait(sb + OFF_XFULL + 8 * kb, 0);
      if (kb == 0) mbar_wait(fullb, 0);
      if (kb == 2) { sh16 = late16(sb + OFF_XFULL); mhi = 0xffffffffu << sh16; }
      if (kb == 4) {
        mbar_wait(sb + OFF_LBAR, 0);
#pragma unroll
        for (int h = 0; h < 2; h++) {
          const uint4 v = lds_u4(sb + OFF_LC + (w * 16 + gr + 8 * h) * 16);
          lam[h] = cplx{__uint_as_float(v.x), __uint_as_float(v.y)};
          coef[h] = cplx{__uint_as_float(v.z), __uint_as_float(v.w)};
        }
      }
      wg_fence();
      const uint32_t dxa = dxw + ((kb + xrot) & 7) * 1024;
#pragma unroll
      for (int kk = 0; kk < 4; kk++) {
        wgmma_n64_ss<0, 0, DH128, DH128>(ure, dring, slot * 16384 + kk * 32, dxa, kk * 32, (kb | kk) != 0);
        wgmma_n64_ss<0, 0, DH128, DH128>(uim, dring, slot * 16384 + 8192 + kk * 32, dxa, kk * 32, (kb | kk) != 0);
      }
      wg_commit();
      if (kb > 0) { wg_wait<1>(); release((kb - 1) % NSLOT); }
      if (kb >= 2 && kb < 5) bias(kb - 2);
      if (kb == 6) {
#pragma unroll
        for (int h = 0; h < 2; h++) {
          pin(lam[h].re); pin(lam[h].im);
          cplx t = cmul(lam[h], lam[h]); t = cmul(t, t); t = cmul(t, t);
          l16[h] = cmul(t, t);
          pin(l16[h].re); pin(l16[h].im);
        }
      }
      if (kb == 7) {
#pragma unroll
        for (int h = 0; h < 2; h++) {
          pin(l16[h].re); pin(l16[h].im);
          l32[h] = cmul(l16[h], l16[h]);
          const cplx a = (q & 1) ? l16[h] : cplx{1.f, 0.f}, c = (q & 2) ? l32[h] : cplx{1.f, 0.f};
          lq[h] = cmul(cmul(a, c), coef[h]);
          pin(lq[h].re); pin(lq[h].im);
        }
      }
    }
    auto scale_u = [&](int i0) {
#pragma unroll
      for (int i = i0; i < i0 + 8; i++) {
        pin(ure[i]); pin(uim[i]);
        const cplx v = cmul(coef[(i >> 1) & 1], cplx{ure[i], uim[i]});
        ure[i] = v.re; uim[i] = v.im;
        pin(ure[i]); pin(uim[i]);
      }
    };
#pragma unroll
    for (int kb = 0; kb < 8; kb++) {
      const int u = 8 + kb, slot = u % NSLOT;
      mbar_wait(fullb + 8 * slot, full_par(u));
      wg_fence();
      const uint32_t dxa = dxw + ((kb + xrot) & 7) * 1024;
#pragma unroll
      for (int kk = 0; kk < 4; kk++)
        wgmma_n96_ss<0, 1, DH128, DH64>(aa, dxa, kk * 32, dring, slot * 16384 + kk * 1024 + lbo(4096), 1);
      wg_commit();
      if (kb == 0) bias(3);
      if (kb != 4) { wg_wait<1>(); release((u - 1) % NSLOT); }
      if (kb == 0) {
        reg_fence(ure); reg_fence(uim);
#pragma unroll
        for (int h = 0; h < 2; h++) e[h] = cplx{ure[2 * h], uim[2 * h]};
      }
      if (kb == 0 || kb == 2 || kb == 3) {
        const int t0 = kb ? 5 * kb - 4 : 1;
#pragma unroll
        for (int t = t0; t < t0 + 5; t++) {
#pragma unroll
          for (int h = 0; h < 2; h++) { const int i = 4 * (t >> 1) + 2 * h + (t & 1); e[h] = cfma(lam[h], e[h], cplx{ure[i], uim[i]}); }
        }
#pragma unroll
        for (int h = 0; h < 2; h++) { pin(e[h].re); pin(e[h].im); }
      }
      if (kb == 4) {
        scale_u(0);
        sched_fence(ck);
#pragma unroll
        for (int h = 0; h < 2; h++) {
          cplx y = {__shfl_up_sync(0xffffffffu, e[h].re, 1, 4), __shfl_up_sync(0xffffffffu, e[h].im, 1, 4)};
          if (q >= 1) e[h] = cfma(l16[h], y, e[h]);
          y = cplx{__shfl_up_sync(0xffffffffu, e[h].re, 2, 4), __shfl_up_sync(0xffffffffu, e[h].im, 2, 4)};
          if (q >= 2) e[h] = cfma(l32[h], y, e[h]);
        }
        if (q == 3) {
#pragma unroll
          for (int h = 0; h < 2; h++) sts_f2(sb + OFF_CARRY + wg * 512 + (w * 16 + gr + 8 * h) * 8, e[h].re, e[h].im);
          mbar_arrive(sb + OFF_GBAR);
        }
#pragma unroll
        for (int h = 0; h < 2; h++) e[h] = cplx{__shfl_up_sync(0xffffffffu, e[h].re, 1, 4), __shfl_up_sync(0xffffffffu, e[h].im, 1, 4)};
        wg_wait<1>(); release((u - 1) % NSLOT);
      }
      if (kb == 5) {
#pragma unroll
        for (int h = 0; h < 2; h++) {
          pre[h] = (q >= 1) ? cmul(coef[h], e[h]) : cplx{0.f, 0.f};
          pin(pre[h].re); pin(pre[h].im);
        }
      }
      if (kb > 5) scale_u((kb - 5) * 8);
    }
    uint32_t H[56], hf[32];
    cplx hst[2];
    const uint32_t hst_addr = xw + (w * 16 + (lane & 15)) * 128 + (((lane >> 4) ^ (lane & 7)) << 4);
    const uint32_t him = (2 - rank) * 16384;
    uint32_t peer;
    asm volatile("mapa.shared::cluster.u32 %0, %1, %2;" : "=r"(peer) : "r"(sb), "r"(rank ^ 1));
    auto credit = [&]() { if (lane == 0) mbar_arrive_cl(peer + OFF_KBAR + wg * 8); };
    uint32_t g2[8];
#pragma unroll
    for (int kb = 0; kb < 8; kb++) {
      const int u = 16 + kb, slot = u % NSLOT;
      mbar_wait(fullb + 8 * slot, full_par(u));
      wg_fence();
#pragma unroll
      for (int kk = 0; kk < 4; kk++)
        wgmma_n128_ss<0, 1, DH128, DH128>(ab, dxw, kb * 16384 + kk * 32, dring, slot * 16384 + kk * 2048 + lbo(8192), 1);
      wg_commit();
      if (kb == 0) scale_u(24);
      if (kb == 4) {
        mbar_wait(sb + OFF_CBAR, 0);
#pragma unroll
        for (int h = 0; h < 2; h++) {
          const float2 c = lds_f2(sb + OFF_CARRY + wg * 512 + (w * 16 + gr + 8 * h) * 8);
          hst[h] = cfma(lq[h], cplx{c.x, c.y}, pre[h]);
        }
#pragma unroll
        for (int i = 0; i < 2; i++) {
          const uint4 v = lds_u4(sb + OFF_GT + wg * 128 + q * 32 + i * 16);
          g2[4 * i] = v.x; g2[4 * i + 1] = v.y; g2[4 * i + 2] = v.z; g2[4 * i + 3] = v.w;
        }
      }
      wg_wait<1>(); release((u - 1) % NSLOT);
      if (kb) sched_fence(ck);
      if (kb < 4) {
#pragma unroll
        for (int i = kb * 6; i < kb * 6 + 6; i++) {
          pin(aa[2 * i]); pin(aa[2 * i + 1]);
          H[i] = gelu2_pair(aa[2 * i], aa[2 * i + 1]);
          pin(H[i]);
        }
      } else {
        const int j0 = (kb - 4) * 2;
        uint32_t rr[4], ri[4];
#pragma unroll
        for (int jj = 0; jj < 2; jj++) {
          const int j = j0 + jj;
#pragma unroll
          for (int h = 0; h < 2; h++) {
            const int i = 4 * j + 2 * h;
            const cplx h0 = cfma(lam[h], hst[h], cplx{ure[i], uim[i]});
            hst[h] = cfma(lam[h], h0, cplx{ure[i + 1], uim[i + 1]});
            rr[jj * 2 + h] = bf2_mul(pack_bf16(h0.re, hst[h].re), g2[j]);
            ri[jj * 2 + h] = bf2_mul(pack_bf16(h0.im, hst[h].im), g2[j]);
          }
        }
        const uint32_t a = hst_addr ^ (j0 << 4);
        asm volatile("stmatrix.sync.aligned.m8n8.x4.shared.b16 [%0], {%1,%2,%3,%4};" ::"r"(a), "r"(rr[0]), "r"(rr[1]), "r"(rr[2]), "r"(rr[3]) : "memory");
        asm volatile("stmatrix.sync.aligned.m8n8.x4.shared.b16 [%0], {%1,%2,%3,%4};" ::"r"(a + him), "r"(ri[0]), "r"(ri[1]), "r"(ri[2]), "r"(ri[3]) : "memory");
      }
    }

    uint4* const psend = g_part + (size_t)(m * 8 + rank) * 3072 + warp * 128 + lane;
    const uint4* const precv = g_part + (size_t)(m * 8 + s) * 3072 + warp * 128 + lane;
    const uint32_t pbuf = OFF_X + warp * 2048 + lane * 16;
    const uint32_t dx0 = ((sb + OFF_X) & 0x3FFFF) >> 4;
    float o[32], fin[32], fs[2];
    uint32_t r0[16], pt[16], sum[16], tag;
    auto recv_issue = [&](uint32_t (&r)[16], int k) {
#pragma unroll
      for (int i = 0; i < 4; i++) ld_b128(precv + k * 1024 + i * 32, r[4 * i], r[4 * i + 1], r[4 * i + 2], r[4 * i + 3]);
    };
    auto stale = [&](uint32_t (&r)[16]) {
      uint32_t r_;
#pragma unroll
      for (int i = 0; i < 16; i += 4) asm("lop3.b32 %0, %0, %1, 1, 0x78;" : "+r"(r[i]) : "r"(tag));
      asm volatile("{.reg .pred p; .reg .b32 t; lop3.b32 t, %1, %2, %3, 0xfe; lop3.b32 t, t, %4, 1, 0xa8; setp.ne.u32 p, t, 0; vote.sync.any.pred p, p, 0xffffffff; selp.u32 %0, 1, 0, p;}"
                   : "=r"(r_) : "r"(r[0]), "r"(r[4]), "r"(r[8]), "r"(r[12]));
      return r_ != 0;
    };
    auto recv_check = [&](uint32_t (&r)[16], int k) {
      if (__builtin_expect(stale(r), 0)) {
        int tries = 0;
#pragma unroll 1
        do { recv_issue(r, k); } while (stale(r) && ++tries < 200000);
      }
    };
    auto gelu_b = [&](int i0, int i1) {
#pragma unroll
      for (int i = i0; i < i1; i++) {
        pin(ab[2 * i]); pin(ab[2 * i + 1]);
        H[24 + i] = gelu2_pair(ab[2 * i], ab[2 * i + 1]);
        pin(H[24 + i]);
      }
    };
    auto mma = [&](float (&d)[32], int p, int k0, int k1, int acc) {
      const uint32_t wo = stage_off(p);
      wg_fence();
#pragma unroll
      for (int k = k0; k < k1; k++) {
        if (k >= 6 && k < 14) {
          const int kk = k - 6;
          if (kk < 4) wgmma_n64_rs<0, DH128, 1>(d, hf[4 * kk], hf[4 * kk + 1], hf[4 * kk + 2], hf[4 * kk + 3], dx0, wo + 14336 + kk * 32, 1);
          else wgmma_n64_rs<0, DH128, -1>(d, hf[4 * kk], hf[4 * kk + 1], hf[4 * kk + 2], hf[4 * kk + 3], dx0, wo + 22528 + (kk - 4) * 32, 1);
        } else {
          const int kk = k < 6 ? k : k - 8;
          wgmma_n64_rs<1, DH128>(d, H[4 * kk], H[4 * kk + 1], H[4 * kk + 2], H[4 * kk + 3], dx0, wo + (kk / 7) * 30720 + (kk % 7) * 2048, k != 0 || acc);
        }
      }
      wg_commit();
    };
    auto recv_peer = [&](int k) {
      mbar_wait(sb + OFF_RBAR + wg * 8, k & 1);
#pragma unroll
      for (int i = 0; i < 4; i++) { const uint4 v = lds_u4(sb + pbuf + i * 512); pt[4 * i] = v.x; pt[4 * i + 1] = v.y; pt[4 * i + 2] = v.z; pt[4 * i + 3] = v.w; }
    };
#pragma unroll
    for (int p = 0; p < 8; p++) {
      if (p == 0) {
        mbar_wait(fullb, full_par(24));
        mma(o, 0, 0, 4, 0);
        bar_sync(1 + wg, 128);
        {
          const uint32_t ha = xw + ((lane >> 4) * 8 + (lane & 7)) * 128 + (((2 * w + ((lane >> 3) & 1)) ^ (lane & 7)) << 4);
#pragma unroll
          for (int kk = 0; kk < 8; kk++)
            asm volatile("ldmatrix.sync.aligned.m8n8.x4.trans.shared.b16 {%0,%1,%2,%3}, [%4];" : "=r"(hf[4 * kk]), "=r"(hf[4 * kk + 1]), "=r"(hf[4 * kk + 2]), "=r"(hf[4 * kk + 3])
                         : "r"(ha + (kk >> 2) * him + (kk & 3) * 2048) : "memory");
        }
        mbar_wait(fullb + 8, full_par(25));
        wg_wait<1>(); release(5);
        gelu_b(0, 6);
        mma(o, 0, 4, 8, 0);
        gelu_b(6, 12);
        mma(o, 0, 8, 12, 0);
        credit();
        gelu_b(12, 18);
        mbar_wait(fullb + 16, full_par(26));
        mma(o, 0, 12, 15, 0);
        gelu_b(18, 24);
        mma(o, 0, 15, 18, 0);
        gelu_b(24, 32);
        if (wg == 1) bar_sync(4, 256);
        mma(o, 0, 18, 22, 0);
      } else {
        bar_sync(3 + wg, 256);
        if (p < 7) mma(o, p, 0, 22, 0); else mma(fin, p, 0, 22, 1);
      }
      if (p < 7 || wg == 0) bar_arrive(4 - wg, 256);
      if (p < 7) mbar_wait(sb + OFF_XFULL + 8 * (p + 1), 1);
      if (p == 2) sts_u(sb + OFF_EPOCH + 4, ck);
      if ((p & 1) == 0) {
        if (w == 0 && lane == 0) mbar_expect_tx(sb + OFF_RBAR + wg * 8, 8192);
        if (p == 6) {
          mbar_wait(sb + OFF_EMPTY + 32, 0);
          tag = lds_u(sb + OFF_EPOCH);
          recv_check(sum, 0); recv_check(r0, 1);
#pragma unroll
          for (int i = 0; i < 16; i++) sum[i] = bf2_add(sum[i], r0[i]);
        }
        mbar_wait(sb + OFF_KBAR + wg * 8, (p >> 1) & 1);
      } else {
        if (p == 1 || p == 7) tag = lds_u(sb + OFF_EPOCH);
        recv_peer(p >> 1);
        if (p == 7) {
          recv_check(r0, 2);
#pragma unroll
          for (int i = 0; i < 16; i++) sum[i] = bf2_add(sum[i], bf2_add(r0[i], pt[i]));
        }
      }
      if (p == 4) {
        mbar_wait(sb + OFF_LBAR, 1);
#pragma unroll
        for (int j = 0; j < 8; j++) {
          const uint4 v = lds_u4(sb + pbuf + 16384 + (j >> 2) * 16384 + (j & 3) * 512);
          fin[4 * j] = __uint_as_float(v.x); fin[4 * j + 1] = __uint_as_float(v.y); fin[4 * j + 2] = __uint_as_float(v.z); fin[4 * j + 3] = __uint_as_float(v.w);
        }
        recv_issue(sum, 0);
      }
      wg_wait<0>();
      if (p < 5) release(p);
      if (p < 7) reg_fence(o); else reg_fence(fin);
      if ((p & 1) == 0) {
        if (p == 6) recv_issue(r0, 2);
#pragma unroll
        for (int i = 0; i < 4; i++)
          asm volatile("st.async.shared::cluster.mbarrier::complete_tx::bytes.v4.b32 [%0], {%1,%2,%3,%4}, [%5];" ::"r"(peer + pbuf + i * 512),
                       "r"(pack_bf16(o[8 * i], o[8 * i + 1])), "r"(pack_bf16(o[8 * i + 2], o[8 * i + 3])), "r"(pack_bf16(o[8 * i + 4], o[8 * i + 5])),
                       "r"(pack_bf16(o[8 * i + 6], o[8 * i + 7])), "r"(peer + OFF_RBAR + wg * 8) : "memory");
      } else if (p < 7) {
        const int k = p >> 1;
#pragma unroll
        for (int i = 0; i < 4; i++) {
#pragma unroll
          for (int c = 4 * i; c < 4 * i + 4; c++) pt[c] = bf2_add(pt[c], pack_bf16(o[2 * c], o[2 * c + 1]));
          asm("lop3.b32 %0, %0, 1, %1, 0xb8;" : "+r"(pt[4 * i]) : "r"(tag));
          st_b128(psend + (((sp + 1 + k) & 3) * 6 + k) * 1024 + i * 32, pt[4 * i], pt[4 * i + 1], pt[4 * i + 2], pt[4 * i + 3]);
        }
        __syncwarp();
        credit();
        if (p == 5) recv_issue(r0, 1);
      }
      if (p == 2) {
#pragma unroll
        for (int h = 0; h < 2; h++) { fs[h] = __fdividef(2.f, 4.f + bf_lo(lds_h(sb + OFF_GS + (wg * 64 + w * 16 + gr + 8 * h) * 2))); pin(fs[h]); }
      }
    }
    {
      const uint32_t tb = sb + OFF_X + stage_off(0) + warp * 4096;
      const uint32_t ta = tb + gr * 256 + ((gr & 3) << 5) + q * 8;
      const uint32_t la = tb + (lane >> 3) * 256 + (((lane & 7) << 4) ^ ((lane >> 3) << 5));
      float* op = out + (size_t)(m * 128 + wg * 64 + (lane >> 4) * 16 + w * 4 + ((lane >> 3) & 1)) * DM + s * 64 + (lane & 7) * 4;
#pragma unroll
      for (int qt = 0; qt < 4; qt++) {
        const int h = qt & 1, ch = qt >> 1;
#pragma unroll
        for (int j = 0; j < 4; j++) {
          const int i = ch * 8 + j * 2 + h;
          sts_f2((ta ^ (j << 5)) + h * 2048 + ch * 128, (fin[2 * i] + bf_lo(sum[i])) * fs[h], (fin[2 * i + 1] + bf_hi(sum[i])) * fs[h]);
        }
        __syncwarp();
#pragma unroll
        for (int r = 0; r < 2; r++)
          *reinterpret_cast<uint4*>(op + (r * 32 + h * 2) * DM + ch * 32) = lds_u4(la + (h * 2 + r) * 1024 + ch * 128);
      }
      if (warp == 4 && lane == 0) g_epoch[b] = tag;
    }
  } else {
    const int lane = __shfl_sync(0xffffffffu, lane0, lane0);
    asm volatile("setmaxnreg.dec.sync.aligned.u32 56;");
    int wsel = warp;
    asm("" : "+r"(wsel));
    if (wsel > 8) {
      const uint4* gwp = reinterpret_cast<const uint4*>(gate_w) + (lane & 7);
      uint4 gw[4];
      if (warp != 11) {
        const int t = (warp - 9) * 32 + lane;
        unsigned par;
        asm volatile("ld.relaxed.gpu.global.u32 %0, [%1];" : "=r"(par) : "l"(g_epoch + b) : "memory");
        const float pr = bf_ld(lam_re + s * 64 + t), pi = bf_ld(lam_im + s * 64 + t), pd = bf_ld(log_dt + s * 64 + t);
#pragma unroll
        for (int i = 0; i < 4; i++) gw[i] = __ldg(gwp + i * 8);
        cluster_wait();
        par = __shfl_sync(0xffffffffu, (par + 1) & 1, 0);
        cplx l64 = make_lam(pr, pi, pd);
        {
          const float inv = __fdividef(1.f, fmaf(pr, pr, pi * pi));
          const cplx cf = cmul(cplx{l64.re - 1.f, l64.im}, cplx{pr * inv, -pi * inv});
          sts_f4(sb + OFF_LC + t * 16, l64.re, l64.im, cf.re, cf.im);
          mbar_arrive(sb + OFF_LBAR);
        }
#pragma unroll
        for (int i = 0; i < 6; i++) l64 = cmul(l64, l64);
        cplx l128 = cmul(l64, l64);
        pin(l128.re); pin(l128.im);
        gate_rows<1>(sb, lane, xrot, s * 16 + (warp - 9) * 4, gw, gwp, g_gate + m * 128, par);
        uint32_t vr[15], vi[15];
#pragma unroll
        for (int i = 0; i < 15; i++) { vr[i] = par; vi[i] = 0; pin(vr[i]); pin(vi[i]); }
        mbar_wait(sb + OFF_GBAR, 0);
        const float2 e0 = lds_f2(sb + OFF_CARRY + t * 8), e1 = lds_f2(sb + OFF_CARRY + 512 + t * 8);
        float2* eb = g_end + s * 1024 + t;
        {
          const cplx e = cfma(l64, cplx{e0.x, e0.y}, cplx{e1.x, e1.y});
          const unsigned long long v = ((unsigned long long)__float_as_uint(e.im) << 32) | ((__float_as_uint(e.re) & ~1u) | par);
          asm volatile("st.relaxed.gpu.global.b64 [%0], %1;" ::"l"(eb + m * 64), "l"(v) : "memory");
        }
        __nanosleep(400);
        const float2* e15 = eb + (m - 15) * 64;
        int tries = 0;
        bool bad;
#pragma unroll 1
        do {
#pragma unroll
          for (int i = 0; i < 15; i++)
            asm volatile("{.reg .pred p; .reg .b64 v; mov.b64 v, {%0,%1}; setp.ge.s32 p, %3, %4; @p ld.relaxed.gpu.global.b64 v, [%2]; mov.b64 {%0,%1}, v;}"
                         : "+r"(vr[i]), "+r"(vi[i]) : "l"(e15 + i * 64), "r"(m), "r"(15 - i) : "memory");
          uint32_t x = vr[0] ^ par;
#pragma unroll
          for (int i = 1; i < 15; i++) asm("lop3.b32 %0, %0, %1, %2, 0xf6;" : "+r"(x) : "r"(vr[i]), "r"(par));
          bad = __any_sync(0xffffffffu, x & 1);
        } while (bad && ++tries < 200000);
        cplx S = {__uint_as_float(vr[0] ^ par), __uint_as_float(vi[0])};
#pragma unroll
        for (int i = 1; i < 15; i++) S = cfma(l128, S, cplx{__uint_as_float(vr[i] ^ par), __uint_as_float(vi[i])});
        const cplx S1 = cfma(l64, S, cplx{e0.x, e0.y});
        sts_f2(sb + OFF_CARRY + t * 8, S.re, S.im);
        sts_f2(sb + OFF_CARRY + 512 + t * 8, S1.re, S1.im);
        mbar_arrive(sb + OFF_CBAR);
        mbar_wait(sb + OFF_CBAR, 0);
        const int gr = lane >> 2, q = lane & 3;
        float2 db[8];
#pragma unroll
        for (int j = 0; j < 8; j++) db[j] = lds_f2(sb + OFF_DB + j * 32 + q * 8);
        mbar_wait(sb + OFF_XFULL + 16, 1);
        mbar_wait(sb + OFF_EMPTY, 0);
#pragma unroll 1
        for (int cw = warp - 9; cw < 8; cw += 2) {
          const float r0 = 0.5f * bf_lo(lds_h(sb + OFF_GS + (cw * 16 + gr) * 2)), r1 = 0.5f * bf_lo(lds_h(sb + OFF_GS + (cw * 16 + gr) * 2 + 16));
          const uint32_t xa = sb + OFF_X + (1 + rank) * 16384 + (cw * 16 + (lane & 15)) * 128 + (((lane >> 4) ^ (lane & 7)) << 4);
          uint32_t xv[16];
#pragma unroll
          for (int i = 0; i < 4; i++)
            asm volatile("ldmatrix.sync.aligned.m8n8.x4.shared.b16 {%0,%1,%2,%3}, [%4];" : "=r"(xv[4 * i]), "=r"(xv[4 * i + 1]), "=r"(xv[4 * i + 2]), "=r"(xv[4 * i + 3])
                         : "r"(xa ^ (i << 5)) : "memory");
          __syncwarp();
#pragma unroll
          for (int j = 0; j < 8; j++) {
            const uint32_t x0 = bf2_mul(xv[2 * j], __float_as_uint(db[j].x)), x1 = bf2_mul(xv[2 * j + 1], __float_as_uint(db[j].x));
            pin(db[j].y);
            const float bl = bf_lo(__float_as_uint(db[j].y)), bh = bf_hi(__float_as_uint(db[j].y));
            sts_f4(sb + OFF_X + 16384 + (j >> 2) * 16384 + cw * 2048 + (j & 3) * 512 + lane * 16, fmaf(bf_lo(x0), r0, bl), fmaf(bf_hi(x0), r0, bh),
                   fmaf(bf_lo(x1), r1, bl), fmaf(bf_hi(x1), r1, bh));
          }
        }
        mbar_arrive(sb + OFF_LBAR);
      } else {
#pragma unroll
        for (int i = 0; i < 4; i++) gw[i] = __ldg(gwp + i * 8);
        unsigned par;
        asm volatile("ld.relaxed.gpu.global.u32 %0, [%1];" : "=r"(par) : "l"(g_epoch + b) : "memory");
        const uint32_t dk = __ldg(reinterpret_cast<const uint32_t*>(dskip + s * 64) + lane), bb = __ldg(reinterpret_cast<const uint32_t*>(b2 + s * 64) + lane);
        cluster_wait();
        if (lane == 0) sts_u(sb + OFF_EPOCH, par + 1);
        par = (par + 1) & 1;
        gate_rows<2>(sb, lane, xrot, s * 16 + 8, gw, gwp, g_gate + m * 128, par);
        mbar_wait(sb + OFF_GBAR, 0);
        sts_u2(sb + OFF_DB + lane * 8, dk, bf2_add(bb, bb));
        uint32_t g0, g1, g2, g3;
        int tries = 0;
#pragma unroll 1
        do {
          asm volatile("ld.relaxed.gpu.global.v4.u32 {%0,%1,%2,%3}, [%4];" : "=r"(g0), "=r"(g1), "=r"(g2), "=r"(g3) : "l"(g_gate + m * 128 + lane * 4) : "memory");
          g0 ^= par; g1 ^= par; g2 ^= par; g3 ^= par;
        } while (((g0 | g1 | g2 | g3) & 1) && ++tries < 200000);
        const uint32_t p01 = pack_bf16(__uint_as_float(g0), __uint_as_float(g1)), p23 = pack_bf16(__uint_as_float(g2), __uint_as_float(g3));
        sts_u2(sb + OFF_GS + lane * 8, p01, p23);
        const uint32_t gt = sb + OFF_GT + (lane >> 4) * 128 + (lane & 1) * 64 + ((lane >> 1) & 7) * 4;
        sts_u(gt, p01);
        sts_u(gt + 32, p23);
        mbar_arrive(sb + OFF_CBAR);
      }
    } else {
      cluster_wait();
      if (elect_one()) {
        const uint32_t t0 = clock();
#pragma unroll 1
        for (int u = 1; u < 8; u++) {
          while ((uint32_t)clock() - t0 < 200 + (u - 1) * 480) {}
          const uint32_t fb = sb + OFF_XFULL + 8 * u;
          mbar_expect_tx(fb, 32768);
          tma5d_mc(sb + OFF_X + ((u + xrot) & 7) * 16384 + rank * 8192, &maps.x, u * 64, 2 * m + rank, fb);
          const int sl = u < 6 ? u : u - 6;
          if (u >= 6) mbar_wait(sb + OFF_EMPTY + 8 * sl, 0);
          tma2d(sb + OFF_RING + sl * 16384, &maps.bre, u * 64, s * 64, fb);
          tma2d(sb + OFF_RING + sl * 16384 + 8192, &maps.bim, u * 64, s * 64, fb);
          if (u == 2) map_prefetch(&maps.w1b);
        }
        int slot = 2; uint32_t ph = 0;
#pragma unroll 1
        for (int u = 8; u < 24; u++) {
          const uint32_t fb = sb + OFF_FULL + 8 * slot, dst = sb + OFF_RING + slot * 16384;
          mbar_wait(sb + OFF_EMPTY + 8 * slot, ph);
          if (u < 16) {
            mbar_expect_tx(fb, 12288);
            tma3d(dst, &maps.w1b, 0, (u - 8) * 64, s * 7, fb);
            if (u < 12) map_prefetch(&maps.w1a + (u - 8));
          } else {
            mbar_expect_tx(fb, 16384);
            tma2d(dst, &maps.w1a, s * 224 + 96, ((u - xrot) & 7) * 64, fb);
            tma2d(dst + 8192, &maps.w1a, s * 224 + 160, ((u - xrot) & 7) * 64, fb);
          }
          if (++slot == NSLOT) { slot = 0; ph ^= 1; }
        }
#pragma unroll 1
        for (int j = 0; j < 3; j++) {
          const uint32_t fb = sb + OFF_FULL + 8 * j, dst = sb + OFF_X + stage_off(0);
          const int c = ((sp + 1) & 3) * 128 + ((rank ^ 1) << 6);
          mbar_wait(sb + OFF_EMPTY + 8 + 8 * j, 1);
          mbar_expect_tx(fb, j == 1 ? 16384 : 14336);
          if (j == 1) {
            tma2d(dst + 14336, &maps.cre, s * 64, c, fb);
            tma2d(dst + 22528, &maps.cim, s * 64, c, fb);
          } else {
            tma2d(dst + j * 15360, &maps.w2, c, s * 224 + j * 56, fb);
          }
        }
#pragma unroll 1
        for (int p = 1; p < 8; p++) {
          const int c = ((sp + 1 + (p >> 1)) & 3) * 128 + (((rank ^ p ^ 1) & 1) << 6);
          const uint32_t fb = sb + OFF_XFULL + 8 * p, dst = sb + OFF_X + stage_off(p);
          if (p == 2 || p > 3) mbar_wait(sb + OFF_EMPTY + (p == 2 ? 40 : (p - 4) * 8), p == 2);
          mbar_expect_tx(fb, 45056);
          tma2d(dst, &maps.w2, c, s * 224, fb);
          tma2d(dst + 14336, &maps.cre, s * 64, c, fb);
          tma2d(dst + 22528, &maps.cim, s * 64, c, fb);
          tma2d(dst + 30720, &maps.w2, c, s * 224 + 112, fb);
        }
      }
    }
  }
}

typedef CUresult (*EncFn)(CUtensorMap*, CUtensorMapDataType, cuuint32_t, void*, const cuuint64_t*, const cuuint64_t*, const cuuint32_t*,
                          const cuuint32_t*, CUtensorMapInterleave, CUtensorMapSwizzle, CUtensorMapL2promotion, CUtensorMapFloatOOBfill);

void encode(EncFn f, CUtensorMap* mp, const void* p, int rank, const cuuint64_t* dims, const cuuint64_t* strides, const cuuint32_t* box, CUtensorMapSwizzle sw) {
  cuuint32_t es[5] = {1, 1, 1, 1, 1};
  f(mp, CU_TENSOR_MAP_DATA_TYPE_BFLOAT16, rank, const_cast<void*>(p), dims, strides, box, es, CU_TENSOR_MAP_INTERLEAVE_NONE, sw,
    CU_TENSOR_MAP_L2_PROMOTION_L2_128B, CU_TENSOR_MAP_FLOAT_OOB_FILL_NONE);
}

}

extern "C" void kernel_launch(void* const* d_in, const int* in_sizes, int n_in, void* d_out, int out_size) {
  typedef const __nv_bfloat16* bp;
  bp x = (bp)d_in[0], lre = (bp)d_in[1], lim = (bp)d_in[2], bre = (bp)d_in[3], bim = (bp)d_in[4], cre = (bp)d_in[5], cim = (bp)d_in[6],
     ldt = (bp)d_in[7], dsk = (bp)d_in[8], w1 = (bp)d_in[10], b1 = (bp)d_in[11], w2 = (bp)d_in[12], b2 = (bp)d_in[13], gw = (bp)d_in[14];
  static EncFn enc = nullptr;
  if (!enc) {
    void* f = nullptr;
    cudaDriverEntryPointQueryResult qr;
    cudaGetDriverEntryPoint("cuTensorMapEncodeTiled", &f, cudaEnableDefault, &qr);
    enc = (EncFn)f;
    cudaFuncSetAttribute(fused_kernel, cudaFuncAttributeMaxDynamicSharedMemorySize, SMEM_BYTES);
  }
  Maps maps;
  {
    cuuint64_t d[5] = {DM, 2, 4, 8, SEQ / 64}, st[4] = {DM * 2, 16 * DM * 2, 2 * DM * 2, 64 * DM * 2};
    cuuint32_t bx[5] = {64, 2, 4, 8, 1};
    encode(enc, &maps.x, x, 5, d, st, bx, CU_TENSOR_MAP_SWIZZLE_128B);
  }
  {
    cuuint64_t d[2] = {DM, DM}, st[1] = {DM * 2};
    cuuint32_t bx[2] = {64, 64};
    encode(enc, &maps.bre, bre, 2, d, st, bx, CU_TENSOR_MAP_SWIZZLE_128B);
    encode(enc, &maps.bim, bim, 2, d, st, bx, CU_TENSOR_MAP_SWIZZLE_128B);
    encode(enc, &maps.cre, cre, 2, d, st, bx, CU_TENSOR_MAP_SWIZZLE_128B);
    encode(enc, &maps.cim, cim, 2, d, st, bx, CU_TENSOR_MAP_SWIZZLE_128B);
  }
  {
    cuuint64_t d[2] = {FF, DM}, st[1] = {FF * 2};
    cuuint32_t bx[2] = {64, 64};
    encode(enc, &maps.w1a, w1, 2, d, st, bx, CU_TENSOR_MAP_SWIZZLE_128B);
    cuuint64_t d3[3] = {32, DM, FF / 32}, st3[2] = {FF * 2, 64};
    cuuint32_t bx3[3] = {32, 64, 3};
    encode(enc, &maps.w1b, w1, 3, d3, st3, bx3, CU_TENSOR_MAP_SWIZZLE_64B);
  }
  {
    cuuint64_t d[2] = {DM, FF}, st[1] = {DM * 2};
    cuuint32_t bx[2] = {64, 112};
    encode(enc, &maps.w2, w2, 2, d, st, bx, CU_TENSOR_MAP_SWIZZLE_128B);
  }
  fused_kernel<<<128, 384, SMEM_BYTES>>>(lre, lim, ldt, dsk, b1, b2, gw, (float*)d_out, maps);
}
```

```cpp
#include <cuda_runtime.h>
#include <cuda_bf16.h>
#include <cuda.h>
#include <stdint.h>

namespace {

constexpr int SEQ = 2048, DM = 512, FF = 1792;
constexpr int NSLOT = 6;
constexpr uint32_t OFF_X = 0, OFF_RING = 131072, OFF_MISC = 229376;
constexpr uint32_t OFF_XFULL = OFF_MISC, OFF_FULL = OFF_XFULL + 64, OFF_RBAR = OFF_FULL + 48, OFF_EMPTY = OFF_RBAR + 16, OFF_KBAR = OFF_EMPTY + 48,
                   OFF_GBAR = OFF_KBAR + 16, OFF_LBAR = OFF_GBAR + 8, OFF_CBAR = OFF_LBAR + 8, OFF_EPOCH = OFF_CBAR + 8;
constexpr uint32_t OFF_LC = OFF_MISC + 256;
constexpr uint32_t OFF_GS = OFF_LC;
constexpr uint32_t OFF_GT = OFF_LC + 256;
constexpr uint32_t OFF_DB = OFF_LC + 512;
constexpr uint32_t OFF_CARRY = OFF_LC + 1024;
constexpr uint32_t SMEM_BYTES = OFF_CARRY + 1024;
static_assert(SMEM_BYTES <= 232448, "smem");

struct Maps { CUtensorMap x, bre, bim, w1b, w1a, w2, cre, cim; };
__host__ __device__ constexpr uint32_t stage_off(int p) { return 49152 + 45056 * (((p >> 1) & 1) + 2 * (p & 1)); }
__host__ __device__ constexpr uint32_t full_par(int u) { return ((u - 8) / 6 + (u % 6 == 0)) & 1; }

__device__ uint4 g_part[16 * 8 * 3 * 1024];
__device__ float2 g_end[8 * 16 * 64];
__device__ unsigned g_gate[SEQ];
__device__ unsigned g_epoch[128];

__device__ __forceinline__ void mbar_init(uint32_t bar, uint32_t cnt) { asm volatile("mbarrier.init.shared::cta.b64 [%0], %1;" ::"r"(bar), "r"(cnt)); }
__device__ __forceinline__ void mbar_expect_tx(uint32_t bar, uint32_t bytes) { asm volatile("mbarrier.arrive.expect_tx.shared::cta.b64 _, [%0], %1;" ::"r"(bar), "r"(bytes) : "memory"); }
__device__ __forceinline__ void mbar_arrive(uint32_t bar) { asm volatile("mbarrier.arrive.shared::cta.b64 _, [%0];" ::"r"(bar) : "memory"); }
__device__ __forceinline__ void mbar_arrive_cl(uint32_t cbar) { asm volatile("mbarrier.arrive.shared::cluster.b64 _, [%0];" ::"r"(cbar) : "memory"); }
__device__ __forceinline__ void mbar_wait(uint32_t bar, uint32_t parity) {
  asm volatile(
      "{\n.reg .pred p;\n.reg .u32 c;\n"
      "mbarrier.try_wait.parity.shared::cta.b64 p, [%0], %1;\n"
      "@p bra.uni LAB_DONE;\n"
      "mov.u32 c, 0;\n"
      "LAB_WAIT:\n"
      "mbarrier.try_wait.parity.shared::cta.b64 p, [%0], %1;\n"
      "@p bra.uni LAB_DONE;\n"
      "add.u32 c, c, 1;\nsetp.lt.u32 p, c, 200000;\n@p bra.uni LAB_WAIT;\n"
      "LAB_DONE:\n}" ::"r"(bar), "r"(parity) : "memory");
}
__device__ __forceinline__ void tma2d(uint32_t dst, const CUtensorMap* m, int c0, int c1, uint32_t bar) {
  asm volatile("cp.async.bulk.tensor.2d.shared::cluster.global.mbarrier::complete_tx::bytes [%0], [%1, {%3,%4}], [%2];"
               ::"r"(dst), "l"(m), "r"(bar), "r"(c0), "r"(c1) : "memory");
}
__device__ __forceinline__ void tma3d(uint32_t dst, const CUtensorMap* m, int c0, int c1, int c2, uint32_t bar) {
  asm volatile("cp.async.bulk.tensor.3d.shared::cluster.global.mbarrier::complete_tx::bytes [%0], [%1, {%3,%4,%5}], [%2];"
               ::"r"(dst), "l"(m), "r"(bar), "r"(c0), "r"(c1), "r"(c2) : "memory");
}
__device__ __forceinline__ void tma5d(uint32_t dst, const CUtensorMap* m, int c0, int c4, uint32_t bar) {
  asm volatile("cp.async.bulk.tensor.5d.shared::cluster.global.mbarrier::complete_tx::bytes [%0], [%1, {%3,%5,%5,%5,%4}], [%2];"
               ::"r"(dst), "l"(m), "r"(bar), "r"(c0), "r"(c4), "r"(0) : "memory");
}
__device__ __forceinline__ void tma5d_mc(uint32_t dst, const CUtensorMap* m, int c0, int c4, uint32_t bar) {
  asm volatile("cp.async.bulk.tensor.5d.shared::cluster.global.mbarrier::complete_tx::bytes.multicast::cluster [%0], [%1, {%3,%5,%5,%5,%4}], [%2], %6;"
               ::"r"(dst), "l"(m), "r"(bar), "r"(c0), "r"(c4), "r"(0), "h"((uint16_t)3) : "memory");
}
__device__ __forceinline__ void map_prefetch(const CUtensorMap* m) { asm volatile("prefetch.tensormap [%0];" ::"l"(m) : "memory"); }
__device__ __forceinline__ bool elect_one() {
  uint32_t pred;
  asm volatile("{.reg .pred P; elect.sync _|P, 0xffffffff; selp.u32 %0, 1, 0, P;}" : "=r"(pred));
  return pred != 0;
}
__device__ __forceinline__ void cluster_wait() { asm volatile("barrier.cluster.wait.aligned;" ::: "memory"); }
__device__ __forceinline__ void wg_fence() { asm volatile("wgmma.fence.sync.aligned;" ::: "memory"); }
__device__ __forceinline__ void wg_commit() { asm volatile("wgmma.commit_group.sync.aligned;" ::: "memory"); }
template <int N> __device__ __forceinline__ void wg_wait() { asm volatile("wgmma.wait_group.sync.aligned %0;" ::"n"(N) : "memory"); }
__device__ __forceinline__ void pin(float& a) { asm volatile("" : "+f"(a)::"memory"); }
__device__ __forceinline__ void pin(uint32_t& a) { asm volatile("" : "+r"(a)::"memory"); }
template <int N> __device__ __forceinline__ void reg_fence(float (&d)[N]) {
#pragma unroll
  for (int i = 0; i < N; i++) pin(d[i]);
}
__device__ __forceinline__ void sched_fence(uint32_t& ck) { asm volatile("{.reg .b32 c; mov.u32 c, %%clock; xor.b32 %0, %0, c;}" : "+r"(ck)::"memory"); }
__device__ __forceinline__ void bar_sync(int id, int n) { asm volatile("bar.sync %0, %1;" ::"r"(id), "r"(n) : "memory"); }
__device__ __forceinline__ void bar_arrive(int id, int n) { asm volatile("bar.arrive %0, %1;" ::"r"(id), "r"(n) : "memory"); }
constexpr uint32_t DH128 = (1024 >> 4) | (1u << 30), DH64 = (512 >> 4) | (2u << 30);
__host__ __device__ constexpr uint32_t lbo(uint32_t bytes) { return (bytes >> 4) << 20; }
__device__ __forceinline__ uint32_t pack_bf16(float lo, float hi) { uint32_t r; asm("cvt.rn.bf16x2.f32 %0, %1, %2;" : "=r"(r) : "f"(hi), "f"(lo)); return r; }
__device__ __forceinline__ float bf_lo(uint32_t v) { return __uint_as_float(v << 16); }
__device__ __forceinline__ float bf_hi(uint32_t v) { return __uint_as_float(v & 0xffff0000u); }
__device__ __forceinline__ float bf_ld(const __nv_bfloat16* p) { return __bfloat162float(__ldg(p)); }
__device__ __forceinline__ uint32_t late16(uint32_t bar) {
  uint32_t r;
  asm volatile("{.reg .pred p; mbarrier.test_wait.parity.shared::cta.b64 p, [%1], 0; selp.u32 %0, 16, 0, p;}" : "=r"(r) : "r"(bar) : "memory");
  return r;
}
__device__ __forceinline__ float2 lds_f2(uint32_t a) { float2 v; asm volatile("ld.shared.v2.f32 {%0,%1}, [%2];" : "=f"(v.x), "=f"(v.y) : "r"(a)); return v; }
__device__ __forceinline__ uint32_t lds_h(uint32_t a) { uint32_t v; asm volatile("ld.shared.u16 %0, [%1];" : "=r"(v) : "r"(a)); return v; }
__device__ __forceinline__ uint32_t lds_u(uint32_t a) { uint32_t v; asm volatile("ld.shared.u32 %0, [%1];" : "=r"(v) : "r"(a)); return v; }
__device__ __forceinline__ uint4 lds_u4(uint32_t a) { uint4 v; asm volatile("ld.shared.v4.u32 {%0,%1,%2,%3}, [%4];" : "=r"(v.x), "=r"(v.y), "=r"(v.z), "=r"(v.w) : "r"(a)); return v; }
__device__ __forceinline__ void sts_u(uint32_t a, uint32_t v) { asm volatile("st.shared.u32 [%0], %1;" ::"r"(a), "r"(v) : "memory"); }
__device__ __forceinline__ void sts_u2(uint32_t a, uint32_t x, uint32_t y) { asm volatile("st.shared.v2.u32 [%0], {%1,%2};" ::"r"(a), "r"(x), "r"(y) : "memory"); }
__device__ __forceinline__ void sts_f2(uint32_t a, float x, float y) { asm volatile("st.shared.v2.f32 [%0], {%1,%2};" ::"r"(a), "f"(x), "f"(y) : "memory"); }
__device__ __forceinline__ void sts_f4(uint32_t a, float x, float y, float z, float w) {
  asm volatile("st.shared.v4.f32 [%0], {%1,%2,%3,%4};" ::"r"(a), "f"(x), "f"(y), "f"(z), "f"(w) : "memory");
}
__device__ __forceinline__ void st_b128(uint4* p, uint32_t a, uint32_t b, uint32_t c, uint32_t d) {
  asm volatile("st.relaxed.gpu.global.v4.b32 [%0], {%1,%2,%3,%4};" ::"l"(p), "r"(a), "r"(b), "r"(c), "r"(d) : "memory");
}
__device__ __forceinline__ void ld_b128(const uint4* p, uint32_t& a, uint32_t& b, uint32_t& c, uint32_t& d) {
  asm volatile("{.reg .b64 l, h; .reg .b128 v; ld.relaxed.gpu.global.b128 v, [%4]; mov.b128 {l,h}, v; mov.b64 {%0,%1}, l; mov.b64 {%2,%3}, h;}"
               : "=r"(a), "=r"(b), "=r"(c), "=r"(d) : "l"(p) : "memory");
}
__device__ __forceinline__ uint32_t bf2_mul(uint32_t a, uint32_t b) { uint32_t r; asm("mul.rn.bf16x2 %0, %1, %2;" : "=r"(r) : "r"(a), "r"(b)); return r; }
__device__ __forceinline__ uint32_t bf2_add(uint32_t a, uint32_t b) { uint32_t r; asm("add.rn.bf16x2 %0, %1, %2;" : "=r"(r) : "r"(a), "r"(b)); return r; }
__device__ __forceinline__ uint32_t bf2_fma(uint32_t a, uint32_t b, uint32_t c) { uint32_t r; asm("fma.rn.bf16x2 %0, %1, %2, %3;" : "=r"(r) : "r"(a), "r"(b), "r"(c)); return r; }
__device__ __forceinline__ uint32_t gelu2_pair(float a, float b) {
  const uint32_t v = pack_bf16(a, b);
  uint32_t t;
  asm("tanh.approx.bf16x2 %0, %1;" : "=r"(t) : "r"(bf2_fma(v, bf2_fma(bf2_mul(v, v), 0x3d123d12u, 0xbe4fbe4fu), v)));
  return bf2_fma(v, t, v);
}
struct cplx { float re, im; };
__device__ __forceinline__ cplx cmul(cplx a, cplx b) { return {fmaf(a.re, b.re, -a.im * b.im), fmaf(a.re, b.im, a.im * b.re)}; }
__device__ __forceinline__ cplx cfma(cplx a, cplx b, cplx c) {
  return {fmaf(a.re, b.re, fmaf(-a.im, b.im, c.re)), fmaf(a.re, b.im, fmaf(a.im, b.re, c.im))};
}
__device__ __forceinline__ cplx make_lam(float lre, float lim, float ldt) {
  float dt = __bfloat162float(__float2bfloat16_rn(expf(ldt)));
  float mag = expf(dt * lre), sn, cs;
  sincospif(dt * lim * 0.31830988618379067f, &sn, &cs);
  return {mag * cs, mag * sn};
}

template <int NG>
__device__ __forceinline__ void gate_rows(uint32_t sb, int lane, int xrot, int row0, uint4 (&gw)[4], const uint4* gwp, unsigned* dst, unsigned par) {
  const int row = row0 + (lane >> 3);
  const uint32_t xr0 = sb + OFF_X + row * 128 + (((lane & 7) ^ (row & 7)) << 4), xr1 = (xr0 + 512) ^ 64;
  float z[NG], y[NG];
#pragma unroll
  for (int r = 0; r < NG; r++) z[r] = y[r] = 0.f;
#pragma unroll
  for (int kb = 0; kb < 8; kb++) {
    const uint4 w = gw[kb & 3];
    if (kb < 4) gw[kb] = __ldg(gwp + (kb + 4) * 8);
    mbar_wait(sb + OFF_XFULL + 8 * kb, 0);
#pragma unroll
    for (int r = 0; r < NG; r++) {
      const uint4 a = lds_u4((r ? xr1 : xr0) + ((kb + xrot) & 7) * 16384);
      const uint32_t p[4] = {bf2_mul(a.x, w.x), bf2_mul(a.y, w.y), bf2_mul(a.z, w.z), bf2_mul(a.w, w.w)};
#pragma unroll
      for (int c = 0; c < 4; c++) { z[r] += bf_lo(p[c]); y[r] += bf_hi(p[c]); }
    }
  }
  float zz = z[0] + y[0];
  if (NG == 2) {
    const float z1 = z[NG - 1] + y[NG - 1];
    zz = ((lane & 4) ? z1 : zz) + __shfl_xor_sync(0xffffffffu, (lane & 4) ? zz : z1, 4);
  } else {
    zz += __shfl_xor_sync(0xffffffffu, zz, 4);
  }
  zz += __shfl_xor_sync(0xffffffffu, zz, 2);
  zz += __shfl_xor_sync(0xffffffffu, zz, 1);
  zz = bf_lo(pack_bf16(zz, 0.f));
  const float rho = 4.f * expf(zz > 40.f ? 40.f : zz);
  if ((lane & (NG == 2 ? 3 : 7)) == 0)
    asm volatile("st.relaxed.gpu.global.u32 [%0], %1;" ::"l"(dst + row + (lane & 4)), "r"((__float_as_uint(rho) & ~1u) | par) : "memory");
}

template<int TA,int TB,uint32_t AH,uint32_t BH> __device__ __forceinline__ void wgmma_n64_ss(float (&d)[32], uint32_t al, uint32_t ao, uint32_t bl, uint32_t bo, int scale_d){
  asm volatile("{.reg .pred p; .reg .b32 t, v; .reg .b64 da, db; setp.ne.b32 p, %36, 0; add.u32 t, %32, %33; mov.b64 da, {t, %39}; add.u32 v, %34, %35; mov.b64 db, {v, %40};\n"
   "wgmma.mma_async.sync.aligned.m64n64k16.f32.bf16.bf16 {%0,%1,%2,%3,%4,%5,%6,%7,%8,%9,%10,%11,%12,%13,%14,%15,%16,%17,%18,%19,%20,%21,%22,%23,%24,%25,%26,%27,%28,%29,%30,%31}, da, db, p, 1, 1, %37, %38;}"
   : "+f"(d[0]),"+f"(d[1]),"+f"(d[2]),"+f"(d[3]),"+f"(d[4]),"+f"(d[5]),"+f"(d[6]),"+f"(d[7]),"+f"(d[8]),"+f"(d[9]),"+f"(d[10]),"+f"(d[11]),"+f"(d[12]),"+f"(d[13]),"+f"(d[14]),"+f"(d[15]),"+f"(d[16]),"+f"(d[17]),"+f"(d[18]),"+f"(d[19]),"+f"(d[20]),"+f"(d[21]),"+f"(d[22]),"+f"(d[23]),"+f"(d[24]),"+f"(d[25]),"+f"(d[26]),"+f"(d[27]),"+f"(d[28]),"+f"(d[29]),"+f"(d[30]),"+f"(d[31])
   : "r"(al),"r"(ao >> 4),"r"(bl),"r"(bo >> 4),"r"(scale_d),"n"(TA),"n"(TB),"n"(AH),"n"(BH));
}
template<int TB,uint32_t BH,int SA=1> __device__ __forceinline__ void wgmma_n64_rs(float (&d)[32], uint32_t a0,uint32_t a1,uint32_t a2,uint32_t a3, uint32_t bl, uint32_t bo, int scale_d){
  asm volatile("{.reg .pred p; .reg .b32 t; .reg .b64 db; setp.ne.b32 p, %38, 0; add.u32 t, %36, %37; mov.b64 db, {t, %40};\n"
   "wgmma.mma_async.sync.aligned.m64n64k16.f32.bf16.bf16 {%0,%1,%2,%3,%4,%5,%6,%7,%8,%9,%10,%11,%12,%13,%14,%15,%16,%17,%18,%19,%20,%21,%22,%23,%24,%25,%26,%27,%28,%29,%30,%31}, {%32,%33,%34,%35}, db, p, %41, 1, %39;}"
   : "+f"(d[0]),"+f"(d[1]),"+f"(d[2]),"+f"(d[3]),"+f"(d[4]),"+f"(d[5]),"+f"(d[6]),"+f"(d[7]),"+f"(d[8]),"+f"(d[9]),"+f"(d[10]),"+f"(d[11]),"+f"(d[12]),"+f"(d[13]),"+f"(d[14]),"+f"(d[15]),"+f"(d[16]),"+f"(d[17]),"+f"(d[18]),"+f"(d[19]),"+f"(d[20]),"+f"(d[21]),"+f"(d[22]),"+f"(d[23]),"+f"(d[24]),"+f"(d[25]),"+f"(d[26]),"+f"(d[27]),"+f"(d[28]),"+f"(d[29]),"+f"(d[30]),"+f"(d[31])
   : "r"(a0),"r"(a1),"r"(a2),"r"(a3),"r"(bl),"r"(bo >> 4),"r"(scale_d),"n"(TB),"n"(BH),"n"(SA));
}
template<int TA,int TB,uint32_t AH,uint32_t BH> __device__ __forceinline__ void wgmma_n96_ss(float (&d)[48], uint32_t al, uint32_t ao, uint32_t bl, uint32_t bo, int scale_d){
  asm volatile("{.reg .pred p; .reg .b32 t, v; .reg .b64 da, db; setp.ne.b32 p, %52, 0; add.u32 t, %48, %49; mov.b64 da, {t, %55}; add.u32 v, %50, %51; mov.b64 db, {v, %56};\n"
   "wgmma.mma_async.sync.aligned.m64n96k16.f32.bf16.bf16 {%0,%1,%2,%3,%4,%5,%6,%7,%8,%9,%10,%11,%12,%13,%14,%15,%16,%17,%18,%19,%20,%21,%22,%23,%24,%25,%26,%27,%28,%29,%30,%31,%32,%33,%34,%35,%36,%37,%38,%39,%40,%41,%42,%43,%44,%45,%46,%47}, da, db, p, 1, 1, %53, %54;}"
   : "+f"(d[0]),"+f"(d[1]),"+f"(d[2]),"+f"(d[3]),"+f"(d[4]),"+f"(d[5]),"+f"(d[6]),"+f"(d[7]),"+f"(d[8]),"+f"(d[9]),"+f"(d[10]),"+f"(d[11]),"+f"(d[12]),"+f"(d[13]),"+f"(d[14]),"+f"(d[15]),"+f"(d[16]),"+f"(d[17]),"+f"(d[18]),"+f"(d[19]),"+f"(d[20]),"+f"(d[21]),"+f"(d[22]),"+f"(d[23]),"+f"(d[24]),"+f"(d[25]),"+f"(d[26]),"+f"(d[27]),"+f"(d[28]),"+f"(d[29]),"+f"(d[30]),"+f"(d[31]),"+f"(d[32]),"+f"(d[33]),"+f"(d[34]),"+f"(d[35]),"+f"(d[36]),"+f"(d[37]),"+f"(d[38]),"+f"(d[39]),"+f"(d[40]),"+f"(d[41]),"+f"(d[42]),"+f"(d[43]),"+f"(d[44]),"+f"(d[45]),"+f"(d[46]),"+f"(d[47])
   : "r"(al),"r"(ao >> 4),"r"(bl),"r"(bo >> 4),"r"(scale_d),"n"(TA),"n"(TB),"n"(AH),"n"(BH));
}
template<int TA,int TB,uint32_t AH,uint32_t BH> __device__ __forceinline__ void wgmma_n128_ss(float (&d)[64], uint32_t al, uint32_t ao, uint32_t bl, uint32_t bo, int scale_d){
  asm volatile("{.reg .pred p; .reg .b32 t, v; .reg .b64 da, db; setp.ne.b32 p, %68, 0; add.u32 t, %64, %65; mov.b64 da, {t, %71}; add.u32 v, %66, %67; mov.b64 db, {v, %72};\n"
   "wgmma.mma_async.sync.aligned.m64n128k16.f32.bf16.bf16 {%0,%1,%2,%3,%4,%5,%6,%7,%8,%9,%10,%11,%12,%13,%14,%15,%16,%17,%18,%19,%20,%21,%22,%23,%24,%25,%26,%27,%28,%29,%30,%31,%32,%33,%34,%35,%36,%37,%38,%39,%40,%41,%42,%43,%44,%45,%46,%47,%48,%49,%50,%51,%52,%53,%54,%55,%56,%57,%58,%59,%60,%61,%62,%63}, da, db, p, 1, 1, %69, %70;}"
   : "+f"(d[0]),"+f"(d[1]),"+f"(d[2]),"+f"(d[3]),"+f"(d[4]),"+f"(d[5]),"+f"(d[6]),"+f"(d[7]),"+f"(d[8]),"+f"(d[9]),"+f"(d[10]),"+f"(d[11]),"+f"(d[12]),"+f"(d[13]),"+f"(d[14]),"+f"(d[15]),"+f"(d[16]),"+f"(d[17]),"+f"(d[18]),"+f"(d[19]),"+f"(d[20]),"+f"(d[21]),"+f"(d[22]),"+f"(d[23]),"+f"(d[24]),"+f"(d[25]),"+f"(d[26]),"+f"(d[27]),"+f"(d[28]),"+f"(d[29]),"+f"(d[30]),"+f"(d[31]),"+f"(d[32]),"+f"(d[33]),"+f"(d[34]),"+f"(d[35]),"+f"(d[36]),"+f"(d[37]),"+f"(d[38]),"+f"(d[39]),"+f"(d[40]),"+f"(d[41]),"+f"(d[42]),"+f"(d[43]),"+f"(d[44]),"+f"(d[45]),"+f"(d[46]),"+f"(d[47]),"+f"(d[48]),"+f"(d[49]),"+f"(d[50]),"+f"(d[51]),"+f"(d[52]),"+f"(d[53]),"+f"(d[54]),"+f"(d[55]),"+f"(d[56]),"+f"(d[57]),"+f"(d[58]),"+f"(d[59]),"+f"(d[60]),"+f"(d[61]),"+f"(d[62]),"+f"(d[63])
   : "r"(al),"r"(ao >> 4),"r"(bl),"r"(bo >> 4),"r"(scale_d),"n"(TA),"n"(TB),"n"(AH),"n"(BH));
}

__global__ void __cluster_dims__(2, 1, 1) __launch_bounds__(384, 1)
fused_kernel(const __nv_bfloat16* __restrict__ lam_re, const __nv_bfloat16* __restrict__ lam_im, const __nv_bfloat16* __restrict__ log_dt,
             const __nv_bfloat16* __restrict__ dskip, const __nv_bfloat16* __restrict__ b1, const __nv_bfloat16* __restrict__ b2,
             const __nv_bfloat16* __restrict__ gate_w, float* __restrict__ out, const __grid_constant__ Maps maps) {
  extern __shared__ __align__(1024) unsigned char smem_raw[];
  const uint32_t sb = (uint32_t)__cvta_generic_to_shared(smem_raw);
  const int b = blockIdx.x;
  const int rank = b & 1, cl = b >> 1;
  const int sp = (cl & 1) | ((cl >> 2) & 2), m = ((cl >> 1) & 3) | ((cl >> 4) << 2);
  const int s = sp * 2 + rank;
  const int xrot = 9 - 2 * sp;
  if (threadIdx.x == 0) {
    mbar_init(sb + OFF_XFULL, 1);
    mbar_expect_tx(sb + OFF_XFULL, 16384);
    tma5d(sb + OFF_X + (xrot & 7) * 16384, &maps.x, 0, 2 * m, sb + OFF_XFULL);
    tma5d(sb + OFF_X + (xrot & 7) * 16384 + 8192, &maps.x, 0, 2 * m + 1, sb + OFF_XFULL);
  }
  if (threadIdx.x == 128) {
    mbar_init(sb + OFF_FULL, 1);
    mbar_expect_tx(sb + OFF_FULL, 16384);
    tma2d(sb + OFF_RING, &maps.bre, 0, s * 64, sb + OFF_FULL);
    tma2d(sb + OFF_RING + 8192, &maps.bim, 0, s * 64, sb + OFF_FULL);
  }
  const int warp = __shfl_sync(0xffffffffu, (int)(threadIdx.x >> 5), 0);
  const int lane0 = threadIdx.x & 31;

  if (elect_one()) {
    if (warp > 8) {
      map_prefetch(&maps.x + (warp - 9));
      mbar_init(sb + OFF_GBAR + 8 * (warp - 9), warp < 11 ? 64 : 96);
    }
    const uint32_t c = warp < 8 ? 1 : warp < 11 ? 8 : 4, bar = sb + OFF_XFULL + 16 * warp;
    if ((warp & 11) != 0) mbar_init(bar, c);
    mbar_init(bar + 8, c);
    asm volatile("fence.mbarrier_init.release.cluster;" ::: "memory");
  }
  __syncwarp();
  asm volatile("barrier.cluster.arrive.relaxed.aligned;" ::: "memory");

  if (warp < 8) {
    const int lane = __shfl_sync(0xffffffffu, lane0, lane0);
    const int wg = warp >> 2, w = warp & 3, q = lane & 3, gr = lane >> 2;
    uint32_t bv[28];
#pragma unroll
    for (int j = 0; j < 28; j++) bv[j] = __ldg(reinterpret_cast<const uint32_t*>(b1 + s * 224 + j * 8) + q);
    asm volatile("setmaxnreg.inc.sync.aligned.u32 224;");
    cluster_wait();
    auto release = [&](int slot) { if (lane == 0) mbar_arrive(sb + OFF_EMPTY + 8 * slot); };
    const uint32_t xw = sb + OFF_X + wg * 8192, fullb = sb + OFF_FULL;
    const uint32_t dxw = (xw & 0x3FFFF) >> 4, dring = ((sb + OFF_RING) & 0x3FFFF) >> 4;

    float ure[32], uim[32], aa[48], ab[64];
    cplx lam[2], coef[2], l16[2], l32[2], lq[2], pre[2], e[2];
    uint32_t sh16, mhi, ck = 0;

    auto bias = [&](int c) {
#pragma unroll
      for (int j = c * 7; j < c * 7 + 7; j++) {
        pin(bv[j]);
        float* d = j < 12 ? aa + 4 * j : ab + 4 * (j - 12);
        d[0] = d[2] = __uint_as_float(bv[j] << sh16); d[1] = d[3] = __uint_as_float(bv[j] & mhi);
        pin(d[0]); pin(d[1]); pin(d[2]); pin(d[3]);
      }
    };
#pragma unroll
    for (int kb = 0; kb < 8; kb++) {
      const int slot = kb % NSLOT;
      mbar_wait(sb + OFF_XFULL + 8 * kb, 0);
      if (kb == 0) mbar_wait(fullb, 0);
      if (kb == 2) { sh16 = late16(sb + OFF_XFULL); mhi = 0xffffffffu << sh16; }
      if (kb == 4) {
        mbar_wait(sb + OFF_LBAR, 0);
#pragma unroll
        for (int h = 0; h < 2; h++) {
          const uint4 v = lds_u4(sb + OFF_LC + (w * 16 + gr + 8 * h) * 16);
          lam[h] = cplx{__uint_as_float(v.x), __uint_as_float(v.y)};
          coef[h] = cplx{__uint_as_float(v.z), __uint_as_float(v.w)};
        }
      }
      wg_fence();
      const uint32_t dxa = dxw + ((kb + xrot) & 7) * 1024;
#pragma unroll
      for (int kk = 0; kk < 4; kk++) {
        wgmma_n64_ss<0, 0, DH128, DH128>(ure, dring, slot * 16384 + kk * 32, dxa, kk * 32, (kb | kk) != 0);
        wgmma_n64_ss<0, 0, DH128, DH128>(uim, dring, slot * 16384 + 8192 + kk * 32, dxa, kk * 32, (kb | kk) != 0);
      }
      wg_commit();
      if (kb > 0) { wg_wait<1>(); release((kb - 1) % NSLOT); }
      if (kb >= 2 && kb < 5) bias(kb - 2);
      if (kb == 6) {
#pragma unroll
        for (int h = 0; h < 2; h++) {
          pin(lam[h].re); pin(lam[h].im);
          cplx t = cmul(lam[h], lam[h]); t = cmul(t, t); t = cmul(t, t);
          l16[h] = cmul(t, t);
          pin(l16[h].re); pin(l16[h].im);
        }
      }
      if (kb == 7) {
#pragma unroll
        for (int h = 0; h < 2; h++) {
          pin(l16[h].re); pin(l16[h].im);
          l32[h] = cmul(l16[h], l16[h]);
          const cplx a = (q & 1) ? l16[h] : cplx{1.f, 0.f}, c = (q & 2) ? l32[h] : cplx{1.f, 0.f};
          lq[h] = cmul(cmul(a, c), coef[h]);
          pin(lq[h].re); pin(lq[h].im);
        }
      }
    }
    auto scale_u = [&](int i0) {
#pragma unroll
      for (int i = i0; i < i0 + 8; i++) {
        pin(ure[i]); pin(uim[i]);
        const cplx v = cmul(coef[(i >> 1) & 1], cplx{ure[i], uim[i]});
        ure[i] = v.re; uim[i] = v.im;
        pin(ure[i]); pin(uim[i]);
      }
    };
#pragma unroll
    for (int kb = 0; kb < 8; kb++) {
      const int u = 8 + kb, slot = u % NSLOT;
      mbar_wait(fullb + 8 * slot, full_par(u));
      wg_fence();
      const uint32_t dxa = dxw + ((kb + xrot) & 7) * 1024;
#pragma unroll
      for (int kk = 0; kk < 4; kk++)
        wgmma_n96_ss<0, 1, DH128, DH64>(aa, dxa, kk * 32, dring, slot * 16384 + kk * 1024 + lbo(4096), 1);
      wg_commit();
      if (kb == 0) bias(3);
      if (kb != 4) { wg_wait<1>(); release((u - 1) % NSLOT); }
      if (kb == 0) {
        reg_fence(ure); reg_fence(uim);
#pragma unroll
        for (int h = 0; h < 2; h++) e[h] = cplx{ure[2 * h], uim[2 * h]};
      }
      if (kb == 0 || kb == 2 || kb == 3) {
        const int t0 = kb ? 5 * kb - 4 : 1;
#pragma unroll
        for (int t = t0; t < t0 + 5; t++) {
#pragma unroll
          for (int h = 0; h < 2; h++) { const int i = 4 * (t >> 1) + 2 * h + (t & 1); e[h] = cfma(lam[h], e[h], cplx{ure[i], uim[i]}); }
        }
#pragma unroll
        for (int h = 0; h < 2; h++) { pin(e[h].re); pin(e[h].im); }
      }
      if (kb == 4) {
        scale_u(0);
        sched_fence(ck);
#pragma unroll
        for (int h = 0; h < 2; h++) {
          cplx y = {__shfl_up_sync(0xffffffffu, e[h].re, 1, 4), __shfl_up_sync(0xffffffffu, e[h].im, 1, 4)};
          if (q >= 1) e[h] = cfma(l16[h], y, e[h]);
          y = cplx{__shfl_up_sync(0xffffffffu, e[h].re, 2, 4), __shfl_up_sync(0xffffffffu, e[h].im, 2, 4)};
          if (q >= 2) e[h] = cfma(l32[h], y, e[h]);
        }
        if (q == 3) {
#pragma unroll
          for (int h = 0; h < 2; h++) sts_f2(sb + OFF_CARRY + wg * 512 + (w * 16 + gr + 8 * h) * 8, e[h].re, e[h].im);
          mbar_arrive(sb + OFF_GBAR);
        }
#pragma unroll
        for (int h = 0; h < 2; h++) e[h] = cplx{__shfl_up_sync(0xffffffffu, e[h].re, 1, 4), __shfl_up_sync(0xffffffffu, e[h].im, 1, 4)};
        wg_wait<1>(); release((u - 1) % NSLOT);
      }
      if (kb == 5) {
#pragma unroll
        for (int h = 0; h < 2; h++) {
          pre[h] = (q >= 1) ? cmul(coef[h], e[h]) : cplx{0.f, 0.f};
          pin(pre[h].re); pin(pre[h].im);
        }
      }
      if (kb > 5) scale_u((kb - 5) * 8);
    }
    uint32_t H[56], hf[32];
    cplx hst[2];
    const uint32_t hst_addr = xw + (w * 16 + (lane & 15)) * 128 + (((lane >> 4) ^ (lane & 7)) << 4);
    const uint32_t him = (2 - rank) * 16384;
    uint32_t peer;
    asm volatile("mapa.shared::cluster.u32 %0, %1, %2;" : "=r"(peer) : "r"(sb), "r"(rank ^ 1));
    auto credit = [&]() { if (lane == 0) mbar_arrive_cl(peer + OFF_KBAR + wg * 8); };
    uint32_t g2[8];
#pragma unroll
    for (int kb = 0; kb < 8; kb++) {
      const int u = 16 + kb, slot = u % NSLOT;
      mbar_wait(fullb + 8 * slot, full_par(u));
      wg_fence();
#pragma unroll
      for (int kk = 0; kk < 4; kk++)
        wgmma_n128_ss<0, 1, DH128, DH128>(ab, dxw, kb * 16384 + kk * 32, dring, slot * 16384 + kk * 2048 + lbo(8192), 1);
      wg_commit();
      if (kb == 0) scale_u(24);
      if (kb == 4) {
        mbar_wait(sb + OFF_CBAR, 0);
#pragma unroll
        for (int h = 0; h < 2; h++) {
          const float2 c = lds_f2(sb + OFF_CARRY + wg * 512 + (w * 16 + gr + 8 * h) * 8);
          hst[h] = cfma(lq[h], cplx{c.x, c.y}, pre[h]);
        }
#pragma unroll
        for (int i = 0; i < 2; i++) {
          const uint4 v = lds_u4(sb + OFF_GT + wg * 128 + q * 32 + i * 16);
          g2[4 * i] = v.x; g2[4 * i + 1] = v.y; g2[4 * i + 2] = v.z; g2[4 * i + 3] = v.w;
        }
      }
      wg_wait<1>(); release((u - 1) % NSLOT);
      if (kb) sched_fence(ck);
      if (kb < 4) {
#pragma unroll
        for (int i = kb * 6; i < kb * 6 + 6; i++) {
          pin(aa[2 * i]); pin(aa[2 * i + 1]);
          H[i] = gelu2_pair(aa[2 * i], aa[2 * i + 1]);
          pin(H[i]);
        }
      } else {
        const int j0 = (kb - 4) * 2;
        uint32_t rr[4], ri[4];
#pragma unroll
        for (int jj = 0; jj < 2; jj++) {
          const int j = j0 + jj;
#pragma unroll
          for (int h = 0; h < 2; h++) {
            const int i = 4 * j + 2 * h;
            const cplx h0 = cfma(lam[h], hst[h], cplx{ure[i], uim[i]});
            hst[h] = cfma(lam[h], h0, cplx{ure[i + 1], uim[i + 1]});
            rr[jj * 2 + h] = bf2_mul(pack_bf16(h0.re, hst[h].re), g2[j]);
            ri[jj * 2 + h] = bf2_mul(pack_bf16(h0.im, hst[h].im), g2[j]);
          }
        }
        const uint32_t a = hst_addr ^ (j0 << 4);
        asm volatile("stmatrix.sync.aligned.m8n8.x4.shared.b16 [%0], {%1,%2,%3,%4};" ::"r"(a), "r"(rr[0]), "r"(rr[1]), "r"(rr[2]), "r"(rr[3]) : "memory");
        asm volatile("stmatrix.sync.aligned.m8n8.x4.shared.b16 [%0], {%1,%2,%3,%4};" ::"r"(a + him), "r"(ri[0]), "r"(ri[1]), "r"(ri[2]), "r"(ri[3]) : "memory");
      }
    }

    uint4* const psend = g_part + (size_t)(m * 8 + rank) * 3072 + warp * 128 + lane;
    const uint4* const precv = g_part + (size_t)(m * 8 + s) * 3072 + warp * 128 + lane;
    const uint32_t pbuf = OFF_X + warp * 2048 + lane * 16;
    const uint32_t dx0 = ((sb + OFF_X) & 0x3FFFF) >> 4;
    float o[32], fin[32], fs[2];
    uint32_t r0[16], pt[16], sum[16], tag;
    auto recv_issue = [&](uint32_t (&r)[16], int k) {
#pragma unroll
      for (int i = 0; i < 4; i++) ld_b128(precv + k * 1024 + i * 32, r[4 * i], r[4 * i + 1], r[4 * i + 2], r[4 * i + 3]);
    };
    auto stale = [&](uint32_t (&r)[16]) {
      uint32_t r_;
#pragma unroll
      for (int i = 0; i < 16; i += 4) asm("lop3.b32 %0, %0, %1, 1, 0x78;" : "+r"(r[i]) : "r"(tag));
      asm volatile("{.reg .pred p; .reg .b32 t; lop3.b32 t, %1, %2, %3, 0xfe; lop3.b32 t, t, %4, 1, 0xa8; setp.ne.u32 p, t, 0; vote.sync.any.pred p, p, 0xffffffff; selp.u32 %0, 1, 0, p;}"
                   : "=r"(r_) : "r"(r[0]), "r"(r[4]), "r"(r[8]), "r"(r[12]));
      return r_ != 0;
    };
    auto recv_check = [&](uint32_t (&r)[16], int k) {
      if (__builtin_expect(stale(r), 0)) {
        int tries = 0;
#pragma unroll 1
        do { recv_issue(r, k); } while (stale(r) && ++tries < 200000);
      }
    };
    auto gelu_b = [&](int i0, int i1) {
#pragma unroll
      for (int i = i0; i < i1; i++) {
        pin(ab[2 * i]); pin(ab[2 * i + 1]);
        H[24 + i] = gelu2_pair(ab[2 * i], ab[2 * i + 1]);
        pin(H[24 + i]);
      }
    };
    auto mma = [&](float (&d)[32], int p, int k0, int k1, int acc) {
      const uint32_t wo = stage_off(p);
      wg_fence();
#pragma unroll
      for (int k = k0; k < k1; k++) {
        if (k >= 6 && k < 14) {
          const int kk = k - 6;
          if (kk < 4) wgmma_n64_rs<0, DH128, 1>(d, hf[4 * kk], hf[4 * kk + 1], hf[4 * kk + 2], hf[4 * kk + 3], dx0, wo + 14336 + kk * 32, 1);
          else wgmma_n64_rs<0, DH128, -1>(d, hf[4 * kk], hf[4 * kk + 1], hf[4 * kk + 2], hf[4 * kk + 3], dx0, wo + 22528 + (kk - 4) * 32, 1);
        } else {
          const int kk = k < 6 ? k : k - 8;
          wgmma_n64_rs<1, DH128>(d, H[4 * kk], H[4 * kk + 1], H[4 * kk + 2], H[4 * kk + 3], dx0, wo + (kk / 7) * 30720 + (kk % 7) * 2048, k != 0 || acc);
        }
      }
      wg_commit();
    };
    auto recv_peer = [&](int k) {
      mbar_wait(sb + OFF_RBAR + wg * 8, k & 1);
#pragma unroll
      for (int i = 0; i < 4; i++) { const uint4 v = lds_u4(sb + pbuf + i * 512); pt[4 * i] = v.x; pt[4 * i + 1] = v.y; pt[4 * i + 2] = v.z; pt[4 * i + 3] = v.w; }
    };
#pragma unroll
    for (int p = 0; p < 8; p++) {
      if (p == 0) {
        mbar_wait(fullb, full_par(24));
        mma(o, 0, 0, 4, 0);
        bar_sync(1 + wg, 128);
        {
          const uint32_t ha = xw + ((lane >> 4) * 8 + (lane & 7)) * 128 + (((2 * w + ((lane >> 3) & 1)) ^ (lane & 7)) << 4);
#pragma unroll
          for (int kk = 0; kk < 8; kk++)
            asm volatile("ldmatrix.sync.aligned.m8n8.x4.trans.shared.b16 {%0,%1,%2,%3}, [%4];" : "=r"(hf[4 * kk]), "=r"(hf[4 * kk + 1]), "=r"(hf[4 * kk + 2]), "=r"(hf[4 * kk + 3])
                         : "r"(ha + (kk >> 2) * him + (kk & 3) * 2048) : "memory");
        }
        mbar_wait(fullb + 8, full_par(25));
        wg_wait<1>(); release(5);
        gelu_b(0, 6);
        mma(o, 0, 4, 8, 0);
        gelu_b(6, 12);
        mma(o, 0, 8, 12, 0);
        credit();
        gelu_b(12, 18);
        mbar_wait(fullb + 16, full_par(26));
        mma(o, 0, 12, 15, 0);
        gelu_b(18, 24);
        mma(o, 0, 15, 18, 0);
        gelu_b(24, 32);
        if (wg == 1) bar_sync(4, 256);
        mma(o, 0, 18, 22, 0);
      } else {
        bar_sync(3 + wg, 256);
        if (p < 7) mma(o, p, 0, 22, 0); else mma(fin, p, 0, 22, 1);
      }
      if (p < 7 || wg == 0) bar_arrive(4 - wg, 256);
      if (p < 7) mbar_wait(sb + OFF_XFULL + 8 * (p + 1), 1);
      if ((p & 1) == 0) {
        if (w == 0 && lane == 0) mbar_expect_tx(sb + OFF_RBAR + wg * 8, 8192);
        if (p == 6) {
          mbar_wait(sb + OFF_EMPTY + 32, 0);
          tag = lds_u(sb + OFF_EPOCH);
          recv_check(sum, 0); recv_check(r0, 1);
#pragma unroll
          for (int i = 0; i < 16; i++) sum[i] = bf2_add(sum[i], r0[i]);
        }
        mbar_wait(sb + OFF_KBAR + wg * 8, (p >> 1) & 1);
      } else {
        if (p == 1 || p == 7) tag = lds_u(sb + OFF_EPOCH);
        recv_peer(p >> 1);
        if (p == 7) {
          recv_check(r0, 2);
#pragma unroll
          for (int i = 0; i < 16; i++) { sum[i] = bf2_add(sum[i], bf2_add(r0[i], pt[i])); pin(sum[i]); }
          sched_fence(ck);
        }
      }
      if (p == 4) {
        mbar_wait(sb + OFF_LBAR, 1);
#pragma unroll
        for (int j = 0; j < 8; j++) {
          const uint4 v = lds_u4(sb + pbuf + 16384 + (j >> 2) * 16384 + (j & 3) * 512);
          fin[4 * j] = __uint_as_float(v.x); fin[4 * j + 1] = __uint_as_float(v.y); fin[4 * j + 2] = __uint_as_float(v.z); fin[4 * j + 3] = __uint_as_float(v.w);
        }
        recv_issue(sum, 0);
      }
      wg_wait<0>();
      if (p < 5) release(p);
      if (p < 7) reg_fence(o); else reg_fence(fin);
      if ((p & 1) == 0) {
        if (p == 6) recv_issue(r0, 2);
#pragma unroll
        for (int i = 0; i < 4; i++)
          asm volatile("st.async.shared::cluster.mbarrier::complete_tx::bytes.v4.b32 [%0], {%1,%2,%3,%4}, [%5];" ::"r"(peer + pbuf + i * 512),
                       "r"(pack_bf16(o[8 * i], o[8 * i + 1])), "r"(pack_bf16(o[8 * i + 2], o[8 * i + 3])), "r"(pack_bf16(o[8 * i + 4], o[8 * i + 5])),
                       "r"(pack_bf16(o[8 * i + 6], o[8 * i + 7])), "r"(peer + OFF_RBAR + wg * 8) : "memory");
      } else if (p < 7) {
        const int k = p >> 1;
#pragma unroll
        for (int i = 0; i < 4; i++) {
#pragma unroll
          for (int c = 4 * i; c < 4 * i + 4; c++) pt[c] = bf2_add(pt[c], pack_bf16(o[2 * c], o[2 * c + 1]));
          asm("lop3.b32 %0, %0, 1, %1, 0xb8;" : "+r"(pt[4 * i]) : "r"(tag));
          st_b128(psend + (((sp + 1 + k) & 3) * 6 + k) * 1024 + i * 32, pt[4 * i], pt[4 * i + 1], pt[4 * i + 2], pt[4 * i + 3]);
        }
        __syncwarp();
        credit();
        if (p == 5) recv_issue(r0, 1);
      }
      if (p == 2) {
#pragma unroll
        for (int h = 0; h < 2; h++) { fs[h] = __fdividef(2.f, 4.f + bf_lo(lds_h(sb + OFF_GS + (wg * 64 + w * 16 + gr + 8 * h) * 2))); pin(fs[h]); }
      }
    }
    {
      const uint32_t tb = sb + OFF_X + stage_off(0) + warp * 4096;
      const uint32_t ta = tb + gr * 256 + ((gr & 3) << 5) + q * 8;
      const uint32_t la = tb + (lane >> 3) * 256 + (((lane & 7) << 4) ^ ((lane >> 3) << 5));
      float* op = out + (size_t)(m * 128 + wg * 64 + (lane >> 4) * 16 + w * 4 + ((lane >> 3) & 1)) * DM + s * 64 + (lane & 7) * 4;
#pragma unroll
      for (int qt = 0; qt < 4; qt++) {
        const int h = qt & 1, ch = qt >> 1;
#pragma unroll
        for (int j = 0; j < 4; j++) {
          const int i = ch * 8 + j * 2 + h;
          sts_f2((ta ^ (j << 5)) + h * 2048 + ch * 128, (fin[2 * i] + bf_lo(sum[i])) * fs[h], (fin[2 * i + 1] + bf_hi(sum[i])) * fs[h]);
        }
        __syncwarp();
#pragma unroll
        for (int r = 0; r < 2; r++)
          *reinterpret_cast<uint4*>(op + (r * 32 + h * 2) * DM + ch * 32) = lds_u4(la + (h * 2 + r) * 1024 + ch * 128);
      }
      sts_u(sb + OFF_EPOCH + 4, ck);
      if (warp == 4 && lane == 0) g_epoch[b] = tag;
    }
  } else {
    const int lane = __shfl_sync(0xffffffffu, lane0, lane0);
    asm volatile("setmaxnreg.dec.sync.aligned.u32 56;");
    int wsel = warp;
    asm("" : "+r"(wsel));
    if (wsel > 8) {
      const uint4* gwp = reinterpret_cast<const uint4*>(gate_w) + (lane & 7);
      uint4 gw[4];
      if (warp != 11) {
        const int t = (warp - 9) * 32 + lane;
        unsigned par;
        asm volatile("ld.relaxed.gpu.global.u32 %0, [%1];" : "=r"(par) : "l"(g_epoch + b) : "memory");
        const float pr = bf_ld(lam_re + s * 64 + t), pi = bf_ld(lam_im + s * 64 + t), pd = bf_ld(log_dt + s * 64 + t);
#pragma unroll
        for (int i = 0; i < 4; i++) gw[i] = __ldg(gwp + i * 8);
        cluster_wait();
        par = __shfl_sync(0xffffffffu, (par + 1) & 1, 0);
        cplx l64 = make_lam(pr, pi, pd);
        {
          const float inv = __fdividef(1.f, fmaf(pr, pr, pi * pi));
          const cplx cf = cmul(cplx{l64.re - 1.f, l64.im}, cplx{pr * inv, -pi * inv});
          sts_f4(sb + OFF_LC + t * 16, l64.re, l64.im, cf.re, cf.im);
          mbar_arrive(sb + OFF_LBAR);
        }
#pragma unroll
        for (int i = 0; i < 6; i++) l64 = cmul(l64, l64);
        cplx l128 = cmul(l64, l64);
        pin(l128.re); pin(l128.im);
        gate_rows<1>(sb, lane, xrot, s * 16 + (warp - 9) * 4, gw, gwp, g_gate + m * 128, par);
        uint32_t vr[15], vi[15];
#pragma unroll
        for (int i = 0; i < 15; i++) { vr[i] = par; vi[i] = 0; pin(vr[i]); pin(vi[i]); }
        mbar_wait(sb + OFF_GBAR, 0);
        const float2 e0 = lds_f2(sb + OFF_CARRY + t * 8), e1 = lds_f2(sb + OFF_CARRY + 512 + t * 8);
        float2* eb = g_end + s * 1024 + t;
        {
          const cplx e = cfma(l64, cplx{e0.x, e0.y}, cplx{e1.x, e1.y});
          const unsigned long long v = ((unsigned long long)__float_as_uint(e.im) << 32) | ((__float_as_uint(e.re) & ~1u) | par);
          asm volatile("st.relaxed.gpu.global.b64 [%0], %1;" ::"l"(eb + m * 64), "l"(v) : "memory");
        }
        __nanosleep(400);
        const float2* e15 = eb + (m - 15) * 64;
        int tries = 0;
        bool bad;
#pragma unroll 1
        do {
#pragma unroll
          for (int i = 0; i < 15; i++)
            asm volatile("{.reg .pred p; .reg .b64 v; mov.b64 v, {%0,%1}; setp.ge.s32 p, %3, %4; @p ld.relaxed.gpu.global.b64 v, [%2]; mov.b64 {%0,%1}, v;}"
                         : "+r"(vr[i]), "+r"(vi[i]) : "l"(e15 + i * 64), "r"(m), "r"(15 - i) : "memory");
          uint32_t x = vr[0] ^ par;
#pragma unroll
          for (int i = 1; i < 15; i++) asm("lop3.b32 %0, %0, %1, %2, 0xf6;" : "+r"(x) : "r"(vr[i]), "r"(par));
          bad = __any_sync(0xffffffffu, x & 1);
        } while (bad && ++tries < 200000);
        cplx S = {__uint_as_float(vr[0] ^ par), __uint_as_float(vi[0])};
#pragma unroll
        for (int i = 1; i < 15; i++) S = cfma(l128, S, cplx{__uint_as_float(vr[i] ^ par), __uint_as_float(vi[i])});
        const cplx S1 = cfma(l64, S, cplx{e0.x, e0.y});
        sts_f2(sb + OFF_CARRY + t * 8, S.re, S.im);
        sts_f2(sb + OFF_CARRY + 512 + t * 8, S1.re, S1.im);
        mbar_arrive(sb + OFF_CBAR);
        mbar_wait(sb + OFF_CBAR, 0);
        const int gr = lane >> 2, q = lane & 3;
        float2 db[8];
#pragma unroll
        for (int j = 0; j < 8; j++) db[j] = lds_f2(sb + OFF_DB + j * 32 + q * 8);
        mbar_wait(sb + OFF_XFULL + 16, 1);
        mbar_wait(sb + OFF_EMPTY, 0);
#pragma unroll 1
        for (int cw = warp - 9; cw < 8; cw += 2) {
          const float r0 = 0.5f * bf_lo(lds_h(sb + OFF_GS + (cw * 16 + gr) * 2)), r1 = 0.5f * bf_lo(lds_h(sb + OFF_GS + (cw * 16 + gr) * 2 + 16));
          const uint32_t xa = sb + OFF_X + (1 + rank) * 16384 + (cw * 16 + (lane & 15)) * 128 + (((lane >> 4) ^ (lane & 7)) << 4);
          uint32_t xv[16];
#pragma unroll
          for (int i = 0; i < 4; i++)
            asm volatile("ldmatrix.sync.aligned.m8n8.x4.shared.b16 {%0,%1,%2,%3}, [%4];" : "=r"(xv[4 * i]), "=r"(xv[4 * i + 1]), "=r"(xv[4 * i + 2]), "=r"(xv[4 * i + 3])
                         : "r"(xa ^ (i << 5)) : "memory");
          __syncwarp();
#pragma unroll
          for (int j = 0; j < 8; j++) {
            const uint32_t x0 = bf2_mul(xv[2 * j], __float_as_uint(db[j].x)), x1 = bf2_mul(xv[2 * j + 1], __float_as_uint(db[j].x));
            pin(db[j].y);
            const float bl = bf_lo(__float_as_uint(db[j].y)), bh = bf_hi(__float_as_uint(db[j].y));
            sts_f4(sb + OFF_X + 16384 + (j >> 2) * 16384 + cw * 2048 + (j & 3) * 512 + lane * 16, fmaf(bf_lo(x0), r0, bl), fmaf(bf_hi(x0), r0, bh),
                   fmaf(bf_lo(x1), r1, bl), fmaf(bf_hi(x1), r1, bh));
          }
        }
        mbar_arrive(sb + OFF_LBAR);
      } else {
#pragma unroll
        for (int i = 0; i < 4; i++) gw[i] = __ldg(gwp + i * 8);
        unsigned par;
        asm volatile("ld.relaxed.gpu.global.u32 %0, [%1];" : "=r"(par) : "l"(g_epoch + b) : "memory");
        const uint32_t dk = __ldg(reinterpret_cast<const uint32_t*>(dskip + s * 64) + lane), bb = __ldg(reinterpret_cast<const uint32_t*>(b2 + s * 64) + lane);
        cluster_wait();
        if (lane == 0) sts_u(sb + OFF_EPOCH, par + 1);
        par = (par + 1) & 1;
        gate_rows<2>(sb, lane, xrot, s * 16 + 8, gw, gwp, g_gate + m * 128, par);
        mbar_wait(sb + OFF_GBAR, 0);
        sts_u2(sb + OFF_DB + lane * 8, dk, bf2_add(bb, bb));
        uint32_t g0, g1, g2, g3;
        int tries = 0;
#pragma unroll 1
        do {
          asm volatile("ld.relaxed.gpu.global.v4.u32 {%0,%1,%2,%3}, [%4];" : "=r"(g0), "=r"(g1), "=r"(g2), "=r"(g3) : "l"(g_gate + m * 128 + lane * 4) : "memory");
          g0 ^= par; g1 ^= par; g2 ^= par; g3 ^= par;
        } while (((g0 | g1 | g2 | g3) & 1) && ++tries < 200000);
        const uint32_t p01 = pack_bf16(__uint_as_float(g0), __uint_as_float(g1)), p23 = pack_bf16(__uint_as_float(g2), __uint_as_float(g3));
        sts_u2(sb + OFF_GS + lane * 8, p01, p23);
        const uint32_t gt = sb + OFF_GT + (lane >> 4) * 128 + (lane & 1) * 64 + ((lane >> 1) & 7) * 4;
        sts_u(gt, p01);
        sts_u(gt + 32, p23);
        mbar_arrive(sb + OFF_CBAR);
      }
    } else {
      cluster_wait();
      if (elect_one()) {
        const uint32_t t0 = clock();
#pragma unroll 1
        for (int u = 1; u < 8; u++) {
          while ((uint32_t)clock() - t0 < 200 + (u - 1) * 480) {}
          const uint32_t fb = sb + OFF_XFULL + 8 * u;
          mbar_expect_tx(fb, 32768);
          tma5d_mc(sb + OFF_X + ((u + xrot) & 7) * 16384 + rank * 8192, &maps.x, u * 64, 2 * m + rank, fb);
          const int sl = u < 6 ? u : u - 6;
          if (u >= 6) mbar_wait(sb + OFF_EMPTY + 8 * sl, 0);
          tma2d(sb + OFF_RING + sl * 16384, &maps.bre, u * 64, s * 64, fb);
          tma2d(sb + OFF_RING + sl * 16384 + 8192, &maps.bim, u * 64, s * 64, fb);
          if (u == 2) map_prefetch(&maps.w1b);
        }
        int slot = 2; uint32_t ph = 0;
#pragma unroll 1
        for (int u = 8; u < 24; u++) {
          const uint32_t fb = sb + OFF_FULL + 8 * slot, dst = sb + OFF_RING + slot * 16384;
          mbar_wait(sb + OFF_EMPTY + 8 * slot, ph);
          if (u < 16) {
            mbar_expect_tx(fb, 12288);
            tma3d(dst, &maps.w1b, 0, (u - 8) * 64, s * 7, fb);
            if (u < 12) map_prefetch(&maps.w1a + (u - 8));
          } else {
            mbar_expect_tx(fb, 16384);
            tma2d(dst, &maps.w1a, s * 224 + 96, ((u - xrot) & 7) * 64, fb);
            tma2d(dst + 8192, &maps.w1a, s * 224 + 160, ((u - xrot) & 7) * 64, fb);
          }
          if (++slot == NSLOT) { slot = 0; ph ^= 1; }
        }
#pragma unroll 1
        for (int j = 0; j < 3; j++) {
          const uint32_t fb = sb + OFF_FULL + 8 * j, dst = sb + OFF_X + stage_off(0);
          const int c = ((sp + 1) & 3) * 128 + ((rank ^ 1) << 6);
          mbar_wait(sb + OFF_EMPTY + 8 + 8 * j, 1);
          mbar_expect_tx(fb, j == 1 ? 16384 : 14336);
          if (j == 1) {
            tma2d(dst + 14336, &maps.cre, s * 64, c, fb);
            tma2d(dst + 22528, &maps.cim, s * 64, c, fb);
          } else {
            tma2d(dst + j * 15360, &maps.w2, c, s * 224 + j * 56, fb);
          }
        }
#pragma unroll 1
        for (int p = 1; p < 8; p++) {
          const int c = ((sp + 1 + (p >> 1)) & 3) * 128 + (((rank ^ p ^ 1) & 1) << 6);
          const uint32_t fb = sb + OFF_XFULL + 8 * p, dst = sb + OFF_X + stage_off(p);
          if (p == 2 || p > 3) mbar_wait(sb + OFF_EMPTY + (p == 2 ? 40 : (p - 4) * 8), p == 2);
          mbar_expect_tx(fb, 45056);
          tma2d(dst, &maps.w2, c, s * 224, fb);
          tma2d(dst + 14336, &maps.cre, s * 64, c, fb);
          tma2d(dst + 22528, &maps.cim, s * 64, c, fb);
          tma2d(dst + 30720, &maps.w2, c, s * 224 + 112, fb);
        }
      }
    }
  }
}

typedef CUresult (*EncFn)(CUtensorMap*, CUtensorMapDataType, cuuint32_t, void*, const cuuint64_t*, const cuuint64_t*, const cuuint32_t*,
                          const cuuint32_t*, CUtensorMapInterleave, CUtensorMapSwizzle, CUtensorMapL2promotion, CUtensorMapFloatOOBfill);

void encode(EncFn f, CUtensorMap* mp, const void* p, int rank, const cuuint64_t* dims, const cuuint64_t* strides, const cuuint32_t* box, CUtensorMapSwizzle sw) {
  cuuint32_t es[5] = {1, 1, 1, 1, 1};
  f(mp, CU_TENSOR_MAP_DATA_TYPE_BFLOAT16, rank, const_cast<void*>(p), dims, strides, box, es, CU_TENSOR_MAP_INTERLEAVE_NONE, sw,
    CU_TENSOR_MAP_L2_PROMOTION_L2_128B, CU_TENSOR_MAP_FLOAT_OOB_FILL_NONE);
}

}

extern "C" void kernel_launch(void* const* d_in, const int* in_sizes, int n_in, void* d_out, int out_size) {
  typedef const __nv_bfloat16* bp;
  bp x = (bp)d_in[0], lre = (bp)d_in[1], lim = (bp)d_in[2], bre = (bp)d_in[3], bim = (bp)d_in[4], cre = (bp)d_in[5], cim = (bp)d_in[6],
     ldt = (bp)d_in[7], dsk = (bp)d_in[8], w1 = (bp)d_in[10], b1 = (bp)d_in[11], w2 = (bp)d_in[12], b2 = (bp)d_in[13], gw = (bp)d_in[14];
  static EncFn enc = nullptr;
  if (!enc) {
    void* f = nullptr;
    cudaDriverEntryPointQueryResult qr;
    cudaGetDriverEntryPoint("cuTensorMapEncodeTiled", &f, cudaEnableDefault, &qr);
    enc = (EncFn)f;
    cudaFuncSetAttribute(fused_kernel, cudaFuncAttributeMaxDynamicSharedMemorySize, SMEM_BYTES);
  }
  Maps maps;
  {
    cuuint64_t d[5] = {DM, 2, 4, 8, SEQ / 64}, st[4] = {DM * 2, 16 * DM * 2, 2 * DM * 2, 64 * DM * 2};
    cuuint32_t bx[5] = {64, 2, 4, 8, 1};
    encode(enc, &maps.x, x, 5, d, st, bx, CU_TENSOR_MAP_SWIZZLE_128B);
  }
  {
    cuuint64_t d[2] = {DM, DM}, st[1] = {DM * 2};
    cuuint32_t bx[2] = {64, 64};
    encode(enc, &maps.bre, bre, 2, d, st, bx, CU_TENSOR_MAP_SWIZZLE_128B);
    encode(enc, &maps.bim, bim, 2, d, st, bx, CU_TENSOR_MAP_SWIZZLE_128B);
    encode(enc, &maps.cre, cre, 2, d, st, bx, CU_TENSOR_MAP_SWIZZLE_128B);
    encode(enc, &maps.cim, cim, 2, d, st, bx, CU_TENSOR_MAP_SWIZZLE_128B);
  }
  {
    cuuint64_t d[2] = {FF, DM}, st[1] = {FF * 2};
    cuuint32_t bx[2] = {64, 64};
    encode(enc, &maps.w1a, w1, 2, d, st, bx, CU_TENSOR_MAP_SWIZZLE_128B);
    cuuint64_t d3[3] = {32, DM, FF / 32}, st3[2] = {FF * 2, 64};
    cuuint32_t bx3[3] = {32, 64, 3};
    encode(enc, &maps.w1b, w1, 3, d3, st3, bx3, CU_TENSOR_MAP_SWIZZLE_64B);
  }
  {
    cuuint64_t d[2] = {DM, FF}, st[1] = {DM * 2};
    cuuint32_t bx[2] = {64, 112};
    encode(enc, &maps.w2, w2, 2, d, st, bx, CU_TENSOR_MAP_SWIZZLE_128B);
  }
  fused_kernel<<<128, 384, SMEM_BYTES>>>(lre, lim, ldt, dsk, b1, b2, gw, (float*)d_out, maps);
}
```

```cpp
#include <cuda_runtime.h>
#include <cuda_bf16.h>
#include <cuda.h>
#include <stdint.h>

#define MAP 1
#define D0 200
#define D1 480
#define PF 4
#define PFK 5
#define GELUP 1
#define EW 2
#define K1E 1
#define K2E 0
#define QS 1
#define K2G 4
#define FINP 5
#define LBD 400
#define PFS 32
#define SB0 2
#define PFD 2
#define HOLD 0
#define GAP 0
#define FINW 0
#define K0P 41
#define K1P 53
#define TMP2 1
#define W0 1
#define LCK 4
#define TOKA 0
#define TOKB 2
#define TOKD 0
#define TKT 999
#define AV 4
#define QK 4
#define TCUT {1, 6, 6, 11, 16}
#define SCUT {0, 0, 0, 0, 0, 8, 8, 16, 24}
#define PV 2
#define KCUT {4, 8, 12, 15, 18}
#define GCUT {6, 12, 18, 24}
#define OPQ 1
#define OPS 0
#define FF1 1
#define Q1 0
#define QF 1
#define PA 99
#define PB 99
#define PC 99
#define NOH 0
#define OPH 1
#define REL 0
#define EP 0
#define FP 1
#define L16K 2
#define B0K 2
#define B1K 3
#define B2K 4
#define B3K 8
#define ADP 0
#define BB 0
#define DV 0
#define DCUT {3, 5, 8, 10, 13, 15, 17, 19}
#define E1L 0
#define A0 0
#define LW4 1
#define TP 9
#define TW 0

namespace {

constexpr int SEQ = 2048, DM = 512, FF = 1792;
constexpr int NSLOT = 6;
constexpr uint32_t OFF_X = 0, OFF_RING = 131072, OFF_MISC = 229376;
constexpr uint32_t OFF_XFULL = OFF_MISC, OFF_FULL = OFF_XFULL + 64, OFF_RBAR = OFF_FULL + 48, OFF_EMPTY = OFF_RBAR + 16, OFF_KBAR = OFF_EMPTY + 48,
                   OFF_GBAR = OFF_KBAR + 16, OFF_LBAR = OFF_GBAR + 8, OFF_CBAR = OFF_LBAR + 8, OFF_EPOCH = OFF_CBAR + 8;
constexpr uint32_t OFF_LC = OFF_MISC + 256;
constexpr uint32_t OFF_GS = OFF_LC;
constexpr uint32_t OFF_GT = OFF_LC + 256;
constexpr uint32_t OFF_DB = OFF_LC + 512;
constexpr uint32_t OFF_CARRY = OFF_LC + 1024;
constexpr uint32_t OFF_DBG = OFF_CARRY + 1024;
constexpr uint32_t SMEM_BYTES = OFF_DBG + 768;
static_assert(SMEM_BYTES <= 232448, "smem");

struct Maps { CUtensorMap x, bre, bim, w1b, w1a, w2, cre, cim; };
__host__ __device__ constexpr uint32_t stage_off(int p) { return 49152 + 45056 * (((p >> 1) & 1) + 2 * (p & 1)); }

__host__ __device__ constexpr uint32_t full_par(int u) { return ((u - 8) / 6 + (FP != 3 && u % 6 == 0)) & 1; }

__device__ uint4 g_part[16 * 8 * 3 * 1024];
__device__ float2 g_end[8 * 16 * 64];
__device__ unsigned g_gate[SEQ];
__device__ unsigned g_epoch[128];
#define TG(role) do {} while (0)
#define TS2(role, i) do {} while (0)
#define TS(role, i) do {} while (0)
#define TDUMP() do {} while (0)
#define TR(i) do {} while (0)
#define TK(i) do {} while (0)
#define TRD() do {} while (0)

__device__ __forceinline__ void mbar_init(uint32_t bar, uint32_t cnt) { asm volatile("mbarrier.init.shared::cta.b64 [%0], %1;" ::"r"(bar), "r"(cnt)); }
__device__ __forceinline__ void mbar_expect_tx(uint32_t bar, uint32_t bytes) { asm volatile("mbarrier.arrive.expect_tx.shared::cta.b64 _, [%0], %1;" ::"r"(bar), "r"(bytes) : "memory"); }
__device__ __forceinline__ void mbar_arrive(uint32_t bar) { asm volatile("mbarrier.arrive.shared::cta.b64 _, [%0];" ::"r"(bar) : "memory"); }
__device__ __forceinline__ void mbar_arrive_cl(uint32_t cbar) { asm volatile("mbarrier.arrive.shared::cluster.b64 _, [%0];" ::"r"(cbar) : "memory"); }
__device__ __forceinline__ void mbar_wait(uint32_t bar, uint32_t parity) {
  asm volatile(
      "{\n.reg .pred p;\n.reg .u32 c;\n"
      "mbarrier.try_wait.parity.shared::cta.b64 p, [%0], %1;\n"
      "@p bra.uni LAB_DONE;\n"
      "mov.u32 c, 0;\n"
      "LAB_WAIT:\n"
      "mbarrier.try_wait.parity.shared::cta.b64 p, [%0], %1;\n"
      "@p bra.uni LAB_DONE;\n"
      "add.u32 c, c, 1;\nsetp.lt.u32 p, c, 200000;\n@p bra.uni LAB_WAIT;\n"
      "LAB_DONE:\n}" ::"r"(bar), "r"(parity) : "memory");
}
__device__ __forceinline__ void tma2d(uint32_t dst, const CUtensorMap* m, int c0, int c1, uint32_t bar) {
  asm volatile("cp.async.bulk.tensor.2d.shared::cluster.global.mbarrier::complete_tx::bytes [%0], [%1, {%3,%4}], [%2];"
               ::"r"(dst), "l"(m), "r"(bar), "r"(c0), "r"(c1) : "memory");
}
__device__ __forceinline__ void tma3d(uint32_t dst, const CUtensorMap* m, int c0, int c1, int c2, uint32_t bar) {
  asm volatile("cp.async.bulk.tensor.3d.shared::cluster.global.mbarrier::complete_tx::bytes [%0], [%1, {%3,%4,%5}], [%2];"
               ::"r"(dst), "l"(m), "r"(bar), "r"(c0), "r"(c1), "r"(c2) : "memory");
}
__device__ __forceinline__ void tma5d(uint32_t dst, const CUtensorMap* m, int c0, int c4, uint32_t bar) {
  asm volatile("cp.async.bulk.tensor.5d.shared::cluster.global.mbarrier::complete_tx::bytes [%0], [%1, {%3,%5,%5,%5,%4}], [%2];"
               ::"r"(dst), "l"(m), "r"(bar), "r"(c0), "r"(c4), "r"(0) : "memory");
}
__device__ __forceinline__ void tma5d_mc(uint32_t dst, const CUtensorMap* m, int c0, int c4, uint32_t bar) {
  asm volatile("cp.async.bulk.tensor.5d.shared::cluster.global.mbarrier::complete_tx::bytes.multicast::cluster [%0], [%1, {%3,%5,%5,%5,%4}], [%2], %6;"
               ::"r"(dst), "l"(m), "r"(bar), "r"(c0), "r"(c4), "r"(0), "h"((uint16_t)3) : "memory");
}
__device__ __forceinline__ void l2_prefetch(const void* p, uint32_t bytes) { asm volatile("cp.async.bulk.prefetch.L2.global [%0], %1;" ::"l"(p), "r"(bytes) : "memory"); }
__device__ __forceinline__ bool elect_one() {
  uint32_t pred;
  asm volatile("{.reg .pred P; elect.sync _|P, 0xffffffff; selp.u32 %0, 1, 0, P;}" : "=r"(pred));
  return pred != 0;
}
__device__ __forceinline__ void wg_fence() { asm volatile("wgmma.fence.sync.aligned;" ::: "memory"); }
__device__ __forceinline__ void wg_commit() { asm volatile("wgmma.commit_group.sync.aligned;" ::: "memory"); }
template <int N> __device__ __forceinline__ void wg_wait() { asm volatile("wgmma.wait_group.sync.aligned %0;" ::"n"(N) : "memory"); }
__device__ __forceinline__ void pin(float& a) { asm volatile("" : "+f"(a)::"memory"); }
__device__ __forceinline__ void pin(uint32_t& a) { asm volatile("" : "+r"(a)::"memory"); }
template <int N> __device__ __forceinline__ void reg_fence(float (&d)[N]) {
#pragma unroll
  for (int i = 0; i < N; i++) pin(d[i]);
}
__device__ __forceinline__ void bar_sync(int id, int n) { asm volatile("bar.sync %0, %1;" ::"r"(id), "r"(n) : "memory"); }
__device__ __forceinline__ void bar_arrive(int id, int n) { asm volatile("bar.arrive %0, %1;" ::"r"(id), "r"(n) : "memory"); }
constexpr uint32_t DH128 = (1024 >> 4) | (1u << 30), DH64 = (512 >> 4) | (2u << 30);
__host__ __device__ constexpr uint32_t lbo(uint32_t bytes) { return (bytes >> 4) << 20; }
__device__ __forceinline__ uint32_t pack_bf16(float lo, float hi) { uint32_t r; asm("cvt.rn.bf16x2.f32 %0, %1, %2;" : "=r"(r) : "f"(hi), "f"(lo)); return r; }
__device__ __forceinline__ float bf_lo(uint32_t v) { return __uint_as_float(v << 16); }
__device__ __forceinline__ float bf_hi(uint32_t v) { return __uint_as_float(v & 0xffff0000u); }
__device__ __forceinline__ float bf_ld(const __nv_bfloat16* p) { return __bfloat162float(__ldg(p)); }
__device__ __forceinline__ uint32_t late16(uint32_t bar) {
  uint32_t r;
  asm volatile("{.reg .pred p; mbarrier.test_wait.parity.shared::cta.b64 p, [%1], 0; selp.u32 %0, 16, 0, p;}" : "=r"(r) : "r"(bar) : "memory");
  return r;
}
__device__ __forceinline__ float2 lds_f2(uint32_t a) { float2 v; asm volatile("ld.shared.v2.f32 {%0,%1}, [%2];" : "=f"(v.x), "=f"(v.y) : "r"(a)); return v; }
__device__ __forceinline__ uint32_t lds_h(uint32_t a) { uint32_t v; asm volatile("ld.shared.u16 %0, [%1];" : "=r"(v) : "r"(a)); return v; }
__device__ __forceinline__ uint32_t lds_u(uint32_t a) { uint32_t v; asm volatile("ld.shared.u32 %0, [%1];" : "=r"(v) : "r"(a)); return v; }
__device__ __forceinline__ uint4 lds_u4(uint32_t a) { uint4 v; asm volatile("ld.shared.v4.u32 {%0,%1,%2,%3}, [%4];" : "=r"(v.x), "=r"(v.y), "=r"(v.z), "=r"(v.w) : "r"(a)); return v; }
__device__ __forceinline__ void st_b128(uint4* p, uint32_t a, uint32_t b, uint32_t c, uint32_t d) {
  asm volatile("st.relaxed.gpu.global.v4.b32 [%0], {%1,%2,%3,%4};" ::"l"(p), "r"(a), "r"(b), "r"(c), "r"(d) : "memory");
}
__device__ __forceinline__ void ld_b128(const uint4* p, uint32_t& a, uint32_t& b, uint32_t& c, uint32_t& d) {
  asm volatile("{.reg .b64 l, h; .reg .b128 v; ld.relaxed.gpu.global.b128 v, [%4]; mov.b128 {l,h}, v; mov.b64 {%0,%1}, l; mov.b64 {%2,%3}, h;}"
               : "=r"(a), "=r"(b), "=r"(c), "=r"(d) : "l"(p) : "memory");
}
__device__ __forceinline__ float tanh_fast(float x) { float y; asm("tanh.approx.f32 %0, %1;" : "=f"(y) : "f"(x)); return y; }
__device__ __forceinline__ float gelu2(float v) {
  float p = fmaf(v * v, 0.0356774081363f, 0.7978845608029f);
  return fmaf(v, tanh_fast(v * p), v);
}
__device__ __forceinline__ void sched_fence(uint32_t& ck) { asm volatile("{.reg .b32 c; mov.u32 c, %%clock; xor.b32 %0, %0, c;}" : "+r"(ck)::"memory"); }
__device__ __forceinline__ uint32_t bf2_mul(uint32_t a, uint32_t b) { uint32_t r; asm("mul.rn.bf16x2 %0, %1, %2;" : "=r"(r) : "r"(a), "r"(b)); return r; }
__device__ __forceinline__ uint32_t bf2_add(uint32_t a, uint32_t b) { uint32_t r; asm("add.rn.bf16x2 %0, %1, %2;" : "=r"(r) : "r"(a), "r"(b)); return r; }
__device__ __forceinline__ uint32_t bf2_fma(uint32_t a, uint32_t b, uint32_t c) { uint32_t r; asm("fma.rn.bf16x2 %0, %1, %2, %3;" : "=r"(r) : "r"(a), "r"(b), "r"(c)); return r; }
__device__ __forceinline__ uint32_t gelu2_pair(float a, float b) {
  const uint32_t v = pack_bf16(a, b);
  uint32_t t;
  asm("tanh.approx.bf16x2 %0, %1;" : "=r"(t) : "r"(bf2_fma(v, bf2_fma(bf2_mul(v, v), 0x3d123d12u, 0xbe4fbe4fu), v)));
  return bf2_fma(v, t, v);
}
struct cplx { float re, im; };
__device__ __forceinline__ cplx cmul(cplx a, cplx b) { return {fmaf(a.re, b.re, -a.im * b.im), fmaf(a.re, b.im, a.im * b.re)}; }
__device__ __forceinline__ cplx cfma(cplx a, cplx b, cplx c) {
  return {fmaf(a.re, b.re, fmaf(-a.im, b.im, c.re)), fmaf(a.re, b.im, fmaf(a.im, b.re, c.im))};
}
__device__ __forceinline__ cplx make_lam(float lre, float lim, float ldt) {
  float dt = __bfloat162float(__float2bfloat16_rn(expf(ldt)));
  float mag = expf(dt * lre), sn, cs;
  sincospif(dt * lim * 0.31830988618379067f, &sn, &cs);
  return {mag * cs, mag * sn};
}

template <int NG>
__device__ __forceinline__ void gate_rows(uint32_t sb, int lane, int xrot, int row0, uint4 (&gw)[4], const uint4* gwp, unsigned* dst, unsigned par) {
  const int row = row0 + (lane >> 3);
  const uint32_t xr0 = sb + OFF_X + row * 128 + (((lane & 7) ^ (row & 7)) << 4), xr1 = (xr0 + 512) ^ 64;
  float z[NG], y[NG];
#pragma unroll
  for (int r = 0; r < NG; r++) z[r] = y[r] = 0.f;
#pragma unroll
  for (int kb = 0; kb < 8; kb++) {
    const uint4 w = gw[kb & 3];
    if (kb < 4) gw[kb] = __ldg(gwp + (kb + 4) * 8);
    mbar_wait(sb + OFF_XFULL + 8 * kb, 0);
#pragma unroll
    for (int r = 0; r < NG; r++) {
      const uint4 a = lds_u4((r ? xr1 : xr0) + ((kb + xrot) & 7) * 16384);
      const uint32_t p[4] = {bf2_mul(a.x, w.x), bf2_mul(a.y, w.y), bf2_mul(a.z, w.z), bf2_mul(a.w, w.w)};
#pragma unroll
      for (int c = 0; c < 4; c++) { z[r] += bf_lo(p[c]); y[r] += bf_hi(p[c]); }
    }
  }
  float zz = z[0] + y[0];
  if (NG == 2) {
    const float z1 = z[NG - 1] + y[NG - 1];
    zz = ((lane & 4) ? z1 : zz) + __shfl_xor_sync(0xffffffffu, (lane & 4) ? zz : z1, 4);
  } else {
    zz += __shfl_xor_sync(0xffffffffu, zz, 4);
  }
  zz += __shfl_xor_sync(0xffffffffu, zz, 2);
  zz += __shfl_xor_sync(0xffffffffu, zz, 1);
  zz = bf_lo(pack_bf16(zz, 0.f));
  const float rho = 4.f * expf(zz > 40.f ? 40.f : zz);
  if ((lane & (NG == 2 ? 3 : 7)) == 0)
    asm volatile("st.relaxed.gpu.global.u32 [%0], %1;" ::"l"(dst + row + (lane & 4)), "r"((__float_as_uint(rho) & ~1u) | par) : "memory");
}

template<int TA,int TB,uint32_t AH,uint32_t BH> __device__ __forceinline__ void wgmma_n64_ss(float (&d)[32], uint32_t al, uint32_t ao, uint32_t bl, uint32_t bo, int scale_d){
  asm volatile("{.reg .pred p; .reg .b32 t, v; .reg .b64 da, db; setp.ne.b32 p, %36, 0; add.u32 t, %32, %33; mov.b64 da, {t, %39}; add.u32 v, %34, %35; mov.b64 db, {v, %40};\n"
   "wgmma.mma_async.sync.aligned.m64n64k16.f32.bf16.bf16 {%0,%1,%2,%3,%4,%5,%6,%7,%8,%9,%10,%11,%12,%13,%14,%15,%16,%17,%18,%19,%20,%21,%22,%23,%24,%25,%26,%27,%28,%29,%30,%31}, da, db, p, 1, 1, %37, %38;}"
   : "+f"(d[0]),"+f"(d[1]),"+f"(d[2]),"+f"(d[3]),"+f"(d[4]),"+f"(d[5]),"+f"(d[6]),"+f"(d[7]),"+f"(d[8]),"+f"(d[9]),"+f"(d[10]),"+f"(d[11]),"+f"(d[12]),"+f"(d[13]),"+f"(d[14]),"+f"(d[15]),"+f"(d[16]),"+f"(d[17]),"+f"(d[18]),"+f"(d[19]),"+f"(d[20]),"+f"(d[21]),"+f"(d[22]),"+f"(d[23]),"+f"(d[24]),"+f"(d[25]),"+f"(d[26]),"+f"(d[27]),"+f"(d[28]),"+f"(d[29]),"+f"(d[30]),"+f"(d[31])
   : "r"(al),"r"(ao >> 4),"r"(bl),"r"(bo >> 4),"r"(scale_d),"n"(TA),"n"(TB),"n"(AH),"n"(BH));
}
template<int TB,uint32_t BH,int SA=1> __device__ __forceinline__ void wgmma_n64_rs(float (&d)[32], uint32_t a0,uint32_t a1,uint32_t a2,uint32_t a3, uint32_t bl, uint32_t bo, int scale_d){
  asm volatile("{.reg .pred p; .reg .b32 t; .reg .b64 db; setp.ne.b32 p, %38, 0; add.u32 t, %36, %37; mov.b64 db, {t, %40};\n"
   "wgmma.mma_async.sync.aligned.m64n64k16.f32.bf16.bf16 {%0,%1,%2,%3,%4,%5,%6,%7,%8,%9,%10,%11,%12,%13,%14,%15,%16,%17,%18,%19,%20,%21,%22,%23,%24,%25,%26,%27,%28,%29,%30,%31}, {%32,%33,%34,%35}, db, p, %41, 1, %39;}"
   : "+f"(d[0]),"+f"(d[1]),"+f"(d[2]),"+f"(d[3]),"+f"(d[4]),"+f"(d[5]),"+f"(d[6]),"+f"(d[7]),"+f"(d[8]),"+f"(d[9]),"+f"(d[10]),"+f"(d[11]),"+f"(d[12]),"+f"(d[13]),"+f"(d[14]),"+f"(d[15]),"+f"(d[16]),"+f"(d[17]),"+f"(d[18]),"+f"(d[19]),"+f"(d[20]),"+f"(d[21]),"+f"(d[22]),"+f"(d[23]),"+f"(d[24]),"+f"(d[25]),"+f"(d[26]),"+f"(d[27]),"+f"(d[28]),"+f"(d[29]),"+f"(d[30]),"+f"(d[31])
   : "r"(a0),"r"(a1),"r"(a2),"r"(a3),"r"(bl),"r"(bo >> 4),"r"(scale_d),"n"(TB),"n"(BH),"n"(SA));
}
template<int TA,int TB,uint32_t AH,uint32_t BH> __device__ __forceinline__ void wgmma_n96_ss(float (&d)[48], uint32_t al, uint32_t ao, uint32_t bl, uint32_t bo, int scale_d){
  asm volatile("{.reg .pred p; .reg .b32 t, v; .reg .b64 da, db; setp.ne.b32 p, %52, 0; add.u32 t, %48, %49; mov.b64 da, {t, %55}; add.u32 v, %50, %51; mov.b64 db, {v, %56};\n"
   "wgmma.mma_async.sync.aligned.m64n96k16.f32.bf16.bf16 {%0,%1,%2,%3,%4,%5,%6,%7,%8,%9,%10,%11,%12,%13,%14,%15,%16,%17,%18,%19,%20,%21,%22,%23,%24,%25,%26,%27,%28,%29,%30,%31,%32,%33,%34,%35,%36,%37,%38,%39,%40,%41,%42,%43,%44,%45,%46,%47}, da, db, p, 1, 1, %53, %54;}"
   : "+f"(d[0]),"+f"(d[1]),"+f"(d[2]),"+f"(d[3]),"+f"(d[4]),"+f"(d[5]),"+f"(d[6]),"+f"(d[7]),"+f"(d[8]),"+f"(d[9]),"+f"(d[10]),"+f"(d[11]),"+f"(d[12]),"+f"(d[13]),"+f"(d[14]),"+f"(d[15]),"+f"(d[16]),"+f"(d[17]),"+f"(d[18]),"+f"(d[19]),"+f"(d[20]),"+f"(d[21]),"+f"(d[22]),"+f"(d[23]),"+f"(d[24]),"+f"(d[25]),"+f"(d[26]),"+f"(d[27]),"+f"(d[28]),"+f"(d[29]),"+f"(d[30]),"+f"(d[31]),"+f"(d[32]),"+f"(d[33]),"+f"(d[34]),"+f"(d[35]),"+f"(d[36]),"+f"(d[37]),"+f"(d[38]),"+f"(d[39]),"+f"(d[40]),"+f"(d[41]),"+f"(d[42]),"+f"(d[43]),"+f"(d[44]),"+f"(d[45]),"+f"(d[46]),"+f"(d[47])
   : "r"(al),"r"(ao >> 4),"r"(bl),"r"(bo >> 4),"r"(scale_d),"n"(TA),"n"(TB),"n"(AH),"n"(BH));
}
template<int TA,int TB,uint32_t AH,uint32_t BH> __device__ __forceinline__ void wgmma_n128_ss(float (&d)[64], uint32_t al, uint32_t ao, uint32_t bl, uint32_t bo, int scale_d){
  asm volatile("{.reg .pred p; .reg .b32 t, v; .reg .b64 da, db; setp.ne.b32 p, %68, 0; add.u32 t, %64, %65; mov.b64 da, {t, %71}; add.u32 v, %66, %67; mov.b64 db, {v, %72};\n"
   "wgmma.mma_async.sync.aligned.m64n128k16.f32.bf16.bf16 {%0,%1,%2,%3,%4,%5,%6,%7,%8,%9,%10,%11,%12,%13,%14,%15,%16,%17,%18,%19,%20,%21,%22,%23,%24,%25,%26,%27,%28,%29,%30,%31,%32,%33,%34,%35,%36,%37,%38,%39,%40,%41,%42,%43,%44,%45,%46,%47,%48,%49,%50,%51,%52,%53,%54,%55,%56,%57,%58,%59,%60,%61,%62,%63}, da, db, p, 1, 1, %69, %70;}"
   : "+f"(d[0]),"+f"(d[1]),"+f"(d[2]),"+f"(d[3]),"+f"(d[4]),"+f"(d[5]),"+f"(d[6]),"+f"(d[7]),"+f"(d[8]),"+f"(d[9]),"+f"(d[10]),"+f"(d[11]),"+f"(d[12]),"+f"(d[13]),"+f"(d[14]),"+f"(d[15]),"+f"(d[16]),"+f"(d[17]),"+f"(d[18]),"+f"(d[19]),"+f"(d[20]),"+f"(d[21]),"+f"(d[22]),"+f"(d[23]),"+f"(d[24]),"+f"(d[25]),"+f"(d[26]),"+f"(d[27]),"+f"(d[28]),"+f"(d[29]),"+f"(d[30]),"+f"(d[31]),"+f"(d[32]),"+f"(d[33]),"+f"(d[34]),"+f"(d[35]),"+f"(d[36]),"+f"(d[37]),"+f"(d[38]),"+f"(d[39]),"+f"(d[40]),"+f"(d[41]),"+f"(d[42]),"+f"(d[43]),"+f"(d[44]),"+f"(d[45]),"+f"(d[46]),"+f"(d[47]),"+f"(d[48]),"+f"(d[49]),"+f"(d[50]),"+f"(d[51]),"+f"(d[52]),"+f"(d[53]),"+f"(d[54]),"+f"(d[55]),"+f"(d[56]),"+f"(d[57]),"+f"(d[58]),"+f"(d[59]),"+f"(d[60]),"+f"(d[61]),"+f"(d[62]),"+f"(d[63])
   : "r"(al),"r"(ao >> 4),"r"(bl),"r"(bo >> 4),"r"(scale_d),"n"(TA),"n"(TB),"n"(AH),"n"(BH));
}

__global__ void __cluster_dims__(2, 1, 1) __launch_bounds__(384, 1)
fused_kernel(const __nv_bfloat16* __restrict__ lam_re, const __nv_bfloat16* __restrict__ lam_im, const __nv_bfloat16* __restrict__ log_dt,
             const __nv_bfloat16* __restrict__ dskip, const __nv_bfloat16* __restrict__ b1, const __nv_bfloat16* __restrict__ b2,
             const __nv_bfloat16* __restrict__ gate_w, const __nv_bfloat16* __restrict__ pf_w1, const __nv_bfloat16* __restrict__ pf_w2,
             const __nv_bfloat16* __restrict__ pf_cre, const __nv_bfloat16* __restrict__ pf_cim, float* __restrict__ out,
             const __grid_constant__ Maps maps) {
  extern __shared__ __align__(1024) unsigned char smem_raw[];
  uint32_t sb = (uint32_t)__cvta_generic_to_shared(smem_raw);
  if (EP == 1 && threadIdx.x == 352) {
    asm volatile("prefetch.tensormap [%0];" ::"l"(&maps.x) : "memory");
    asm volatile("prefetch.tensormap [%0];" ::"l"(&maps.bre) : "memory");
    asm volatile("prefetch.tensormap [%0];" ::"l"(&maps.bim) : "memory");
  }
  if (EP == 2 && elect_one()) {
    asm volatile("prefetch.tensormap [%0];" ::"l"(&maps.x) : "memory");
    asm volatile("prefetch.tensormap [%0];" ::"l"(&maps.bre) : "memory");
    asm volatile("prefetch.tensormap [%0];" ::"l"(&maps.bim) : "memory");
  }
  int tid_ = threadIdx.x;
  const int b = blockIdx.x;
  const int rank = b & 1, cl = b >> 1;
  const int sp = (cl & 1) | ((cl >> 2) & 2), m = ((cl >> 1) & 3) | ((cl >> 4) << 2);
  const int s = sp * 2 + rank;
  const int xrot = 9 - 2 * sp;
  if (FP == 1 ? threadIdx.x == 0 : (threadIdx.x < 32 && elect_one())) {
    mbar_init(sb + OFF_XFULL, 1);
    mbar_expect_tx(sb + OFF_XFULL, FP == 3 ? 32768 : 16384);
    tma5d(sb + OFF_X + (xrot & 7) * 16384, &maps.x, 0, 2 * m, sb + OFF_XFULL);
    if (FP == 3) tma2d(sb + OFF_RING, &maps.bre, 0, s * 64, sb + OFF_XFULL);
    tma5d(sb + OFF_X + (xrot & 7) * 16384 + 8192, &maps.x, 0, 2 * m + 1, sb + OFF_XFULL);
    if (FP == 3) tma2d(sb + OFF_RING + 8192, &maps.bim, 0, s * 64, sb + OFF_XFULL);
    TS(2, 3);
  }
  if (FP != 3 && (FP == 1 ? threadIdx.x == 128 : ((threadIdx.x >> 5) == 4 && elect_one()))) {
    mbar_init(sb + OFF_FULL, 1);
    mbar_expect_tx(sb + OFF_FULL, 16384);
    tma2d(sb + OFF_RING, &maps.bre, 0, s * 64, sb + OFF_FULL);
    tma2d(sb + OFF_RING + 8192, &maps.bim, 0, s * 64, sb + OFF_FULL);
    TS(2, 4);
  }
  const int warp = __shfl_sync(0xffffffffu, (int)(threadIdx.x >> 5), 0);
  const int lane0 = threadIdx.x & 31;

  if (elect_one()) {
    if (warp > 8) {
      if (EP == 0) asm volatile("prefetch.tensormap [%0];" ::"l"(&maps.x + (warp - 9)) : "memory");
      mbar_init(sb + OFF_GBAR + 8 * (warp - 9), warp < 11 ? 64 : 96);
    }
    const uint32_t c = warp < 8 ? 1 : warp < 11 ? 8 : 4, bar = sb + OFF_XFULL + 16 * warp;
    if (FP == 3 ? warp != 0 : (warp & 11) != 0) mbar_init(bar, c);
    mbar_init(bar + 8, c);
    asm volatile("fence.mbarrier_init.release.cluster;" ::: "memory");
  }
  __syncwarp();
  asm volatile("barrier.cluster.arrive.relaxed.aligned;" ::: "memory");

  if (warp < 8) {
    const int lane = OPQ ? __shfl_sync(0xffffffffu, lane0, lane0) : lane0;
    tid_ = warp * 32 + lane;
    if (OPS) sb = __shfl_sync(0xffffffffu, sb, 0);
    const int wg = warp >> 2, w = warp & 3, q = lane & 3, gr = lane >> 2;
    uint32_t bv[28];
#pragma unroll
    for (int j = 0; j < 28; j++) bv[j] = __ldg(reinterpret_cast<const uint32_t*>(b1 + s * 224 + j * 8) + q);
    asm volatile("setmaxnreg.inc.sync.aligned.u32 224;");
    asm volatile("barrier.cluster.wait.aligned;" ::: "memory");
    TS(wg, 0);
    auto release = [&](int slot) {
      if (REL) asm volatile("{.reg .pred P; elect.sync _|P, 0xffffffff; @P mbarrier.arrive.shared::cta.b64 _, [%0];}" ::"r"(sb + OFF_EMPTY + 8 * slot) : "memory");
      else if (lane == 0) mbar_arrive(sb + OFF_EMPTY + 8 * slot);
    };
    const uint32_t xw = sb + OFF_X + wg * 8192, fullb = sb + OFF_FULL;
    const uint32_t dxw = (xw & 0x3FFFF) >> 4, dring = ((sb + OFF_RING) & 0x3FFFF) >> 4;

    float ure[32], uim[32], aa[48], ab[64];
    cplx lam[2], coef[2], l16[2], l32[2], lq[2], pre[2], e[2];
    uint32_t sh16, mhi, ck = 0;

    auto bias = [&](int c) {
#pragma unroll
      for (int j = c * 7; j < c * 7 + 7; j++) {
        pin(bv[j]);
        float* d = j < 12 ? aa + 4 * j : ab + 4 * (j - 12);
        d[0] = d[2] = __uint_as_float(bv[j] << sh16); d[1] = d[3] = __uint_as_float(bv[j] & mhi);
        pin(d[0]); pin(d[1]); pin(d[2]); pin(d[3]);
      }
    };
#pragma unroll
    for (int kb = 0; kb < 8; kb++) {
      const int slot = kb % NSLOT;
      mbar_wait(sb + OFF_XFULL + 8 * kb, 0);
      if (kb == 0) TS(wg, 18);
      if (kb == 0 && FP != 3) mbar_wait(fullb, 0);
      TS2(2, kb);
      if (kb == 0) TS(wg, 1);
      if (kb == L16K) { sh16 = late16(sb + OFF_XFULL); mhi = 0xffffffffu << sh16; }
      if (kb == LCK) {
        mbar_wait(sb + OFF_LBAR, 0);
#pragma unroll
        for (int h = 0; h < 2; h++) {
          const uint4 v = lds_u4(sb + OFF_LC + (w * 16 + gr + 8 * h) * 16);
          lam[h] = cplx{__uint_as_float(v.x), __uint_as_float(v.y)};
          coef[h] = cplx{__uint_as_float(v.z), __uint_as_float(v.w)};
        }
      }
      wg_fence();
      const uint32_t dxa = dxw + ((kb + xrot) & 7) * 1024;
#pragma unroll
      for (int kk = 0; kk < 4; kk++) {
        wgmma_n64_ss<0, 0, DH128, DH128>(ure, dring, slot * 16384 + kk * 32, dxa, kk * 32, (kb | kk) != 0);
        wgmma_n64_ss<0, 0, DH128, DH128>(uim, dring, slot * 16384 + 8192 + kk * 32, dxa, kk * 32, (kb | kk) != 0);
      }
      wg_commit();
      if (kb > 0) { wg_wait<1>(); release((kb - 1) % NSLOT); }
      if (kb == B0K) bias(0);
      if (kb == B1K) bias(1);
      if (kb == B2K) bias(2);
      if (kb == B3K) bias(3);
      if (kb == 6) {
#pragma unroll
        for (int h = 0; h < 2; h++) {
          pin(lam[h].re); pin(lam[h].im);
          cplx t = cmul(lam[h], lam[h]); t = cmul(t, t); t = cmul(t, t);
          l16[h] = cmul(t, t);
          pin(l16[h].re); pin(l16[h].im);
        }
      }
      if (kb == 7) {
#pragma unroll
        for (int h = 0; h < 2; h++) {
          pin(l16[h].re); pin(l16[h].im);
          l32[h] = cmul(l16[h], l16[h]);
          const cplx a = (q & 1) ? l16[h] : cplx{1.f, 0.f}, c = (q & 2) ? l32[h] : cplx{1.f, 0.f};
          lq[h] = cmul(cmul(a, c), coef[h]);
          pin(lq[h].re); pin(lq[h].im);
          if (Q1) {
            if (q < 2) l16[h] = cplx{0.f, 0.f};
            if (q < 3) l32[h] = cplx{0.f, 0.f};
            pin(l16[h].re); pin(l16[h].im); pin(l32[h].re); pin(l32[h].im);
          }
        }
      }
    }
    TS(wg, 2);
    auto scale_u = [&](int i0, int i1) {
#pragma unroll
      for (int i = 0; i < 32; i++) if (i >= i0 && i < i1) {
        pin(ure[i]); pin(uim[i]);
        const cplx v = cmul(coef[(i >> 1) & 1], cplx{ure[i], uim[i]});
        ure[i] = v.re; uim[i] = v.im;
        pin(ure[i]); pin(uim[i]);
      }
    };
#pragma unroll
    for (int kb = 0; kb < 8; kb++) {
      const int u = 8 + kb, slot = u % NSLOT;
      mbar_wait(fullb + 8 * slot, full_par(u));
      TK(kb);
      wg_fence();
      const uint32_t dxa = dxw + ((kb + xrot) & 7) * 1024;
#pragma unroll
      for (int kk = 0; kk < 4; kk++)
        wgmma_n96_ss<0, 1, DH128, DH64>(aa, dxa, kk * 32, dring, slot * 16384 + kk * 1024 + lbo(4096), 1);
      wg_commit();
      if (kb + 8 == B3K) bias(3);
      if (kb != QK) { wg_wait<1>(); release((u - 1) % NSLOT); }
      if (kb == 0) {
        reg_fence(ure); reg_fence(uim);
#pragma unroll
        for (int h = 0; h < 2; h++) e[h] = cplx{ure[2 * h], uim[2 * h]};
      }
      if (kb == 0 || (kb >= 2 && kb <= QK && kb < 4)) {
        constexpr int tc[5] = TCUT;
#pragma unroll
        for (int t = 1; t < 16; t++) if (t >= tc[kb] && t < tc[kb + 1]) {
#pragma unroll
          for (int h = 0; h < 2; h++) { const int i = 4 * (t >> 1) + 2 * h + (t & 1); e[h] = cfma(lam[h], e[h], cplx{ure[i], uim[i]}); }
        }
#pragma unroll
        for (int h = 0; h < 2; h++) { pin(e[h].re); pin(e[h].im); }
      }
      if (kb == QK) {
        { constexpr int sc[9] = SCUT; scale_u(sc[kb], sc[kb + 1]); }
        if (QF) sched_fence(ck);
#pragma unroll
        for (int h = 0; h < 2; h++) {
          cplx y = {__shfl_up_sync(0xffffffffu, e[h].re, 1, 4), __shfl_up_sync(0xffffffffu, e[h].im, 1, 4)};
          if (q >= 1) e[h] = cfma(l16[h], y, e[h]);
          y = cplx{__shfl_up_sync(0xffffffffu, e[h].re, 2, 4), __shfl_up_sync(0xffffffffu, e[h].im, 2, 4)};
          if (q >= 2) e[h] = cfma(l32[h], y, e[h]);
        }
        if (q == 3) {
#pragma unroll
          for (int h = 0; h < 2; h++)
            asm volatile("st.shared.v2.f32 [%0], {%1,%2};" ::"r"(sb + OFF_CARRY + wg * 512 + (w * 16 + gr + 8 * h) * 8), "f"(e[h].re), "f"(e[h].im) : "memory");
          mbar_arrive(sb + OFF_GBAR);
        }
#pragma unroll
        for (int h = 0; h < 2; h++) e[h] = cplx{__shfl_up_sync(0xffffffffu, e[h].re, 1, 4), __shfl_up_sync(0xffffffffu, e[h].im, 1, 4)};
        wg_wait<1>(); release((u - 1) % NSLOT);
        if (TKT > 500) TS(wg, 3);
      }
      if (kb == QK + 1) {
#pragma unroll
        for (int h = 0; h < 2; h++) {
          pre[h] = Q1 ? cmul(coef[h], pre[h]) : (q >= 1) ? cmul(coef[h], e[h]) : cplx{0.f, 0.f};
          pin(pre[h].re); pin(pre[h].im);
        }
      }
      if (kb > QK) { constexpr int sc[9] = SCUT; scale_u(sc[kb], sc[kb + 1]); }
    }
    TS(wg, 4);
    uint32_t H[56], hf[32];
    cplx hst[2];
    const uint32_t hst_addr = xw + (w * 16 + (lane & 15)) * 128 + (((lane >> 4) ^ (lane & 7)) << 4);
    const uint32_t him = (2 - rank) * 16384;
    uint32_t peer;
    asm volatile("mapa.shared::cluster.u32 %0, %1, %2;" : "=r"(peer) : "r"(sb), "r"(rank ^ 1));
    auto credit = [&]() { if (lane == 0) mbar_arrive_cl(peer + OFF_KBAR + wg * 8); };
    uint32_t g2[8];
#pragma unroll
    for (int kb = 0; kb < 8; kb++) {
      const int u = 16 + kb, slot = u % NSLOT;
      mbar_wait(fullb + 8 * slot, full_par(u));
      TK(kb < 7 ? 24 + kb : 32);
      wg_fence();
#pragma unroll
      for (int kk = 0; kk < 4; kk++)
        wgmma_n128_ss<0, 1, DH128, DH128>(ab, dxw, kb * 16384 + kk * 32, dring, slot * 16384 + kk * 2048 + lbo(8192), 1);
      wg_commit();
      if (kb == 0) { constexpr int sc[9] = SCUT; scale_u(sc[8], 32); }
      if (kb == 4) {
        if (TKT > 500) TS(wg, 5);
        mbar_wait(sb + OFF_CBAR, 0);
        if (TKT > 500) TS(wg, 6);
#pragma unroll
        for (int h = 0; h < 2; h++) {
          const float2 c = lds_f2(sb + OFF_CARRY + wg * 512 + (w * 16 + gr + 8 * h) * 8);
          hst[h] = cfma(lq[h], cplx{c.x, c.y}, pre[h]);
        }
#pragma unroll
        for (int i = 0; i < 2; i++) {
          const uint4 v = lds_u4(sb + OFF_GT + wg * 128 + q * 32 + i * 16);
          g2[4 * i] = v.x; g2[4 * i + 1] = v.y; g2[4 * i + 2] = v.z; g2[4 * i + 3] = v.w;
        }
      }
      if (kb == 0 || TOKB != 1) { wg_wait<1>(); release((u - 1) % NSLOT); }
      if (kb) sched_fence(ck);
      if (kb < 4) {
#pragma unroll
        for (int i = kb * 6; i < kb * 6 + 6; i++) {
          pin(aa[2 * i]); pin(aa[2 * i + 1]);
          H[i] = gelu2_pair(aa[2 * i], aa[2 * i + 1]);
          pin(H[i]);
        }
      } else {
        const int j0 = (kb - 4) * 2;
        uint32_t rr[4], ri[4];
#pragma unroll
        for (int jj = 0; jj < 2; jj++) {
          const int j = j0 + jj;
#pragma unroll
          for (int h = 0; h < 2; h++) {
            const int i = 4 * j + 2 * h;
            const cplx h0 = cfma(lam[h], hst[h], cplx{ure[i], uim[i]});
            hst[h] = cfma(lam[h], h0, cplx{ure[i + 1], uim[i + 1]});
            rr[jj * 2 + h] = bf2_mul(pack_bf16(h0.re, hst[h].re), g2[j]);
            ri[jj * 2 + h] = bf2_mul(pack_bf16(h0.im, hst[h].im), g2[j]);
          }
        }
        const uint32_t a = hst_addr ^ (j0 << 4);
        asm volatile("stmatrix.sync.aligned.m8n8.x4.shared.b16 [%0], {%1,%2,%3,%4};" ::"r"(a), "r"(rr[0]), "r"(rr[1]), "r"(rr[2]), "r"(rr[3]) : "memory");
        asm volatile("stmatrix.sync.aligned.m8n8.x4.shared.b16 [%0], {%1,%2,%3,%4};" ::"r"(a + him), "r"(ri[0]), "r"(ri[1]), "r"(ri[2]), "r"(ri[3]) : "memory");
      }
      if (kb && TOKB == 1) { wg_wait<1>(); release((u - 1) % NSLOT); }
    }
    TS(wg, 7);

    uint4* const psend = g_part + (size_t)(m * 8 + rank) * 3072 + warp * 128 + lane;
    const uint4* const precv = g_part + (size_t)(m * 8 + s) * 3072 + warp * 128 + lane;
    const uint32_t pbuf = OFF_X + warp * 2048 + lane * 16;
    const uint32_t dx0 = ((sb + OFF_X) & 0x3FFFF) >> 4;
    float o[32], fin[32], rho[2];
    uint32_t tr[8];
    uint32_t r0[16], pt[16], sum[16], tag;
    auto recv_issue = [&](uint32_t (&r)[16], int k) {
#pragma unroll
      for (int i = 0; i < 4; i++) ld_b128(precv + k * 1024 + i * 32, r[4 * i], r[4 * i + 1], r[4 * i + 2], r[4 * i + 3]);
    };
    auto stale = [&](uint32_t (&r)[16]) {
      uint32_t r_;
#pragma unroll
      for (int i = 0; i < 16; i += 4) asm("lop3.b32 %0, %0, %1, 1, 0x78;" : "+r"(r[i]) : "r"(tag));
      asm volatile("{.reg .pred p; .reg .b32 t; lop3.b32 t, %1, %2, %3, 0xfe; lop3.b32 t, t, %4, 1, 0xa8; setp.ne.u32 p, t, 0; vote.sync.any.pred p, p, 0xffffffff; selp.u32 %0, 1, 0, p;}"
                   : "=r"(r_) : "r"(r[0]), "r"(r[4]), "r"(r[8]), "r"(r[12]));
      return r_ != 0;
    };
    auto recv_check = [&](uint32_t (&r)[16], int k) {
      if (__builtin_expect(stale(r), 0)) {
        int tries = 0;
#pragma unroll 1
        do { recv_issue(r, k); } while (stale(r) && ++tries < 200000);
      }
    };
    auto gelu_b = [&](int i0, int i1) {
      if (TOKD && i0) sched_fence(ck);
#pragma unroll
      for (int i = i0; i < i1; i++) {
        pin(ab[2 * i]); pin(ab[2 * i + 1]);
        H[24 + i] = gelu2_pair(ab[2 * i], ab[2 * i + 1]);
        pin(H[24 + i]);
      }
      if (TOKD == 2) sched_fence(ck);
    };
    auto step = [&](float (&d)[32], int p, int k, int acc) {
      const uint32_t wo = stage_off(p);
      if (k >= 6 && k < 14) {
        const int kk = k - 6;
        if (kk < 4) wgmma_n64_rs<0, DH128, 1>(d, hf[4 * kk], hf[4 * kk + 1], hf[4 * kk + 2], hf[4 * kk + 3], dx0, wo + 14336 + kk * 32, 1);
        else wgmma_n64_rs<0, DH128, -1>(d, hf[4 * kk], hf[4 * kk + 1], hf[4 * kk + 2], hf[4 * kk + 3], dx0, wo + 22528 + (kk - 4) * 32, 1);
      } else {
        const int kk = k < 6 ? k : k - 8;
        wgmma_n64_rs<1, DH128>(d, H[4 * kk], H[4 * kk + 1], H[4 * kk + 2], H[4 * kk + 3], dx0, wo + (kk / 7) * 30720 + (kk % 7) * 2048, k != 0 || acc);
      }
    };
    auto mma = [&](float (&d)[32], int p, int k0, int k1, int acc) {
      wg_fence();
#pragma unroll
      for (int k = k0; k < k1; k++) step(d, p, k, acc);
      wg_commit();
    };
    auto send_peer = [&](float (&d)[32], uint32_t off) {
#pragma unroll
      for (int i = 0; i < 4; i++)
        asm volatile("st.async.shared::cluster.mbarrier::complete_tx::bytes.v4.b32 [%0], {%1,%2,%3,%4}, [%5];" ::"r"(peer + pbuf + off + i * 512),
                     "r"(pack_bf16(d[8 * i], d[8 * i + 1])), "r"(pack_bf16(d[8 * i + 2], d[8 * i + 3])), "r"(pack_bf16(d[8 * i + 4], d[8 * i + 5])),
                     "r"(pack_bf16(d[8 * i + 6], d[8 * i + 7])), "r"(peer + OFF_RBAR + wg * 8) : "memory");
    };
    auto read_peer = [&](uint32_t (&r)[16], uint32_t off) {
#pragma unroll
      for (int i = 0; i < 4; i++) { const uint4 v = lds_u4(sb + pbuf + off + i * 512); r[4 * i] = v.x; r[4 * i + 1] = v.y; r[4 * i + 2] = v.z; r[4 * i + 3] = v.w; }
    };
    auto send_owner = [&](uint32_t (&r)[16], int k) {
#pragma unroll
      for (int i = 0; i < 4; i++) {
#pragma unroll
        for (int c = 4 * i; c < 4 * i + 4; c++) r[c] = bf2_add(r[c], pack_bf16(o[2 * c], o[2 * c + 1]));
        asm("lop3.b32 %0, %0, 1, %1, 0xb8;" : "+r"(r[4 * i]) : "r"(tag));
        st_b128(psend + (((sp + 1 + k) & 3) * 6 + k) * 1024 + i * 32, r[4 * i], r[4 * i + 1], r[4 * i + 2], r[4 * i + 3]);
      }
    };
    auto load_fin = [&]() {
      mbar_wait(sb + OFF_LBAR, 1);
#pragma unroll
      for (int j = 0; j < 8; j++) {
        const uint4 v = lds_u4(sb + pbuf + 16384 + (j >> 2) * 16384 + (j & 3) * 512);
        fin[4 * j] = __uint_as_float(v.x); fin[4 * j + 1] = __uint_as_float(v.y); fin[4 * j + 2] = __uint_as_float(v.z); fin[4 * j + 3] = __uint_as_float(v.w);
      }
    };
    auto ldk = [&](int pos) { if (pos == K0P) recv_issue(sum, 0); if (pos == K1P) recv_issue(r0, 1); };
    uint32_t ta, la;
    float* op;
    auto out_addr = [&]() {
      const uint32_t tb = sb + OFF_X + stage_off(0) + warp * 4096;
      ta = tb + gr * 256 + ((gr & 3) << 5) + q * 8;
      la = tb + (lane >> 3) * 256 + (((lane & 7) << 4) ^ ((lane >> 3) << 5));
      op = out + (size_t)(m * 128 + wg * 64 + (lane >> 4) * 16 + w * 4 + ((lane >> 3) & 1)) * DM + s * 64 + (lane & 7) * 4;
      if (ADP) { pin(ta); pin(la); asm volatile("" : "+l"(op)); sched_fence(ck); }
    };
    auto arm = [&](uint32_t bytes) { if ((w == 0 && lane == 0)) mbar_expect_tx(sb + OFF_RBAR + wg * 8, bytes); };
    auto mma2 = [&](int k0, int k1) {
      wg_fence();
#pragma unroll
      for (int k = k0; k < k1; k++) { step(o, 0, k, 0); step(fin, 1, k, 0); }
      wg_commit();
    };
    auto hand = [&](int pos) { if (A0 == pos && wg == 0) bar_arrive(5, 256); };
    {
        constexpr int kc[8] = DCUT;
        mbar_wait(fullb, full_par(24));
        mma2(0, kc[0]);
        bar_sync(1 + wg, 128);
        {
          const uint32_t ha = xw + ((lane >> 4) * 8 + (lane & 7)) * 128 + (((2 * w + ((lane >> 3) & 1)) ^ (lane & 7)) << 4);
#pragma unroll
          for (int kk = 0; kk < 8; kk++)
            asm volatile("ldmatrix.sync.aligned.m8n8.x4.trans.shared.b16 {%0,%1,%2,%3}, [%4];" : "=r"(hf[4 * kk]), "=r"(hf[4 * kk + 1]), "=r"(hf[4 * kk + 2]), "=r"(hf[4 * kk + 3])
                         : "r"(ha + (kk >> 2) * him + (kk & 3) * 2048) : "memory");
        }
        tag = lds_u(sb + OFF_EPOCH);
        arm(16384);
        mbar_wait(fullb + 8, full_par(25));
        wg_wait<1>(); release(5);
        if (A0 && wg == 1) bar_sync(5, 256);
        gelu_b(0, 4);   mma2(kc[0], kc[1]); hand(1);
        gelu_b(4, 8);   mma2(kc[1], kc[2]); hand(2);
        gelu_b(8, 12);  mma2(kc[2], kc[3]); hand(3);
        gelu_b(12, 16); mma2(kc[3], kc[4]); hand(4);
        gelu_b(16, 20);
        mbar_wait(fullb + 16, full_par(26));
        mma2(kc[4], kc[5]); hand(5);
        credit();
        gelu_b(20, 24); mma2(kc[5], kc[6]); hand(6);
        gelu_b(24, 28); mma2(kc[6], kc[7]);
        mbar_wait(sb + OFF_XFULL + 16, 1);
        gelu_b(28, 32);
        if (wg == 1) bar_sync(4, 256);
        mma(o, 0, kc[7], 22, 0);
        mma(fin, 1, kc[7], 22, 0);
        bar_arrive(4 - wg, 256);
        TS(wg, 9);
        mbar_wait(sb + OFF_KBAR + wg * 8, 0);
        wg_wait<1>();
        reg_fence(o);
        send_peer(o, 0);
        if (!E1L) { wg_wait<0>(); release(0); release(1); reg_fence(fin); send_peer(fin, 49152 - him); }
    }
#pragma unroll
    for (int p = 2; p < 8; p++) {
      const bool even = p == 4 || p == 6;
      if (p == 4 && LW4) mbar_wait(sb + OFF_XFULL + 32, 1);
      bar_sync(3 + wg, 256);
      if (p < 7) mma(o, p, 0, 22, 0); else mma(fin, p, 0, 22, 1);
      if (p < 7 || wg == 0) bar_arrive(4 - wg, 256);
      TS(wg, 8 + p);
      if (p == 2 && E1L) { wg_wait<1>(); release(0); release(1); reg_fence(fin); send_peer(fin, 49152 - him); }
      if (p < 7 && !(p == 3 && LW4)) mbar_wait(sb + OFF_XFULL + 8 * (p + 1), 1);
      ldk(10 * p);
      if (even) {
        arm(8192);
        if (p == 6) {
          mbar_wait(sb + OFF_EMPTY + 32, 0);
          tag = lds_u(sb + OFF_EPOCH);
          recv_check(sum, 0); recv_check(r0, 1);
#pragma unroll
          for (int i = 0; i < 16; i++) sum[i] = bf2_add(sum[i], r0[i]);
        }
        mbar_wait(sb + OFF_KBAR + wg * 8, p == 4);
      } else if (p != 3) {
        if (p == 7) tag = lds_u(sb + OFF_EPOCH);
        mbar_wait(sb + OFF_RBAR + wg * 8, p == 5);
        read_peer(pt, 0);
        if (p == 2) read_peer(r0, him);
        if (p == 7) {
          recv_check(r0, 2);
#pragma unroll
          for (int i = 0; i < 16; i++) { sum[i] = bf2_add(sum[i], bf2_add(r0[i], pt[i])); pin(sum[i]); }
          sched_fence(ck);
        }
      } else {
#pragma unroll
        for (int h = 0; h < 2; h++) { rho[h] = __fdividef(2.f, 4.f + bf_lo(lds_h(sb + OFF_GS + (wg * 64 + w * 16 + gr + 8 * h) * 2))); pin(rho[h]); }
      }
      if (p == FINP && !FINW) load_fin();
      ldk(10 * p + 1);
      wg_wait<0>();
      if (p < 5) release(p);
      if (p < 7) reg_fence(o); else reg_fence(fin);
      ldk(10 * p + 2);
      if (even) {
        if (p == 6) recv_issue(r0, 2);
        send_peer(o, 0);
        if (p == FINP && FINW) load_fin();
      } else if (p == 3) {
        send_owner(r0, 1);
      } else if (p < 7) {
        send_owner(pt, p == 2 ? 0 : 2);
        __syncwarp();
        credit();
      }
      ldk(10 * p + 3);
    }
    {
      TS(wg, 16);
      if (ADP == 0) out_addr();
#pragma unroll
      for (int qq = 0; qq < 4; qq += QS) {
#pragma unroll
        for (int qt = qq; qt < qq + QS; qt++) {
          const int h = qt & 1, ch = qt >> 1;
#pragma unroll
          for (int j = 0; j < 4; j++) {
            const int i = ch * 8 + j * 2 + h;
            asm volatile("st.shared.v2.f32 [%0], {%1,%2};" ::"r"((ta ^ (j << 5)) + h * 2048 + ch * 128),
                         "f"((fin[2 * i] + bf_lo(sum[i])) * rho[h]), "f"((fin[2 * i + 1] + bf_hi(sum[i])) * rho[h]) : "memory");
          }
        }
        __syncwarp();
#pragma unroll
        for (int qt = qq; qt < qq + QS; qt++) {
          const int h = qt & 1, ch = qt >> 1;
#pragma unroll
          for (int r = 0; r < 2; r++)
            *reinterpret_cast<uint4*>(op + (r * 32 + h * 2) * DM + ch * 32) = lds_u4(la + (h * 2 + r) * 1024 + ch * 128);
        }
      }
      if (FF1 || ADP) asm volatile("st.shared.u32 [%0], %1;" ::"r"(sb + OFF_EPOCH + 4), "r"(ck) : "memory");
      if ((warp == 4 && lane == 0)) g_epoch[b] = tag;
      TS(wg, 17); TG(wg); TRD(); TDUMP();
    }
  } else {
    const int lane = OPH ? __shfl_sync(0xffffffffu, lane0, lane0) : lane0;
    asm volatile("setmaxnreg.dec.sync.aligned.u32 56;");
    int wsel = warp;
    asm("" : "+r"(wsel));
    if (wsel > 8) {
      const uint4* gwp = reinterpret_cast<const uint4*>(gate_w) + (lane & 7);
      uint4 gw[4];
      if (warp != 11) {
        const int t = OPH ? (warp - 9) * 32 + lane : threadIdx.x - 288;
        unsigned par;
        asm volatile("ld.relaxed.gpu.global.u32 %0, [%1];" : "=r"(par) : "l"(g_epoch + b) : "memory");
        const float pr = bf_ld(lam_re + s * 64 + t), pi = bf_ld(lam_im + s * 64 + t), pd = bf_ld(log_dt + s * 64 + t);
#pragma unroll
        for (int i = 0; i < 4; i++) gw[i] = __ldg(gwp + i * 8);
        asm volatile("barrier.cluster.wait.aligned;" ::: "memory");
        par = __shfl_sync(0xffffffffu, (par + 1) & 1, 0);
        cplx l64 = make_lam(pr, pi, pd);
        {
          const float inv = __fdividef(1.f, fmaf(pr, pr, pi * pi));
          const cplx cf = cmul(cplx{l64.re - 1.f, l64.im}, cplx{pr * inv, -pi * inv});
          asm volatile("st.shared.v4.f32 [%0], {%1,%2,%3,%4};" ::"r"(sb + OFF_LC + t * 16), "f"(l64.re), "f"(l64.im), "f"(cf.re), "f"(cf.im) : "memory");
          mbar_arrive(sb + OFF_LBAR);
        }
#pragma unroll
        for (int i = 0; i < 6; i++) l64 = cmul(l64, l64);
        cplx l128 = cmul(l64, l64);
        pin(l128.re); pin(l128.im);
        gate_rows<1>(sb, lane, xrot, s * 16 + (warp - 9) * 4, gw, gwp, g_gate + m * 128, par);
        if (t == 0) TS(3, 6);
        uint32_t vr[15], vi[15];
#pragma unroll
        for (int i = 0; i < 15; i++) { vr[i] = par; vi[i] = 0; pin(vr[i]); pin(vi[i]); }
        mbar_wait(sb + OFF_GBAR, 0);
        const float2 e0 = lds_f2(sb + OFF_CARRY + t * 8), e1 = lds_f2(sb + OFF_CARRY + 512 + t * 8);
        float2* eb = g_end + s * 1024 + t;
        {
          const cplx e = cfma(l64, cplx{e0.x, e0.y}, cplx{e1.x, e1.y});
          const unsigned long long v = ((unsigned long long)__float_as_uint(e.im) << 32) | ((__float_as_uint(e.re) & ~1u) | par);
          asm volatile("st.relaxed.gpu.global.b64 [%0], %1;" ::"l"(eb + m * 64), "l"(v) : "memory");
        }
        if (t == 0) TS(3, 1);
        cplx S = {0.f, 0.f};
        {
          if (LBD) __nanosleep(LBD);
          const float2* e15 = eb + (m - 15) * 64;
          int tries = 0;
          bool bad;
#pragma unroll 1
          do {
#pragma unroll
            for (int i = 0; i < 15; i++)
              asm volatile("{.reg .pred p; .reg .b64 v; mov.b64 v, {%0,%1}; setp.ge.s32 p, %3, %4; @p ld.relaxed.gpu.global.b64 v, [%2]; mov.b64 {%0,%1}, v;}"
                           : "+r"(vr[i]), "+r"(vi[i]) : "l"(e15 + i * 64), "r"(m), "r"(15 - i) : "memory");
            uint32_t x = vr[0] ^ par;
#pragma unroll
            for (int i = 1; i < 15; i++) asm("lop3.b32 %0, %0, %1, %2, 0xf6;" : "+r"(x) : "r"(vr[i]), "r"(par));
            bad = __any_sync(0xffffffffu, x & 1);
          } while (bad && ++tries < 200000);
          if (t == 0) TS(3, 2);
          S = cplx{__uint_as_float(vr[0] ^ par), __uint_as_float(vi[0])};
#pragma unroll
          for (int i = 1; i < 15; i++) S = cfma(l128, S, cplx{__uint_as_float(vr[i] ^ par), __uint_as_float(vi[i])});
        }
        const cplx S1 = cfma(l64, S, cplx{e0.x, e0.y});
        asm volatile("st.shared.v2.f32 [%0], {%1,%2};" ::"r"(sb + OFF_CARRY + t * 8), "f"(S.re), "f"(S.im) : "memory");
        asm volatile("st.shared.v2.f32 [%0], {%1,%2};" ::"r"(sb + OFF_CARRY + 512 + t * 8), "f"(S1.re), "f"(S1.im) : "memory");
        mbar_arrive(sb + OFF_CBAR);
        if (t == 0) TS(3, 3);
        mbar_wait(sb + OFF_CBAR, 0);
        const int gr = lane >> 2, q = lane & 3;
        float2 db[8];
#pragma unroll
        for (int j = 0; j < 8; j++) db[j] = lds_f2(sb + OFF_DB + j * 32 + q * 8);
        mbar_wait(sb + OFF_XFULL + 16, 1);
        mbar_wait(sb + OFF_EMPTY + 16, 0);
#pragma unroll 1
        for (int cw = warp - 9; cw < 8; cw += 2) {
          const float r0 = 0.5f * bf_lo(lds_h(sb + OFF_GS + (cw * 16 + gr) * 2)), r1 = 0.5f * bf_lo(lds_h(sb + OFF_GS + (cw * 16 + gr) * 2 + 16));
          const uint32_t xa = sb + OFF_X + (1 + rank) * 16384 + (cw * 16 + (lane & 15)) * 128 + (((lane >> 4) ^ (lane & 7)) << 4);
          uint32_t xv[16];
#pragma unroll
          for (int i = 0; i < 4; i++)
            asm volatile("ldmatrix.sync.aligned.m8n8.x4.shared.b16 {%0,%1,%2,%3}, [%4];" : "=r"(xv[4 * i]), "=r"(xv[4 * i + 1]), "=r"(xv[4 * i + 2]), "=r"(xv[4 * i + 3])
                         : "r"(xa ^ (i << 5)) : "memory");
          __syncwarp();
#pragma unroll
          for (int j = 0; j < 8; j++) {
            const uint32_t x0 = bf2_mul(xv[2 * j], __float_as_uint(db[j].x)), x1 = bf2_mul(xv[2 * j + 1], __float_as_uint(db[j].x));
            pin(db[j].y);
            const float bl = bf_lo(__float_as_uint(db[j].y)), bh = bf_hi(__float_as_uint(db[j].y));
            asm volatile("st.shared.v4.f32 [%0], {%1,%2,%3,%4};" ::"r"(sb + OFF_X + 16384 + (j >> 2) * 16384 + cw * 2048 + (j & 3) * 512 + lane * 16), "f"(fmaf(bf_lo(x0), r0, bl)),
                         "f"(fmaf(bf_hi(x0), r0, bh)), "f"(fmaf(bf_lo(x1), r1, bl)), "f"(fmaf(bf_hi(x1), r1, bh)) : "memory");
          }
        }
        mbar_arrive(sb + OFF_LBAR);
        if (t == 0) TS(3, 5);
      } else {
        if (lane == 0) TG(2);
#pragma unroll
        for (int i = 0; i < 4; i++) gw[i] = __ldg(gwp + i * 8);
        unsigned par;
        asm volatile("ld.relaxed.gpu.global.u32 %0, [%1];" : "=r"(par) : "l"(g_epoch + b) : "memory");
        const uint32_t dk = __ldg(reinterpret_cast<const uint32_t*>(dskip + s * 64) + lane), bb = __ldg(reinterpret_cast<const uint32_t*>(b2 + s * 64) + lane);
        asm volatile("barrier.cluster.wait.aligned;" ::: "memory");
        if (lane == 0) asm volatile("st.shared.u32 [%0], %1;" ::"r"(sb + OFF_EPOCH), "r"(par + 1) : "memory");
        par = (par + 1) & 1;
        gate_rows<2>(sb, lane, xrot, s * 16 + 8, gw, gwp, g_gate + m * 128, par);
        if (lane == 0) TS(3, 0);
        mbar_wait(sb + OFF_GBAR, 0);
        asm volatile("st.shared.v2.u32 [%0], {%1,%2};" ::"r"(sb + OFF_DB + lane * 8), "r"(dk), "r"(bf2_add(bb, bb)) : "memory");
        uint32_t g0, g1, g2, g3;
        int tries = 0;
#pragma unroll 1
        do {
          asm volatile("ld.relaxed.gpu.global.v4.u32 {%0,%1,%2,%3}, [%4];" : "=r"(g0), "=r"(g1), "=r"(g2), "=r"(g3) : "l"(g_gate + m * 128 + lane * 4) : "memory");
          g0 ^= par; g1 ^= par; g2 ^= par; g3 ^= par;
        } while (((g0 | g1 | g2 | g3) & 1) && ++tries < 200000);
        asm volatile("st.shared.v2.u32 [%0], {%1,%2};" ::"r"(sb + OFF_GS + lane * 8), "r"(pack_bf16(__uint_as_float(g0), __uint_as_float(g1))),
                     "r"(pack_bf16(__uint_as_float(g2), __uint_as_float(g3))) : "memory");
        const uint32_t gt = sb + OFF_GT + (lane >> 4) * 128 + (lane & 1) * 64 + ((lane >> 1) & 7) * 4;
        asm volatile("st.shared.u32 [%0], %1;" ::"r"(gt), "r"(pack_bf16(__uint_as_float(g0), __uint_as_float(g1))) : "memory");
        asm volatile("st.shared.u32 [%0], %1;" ::"r"(gt + 32), "r"(pack_bf16(__uint_as_float(g2), __uint_as_float(g3))) : "memory");
        mbar_arrive(sb + OFF_CBAR);
        if (lane == 0) TS(3, 4);
      }
    } else {
      asm volatile("barrier.cluster.wait.aligned;" ::: "memory");
      if (elect_one()) {
        TS(2, 1);
        const uint32_t t0 = clock();
#pragma unroll 1
        for (int u = W0; u < 8; u++) {
          if (u >= 1) while ((uint32_t)clock() - t0 < D0 + (u - 1) * D1) {}
          mbar_expect_tx(sb + OFF_XFULL + 8 * u, 32768);
          tma5d_mc(sb + OFF_X + ((u + xrot) & 7) * 16384 + rank * 8192, &maps.x, u * 64, 2 * m + rank, sb + OFF_XFULL + 8 * u);
          const int sl = u < 6 ? u : u - 6;
          if (u >= 6) mbar_wait(sb + OFF_EMPTY + 8 * sl, 0);
          tma2d(sb + OFF_RING + sl * 16384, &maps.bre, u * 64, s * 64, sb + OFF_XFULL + 8 * u);
          tma2d(sb + OFF_RING + sl * 16384 + 8192, &maps.bim, u * 64, s * 64, sb + OFF_XFULL + 8 * u);
          if (u == 2) asm volatile("prefetch.tensormap [%0];" ::"l"(&maps.w1b) : "memory");
          if (u == PA && m < 8) asm volatile("cp.async.bulk.prefetch.tensor.3d.L2.global [%0, {%1,%2,%3}];" ::"l"(&maps.w1b), "r"(0), "r"(m * 64), "r"(s * 7) : "memory");
        }
        TS(2, 5);
        int slot = 2; uint32_t ph = 0;
#pragma unroll 1
        for (int u = 8; u < 24; u++) {
          const uint32_t fb = sb + OFF_FULL + 8 * slot, dst = sb + OFF_RING + slot * 16384;
          mbar_wait(sb + OFF_EMPTY + 8 * slot, ph);
          TS2(0, u);
          if (u < 16) {
            mbar_expect_tx(fb, 12288);
            tma3d(dst, &maps.w1b, 0, (u - 8) * 64, s * 7, fb);
            if (TMP2 && u < 12) asm volatile("prefetch.tensormap [%0];" ::"l"(&maps.w1a + (u - 8)) : "memory");
          } else {
            mbar_expect_tx(fb, 16384);
            tma2d(dst, &maps.w1a, s * 224 + 96, ((u - xrot) & 7) * 64, fb);
            tma2d(dst + 8192, &maps.w1a, s * 224 + 160, ((u - xrot) & 7) * 64, fb);
          }
          if (u == PB) asm volatile("cp.async.bulk.prefetch.tensor.2d.L2.global [%0, {%1,%2}];" ::"l"(&maps.w1a), "r"(s * 224 + 96 + (m & 1) * 64), "r"((m >> 1) * 64) : "memory");
          if (u == PC) {
            const int c = ((sp + 1 + (m >> 3)) & 3) * 128 + ((m >> 2) & 1) * 64;
            if (m & 2) asm volatile("cp.async.bulk.prefetch.tensor.2d.L2.global [%0, {%1,%2}];" ::"l"((m & 1) ? &maps.cim : &maps.cre), "r"(s * 64), "r"(c) : "memory");
            else asm volatile("cp.async.bulk.prefetch.tensor.2d.L2.global [%0, {%1,%2}];" ::"l"(&maps.w2), "r"(c), "r"(s * 224 + (m & 1) * 112) : "memory");
          }
          if (++slot == NSLOT) { slot = 0; ph ^= 1; }
        }
#pragma unroll 1
        for (int j = 0; j < 3; j++) {
          const uint32_t fb = sb + OFF_FULL + 8 * j;
          mbar_wait(sb + OFF_EMPTY + 8 + 8 * j, 1);
          mbar_expect_tx(fb, j == 1 ? 32768 : 28672);
#pragma unroll
          for (int e = 0; e < 2; e++) {
            const int c = ((sp + 1 + e) & 3) * 128 + ((rank ^ 1) << 6);
            const uint32_t dst = sb + OFF_X + stage_off(e);
            if (j == 1) {
              tma2d(dst + 14336, &maps.cre, s * 64, c, fb);
              tma2d(dst + 22528, &maps.cim, s * 64, c, fb);
            } else {
              tma2d(dst + j * 15360, &maps.w2, c, s * 224 + j * 56, fb);
            }
          }
        }
#pragma unroll 1
        for (int p = 2; p < 8; p++) {
          const int c = p < 4 ? ((sp + p - 1) & 3) * 128 + (rank << 6) : ((sp + 1 + (p >> 1)) & 3) * 128 + (((rank ^ p ^ 1) & 1) << 6);
          const uint32_t fb = sb + OFF_XFULL + 8 * p, dst = sb + OFF_X + stage_off(p);
          if (p == 2 || p > 3) mbar_wait(sb + OFF_EMPTY + (p == 2 ? 40 : (p - 4) * 8), p == 2);
          TS2(0, 32 + p);
          mbar_expect_tx(fb, 45056);
          tma2d(dst, &maps.w2, c, s * 224, fb);
          tma2d(dst + 14336, &maps.cre, s * 64, c, fb);
          tma2d(dst + 22528, &maps.cim, s * 64, c, fb);
          tma2d(dst + 30720, &maps.w2, c, s * 224 + 112, fb);
        }
        TS(2, 2);
      }
    }
  }
}

typedef CUresult (*EncFn)(CUtensorMap*, CUtensorMapDataType, cuuint32_t, void*, const cuuint64_t*, const cuuint64_t*, const cuuint32_t*,
                          const cuuint32_t*, CUtensorMapInterleave, CUtensorMapSwizzle, CUtensorMapL2promotion, CUtensorMapFloatOOBfill);

void encode(EncFn f, CUtensorMap* mp, const void* p, int rank, const cuuint64_t* dims, const cuuint64_t* strides, const cuuint32_t* box, CUtensorMapSwizzle sw) {
  cuuint32_t es[5] = {1, 1, 1, 1, 1};
  f(mp, CU_TENSOR_MAP_DATA_TYPE_BFLOAT16, rank, const_cast<void*>(p), dims, strides, box, es, CU_TENSOR_MAP_INTERLEAVE_NONE, sw,
    CU_TENSOR_MAP_L2_PROMOTION_L2_128B, CU_TENSOR_MAP_FLOAT_OOB_FILL_NONE);
}

}

extern "C" void kernel_launch(void* const* d_in, const int* in_sizes, int n_in, void* d_out, int out_size) {
  typedef const __nv_bfloat16* bp;
  bp x = (bp)d_in[0], lre = (bp)d_in[1], lim = (bp)d_in[2], bre = (bp)d_in[3], bim = (bp)d_in[4], cre = (bp)d_in[5], cim = (bp)d_in[6],
     ldt = (bp)d_in[7], dsk = (bp)d_in[8], w1 = (bp)d_in[10], b1 = (bp)d_in[11], w2 = (bp)d_in[12], b2 = (bp)d_in[13], gw = (bp)d_in[14];
  static EncFn enc = nullptr;
  if (!enc) {
    void* f = nullptr;
    cudaDriverEntryPointQueryResult qr;
    cudaGetDriverEntryPoint("cuTensorMapEncodeTiled", &f, cudaEnableDefault, &qr);
    enc = (EncFn)f;
    cudaFuncSetAttribute(fused_kernel, cudaFuncAttributeMaxDynamicSharedMemorySize, SMEM_BYTES);
  }
  Maps maps;
  {
    cuuint64_t d[5] = {DM, 2, 4, 8, SEQ / 64}, st[4] = {DM * 2, 16 * DM * 2, 2 * DM * 2, 64 * DM * 2};
    cuuint32_t bx[5] = {64, 2, 4, 8, 1};
    encode(enc, &maps.x, x, 5, d, st, bx, CU_TENSOR_MAP_SWIZZLE_128B);
  }
  {
    cuuint64_t d[2] = {DM, DM}, st[1] = {DM * 2};
    cuuint32_t bx[2] = {64, 64};
    encode(enc, &maps.bre, bre, 2, d, st, bx, CU_TENSOR_MAP_SWIZZLE_128B);
    encode(enc, &maps.bim, bim, 2, d, st, bx, CU_TENSOR_MAP_SWIZZLE_128B);
    encode(enc, &maps.cre, cre, 2, d, st, bx, CU_TENSOR_MAP_SWIZZLE_128B);
    encode(enc, &maps.cim, cim, 2, d, st, bx, CU_TENSOR_MAP_SWIZZLE_128B);
  }
  {
    cuuint64_t d[2] = {FF, DM}, st[1] = {FF * 2};
    cuuint32_t bx[2] = {64, 64};
    encode(enc, &maps.w1a, w1, 2, d, st, bx, CU_TENSOR_MAP_SWIZZLE_128B);
    cuuint64_t d3[3] = {32, DM, FF / 32}, st3[2] = {FF * 2, 64};
    cuuint32_t bx3[3] = {32, 64, 3};
    encode(enc, &maps.w1b, w1, 3, d3, st3, bx3, CU_TENSOR_MAP_SWIZZLE_64B);
  }
  {
    cuuint64_t d[2] = {DM, FF}, st[1] = {DM * 2};
    cuuint32_t bx[2] = {64, 112};
    encode(enc, &maps.w2, w2, 2, d, st, bx, CU_TENSOR_MAP_SWIZZLE_128B);
  }
  fused_kernel<<<128, 384, SMEM_BYTES>>>(lre, lim, ldt, dsk, b1, b2, gw, w1, w2, cre, cim, (float*)d_out, maps);
}
```

```cpp
#include <cuda_runtime.h>
#include <cuda_bf16.h>
#include <cuda.h>
#include <stdint.h>

#define MAP 1
#define D0 200
#define D1 480
#define PF 4
#define PFK 5
#define GELUP 1
#define EW 2
#define K1E 1
#define K2E 0
#define QS 1
#define K2G 4
#define FINP 5
#define LBD 400
#define PFS 32
#define SB0 2
#define PFD 2
#define HOLD 0
#define GAP 0
#define FINW 0
#define K0P 41
#define K1P 53
#define TMP2 1
#define W0 1
#define LCK 4
#define TOKA 0
#define TOKB 2
#define TOKD 0
#define TKT 999
#define AV 4
#define QK 4
#define TCUT {1, 6, 6, 11, 16}
#define SCUT {0, 0, 0, 0, 0, 8, 8, 16, 24}
#define PV 2
#define KCUT {4, 8, 12, 15, 18}
#define GCUT {6, 12, 18, 24}
#define OPQ 1
#define OPS 0
#define FF1 1
#define Q1 0
#define QF 1
#define PA 99
#define PB 99
#define PC 99
#define NOH 0
#define OPH 1
#define REL 0
#define EP 0
#define FP 1
#define L16K 2
#define B0K 2
#define B1K 3
#define B2K 4
#define B3K 8
#define ADP 0
#define BB 0
#define DV 2
#define DCUT {2, 4, 7, 9, 12, 14, 15, 17}
#define E1L 0
#define A0 0
#define LW4 1
#define PD 3
#define LWM 0x10
#define HW 1
#define TP 9
#define TW 0

namespace {

constexpr int SEQ = 2048, DM = 512, FF = 1792;
constexpr int NSLOT = 6;
constexpr uint32_t OFF_X = 0, OFF_RING = 131072, OFF_MISC = 229376;
constexpr uint32_t OFF_XFULL = OFF_MISC, OFF_FULL = OFF_XFULL + 64, OFF_RBAR = OFF_FULL + 48, OFF_EMPTY = OFF_RBAR + 16, OFF_KBAR = OFF_EMPTY + 48,
                   OFF_GBAR = OFF_KBAR + 16, OFF_LBAR = OFF_GBAR + 8, OFF_CBAR = OFF_LBAR + 8, OFF_EPOCH = OFF_CBAR + 8;
constexpr uint32_t OFF_LC = OFF_MISC + 256;
constexpr uint32_t OFF_GS = OFF_LC;
constexpr uint32_t OFF_GT = OFF_LC + 256;
constexpr uint32_t OFF_DB = OFF_LC + 512;
constexpr uint32_t OFF_CARRY = OFF_LC + 1024;
constexpr uint32_t OFF_DBG = OFF_CARRY + 1024;
constexpr uint32_t SMEM_BYTES = OFF_DBG + 768;
static_assert(SMEM_BYTES <= 232448, "smem");

struct Maps { CUtensorMap x, bre, bim, w1b, w1a, w2, cre, cim; };
__host__ __device__ constexpr uint32_t stage_off(int p) { return 49152 + 45056 * (((p >> 1) & 1) + 2 * (p & 1)); }

__host__ __device__ constexpr uint32_t full_par(int u) { return ((u - 8) / 6 + (FP != 3 && u % 6 == 0)) & 1; }

__device__ uint4 g_part[16 * 8 * 3 * 1024];
__device__ float2 g_end[8 * 16 * 64];
__device__ unsigned g_gate[SEQ];
__device__ unsigned g_epoch[128];
#define TG(role) do {} while (0)
#define TS2(role, i) do {} while (0)
#define TS(role, i) do {} while (0)
#define TDUMP() do {} while (0)
#define TR(i) do {} while (0)
#define TK(i) do {} while (0)
#define TRD() do {} while (0)

__device__ __forceinline__ void mbar_init(uint32_t bar, uint32_t cnt) { asm volatile("mbarrier.init.shared::cta.b64 [%0], %1;" ::"r"(bar), "r"(cnt)); }
__device__ __forceinline__ void mbar_expect_tx(uint32_t bar, uint32_t bytes) { asm volatile("mbarrier.arrive.expect_tx.shared::cta.b64 _, [%0], %1;" ::"r"(bar), "r"(bytes) : "memory"); }
__device__ __forceinline__ void mbar_arrive(uint32_t bar) { asm volatile("mbarrier.arrive.shared::cta.b64 _, [%0];" ::"r"(bar) : "memory"); }
__device__ __forceinline__ void mbar_arrive_cl(uint32_t cbar) { asm volatile("mbarrier.arrive.shared::cluster.b64 _, [%0];" ::"r"(cbar) : "memory"); }
__device__ __forceinline__ void mbar_wait(uint32_t bar, uint32_t parity) {
  asm volatile(
      "{\n.reg .pred p;\n.reg .u32 c;\n"
      "mbarrier.try_wait.parity.shared::cta.b64 p, [%0], %1;\n"
      "@p bra.uni LAB_DONE;\n"
      "mov.u32 c, 0;\n"
      "LAB_WAIT:\n"
      "mbarrier.try_wait.parity.shared::cta.b64 p, [%0], %1;\n"
      "@p bra.uni LAB_DONE;\n"
      "add.u32 c, c, 1;\nsetp.lt.u32 p, c, 200000;\n@p bra.uni LAB_WAIT;\n"
      "LAB_DONE:\n}" ::"r"(bar), "r"(parity) : "memory");
}
__device__ __forceinline__ void tma2d(uint32_t dst, const CUtensorMap* m, int c0, int c1, uint32_t bar) {
  asm volatile("cp.async.bulk.tensor.2d.shared::cluster.global.mbarrier::complete_tx::bytes [%0], [%1, {%3,%4}], [%2];"
               ::"r"(dst), "l"(m), "r"(bar), "r"(c0), "r"(c1) : "memory");
}
__device__ __forceinline__ void tma3d(uint32_t dst, const CUtensorMap* m, int c0, int c1, int c2, uint32_t bar) {
  asm volatile("cp.async.bulk.tensor.3d.shared::cluster.global.mbarrier::complete_tx::bytes [%0], [%1, {%3,%4,%5}], [%2];"
               ::"r"(dst), "l"(m), "r"(bar), "r"(c0), "r"(c1), "r"(c2) : "memory");
}
__device__ __forceinline__ void tma5d(uint32_t dst, const CUtensorMap* m, int c0, int c4, uint32_t bar) {
  asm volatile("cp.async.bulk.tensor.5d.shared::cluster.global.mbarrier::complete_tx::bytes [%0], [%1, {%3,%5,%5,%5,%4}], [%2];"
               ::"r"(dst), "l"(m), "r"(bar), "r"(c0), "r"(c4), "r"(0) : "memory");
}
__device__ __forceinline__ void tma5d_mc(uint32_t dst, const CUtensorMap* m, int c0, int c4, uint32_t bar) {
  asm volatile("cp.async.bulk.tensor.5d.shared::cluster.global.mbarrier::complete_tx::bytes.multicast::cluster [%0], [%1, {%3,%5,%5,%5,%4}], [%2], %6;"
               ::"r"(dst), "l"(m), "r"(bar), "r"(c0), "r"(c4), "r"(0), "h"((uint16_t)3) : "memory");
}
__device__ __forceinline__ void l2_prefetch(const void* p, uint32_t bytes) { asm volatile("cp.async.bulk.prefetch.L2.global [%0], %1;" ::"l"(p), "r"(bytes) : "memory"); }
__device__ __forceinline__ bool elect_one() {
  uint32_t pred;
  asm volatile("{.reg .pred P; elect.sync _|P, 0xffffffff; selp.u32 %0, 1, 0, P;}" : "=r"(pred));
  return pred != 0;
}
__device__ __forceinline__ void wg_fence() { asm volatile("wgmma.fence.sync.aligned;" ::: "memory"); }
__device__ __forceinline__ void wg_commit() { asm volatile("wgmma.commit_group.sync.aligned;" ::: "memory"); }
template <int N> __device__ __forceinline__ void wg_wait() { asm volatile("wgmma.wait_group.sync.aligned %0;" ::"n"(N) : "memory"); }
__device__ __forceinline__ void pin(float& a) { asm volatile("" : "+f"(a)::"memory"); }
__device__ __forceinline__ void pin(uint32_t& a) { asm volatile("" : "+r"(a)::"memory"); }
template <int N> __device__ __forceinline__ void reg_fence(float (&d)[N]) {
#pragma unroll
  for (int i = 0; i < N; i++) pin(d[i]);
}
__device__ __forceinline__ void bar_sync(int id, int n) { asm volatile("bar.sync %0, %1;" ::"r"(id), "r"(n) : "memory"); }
__device__ __forceinline__ void bar_arrive(int id, int n) { asm volatile("bar.arrive %0, %1;" ::"r"(id), "r"(n) : "memory"); }
constexpr uint32_t DH128 = (1024 >> 4) | (1u << 30), DH64 = (512 >> 4) | (2u << 30);
__host__ __device__ constexpr uint32_t lbo(uint32_t bytes) { return (bytes >> 4) << 20; }
__device__ __forceinline__ uint32_t pack_bf16(float lo, float hi) { uint32_t r; asm("cvt.rn.bf16x2.f32 %0, %1, %2;" : "=r"(r) : "f"(hi), "f"(lo)); return r; }
__device__ __forceinline__ float bf_lo(uint32_t v) { return __uint_as_float(v << 16); }
__device__ __forceinline__ float bf_hi(uint32_t v) { return __uint_as_float(v & 0xffff0000u); }
__device__ __forceinline__ float bf_ld(const __nv_bfloat16* p) { return __bfloat162float(__ldg(p)); }
__device__ __forceinline__ uint32_t late16(uint32_t bar) {
  uint32_t r;
  asm volatile("{.reg .pred p; mbarrier.test_wait.parity.shared::cta.b64 p, [%1], 0; selp.u32 %0, 16, 0, p;}" : "=r"(r) : "r"(bar) : "memory");
  return r;
}
__device__ __forceinline__ float2 lds_f2(uint32_t a) { float2 v; asm volatile("ld.shared.v2.f32 {%0,%1}, [%2];" : "=f"(v.x), "=f"(v.y) : "r"(a)); return v; }
__device__ __forceinline__ uint32_t lds_h(uint32_t a) { uint32_t v; asm volatile("ld.shared.u16 %0, [%1];" : "=r"(v) : "r"(a)); return v; }
__device__ __forceinline__ uint32_t lds_u(uint32_t a) { uint32_t v; asm volatile("ld.shared.u32 %0, [%1];" : "=r"(v) : "r"(a)); return v; }
__device__ __forceinline__ uint4 lds_u4(uint32_t a) { uint4 v; asm volatile("ld.shared.v4.u32 {%0,%1,%2,%3}, [%4];" : "=r"(v.x), "=r"(v.y), "=r"(v.z), "=r"(v.w) : "r"(a)); return v; }
__device__ __forceinline__ void st_b128(uint4* p, uint32_t a, uint32_t b, uint32_t c, uint32_t d) {
  asm volatile("st.relaxed.gpu.global.v4.b32 [%0], {%1,%2,%3,%4};" ::"l"(p), "r"(a), "r"(b), "r"(c), "r"(d) : "memory");
}
__device__ __forceinline__ void ld_b128(const uint4* p, uint32_t& a, uint32_t& b, uint32_t& c, uint32_t& d) {
  asm volatile("{.reg .b64 l, h; .reg .b128 v; ld.relaxed.gpu.global.b128 v, [%4]; mov.b128 {l,h}, v; mov.b64 {%0,%1}, l; mov.b64 {%2,%3}, h;}"
               : "=r"(a), "=r"(b), "=r"(c), "=r"(d) : "l"(p) : "memory");
}
__device__ __forceinline__ float tanh_fast(float x) { float y; asm("tanh.approx.f32 %0, %1;" : "=f"(y) : "f"(x)); return y; }
__device__ __forceinline__ float gelu2(float v) {
  float p = fmaf(v * v, 0.0356774081363f, 0.7978845608029f);
  return fmaf(v, tanh_fast(v * p), v);
}
__device__ __forceinline__ void sched_fence(uint32_t& ck) { asm volatile("{.reg .b32 c; mov.u32 c, %%clock; xor.b32 %0, %0, c;}" : "+r"(ck)::"memory"); }
__device__ __forceinline__ uint32_t bf2_mul(uint32_t a, uint32_t b) { uint32_t r; asm("mul.rn.bf16x2 %0, %1, %2;" : "=r"(r) : "r"(a), "r"(b)); return r; }
__device__ __forceinline__ uint32_t bf2_add(uint32_t a, uint32_t b) { uint32_t r; asm("add.rn.bf16x2 %0, %1, %2;" : "=r"(r) : "r"(a), "r"(b)); return r; }
__device__ __forceinline__ uint32_t bf2_fma(uint32_t a, uint32_t b, uint32_t c) { uint32_t r; asm("fma.rn.bf16x2 %0, %1, %2, %3;" : "=r"(r) : "r"(a), "r"(b), "r"(c)); return r; }
__device__ __forceinline__ uint32_t gelu2_pair(float a, float b) {
  const uint32_t v = pack_bf16(a, b);
  uint32_t t;
  asm("tanh.approx.bf16x2 %0, %1;" : "=r"(t) : "r"(bf2_fma(v, bf2_fma(bf2_mul(v, v), 0x3d123d12u, 0xbe4fbe4fu), v)));
  return bf2_fma(v, t, v);
}
struct cplx { float re, im; };
__device__ __forceinline__ cplx cmul(cplx a, cplx b) { return {fmaf(a.re, b.re, -a.im * b.im), fmaf(a.re, b.im, a.im * b.re)}; }
__device__ __forceinline__ cplx cfma(cplx a, cplx b, cplx c) {
  return {fmaf(a.re, b.re, fmaf(-a.im, b.im, c.re)), fmaf(a.re, b.im, fmaf(a.im, b.re, c.im))};
}
__device__ __forceinline__ cplx make_lam(float lre, float lim, float ldt) {
  float dt = __bfloat162float(__float2bfloat16_rn(expf(ldt)));
  float mag = expf(dt * lre), sn, cs;
  sincospif(dt * lim * 0.31830988618379067f, &sn, &cs);
  return {mag * cs, mag * sn};
}

template <int NG>
__device__ __forceinline__ void gate_rows(uint32_t sb, int lane, int xrot, int row0, uint4 (&gw)[4], const uint4* gwp, unsigned* dst, unsigned par) {
  const int row = row0 + (lane >> 3);
  const uint32_t xr0 = sb + OFF_X + row * 128 + (((lane & 7) ^ (row & 7)) << 4), xr1 = (xr0 + 512) ^ 64;
  float z[NG], y[NG];
#pragma unroll
  for (int r = 0; r < NG; r++) z[r] = y[r] = 0.f;
#pragma unroll
  for (int kb = 0; kb < 8; kb++) {
    const uint4 w = gw[kb & 3];
    if (kb < 4) gw[kb] = __ldg(gwp + (kb + 4) * 8);
    mbar_wait(sb + OFF_XFULL + 8 * kb, 0);
#pragma unroll
    for (int r = 0; r < NG; r++) {
      const uint4 a = lds_u4((r ? xr1 : xr0) + ((kb + xrot) & 7) * 16384);
      const uint32_t p[4] = {bf2_mul(a.x, w.x), bf2_mul(a.y, w.y), bf2_mul(a.z, w.z), bf2_mul(a.w, w.w)};
#pragma unroll
      for (int c = 0; c < 4; c++) { z[r] += bf_lo(p[c]); y[r] += bf_hi(p[c]); }
    }
  }
  float zz = z[0] + y[0];
  if (NG == 2) {
    const float z1 = z[NG - 1] + y[NG - 1];
    zz = ((lane & 4) ? z1 : zz) + __shfl_xor_sync(0xffffffffu, (lane & 4) ? zz : z1, 4);
  } else {
    zz += __shfl_xor_sync(0xffffffffu, zz, 4);
  }
  zz += __shfl_xor_sync(0xffffffffu, zz, 2);
  zz += __shfl_xor_sync(0xffffffffu, zz, 1);
  zz = bf_lo(pack_bf16(zz, 0.f));
  const float rho = 4.f * expf(zz > 40.f ? 40.f : zz);
  if ((lane & (NG == 2 ? 3 : 7)) == 0)
    asm volatile("st.relaxed.gpu.global.u32 [%0], %1;" ::"l"(dst + row + (lane & 4)), "r"((__float_as_uint(rho) & ~1u) | par) : "memory");
}

template<int TA,int TB,uint32_t AH,uint32_t BH> __device__ __forceinline__ void wgmma_n64_ss(float (&d)[32], uint32_t al, uint32_t ao, uint32_t bl, uint32_t bo, int scale_d){
  asm volatile("{.reg .pred p; .reg .b32 t, v; .reg .b64 da, db; setp.ne.b32 p, %36, 0; add.u32 t, %32, %33; mov.b64 da, {t, %39}; add.u32 v, %34, %35; mov.b64 db, {v, %40};\n"
   "wgmma.mma_async.sync.aligned.m64n64k16.f32.bf16.bf16 {%0,%1,%2,%3,%4,%5,%6,%7,%8,%9,%10,%11,%12,%13,%14,%15,%16,%17,%18,%19,%20,%21,%22,%23,%24,%25,%26,%27,%28,%29,%30,%31}, da, db, p, 1, 1, %37, %38;}"
   : "+f"(d[0]),"+f"(d[1]),"+f"(d[2]),"+f"(d[3]),"+f"(d[4]),"+f"(d[5]),"+f"(d[6]),"+f"(d[7]),"+f"(d[8]),"+f"(d[9]),"+f"(d[10]),"+f"(d[11]),"+f"(d[12]),"+f"(d[13]),"+f"(d[14]),"+f"(d[15]),"+f"(d[16]),"+f"(d[17]),"+f"(d[18]),"+f"(d[19]),"+f"(d[20]),"+f"(d[21]),"+f"(d[22]),"+f"(d[23]),"+f"(d[24]),"+f"(d[25]),"+f"(d[26]),"+f"(d[27]),"+f"(d[28]),"+f"(d[29]),"+f"(d[30]),"+f"(d[31])
   : "r"(al),"r"(ao >> 4),"r"(bl),"r"(bo >> 4),"r"(scale_d),"n"(TA),"n"(TB),"n"(AH),"n"(BH));
}
template<int TB,uint32_t BH,int SA=1> __device__ __forceinline__ void wgmma_n64_rs(float (&d)[32], uint32_t a0,uint32_t a1,uint32_t a2,uint32_t a3, uint32_t bl, uint32_t bo, int scale_d){
  asm volatile("{.reg .pred p; .reg .b32 t; .reg .b64 db; setp.ne.b32 p, %38, 0; add.u32 t, %36, %37; mov.b64 db, {t, %40};\n"
   "wgmma.mma_async.sync.aligned.m64n64k16.f32.bf16.bf16 {%0,%1,%2,%3,%4,%5,%6,%7,%8,%9,%10,%11,%12,%13,%14,%15,%16,%17,%18,%19,%20,%21,%22,%23,%24,%25,%26,%27,%28,%29,%30,%31}, {%32,%33,%34,%35}, db, p, %41, 1, %39;}"
   : "+f"(d[0]),"+f"(d[1]),"+f"(d[2]),"+f"(d[3]),"+f"(d[4]),"+f"(d[5]),"+f"(d[6]),"+f"(d[7]),"+f"(d[8]),"+f"(d[9]),"+f"(d[10]),"+f"(d[11]),"+f"(d[12]),"+f"(d[13]),"+f"(d[14]),"+f"(d[15]),"+f"(d[16]),"+f"(d[17]),"+f"(d[18]),"+f"(d[19]),"+f"(d[20]),"+f"(d[21]),"+f"(d[22]),"+f"(d[23]),"+f"(d[24]),"+f"(d[25]),"+f"(d[26]),"+f"(d[27]),"+f"(d[28]),"+f"(d[29]),"+f"(d[30]),"+f"(d[31])
   : "r"(a0),"r"(a1),"r"(a2),"r"(a3),"r"(bl),"r"(bo >> 4),"r"(scale_d),"n"(TB),"n"(BH),"n"(SA));
}
template<int TA,int TB,uint32_t AH,uint32_t BH> __device__ __forceinline__ void wgmma_n96_ss(float (&d)[48], uint32_t al, uint32_t ao, uint32_t bl, uint32_t bo, int scale_d){
  asm volatile("{.reg .pred p; .reg .b32 t, v; .reg .b64 da, db; setp.ne.b32 p, %52, 0; add.u32 t, %48, %49; mov.b64 da, {t, %55}; add.u32 v, %50, %51; mov.b64 db, {v, %56};\n"
   "wgmma.mma_async.sync.aligned.m64n96k16.f32.bf16.bf16 {%0,%1,%2,%3,%4,%5,%6,%7,%8,%9,%10,%11,%12,%13,%14,%15,%16,%17,%18,%19,%20,%21,%22,%23,%24,%25,%26,%27,%28,%29,%30,%31,%32,%33,%34,%35,%36,%37,%38,%39,%40,%41,%42,%43,%44,%45,%46,%47}, da, db, p, 1, 1, %53, %54;}"
   : "+f"(d[0]),"+f"(d[1]),"+f"(d[2]),"+f"(d[3]),"+f"(d[4]),"+f"(d[5]),"+f"(d[6]),"+f"(d[7]),"+f"(d[8]),"+f"(d[9]),"+f"(d[10]),"+f"(d[11]),"+f"(d[12]),"+f"(d[13]),"+f"(d[14]),"+f"(d[15]),"+f"(d[16]),"+f"(d[17]),"+f"(d[18]),"+f"(d[19]),"+f"(d[20]),"+f"(d[21]),"+f"(d[22]),"+f"(d[23]),"+f"(d[24]),"+f"(d[25]),"+f"(d[26]),"+f"(d[27]),"+f"(d[28]),"+f"(d[29]),"+f"(d[30]),"+f"(d[31]),"+f"(d[32]),"+f"(d[33]),"+f"(d[34]),"+f"(d[35]),"+f"(d[36]),"+f"(d[37]),"+f"(d[38]),"+f"(d[39]),"+f"(d[40]),"+f"(d[41]),"+f"(d[42]),"+f"(d[43]),"+f"(d[44]),"+f"(d[45]),"+f"(d[46]),"+f"(d[47])
   : "r"(al),"r"(ao >> 4),"r"(bl),"r"(bo >> 4),"r"(scale_d),"n"(TA),"n"(TB),"n"(AH),"n"(BH));
}
template<int TA,int TB,uint32_t AH,uint32_t BH> __device__ __forceinline__ void wgmma_n128_ss(float (&d)[64], uint32_t al, uint32_t ao, uint32_t bl, uint32_t bo, int scale_d){
  asm volatile("{.reg .pred p; .reg .b32 t, v; .reg .b64 da, db; setp.ne.b32 p, %68, 0; add.u32 t, %64, %65; mov.b64 da, {t, %71}; add.u32 v, %66, %67; mov.b64 db, {v, %72};\n"
   "wgmma.mma_async.sync.aligned.m64n128k16.f32.bf16.bf16 {%0,%1,%2,%3,%4,%5,%6,%7,%8,%9,%10,%11,%12,%13,%14,%15,%16,%17,%18,%19,%20,%21,%22,%23,%24,%25,%26,%27,%28,%29,%30,%31,%32,%33,%34,%35,%36,%37,%38,%39,%40,%41,%42,%43,%44,%45,%46,%47,%48,%49,%50,%51,%52,%53,%54,%55,%56,%57,%58,%59,%60,%61,%62,%63}, da, db, p, 1, 1, %69, %70;}"
   : "+f"(d[0]),"+f"(d[1]),"+f"(d[2]),"+f"(d[3]),"+f"(d[4]),"+f"(d[5]),"+f"(d[6]),"+f"(d[7]),"+f"(d[8]),"+f"(d[9]),"+f"(d[10]),"+f"(d[11]),"+f"(d[12]),"+f"(d[13]),"+f"(d[14]),"+f"(d[15]),"+f"(d[16]),"+f"(d[17]),"+f"(d[18]),"+f"(d[19]),"+f"(d[20]),"+f"(d[21]),"+f"(d[22]),"+f"(d[23]),"+f"(d[24]),"+f"(d[25]),"+f"(d[26]),"+f"(d[27]),"+f"(d[28]),"+f"(d[29]),"+f"(d[30]),"+f"(d[31]),"+f"(d[32]),"+f"(d[33]),"+f"(d[34]),"+f"(d[35]),"+f"(d[36]),"+f"(d[37]),"+f"(d[38]),"+f"(d[39]),"+f"(d[40]),"+f"(d[41]),"+f"(d[42]),"+f"(d[43]),"+f"(d[44]),"+f"(d[45]),"+f"(d[46]),"+f"(d[47]),"+f"(d[48]),"+f"(d[49]),"+f"(d[50]),"+f"(d[51]),"+f"(d[52]),"+f"(d[53]),"+f"(d[54]),"+f"(d[55]),"+f"(d[56]),"+f"(d[57]),"+f"(d[58]),"+f"(d[59]),"+f"(d[60]),"+f"(d[61]),"+f"(d[62]),"+f"(d[63])
   : "r"(al),"r"(ao >> 4),"r"(bl),"r"(bo >> 4),"r"(scale_d),"n"(TA),"n"(TB),"n"(AH),"n"(BH));
}

__global__ void __cluster_dims__(2, 1, 1) __launch_bounds__(384, 1)
fused_kernel(const __nv_bfloat16* __restrict__ lam_re, const __nv_bfloat16* __restrict__ lam_im, const __nv_bfloat16* __restrict__ log_dt,
             const __nv_bfloat16* __restrict__ dskip, const __nv_bfloat16* __restrict__ b1, const __nv_bfloat16* __restrict__ b2,
             const __nv_bfloat16* __restrict__ gate_w, const __nv_bfloat16* __restrict__ pf_w1, const __nv_bfloat16* __restrict__ pf_w2,
             const __nv_bfloat16* __restrict__ pf_cre, const __nv_bfloat16* __restrict__ pf_cim, float* __restrict__ out,
             const __grid_constant__ Maps maps) {
  extern __shared__ __align__(1024) unsigned char smem_raw[];
  uint32_t sb = (uint32_t)__cvta_generic_to_shared(smem_raw);
  if (EP == 1 && threadIdx.x == 352) {
    asm volatile("prefetch.tensormap [%0];" ::"l"(&maps.x) : "memory");
    asm volatile("prefetch.tensormap [%0];" ::"l"(&maps.bre) : "memory");
    asm volatile("prefetch.tensormap [%0];" ::"l"(&maps.bim) : "memory");
  }
  if (EP == 2 && elect_one()) {
    asm volatile("prefetch.tensormap [%0];" ::"l"(&maps.x) : "memory");
    asm volatile("prefetch.tensormap [%0];" ::"l"(&maps.bre) : "memory");
    asm volatile("prefetch.tensormap [%0];" ::"l"(&maps.bim) : "memory");
  }
  int tid_ = threadIdx.x;
  const int b = blockIdx.x;
  const int rank = b & 1, cl = b >> 1;
  const int sp = (cl & 1) | ((cl >> 2) & 2), m = ((cl >> 1) & 3) | ((cl >> 4) << 2);
  const int s = sp * 2 + rank;
  const int xrot = 9 - 2 * sp;
  if (FP == 1 ? threadIdx.x == 0 : (threadIdx.x < 32 && elect_one())) {
    mbar_init(sb + OFF_XFULL, 1);
    mbar_expect_tx(sb + OFF_XFULL, FP == 3 ? 32768 : 16384);
    tma5d(sb + OFF_X + (xrot & 7) * 16384, &maps.x, 0, 2 * m, sb + OFF_XFULL);
    if (FP == 3) tma2d(sb + OFF_RING, &maps.bre, 0, s * 64, sb + OFF_XFULL);
    tma5d(sb + OFF_X + (xrot & 7) * 16384 + 8192, &maps.x, 0, 2 * m + 1, sb + OFF_XFULL);
    if (FP == 3) tma2d(sb + OFF_RING + 8192, &maps.bim, 0, s * 64, sb + OFF_XFULL);
    TS(2, 3);
  }
  if (FP != 3 && (FP == 1 ? threadIdx.x == 128 : ((threadIdx.x >> 5) == 4 && elect_one()))) {
    mbar_init(sb + OFF_FULL, 1);
    mbar_expect_tx(sb + OFF_FULL, 16384);
    tma2d(sb + OFF_RING, &maps.bre, 0, s * 64, sb + OFF_FULL);
    tma2d(sb + OFF_RING + 8192, &maps.bim, 0, s * 64, sb + OFF_FULL);
    TS(2, 4);
  }
  const int warp = __shfl_sync(0xffffffffu, (int)(threadIdx.x >> 5), 0);
  const int lane0 = threadIdx.x & 31;

  if (elect_one()) {
    if (warp > 8) {
      if (EP == 0) asm volatile("prefetch.tensormap [%0];" ::"l"(&maps.x + (warp - 9)) : "memory");
      mbar_init(sb + OFF_GBAR + 8 * (warp - 9), warp < 11 ? 64 : 96);
    }
    const uint32_t c = warp < 8 ? 1 : warp < 11 ? 8 : 4, bar = sb + OFF_XFULL + 16 * warp;
    if (FP == 3 ? warp != 0 : (warp & 11) != 0) mbar_init(bar, c);
    mbar_init(bar + 8, c);
    asm volatile("fence.mbarrier_init.release.cluster;" ::: "memory");
  }
  __syncwarp();
  asm volatile("barrier.cluster.arrive.relaxed.aligned;" ::: "memory");

  if (warp < 8) {
    const int lane = OPQ ? __shfl_sync(0xffffffffu, lane0, lane0) : lane0;
    tid_ = warp * 32 + lane;
    if (OPS) sb = __shfl_sync(0xffffffffu, sb, 0);
    const int wg = warp >> 2, w = warp & 3, q = lane & 3, gr = lane >> 2;
    uint32_t bv[28];
#pragma unroll
    for (int j = 0; j < 28; j++) bv[j] = __ldg(reinterpret_cast<const uint32_t*>(b1 + s * 224 + j * 8) + q);
    asm volatile("setmaxnreg.inc.sync.aligned.u32 224;");
    asm volatile("barrier.cluster.wait.aligned;" ::: "memory");
    TS(wg, 0);
    auto release = [&](int slot) {
      if (REL) asm volatile("{.reg .pred P; elect.sync _|P, 0xffffffff; @P mbarrier.arrive.shared::cta.b64 _, [%0];}" ::"r"(sb + OFF_EMPTY + 8 * slot) : "memory");
      else if (lane == 0) mbar_arrive(sb + OFF_EMPTY + 8 * slot);
    };
    const uint32_t xw = sb + OFF_X + wg * 8192, fullb = sb + OFF_FULL;
    const uint32_t dxw = (xw & 0x3FFFF) >> 4, dring = ((sb + OFF_RING) & 0x3FFFF) >> 4;

    float ure[32], uim[32], aa[48], ab[64];
    cplx lam[2], coef[2], l16[2], l32[2], lq[2], pre[2], e[2];
    uint32_t sh16, mhi, ck = 0;

    auto bias = [&](int c) {
#pragma unroll
      for (int j = c * 7; j < c * 7 + 7; j++) {
        pin(bv[j]);
        float* d = j < 12 ? aa + 4 * j : ab + 4 * (j - 12);
        d[0] = d[2] = __uint_as_float(bv[j] << sh16); d[1] = d[3] = __uint_as_float(bv[j] & mhi);
        pin(d[0]); pin(d[1]); pin(d[2]); pin(d[3]);
      }
    };
#pragma unroll
    for (int kb = 0; kb < 8; kb++) {
      const int slot = kb % NSLOT;
      mbar_wait(sb + OFF_XFULL + 8 * kb, 0);
      if (kb == 0) TS(wg, 18);
      if (kb == 0 && FP != 3) mbar_wait(fullb, 0);
      TS2(2, kb);
      if (kb == 0) TS(wg, 1);
      if (kb == L16K) { sh16 = late16(sb + OFF_XFULL); mhi = 0xffffffffu << sh16; }
      if (kb == LCK) {
        mbar_wait(sb + OFF_LBAR, 0);
#pragma unroll
        for (int h = 0; h < 2; h++) {
          const uint4 v = lds_u4(sb + OFF_LC + (w * 16 + gr + 8 * h) * 16);
          lam[h] = cplx{__uint_as_float(v.x), __uint_as_float(v.y)};
          coef[h] = cplx{__uint_as_float(v.z), __uint_as_float(v.w)};
        }
      }
      wg_fence();
      const uint32_t dxa = dxw + ((kb + xrot) & 7) * 1024;
#pragma unroll
      for (int kk = 0; kk < 4; kk++) {
        wgmma_n64_ss<0, 0, DH128, DH128>(ure, dring, slot * 16384 + kk * 32, dxa, kk * 32, (kb | kk) != 0);
        wgmma_n64_ss<0, 0, DH128, DH128>(uim, dring, slot * 16384 + 8192 + kk * 32, dxa, kk * 32, (kb | kk) != 0);
      }
      wg_commit();
      if (kb > 0) { wg_wait<1>(); release((kb - 1) % NSLOT); }
      if (kb == B0K) bias(0);
      if (kb == B1K) bias(1);
      if (kb == B2K) bias(2);
      if (kb == B3K) bias(3);
      if (kb == 6) {
#pragma unroll
        for (int h = 0; h < 2; h++) {
          pin(lam[h].re); pin(lam[h].im);
          cplx t = cmul(lam[h], lam[h]); t = cmul(t, t); t = cmul(t, t);
          l16[h] = cmul(t, t);
          pin(l16[h].re); pin(l16[h].im);
        }
      }
      if (kb == 7) {
#pragma unroll
        for (int h = 0; h < 2; h++) {
          pin(l16[h].re); pin(l16[h].im);
          l32[h] = cmul(l16[h], l16[h]);
          const cplx a = (q & 1) ? l16[h] : cplx{1.f, 0.f}, c = (q & 2) ? l32[h] : cplx{1.f, 0.f};
          lq[h] = cmul(cmul(a, c), coef[h]);
          pin(lq[h].re); pin(lq[h].im);
          if (Q1) {
            if (q < 2) l16[h] = cplx{0.f, 0.f};
            if (q < 3) l32[h] = cplx{0.f, 0.f};
            pin(l16[h].re); pin(l16[h].im); pin(l32[h].re); pin(l32[h].im);
          }
        }
      }
    }
    TS(wg, 2);
    auto scale_u = [&](int i0, int i1) {
#pragma unroll
      for (int i = 0; i < 32; i++) if (i >= i0 && i < i1) {
        pin(ure[i]); pin(uim[i]);
        const cplx v = cmul(coef[(i >> 1) & 1], cplx{ure[i], uim[i]});
        ure[i] = v.re; uim[i] = v.im;
        pin(ure[i]); pin(uim[i]);
      }
    };
#pragma unroll
    for (int kb = 0; kb < 8; kb++) {
      const int u = 8 + kb, slot = u % NSLOT;
      mbar_wait(fullb + 8 * slot, full_par(u));
      TK(kb);
      wg_fence();
      const uint32_t dxa = dxw + ((kb + xrot) & 7) * 1024;
#pragma unroll
      for (int kk = 0; kk < 4; kk++)
        wgmma_n96_ss<0, 1, DH128, DH64>(aa, dxa, kk * 32, dring, slot * 16384 + kk * 1024 + lbo(4096), 1);
      wg_commit();
      if (kb + 8 == B3K) bias(3);
      if (kb != QK) { wg_wait<1>(); release((u - 1) % NSLOT); }
      if (kb == 0) {
        reg_fence(ure); reg_fence(uim);
#pragma unroll
        for (int h = 0; h < 2; h++) e[h] = cplx{ure[2 * h], uim[2 * h]};
      }
      if (kb == 0 || (kb >= 2 && kb <= QK && kb < 4)) {
        constexpr int tc[5] = TCUT;
#pragma unroll
        for (int t = 1; t < 16; t++) if (t >= tc[kb] && t < tc[kb + 1]) {
#pragma unroll
          for (int h = 0; h < 2; h++) { const int i = 4 * (t >> 1) + 2 * h + (t & 1); e[h] = cfma(lam[h], e[h], cplx{ure[i], uim[i]}); }
        }
#pragma unroll
        for (int h = 0; h < 2; h++) { pin(e[h].re); pin(e[h].im); }
      }
      if (kb == QK) {
        { constexpr int sc[9] = SCUT; scale_u(sc[kb], sc[kb + 1]); }
        if (QF) sched_fence(ck);
#pragma unroll
        for (int h = 0; h < 2; h++) {
          cplx y = {__shfl_up_sync(0xffffffffu, e[h].re, 1, 4), __shfl_up_sync(0xffffffffu, e[h].im, 1, 4)};
          if (q >= 1) e[h] = cfma(l16[h], y, e[h]);
          y = cplx{__shfl_up_sync(0xffffffffu, e[h].re, 2, 4), __shfl_up_sync(0xffffffffu, e[h].im, 2, 4)};
          if (q >= 2) e[h] = cfma(l32[h], y, e[h]);
        }
        if (q == 3) {
#pragma unroll
          for (int h = 0; h < 2; h++)
            asm volatile("st.shared.v2.f32 [%0], {%1,%2};" ::"r"(sb + OFF_CARRY + wg * 512 + (w * 16 + gr + 8 * h) * 8), "f"(e[h].re), "f"(e[h].im) : "memory");
          mbar_arrive(sb + OFF_GBAR);
        }
#pragma unroll
        for (int h = 0; h < 2; h++) e[h] = cplx{__shfl_up_sync(0xffffffffu, e[h].re, 1, 4), __shfl_up_sync(0xffffffffu, e[h].im, 1, 4)};
        wg_wait<1>(); release((u - 1) % NSLOT);
        if (TKT > 500) TS(wg, 3);
      }
      if (kb == QK + 1) {
#pragma unroll
        for (int h = 0; h < 2; h++) {
          pre[h] = Q1 ? cmul(coef[h], pre[h]) : (q >= 1) ? cmul(coef[h], e[h]) : cplx{0.f, 0.f};
          pin(pre[h].re); pin(pre[h].im);
        }
      }
      if (kb > QK) { constexpr int sc[9] = SCUT; scale_u(sc[kb], sc[kb + 1]); }
    }
    TS(wg, 4);
    uint32_t H[56], hf[32];
    cplx hst[2];
    const uint32_t hst_addr = xw + (w * 16 + (lane & 15)) * 128 + (((lane >> 4) ^ (lane & 7)) << 4);
    const uint32_t him = (2 - rank) * 16384;
    uint32_t peer;
    asm volatile("mapa.shared::cluster.u32 %0, %1, %2;" : "=r"(peer) : "r"(sb), "r"(rank ^ 1));
    auto credit = [&]() { if (lane == 0) mbar_arrive_cl(peer + OFF_KBAR + wg * 8); };
    uint32_t g2[8];
#pragma unroll
    for (int kb = 0; kb < 8; kb++) {
      const int u = 16 + kb, slot = u % NSLOT;
      mbar_wait(fullb + 8 * slot, full_par(u));
      TK(kb < 7 ? 24 + kb : 32);
      wg_fence();
#pragma unroll
      for (int kk = 0; kk < 4; kk++)
        wgmma_n128_ss<0, 1, DH128, DH128>(ab, dxw, kb * 16384 + kk * 32, dring, slot * 16384 + kk * 2048 + lbo(8192), 1);
      wg_commit();
      if (kb == 0) { constexpr int sc[9] = SCUT; scale_u(sc[8], 32); }
      if (kb == 4) {
        if (TKT > 500) TS(wg, 5);
        mbar_wait(sb + OFF_CBAR, 0);
        if (TKT > 500) TS(wg, 6);
#pragma unroll
        for (int h = 0; h < 2; h++) {
          const float2 c = lds_f2(sb + OFF_CARRY + wg * 512 + (w * 16 + gr + 8 * h) * 8);
          hst[h] = cfma(lq[h], cplx{c.x, c.y}, pre[h]);
        }
#pragma unroll
        for (int i = 0; i < 2; i++) {
          const uint4 v = lds_u4(sb + OFF_GT + wg * 128 + q * 32 + i * 16);
          g2[4 * i] = v.x; g2[4 * i + 1] = v.y; g2[4 * i + 2] = v.z; g2[4 * i + 3] = v.w;
        }
      }
      if (kb == 0 || TOKB != 1) { wg_wait<1>(); release((u - 1) % NSLOT); }
      if (kb) sched_fence(ck);
      if (kb < 4) {
#pragma unroll
        for (int i = kb * 6; i < kb * 6 + 6; i++) {
          pin(aa[2 * i]); pin(aa[2 * i + 1]);
          H[i] = gelu2_pair(aa[2 * i], aa[2 * i + 1]);
          pin(H[i]);
        }
      } else {
        const int j0 = (kb - 4) * 2;
        uint32_t rr[4], ri[4];
#pragma unroll
        for (int jj = 0; jj < 2; jj++) {
          const int j = j0 + jj;
#pragma unroll
          for (int h = 0; h < 2; h++) {
            const int i = 4 * j + 2 * h;
            const cplx h0 = cfma(lam[h], hst[h], cplx{ure[i], uim[i]});
            hst[h] = cfma(lam[h], h0, cplx{ure[i + 1], uim[i + 1]});
            rr[jj * 2 + h] = bf2_mul(pack_bf16(h0.re, hst[h].re), g2[j]);
            ri[jj * 2 + h] = bf2_mul(pack_bf16(h0.im, hst[h].im), g2[j]);
          }
        }
        const uint32_t a = hst_addr ^ (j0 << 4);
        asm volatile("stmatrix.sync.aligned.m8n8.x4.shared.b16 [%0], {%1,%2,%3,%4};" ::"r"(a), "r"(rr[0]), "r"(rr[1]), "r"(rr[2]), "r"(rr[3]) : "memory");
        asm volatile("stmatrix.sync.aligned.m8n8.x4.shared.b16 [%0], {%1,%2,%3,%4};" ::"r"(a + him), "r"(ri[0]), "r"(ri[1]), "r"(ri[2]), "r"(ri[3]) : "memory");
      }
      if (kb && TOKB == 1) { wg_wait<1>(); release((u - 1) % NSLOT); }
    }
    TS(wg, 7);

    uint4* const psend = g_part + (size_t)(m * 8 + rank) * 3072 + warp * 128 + lane;
    const uint4* const precv = g_part + (size_t)(m * 8 + s) * 3072 + warp * 128 + lane;
    const uint32_t pbuf = OFF_X + warp * 2048 + lane * 16;
    const uint32_t dx0 = ((sb + OFF_X) & 0x3FFFF) >> 4;
    float o[32], fin[32], rho[2];
    uint32_t tr[8];
    uint32_t r0[16], pt[16], sum[16], tag;
    auto recv_issue = [&](uint32_t (&r)[16], int k) {
#pragma unroll
      for (int i = 0; i < 4; i++) ld_b128(precv + k * 1024 + i * 32, r[4 * i], r[4 * i + 1], r[4 * i + 2], r[4 * i + 3]);
    };
    auto stale = [&](uint32_t (&r)[16]) {
      uint32_t r_;
#pragma unroll
      for (int i = 0; i < 16; i += 4) asm("lop3.b32 %0, %0, %1, 1, 0x78;" : "+r"(r[i]) : "r"(tag));
      asm volatile("{.reg .pred p; .reg .b32 t; lop3.b32 t, %1, %2, %3, 0xfe; lop3.b32 t, t, %4, 1, 0xa8; setp.ne.u32 p, t, 0; vote.sync.any.pred p, p, 0xffffffff; selp.u32 %0, 1, 0, p;}"
                   : "=r"(r_) : "r"(r[0]), "r"(r[4]), "r"(r[8]), "r"(r[12]));
      return r_ != 0;
    };
    auto recv_check = [&](uint32_t (&r)[16], int k) {
      if (__builtin_expect(stale(r), 0)) {
        int tries = 0;
#pragma unroll 1
        do { recv_issue(r, k); } while (stale(r) && ++tries < 200000);
      }
    };
    auto gelu_b = [&](int i0, int i1) {
      if (TOKD && i0) sched_fence(ck);
#pragma unroll
      for (int i = i0; i < i1; i++) {
        pin(ab[2 * i]); pin(ab[2 * i + 1]);
        H[24 + i] = gelu2_pair(ab[2 * i], ab[2 * i + 1]);
        pin(H[24 + i]);
      }
      if (TOKD == 2) sched_fence(ck);
    };
    auto step = [&](float (&d)[32], int p, int k, int acc) {
      const uint32_t wo = stage_off(p);
      if (k >= 6 && k < 14) {
        const int kk = k - 6;
        if (kk < 4) wgmma_n64_rs<0, DH128, 1>(d, hf[4 * kk], hf[4 * kk + 1], hf[4 * kk + 2], hf[4 * kk + 3], dx0, wo + 14336 + kk * 32, 1);
        else wgmma_n64_rs<0, DH128, -1>(d, hf[4 * kk], hf[4 * kk + 1], hf[4 * kk + 2], hf[4 * kk + 3], dx0, wo + 22528 + (kk - 4) * 32, 1);
      } else {
        const int kk = k < 6 ? k : k - 8;
        wgmma_n64_rs<1, DH128>(d, H[4 * kk], H[4 * kk + 1], H[4 * kk + 2], H[4 * kk + 3], dx0, wo + (kk / 7) * 30720 + (kk % 7) * 2048, k != 0 || acc);
      }
    };
    auto mma = [&](float (&d)[32], int p, int k0, int k1, int acc) {
      wg_fence();
#pragma unroll
      for (int k = k0; k < k1; k++) step(d, p, k, acc);
      wg_commit();
    };
    auto send_peer = [&](float (&d)[32], uint32_t off) {
#pragma unroll
      for (int i = 0; i < 4; i++)
        asm volatile("st.async.shared::cluster.mbarrier::complete_tx::bytes.v4.b32 [%0], {%1,%2,%3,%4}, [%5];" ::"r"(peer + pbuf + off + i * 512),
                     "r"(pack_bf16(d[8 * i], d[8 * i + 1])), "r"(pack_bf16(d[8 * i + 2], d[8 * i + 3])), "r"(pack_bf16(d[8 * i + 4], d[8 * i + 5])),
                     "r"(pack_bf16(d[8 * i + 6], d[8 * i + 7])), "r"(peer + OFF_RBAR + wg * 8) : "memory");
    };
    auto read_peer = [&](uint32_t (&r)[16], uint32_t off) {
#pragma unroll
      for (int i = 0; i < 4; i++) { const uint4 v = lds_u4(sb + pbuf + off + i * 512); r[4 * i] = v.x; r[4 * i + 1] = v.y; r[4 * i + 2] = v.z; r[4 * i + 3] = v.w; }
    };
    auto send_owner = [&](uint32_t (&r)[16], int k) {
#pragma unroll
      for (int i = 0; i < 4; i++) {
#pragma unroll
        for (int c = 4 * i; c < 4 * i + 4; c++) r[c] = bf2_add(r[c], pack_bf16(o[2 * c], o[2 * c + 1]));
        asm("lop3.b32 %0, %0, 1, %1, 0xb8;" : "+r"(r[4 * i]) : "r"(tag));
        st_b128(psend + (((sp + 1 + k) & 3) * 6 + k) * 1024 + i * 32, r[4 * i], r[4 * i + 1], r[4 * i + 2], r[4 * i + 3]);
      }
    };
    auto load_fin = [&]() {
      mbar_wait(sb + OFF_LBAR, 1);
#pragma unroll
      for (int j = 0; j < 8; j++) {
        const uint4 v = lds_u4(sb + pbuf + (j < 4 ? 49152 - him : him) + (j & 3) * 512);
        fin[4 * j] = __uint_as_float(v.x); fin[4 * j + 1] = __uint_as_float(v.y); fin[4 * j + 2] = __uint_as_float(v.z); fin[4 * j + 3] = __uint_as_float(v.w);
      }
    };
    auto ldk = [&](int pos) { if (pos == K0P) recv_issue(sum, 0); if (pos == K1P) recv_issue(r0, 1); };
    uint32_t ta, la;
    float* op;
    auto out_addr = [&]() {
      const uint32_t tb = sb + OFF_X + stage_off(0) + warp * 4096;
      ta = tb + gr * 256 + ((gr & 3) << 5) + q * 8;
      la = tb + (lane >> 3) * 256 + (((lane & 7) << 4) ^ ((lane >> 3) << 5));
      op = out + (size_t)(m * 128 + wg * 64 + (lane >> 4) * 16 + w * 4 + ((lane >> 3) & 1)) * DM + s * 64 + (lane & 7) * 4;
      if (ADP) { pin(ta); pin(la); asm volatile("" : "+l"(op)); sched_fence(ck); }
    };
    auto arm = [&](uint32_t bytes) { if ((w == 0 && lane == 0)) mbar_expect_tx(sb + OFF_RBAR + wg * 8, bytes); };
    auto mma2 = [&](int k0, int k1) {
      wg_fence();
#pragma unroll
      for (int k = k0; k < k1; k++) { step(o, 0, k, 0); step(fin, 1, k, 0); }
      wg_commit();
    };
    auto hand = [&](int pos) { if (A0 == pos && wg == 0) bar_arrive(5, 256); };
    {
        constexpr int kc[8] = DCUT;
        mbar_wait(fullb, full_par(24));
        mma2(0, kc[0]);
        bar_sync(1 + wg, 128);
        {
          const uint32_t ha = xw + ((lane >> 4) * 8 + (lane & 7)) * 128 + (((2 * w + ((lane >> 3) & 1)) ^ (lane & 7)) << 4);
#pragma unroll
          for (int kk = 0; kk < 8; kk++)
            asm volatile("ldmatrix.sync.aligned.m8n8.x4.trans.shared.b16 {%0,%1,%2,%3}, [%4];" : "=r"(hf[4 * kk]), "=r"(hf[4 * kk + 1]), "=r"(hf[4 * kk + 2]), "=r"(hf[4 * kk + 3])
                         : "r"(ha + (kk >> 2) * him + (kk & 3) * 2048) : "memory");
        }
        tag = lds_u(sb + OFF_EPOCH);
        arm(16384);
        mbar_wait(fullb + 8, full_par(25));
        wg_wait<1>(); release(5);
        if (A0 && wg == 1) bar_sync(5, 256);
        gelu_b(0, 4);   mma2(kc[0], kc[1]); hand(1);
        gelu_b(4, 8);   mma2(kc[1], kc[2]); hand(2);
        gelu_b(8, 12);  mma2(kc[2], kc[3]); hand(3);
        gelu_b(12, 16); mma2(kc[3], kc[4]); hand(4);
        gelu_b(16, 20);
        mbar_wait(fullb + 16, full_par(26));
        mma2(kc[4], kc[5]); hand(5);
        credit();
        gelu_b(20, 24); mma2(kc[5], kc[6]); hand(6);
        gelu_b(24, 28); mma2(kc[6], kc[7]);
        mbar_wait(sb + OFF_XFULL + 16, 1);
        gelu_b(28, 32);
        if (wg == 1) bar_sync(4, 256);
        mma(o, 0, kc[7], 22, 0);
        mma(fin, 1, kc[7], 22, 0);
        bar_arrive(4 - wg, 256);
        TS(wg, 9);
        mbar_wait(sb + OFF_KBAR + wg * 8, 0);
        wg_wait<1>();
        reg_fence(o);
        send_peer(o, 0);
        if (!E1L) { wg_wait<0>(); release(0); release(1); reg_fence(fin); send_peer(fin, 49152 - him); }
    }
#pragma unroll
    for (int p = 2; p < 8; p++) {
      const bool even = p == 4 || p == 6;
      TR(0);
      if ((LWM >> p) & 1) mbar_wait(sb + OFF_XFULL + 8 * p, 1);
      TR(1);
      bar_sync(3 + wg, 256);
      if (p < 7) mma(o, p, 0, 22, 0); else mma(fin, p, 0, 22, 1);
      if (p < 7 || wg == 0) bar_arrive(4 - wg, 256);
      TR(2);
      if (p != TP) TS(wg, 8 + p);
      if (p == 2 && E1L) { wg_wait<1>(); release(0); release(1); reg_fence(fin); send_peer(fin, 49152 - him); }
      if (p < 7 && !((LWM >> (p + 1)) & 1)) mbar_wait(sb + OFF_XFULL + 8 * (p + 1), 1);
      TR(3);
      ldk(10 * p);
      if (even) {
        arm(8192);
        if (p == 6) {
          mbar_wait(sb + OFF_EMPTY + 32, 0);
          tag = lds_u(sb + OFF_EPOCH);
          recv_check(sum, 0); recv_check(r0, 1);
#pragma unroll
          for (int i = 0; i < 16; i++) sum[i] = bf2_add(sum[i], r0[i]);
        }
        mbar_wait(sb + OFF_KBAR + wg * 8, p == 4);
      } else if (p != 3) {
        if (p == 7) tag = lds_u(sb + OFF_EPOCH);
        mbar_wait(sb + OFF_RBAR + wg * 8, p == 5);
        read_peer(pt, 0);
        if (p == 2) read_peer(r0, him);
        if (p == 7) {
          recv_check(r0, 2);
#pragma unroll
          for (int i = 0; i < 16; i++) { sum[i] = bf2_add(sum[i], bf2_add(r0[i], pt[i])); pin(sum[i]); }
          sched_fence(ck);
        }
      } else {
#pragma unroll
        for (int h = 0; h < 2; h++) { rho[h] = __fdividef(2.f, 4.f + bf_lo(lds_h(sb + OFF_GS + (wg * 64 + w * 16 + gr + 8 * h) * 2))); pin(rho[h]); }
      }
      TR(4);
      if (p == FINP && !FINW) load_fin();
      ldk(10 * p + 1);
      TR(5);
      wg_wait<0>();
      TR(6);
      if (p < 5) release(p);
      if (p < 7) reg_fence(o); else reg_fence(fin);
      ldk(10 * p + 2);
      if (even) {
        if (p == 6) recv_issue(r0, 2);
        send_peer(o, 0);
        if (p == FINP && FINW) load_fin();
      } else if (p == 3) {
        send_owner(r0, 1);
      } else if (p < 7) {
        send_owner(pt, p == 2 ? 0 : 2);
        __syncwarp();
        credit();
      }
      ldk(10 * p + 3);
      TR(7);
    }
    {
      TS(wg, 16);
      if (ADP == 0) out_addr();
#pragma unroll
      for (int qq = 0; qq < 4; qq += QS) {
#pragma unroll
        for (int qt = qq; qt < qq + QS; qt++) {
          const int h = qt & 1, ch = qt >> 1;
#pragma unroll
          for (int j = 0; j < 4; j++) {
            const int i = ch * 8 + j * 2 + h;
            asm volatile("st.shared.v2.f32 [%0], {%1,%2};" ::"r"((ta ^ (j << 5)) + h * 2048 + ch * 128),
                         "f"((fin[2 * i] + bf_lo(sum[i])) * rho[h]), "f"((fin[2 * i + 1] + bf_hi(sum[i])) * rho[h]) : "memory");
          }
        }
        __syncwarp();
#pragma unroll
        for (int qt = qq; qt < qq + QS; qt++) {
          const int h = qt & 1, ch = qt >> 1;
#pragma unroll
          for (int r = 0; r < 2; r++)
            *reinterpret_cast<uint4*>(op + (r * 32 + h * 2) * DM + ch * 32) = lds_u4(la + (h * 2 + r) * 1024 + ch * 128);
        }
      }
      if (FF1 || ADP) asm volatile("st.shared.u32 [%0], %1;" ::"r"(sb + OFF_EPOCH + 4), "r"(ck) : "memory");
      if ((warp == 4 && lane == 0)) g_epoch[b] = tag;
      TS(wg, 17); TG(wg); TRD(); TDUMP();
    }
  } else {
    const int lane = OPH ? __shfl_sync(0xffffffffu, lane0, lane0) : lane0;
    asm volatile("setmaxnreg.dec.sync.aligned.u32 56;");
    int wsel = warp;
    asm("" : "+r"(wsel));
    if (wsel > 8) {
      const uint4* gwp = reinterpret_cast<const uint4*>(gate_w) + (lane & 7);
      uint4 gw[4];
      if (warp != 11) {
        const int t = OPH ? (warp - 9) * 32 + lane : threadIdx.x - 288;
        unsigned par;
        asm volatile("ld.relaxed.gpu.global.u32 %0, [%1];" : "=r"(par) : "l"(g_epoch + b) : "memory");
        const float pr = bf_ld(lam_re + s * 64 + t), pi = bf_ld(lam_im + s * 64 + t), pd = bf_ld(log_dt + s * 64 + t);
#pragma unroll
        for (int i = 0; i < 4; i++) gw[i] = __ldg(gwp + i * 8);
        asm volatile("barrier.cluster.wait.aligned;" ::: "memory");
        par = __shfl_sync(0xffffffffu, (par + 1) & 1, 0);
        cplx l64 = make_lam(pr, pi, pd);
        {
          const float inv = __fdividef(1.f, fmaf(pr, pr, pi * pi));
          const cplx cf = cmul(cplx{l64.re - 1.f, l64.im}, cplx{pr * inv, -pi * inv});
          asm volatile("st.shared.v4.f32 [%0], {%1,%2,%3,%4};" ::"r"(sb + OFF_LC + t * 16), "f"(l64.re), "f"(l64.im), "f"(cf.re), "f"(cf.im) : "memory");
          mbar_arrive(sb + OFF_LBAR);
        }
#pragma unroll
        for (int i = 0; i < 6; i++) l64 = cmul(l64, l64);
        cplx l128 = cmul(l64, l64);
        pin(l128.re); pin(l128.im);
        gate_rows<1>(sb, lane, xrot, s * 16 + (warp - 9) * 4, gw, gwp, g_gate + m * 128, par);
        if (t == 0) TS(3, 6);
        uint32_t vr[15], vi[15];
#pragma unroll
        for (int i = 0; i < 15; i++) { vr[i] = par; vi[i] = 0; pin(vr[i]); pin(vi[i]); }
        mbar_wait(sb + OFF_GBAR, 0);
        const float2 e0 = lds_f2(sb + OFF_CARRY + t * 8), e1 = lds_f2(sb + OFF_CARRY + 512 + t * 8);
        float2* eb = g_end + s * 1024 + t;
        {
          const cplx e = cfma(l64, cplx{e0.x, e0.y}, cplx{e1.x, e1.y});
          const unsigned long long v = ((unsigned long long)__float_as_uint(e.im) << 32) | ((__float_as_uint(e.re) & ~1u) | par);
          asm volatile("st.relaxed.gpu.global.b64 [%0], %1;" ::"l"(eb + m * 64), "l"(v) : "memory");
        }
        if (t == 0) TS(3, 1);
        cplx S = {0.f, 0.f};
        {
          if (LBD) __nanosleep(LBD);
          const float2* e15 = eb + (m - 15) * 64;
          int tries = 0;
          bool bad;
#pragma unroll 1
          do {
#pragma unroll
            for (int i = 0; i < 15; i++)
              asm volatile("{.reg .pred p; .reg .b64 v; mov.b64 v, {%0,%1}; setp.ge.s32 p, %3, %4; @p ld.relaxed.gpu.global.b64 v, [%2]; mov.b64 {%0,%1}, v;}"
                           : "+r"(vr[i]), "+r"(vi[i]) : "l"(e15 + i * 64), "r"(m), "r"(15 - i) : "memory");
            uint32_t x = vr[0] ^ par;
#pragma unroll
            for (int i = 1; i < 15; i++) asm("lop3.b32 %0, %0, %1, %2, 0xf6;" : "+r"(x) : "r"(vr[i]), "r"(par));
            bad = __any_sync(0xffffffffu, x & 1);
          } while (bad && ++tries < 200000);
          if (t == 0) TS(3, 2);
          S = cplx{__uint_as_float(vr[0] ^ par), __uint_as_float(vi[0])};
#pragma unroll
          for (int i = 1; i < 15; i++) S = cfma(l128, S, cplx{__uint_as_float(vr[i] ^ par), __uint_as_float(vi[i])});
        }
        const cplx S1 = cfma(l64, S, cplx{e0.x, e0.y});
        asm volatile("st.shared.v2.f32 [%0], {%1,%2};" ::"r"(sb + OFF_CARRY + t * 8), "f"(S.re), "f"(S.im) : "memory");
        asm volatile("st.shared.v2.f32 [%0], {%1,%2};" ::"r"(sb + OFF_CARRY + 512 + t * 8), "f"(S1.re), "f"(S1.im) : "memory");
        mbar_arrive(sb + OFF_CBAR);
        if (t == 0) TS(3, 3);
        mbar_wait(sb + OFF_CBAR, 0);
        const int gr = lane >> 2, q = lane & 3;
        mbar_wait(sb + OFF_XFULL + 16, 1);
        if (HW) mbar_wait(sb + OFF_EMPTY, 0);
        uint32_t keep[4][8];
        auto half = [&](int cw, int hf, const uint32_t* xv) {
          const float r0 = 0.5f * bf_lo(lds_h(sb + OFF_GS + (cw * 16 + gr) * 2)), r1 = 0.5f * bf_lo(lds_h(sb + OFF_GS + (cw * 16 + gr) * 2 + 16));
#pragma unroll
          for (int jp = 0; jp < 2; jp++) {
            const uint4 db = lds_u4(sb + OFF_DB + q * 64 + hf * 32 + jp * 16);
#pragma unroll
            for (int e = 0; e < 2; e++) {
              const int j = jp * 2 + e;
              const uint32_t dk = e ? db.z : db.x, bb = e ? db.w : db.y;
              const uint32_t x0 = bf2_mul(xv[2 * j], dk), x1 = bf2_mul(xv[2 * j + 1], dk);
              asm volatile("st.shared.v4.f32 [%0], {%1,%2,%3,%4};" ::"r"(sb + OFF_X + (hf ? 2 - rank : 1 + rank) * 16384 + cw * 2048 + j * 512 + lane * 16), "f"(fmaf(bf_lo(x0), r0, bf_lo(bb))),
                           "f"(fmaf(bf_hi(x0), r0, bf_hi(bb))), "f"(fmaf(bf_lo(x1), r1, bf_lo(bb))), "f"(fmaf(bf_hi(x1), r1, bf_hi(bb))) : "memory");
            }
          }
        };
#pragma unroll
        for (int it = 0; it < 4; it++) {
          const int cw = warp - 9 + 2 * it;
          const uint32_t xa = sb + OFF_X + (1 + rank) * 16384 + (cw * 16 + (lane & 15)) * 128 + (((lane >> 4) ^ (lane & 7)) << 4);
          uint32_t xv[8];
#pragma unroll
          for (int i = 0; i < 2; i++) {
            asm volatile("ldmatrix.sync.aligned.m8n8.x4.shared.b16 {%0,%1,%2,%3}, [%4];" : "=r"(xv[4 * i]), "=r"(xv[4 * i + 1]), "=r"(xv[4 * i + 2]), "=r"(xv[4 * i + 3])
                         : "r"(xa ^ (i << 5)) : "memory");
            asm volatile("ldmatrix.sync.aligned.m8n8.x4.shared.b16 {%0,%1,%2,%3}, [%4];" : "=r"(keep[it][4 * i]), "=r"(keep[it][4 * i + 1]), "=r"(keep[it][4 * i + 2]), "=r"(keep[it][4 * i + 3])
                         : "r"(xa ^ ((i + 2) << 5)) : "memory");
          }
          __syncwarp();
          half(cw, 0, xv);
        }
        mbar_wait(sb + OFF_EMPTY + 16, 0);
#pragma unroll
        for (int it = 0; it < 4; it++) half(warp - 9 + 2 * it, 1, keep[it]);
        mbar_arrive(sb + OFF_LBAR);
        if (t == 0) TS(3, 5);
      } else {
        if (lane == 0) TG(2);
#pragma unroll
        for (int i = 0; i < 4; i++) gw[i] = __ldg(gwp + i * 8);
        unsigned par;
        asm volatile("ld.relaxed.gpu.global.u32 %0, [%1];" : "=r"(par) : "l"(g_epoch + b) : "memory");
        const uint32_t dk = __ldg(reinterpret_cast<const uint32_t*>(dskip + s * 64) + lane), bb = __ldg(reinterpret_cast<const uint32_t*>(b2 + s * 64) + lane);
        asm volatile("barrier.cluster.wait.aligned;" ::: "memory");
        if (lane == 0) asm volatile("st.shared.u32 [%0], %1;" ::"r"(sb + OFF_EPOCH), "r"(par + 1) : "memory");
        par = (par + 1) & 1;
        gate_rows<2>(sb, lane, xrot, s * 16 + 8, gw, gwp, g_gate + m * 128, par);
        if (lane == 0) TS(3, 0);
        mbar_wait(sb + OFF_GBAR, 0);
        asm volatile("st.shared.v2.u32 [%0], {%1,%2};" ::"r"(sb + OFF_DB + (lane & 3) * 64 + (lane >> 2) * 8), "r"(dk), "r"(bf2_add(bb, bb)) : "memory");
        uint32_t g0, g1, g2, g3;
        int tries = 0;
#pragma unroll 1
        do {
          asm volatile("ld.relaxed.gpu.global.v4.u32 {%0,%1,%2,%3}, [%4];" : "=r"(g0), "=r"(g1), "=r"(g2), "=r"(g3) : "l"(g_gate + m * 128 + lane * 4) : "memory");
          g0 ^= par; g1 ^= par; g2 ^= par; g3 ^= par;
        } while (((g0 | g1 | g2 | g3) & 1) && ++tries < 200000);
        asm volatile("st.shared.v2.u32 [%0], {%1,%2};" ::"r"(sb + OFF_GS + lane * 8), "r"(pack_bf16(__uint_as_float(g0), __uint_as_float(g1))),
                     "r"(pack_bf16(__uint_as_float(g2), __uint_as_float(g3))) : "memory");
        const uint32_t gt = sb + OFF_GT + (lane >> 4) * 128 + (lane & 1) * 64 + ((lane >> 1) & 7) * 4;
        asm volatile("st.shared.u32 [%0], %1;" ::"r"(gt), "r"(pack_bf16(__uint_as_float(g0), __uint_as_float(g1))) : "memory");
        asm volatile("st.shared.u32 [%0], %1;" ::"r"(gt + 32), "r"(pack_bf16(__uint_as_float(g2), __uint_as_float(g3))) : "memory");
        mbar_arrive(sb + OFF_CBAR);
        if (lane == 0) TS(3, 4);
      }
    } else {
      asm volatile("barrier.cluster.wait.aligned;" ::: "memory");
      if (elect_one()) {
        TS(2, 1);
        const uint32_t t0 = clock();
#pragma unroll 1
        for (int u = W0; u < 8; u++) {
          if (u >= 1) while ((uint32_t)clock() - t0 < D0 + (u - 1) * D1) {}
          mbar_expect_tx(sb + OFF_XFULL + 8 * u, 32768);
          tma5d_mc(sb + OFF_X + ((u + xrot) & 7) * 16384 + rank * 8192, &maps.x, u * 64, 2 * m + rank, sb + OFF_XFULL + 8 * u);
          const int sl = u < 6 ? u : u - 6;
          if (u >= 6) mbar_wait(sb + OFF_EMPTY + 8 * sl, 0);
          tma2d(sb + OFF_RING + sl * 16384, &maps.bre, u * 64, s * 64, sb + OFF_XFULL + 8 * u);
          tma2d(sb + OFF_RING + sl * 16384 + 8192, &maps.bim, u * 64, s * 64, sb + OFF_XFULL + 8 * u);
          if (u == 2) asm volatile("prefetch.tensormap [%0];" ::"l"(&maps.w1b) : "memory");
          if (u == PA && m < 8) asm volatile("cp.async.bulk.prefetch.tensor.3d.L2.global [%0, {%1,%2,%3}];" ::"l"(&maps.w1b), "r"(0), "r"(m * 64), "r"(s * 7) : "memory");
        }
        TS(2, 5);
        int slot = 2; uint32_t ph = 0;
#pragma unroll 1
        for (int u = 8; u < 24; u++) {
          const uint32_t fb = sb + OFF_FULL + 8 * slot, dst = sb + OFF_RING + slot * 16384;
          mbar_wait(sb + OFF_EMPTY + 8 * slot, ph);
          TS2(0, u);
          if (u < 16) {
            mbar_expect_tx(fb, 12288);
            tma3d(dst, &maps.w1b, 0, (u - 8) * 64, s * 7, fb);
            if (TMP2 && u < 12) asm volatile("prefetch.tensormap [%0];" ::"l"(&maps.w1a + (u - 8)) : "memory");
          } else {
            mbar_expect_tx(fb, 16384);
            tma2d(dst, &maps.w1a, s * 224 + 96, ((u - xrot) & 7) * 64, fb);
            tma2d(dst + 8192, &maps.w1a, s * 224 + 160, ((u - xrot) & 7) * 64, fb);
          }
          if (u == PB) asm volatile("cp.async.bulk.prefetch.tensor.2d.L2.global [%0, {%1,%2}];" ::"l"(&maps.w1a), "r"(s * 224 + 96 + (m & 1) * 64), "r"((m >> 1) * 64) : "memory");
          if (u == PC) {
            const int c = ((sp + 1 + (m >> 3)) & 3) * 128 + ((m >> 2) & 1) * 64;
            if (m & 2) asm volatile("cp.async.bulk.prefetch.tensor.2d.L2.global [%0, {%1,%2}];" ::"l"((m & 1) ? &maps.cim : &maps.cre), "r"(s * 64), "r"(c) : "memory");
            else asm volatile("cp.async.bulk.prefetch.tensor.2d.L2.global [%0, {%1,%2}];" ::"l"(&maps.w2), "r"(c), "r"(s * 224 + (m & 1) * 112) : "memory");
          }
          if (++slot == NSLOT) { slot = 0; ph ^= 1; }
        }
#pragma unroll 1
        for (int j = 0; j < 3; j++) {
          const uint32_t fb = sb + OFF_FULL + 8 * j;
          mbar_wait(sb + OFF_EMPTY + 8 + 8 * j, 1);
          mbar_expect_tx(fb, j == 1 ? 32768 : 28672);
#pragma unroll
          for (int e = 0; e < 2; e++) {
            const int c = ((sp + 1 + e) & 3) * 128 + ((rank ^ 1) << 6);
            const uint32_t dst = sb + OFF_X + stage_off(e);
            if (j == 1) {
              tma2d(dst + 14336, &maps.cre, s * 64, c, fb);
              tma2d(dst + 22528, &maps.cim, s * 64, c, fb);
            } else {
              tma2d(dst + j * 15360, &maps.w2, c, s * 224 + j * 56, fb);
            }
          }
        }
#pragma unroll 1
        for (int p = 2; p < 8; p++) {
          const int c = p < 4 ? ((sp + p - 1) & 3) * 128 + (rank << 6) : ((sp + 1 + (p >> 1)) & 3) * 128 + (((rank ^ p ^ 1) & 1) << 6);
          const uint32_t fb = sb + OFF_XFULL + 8 * p, dst = sb + OFF_X + stage_off(p);
          if (p == 2 || p > 3) mbar_wait(sb + OFF_EMPTY + (p == 2 ? 40 : (p - 4) * 8), p == 2);
          TS2(0, 32 + p);
          mbar_expect_tx(fb, 45056);
          tma2d(dst, &maps.w2, c, s * 224, fb);
          tma2d(dst + 14336, &maps.cre, s * 64, c, fb);
          tma2d(dst + 22528, &maps.cim, s * 64, c, fb);
          tma2d(dst + 30720, &maps.w2, c, s * 224 + 112, fb);
          if (p == PD) {
            const int c2 = ((sp + 3 + (m >> 3)) & 3) * 128 + ((m >> 2) & 1) * 64;
            if (m & 2) asm volatile("cp.async.bulk.prefetch.tensor.2d.L2.global [%0, {%1,%2}];" ::"l"((m & 1) ? &maps.cim : &maps.cre), "r"(s * 64), "r"(c2) : "memory");
            else asm volatile("cp.async.bulk.prefetch.tensor.2d.L2.global [%0, {%1,%2}];" ::"l"(&maps.w2), "r"(c2), "r"(s * 224 + (m & 1) * 112) : "memory");
          }
        }
        TS(2, 2);
      }
    }
  }
}

typedef CUresult (*EncFn)(CUtensorMap*, CUtensorMapDataType, cuuint32_t, void*, const cuuint64_t*, const cuuint64_t*, const cuuint32_t*,
                          const cuuint32_t*, CUtensorMapInterleave, CUtensorMapSwizzle, CUtensorMapL2promotion, CUtensorMapFloatOOBfill);

void encode(EncFn f, CUtensorMap* mp, const void* p, int rank, const cuuint64_t* dims, const cuuint64_t* strides, const cuuint32_t* box, CUtensorMapSwizzle sw) {
  cuuint32_t es[5] = {1, 1, 1, 1, 1};
  f(mp, CU_TENSOR_MAP_DATA_TYPE_BFLOAT16, rank, const_cast<void*>(p), dims, strides, box, es, CU_TENSOR_MAP_INTERLEAVE_NONE, sw,
    CU_TENSOR_MAP_L2_PROMOTION_L2_128B, CU_TENSOR_MAP_FLOAT_OOB_FILL_NONE);
}

}

extern "C" void kernel_launch(void* const* d_in, const int* in_sizes, int n_in, void* d_out, int out_size) {
  typedef const __nv_bfloat16* bp;
  bp x = (bp)d_in[0], lre = (bp)d_in[1], lim = (bp)d_in[2], bre = (bp)d_in[3], bim = (bp)d_in[4], cre = (bp)d_in[5], cim = (bp)d_in[6],
     ldt = (bp)d_in[7], dsk = (bp)d_in[8], w1 = (bp)d_in[10], b1 = (bp)d_in[11], w2 = (bp)d_in[12], b2 = (bp)d_in[13], gw = (bp)d_in[14];
  static EncFn enc = nullptr;
  if (!enc) {
    void* f = nullptr;
    cudaDriverEntryPointQueryResult qr;
    cudaGetDriverEntryPoint("cuTensorMapEncodeTiled", &f, cudaEnableDefault, &qr);
    enc = (EncFn)f;
    cudaFuncSetAttribute(fused_kernel, cudaFuncAttributeMaxDynamicSharedMemorySize, SMEM_BYTES);
  }
  Maps maps;
  {
    cuuint64_t d[5] = {DM, 2, 4, 8, SEQ / 64}, st[4] = {DM * 2, 16 * DM * 2, 2 * DM * 2, 64 * DM * 2};
    cuuint32_t bx[5] = {64, 2, 4, 8, 1};
    encode(enc, &maps.x, x, 5, d, st, bx, CU_TENSOR_MAP_SWIZZLE_128B);
  }
  {
    cuuint64_t d[2] = {DM, DM}, st[1] = {DM * 2};
    cuuint32_t bx[2] = {64, 64};
    encode(enc, &maps.bre, bre, 2, d, st, bx, CU_TENSOR_MAP_SWIZZLE_128B);
    encode(enc, &maps.bim, bim, 2, d, st, bx, CU_TENSOR_MAP_SWIZZLE_128B);
    encode(enc, &maps.cre, cre, 2, d, st, bx, CU_TENSOR_MAP_SWIZZLE_128B);
    encode(enc, &maps.cim, cim, 2, d, st, bx, CU_TENSOR_MAP_SWIZZLE_128B);
  }
  {
    cuuint64_t d[2] = {FF, DM}, st[1] = {FF * 2};
    cuuint32_t bx[2] = {64, 64};
    encode(enc, &maps.w1a, w1, 2, d, st, bx, CU_TENSOR_MAP_SWIZZLE_128B);
    cuuint64_t d3[3] = {32, DM, FF / 32}, st3[2] = {FF * 2, 64};
    cuuint32_t bx3[3] = {32, 64, 3};
    encode(enc, &maps.w1b, w1, 3, d3, st3, bx3, CU_TENSOR_MAP_SWIZZLE_64B);
  }
  {
    cuuint64_t d[2] = {DM, FF}, st[1] = {DM * 2};
    cuuint32_t bx[2] = {64, 112};
    encode(enc, &maps.w2, w2, 2, d, st, bx, CU_TENSOR_MAP_SWIZZLE_128B);
  }
  fused_kernel<<<128, 384, SMEM_BYTES>>>(lre, lim, ldt, dsk, b1, b2, gw, w1, w2, cre, cim, (float*)d_out, maps);
}
```

```cpp
#include <cuda_runtime.h>
#include <cuda_bf16.h>
#include <cuda.h>
#include <stdint.h>

#define MAP 1
#define D0 200
#define D1 480
#define PF 4
#define PFK 5
#define GELUP 1
#define EW 2
#define K1E 1
#define K2E 0
#define QS 1
#define K2G 4
#define FINP 5
#define LBD 400
#define PFS 32
#define SB0 2
#define PFD 2
#define HOLD 0
#define GAP 0
#define FINW 0
#define K0P 41
#define K1P 53
#define TMP2 1
#define W0 1
#define LCK 4
#define TOKA 0
#define TOKB 2
#define TOKD 0
#define TKT 999
#define AV 4
#define QK 4
#define TCUT {1, 6, 6, 11, 16}
#define SCUT {0, 0, 0, 0, 0, 8, 8, 16, 24}
#define PV 2
#define KCUT {4, 8, 12, 15, 18}
#define GCUT {6, 12, 18, 24}
#define OPQ 1
#define OPS 0
#define FF1 1
#define Q1 0
#define QF 1
#define PA 99
#define PB 99
#define PC 99
#define NOH 0
#define OPH 1
#define REL 0
#define EP 0
#define FP 1
#define L16K 2
#define B0K 2
#define B1K 3
#define B2K 4
#define B3K 8
#define ADP 0
#define BB 0
#define DV 2
#define DCUT {2, 4, 7, 9, 12, 14, 15, 17}
#define E1L 0
#define A0 0
#define LW4 1
#define OV 1
#define PD 3
#define LWM 0x10
#define TP 9
#define TW 0

namespace {

constexpr int SEQ = 2048, DM = 512, FF = 1792;
constexpr int NSLOT = 6;
constexpr uint32_t OFF_X = 0, OFF_RING = 131072, OFF_MISC = 229376;
constexpr uint32_t OFF_XFULL = OFF_MISC, OFF_FULL = OFF_XFULL + 64, OFF_RBAR = OFF_FULL + 48, OFF_EMPTY = OFF_RBAR + 16, OFF_KBAR = OFF_EMPTY + 48,
                   OFF_GBAR = OFF_KBAR + 16, OFF_LBAR = OFF_GBAR + 8, OFF_CBAR = OFF_LBAR + 8, OFF_EPOCH = OFF_CBAR + 8;
constexpr uint32_t OFF_LC = OFF_MISC + 256;
constexpr uint32_t OFF_GS = OFF_LC;
constexpr uint32_t OFF_GT = OFF_LC + 256;
constexpr uint32_t OFF_DB = OFF_LC + 512;
constexpr uint32_t OFF_CARRY = OFF_LC + 1024;
constexpr uint32_t OFF_DBG = OFF_CARRY + 1024;
constexpr uint32_t SMEM_BYTES = OFF_DBG + 768;
static_assert(SMEM_BYTES <= 232448, "smem");

struct Maps { CUtensorMap x, bre, bim, w1b, w1a, w2, cre, cim; };
__host__ __device__ constexpr uint32_t stage_off(int p) { return 49152 + 45056 * (((p >> 1) & 1) + 2 * (p & 1)); }

__host__ __device__ constexpr uint32_t full_par(int u) { return ((u - 8) / 6 + (FP != 3 && u % 6 == 0)) & 1; }

__device__ uint4 g_part[16 * 8 * 3 * 1024];
__device__ float2 g_end[8 * 16 * 64];
__device__ unsigned g_gate[SEQ];
__device__ unsigned g_epoch[128];
#define TG(role) do {} while (0)
#define TS2(role, i) do {} while (0)
#define TS(role, i) do {} while (0)
#define TDUMP() do {} while (0)
#define TR(i) do {} while (0)
#define TK(i) do {} while (0)
#define TRD() do {} while (0)

__device__ __forceinline__ void mbar_init(uint32_t bar, uint32_t cnt) { asm volatile("mbarrier.init.shared::cta.b64 [%0], %1;" ::"r"(bar), "r"(cnt)); }
__device__ __forceinline__ void mbar_expect_tx(uint32_t bar, uint32_t bytes) { asm volatile("mbarrier.arrive.expect_tx.shared::cta.b64 _, [%0], %1;" ::"r"(bar), "r"(bytes) : "memory"); }
__device__ __forceinline__ void mbar_arrive(uint32_t bar) { asm volatile("mbarrier.arrive.shared::cta.b64 _, [%0];" ::"r"(bar) : "memory"); }
__device__ __forceinline__ void mbar_arrive_cl(uint32_t cbar) { asm volatile("mbarrier.arrive.shared::cluster.b64 _, [%0];" ::"r"(cbar) : "memory"); }
__device__ __forceinline__ void mbar_wait(uint32_t bar, uint32_t parity) {
  asm volatile(
      "{\n.reg .pred p;\n.reg .u32 c;\n"
      "mbarrier.try_wait.parity.shared::cta.b64 p, [%0], %1;\n"
      "@p bra.uni LAB_DONE;\n"
      "mov.u32 c, 0;\n"
      "LAB_WAIT:\n"
      "mbarrier.try_wait.parity.shared::cta.b64 p, [%0], %1;\n"
      "@p bra.uni LAB_DONE;\n"
      "add.u32 c, c, 1;\nsetp.lt.u32 p, c, 200000;\n@p bra.uni LAB_WAIT;\n"
      "LAB_DONE:\n}" ::"r"(bar), "r"(parity) : "memory");
}
__device__ __forceinline__ void tma2d(uint32_t dst, const CUtensorMap* m, int c0, int c1, uint32_t bar) {
  asm volatile("cp.async.bulk.tensor.2d.shared::cluster.global.mbarrier::complete_tx::bytes [%0], [%1, {%3,%4}], [%2];"
               ::"r"(dst), "l"(m), "r"(bar), "r"(c0), "r"(c1) : "memory");
}
__device__ __forceinline__ void tma3d(uint32_t dst, const CUtensorMap* m, int c0, int c1, int c2, uint32_t bar) {
  asm volatile("cp.async.bulk.tensor.3d.shared::cluster.global.mbarrier::complete_tx::bytes [%0], [%1, {%3,%4,%5}], [%2];"
               ::"r"(dst), "l"(m), "r"(bar), "r"(c0), "r"(c1), "r"(c2) : "memory");
}
__device__ __forceinline__ void tma5d(uint32_t dst, const CUtensorMap* m, int c0, int c4, uint32_t bar) {
  asm volatile("cp.async.bulk.tensor.5d.shared::cluster.global.mbarrier::complete_tx::bytes [%0], [%1, {%3,%5,%5,%5,%4}], [%2];"
               ::"r"(dst), "l"(m), "r"(bar), "r"(c0), "r"(c4), "r"(0) : "memory");
}
__device__ __forceinline__ void tma5d_mc(uint32_t dst, const CUtensorMap* m, int c0, int c4, uint32_t bar) {
  asm volatile("cp.async.bulk.tensor.5d.shared::cluster.global.mbarrier::complete_tx::bytes.multicast::cluster [%0], [%1, {%3,%5,%5,%5,%4}], [%2], %6;"
               ::"r"(dst), "l"(m), "r"(bar), "r"(c0), "r"(c4), "r"(0), "h"((uint16_t)3) : "memory");
}
__device__ __forceinline__ void l2_prefetch(const void* p, uint32_t bytes) { asm volatile("cp.async.bulk.prefetch.L2.global [%0], %1;" ::"l"(p), "r"(bytes) : "memory"); }
__device__ __forceinline__ bool elect_one() {
  uint32_t pred;
  asm volatile("{.reg .pred P; elect.sync _|P, 0xffffffff; selp.u32 %0, 1, 0, P;}" : "=r"(pred));
  return pred != 0;
}
__device__ __forceinline__ void wg_fence() { asm volatile("wgmma.fence.sync.aligned;" ::: "memory"); }
__device__ __forceinline__ void wg_commit() { asm volatile("wgmma.commit_group.sync.aligned;" ::: "memory"); }
template <int N> __device__ __forceinline__ void wg_wait() { asm volatile("wgmma.wait_group.sync.aligned %0;" ::"n"(N) : "memory"); }
__device__ __forceinline__ void pin(float& a) { asm volatile("" : "+f"(a)::"memory"); }
__device__ __forceinline__ void pin(uint32_t& a) { asm volatile("" : "+r"(a)::"memory"); }
template <int N> __device__ __forceinline__ void reg_fence(float (&d)[N]) {
#pragma unroll
  for (int i = 0; i < N; i++) pin(d[i]);
}
__device__ __forceinline__ void bar_sync(int id, int n) { asm volatile("bar.sync %0, %1;" ::"r"(id), "r"(n) : "memory"); }
__device__ __forceinline__ void bar_arrive(int id, int n) { asm volatile("bar.arrive %0, %1;" ::"r"(id), "r"(n) : "memory"); }
constexpr uint32_t DH128 = (1024 >> 4) | (1u << 30), DH64 = (512 >> 4) | (2u << 30);
__host__ __device__ constexpr uint32_t lbo(uint32_t bytes) { return (bytes >> 4) << 20; }
__device__ __forceinline__ uint32_t pack_bf16(float lo, float hi) { uint32_t r; asm("cvt.rn.bf16x2.f32 %0, %1, %2;" : "=r"(r) : "f"(hi), "f"(lo)); return r; }
__device__ __forceinline__ float bf_lo(uint32_t v) { return __uint_as_float(v << 16); }
__device__ __forceinline__ float bf_hi(uint32_t v) { return __uint_as_float(v & 0xffff0000u); }
__device__ __forceinline__ float bf_ld(const __nv_bfloat16* p) { return __bfloat162float(__ldg(p)); }
__device__ __forceinline__ uint32_t late16(uint32_t bar) {
  uint32_t r;
  asm volatile("{.reg .pred p; mbarrier.test_wait.parity.shared::cta.b64 p, [%1], 0; selp.u32 %0, 16, 0, p;}" : "=r"(r) : "r"(bar) : "memory");
  return r;
}
__device__ __forceinline__ float2 lds_f2(uint32_t a) { float2 v; asm volatile("ld.shared.v2.f32 {%0,%1}, [%2];" : "=f"(v.x), "=f"(v.y) : "r"(a)); return v; }
__device__ __forceinline__ uint32_t lds_h(uint32_t a) { uint32_t v; asm volatile("ld.shared.u16 %0, [%1];" : "=r"(v) : "r"(a)); return v; }
__device__ __forceinline__ uint32_t lds_u(uint32_t a) { uint32_t v; asm volatile("ld.shared.u32 %0, [%1];" : "=r"(v) : "r"(a)); return v; }
__device__ __forceinline__ uint4 lds_u4(uint32_t a) { uint4 v; asm volatile("ld.shared.v4.u32 {%0,%1,%2,%3}, [%4];" : "=r"(v.x), "=r"(v.y), "=r"(v.z), "=r"(v.w) : "r"(a)); return v; }
__device__ __forceinline__ void st_b128(uint4* p, uint32_t a, uint32_t b, uint32_t c, uint32_t d) {
  asm volatile("st.relaxed.gpu.global.v4.b32 [%0], {%1,%2,%3,%4};" ::"l"(p), "r"(a), "r"(b), "r"(c), "r"(d) : "memory");
}
__device__ __forceinline__ void ld_b128(const uint4* p, uint32_t& a, uint32_t& b, uint32_t& c, uint32_t& d) {
  asm volatile("{.reg .b64 l, h; .reg .b128 v; ld.relaxed.gpu.global.b128 v, [%4]; mov.b128 {l,h}, v; mov.b64 {%0,%1}, l; mov.b64 {%2,%3}, h;}"
               : "=r"(a), "=r"(b), "=r"(c), "=r"(d) : "l"(p) : "memory");
}
__device__ __forceinline__ float tanh_fast(float x) { float y; asm("tanh.approx.f32 %0, %1;" : "=f"(y) : "f"(x)); return y; }
__device__ __forceinline__ float gelu2(float v) {
  float p = fmaf(v * v, 0.0356774081363f, 0.7978845608029f);
  return fmaf(v, tanh_fast(v * p), v);
}
__device__ __forceinline__ void sched_fence(uint32_t& ck) { asm volatile("{.reg .b32 c; mov.u32 c, %%clock; xor.b32 %0, %0, c;}" : "+r"(ck)::"memory"); }
__device__ __forceinline__ uint32_t bf2_mul(uint32_t a, uint32_t b) { uint32_t r; asm("mul.rn.bf16x2 %0, %1, %2;" : "=r"(r) : "r"(a), "r"(b)); return r; }
__device__ __forceinline__ uint32_t bf2_add(uint32_t a, uint32_t b) { uint32_t r; asm("add.rn.bf16x2 %0, %1, %2;" : "=r"(r) : "r"(a), "r"(b)); return r; }
__device__ __forceinline__ uint32_t bf2_fma(uint32_t a, uint32_t b, uint32_t c) { uint32_t r; asm("fma.rn.bf16x2 %0, %1, %2, %3;" : "=r"(r) : "r"(a), "r"(b), "r"(c)); return r; }
__device__ __forceinline__ uint32_t gelu2_pair(float a, float b) {
  const uint32_t v = pack_bf16(a, b);
  uint32_t t;
  asm("tanh.approx.bf16x2 %0, %1;" : "=r"(t) : "r"(bf2_fma(v, bf2_fma(bf2_mul(v, v), 0x3d123d12u, 0xbe4fbe4fu), v)));
  return bf2_fma(v, t, v);
}
struct cplx { float re, im; };
__device__ __forceinline__ cplx cmul(cplx a, cplx b) { return {fmaf(a.re, b.re, -a.im * b.im), fmaf(a.re, b.im, a.im * b.re)}; }
__device__ __forceinline__ cplx cfma(cplx a, cplx b, cplx c) {
  return {fmaf(a.re, b.re, fmaf(-a.im, b.im, c.re)), fmaf(a.re, b.im, fmaf(a.im, b.re, c.im))};
}
__device__ __forceinline__ cplx make_lam(float lre, float lim, float ldt) {
  float dt = __bfloat162float(__float2bfloat16_rn(expf(ldt)));
  float mag = expf(dt * lre), sn, cs;
  sincospif(dt * lim * 0.31830988618379067f, &sn, &cs);
  return {mag * cs, mag * sn};
}

template <int NG>
__device__ __forceinline__ void gate_rows(uint32_t sb, int lane, int xrot, int row0, uint4 (&gw)[4], const uint4* gwp, unsigned* dst, unsigned par) {
  const int row = row0 + (lane >> 3);
  const uint32_t xr0 = sb + OFF_X + row * 128 + (((lane & 7) ^ (row & 7)) << 4), xr1 = (xr0 + 512) ^ 64;
  float z[NG], y[NG];
#pragma unroll
  for (int r = 0; r < NG; r++) z[r] = y[r] = 0.f;
#pragma unroll
  for (int kb = 0; kb < 8; kb++) {
    const uint4 w = gw[kb & 3];
    if (kb < 4) gw[kb] = __ldg(gwp + (kb + 4) * 8);
    mbar_wait(sb + OFF_XFULL + 8 * kb, 0);
#pragma unroll
    for (int r = 0; r < NG; r++) {
      const uint4 a = lds_u4((r ? xr1 : xr0) + ((kb + xrot) & 7) * 16384);
      const uint32_t p[4] = {bf2_mul(a.x, w.x), bf2_mul(a.y, w.y), bf2_mul(a.z, w.z), bf2_mul(a.w, w.w)};
#pragma unroll
      for (int c = 0; c < 4; c++) { z[r] += bf_lo(p[c]); y[r] += bf_hi(p[c]); }
    }
  }
  float zz = z[0] + y[0];
  if (NG == 2) {
    const float z1 = z[NG - 1] + y[NG - 1];
    zz = ((lane & 4) ? z1 : zz) + __shfl_xor_sync(0xffffffffu, (lane & 4) ? zz : z1, 4);
  } else {
    zz += __shfl_xor_sync(0xffffffffu, zz, 4);
  }
  zz += __shfl_xor_sync(0xffffffffu, zz, 2);
  zz += __shfl_xor_sync(0xffffffffu, zz, 1);
  zz = bf_lo(pack_bf16(zz, 0.f));
  const float rho = 4.f * expf(zz > 40.f ? 40.f : zz);
  if ((lane & (NG == 2 ? 3 : 7)) == 0)
    asm volatile("st.relaxed.gpu.global.u32 [%0], %1;" ::"l"(dst + row + (lane & 4)), "r"((__float_as_uint(rho) & ~1u) | par) : "memory");
}

template<int TA,int TB,uint32_t AH,uint32_t BH> __device__ __forceinline__ void wgmma_n64_ss(float (&d)[32], uint32_t al, uint32_t ao, uint32_t bl, uint32_t bo, int scale_d){
  asm volatile("{.reg .pred p; .reg .b32 t, v; .reg .b64 da, db; setp.ne.b32 p, %36, 0; add.u32 t, %32, %33; mov.b64 da, {t, %39}; add.u32 v, %34, %35; mov.b64 db, {v, %40};\n"
   "wgmma.mma_async.sync.aligned.m64n64k16.f32.bf16.bf16 {%0,%1,%2,%3,%4,%5,%6,%7,%8,%9,%10,%11,%12,%13,%14,%15,%16,%17,%18,%19,%20,%21,%22,%23,%24,%25,%26,%27,%28,%29,%30,%31}, da, db, p, 1, 1, %37, %38;}"
   : "+f"(d[0]),"+f"(d[1]),"+f"(d[2]),"+f"(d[3]),"+f"(d[4]),"+f"(d[5]),"+f"(d[6]),"+f"(d[7]),"+f"(d[8]),"+f"(d[9]),"+f"(d[10]),"+f"(d[11]),"+f"(d[12]),"+f"(d[13]),"+f"(d[14]),"+f"(d[15]),"+f"(d[16]),"+f"(d[17]),"+f"(d[18]),"+f"(d[19]),"+f"(d[20]),"+f"(d[21]),"+f"(d[22]),"+f"(d[23]),"+f"(d[24]),"+f"(d[25]),"+f"(d[26]),"+f"(d[27]),"+f"(d[28]),"+f"(d[29]),"+f"(d[30]),"+f"(d[31])
   : "r"(al),"r"(ao >> 4),"r"(bl),"r"(bo >> 4),"r"(scale_d),"n"(TA),"n"(TB),"n"(AH),"n"(BH));
}
template<int TB,uint32_t BH,int SA=1> __device__ __forceinline__ void wgmma_n64_rs(float (&d)[32], uint32_t a0,uint32_t a1,uint32_t a2,uint32_t a3, uint32_t bl, uint32_t bo, int scale_d){
  asm volatile("{.reg .pred p; .reg .b32 t; .reg .b64 db; setp.ne.b32 p, %38, 0; add.u32 t, %36, %37; mov.b64 db, {t, %40};\n"
   "wgmma.mma_async.sync.aligned.m64n64k16.f32.bf16.bf16 {%0,%1,%2,%3,%4,%5,%6,%7,%8,%9,%10,%11,%12,%13,%14,%15,%16,%17,%18,%19,%20,%21,%22,%23,%24,%25,%26,%27,%28,%29,%30,%31}, {%32,%33,%34,%35}, db, p, %41, 1, %39;}"
   : "+f"(d[0]),"+f"(d[1]),"+f"(d[2]),"+f"(d[3]),"+f"(d[4]),"+f"(d[5]),"+f"(d[6]),"+f"(d[7]),"+f"(d[8]),"+f"(d[9]),"+f"(d[10]),"+f"(d[11]),"+f"(d[12]),"+f"(d[13]),"+f"(d[14]),"+f"(d[15]),"+f"(d[16]),"+f"(d[17]),"+f"(d[18]),"+f"(d[19]),"+f"(d[20]),"+f"(d[21]),"+f"(d[22]),"+f"(d[23]),"+f"(d[24]),"+f"(d[25]),"+f"(d[26]),"+f"(d[27]),"+f"(d[28]),"+f"(d[29]),"+f"(d[30]),"+f"(d[31])
   : "r"(a0),"r"(a1),"r"(a2),"r"(a3),"r"(bl),"r"(bo >> 4),"r"(scale_d),"n"(TB),"n"(BH),"n"(SA));
}
template<int TA,int TB,uint32_t AH,uint32_t BH> __device__ __forceinline__ void wgmma_n96_ss(float (&d)[48], uint32_t al, uint32_t ao, uint32_t bl, uint32_t bo, int scale_d){
  asm volatile("{.reg .pred p; .reg .b32 t, v; .reg .b64 da, db; setp.ne.b32 p, %52, 0; add.u32 t, %48, %49; mov.b64 da, {t, %55}; add.u32 v, %50, %51; mov.b64 db, {v, %56};\n"
   "wgmma.mma_async.sync.aligned.m64n96k16.f32.bf16.bf16 {%0,%1,%2,%3,%4,%5,%6,%7,%8,%9,%10,%11,%12,%13,%14,%15,%16,%17,%18,%19,%20,%21,%22,%23,%24,%25,%26,%27,%28,%29,%30,%31,%32,%33,%34,%35,%36,%37,%38,%39,%40,%41,%42,%43,%44,%45,%46,%47}, da, db, p, 1, 1, %53, %54;}"
   : "+f"(d[0]),"+f"(d[1]),"+f"(d[2]),"+f"(d[3]),"+f"(d[4]),"+f"(d[5]),"+f"(d[6]),"+f"(d[7]),"+f"(d[8]),"+f"(d[9]),"+f"(d[10]),"+f"(d[11]),"+f"(d[12]),"+f"(d[13]),"+f"(d[14]),"+f"(d[15]),"+f"(d[16]),"+f"(d[17]),"+f"(d[18]),"+f"(d[19]),"+f"(d[20]),"+f"(d[21]),"+f"(d[22]),"+f"(d[23]),"+f"(d[24]),"+f"(d[25]),"+f"(d[26]),"+f"(d[27]),"+f"(d[28]),"+f"(d[29]),"+f"(d[30]),"+f"(d[31]),"+f"(d[32]),"+f"(d[33]),"+f"(d[34]),"+f"(d[35]),"+f"(d[36]),"+f"(d[37]),"+f"(d[38]),"+f"(d[39]),"+f"(d[40]),"+f"(d[41]),"+f"(d[42]),"+f"(d[43]),"+f"(d[44]),"+f"(d[45]),"+f"(d[46]),"+f"(d[47])
   : "r"(al),"r"(ao >> 4),"r"(bl),"r"(bo >> 4),"r"(scale_d),"n"(TA),"n"(TB),"n"(AH),"n"(BH));
}
template<int TA,int TB,uint32_t AH,uint32_t BH> __device__ __forceinline__ void wgmma_n128_ss(float (&d)[64], uint32_t al, uint32_t ao, uint32_t bl, uint32_t bo, int scale_d){
  asm volatile("{.reg .pred p; .reg .b32 t, v; .reg .b64 da, db; setp.ne.b32 p, %68, 0; add.u32 t, %64, %65; mov.b64 da, {t, %71}; add.u32 v, %66, %67; mov.b64 db, {v, %72};\n"
   "wgmma.mma_async.sync.aligned.m64n128k16.f32.bf16.bf16 {%0,%1,%2,%3,%4,%5,%6,%7,%8,%9,%10,%11,%12,%13,%14,%15,%16,%17,%18,%19,%20,%21,%22,%23,%24,%25,%26,%27,%28,%29,%30,%31,%32,%33,%34,%35,%36,%37,%38,%39,%40,%41,%42,%43,%44,%45,%46,%47,%48,%49,%50,%51,%52,%53,%54,%55,%56,%57,%58,%59,%60,%61,%62,%63}, da, db, p, 1, 1, %69, %70;}"
   : "+f"(d[0]),"+f"(d[1]),"+f"(d[2]),"+f"(d[3]),"+f"(d[4]),"+f"(d[5]),"+f"(d[6]),"+f"(d[7]),"+f"(d[8]),"+f"(d[9]),"+f"(d[10]),"+f"(d[11]),"+f"(d[12]),"+f"(d[13]),"+f"(d[14]),"+f"(d[15]),"+f"(d[16]),"+f"(d[17]),"+f"(d[18]),"+f"(d[19]),"+f"(d[20]),"+f"(d[21]),"+f"(d[22]),"+f"(d[23]),"+f"(d[24]),"+f"(d[25]),"+f"(d[26]),"+f"(d[27]),"+f"(d[28]),"+f"(d[29]),"+f"(d[30]),"+f"(d[31]),"+f"(d[32]),"+f"(d[33]),"+f"(d[34]),"+f"(d[35]),"+f"(d[36]),"+f"(d[37]),"+f"(d[38]),"+f"(d[39]),"+f"(d[40]),"+f"(d[41]),"+f"(d[42]),"+f"(d[43]),"+f"(d[44]),"+f"(d[45]),"+f"(d[46]),"+f"(d[47]),"+f"(d[48]),"+f"(d[49]),"+f"(d[50]),"+f"(d[51]),"+f"(d[52]),"+f"(d[53]),"+f"(d[54]),"+f"(d[55]),"+f"(d[56]),"+f"(d[57]),"+f"(d[58]),"+f"(d[59]),"+f"(d[60]),"+f"(d[61]),"+f"(d[62]),"+f"(d[63])
   : "r"(al),"r"(ao >> 4),"r"(bl),"r"(bo >> 4),"r"(scale_d),"n"(TA),"n"(TB),"n"(AH),"n"(BH));
}

__global__ void __cluster_dims__(2, 1, 1) __launch_bounds__(384, 1)
fused_kernel(const __nv_bfloat16* __restrict__ lam_re, const __nv_bfloat16* __restrict__ lam_im, const __nv_bfloat16* __restrict__ log_dt,
             const __nv_bfloat16* __restrict__ dskip, const __nv_bfloat16* __restrict__ b1, const __nv_bfloat16* __restrict__ b2,
             const __nv_bfloat16* __restrict__ gate_w, const __nv_bfloat16* __restrict__ pf_w1, const __nv_bfloat16* __restrict__ pf_w2,
             const __nv_bfloat16* __restrict__ pf_cre, const __nv_bfloat16* __restrict__ pf_cim, float* __restrict__ out,
             const __grid_constant__ Maps maps) {
  extern __shared__ __align__(1024) unsigned char smem_raw[];
  uint32_t sb = (uint32_t)__cvta_generic_to_shared(smem_raw);
  if (EP == 1 && threadIdx.x == 352) {
    asm volatile("prefetch.tensormap [%0];" ::"l"(&maps.x) : "memory");
    asm volatile("prefetch.tensormap [%0];" ::"l"(&maps.bre) : "memory");
    asm volatile("prefetch.tensormap [%0];" ::"l"(&maps.bim) : "memory");
  }
  if (EP == 2 && elect_one()) {
    asm volatile("prefetch.tensormap [%0];" ::"l"(&maps.x) : "memory");
    asm volatile("prefetch.tensormap [%0];" ::"l"(&maps.bre) : "memory");
    asm volatile("prefetch.tensormap [%0];" ::"l"(&maps.bim) : "memory");
  }
  int tid_ = threadIdx.x;
  const int b = blockIdx.x;
  const int rank = b & 1, cl = b >> 1;
  const int sp = (cl & 1) | ((cl >> 2) & 2), m = ((cl >> 1) & 3) | ((cl >> 4) << 2);
  const int s = sp * 2 + rank;
  const int xrot = 9 - 2 * sp;
  if (FP == 1 ? threadIdx.x == 0 : (threadIdx.x < 32 && elect_one())) {
    mbar_init(sb + OFF_XFULL, 1);
    mbar_expect_tx(sb + OFF_XFULL, FP == 3 ? 32768 : 16384);
    tma5d(sb + OFF_X + (xrot & 7) * 16384, &maps.x, 0, 2 * m, sb + OFF_XFULL);
    if (FP == 3) tma2d(sb + OFF_RING, &maps.bre, 0, s * 64, sb + OFF_XFULL);
    tma5d(sb + OFF_X + (xrot & 7) * 16384 + 8192, &maps.x, 0, 2 * m + 1, sb + OFF_XFULL);
    if (FP == 3) tma2d(sb + OFF_RING + 8192, &maps.bim, 0, s * 64, sb + OFF_XFULL);
    TS(2, 3);
  }
  if (FP != 3 && (FP == 1 ? threadIdx.x == 128 : ((threadIdx.x >> 5) == 4 && elect_one()))) {
    mbar_init(sb + OFF_FULL, 1);
    mbar_expect_tx(sb + OFF_FULL, 16384);
    tma2d(sb + OFF_RING, &maps.bre, 0, s * 64, sb + OFF_FULL);
    tma2d(sb + OFF_RING + 8192, &maps.bim, 0, s * 64, sb + OFF_FULL);
    TS(2, 4);
  }
  const int warp = __shfl_sync(0xffffffffu, (int)(threadIdx.x >> 5), 0);
  const int lane0 = threadIdx.x & 31;

  if (elect_one()) {
    if (warp > 8) {
      if (EP == 0) asm volatile("prefetch.tensormap [%0];" ::"l"(&maps.x + (warp - 9)) : "memory");
      mbar_init(sb + OFF_GBAR + 8 * (warp - 9), warp < 11 ? 64 : 96);
    }
    const uint32_t c = warp < 8 ? 1 : warp < 11 ? 8 : 4, bar = sb + OFF_XFULL + 16 * warp;
    if (FP == 3 ? warp != 0 : (warp & 11) != 0) mbar_init(bar, c);
    mbar_init(bar + 8, c);
    asm volatile("fence.mbarrier_init.release.cluster;" ::: "memory");
  }
  __syncwarp();
  asm volatile("barrier.cluster.arrive.relaxed.aligned;" ::: "memory");

  if (warp < 8) {
    const int lane = OPQ ? __shfl_sync(0xffffffffu, lane0, lane0) : lane0;
    tid_ = warp * 32 + lane;
    if (OPS) sb = __shfl_sync(0xffffffffu, sb, 0);
    const int wg = warp >> 2, w = warp & 3, q = lane & 3, gr = lane >> 2;
    uint32_t bv[28];
#pragma unroll
    for (int j = 0; j < 28; j++) bv[j] = __ldg(reinterpret_cast<const uint32_t*>(b1 + s * 224 + j * 8) + q);
    asm volatile("setmaxnreg.inc.sync.aligned.u32 224;");
    asm volatile("barrier.cluster.wait.aligned;" ::: "memory");
    TS(wg, 0);
    auto release = [&](int slot) {
      if (REL) asm volatile("{.reg .pred P; elect.sync _|P, 0xffffffff; @P mbarrier.arrive.shared::cta.b64 _, [%0];}" ::"r"(sb + OFF_EMPTY + 8 * slot) : "memory");
      else if (lane == 0) mbar_arrive(sb + OFF_EMPTY + 8 * slot);
    };
    const uint32_t xw = sb + OFF_X + wg * 8192, fullb = sb + OFF_FULL;
    const uint32_t dxw = (xw & 0x3FFFF) >> 4, dring = ((sb + OFF_RING) & 0x3FFFF) >> 4;

    float ure[32], uim[32], aa[48], ab[64];
    cplx lam[2], coef[2], l16[2], l32[2], lq[2], pre[2], e[2];
    uint32_t sh16, mhi, ck = 0;

    auto bias = [&](int c) {
#pragma unroll
      for (int j = c * 7; j < c * 7 + 7; j++) {
        pin(bv[j]);
        float* d = j < 12 ? aa + 4 * j : ab + 4 * (j - 12);
        d[0] = d[2] = __uint_as_float(bv[j] << sh16); d[1] = d[3] = __uint_as_float(bv[j] & mhi);
        pin(d[0]); pin(d[1]); pin(d[2]); pin(d[3]);
      }
    };
#pragma unroll
    for (int kb = 0; kb < 8; kb++) {
      const int slot = kb % NSLOT;
      mbar_wait(sb + OFF_XFULL + 8 * kb, 0);
      if (kb == 0) TS(wg, 18);
      if (kb == 0 && FP != 3) mbar_wait(fullb, 0);
      TS2(2, kb);
      if (kb == 0) TS(wg, 1);
      if (kb == L16K) { sh16 = late16(sb + OFF_XFULL); mhi = 0xffffffffu << sh16; }
      if (kb == LCK) {
        mbar_wait(sb + OFF_LBAR, 0);
#pragma unroll
        for (int h = 0; h < 2; h++) {
          const uint4 v = lds_u4(sb + OFF_LC + (w * 16 + gr + 8 * h) * 16);
          lam[h] = cplx{__uint_as_float(v.x), __uint_as_float(v.y)};
          coef[h] = cplx{__uint_as_float(v.z), __uint_as_float(v.w)};
        }
      }
      wg_fence();
      const uint32_t dxa = dxw + ((kb + xrot) & 7) * 1024;
#pragma unroll
      for (int kk = 0; kk < 4; kk++) {
        wgmma_n64_ss<0, 0, DH128, DH128>(ure, dring, slot * 16384 + kk * 32, dxa, kk * 32, (kb | kk) != 0);
        wgmma_n64_ss<0, 0, DH128, DH128>(uim, dring, slot * 16384 + 8192 + kk * 32, dxa, kk * 32, (kb | kk) != 0);
      }
      wg_commit();
      if (kb > 0) { wg_wait<1>(); release((kb - 1) % NSLOT); }
      if (kb == B0K) bias(0);
      if (kb == B1K) bias(1);
      if (kb == B2K) bias(2);
      if (kb == B3K) bias(3);
      if (kb == 6) {
#pragma unroll
        for (int h = 0; h < 2; h++) {
          pin(lam[h].re); pin(lam[h].im);
          cplx t = cmul(lam[h], lam[h]); t = cmul(t, t); t = cmul(t, t);
          l16[h] = cmul(t, t);
          pin(l16[h].re); pin(l16[h].im);
        }
      }
      if (kb == 7) {
#pragma unroll
        for (int h = 0; h < 2; h++) {
          pin(l16[h].re); pin(l16[h].im);
          l32[h] = cmul(l16[h], l16[h]);
          const cplx a = (q & 1) ? l16[h] : cplx{1.f, 0.f}, c = (q & 2) ? l32[h] : cplx{1.f, 0.f};
          lq[h] = cmul(cmul(a, c), coef[h]);
          pin(lq[h].re); pin(lq[h].im);
          if (Q1) {
            if (q < 2) l16[h] = cplx{0.f, 0.f};
            if (q < 3) l32[h] = cplx{0.f, 0.f};
            pin(l16[h].re); pin(l16[h].im); pin(l32[h].re); pin(l32[h].im);
          }
        }
      }
    }
    TS(wg, 2);
    auto scale_u = [&](int i0, int i1) {
#pragma unroll
      for (int i = 0; i < 32; i++) if (i >= i0 && i < i1) {
        pin(ure[i]); pin(uim[i]);
        const cplx v = cmul(coef[(i >> 1) & 1], cplx{ure[i], uim[i]});
        ure[i] = v.re; uim[i] = v.im;
        pin(ure[i]); pin(uim[i]);
      }
    };
#pragma unroll
    for (int kb = 0; kb < 8; kb++) {
      const int u = 8 + kb, slot = u % NSLOT;
      mbar_wait(fullb + 8 * slot, full_par(u));
      TK(kb);
      wg_fence();
      const uint32_t dxa = dxw + ((kb + xrot) & 7) * 1024;
#pragma unroll
      for (int kk = 0; kk < 4; kk++)
        wgmma_n96_ss<0, 1, DH128, DH64>(aa, dxa, kk * 32, dring, slot * 16384 + kk * 1024 + lbo(4096), 1);
      wg_commit();
      if (kb + 8 == B3K) bias(3);
      if (kb != QK) { wg_wait<1>(); release((u - 1) % NSLOT); }
      if (kb == 0) {
        reg_fence(ure); reg_fence(uim);
#pragma unroll
        for (int h = 0; h < 2; h++) e[h] = cplx{ure[2 * h], uim[2 * h]};
      }
      if (kb == 0 || (kb >= 2 && kb <= QK && kb < 4)) {
        constexpr int tc[5] = TCUT;
#pragma unroll
        for (int t = 1; t < 16; t++) if (t >= tc[kb] && t < tc[kb + 1]) {
#pragma unroll
          for (int h = 0; h < 2; h++) { const int i = 4 * (t >> 1) + 2 * h + (t & 1); e[h] = cfma(lam[h], e[h], cplx{ure[i], uim[i]}); }
        }
#pragma unroll
        for (int h = 0; h < 2; h++) { pin(e[h].re); pin(e[h].im); }
      }
      if (kb == QK) {
        { constexpr int sc[9] = SCUT; scale_u(sc[kb], sc[kb + 1]); }
        if (QF) sched_fence(ck);
#pragma unroll
        for (int h = 0; h < 2; h++) {
          cplx y = {__shfl_up_sync(0xffffffffu, e[h].re, 1, 4), __shfl_up_sync(0xffffffffu, e[h].im, 1, 4)};
          if (q >= 1) e[h] = cfma(l16[h], y, e[h]);
          y = cplx{__shfl_up_sync(0xffffffffu, e[h].re, 2, 4), __shfl_up_sync(0xffffffffu, e[h].im, 2, 4)};
          if (q >= 2) e[h] = cfma(l32[h], y, e[h]);
        }
        if (q == 3) {
#pragma unroll
          for (int h = 0; h < 2; h++)
            asm volatile("st.shared.v2.f32 [%0], {%1,%2};" ::"r"(sb + OFF_CARRY + wg * 512 + (w * 16 + gr + 8 * h) * 8), "f"(e[h].re), "f"(e[h].im) : "memory");
          mbar_arrive(sb + OFF_GBAR);
        }
#pragma unroll
        for (int h = 0; h < 2; h++) e[h] = cplx{__shfl_up_sync(0xffffffffu, e[h].re, 1, 4), __shfl_up_sync(0xffffffffu, e[h].im, 1, 4)};
        wg_wait<1>(); release((u - 1) % NSLOT);
        if (TKT > 500) TS(wg, 3);
      }
      if (kb == QK + 1) {
#pragma unroll
        for (int h = 0; h < 2; h++) {
          pre[h] = Q1 ? cmul(coef[h], pre[h]) : (q >= 1) ? cmul(coef[h], e[h]) : cplx{0.f, 0.f};
          pin(pre[h].re); pin(pre[h].im);
        }
      }
      if (kb > QK) { constexpr int sc[9] = SCUT; scale_u(sc[kb], sc[kb + 1]); }
    }
    TS(wg, 4);
    uint32_t H[56], hf[32];
    cplx hst[2];
    const uint32_t hst_addr = xw + (w * 16 + (lane & 15)) * 128 + (((lane >> 4) ^ (lane & 7)) << 4);
    const uint32_t him = (2 - rank) * 16384;
    uint32_t peer;
    asm volatile("mapa.shared::cluster.u32 %0, %1, %2;" : "=r"(peer) : "r"(sb), "r"(rank ^ 1));
    auto credit = [&]() { if (lane == 0) mbar_arrive_cl(peer + OFF_KBAR + wg * 8); };
    uint32_t g2[8];
#pragma unroll
    for (int kb = 0; kb < 8; kb++) {
      const int u = 16 + kb, slot = u % NSLOT;
      mbar_wait(fullb + 8 * slot, full_par(u));
      TK(kb < 7 ? 24 + kb : 32);
      wg_fence();
#pragma unroll
      for (int kk = 0; kk < 4; kk++)
        wgmma_n128_ss<0, 1, DH128, DH128>(ab, dxw, kb * 16384 + kk * 32, dring, slot * 16384 + kk * 2048 + lbo(8192), 1);
      wg_commit();
      if (kb == 0) { constexpr int sc[9] = SCUT; scale_u(sc[8], 32); }
      if (kb == 4) {
        if (TKT > 500) TS(wg, 5);
        mbar_wait(sb + OFF_CBAR, 0);
        if (TKT > 500) TS(wg, 6);
#pragma unroll
        for (int h = 0; h < 2; h++) {
          const float2 c = lds_f2(sb + OFF_CARRY + wg * 512 + (w * 16 + gr + 8 * h) * 8);
          hst[h] = cfma(lq[h], cplx{c.x, c.y}, pre[h]);
        }
#pragma unroll
        for (int i = 0; i < 2; i++) {
          const uint4 v = lds_u4(sb + OFF_GT + wg * 128 + q * 32 + i * 16);
          g2[4 * i] = v.x; g2[4 * i + 1] = v.y; g2[4 * i + 2] = v.z; g2[4 * i + 3] = v.w;
        }
      }
      if (kb == 0 || TOKB != 1) { wg_wait<1>(); release((u - 1) % NSLOT); }
      if (kb) sched_fence(ck);
      if (kb < 4) {
#pragma unroll
        for (int i = kb * 6; i < kb * 6 + 6; i++) {
          pin(aa[2 * i]); pin(aa[2 * i + 1]);
          H[i] = gelu2_pair(aa[2 * i], aa[2 * i + 1]);
          pin(H[i]);
        }
      } else {
        const int j0 = (kb - 4) * 2;
        uint32_t rr[4], ri[4];
#pragma unroll
        for (int jj = 0; jj < 2; jj++) {
          const int j = j0 + jj;
#pragma unroll
          for (int h = 0; h < 2; h++) {
            const int i = 4 * j + 2 * h;
            const cplx h0 = cfma(lam[h], hst[h], cplx{ure[i], uim[i]});
            hst[h] = cfma(lam[h], h0, cplx{ure[i + 1], uim[i + 1]});
            rr[jj * 2 + h] = bf2_mul(pack_bf16(h0.re, hst[h].re), g2[j]);
            ri[jj * 2 + h] = bf2_mul(pack_bf16(h0.im, hst[h].im), g2[j]);
          }
        }
        const uint32_t a = hst_addr ^ (j0 << 4);
        asm volatile("stmatrix.sync.aligned.m8n8.x4.shared.b16 [%0], {%1,%2,%3,%4};" ::"r"(a), "r"(rr[0]), "r"(rr[1]), "r"(rr[2]), "r"(rr[3]) : "memory");
        asm volatile("stmatrix.sync.aligned.m8n8.x4.shared.b16 [%0], {%1,%2,%3,%4};" ::"r"(a + him), "r"(ri[0]), "r"(ri[1]), "r"(ri[2]), "r"(ri[3]) : "memory");
      }
      if (kb && TOKB == 1) { wg_wait<1>(); release((u - 1) % NSLOT); }
    }
    TS(wg, 7);

    uint4* const psend = g_part + (size_t)(m * 8 + rank) * 3072 + warp * 128 + lane;
    const uint4* const precv = g_part + (size_t)(m * 8 + s) * 3072 + warp * 128 + lane;
    const uint32_t pbuf = OFF_X + warp * 2048 + lane * 16;
    const uint32_t dx0 = ((sb + OFF_X) & 0x3FFFF) >> 4;
    float o[32], fin[32], rho[2];
    uint32_t tr[8];
    uint32_t r0[16], pt[16], sum[16], tag;
    auto recv_issue = [&](uint32_t (&r)[16], int k) {
#pragma unroll
      for (int i = 0; i < 4; i++) ld_b128(precv + k * 1024 + i * 32, r[4 * i], r[4 * i + 1], r[4 * i + 2], r[4 * i + 3]);
    };
    auto stale = [&](uint32_t (&r)[16]) {
      uint32_t r_;
#pragma unroll
      for (int i = 0; i < 16; i += 4) asm("lop3.b32 %0, %0, %1, 1, 0x78;" : "+r"(r[i]) : "r"(tag));
      asm volatile("{.reg .pred p; .reg .b32 t; lop3.b32 t, %1, %2, %3, 0xfe; lop3.b32 t, t, %4, 1, 0xa8; setp.ne.u32 p, t, 0; vote.sync.any.pred p, p, 0xffffffff; selp.u32 %0, 1, 0, p;}"
                   : "=r"(r_) : "r"(r[0]), "r"(r[4]), "r"(r[8]), "r"(r[12]));
      return r_ != 0;
    };
    auto recv_check = [&](uint32_t (&r)[16], int k) {
      if (__builtin_expect(stale(r), 0)) {
        int tries = 0;
#pragma unroll 1
        do { recv_issue(r, k); } while (stale(r) && ++tries < 200000);
      }
    };
    auto gelu_b = [&](int i0, int i1) {
      if (TOKD && i0) sched_fence(ck);
#pragma unroll
      for (int i = i0; i < i1; i++) {
        pin(ab[2 * i]); pin(ab[2 * i + 1]);
        H[24 + i] = gelu2_pair(ab[2 * i], ab[2 * i + 1]);
        pin(H[24 + i]);
      }
      if (TOKD == 2) sched_fence(ck);
    };
    auto step = [&](float (&d)[32], int p, int k, int acc) {
      const uint32_t wo = stage_off(p);
      if (k >= 6 && k < 14) {
        const int kk = k - 6;
        if (kk < 4) wgmma_n64_rs<0, DH128, 1>(d, hf[4 * kk], hf[4 * kk + 1], hf[4 * kk + 2], hf[4 * kk + 3], dx0, wo + 14336 + kk * 32, 1);
        else wgmma_n64_rs<0, DH128, -1>(d, hf[4 * kk], hf[4 * kk + 1], hf[4 * kk + 2], hf[4 * kk + 3], dx0, wo + 22528 + (kk - 4) * 32, 1);
      } else {
        const int kk = k < 6 ? k : k - 8;
        wgmma_n64_rs<1, DH128>(d, H[4 * kk], H[4 * kk + 1], H[4 * kk + 2], H[4 * kk + 3], dx0, wo + (kk / 7) * 30720 + (kk % 7) * 2048, k != 0 || acc);
      }
    };
    auto mma = [&](float (&d)[32], int p, int k0, int k1, int acc) {
      wg_fence();
#pragma unroll
      for (int k = k0; k < k1; k++) step(d, p, k, acc);
      wg_commit();
    };
    auto send_peer = [&](float (&d)[32], uint32_t off) {
#pragma unroll
      for (int i = 0; i < 4; i++)
        asm volatile("st.async.shared::cluster.mbarrier::complete_tx::bytes.v4.b32 [%0], {%1,%2,%3,%4}, [%5];" ::"r"(peer + pbuf + off + i * 512),
                     "r"(pack_bf16(d[8 * i], d[8 * i + 1])), "r"(pack_bf16(d[8 * i + 2], d[8 * i + 3])), "r"(pack_bf16(d[8 * i + 4], d[8 * i + 5])),
                     "r"(pack_bf16(d[8 * i + 6], d[8 * i + 7])), "r"(peer + OFF_RBAR + wg * 8) : "memory");
    };
    auto read_peer = [&](uint32_t (&r)[16], uint32_t off) {
#pragma unroll
      for (int i = 0; i < 4; i++) { const uint4 v = lds_u4(sb + pbuf + off + i * 512); r[4 * i] = v.x; r[4 * i + 1] = v.y; r[4 * i + 2] = v.z; r[4 * i + 3] = v.w; }
    };
    auto send_owner = [&](uint32_t (&r)[16], int k) {
#pragma unroll
      for (int i = 0; i < 4; i++) {
#pragma unroll
        for (int c = 4 * i; c < 4 * i + 4; c++) r[c] = bf2_add(r[c], pack_bf16(o[2 * c], o[2 * c + 1]));
        asm("lop3.b32 %0, %0, 1, %1, 0xb8;" : "+r"(r[4 * i]) : "r"(tag));
        st_b128(psend + (((sp + 1 + k) & 3) * 6 + k) * 1024 + i * 32, r[4 * i], r[4 * i + 1], r[4 * i + 2], r[4 * i + 3]);
      }
    };
    auto load_fin = [&]() {
      mbar_wait(sb + OFF_CBAR, 1);
#pragma unroll
      for (int j = 0; j < 8; j++) {
        const uint4 v = lds_u4(sb + pbuf + 16384 + (j >> 2) * 16384 + (j & 3) * 512);
        fin[4 * j] = __uint_as_float(v.x); fin[4 * j + 1] = __uint_as_float(v.y); fin[4 * j + 2] = __uint_as_float(v.z); fin[4 * j + 3] = __uint_as_float(v.w);
      }
    };
    auto ldk = [&](int pos) { if (pos == K0P) recv_issue(sum, 0); if (pos == K1P) recv_issue(r0, 1); };
    uint32_t ta, la;
    float* op;
    auto out_addr = [&]() {
      const uint32_t tb = sb + OFF_X + stage_off(0) + warp * 4096;
      ta = tb + gr * 256 + ((gr & 3) << 5) + q * 8;
      la = tb + (lane >> 3) * 256 + (((lane & 7) << 4) ^ ((lane >> 3) << 5));
      op = out + (size_t)(m * 128 + wg * 64 + (lane >> 4) * 16 + w * 4 + ((lane >> 3) & 1)) * DM + s * 64 + (lane & 7) * 4;
      if (ADP) { pin(ta); pin(la); asm volatile("" : "+l"(op)); sched_fence(ck); }
    };
    auto arm = [&](uint32_t bytes) { if ((w == 0 && lane == 0)) mbar_expect_tx(sb + OFF_RBAR + wg * 8, bytes); };
    auto mma2 = [&](int k0, int k1) {
      wg_fence();
#pragma unroll
      for (int k = k0; k < k1; k++) { step(o, 0, k, 0); step(fin, 1, k, 0); }
      wg_commit();
    };
    auto hand = [&](int pos) { if (A0 == pos && wg == 0) bar_arrive(5, 256); };
    {
        constexpr int kc[8] = DCUT;
        mbar_wait(fullb, full_par(24));
        mma2(0, kc[0]);
        bar_sync(1 + wg, 128);
        {
          const uint32_t ha = xw + ((lane >> 4) * 8 + (lane & 7)) * 128 + (((2 * w + ((lane >> 3) & 1)) ^ (lane & 7)) << 4);
#pragma unroll
          for (int kk = 0; kk < 8; kk++)
            asm volatile("ldmatrix.sync.aligned.m8n8.x4.trans.shared.b16 {%0,%1,%2,%3}, [%4];" : "=r"(hf[4 * kk]), "=r"(hf[4 * kk + 1]), "=r"(hf[4 * kk + 2]), "=r"(hf[4 * kk + 3])
                         : "r"(ha + (kk >> 2) * him + (kk & 3) * 2048) : "memory");
        }
        tag = lds_u(sb + OFF_EPOCH);
        arm(16384);
        mbar_wait(fullb + 8, full_par(25));
        wg_wait<1>(); release(5);
        if (A0 && wg == 1) bar_sync(5, 256);
        gelu_b(0, 4);   mma2(kc[0], kc[1]); hand(1);
        gelu_b(4, 8);   mma2(kc[1], kc[2]); hand(2);
        gelu_b(8, 12);  mma2(kc[2], kc[3]); hand(3);
        gelu_b(12, 16); mma2(kc[3], kc[4]); hand(4);
        gelu_b(16, 20);
        mbar_wait(fullb + 16, full_par(26));
        mma2(kc[4], kc[5]); hand(5);
        credit();
        gelu_b(20, 24); mma2(kc[5], kc[6]); hand(6);
        gelu_b(24, 28); mma2(kc[6], kc[7]);
        mbar_wait(sb + OFF_XFULL + 16, 1);
        gelu_b(28, 32);
        if (wg == 1) bar_sync(4, 256);
        mma(o, 0, kc[7], 22, 0);
        mma(fin, 1, kc[7], 22, 0);
        bar_arrive(4 - wg, 256);
        TS(wg, 9);
        mbar_wait(sb + OFF_KBAR + wg * 8, 0);
        wg_wait<1>();
        reg_fence(o);
        send_peer(o, 0);
        if (!E1L) { wg_wait<0>(); release(0); release(1); reg_fence(fin); send_peer(fin, 49152 - him); }
    }
#pragma unroll
    for (int p = 2; p < 8; p++) {
      const bool even = p == (OV ? 3 : 4) || p == 6;
      const int po1 = OV ? 4 : 3;
      TR(0);
      if ((LWM >> p) & 1) mbar_wait(sb + OFF_XFULL + 8 * p, 1);
      TR(1);
      bar_sync(3 + wg, 256);
      if (p < 7) mma(o, p, 0, 22, 0); else mma(fin, p, 0, 22, 1);
      if (p < 7 || wg == 0) bar_arrive(4 - wg, 256);
      TR(2);
      if (p != TP) TS(wg, 8 + p);
      if (p == 2 && E1L) { wg_wait<1>(); release(0); release(1); reg_fence(fin); send_peer(fin, 49152 - him); }
      if (p < 7 && !((LWM >> (p + 1)) & 1)) mbar_wait(sb + OFF_XFULL + 8 * (p + 1), 1);
      TR(3);
      ldk(10 * p);
      if (even) {
        arm(8192);
        if (p == 6) {
          mbar_wait(sb + OFF_EMPTY + 32, 0);
          tag = lds_u(sb + OFF_EPOCH);
          recv_check(sum, 0); recv_check(r0, 1);
#pragma unroll
          for (int i = 0; i < 16; i++) sum[i] = bf2_add(sum[i], r0[i]);
        }
        mbar_wait(sb + OFF_KBAR + wg * 8, p != 6);
      } else if (p != po1) {
        if (p == 7) tag = lds_u(sb + OFF_EPOCH);
        mbar_wait(sb + OFF_RBAR + wg * 8, p == 5);
        read_peer(pt, 0);
        if (p == 2) read_peer(r0, him);
        if (p == 7) {
          recv_check(r0, 2);
#pragma unroll
          for (int i = 0; i < 16; i++) { sum[i] = bf2_add(sum[i], bf2_add(r0[i], pt[i])); pin(sum[i]); }
          sched_fence(ck);
        }
      } else {
#pragma unroll
        for (int h = 0; h < 2; h++) { rho[h] = __fdividef(2.f, 4.f + bf_lo(lds_h(sb + OFF_GS + (wg * 64 + w * 16 + gr + 8 * h) * 2))); pin(rho[h]); }
      }
      TR(4);
      if (p == FINP && !FINW) load_fin();
      ldk(10 * p + 1);
      TR(5);
      wg_wait<0>();
      TR(6);
      if (p < 5) release(p);
      if (p < 7) reg_fence(o); else reg_fence(fin);
      ldk(10 * p + 2);
      if (even) {
        if (p == 6) recv_issue(r0, 2);
        send_peer(o, 0);
        if (p == FINP && FINW) load_fin();
      } else if (p == po1) {
        send_owner(r0, 1);
      } else if (p < 7) {
        send_owner(pt, p == 2 ? 0 : 2);
        __syncwarp();
        credit();
      }
      ldk(10 * p + 3);
      TR(7);
    }
    {
      TS(wg, 16);
      if (ADP == 0) out_addr();
#pragma unroll
      for (int qq = 0; qq < 4; qq += QS) {
#pragma unroll
        for (int qt = qq; qt < qq + QS; qt++) {
          const int h = qt & 1, ch = qt >> 1;
#pragma unroll
          for (int j = 0; j < 4; j++) {
            const int i = ch * 8 + j * 2 + h;
            asm volatile("st.shared.v2.f32 [%0], {%1,%2};" ::"r"((ta ^ (j << 5)) + h * 2048 + ch * 128),
                         "f"((fin[2 * i] + bf_lo(sum[i])) * rho[h]), "f"((fin[2 * i + 1] + bf_hi(sum[i])) * rho[h]) : "memory");
          }
        }
        __syncwarp();
#pragma unroll
        for (int qt = qq; qt < qq + QS; qt++) {
          const int h = qt & 1, ch = qt >> 1;
#pragma unroll
          for (int r = 0; r < 2; r++)
            *reinterpret_cast<uint4*>(op + (r * 32 + h * 2) * DM + ch * 32) = lds_u4(la + (h * 2 + r) * 1024 + ch * 128);
        }
      }
      if (FF1 || ADP) asm volatile("st.shared.u32 [%0], %1;" ::"r"(sb + OFF_EPOCH + 4), "r"(ck) : "memory");
      if ((warp == 4 && lane == 0)) g_epoch[b] = tag;
      TS(wg, 17); TG(wg); TRD(); TDUMP();
    }
  } else {
    const int lane = OPH ? __shfl_sync(0xffffffffu, lane0, lane0) : lane0;
    asm volatile("setmaxnreg.dec.sync.aligned.u32 56;");
    int wsel = warp;
    asm("" : "+r"(wsel));
    if (wsel > 8) {
      const uint4* gwp = reinterpret_cast<const uint4*>(gate_w) + (lane & 7);
      uint4 gw[4];
      if (warp != 11) {
        const int t = OPH ? (warp - 9) * 32 + lane : threadIdx.x - 288;
        unsigned par;
        asm volatile("ld.relaxed.gpu.global.u32 %0, [%1];" : "=r"(par) : "l"(g_epoch + b) : "memory");
        const float pr = bf_ld(lam_re + s * 64 + t), pi = bf_ld(lam_im + s * 64 + t), pd = bf_ld(log_dt + s * 64 + t);
#pragma unroll
        for (int i = 0; i < 4; i++) gw[i] = __ldg(gwp + i * 8);
        asm volatile("barrier.cluster.wait.aligned;" ::: "memory");
        par = __shfl_sync(0xffffffffu, (par + 1) & 1, 0);
        cplx l64 = make_lam(pr, pi, pd);
        {
          const float inv = __fdividef(1.f, fmaf(pr, pr, pi * pi));
          const cplx cf = cmul(cplx{l64.re - 1.f, l64.im}, cplx{pr * inv, -pi * inv});
          asm volatile("st.shared.v4.f32 [%0], {%1,%2,%3,%4};" ::"r"(sb + OFF_LC + t * 16), "f"(l64.re), "f"(l64.im), "f"(cf.re), "f"(cf.im) : "memory");
          mbar_arrive(sb + OFF_LBAR);
        }
#pragma unroll
        for (int i = 0; i < 6; i++) l64 = cmul(l64, l64);
        cplx l128 = cmul(l64, l64);
        pin(l128.re); pin(l128.im);
        gate_rows<1>(sb, lane, xrot, s * 16 + (warp - 9) * 4, gw, gwp, g_gate + m * 128, par);
        if (t == 0) TS(3, 6);
        uint32_t vr[15], vi[15];
#pragma unroll
        for (int i = 0; i < 15; i++) { vr[i] = par; vi[i] = 0; pin(vr[i]); pin(vi[i]); }
        mbar_wait(sb + OFF_GBAR, 0);
        const float2 e0 = lds_f2(sb + OFF_CARRY + t * 8), e1 = lds_f2(sb + OFF_CARRY + 512 + t * 8);
        float2* eb = g_end + s * 1024 + t;
        {
          const cplx e = cfma(l64, cplx{e0.x, e0.y}, cplx{e1.x, e1.y});
          const unsigned long long v = ((unsigned long long)__float_as_uint(e.im) << 32) | ((__float_as_uint(e.re) & ~1u) | par);
          asm volatile("st.relaxed.gpu.global.b64 [%0], %1;" ::"l"(eb + m * 64), "l"(v) : "memory");
        }
        if (t == 0) TS(3, 1);
        cplx S = {0.f, 0.f};
        {
          if (LBD) __nanosleep(LBD);
          const float2* e15 = eb + (m - 15) * 64;
          int tries = 0;
          bool bad;
#pragma unroll 1
          do {
#pragma unroll
            for (int i = 0; i < 15; i++)
              asm volatile("{.reg .pred p; .reg .b64 v; mov.b64 v, {%0,%1}; setp.ge.s32 p, %3, %4; @p ld.relaxed.gpu.global.b64 v, [%2]; mov.b64 {%0,%1}, v;}"
                           : "+r"(vr[i]), "+r"(vi[i]) : "l"(e15 + i * 64), "r"(m), "r"(15 - i) : "memory");
            uint32_t x = vr[0] ^ par;
#pragma unroll
            for (int i = 1; i < 15; i++) asm("lop3.b32 %0, %0, %1, %2, 0xf6;" : "+r"(x) : "r"(vr[i]), "r"(par));
            bad = __any_sync(0xffffffffu, x & 1);
          } while (bad && ++tries < 200000);
          if (t == 0) TS(3, 2);
          S = cplx{__uint_as_float(vr[0] ^ par), __uint_as_float(vi[0])};
#pragma unroll
          for (int i = 1; i < 15; i++) S = cfma(l128, S, cplx{__uint_as_float(vr[i] ^ par), __uint_as_float(vi[i])});
        }
        const cplx S1 = cfma(l64, S, cplx{e0.x, e0.y});
        asm volatile("st.shared.v2.f32 [%0], {%1,%2};" ::"r"(sb + OFF_CARRY + t * 8), "f"(S.re), "f"(S.im) : "memory");
        asm volatile("st.shared.v2.f32 [%0], {%1,%2};" ::"r"(sb + OFF_CARRY + 512 + t * 8), "f"(S1.re), "f"(S1.im) : "memory");
        mbar_arrive(sb + OFF_CBAR);
        if (t == 0) TS(3, 3);
      } else {
        if (lane == 0) TG(2);
#pragma unroll
        for (int i = 0; i < 4; i++) gw[i] = __ldg(gwp + i * 8);
        unsigned par;
        asm volatile("ld.relaxed.gpu.global.u32 %0, [%1];" : "=r"(par) : "l"(g_epoch + b) : "memory");
        const uint32_t dk = __ldg(reinterpret_cast<const uint32_t*>(dskip + s * 64) + lane), bb = __ldg(reinterpret_cast<const uint32_t*>(b2 + s * 64) + lane);
        asm volatile("barrier.cluster.wait.aligned;" ::: "memory");
        if (lane == 0) asm volatile("st.shared.u32 [%0], %1;" ::"r"(sb + OFF_EPOCH), "r"(par + 1) : "memory");
        par = (par + 1) & 1;
        gate_rows<2>(sb, lane, xrot, s * 16 + 8, gw, gwp, g_gate + m * 128, par);
        if (lane == 0) TS(3, 0);
        mbar_wait(sb + OFF_GBAR, 0);
        asm volatile("st.shared.v2.u32 [%0], {%1,%2};" ::"r"(sb + OFF_DB + lane * 8), "r"(dk), "r"(bf2_add(bb, bb)) : "memory");
        uint32_t g0, g1, g2, g3;
        int tries = 0;
#pragma unroll 1
        do {
          asm volatile("ld.relaxed.gpu.global.v4.u32 {%0,%1,%2,%3}, [%4];" : "=r"(g0), "=r"(g1), "=r"(g2), "=r"(g3) : "l"(g_gate + m * 128 + lane * 4) : "memory");
          g0 ^= par; g1 ^= par; g2 ^= par; g3 ^= par;
        } while (((g0 | g1 | g2 | g3) & 1) && ++tries < 200000);
        asm volatile("st.shared.v2.u32 [%0], {%1,%2};" ::"r"(sb + OFF_GS + lane * 8), "r"(pack_bf16(__uint_as_float(g0), __uint_as_float(g1))),
                     "r"(pack_bf16(__uint_as_float(g2), __uint_as_float(g3))) : "memory");
        const uint32_t gt = sb + OFF_GT + (lane >> 4) * 128 + (lane & 1) * 64 + ((lane >> 1) & 7) * 4;
        asm volatile("st.shared.u32 [%0], %1;" ::"r"(gt), "r"(pack_bf16(__uint_as_float(g0), __uint_as_float(g1))) : "memory");
        asm volatile("st.shared.u32 [%0], %1;" ::"r"(gt + 32), "r"(pack_bf16(__uint_as_float(g2), __uint_as_float(g3))) : "memory");
        mbar_arrive(sb + OFF_CBAR);
        if (lane == 0) TS(3, 4);
      }
      {
        mbar_wait(sb + OFF_CBAR, 0);
        const int gr = lane >> 2, q = lane & 3;
        float2 db[8];
#pragma unroll
        for (int j = 0; j < 8; j++) db[j] = lds_f2(sb + OFF_DB + j * 32 + q * 8);
        mbar_wait(sb + OFF_XFULL + 16, 1);
        mbar_wait(sb + OFF_EMPTY + 16, 0);
#pragma unroll 1
        for (int cw = warp - 9; cw < 8; cw += 3) {
          const float r0 = 0.5f * bf_lo(lds_h(sb + OFF_GS + (cw * 16 + gr) * 2)), r1 = 0.5f * bf_lo(lds_h(sb + OFF_GS + (cw * 16 + gr) * 2 + 16));
          const uint32_t xa = sb + OFF_X + (1 + rank) * 16384 + (cw * 16 + (lane & 15)) * 128 + (((lane >> 4) ^ (lane & 7)) << 4);
          uint32_t xv[16];
#pragma unroll
          for (int i = 0; i < 4; i++)
            asm volatile("ldmatrix.sync.aligned.m8n8.x4.shared.b16 {%0,%1,%2,%3}, [%4];" : "=r"(xv[4 * i]), "=r"(xv[4 * i + 1]), "=r"(xv[4 * i + 2]), "=r"(xv[4 * i + 3])
                         : "r"(xa ^ (i << 5)) : "memory");
          __syncwarp();
#pragma unroll
          for (int j = 0; j < 8; j++) {
            const uint32_t x0 = bf2_mul(xv[2 * j], __float_as_uint(db[j].x)), x1 = bf2_mul(xv[2 * j + 1], __float_as_uint(db[j].x));
            pin(db[j].y);
            const float bl = bf_lo(__float_as_uint(db[j].y)), bh = bf_hi(__float_as_uint(db[j].y));
            asm volatile("st.shared.v4.f32 [%0], {%1,%2,%3,%4};" ::"r"(sb + OFF_X + 16384 + (j >> 2) * 16384 + cw * 2048 + (j & 3) * 512 + lane * 16), "f"(fmaf(bf_lo(x0), r0, bl)),
                         "f"(fmaf(bf_hi(x0), r0, bh)), "f"(fmaf(bf_lo(x1), r1, bl)), "f"(fmaf(bf_hi(x1), r1, bh)) : "memory");
          }
        }
        mbar_arrive(sb + OFF_CBAR);
        if (warp == 9 && lane == 0) TS(3, 5);
      }
    } else {
      asm volatile("barrier.cluster.wait.aligned;" ::: "memory");
      if (elect_one()) {
        TS(2, 1);
        const uint32_t t0 = clock();
#pragma unroll 1
        for (int u = W0; u < 8; u++) {
          if (u >= 1) while ((uint32_t)clock() - t0 < D0 + (u - 1) * D1) {}
          mbar_expect_tx(sb + OFF_XFULL + 8 * u, 32768);
          tma5d_mc(sb + OFF_X + ((u + xrot) & 7) * 16384 + rank * 8192, &maps.x, u * 64, 2 * m + rank, sb + OFF_XFULL + 8 * u);
          const int sl = u < 6 ? u : u - 6;
          if (u >= 6) mbar_wait(sb + OFF_EMPTY + 8 * sl, 0);
          tma2d(sb + OFF_RING + sl * 16384, &maps.bre, u * 64, s * 64, sb + OFF_XFULL + 8 * u);
          tma2d(sb + OFF_RING + sl * 16384 + 8192, &maps.bim, u * 64, s * 64, sb + OFF_XFULL + 8 * u);
          if (u == 2) asm volatile("prefetch.tensormap [%0];" ::"l"(&maps.w1b) : "memory");
          if (u == PA && m < 8) asm volatile("cp.async.bulk.prefetch.tensor.3d.L2.global [%0, {%1,%2,%3}];" ::"l"(&maps.w1b), "r"(0), "r"(m * 64), "r"(s * 7) : "memory");
        }
        TS(2, 5);
        int slot = 2; uint32_t ph = 0;
#pragma unroll 1
        for (int u = 8; u < 24; u++) {
          const uint32_t fb = sb + OFF_FULL + 8 * slot, dst = sb + OFF_RING + slot * 16384;
          mbar_wait(sb + OFF_EMPTY + 8 * slot, ph);
          TS2(0, u);
          if (u < 16) {
            mbar_expect_tx(fb, 12288);
            tma3d(dst, &maps.w1b, 0, (u - 8) * 64, s * 7, fb);
            if (TMP2 && u < 12) asm volatile("prefetch.tensormap [%0];" ::"l"(&maps.w1a + (u - 8)) : "memory");
          } else {
            mbar_expect_tx(fb, 16384);
            tma2d(dst, &maps.w1a, s * 224 + 96, ((u - xrot) & 7) * 64, fb);
            tma2d(dst + 8192, &maps.w1a, s * 224 + 160, ((u - xrot) & 7) * 64, fb);
          }
          if (u == PB) asm volatile("cp.async.bulk.prefetch.tensor.2d.L2.global [%0, {%1,%2}];" ::"l"(&maps.w1a), "r"(s * 224 + 96 + (m & 1) * 64), "r"((m >> 1) * 64) : "memory");
          if (u == PC) {
            const int c = ((sp + 1 + (m >> 3)) & 3) * 128 + ((m >> 2) & 1) * 64;
            if (m & 2) asm volatile("cp.async.bulk.prefetch.tensor.2d.L2.global [%0, {%1,%2}];" ::"l"((m & 1) ? &maps.cim : &maps.cre), "r"(s * 64), "r"(c) : "memory");
            else asm volatile("cp.async.bulk.prefetch.tensor.2d.L2.global [%0, {%1,%2}];" ::"l"(&maps.w2), "r"(c), "r"(s * 224 + (m & 1) * 112) : "memory");
          }
          if (++slot == NSLOT) { slot = 0; ph ^= 1; }
        }
#pragma unroll 1
        for (int j = 0; j < 3; j++) {
          const uint32_t fb = sb + OFF_FULL + 8 * j;
          mbar_wait(sb + OFF_EMPTY + 8 + 8 * j, 1);
          mbar_expect_tx(fb, j == 1 ? 32768 : 28672);
#pragma unroll
          for (int e = 0; e < 2; e++) {
            const int c = ((sp + 1 + e) & 3) * 128 + ((rank ^ 1) << 6);
            const uint32_t dst = sb + OFF_X + stage_off(e);
            if (j == 1) {
              tma2d(dst + 14336, &maps.cre, s * 64, c, fb);
              tma2d(dst + 22528, &maps.cim, s * 64, c, fb);
            } else {
              tma2d(dst + j * 15360, &maps.w2, c, s * 224 + j * 56, fb);
            }
          }
        }
#pragma unroll 1
        for (int p = 2; p < 8; p++) {
          const int pp = (OV && (p == 3 || p == 4)) ? 7 - p : p;
          const int c = pp < 4 ? ((sp + pp - 1) & 3) * 128 + (rank << 6) : ((sp + 1 + (pp >> 1)) & 3) * 128 + (((rank ^ pp ^ 1) & 1) << 6);
          const uint32_t fb = sb + OFF_XFULL + 8 * p, dst = sb + OFF_X + stage_off(p);
          if (p == 2 || p > 3) mbar_wait(sb + OFF_EMPTY + (p == 2 ? 40 : (p - 4) * 8), p == 2);
          TS2(0, 32 + p);
          mbar_expect_tx(fb, 45056);
          tma2d(dst, &maps.w2, c, s * 224, fb);
          tma2d(dst + 14336, &maps.cre, s * 64, c, fb);
          tma2d(dst + 22528, &maps.cim, s * 64, c, fb);
          tma2d(dst + 30720, &maps.w2, c, s * 224 + 112, fb);
          if (p == PD) {
            const int c2 = ((sp + 3 + (m >> 3)) & 3) * 128 + ((m >> 2) & 1) * 64;
            if (m & 2) asm volatile("cp.async.bulk.prefetch.tensor.2d.L2.global [%0, {%1,%2}];" ::"l"((m & 1) ? &maps.cim : &maps.cre), "r"(s * 64), "r"(c2) : "memory");
            else asm volatile("cp.async.bulk.prefetch.tensor.2d.L2.global [%0, {%1,%2}];" ::"l"(&maps.w2), "r"(c2), "r"(s * 224 + (m & 1) * 112) : "memory");
          }
        }
        TS(2, 2);
      }
    }
  }
}

typedef CUresult (*EncFn)(CUtensorMap*, CUtensorMapDataType, cuuint32_t, void*, const cuuint64_t*, const cuuint64_t*, const cuuint32_t*,
                          const cuuint32_t*, CUtensorMapInterleave, CUtensorMapSwizzle, CUtensorMapL2promotion, CUtensorMapFloatOOBfill);

void encode(EncFn f, CUtensorMap* mp, const void* p, int rank, const cuuint64_t* dims, const cuuint64_t* strides, const cuuint32_t* box, CUtensorMapSwizzle sw) {
  cuuint32_t es[5] = {1, 1, 1, 1, 1};
  f(mp, CU_TENSOR_MAP_DATA_TYPE_BFLOAT16, rank, const_cast<void*>(p), dims, strides, box, es, CU_TENSOR_MAP_INTERLEAVE_NONE, sw,
    CU_TENSOR_MAP_L2_PROMOTION_L2_128B, CU_TENSOR_MAP_FLOAT_OOB_FILL_NONE);
}

}

extern "C" void kernel_launch(void* const* d_in, const int* in_sizes, int n_in, void* d_out, int out_size) {
  typedef const __nv_bfloat16* bp;
  bp x = (bp)d_in[0], lre = (bp)d_in[1], lim = (bp)d_in[2], bre = (bp)d_in[3], bim = (bp)d_in[4], cre = (bp)d_in[5], cim = (bp)d_in[6],
     ldt = (bp)d_in[7], dsk = (bp)d_in[8], w1 = (bp)d_in[10], b1 = (bp)d_in[11], w2 = (bp)d_in[12], b2 = (bp)d_in[13], gw = (bp)d_in[14];
  static EncFn enc = nullptr;
  if (!enc) {
    void* f = nullptr;
    cudaDriverEntryPointQueryResult qr;
    cudaGetDriverEntryPoint("cuTensorMapEncodeTiled", &f, cudaEnableDefault, &qr);
    enc = (EncFn)f;
    cudaFuncSetAttribute(fused_kernel, cudaFuncAttributeMaxDynamicSharedMemorySize, SMEM_BYTES);
  }
  Maps maps;
  {
    cuuint64_t d[5] = {DM, 2, 4, 8, SEQ / 64}, st[4] = {DM * 2, 16 * DM * 2, 2 * DM * 2, 64 * DM * 2};
    cuuint32_t bx[5] = {64, 2, 4, 8, 1};
    encode(enc, &maps.x, x, 5, d, st, bx, CU_TENSOR_MAP_SWIZZLE_128B);
  }
  {
    cuuint64_t d[2] = {DM, DM}, st[1] = {DM * 2};
    cuuint32_t bx[2] = {64, 64};
    encode(enc, &maps.bre, bre, 2, d, st, bx, CU_TENSOR_MAP_SWIZZLE_128B);
    encode(enc, &maps.bim, bim, 2, d, st, bx, CU_TENSOR_MAP_SWIZZLE_128B);
    encode(enc, &maps.cre, cre, 2, d, st, bx, CU_TENSOR_MAP_SWIZZLE_128B);
    encode(enc, &maps.cim, cim, 2, d, st, bx, CU_TENSOR_MAP_SWIZZLE_128B);
  }
  {
    cuuint64_t d[2] = {FF, DM}, st[1] = {FF * 2};
    cuuint32_t bx[2] = {64, 64};
    encode(enc, &maps.w1a, w1, 2, d, st, bx, CU_TENSOR_MAP_SWIZZLE_128B);
    cuuint64_t d3[3] = {32, DM, FF / 32}, st3[2] = {FF * 2, 64};
    cuuint32_t bx3[3] = {32, 64, 3};
    encode(enc, &maps.w1b, w1, 3, d3, st3, bx3, CU_TENSOR_MAP_SWIZZLE_64B);
  }
  {
    cuuint64_t d[2] = {DM, FF}, st[1] = {DM * 2};
    cuuint32_t bx[2] = {64, 112};
    encode(enc, &maps.w2, w2, 2, d, st, bx, CU_TENSOR_MAP_SWIZZLE_128B);
  }
  fused_kernel<<<128, 384, SMEM_BYTES>>>(lre, lim, ldt, dsk, b1, b2, gw, w1, w2, cre, cim, (float*)d_out, maps);
}
```

```cpp
#include <cuda_runtime.h>
#include <cuda_bf16.h>
#include <cuda.h>
#include <stdint.h>

namespace {

constexpr int SEQ = 2048, DM = 512, FF = 1792;
constexpr int NSLOT = 6;
constexpr uint32_t OFF_X = 0, OFF_RING = 131072, OFF_MISC = 229376;
constexpr uint32_t OFF_XFULL = OFF_MISC, OFF_FULL = OFF_XFULL + 64, OFF_RBAR = OFF_FULL + 48, OFF_EMPTY = OFF_RBAR + 16, OFF_KBAR = OFF_EMPTY + 48,
                   OFF_GBAR = OFF_KBAR + 16, OFF_LBAR = OFF_GBAR + 8, OFF_CBAR = OFF_LBAR + 8, OFF_EPOCH = OFF_CBAR + 8;
constexpr uint32_t OFF_LC = OFF_MISC + 256;
constexpr uint32_t OFF_GS = OFF_LC;
constexpr uint32_t OFF_GT = OFF_LC + 256;
constexpr uint32_t OFF_DB = OFF_LC + 512;
constexpr uint32_t OFF_CARRY = OFF_LC + 1024;
constexpr uint32_t SMEM_BYTES = OFF_CARRY + 1024;
static_assert(SMEM_BYTES <= 232448, "smem");

struct Maps { CUtensorMap x, bre, bim, w1b, w1a, w2, cre, cim; };
__host__ __device__ constexpr uint32_t stage_off(int p) { return 49152 + 45056 * (((p >> 1) & 1) + 2 * (p & 1)); }
__host__ __device__ constexpr uint32_t full_par(int u) { return ((u - 8) / 6 + (u % 6 == 0)) & 1; }

__device__ uint4 g_part[16 * 8 * 3 * 1024];
__device__ float2 g_end[8 * 16 * 64];
__device__ unsigned g_gate[SEQ];
__device__ unsigned g_epoch[128];

__device__ __forceinline__ void mbar_init(uint32_t bar, uint32_t cnt) { asm volatile("mbarrier.init.shared::cta.b64 [%0], %1;" ::"r"(bar), "r"(cnt)); }
__device__ __forceinline__ void mbar_expect_tx(uint32_t bar, uint32_t bytes) { asm volatile("mbarrier.arrive.expect_tx.shared::cta.b64 _, [%0], %1;" ::"r"(bar), "r"(bytes) : "memory"); }
__device__ __forceinline__ void mbar_arrive(uint32_t bar) { asm volatile("mbarrier.arrive.shared::cta.b64 _, [%0];" ::"r"(bar) : "memory"); }
__device__ __forceinline__ void mbar_arrive_cl(uint32_t cbar) { asm volatile("mbarrier.arrive.shared::cluster.b64 _, [%0];" ::"r"(cbar) : "memory"); }
__device__ __forceinline__ void mbar_wait(uint32_t bar, uint32_t parity) {
  asm volatile(
      "{\n.reg .pred p;\n.reg .u32 c;\n"
      "mbarrier.try_wait.parity.shared::cta.b64 p, [%0], %1;\n"
      "@p bra.uni LAB_DONE;\n"
      "mov.u32 c, 0;\n"
      "LAB_WAIT:\n"
      "mbarrier.try_wait.parity.shared::cta.b64 p, [%0], %1;\n"
      "@p bra.uni LAB_DONE;\n"
      "add.u32 c, c, 1;\nsetp.lt.u32 p, c, 200000;\n@p bra.uni LAB_WAIT;\n"
      "LAB_DONE:\n}" ::"r"(bar), "r"(parity) : "memory");
}
__device__ __forceinline__ void tma2d(uint32_t dst, const CUtensorMap* m, int c0, int c1, uint32_t bar) {
  asm volatile("cp.async.bulk.tensor.2d.shared::cluster.global.mbarrier::complete_tx::bytes [%0], [%1, {%3,%4}], [%2];"
               ::"r"(dst), "l"(m), "r"(bar), "r"(c0), "r"(c1) : "memory");
}
__device__ __forceinline__ void tma3d(uint32_t dst, const CUtensorMap* m, int c0, int c1, int c2, uint32_t bar) {
  asm volatile("cp.async.bulk.tensor.3d.shared::cluster.global.mbarrier::complete_tx::bytes [%0], [%1, {%3,%4,%5}], [%2];"
               ::"r"(dst), "l"(m), "r"(bar), "r"(c0), "r"(c1), "r"(c2) : "memory");
}
__device__ __forceinline__ void tma5d(uint32_t dst, const CUtensorMap* m, int c0, int c4, uint32_t bar) {
  asm volatile("cp.async.bulk.tensor.5d.shared::cluster.global.mbarrier::complete_tx::bytes [%0], [%1, {%3,%5,%5,%5,%4}], [%2];"
               ::"r"(dst), "l"(m), "r"(bar), "r"(c0), "r"(c4), "r"(0) : "memory");
}
__device__ __forceinline__ void tma5d_mc(uint32_t dst, const CUtensorMap* m, int c0, int c4, uint32_t bar) {
  asm volatile("cp.async.bulk.tensor.5d.shared::cluster.global.mbarrier::complete_tx::bytes.multicast::cluster [%0], [%1, {%3,%5,%5,%5,%4}], [%2], %6;"
               ::"r"(dst), "l"(m), "r"(bar), "r"(c0), "r"(c4), "r"(0), "h"((uint16_t)3) : "memory");
}
__device__ __forceinline__ void map_prefetch(const CUtensorMap* m) { asm volatile("prefetch.tensormap [%0];" ::"l"(m) : "memory"); }
__device__ __forceinline__ bool elect_one() {
  uint32_t pred;
  asm volatile("{.reg .pred P; elect.sync _|P, 0xffffffff; selp.u32 %0, 1, 0, P;}" : "=r"(pred));
  return pred != 0;
}
__device__ __forceinline__ void cluster_wait() { asm volatile("barrier.cluster.wait.aligned;" ::: "memory"); }
__device__ __forceinline__ void wg_fence() { asm volatile("wgmma.fence.sync.aligned;" ::: "memory"); }
__device__ __forceinline__ void wg_commit() { asm volatile("wgmma.commit_group.sync.aligned;" ::: "memory"); }
template <int N> __device__ __forceinline__ void wg_wait() { asm volatile("wgmma.wait_group.sync.aligned %0;" ::"n"(N) : "memory"); }
__device__ __forceinline__ void pin(float& a) { asm volatile("" : "+f"(a)::"memory"); }
__device__ __forceinline__ void pin(uint32_t& a) { asm volatile("" : "+r"(a)::"memory"); }
template <int N> __device__ __forceinline__ void reg_fence(float (&d)[N]) {
#pragma unroll
  for (int i = 0; i < N; i++) pin(d[i]);
}
__device__ __forceinline__ void sched_fence(uint32_t& ck) { asm volatile("{.reg .b32 c; mov.u32 c, %%clock; xor.b32 %0, %0, c;}" : "+r"(ck)::"memory"); }
__device__ __forceinline__ void bar_sync(int id, int n) { asm volatile("bar.sync %0, %1;" ::"r"(id), "r"(n) : "memory"); }
__device__ __forceinline__ void bar_arrive(int id, int n) { asm volatile("bar.arrive %0, %1;" ::"r"(id), "r"(n) : "memory"); }
constexpr uint32_t DH128 = (1024 >> 4) | (1u << 30), DH64 = (512 >> 4) | (2u << 30);
__host__ __device__ constexpr uint32_t lbo(uint32_t bytes) { return (bytes >> 4) << 20; }
__device__ __forceinline__ uint32_t pack_bf16(float lo, float hi) { uint32_t r; asm("cvt.rn.bf16x2.f32 %0, %1, %2;" : "=r"(r) : "f"(hi), "f"(lo)); return r; }
__device__ __forceinline__ float bf_lo(uint32_t v) { return __uint_as_float(v << 16); }
__device__ __forceinline__ float bf_hi(uint32_t v) { return __uint_as_float(v & 0xffff0000u); }
__device__ __forceinline__ float bf_ld(const __nv_bfloat16* p) { return __bfloat162float(__ldg(p)); }
__device__ __forceinline__ uint32_t late16(uint32_t bar) {
  uint32_t r;
  asm volatile("{.reg .pred p; mbarrier.test_wait.parity.shared::cta.b64 p, [%1], 0; selp.u32 %0, 16, 0, p;}" : "=r"(r) : "r"(bar) : "memory");
  return r;
}
__device__ __forceinline__ float2 lds_f2(uint32_t a) { float2 v; asm volatile("ld.shared.v2.f32 {%0,%1}, [%2];" : "=f"(v.x), "=f"(v.y) : "r"(a)); return v; }
__device__ __forceinline__ uint32_t lds_h(uint32_t a) { uint32_t v; asm volatile("ld.shared.u16 %0, [%1];" : "=r"(v) : "r"(a)); return v; }
__device__ __forceinline__ uint32_t lds_u(uint32_t a) { uint32_t v; asm volatile("ld.shared.u32 %0, [%1];" : "=r"(v) : "r"(a)); return v; }
__device__ __forceinline__ uint4 lds_u4(uint32_t a) { uint4 v; asm volatile("ld.shared.v4.u32 {%0,%1,%2,%3}, [%4];" : "=r"(v.x), "=r"(v.y), "=r"(v.z), "=r"(v.w) : "r"(a)); return v; }
__device__ __forceinline__ void sts_u(uint32_t a, uint32_t v) { asm volatile("st.shared.u32 [%0], %1;" ::"r"(a), "r"(v) : "memory"); }
__device__ __forceinline__ void sts_u2(uint32_t a, uint32_t x, uint32_t y) { asm volatile("st.shared.v2.u32 [%0], {%1,%2};" ::"r"(a), "r"(x), "r"(y) : "memory"); }
__device__ __forceinline__ void sts_f2(uint32_t a, float x, float y) { asm volatile("st.shared.v2.f32 [%0], {%1,%2};" ::"r"(a), "f"(x), "f"(y) : "memory"); }
__device__ __forceinline__ void sts_f4(uint32_t a, float x, float y, float z, float w) {
  asm volatile("st.shared.v4.f32 [%0], {%1,%2,%3,%4};" ::"r"(a), "f"(x), "f"(y), "f"(z), "f"(w) : "memory");
}
__device__ __forceinline__ void st_b128(uint4* p, uint32_t a, uint32_t b, uint32_t c, uint32_t d) {
  asm volatile("st.relaxed.gpu.global.v4.b32 [%0], {%1,%2,%3,%4};" ::"l"(p), "r"(a), "r"(b), "r"(c), "r"(d) : "memory");
}
__device__ __forceinline__ void ld_b128(const uint4* p, uint32_t& a, uint32_t& b, uint32_t& c, uint32_t& d) {
  asm volatile("{.reg .b64 l, h; .reg .b128 v; ld.relaxed.gpu.global.b128 v, [%4]; mov.b128 {l,h}, v; mov.b64 {%0,%1}, l; mov.b64 {%2,%3}, h;}"
               : "=r"(a), "=r"(b), "=r"(c), "=r"(d) : "l"(p) : "memory");
}
__device__ __forceinline__ uint32_t bf2_mul(uint32_t a, uint32_t b) { uint32_t r; asm("mul.rn.bf16x2 %0, %1, %2;" : "=r"(r) : "r"(a), "r"(b)); return r; }
__device__ __forceinline__ uint32_t bf2_add(uint32_t a, uint32_t b) { uint32_t r; asm("add.rn.bf16x2 %0, %1, %2;" : "=r"(r) : "r"(a), "r"(b)); return r; }
__device__ __forceinline__ uint32_t bf2_fma(uint32_t a, uint32_t b, uint32_t c) { uint32_t r; asm("fma.rn.bf16x2 %0, %1, %2, %3;" : "=r"(r) : "r"(a), "r"(b), "r"(c)); return r; }
__device__ __forceinline__ uint32_t gelu2_pair(float a, float b) {
  const uint32_t v = pack_bf16(a, b);
  uint32_t t;
  asm("tanh.approx.bf16x2 %0, %1;" : "=r"(t) : "r"(bf2_fma(v, bf2_fma(bf2_mul(v, v), 0x3d123d12u, 0xbe4fbe4fu), v)));
  return bf2_fma(v, t, v);
}
struct cplx { float re, im; };
__device__ __forceinline__ cplx cmul(cplx a, cplx b) { return {fmaf(a.re, b.re, -a.im * b.im), fmaf(a.re, b.im, a.im * b.re)}; }
__device__ __forceinline__ cplx cfma(cplx a, cplx b, cplx c) {
  return {fmaf(a.re, b.re, fmaf(-a.im, b.im, c.re)), fmaf(a.re, b.im, fmaf(a.im, b.re, c.im))};
}
__device__ __forceinline__ cplx make_lam(float lre, float lim, float ldt) {
  float dt = __bfloat162float(__float2bfloat16_rn(expf(ldt)));
  float mag = expf(dt * lre), sn, cs;
  sincospif(dt * lim * 0.31830988618379067f, &sn, &cs);
  return {mag * cs, mag * sn};
}

template<int TA,int TB,uint32_t AH,uint32_t BH> __device__ __forceinline__ void wgmma_n64_ss(float (&d)[32], uint32_t al, uint32_t ao, uint32_t bl, uint32_t bo, int scale_d){
  asm volatile("{.reg .pred p; .reg .b32 t, v; .reg .b64 da, db; setp.ne.b32 p, %36, 0; add.u32 t, %32, %33; mov.b64 da, {t, %39}; add.u32 v, %34, %35; mov.b64 db, {v, %40};\n"
   "wgmma.mma_async.sync.aligned.m64n64k16.f32.bf16.bf16 {%0,%1,%2,%3,%4,%5,%6,%7,%8,%9,%10,%11,%12,%13,%14,%15,%16,%17,%18,%19,%20,%21,%22,%23,%24,%25,%26,%27,%28,%29,%30,%31}, da, db, p, 1, 1, %37, %38;}"
   : "+f"(d[0]),"+f"(d[1]),"+f"(d[2]),"+f"(d[3]),"+f"(d[4]),"+f"(d[5]),"+f"(d[6]),"+f"(d[7]),"+f"(d[8]),"+f"(d[9]),"+f"(d[10]),"+f"(d[11]),"+f"(d[12]),"+f"(d[13]),"+f"(d[14]),"+f"(d[15]),"+f"(d[16]),"+f"(d[17]),"+f"(d[18]),"+f"(d[19]),"+f"(d[20]),"+f"(d[21]),"+f"(d[22]),"+f"(d[23]),"+f"(d[24]),"+f"(d[25]),"+f"(d[26]),"+f"(d[27]),"+f"(d[28]),"+f"(d[29]),"+f"(d[30]),"+f"(d[31])
   : "r"(al),"r"(ao >> 4),"r"(bl),"r"(bo >> 4),"r"(scale_d),"n"(TA),"n"(TB),"n"(AH),"n"(BH));
}
template<int TB,uint32_t BH,int SA=1> __device__ __forceinline__ void wgmma_n64_rs(float (&d)[32], uint32_t a0,uint32_t a1,uint32_t a2,uint32_t a3, uint32_t bl, uint32_t bo, int scale_d){
  asm volatile("{.reg .pred p; .reg .b32 t; .reg .b64 db; setp.ne.b32 p, %38, 0; add.u32 t, %36, %37; mov.b64 db, {t, %40};\n"
   "wgmma.mma_async.sync.aligned.m64n64k16.f32.bf16.bf16 {%0,%1,%2,%3,%4,%5,%6,%7,%8,%9,%10,%11,%12,%13,%14,%15,%16,%17,%18,%19,%20,%21,%22,%23,%24,%25,%26,%27,%28,%29,%30,%31}, {%32,%33,%34,%35}, db, p, %41, 1, %39;}"
   : "+f"(d[0]),"+f"(d[1]),"+f"(d[2]),"+f"(d[3]),"+f"(d[4]),"+f"(d[5]),"+f"(d[6]),"+f"(d[7]),"+f"(d[8]),"+f"(d[9]),"+f"(d[10]),"+f"(d[11]),"+f"(d[12]),"+f"(d[13]),"+f"(d[14]),"+f"(d[15]),"+f"(d[16]),"+f"(d[17]),"+f"(d[18]),"+f"(d[19]),"+f"(d[20]),"+f"(d[21]),"+f"(d[22]),"+f"(d[23]),"+f"(d[24]),"+f"(d[25]),"+f"(d[26]),"+f"(d[27]),"+f"(d[28]),"+f"(d[29]),"+f"(d[30]),"+f"(d[31])
   : "r"(a0),"r"(a1),"r"(a2),"r"(a3),"r"(bl),"r"(bo >> 4),"r"(scale_d),"n"(TB),"n"(BH),"n"(SA));
}
template<int TA,int TB,uint32_t AH,uint32_t BH> __device__ __forceinline__ void wgmma_n96_ss(float (&d)[48], uint32_t al, uint32_t ao, uint32_t bl, uint32_t bo, int scale_d){
  asm volatile("{.reg .pred p; .reg .b32 t, v; .reg .b64 da, db; setp.ne.b32 p, %52, 0; add.u32 t, %48, %49; mov.b64 da, {t, %55}; add.u32 v, %50, %51; mov.b64 db, {v, %56};\n"
   "wgmma.mma_async.sync.aligned.m64n96k16.f32.bf16.bf16 {%0,%1,%2,%3,%4,%5,%6,%7,%8,%9,%10,%11,%12,%13,%14,%15,%16,%17,%18,%19,%20,%21,%22,%23,%24,%25,%26,%27,%28,%29,%30,%31,%32,%33,%34,%35,%36,%37,%38,%39,%40,%41,%42,%43,%44,%45,%46,%47}, da, db, p, 1, 1, %53, %54;}"
   : "+f"(d[0]),"+f"(d[1]),"+f"(d[2]),"+f"(d[3]),"+f"(d[4]),"+f"(d[5]),"+f"(d[6]),"+f"(d[7]),"+f"(d[8]),"+f"(d[9]),"+f"(d[10]),"+f"(d[11]),"+f"(d[12]),"+f"(d[13]),"+f"(d[14]),"+f"(d[15]),"+f"(d[16]),"+f"(d[17]),"+f"(d[18]),"+f"(d[19]),"+f"(d[20]),"+f"(d[21]),"+f"(d[22]),"+f"(d[23]),"+f"(d[24]),"+f"(d[25]),"+f"(d[26]),"+f"(d[27]),"+f"(d[28]),"+f"(d[29]),"+f"(d[30]),"+f"(d[31]),"+f"(d[32]),"+f"(d[33]),"+f"(d[34]),"+f"(d[35]),"+f"(d[36]),"+f"(d[37]),"+f"(d[38]),"+f"(d[39]),"+f"(d[40]),"+f"(d[41]),"+f"(d[42]),"+f"(d[43]),"+f"(d[44]),"+f"(d[45]),"+f"(d[46]),"+f"(d[47])
   : "r"(al),"r"(ao >> 4),"r"(bl),"r"(bo >> 4),"r"(scale_d),"n"(TA),"n"(TB),"n"(AH),"n"(BH));
}
template<int TA,int TB,uint32_t AH,uint32_t BH> __device__ __forceinline__ void wgmma_n128_ss(float (&d)[64], uint32_t al, uint32_t ao, uint32_t bl, uint32_t bo, int scale_d){
  asm volatile("{.reg .pred p; .reg .b32 t, v; .reg .b64 da, db; setp.ne.b32 p, %68, 0; add.u32 t, %64, %65; mov.b64 da, {t, %71}; add.u32 v, %66, %67; mov.b64 db, {v, %72};\n"
   "wgmma.mma_async.sync.aligned.m64n128k16.f32.bf16.bf16 {%0,%1,%2,%3,%4,%5,%6,%7,%8,%9,%10,%11,%12,%13,%14,%15,%16,%17,%18,%19,%20,%21,%22,%23,%24,%25,%26,%27,%28,%29,%30,%31,%32,%33,%34,%35,%36,%37,%38,%39,%40,%41,%42,%43,%44,%45,%46,%47,%48,%49,%50,%51,%52,%53,%54,%55,%56,%57,%58,%59,%60,%61,%62,%63}, da, db, p, 1, 1, %69, %70;}"
   : "+f"(d[0]),"+f"(d[1]),"+f"(d[2]),"+f"(d[3]),"+f"(d[4]),"+f"(d[5]),"+f"(d[6]),"+f"(d[7]),"+f"(d[8]),"+f"(d[9]),"+f"(d[10]),"+f"(d[11]),"+f"(d[12]),"+f"(d[13]),"+f"(d[14]),"+f"(d[15]),"+f"(d[16]),"+f"(d[17]),"+f"(d[18]),"+f"(d[19]),"+f"(d[20]),"+f"(d[21]),"+f"(d[22]),"+f"(d[23]),"+f"(d[24]),"+f"(d[25]),"+f"(d[26]),"+f"(d[27]),"+f"(d[28]),"+f"(d[29]),"+f"(d[30]),"+f"(d[31]),"+f"(d[32]),"+f"(d[33]),"+f"(d[34]),"+f"(d[35]),"+f"(d[36]),"+f"(d[37]),"+f"(d[38]),"+f"(d[39]),"+f"(d[40]),"+f"(d[41]),"+f"(d[42]),"+f"(d[43]),"+f"(d[44]),"+f"(d[45]),"+f"(d[46]),"+f"(d[47]),"+f"(d[48]),"+f"(d[49]),"+f"(d[50]),"+f"(d[51]),"+f"(d[52]),"+f"(d[53]),"+f"(d[54]),"+f"(d[55]),"+f"(d[56]),"+f"(d[57]),"+f"(d[58]),"+f"(d[59]),"+f"(d[60]),"+f"(d[61]),"+f"(d[62]),"+f"(d[63])
   : "r"(al),"r"(ao >> 4),"r"(bl),"r"(bo >> 4),"r"(scale_d),"n"(TA),"n"(TB),"n"(AH),"n"(BH));
}

__global__ void __cluster_dims__(2, 1, 1) __launch_bounds__(384, 1)
fused_kernel(const __nv_bfloat16* __restrict__ lam_re, const __nv_bfloat16* __restrict__ lam_im, const __nv_bfloat16* __restrict__ log_dt,
             const __nv_bfloat16* __restrict__ dskip, const __nv_bfloat16* __restrict__ b1, const __nv_bfloat16* __restrict__ b2,
             const __nv_bfloat16* __restrict__ gate_w, float* __restrict__ out, const __grid_constant__ Maps maps) {
  extern __shared__ __align__(1024) unsigned char smem_raw[];
  const uint32_t sb = (uint32_t)__cvta_generic_to_shared(smem_raw);
  const int b = blockIdx.x;
  const int rank = b & 1, cl = b >> 1;
  const int sp = (cl & 1) | ((cl >> 2) & 2), m = ((cl >> 1) & 3) | ((cl >> 4) << 2);
  const int s = sp * 2 + rank;
  const int xrot = 9 - 2 * sp;
  if (threadIdx.x == 0) {
    mbar_init(sb + OFF_XFULL, 1);
    mbar_expect_tx(sb + OFF_XFULL, 16384);
    tma5d(sb + OFF_X + (xrot & 7) * 16384, &maps.x, 0, 2 * m, sb + OFF_XFULL);
    tma5d(sb + OFF_X + (xrot & 7) * 16384 + 8192, &maps.x, 0, 2 * m + 1, sb + OFF_XFULL);
  }
  if (threadIdx.x == 128) {
    mbar_init(sb + OFF_FULL, 1);
    mbar_expect_tx(sb + OFF_FULL, 16384);
    tma2d(sb + OFF_RING, &maps.bre, 0, s * 64, sb + OFF_FULL);
    tma2d(sb + OFF_RING + 8192, &maps.bim, 0, s * 64, sb + OFF_FULL);
  }
  const int warp = __shfl_sync(0xffffffffu, (int)(threadIdx.x >> 5), 0);
  const int lane0 = threadIdx.x & 31;

  if (elect_one()) {
    if (warp > 8) {
      map_prefetch(&maps.x + (warp - 9));
      mbar_init(sb + OFF_GBAR + 8 * (warp - 9), warp < 11 ? 64 : 96);
    }
    const uint32_t c = warp < 8 ? 1 : warp < 11 ? 8 : 4, bar = sb + OFF_XFULL + 16 * warp;
    if ((warp & 11) != 0) mbar_init(bar, c);
    mbar_init(bar + 8, c);
    asm volatile("fence.mbarrier_init.release.cluster;" ::: "memory");
  }
  __syncwarp();
  asm volatile("barrier.cluster.arrive.relaxed.aligned;" ::: "memory");

  if (warp < 8) {
    const int lane = __shfl_sync(0xffffffffu, lane0, lane0);
    const int wg = warp >> 2, w = warp & 3, q = lane & 3, gr = lane >> 2;
    uint32_t bv[28];
#pragma unroll
    for (int j = 0; j < 28; j++) bv[j] = __ldg(reinterpret_cast<const uint32_t*>(b1 + s * 224 + j * 8) + q);
    asm volatile("setmaxnreg.inc.sync.aligned.u32 224;");
    cluster_wait();
    auto release = [&](int slot) { if (lane == 0) mbar_arrive(sb + OFF_EMPTY + 8 * slot); };
    const uint32_t xw = sb + OFF_X + wg * 8192, fullb = sb + OFF_FULL;
    const uint32_t dxw = (xw & 0x3FFFF) >> 4, dring = ((sb + OFF_RING) & 0x3FFFF) >> 4;

    float ure[32], uim[32], aa[48], ab[64];
    cplx lam[2], coef[2], l16[2], l32[2], lq[2], pre[2], e[2];
    uint32_t sh16, mhi, ck = 0;

    auto bias = [&](int c) {
#pragma unroll
      for (int j = c * 7; j < c * 7 + 7; j++) {
        pin(bv[j]);
        float* d = j < 12 ? aa + 4 * j : ab + 4 * (j - 12);
        d[0] = d[2] = __uint_as_float(bv[j] << sh16); d[1] = d[3] = __uint_as_float(bv[j] & mhi);
        pin(d[0]); pin(d[1]); pin(d[2]); pin(d[3]);
      }
    };
#pragma unroll
    for (int kb = 0; kb < 8; kb++) {
      const int slot = kb % NSLOT;
      mbar_wait(sb + OFF_XFULL + 8 * kb, 0);
      if (kb == 0) mbar_wait(fullb, 0);
      if (kb == 2) { sh16 = late16(sb + OFF_XFULL); mhi = 0xffffffffu << sh16; }
      if (kb == 4) {
        mbar_wait(sb + OFF_LBAR, 0);
#pragma unroll
        for (int h = 0; h < 2; h++) {
          const uint4 v = lds_u4(sb + OFF_LC + (w * 16 + gr + 8 * h) * 16);
          lam[h] = cplx{__uint_as_float(v.x), __uint_as_float(v.y)};
          coef[h] = cplx{__uint_as_float(v.z), __uint_as_float(v.w)};
        }
      }
      wg_fence();
      const uint32_t dxa = dxw + ((kb + xrot) & 7) * 1024;
#pragma unroll
      for (int kk = 0; kk < 4; kk++) {
        wgmma_n64_ss<0, 0, DH128, DH128>(ure, dring, slot * 16384 + kk * 32, dxa, kk * 32, (kb | kk) != 0);
        wgmma_n64_ss<0, 0, DH128, DH128>(uim, dring, slot * 16384 + 8192 + kk * 32, dxa, kk * 32, (kb | kk) != 0);
      }
      wg_commit();
      if (kb > 0) { wg_wait<1>(); release((kb - 1) % NSLOT); }
      if (kb >= 2 && kb < 5) bias(kb - 2);
      if (kb == 6) {
#pragma unroll
        for (int h = 0; h < 2; h++) {
          pin(lam[h].re); pin(lam[h].im);
          cplx t = cmul(lam[h], lam[h]); t = cmul(t, t); t = cmul(t, t);
          l16[h] = cmul(t, t);
          pin(l16[h].re); pin(l16[h].im);
        }
      }
      if (kb == 7) {
#pragma unroll
        for (int h = 0; h < 2; h++) {
          pin(l16[h].re); pin(l16[h].im);
          l32[h] = cmul(l16[h], l16[h]);
          const cplx a = (q & 1) ? l16[h] : cplx{1.f, 0.f}, c = (q & 2) ? l32[h] : cplx{1.f, 0.f};
          lq[h] = cmul(cmul(a, c), coef[h]);
          pin(lq[h].re); pin(lq[h].im);
        }
      }
    }
    auto scale_u = [&](int i0) {
#pragma unroll
      for (int i = i0; i < i0 + 8; i++) {
        pin(ure[i]); pin(uim[i]);
        const cplx v = cmul(coef[(i >> 1) & 1], cplx{ure[i], uim[i]});
        ure[i] = v.re; uim[i] = v.im;
        pin(ure[i]); pin(uim[i]);
      }
    };
#pragma unroll
    for (int kb = 0; kb < 8; kb++) {
      const int u = 8 + kb, slot = u % NSLOT;
      mbar_wait(fullb + 8 * slot, full_par(u));
      wg_fence();
      const uint32_t dxa = dxw + ((kb + xrot) & 7) * 1024;
#pragma unroll
      for (int kk = 0; kk < 4; kk++)
        wgmma_n96_ss<0, 1, DH128, DH64>(aa, dxa, kk * 32, dring, slot * 16384 + kk * 1024 + lbo(4096), 1);
      wg_commit();
      if (kb == 0) bias(3);
      if (kb != 4) { wg_wait<1>(); release((u - 1) % NSLOT); }
      if (kb == 0) {
        reg_fence(ure); reg_fence(uim);
#pragma unroll
        for (int h = 0; h < 2; h++) e[h] = cplx{ure[2 * h], uim[2 * h]};
      }
      if (kb == 0 || kb == 2 || kb == 3) {
        const int t0 = kb ? 5 * kb - 4 : 1;
#pragma unroll
        for (int t = t0; t < t0 + 5; t++) {
#pragma unroll
          for (int h = 0; h < 2; h++) { const int i = 4 * (t >> 1) + 2 * h + (t & 1); e[h] = cfma(lam[h], e[h], cplx{ure[i], uim[i]}); }
        }
#pragma unroll
        for (int h = 0; h < 2; h++) { pin(e[h].re); pin(e[h].im); }
      }
      if (kb == 4) {
        scale_u(0);
        sched_fence(ck);
#pragma unroll
        for (int h = 0; h < 2; h++) {
          cplx y = {__shfl_up_sync(0xffffffffu, e[h].re, 1, 4), __shfl_up_sync(0xffffffffu, e[h].im, 1, 4)};
          if (q >= 1) e[h] = cfma(l16[h], y, e[h]);
          y = cplx{__shfl_up_sync(0xffffffffu, e[h].re, 2, 4), __shfl_up_sync(0xffffffffu, e[h].im, 2, 4)};
          if (q >= 2) e[h] = cfma(l32[h], y, e[h]);
        }
        if (q == 3) {
#pragma unroll
          for (int h = 0; h < 2; h++) sts_f2(sb + OFF_CARRY + wg * 512 + (w * 16 + gr + 8 * h) * 8, e[h].re, e[h].im);
          mbar_arrive(sb + OFF_GBAR);
        }
#pragma unroll
        for (int h = 0; h < 2; h++) e[h] = cplx{__shfl_up_sync(0xffffffffu, e[h].re, 1, 4), __shfl_up_sync(0xffffffffu, e[h].im, 1, 4)};
        wg_wait<1>(); release((u - 1) % NSLOT);
      }
      if (kb == 5) {
#pragma unroll
        for (int h = 0; h < 2; h++) {
          pre[h] = (q >= 1) ? cmul(coef[h], e[h]) : cplx{0.f, 0.f};
          pin(pre[h].re); pin(pre[h].im);
        }
      }
      if (kb > 5) scale_u((kb - 5) * 8);
    }
    uint32_t H[56], hf[32];
    cplx hst[2];
    const uint32_t hst_addr = xw + (w * 16 + (lane & 15)) * 128 + (((lane >> 4) ^ (lane & 7)) << 4);
    const uint32_t him = (2 - rank) * 16384;
    uint32_t peer;
    asm volatile("mapa.shared::cluster.u32 %0, %1, %2;" : "=r"(peer) : "r"(sb), "r"(rank ^ 1));
    auto credit = [&]() { if (lane == 0) mbar_arrive_cl(peer + OFF_KBAR + wg * 8); };
    uint32_t g2[8];
#pragma unroll
    for (int kb = 0; kb < 8; kb++) {
      const int u = 16 + kb, slot = u % NSLOT;
      mbar_wait(fullb + 8 * slot, full_par(u));
      wg_fence();
#pragma unroll
      for (int kk = 0; kk < 4; kk++)
        wgmma_n128_ss<0, 1, DH128, DH128>(ab, dxw, kb * 16384 + kk * 32, dring, slot * 16384 + kk * 2048 + lbo(8192), 1);
      wg_commit();
      if (kb == 0) scale_u(24);
      if (kb == 4) {
        mbar_wait(sb + OFF_CBAR, 0);
#pragma unroll
        for (int h = 0; h < 2; h++) {
          const float2 c = lds_f2(sb + OFF_CARRY + wg * 512 + (w * 16 + gr + 8 * h) * 8);
          hst[h] = cfma(lq[h], cplx{c.x, c.y}, pre[h]);
        }
#pragma unroll
        for (int i = 0; i < 2; i++) {
          const uint4 v = lds_u4(sb + OFF_GT + wg * 128 + q * 32 + i * 16);
          g2[4 * i] = v.x; g2[4 * i + 1] = v.y; g2[4 * i + 2] = v.z; g2[4 * i + 3] = v.w;
        }
      }
      wg_wait<1>(); release((u - 1) % NSLOT);
      if (kb) sched_fence(ck);
      if (kb < 4) {
#pragma unroll
        for (int i = kb * 6; i < kb * 6 + 6; i++) {
          pin(aa[2 * i]); pin(aa[2 * i + 1]);
          H[i] = gelu2_pair(aa[2 * i], aa[2 * i + 1]);
          pin(H[i]);
        }
      } else {
        const int j0 = (kb - 4) * 2;
        uint32_t rr[4], ri[4];
#pragma unroll
        for (int jj = 0; jj < 2; jj++) {
          const int j = j0 + jj;
#pragma unroll
          for (int h = 0; h < 2; h++) {
            const int i = 4 * j + 2 * h;
            const cplx h0 = cfma(lam[h], hst[h], cplx{ure[i], uim[i]});
            hst[h] = cfma(lam[h], h0, cplx{ure[i + 1], uim[i + 1]});
            rr[jj * 2 + h] = bf2_mul(pack_bf16(h0.re, hst[h].re), g2[j]);
            ri[jj * 2 + h] = bf2_mul(pack_bf16(h0.im, hst[h].im), g2[j]);
          }
        }
        const uint32_t a = hst_addr ^ (j0 << 4);
        asm volatile("stmatrix.sync.aligned.m8n8.x4.shared.b16 [%0], {%1,%2,%3,%4};" ::"r"(a), "r"(rr[0]), "r"(rr[1]), "r"(rr[2]), "r"(rr[3]) : "memory");
        asm volatile("stmatrix.sync.aligned.m8n8.x4.shared.b16 [%0], {%1,%2,%3,%4};" ::"r"(a + him), "r"(ri[0]), "r"(ri[1]), "r"(ri[2]), "r"(ri[3]) : "memory");
      }
    }

    uint4* const psend = g_part + (size_t)(m * 8 + rank) * 3072 + warp * 128 + lane;
    const uint4* const precv = g_part + (size_t)(m * 8 + s) * 3072 + warp * 128 + lane;
    const uint32_t pbuf = OFF_X + warp * 2048 + lane * 16;
    const uint32_t dx0 = ((sb + OFF_X) & 0x3FFFF) >> 4;
    float o[32], fin[32], fs[2];
    uint32_t r0[16], pt[16], sum[16], tag;
    auto recv_issue = [&](uint32_t (&r)[16], int k) {
#pragma unroll
      for (int i = 0; i < 4; i++) ld_b128(precv + k * 1024 + i * 32, r[4 * i], r[4 * i + 1], r[4 * i + 2], r[4 * i + 3]);
    };
    auto stale = [&](uint32_t (&r)[16]) {
      uint32_t r_;
#pragma unroll
      for (int i = 0; i < 16; i += 4) asm("lop3.b32 %0, %0, %1, 1, 0x78;" : "+r"(r[i]) : "r"(tag));
      asm volatile("{.reg .pred p; .reg .b32 t; lop3.b32 t, %1, %2, %3, 0xfe; lop3.b32 t, t, %4, 1, 0xa8; setp.ne.u32 p, t, 0; vote.sync.any.pred p, p, 0xffffffff; selp.u32 %0, 1, 0, p;}"
                   : "=r"(r_) : "r"(r[0]), "r"(r[4]), "r"(r[8]), "r"(r[12]));
      return r_ != 0;
    };
    auto recv_check = [&](uint32_t (&r)[16], int k) {
      if (__builtin_expect(stale(r), 0)) {
        int tries = 0;
#pragma unroll 1
        do { recv_issue(r, k); } while (stale(r) && ++tries < 200000);
      }
    };
    auto gelu_b = [&](int i0, int i1) {
#pragma unroll
      for (int i = i0; i < i1; i++) {
        pin(ab[2 * i]); pin(ab[2 * i + 1]);
        H[24 + i] = gelu2_pair(ab[2 * i], ab[2 * i + 1]);
        pin(H[24 + i]);
      }
    };
    auto mma = [&](float (&d)[32], int p, int k0, int k1, int acc) {
      const uint32_t wo = stage_off(p);
      wg_fence();
#pragma unroll
      for (int k = k0; k < k1; k++) {
        if (k >= 6 && k < 14) {
          const int kk = k - 6;
          if (kk < 4) wgmma_n64_rs<0, DH128, 1>(d, hf[4 * kk], hf[4 * kk + 1], hf[4 * kk + 2], hf[4 * kk + 3], dx0, wo + 14336 + kk * 32, 1);
          else wgmma_n64_rs<0, DH128, -1>(d, hf[4 * kk], hf[4 * kk + 1], hf[4 * kk + 2], hf[4 * kk + 3], dx0, wo + 22528 + (kk - 4) * 32, 1);
        } else {
          const int kk = k < 6 ? k : k - 8;
          wgmma_n64_rs<1, DH128>(d, H[4 * kk], H[4 * kk + 1], H[4 * kk + 2], H[4 * kk + 3], dx0, wo + (kk / 7) * 30720 + (kk % 7) * 2048, k != 0 || acc);
        }
      }
      wg_commit();
    };
    auto recv_peer = [&](int k) {
      mbar_wait(sb + OFF_RBAR + wg * 8, k & 1);
#pragma unroll
      for (int i = 0; i < 4; i++) { const uint4 v = lds_u4(sb + pbuf + i * 512); pt[4 * i] = v.x; pt[4 * i + 1] = v.y; pt[4 * i + 2] = v.z; pt[4 * i + 3] = v.w; }
    };
#pragma unroll
    for (int p = 0; p < 8; p++) {
      if (p == 0) {
        mbar_wait(fullb, full_par(24));
        mma(o, 0, 0, 4, 0);
        bar_sync(1 + wg, 128);
        {
          const uint32_t ha = xw + ((lane >> 4) * 8 + (lane & 7)) * 128 + (((2 * w + ((lane >> 3) & 1)) ^ (lane & 7)) << 4);
#pragma unroll
          for (int kk = 0; kk < 8; kk++)
            asm volatile("ldmatrix.sync.aligned.m8n8.x4.trans.shared.b16 {%0,%1,%2,%3}, [%4];" : "=r"(hf[4 * kk]), "=r"(hf[4 * kk + 1]), "=r"(hf[4 * kk + 2]), "=r"(hf[4 * kk + 3])
                         : "r"(ha + (kk >> 2) * him + (kk & 3) * 2048) : "memory");
        }
        mbar_wait(fullb + 8, full_par(25));
        wg_wait<1>(); release(5);
        gelu_b(0, 6);
        mma(o, 0, 4, 8, 0);
        gelu_b(6, 12);
        mma(o, 0, 8, 12, 0);
        credit();
        gelu_b(12, 18);
        mbar_wait(fullb + 16, full_par(26));
        mma(o, 0, 12, 15, 0);
        gelu_b(18, 24);
        mma(o, 0, 15, 18, 0);
        gelu_b(24, 32);
        if (wg == 1) bar_sync(4, 256);
        mma(o, 0, 18, 22, 0);
      } else {
        bar_sync(3 + wg, 256);
        if (p < 7) mma(o, p, 0, 22, 0); else mma(fin, p, 0, 22, 1);
      }
      if (p < 7 || wg == 0) bar_arrive(4 - wg, 256);
      if (p < 7) mbar_wait(sb + OFF_XFULL + 8 * (p + 1), 1);
      if ((p & 1) == 0) {
        if (w == 0 && lane == 0) mbar_expect_tx(sb + OFF_RBAR + wg * 8, 8192);
        if (p == 6) {
          mbar_wait(sb + OFF_EMPTY + 32, 0);
          tag = lds_u(sb + OFF_EPOCH);
          recv_check(sum, 0); recv_check(r0, 1);
#pragma unroll
          for (int i = 0; i < 16; i++) sum[i] = bf2_add(sum[i], r0[i]);
        }
        mbar_wait(sb + OFF_KBAR + wg * 8, (p >> 1) & 1);
      } else {
        if (p == 1 || p == 7) tag = lds_u(sb + OFF_EPOCH);
        recv_peer(p >> 1);
        if (p == 7) {
          recv_check(r0, 2);
#pragma unroll
          for (int i = 0; i < 16; i++) { sum[i] = bf2_add(sum[i], bf2_add(r0[i], pt[i])); pin(sum[i]); }
          sched_fence(ck);
        }
      }
      if (p == 4) {
        mbar_wait(sb + OFF_LBAR, 1);
#pragma unroll
        for (int j = 0; j < 8; j++) {
          const uint4 v = lds_u4(sb + pbuf + 16384 + (j >> 2) * 16384 + (j & 3) * 512);
          fin[4 * j] = __uint_as_float(v.x); fin[4 * j + 1] = __uint_as_float(v.y); fin[4 * j + 2] = __uint_as_float(v.z); fin[4 * j + 3] = __uint_as_float(v.w);
        }
        recv_issue(sum, 0);
      }
      wg_wait<0>();
      if (p < 5) release(p);
      if (p < 7) reg_fence(o); else reg_fence(fin);
      if ((p & 1) == 0) {
        if (p == 6) recv_issue(r0, 2);
#pragma unroll
        for (int i = 0; i < 4; i++)
          asm volatile("st.async.shared::cluster.mbarrier::complete_tx::bytes.v4.b32 [%0], {%1,%2,%3,%4}, [%5];" ::"r"(peer + pbuf + i * 512),
                       "r"(pack_bf16(o[8 * i], o[8 * i + 1])), "r"(pack_bf16(o[8 * i + 2], o[8 * i + 3])), "r"(pack_bf16(o[8 * i + 4], o[8 * i + 5])),
                       "r"(pack_bf16(o[8 * i + 6], o[8 * i + 7])), "r"(peer + OFF_RBAR + wg * 8) : "memory");
      } else if (p < 7) {
        const int k = p >> 1;
#pragma unroll
        for (int i = 0; i < 4; i++) {
#pragma unroll
          for (int c = 4 * i; c < 4 * i + 4; c++) pt[c] = bf2_add(pt[c], pack_bf16(o[2 * c], o[2 * c + 1]));
          asm("lop3.b32 %0, %0, 1, %1, 0xb8;" : "+r"(pt[4 * i]) : "r"(tag));
          st_b128(psend + (((sp + 1 + k) & 3) * 6 + k) * 1024 + i * 32, pt[4 * i], pt[4 * i + 1], pt[4 * i + 2], pt[4 * i + 3]);
        }
        __syncwarp();
        credit();
        if (p == 5) recv_issue(r0, 1);
      }
      if (p == 2) {
#pragma unroll
        for (int h = 0; h < 2; h++) { fs[h] = __fdividef(2.f, 4.f + bf_lo(lds_h(sb + OFF_GS + (wg * 64 + w * 16 + gr + 8 * h) * 2))); pin(fs[h]); }
      }
    }
    {
      const uint32_t tb = sb + OFF_X + stage_off(0) + warp * 4096;
      const uint32_t ta = tb + gr * 256 + ((gr & 3) << 5) + q * 8;
      const uint32_t la = tb + (lane >> 3) * 256 + (((lane & 7) << 4) ^ ((lane >> 3) << 5));
      float* op = out + (size_t)(m * 128 + wg * 64 + (lane >> 4) * 16 + w * 4 + ((lane >> 3) & 1)) * DM + s * 64 + (lane & 7) * 4;
#pragma unroll
      for (int qt = 0; qt < 4; qt++) {
        const int h = qt & 1, ch = qt >> 1;
#pragma unroll
        for (int j = 0; j < 4; j++) {
          const int i = ch * 8 + j * 2 + h;
          sts_f2((ta ^ (j << 5)) + h * 2048 + ch * 128, (fin[2 * i] + bf_lo(sum[i])) * fs[h], (fin[2 * i + 1] + bf_hi(sum[i])) * fs[h]);
        }
        __syncwarp();
#pragma unroll
        for (int r = 0; r < 2; r++)
          *reinterpret_cast<uint4*>(op + (r * 32 + h * 2) * DM + ch * 32) = lds_u4(la + (h * 2 + r) * 1024 + ch * 128);
      }
      sts_u(sb + OFF_EPOCH + 4, ck);
      if (warp == 4 && lane == 0) g_epoch[b] = tag;
    }
  } else {
    const int lane = __shfl_sync(0xffffffffu, lane0, lane0);
    asm volatile("setmaxnreg.dec.sync.aligned.u32 56;");
    int wsel = warp;
    asm("" : "+r"(wsel));
    if (wsel > 8) {
      const int t = (warp - 9) * 32 + lane;
      const bool two = warp == 11;
      unsigned par;
      asm volatile("ld.relaxed.gpu.global.u32 %0, [%1];" : "=r"(par) : "l"(g_epoch + b) : "memory");
      const uint4* gwp = reinterpret_cast<const uint4*>(gate_w) + (lane & 7);
      uint4 gw[4];
      cplx l64, l128;
      if (!two) {
        const float pr = bf_ld(lam_re + s * 64 + t), pi = bf_ld(lam_im + s * 64 + t), pd = bf_ld(log_dt + s * 64 + t);
#pragma unroll
        for (int i = 0; i < 4; i++) gw[i] = __ldg(gwp + i * 8);
        cluster_wait();
        l64 = make_lam(pr, pi, pd);
        const float inv = __fdividef(1.f, fmaf(pr, pr, pi * pi));
        const cplx cf = cmul(cplx{l64.re - 1.f, l64.im}, cplx{pr * inv, -pi * inv});
        sts_f4(sb + OFF_LC + t * 16, l64.re, l64.im, cf.re, cf.im);
        mbar_arrive(sb + OFF_LBAR);
#pragma unroll
        for (int i = 0; i < 6; i++) l64 = cmul(l64, l64);
        l128 = cmul(l64, l64);
        pin(l128.re); pin(l128.im);
      } else {
#pragma unroll
        for (int i = 0; i < 4; i++) gw[i] = __ldg(gwp + i * 8);
        l64.re = __ldg(reinterpret_cast<const float*>(dskip + s * 64) + lane);
        l64.im = __ldg(reinterpret_cast<const float*>(b2 + s * 64) + lane);
        l128 = l64;
        cluster_wait();
        if (lane == 0) sts_u(sb + OFF_EPOCH, par + 1);
      }
      par = __shfl_sync(0xffffffffu, (par + 1) & 1, 0);
      {
        const int row = s * 16 + (t >> 3);
        const uint32_t xr0 = sb + OFF_X + row * 128 + (((lane & 7) ^ (row & 7)) << 4), xr1 = (xr0 + 512) ^ 64;
        float z0 = 0.f, y0 = 0.f, z1 = 0.f, y1 = 0.f;
#pragma unroll 1
        for (int k4 = 0; k4 < 8; k4 += 4) {
#pragma unroll
          for (int j = 0; j < 4; j++) {
            const uint4 w = gw[j];
            gw[j] = __ldg(gwp + (j + 4) * 8);
            mbar_wait(sb + OFF_XFULL + 8 * (k4 + j), 0);
            const uint32_t xo = ((k4 + j + xrot) & 7) * 16384;
            const uint4 a = lds_u4(xr0 + xo);
            uint4 d;
            if (two) d = lds_u4(xr1 + xo);
            const uint32_t p[4] = {bf2_mul(a.x, w.x), bf2_mul(a.y, w.y), bf2_mul(a.z, w.z), bf2_mul(a.w, w.w)};
#pragma unroll
            for (int c = 0; c < 4; c++) { z0 += bf_lo(p[c]); y0 += bf_hi(p[c]); }
            if (two) {
              const uint32_t r[4] = {bf2_mul(d.x, w.x), bf2_mul(d.y, w.y), bf2_mul(d.z, w.z), bf2_mul(d.w, w.w)};
#pragma unroll
              for (int c = 0; c < 4; c++) { z1 += bf_lo(r[c]); y1 += bf_hi(r[c]); }
            }
          }
        }
        z0 += y0; z1 += y1;
        float zz = ((lane & 4) ? z1 : z0) + __shfl_xor_sync(0xffffffffu, (lane & 4) ? z0 : z1, 4);
        zz += __shfl_xor_sync(0xffffffffu, zz, 2);
        zz += __shfl_xor_sync(0xffffffffu, zz, 1);
        zz = bf_lo(pack_bf16(zz, 0.f));
        const float rho = 4.f * expf(zz > 40.f ? 40.f : zz);
        if ((lane & (two ? 3 : 7)) == 0)
          asm volatile("st.relaxed.gpu.global.u32 [%0], %1;" ::"l"(g_gate + m * 128 + row + (lane & 4)), "r"((__float_as_uint(rho) & ~1u) | par) : "memory");
      }
      if (!two) {
        uint32_t vr[15], vi[15];
#pragma unroll
        for (int i = 0; i < 15; i++) { vr[i] = par; vi[i] = 0; pin(vr[i]); pin(vi[i]); }
        mbar_wait(sb + OFF_GBAR, 0);
        const float2 e0 = lds_f2(sb + OFF_CARRY + t * 8), e1 = lds_f2(sb + OFF_CARRY + 512 + t * 8);
        float2* eb = g_end + s * 1024 + t;
        {
          const cplx e = cfma(l64, cplx{e0.x, e0.y}, cplx{e1.x, e1.y});
          const unsigned long long v = ((unsigned long long)__float_as_uint(e.im) << 32) | ((__float_as_uint(e.re) & ~1u) | par);
          asm volatile("st.relaxed.gpu.global.b64 [%0], %1;" ::"l"(eb + m * 64), "l"(v) : "memory");
        }
        __nanosleep(400);
        const float2* e15 = eb + (m - 15) * 64;
        int tries = 0;
        bool bad;
#pragma unroll 1
        do {
#pragma unroll
          for (int i = 0; i < 15; i++)
            asm volatile("{.reg .pred p; .reg .b64 v; mov.b64 v, {%0,%1}; setp.ge.s32 p, %3, %4; @p ld.relaxed.gpu.global.b64 v, [%2]; mov.b64 {%0,%1}, v;}"
                         : "+r"(vr[i]), "+r"(vi[i]) : "l"(e15 + i * 64), "r"(m), "r"(15 - i) : "memory");
          uint32_t x = vr[0] ^ par;
#pragma unroll
          for (int i = 1; i < 15; i++) asm("lop3.b32 %0, %0, %1, %2, 0xf6;" : "+r"(x) : "r"(vr[i]), "r"(par));
          bad = __any_sync(0xffffffffu, x & 1);
        } while (bad && ++tries < 200000);
        cplx S = {__uint_as_float(vr[0] ^ par), __uint_as_float(vi[0])};
#pragma unroll
        for (int i = 1; i < 15; i++) S = cfma(l128, S, cplx{__uint_as_float(vr[i] ^ par), __uint_as_float(vi[i])});
        const cplx S1 = cfma(l64, S, cplx{e0.x, e0.y});
        sts_f2(sb + OFF_CARRY + t * 8, S.re, S.im);
        sts_f2(sb + OFF_CARRY + 512 + t * 8, S1.re, S1.im);
        mbar_arrive(sb + OFF_CBAR);
        mbar_wait(sb + OFF_CBAR, 0);
        const int gr = lane >> 2, q = lane & 3;
        float2 db[8];
#pragma unroll
        for (int j = 0; j < 8; j++) db[j] = lds_f2(sb + OFF_DB + j * 32 + q * 8);
        mbar_wait(sb + OFF_XFULL + 16, 1);
        mbar_wait(sb + OFF_EMPTY, 0);
#pragma unroll 1
        for (int cw = warp - 9; cw < 8; cw += 2) {
          const float r0 = 0.5f * bf_lo(lds_h(sb + OFF_GS + (cw * 16 + gr) * 2)), r1 = 0.5f * bf_lo(lds_h(sb + OFF_GS + (cw * 16 + gr) * 2 + 16));
          const uint32_t xa = sb + OFF_X + (1 + rank) * 16384 + (cw * 16 + (lane & 15)) * 128 + (((lane >> 4) ^ (lane & 7)) << 4);
          uint32_t xv[16];
#pragma unroll
          for (int i = 0; i < 4; i++)
            asm volatile("ldmatrix.sync.aligned.m8n8.x4.shared.b16 {%0,%1,%2,%3}, [%4];" : "=r"(xv[4 * i]), "=r"(xv[4 * i + 1]), "=r"(xv[4 * i + 2]), "=r"(xv[4 * i + 3])
                         : "r"(xa ^ (i << 5)) : "memory");
          __syncwarp();
#pragma unroll
          for (int j = 0; j < 8; j++) {
            const uint32_t x0 = bf2_mul(xv[2 * j], __float_as_uint(db[j].x)), x1 = bf2_mul(xv[2 * j + 1], __float_as_uint(db[j].x));
            pin(db[j].y);
            const float bl = bf_lo(__float_as_uint(db[j].y)), bh = bf_hi(__float_as_uint(db[j].y));
            sts_f4(sb + OFF_X + 16384 + (j >> 2) * 16384 + cw * 2048 + (j & 3) * 512 + lane * 16, fmaf(bf_lo(x0), r0, bl), fmaf(bf_hi(x0), r0, bh),
                   fmaf(bf_lo(x1), r1, bl), fmaf(bf_hi(x1), r1, bh));
          }
        }
        mbar_arrive(sb + OFF_LBAR);
      } else {
        mbar_wait(sb + OFF_GBAR, 0);
        sts_u2(sb + OFF_DB + lane * 8, __float_as_uint(l64.re), bf2_add(__float_as_uint(l64.im), __float_as_uint(l64.im)));
        uint32_t g0, g1, g2, g3;
        int tries = 0;
#pragma unroll 1
        do {
          asm volatile("ld.relaxed.gpu.global.v4.u32 {%0,%1,%2,%3}, [%4];" : "=r"(g0), "=r"(g1), "=r"(g2), "=r"(g3) : "l"(g_gate + m * 128 + lane * 4) : "memory");
          g0 ^= par; g1 ^= par; g2 ^= par; g3 ^= par;
        } while (((g0 | g1 | g2 | g3) & 1) && ++tries < 200000);
        const uint32_t p01 = pack_bf16(__uint_as_float(g0), __uint_as_float(g1)), p23 = pack_bf16(__uint_as_float(g2), __uint_as_float(g3));
        sts_u2(sb + OFF_GS + lane * 8, p01, p23);
        const uint32_t gt = sb + OFF_GT + (lane >> 4) * 128 + (lane & 1) * 64 + ((lane >> 1) & 7) * 4;
        sts_u(gt, p01);
        sts_u(gt + 32, p23);
        mbar_arrive(sb + OFF_CBAR);
      }
    } else {
      cluster_wait();
      if (elect_one()) {
        const uint32_t t0 = clock();
#pragma unroll 1
        for (int u = 1; u < 8; u++) {
          while ((uint32_t)clock() - t0 < 200 + (u - 1) * 480) {}
          const uint32_t fb = sb + OFF_XFULL + 8 * u;
          mbar_expect_tx(fb, 32768);
          tma5d_mc(sb + OFF_X + ((u + xrot) & 7) * 16384 + rank * 8192, &maps.x, u * 64, 2 * m + rank, fb);
          const int sl = u < 6 ? u : u - 6;
          if (u >= 6) mbar_wait(sb + OFF_EMPTY + 8 * sl, 0);
          tma2d(sb + OFF_RING + sl * 16384, &maps.bre, u * 64, s * 64, fb);
          tma2d(sb + OFF_RING + sl * 16384 + 8192, &maps.bim, u * 64, s * 64, fb);
          if (u == 2) map_prefetch(&maps.w1b);
        }
        int slot = 2; uint32_t ph = 0;
#pragma unroll 1
        for (int u = 8; u < 24; u++) {
          const uint32_t fb = sb + OFF_FULL + 8 * slot, dst = sb + OFF_RING + slot * 16384;
          mbar_wait(sb + OFF_EMPTY + 8 * slot, ph);
          if (u < 16) {
            mbar_expect_tx(fb, 12288);
            tma3d(dst, &maps.w1b, 0, (u - 8) * 64, s * 7, fb);
            if (u < 12) map_prefetch(&maps.w1a + (u - 8));
          } else {
            mbar_expect_tx(fb, 16384);
            tma2d(dst, &maps.w1a, s * 224 + 96, ((u - xrot) & 7) * 64, fb);
            tma2d(dst + 8192, &maps.w1a, s * 224 + 160, ((u - xrot) & 7) * 64, fb);
          }
          if (++slot == NSLOT) { slot = 0; ph ^= 1; }
        }
#pragma unroll 1
        for (int j = 0; j < 3; j++) {
          const uint32_t fb = sb + OFF_FULL + 8 * j, dst = sb + OFF_X + stage_off(0);
          const int c = ((sp + 1) & 3) * 128 + ((rank ^ 1) << 6);
          mbar_wait(sb + OFF_EMPTY + 8 + 8 * j, 1);
          mbar_expect_tx(fb, j == 1 ? 16384 : 14336);
          if (j == 1) {
            tma2d(dst + 14336, &maps.cre, s * 64, c, fb);
            tma2d(dst + 22528, &maps.cim, s * 64, c, fb);
          } else {
            tma2d(dst + j * 15360, &maps.w2, c, s * 224 + j * 56, fb);
          }
        }
#pragma unroll 1
        for (int p = 1; p < 8; p++) {
          const int c = ((sp + 1 + (p >> 1)) & 3) * 128 + (((rank ^ p ^ 1) & 1) << 6);
          const uint32_t fb = sb + OFF_XFULL + 8 * p, dst = sb + OFF_X + stage_off(p);
          if (p == 2 || p > 3) mbar_wait(sb + OFF_EMPTY + (p == 2 ? 40 : (p - 4) * 8), p == 2);
          mbar_expect_tx(fb, 45056);
          tma2d(dst, &maps.w2, c, s * 224, fb);
          tma2d(dst + 14336, &maps.cre, s * 64, c, fb);
          tma2d(dst + 22528, &maps.cim, s * 64, c, fb);
          tma2d(dst + 30720, &maps.w2, c, s * 224 + 112, fb);
        }
      }
    }
  }
}

typedef CUresult (*EncFn)(CUtensorMap*, CUtensorMapDataType, cuuint32_t, void*, const cuuint64_t*, const cuuint64_t*, const cuuint32_t*,
                          const cuuint32_t*, CUtensorMapInterleave, CUtensorMapSwizzle, CUtensorMapL2promotion, CUtensorMapFloatOOBfill);

void encode(EncFn f, CUtensorMap* mp, const void* p, int rank, const cuuint64_t* dims, const cuuint64_t* strides, const cuuint32_t* box, CUtensorMapSwizzle sw) {
  cuuint32_t es[5] = {1, 1, 1, 1, 1};
  f(mp, CU_TENSOR_MAP_DATA_TYPE_BFLOAT16, rank, const_cast<void*>(p), dims, strides, box, es, CU_TENSOR_MAP_INTERLEAVE_NONE, sw,
    CU_TENSOR_MAP_L2_PROMOTION_L2_128B, CU_TENSOR_MAP_FLOAT_OOB_FILL_NONE);
}

}

extern "C" void kernel_launch(void* const* d_in, const int* in_sizes, int n_in, void* d_out, int out_size) {
  typedef const __nv_bfloat16* bp;
  bp x = (bp)d_in[0], lre = (bp)d_in[1], lim = (bp)d_in[2], bre = (bp)d_in[3], bim = (bp)d_in[4], cre = (bp)d_in[5], cim = (bp)d_in[6],
     ldt = (bp)d_in[7], dsk = (bp)d_in[8], w1 = (bp)d_in[10], b1 = (bp)d_in[11], w2 = (bp)d_in[12], b2 = (bp)d_in[13], gw = (bp)d_in[14];
  static EncFn enc = nullptr;
  if (!enc) {
    void* f = nullptr;
    cudaDriverEntryPointQueryResult qr;
    cudaGetDriverEntryPoint("cuTensorMapEncodeTiled", &f, cudaEnableDefault, &qr);
    enc = (EncFn)f;
    cudaFuncSetAttribute(fused_kernel, cudaFuncAttributeMaxDynamicSharedMemorySize, SMEM_BYTES);
  }
  Maps maps;
  {
    cuuint64_t d[5] = {DM, 2, 4, 8, SEQ / 64}, st[4] = {DM * 2, 16 * DM * 2, 2 * DM * 2, 64 * DM * 2};
    cuuint32_t bx[5] = {64, 2, 4, 8, 1};
    encode(enc, &maps.x, x, 5, d, st, bx, CU_TENSOR_MAP_SWIZZLE_128B);
  }
  {
    cuuint64_t d[2] = {DM, DM}, st[1] = {DM * 2};
    cuuint32_t bx[2] = {64, 64};
    encode(enc, &maps.bre, bre, 2, d, st, bx, CU_TENSOR_MAP_SWIZZLE_128B);
    encode(enc, &maps.bim, bim, 2, d, st, bx, CU_TENSOR_MAP_SWIZZLE_128B);
    encode(enc, &maps.cre, cre, 2, d, st, bx, CU_TENSOR_MAP_SWIZZLE_128B);
    encode(enc, &maps.cim, cim, 2, d, st, bx, CU_TENSOR_MAP_SWIZZLE_128B);
  }
  {
    cuuint64_t d[2] = {FF, DM}, st[1] = {FF * 2};
    cuuint32_t bx[2] = {64, 64};
    encode(enc, &maps.w1a, w1, 2, d, st, bx, CU_TENSOR_MAP_SWIZZLE_128B);
    cuuint64_t d3[3] = {32, DM, FF / 32}, st3[2] = {FF * 2, 64};
    cuuint32_t bx3[3] = {32, 64, 3};
    encode(enc, &maps.w1b, w1, 3, d3, st3, bx3, CU_TENSOR_MAP_SWIZZLE_64B);
  }
  {
    cuuint64_t d[2] = {DM, FF}, st[1] = {DM * 2};
    cuuint32_t bx[2] = {64, 112};
    encode(enc, &maps.w2, w2, 2, d, st, bx, CU_TENSOR_MAP_SWIZZLE_128B);
  }
  fused_kernel<<<128, 384, SMEM_BYTES>>>(lre, lim, ldt, dsk, b1, b2, gw, (float*)d_out, maps);
}
```

```cpp
#include <cuda_runtime.h>
#include <cuda_bf16.h>
#include <cuda.h>
#include <stdint.h>

namespace {

constexpr int SEQ = 2048, DM = 512, FF = 1792;
constexpr int NSLOT = 6;
constexpr uint32_t OFF_X = 0, OFF_RING = 131072, OFF_MISC = 229376;
constexpr uint32_t OFF_XFULL = OFF_MISC, OFF_FULL = OFF_XFULL + 64, OFF_RBAR = OFF_FULL + 48, OFF_EMPTY = OFF_RBAR + 16, OFF_KBAR = OFF_EMPTY + 48,
                   OFF_GBAR = OFF_KBAR + 16, OFF_LBAR = OFF_GBAR + 8, OFF_CBAR = OFF_LBAR + 8, OFF_EPOCH = OFF_CBAR + 8;
constexpr uint32_t OFF_LC = OFF_MISC + 256;
constexpr uint32_t OFF_GS = OFF_LC;
constexpr uint32_t OFF_GT = OFF_LC + 256;
constexpr uint32_t OFF_DB = OFF_LC + 512;
constexpr uint32_t OFF_CARRY = OFF_LC + 1024;
constexpr uint32_t SMEM_BYTES = OFF_CARRY + 512;
static_assert(SMEM_BYTES <= 232448, "smem");

struct Maps { CUtensorMap x, bb, w1b, w1a, w2, cre, cim; };
__host__ __device__ constexpr uint32_t stage_off(int p) { return 49152 + 45056 * (((p >> 1) & 1) + 2 * (p & 1)); }
__host__ __device__ constexpr uint32_t full_par(int u) { return ((u - 8) / 6 + (u % 6 == 0)) & 1; }

__device__ uint4 g_part[16 * 8 * 3 * 1024];
__device__ float2 g_end[8 * 16 * 64];
__device__ unsigned g_gate[SEQ];
__device__ unsigned g_epoch[128];

__device__ __forceinline__ void mbar_init(uint32_t bar, uint32_t cnt) { asm volatile("mbarrier.init.shared::cta.b64 [%0], %1;" ::"r"(bar), "r"(cnt)); }
__device__ __forceinline__ void mbar_expect_tx(uint32_t bar, uint32_t bytes) { asm volatile("mbarrier.arrive.expect_tx.shared::cta.b64 _, [%0], %1;" ::"r"(bar), "r"(bytes) : "memory"); }
__device__ __forceinline__ void mbar_arrive(uint32_t bar) { asm volatile("mbarrier.arrive.shared::cta.b64 _, [%0];" ::"r"(bar) : "memory"); }
__device__ __forceinline__ void mbar_arrive_cl(uint32_t cbar) { asm volatile("mbarrier.arrive.shared::cluster.b64 _, [%0];" ::"r"(cbar) : "memory"); }
__device__ __forceinline__ void mbar_wait(uint32_t bar, uint32_t parity) {
  asm volatile(
      "{\n.reg .pred p;\n.reg .u32 c;\n"
      "mbarrier.try_wait.parity.shared::cta.b64 p, [%0], %1;\n"
      "@p bra.uni LAB_DONE;\n"
      "mov.u32 c, 0;\n"
      "LAB_WAIT:\n"
      "mbarrier.try_wait.parity.shared::cta.b64 p, [%0], %1;\n"
      "@p bra.uni LAB_DONE;\n"
      "add.u32 c, c, 1;\nsetp.lt.u32 p, c, 200000;\n@p bra.uni LAB_WAIT;\n"
      "LAB_DONE:\n}" ::"r"(bar), "r"(parity) : "memory");
}
__device__ __forceinline__ void tma2d(uint32_t dst, const CUtensorMap* m, int c0, int c1, uint32_t bar) {
  asm volatile("cp.async.bulk.tensor.2d.shared::cluster.global.mbarrier::complete_tx::bytes [%0], [%1, {%3,%4}], [%2];"
               ::"r"(dst), "l"(m), "r"(bar), "r"(c0), "r"(c1) : "memory");
}
__device__ __forceinline__ void tma3d(uint32_t dst, const CUtensorMap* m, int c0, int c1, int c2, uint32_t bar) {
  asm volatile("cp.async.bulk.tensor.3d.shared::cluster.global.mbarrier::complete_tx::bytes [%0], [%1, {%3,%4,%5}], [%2];"
               ::"r"(dst), "l"(m), "r"(bar), "r"(c0), "r"(c1), "r"(c2) : "memory");
}
__device__ __forceinline__ void tma4d(uint32_t dst, const CUtensorMap* m, int c0, int c3, uint32_t bar) {
  asm volatile("cp.async.bulk.tensor.4d.shared::cluster.global.mbarrier::complete_tx::bytes [%0], [%1, {%3,%5,%5,%4}], [%2];"
               ::"r"(dst), "l"(m), "r"(bar), "r"(c0), "r"(c3), "r"(0) : "memory");
}
__device__ __forceinline__ void tma5d(uint32_t dst, const CUtensorMap* m, int c0, int c3, int c4, uint32_t bar) {
  asm volatile("cp.async.bulk.tensor.5d.shared::cluster.global.mbarrier::complete_tx::bytes [%0], [%1, {%3,%6,%6,%4,%5}], [%2];"
               ::"r"(dst), "l"(m), "r"(bar), "r"(c0), "r"(c3), "r"(c4), "r"(0) : "memory");
}
__device__ __forceinline__ void tma5d_mc(uint32_t dst, const CUtensorMap* m, int c0, int c3, int c4, uint32_t bar) {
  asm volatile("cp.async.bulk.tensor.5d.shared::cluster.global.mbarrier::complete_tx::bytes.multicast::cluster [%0], [%1, {%3,%6,%6,%4,%5}], [%2], %7;"
               ::"r"(dst), "l"(m), "r"(bar), "r"(c0), "r"(c3), "r"(c4), "r"(0), "h"((uint16_t)3) : "memory");
}
__device__ __forceinline__ void map_prefetch(const CUtensorMap* m) { asm volatile("prefetch.tensormap [%0];" ::"l"(m) : "memory"); }
__device__ __forceinline__ bool elect_one() {
  uint32_t pred;
  asm volatile("{.reg .pred P; elect.sync _|P, 0xffffffff; selp.u32 %0, 1, 0, P;}" : "=r"(pred));
  return pred != 0;
}
__device__ __forceinline__ void cluster_wait() { asm volatile("barrier.cluster.wait.aligned;" ::: "memory"); }
__device__ __forceinline__ void wg_fence() { asm volatile("wgmma.fence.sync.aligned;" ::: "memory"); }
__device__ __forceinline__ void wg_commit() { asm volatile("wgmma.commit_group.sync.aligned;" ::: "memory"); }
template <int N> __device__ __forceinline__ void wg_wait() { asm volatile("wgmma.wait_group.sync.aligned %0;" ::"n"(N) : "memory"); }
__device__ __forceinline__ void pin(float& a) { asm volatile("" : "+f"(a)::"memory"); }
__device__ __forceinline__ void pin(uint32_t& a) { asm volatile("" : "+r"(a)::"memory"); }
template <int N> __device__ __forceinline__ void reg_fence(float (&d)[N]) {
#pragma unroll
  for (int i = 0; i < N; i++) pin(d[i]);
}
__device__ __forceinline__ void sched_fence(uint32_t& ck) { asm volatile("{.reg .b32 c; mov.u32 c, %%clock; xor.b32 %0, %0, c;}" : "+r"(ck)::"memory"); }
__device__ __forceinline__ void bar_sync(int id, int n) { asm volatile("bar.sync %0, %1;" ::"r"(id), "r"(n) : "memory"); }
__device__ __forceinline__ void bar_arrive(int id, int n) { asm volatile("bar.arrive %0, %1;" ::"r"(id), "r"(n) : "memory"); }
constexpr uint32_t DH128 = (1024 >> 4) | (1u << 30), DH64 = (512 >> 4) | (2u << 30);
__host__ __device__ constexpr uint32_t lbo(uint32_t bytes) { return (bytes >> 4) << 20; }
__device__ __forceinline__ uint32_t pack_bf16(float lo, float hi) { uint32_t r; asm("cvt.rn.bf16x2.f32 %0, %1, %2;" : "=r"(r) : "f"(hi), "f"(lo)); return r; }
__device__ __forceinline__ float bf_lo(uint32_t v) { return __uint_as_float(v << 16); }
__device__ __forceinline__ float bf_hi(uint32_t v) { return __uint_as_float(v & 0xffff0000u); }
__device__ __forceinline__ float bf_ld(const __nv_bfloat16* p) { return __bfloat162float(__ldg(p)); }
__device__ __forceinline__ uint32_t late16(uint32_t bar) {
  uint32_t r;
  asm volatile("{.reg .pred p; mbarrier.test_wait.parity.shared::cta.b64 p, [%1], 0; selp.u32 %0, 16, 0, p;}" : "=r"(r) : "r"(bar) : "memory");
  return r;
}
__device__ __forceinline__ float2 lds_f2(uint32_t a) { float2 v; asm volatile("ld.shared.v2.f32 {%0,%1}, [%2];" : "=f"(v.x), "=f"(v.y) : "r"(a)); return v; }
__device__ __forceinline__ uint32_t lds_h(uint32_t a) { uint32_t v; asm volatile("ld.shared.u16 %0, [%1];" : "=r"(v) : "r"(a)); return v; }
__device__ __forceinline__ uint32_t lds_u(uint32_t a) { uint32_t v; asm volatile("ld.shared.u32 %0, [%1];" : "=r"(v) : "r"(a)); return v; }
__device__ __forceinline__ uint4 lds_u4(uint32_t a) { uint4 v; asm volatile("ld.shared.v4.u32 {%0,%1,%2,%3}, [%4];" : "=r"(v.x), "=r"(v.y), "=r"(v.z), "=r"(v.w) : "r"(a)); return v; }
__device__ __forceinline__ void sts_u(uint32_t a, uint32_t v) { asm volatile("st.shared.u32 [%0], %1;" ::"r"(a), "r"(v) : "memory"); }
__device__ __forceinline__ void sts_u2(uint32_t a, uint32_t x, uint32_t y) { asm volatile("st.shared.v2.u32 [%0], {%1,%2};" ::"r"(a), "r"(x), "r"(y) : "memory"); }
__device__ __forceinline__ void sts_f2(uint32_t a, float x, float y) { asm volatile("st.shared.v2.f32 [%0], {%1,%2};" ::"r"(a), "f"(x), "f"(y) : "memory"); }
__device__ __forceinline__ void sts_f4(uint32_t a, float x, float y, float z, float w) {
  asm volatile("st.shared.v4.f32 [%0], {%1,%2,%3,%4};" ::"r"(a), "f"(x), "f"(y), "f"(z), "f"(w) : "memory");
}
__device__ __forceinline__ void st_b128(uint4* p, uint32_t a, uint32_t b, uint32_t c, uint32_t d) {
  asm volatile("st.relaxed.gpu.global.v4.b32 [%0], {%1,%2,%3,%4};" ::"l"(p), "r"(a), "r"(b), "r"(c), "r"(d) : "memory");
}
__device__ __forceinline__ void ld_b128(const uint4* p, uint32_t& a, uint32_t& b, uint32_t& c, uint32_t& d) {
  asm volatile("{.reg .b64 l, h; .reg .b128 v; ld.relaxed.gpu.global.b128 v, [%4]; mov.b128 {l,h}, v; mov.b64 {%0,%1}, l; mov.b64 {%2,%3}, h;}"
               : "=r"(a), "=r"(b), "=r"(c), "=r"(d) : "l"(p) : "memory");
}
__device__ __forceinline__ uint32_t bf2_mul(uint32_t a, uint32_t b) { uint32_t r; asm("mul.rn.bf16x2 %0, %1, %2;" : "=r"(r) : "r"(a), "r"(b)); return r; }
__device__ __forceinline__ uint32_t bf2_add(uint32_t a, uint32_t b) { uint32_t r; asm("add.rn.bf16x2 %0, %1, %2;" : "=r"(r) : "r"(a), "r"(b)); return r; }
__device__ __forceinline__ uint32_t bf2_fma(uint32_t a, uint32_t b, uint32_t c) { uint32_t r; asm("fma.rn.bf16x2 %0, %1, %2, %3;" : "=r"(r) : "r"(a), "r"(b), "r"(c)); return r; }
__device__ __forceinline__ uint32_t gelu2_pair(float a, float b) {
  const uint32_t v = pack_bf16(a, b);
  uint32_t t;
  asm("tanh.approx.bf16x2 %0, %1;" : "=r"(t) : "r"(bf2_fma(v, bf2_fma(bf2_mul(v, v), 0x3d123d12u, 0xbe4fbe4fu), v)));
  return bf2_fma(v, t, v);
}
struct cplx { float re, im; };
__device__ __forceinline__ cplx cmul(cplx a, cplx b) { return {fmaf(a.re, b.re, -a.im * b.im), fmaf(a.re, b.im, a.im * b.re)}; }
__device__ __forceinline__ cplx cfma(cplx a, cplx b, cplx c) {
  return {fmaf(a.re, b.re, fmaf(-a.im, b.im, c.re)), fmaf(a.re, b.im, fmaf(a.im, b.re, c.im))};
}
__device__ __forceinline__ cplx make_lam(float lre, float lim, float ldt) {
  float dt = __bfloat162float(__float2bfloat16_rn(expf(ldt)));
  float mag = expf(dt * lre), sn, cs;
  sincospif(dt * lim * 0.31830988618379067f, &sn, &cs);
  return {mag * cs, mag * sn};
}

template <int NG>
__device__ __forceinline__ void gate_rows(uint32_t sb, int lane, int xrot, int row0, uint4 (&gw)[4], const uint4* gwp, unsigned* dst, unsigned par) {
  const int row = row0 + (lane >> 3);
  const uint32_t xr0 = sb + OFF_X + row * 128 + (((lane & 7) ^ (row & 7)) << 4), xr1 = (xr0 + 512) ^ 64;
  float z[NG], y[NG];
#pragma unroll
  for (int r = 0; r < NG; r++) z[r] = y[r] = 0.f;
#pragma unroll
  for (int kb = 0; kb < 8; kb++) {
    const uint4 w = gw[kb & 3];
    if (kb < 4) gw[kb] = __ldg(gwp + (kb + 4) * 8);
    mbar_wait(sb + OFF_XFULL + 8 * kb, 0);
#pragma unroll
    for (int r = 0; r < NG; r++) {
      const uint4 a = lds_u4((r ? xr1 : xr0) + ((kb + xrot) & 7) * 16384);
      const uint32_t p[4] = {bf2_mul(a.x, w.x), bf2_mul(a.y, w.y), bf2_mul(a.z, w.z), bf2_mul(a.w, w.w)};
#pragma unroll
      for (int c = 0; c < 4; c++) { z[r] += bf_lo(p[c]); y[r] += bf_hi(p[c]); }
    }
  }
  float zz = z[0] + y[0];
  if (NG == 2) {
    const float z1 = z[NG - 1] + y[NG - 1];
    zz = ((lane & 4) ? z1 : zz) + __shfl_xor_sync(0xffffffffu, (lane & 4) ? zz : z1, 4);
  } else {
    zz += __shfl_xor_sync(0xffffffffu, zz, 4);
  }
  zz += __shfl_xor_sync(0xffffffffu, zz, 2);
  zz += __shfl_xor_sync(0xffffffffu, zz, 1);
  zz = bf_lo(pack_bf16(zz, 0.f));
  const float rho = 4.f * expf(zz > 40.f ? 40.f : zz);
  if ((lane & (NG == 2 ? 3 : 7)) == 0)
    asm volatile("st.relaxed.gpu.global.u32 [%0], %1;" ::"l"(dst + row + (lane & 4)), "r"((__float_as_uint(rho) & ~1u) | par) : "memory");
}

template<int TB,uint32_t BH,int SA=1> __device__ __forceinline__ void wgmma_n64_rs(float (&d)[32], uint32_t a0,uint32_t a1,uint32_t a2,uint32_t a3, uint32_t bl, uint32_t bo, int scale_d){
  asm volatile("{.reg .pred p; .reg .b32 t; .reg .b64 db; setp.ne.b32 p, %38, 0; add.u32 t, %36, %37; mov.b64 db, {t, %40};\n"
   "wgmma.mma_async.sync.aligned.m64n64k16.f32.bf16.bf16 {%0,%1,%2,%3,%4,%5,%6,%7,%8,%9,%10,%11,%12,%13,%14,%15,%16,%17,%18,%19,%20,%21,%22,%23,%24,%25,%26,%27,%28,%29,%30,%31}, {%32,%33,%34,%35}, db, p, %41, 1, %39;}"
   : "+f"(d[0]),"+f"(d[1]),"+f"(d[2]),"+f"(d[3]),"+f"(d[4]),"+f"(d[5]),"+f"(d[6]),"+f"(d[7]),"+f"(d[8]),"+f"(d[9]),"+f"(d[10]),"+f"(d[11]),"+f"(d[12]),"+f"(d[13]),"+f"(d[14]),"+f"(d[15]),"+f"(d[16]),"+f"(d[17]),"+f"(d[18]),"+f"(d[19]),"+f"(d[20]),"+f"(d[21]),"+f"(d[22]),"+f"(d[23]),"+f"(d[24]),"+f"(d[25]),"+f"(d[26]),"+f"(d[27]),"+f"(d[28]),"+f"(d[29]),"+f"(d[30]),"+f"(d[31])
   : "r"(a0),"r"(a1),"r"(a2),"r"(a3),"r"(bl),"r"(bo >> 4),"r"(scale_d),"n"(TB),"n"(BH),"n"(SA));
}
template<int TA,int TB,uint32_t AH,uint32_t BH> __device__ __forceinline__ void wgmma_n96_ss(float (&d)[48], uint32_t al, uint32_t ao, uint32_t bl, uint32_t bo, int scale_d){
  asm volatile("{.reg .pred p; .reg .b32 t, v; .reg .b64 da, db; setp.ne.b32 p, %52, 0; add.u32 t, %48, %49; mov.b64 da, {t, %55}; add.u32 v, %50, %51; mov.b64 db, {v, %56};\n"
   "wgmma.mma_async.sync.aligned.m64n96k16.f32.bf16.bf16 {%0,%1,%2,%3,%4,%5,%6,%7,%8,%9,%10,%11,%12,%13,%14,%15,%16,%17,%18,%19,%20,%21,%22,%23,%24,%25,%26,%27,%28,%29,%30,%31,%32,%33,%34,%35,%36,%37,%38,%39,%40,%41,%42,%43,%44,%45,%46,%47}, da, db, p, 1, 1, %53, %54;}"
   : "+f"(d[0]),"+f"(d[1]),"+f"(d[2]),"+f"(d[3]),"+f"(d[4]),"+f"(d[5]),"+f"(d[6]),"+f"(d[7]),"+f"(d[8]),"+f"(d[9]),"+f"(d[10]),"+f"(d[11]),"+f"(d[12]),"+f"(d[13]),"+f"(d[14]),"+f"(d[15]),"+f"(d[16]),"+f"(d[17]),"+f"(d[18]),"+f"(d[19]),"+f"(d[20]),"+f"(d[21]),"+f"(d[22]),"+f"(d[23]),"+f"(d[24]),"+f"(d[25]),"+f"(d[26]),"+f"(d[27]),"+f"(d[28]),"+f"(d[29]),"+f"(d[30]),"+f"(d[31]),"+f"(d[32]),"+f"(d[33]),"+f"(d[34]),"+f"(d[35]),"+f"(d[36]),"+f"(d[37]),"+f"(d[38]),"+f"(d[39]),"+f"(d[40]),"+f"(d[41]),"+f"(d[42]),"+f"(d[43]),"+f"(d[44]),"+f"(d[45]),"+f"(d[46]),"+f"(d[47])
   : "r"(al),"r"(ao >> 4),"r"(bl),"r"(bo >> 4),"r"(scale_d),"n"(TA),"n"(TB),"n"(AH),"n"(BH));
}
template<int TA,int TB,uint32_t AH,uint32_t BH> __device__ __forceinline__ void wgmma_n128_ss(float (&d)[64], uint32_t al, uint32_t ao, uint32_t bl, uint32_t bo, int scale_d){
  asm volatile("{.reg .pred p; .reg .b32 t, v; .reg .b64 da, db; setp.ne.b32 p, %68, 0; add.u32 t, %64, %65; mov.b64 da, {t, %71}; add.u32 v, %66, %67; mov.b64 db, {v, %72};\n"
   "wgmma.mma_async.sync.aligned.m64n128k16.f32.bf16.bf16 {%0,%1,%2,%3,%4,%5,%6,%7,%8,%9,%10,%11,%12,%13,%14,%15,%16,%17,%18,%19,%20,%21,%22,%23,%24,%25,%26,%27,%28,%29,%30,%31,%32,%33,%34,%35,%36,%37,%38,%39,%40,%41,%42,%43,%44,%45,%46,%47,%48,%49,%50,%51,%52,%53,%54,%55,%56,%57,%58,%59,%60,%61,%62,%63}, da, db, p, 1, 1, %69, %70;}"
   : "+f"(d[0]),"+f"(d[1]),"+f"(d[2]),"+f"(d[3]),"+f"(d[4]),"+f"(d[5]),"+f"(d[6]),"+f"(d[7]),"+f"(d[8]),"+f"(d[9]),"+f"(d[10]),"+f"(d[11]),"+f"(d[12]),"+f"(d[13]),"+f"(d[14]),"+f"(d[15]),"+f"(d[16]),"+f"(d[17]),"+f"(d[18]),"+f"(d[19]),"+f"(d[20]),"+f"(d[21]),"+f"(d[22]),"+f"(d[23]),"+f"(d[24]),"+f"(d[25]),"+f"(d[26]),"+f"(d[27]),"+f"(d[28]),"+f"(d[29]),"+f"(d[30]),"+f"(d[31]),"+f"(d[32]),"+f"(d[33]),"+f"(d[34]),"+f"(d[35]),"+f"(d[36]),"+f"(d[37]),"+f"(d[38]),"+f"(d[39]),"+f"(d[40]),"+f"(d[41]),"+f"(d[42]),"+f"(d[43]),"+f"(d[44]),"+f"(d[45]),"+f"(d[46]),"+f"(d[47]),"+f"(d[48]),"+f"(d[49]),"+f"(d[50]),"+f"(d[51]),"+f"(d[52]),"+f"(d[53]),"+f"(d[54]),"+f"(d[55]),"+f"(d[56]),"+f"(d[57]),"+f"(d[58]),"+f"(d[59]),"+f"(d[60]),"+f"(d[61]),"+f"(d[62]),"+f"(d[63])
   : "r"(al),"r"(ao >> 4),"r"(bl),"r"(bo >> 4),"r"(scale_d),"n"(TA),"n"(TB),"n"(AH),"n"(BH));
}

__global__ void __cluster_dims__(2, 1, 1) __launch_bounds__(384, 1)
fused_kernel(const __nv_bfloat16* __restrict__ lam_re, const __nv_bfloat16* __restrict__ lam_im, const __nv_bfloat16* __restrict__ log_dt,
             const __nv_bfloat16* __restrict__ dskip, const __nv_bfloat16* __restrict__ b1, const __nv_bfloat16* __restrict__ b2,
             const __nv_bfloat16* __restrict__ gate_w, float* __restrict__ out, float sgn, const __grid_constant__ Maps maps) {
  extern __shared__ __align__(1024) unsigned char smem_raw[];
  const uint32_t sb = (uint32_t)__cvta_generic_to_shared(smem_raw);
  const int b = blockIdx.x;
  const int rank = b & 1, cl = b >> 1;
  const int sp = (cl & 1) | ((cl >> 2) & 2), m = ((cl >> 1) & 3) | ((cl >> 4) << 2);
  const int s = sp * 2 + rank;
  const int xrot = 9 - 2 * sp;
  if (threadIdx.x == 0) {
    mbar_init(sb + OFF_XFULL, 1);
    mbar_expect_tx(sb + OFF_XFULL, 16384);
    tma5d(sb + OFF_X + (xrot & 7) * 16384, &maps.x, 0, 0, m, sb + OFF_XFULL);
    tma5d(sb + OFF_X + (xrot & 7) * 16384 + 8192, &maps.x, 0, 8, m, sb + OFF_XFULL);
  }
  if (threadIdx.x == 128) {
    mbar_init(sb + OFF_FULL, 1);
    mbar_expect_tx(sb + OFF_FULL, 16384);
    tma4d(sb + OFF_RING, &maps.bb, 0, s * 8, sb + OFF_FULL);
  }
  const int warp = __shfl_sync(0xffffffffu, (int)(threadIdx.x >> 5), 0);
  const int lane0 = threadIdx.x & 31;

  if (elect_one()) {
    if (warp > 8) {
      map_prefetch(&maps.x + (warp - 9));
      mbar_init(sb + OFF_GBAR + 8 * (warp - 9), warp < 11 ? 64 : 96);
    }
    const uint32_t c = warp < 8 ? 1 : warp < 11 ? 8 : 4, bar = sb + OFF_XFULL + 16 * warp;
    if ((warp & 11) != 0) mbar_init(bar, c);
    mbar_init(bar + 8, c);
    asm volatile("fence.mbarrier_init.release.cluster;" ::: "memory");
  }
  __syncwarp();
  asm volatile("barrier.cluster.arrive.relaxed.aligned;" ::: "memory");

  if (warp < 8) {
    const int lane = __shfl_sync(0xffffffffu, lane0, lane0);
    const int wg = warp >> 2, w = warp & 3, q = lane & 3, gr = lane >> 2;
    uint32_t bv[28];
#pragma unroll
    for (int j = 0; j < 28; j++) bv[j] = __ldg(reinterpret_cast<const uint32_t*>(b1 + s * 224 + j * 8) + q);
    asm volatile("setmaxnreg.inc.sync.aligned.u32 224;");
    cluster_wait();
    auto release = [&](int slot) { if (lane == 0) mbar_arrive(sb + OFF_EMPTY + 8 * slot); };
    const uint32_t xw = sb + OFF_X + wg * 8192, fullb = sb + OFF_FULL;
    const uint32_t dxw = (xw & 0x3FFFF) >> 4, dring = ((sb + OFF_RING) & 0x3FFFF) >> 4;

    float uu[64], aa[48], ab[64];
    cplx lam, coef, l16, l32, l64, lq, pre, e[2];
    uint32_t sh16, mhi, ck = 0;
    const uint32_t dx0 = ((sb + OFF_X) & 0x3FFFF) >> 4;

    auto bias = [&](int c) {
#pragma unroll
      for (int j = c * 7; j < c * 7 + 7; j++) {
        pin(bv[j]);
        float* d = j < 12 ? aa + 4 * j : ab + 4 * (j - 12);
        d[0] = d[2] = __uint_as_float(bv[j] << sh16); d[1] = d[3] = __uint_as_float(bv[j] & mhi);
        pin(d[0]); pin(d[1]); pin(d[2]); pin(d[3]);
      }
    };
#pragma unroll
    for (int kb = 0; kb < 8; kb++) {
      const int slot = kb % NSLOT;
      mbar_wait(sb + OFF_XFULL + 8 * kb, 0);
      if (kb == 0) mbar_wait(fullb, 0);
      if (kb == 2) { sh16 = late16(sb + OFF_XFULL); mhi = 0xffffffffu << sh16; }
      if (kb == 4) {
        mbar_wait(sb + OFF_LBAR, 0);
        const uint4 v = lds_u4(sb + OFF_LC + (warp * 8 + gr) * 16);
        lam = cplx{__uint_as_float(v.x), __uint_as_float(v.y)};
        coef = cplx{__uint_as_float(v.z), __uint_as_float(v.w)};
      }
      wg_fence();
      const uint32_t dxa = dx0 + ((kb + xrot) & 7) * 1024;
#pragma unroll
      for (int kk = 0; kk < 4; kk++)
        wgmma_n128_ss<0, 0, DH128, DH128>(uu, dring + wg * 512, slot * 16384 + kk * 32, dxa, kk * 32, (kb | kk) != 0);
      wg_commit();
      if (kb > 0) { wg_wait<1>(); release((kb - 1) % NSLOT); }
      if (kb >= 2 && kb < 6) bias(kb - 2);
      if (kb == 6) {
        pin(lam.re); pin(lam.im);
        cplx t = cmul(lam, lam); t = cmul(t, t); t = cmul(t, t);
        l16 = cmul(t, t); l32 = cmul(l16, l16); l64 = cmul(l32, l32);
        const cplx a = (q & 1) ? l32 : cplx{1.f, 0.f}, c = (q & 2) ? l64 : cplx{1.f, 0.f};
        lq = cmul(cmul(a, c), coef);
        pin(lq.re); pin(lq.im);
      }
    }
    auto scale_u = [&](int c) {
#pragma unroll
      for (int n = 0; n < 8; n++) {
        const int i = (n >> 2) * 32 + c * 8 + (n & 2) * 2 + (n & 1);
        pin(uu[i]); pin(uu[i + 2]);
        const cplx v = cmul(coef, cplx{uu[i], uu[i + 2]});
        uu[i] = v.re; uu[i + 2] = v.im;
        pin(uu[i]); pin(uu[i + 2]);
      }
    };
#pragma unroll
    for (int kb = 0; kb < 8; kb++) {
      const int u = 8 + kb, slot = u % NSLOT;
      mbar_wait(fullb + 8 * slot, full_par(u));
      wg_fence();
      const uint32_t dxa = dxw + ((kb + xrot) & 7) * 1024;
#pragma unroll
      for (int kk = 0; kk < 4; kk++)
        wgmma_n96_ss<0, 1, DH128, DH64>(aa, dxa, kk * 32, dring, slot * 16384 + kk * 1024 + lbo(4096), 1);
      wg_commit();
      if (kb != 4) { wg_wait<1>(); release((u - 1) % NSLOT); }
      if (kb == 0) {
        reg_fence(uu);
#pragma unroll
        for (int h = 0; h < 2; h++) e[h] = cplx{uu[32 * h], uu[32 * h + 2]};
      }
      if (kb == 0 || kb == 2 || kb == 3) {
        const int t0 = kb ? 5 * kb - 4 : 1;
#pragma unroll
        for (int t = t0; t < t0 + 5; t++) {
#pragma unroll
          for (int h = 0; h < 2; h++) { const int i = 32 * h + 4 * (t >> 1) + (t & 1); e[h] = cfma(lam, e[h], cplx{uu[i], uu[i + 2]}); }
        }
#pragma unroll
        for (int h = 0; h < 2; h++) { pin(e[h].re); pin(e[h].im); }
      }
      if (kb == 4) {
        scale_u(0);
        sched_fence(ck);
        e[1] = cfma(l16, e[0], e[1]);
        cplx y = {__shfl_up_sync(0xffffffffu, e[1].re, 1, 4), __shfl_up_sync(0xffffffffu, e[1].im, 1, 4)};
        if (q >= 1) e[1] = cfma(l32, y, e[1]);
        y = cplx{__shfl_up_sync(0xffffffffu, e[1].re, 2, 4), __shfl_up_sync(0xffffffffu, e[1].im, 2, 4)};
        if (q >= 2) e[1] = cfma(l64, y, e[1]);
        if (q == 3) {
          sts_f2(sb + OFF_CARRY + (warp * 8 + gr) * 8, e[1].re, e[1].im);
          mbar_arrive(sb + OFF_GBAR);
        }
        e[1] = cplx{__shfl_up_sync(0xffffffffu, e[1].re, 1, 4), __shfl_up_sync(0xffffffffu, e[1].im, 1, 4)};
        wg_wait<1>(); release((u - 1) % NSLOT);
      }
      if (kb == 5) {
        pre = (q >= 1) ? cmul(coef, e[1]) : cplx{0.f, 0.f};
        e[0] = cmul(coef, e[0]);
        pin(pre.re); pin(pre.im); pin(e[0].re); pin(e[0].im);
      }
      if (kb > 5) scale_u(kb - 5);
    }
    uint32_t H[56], hf[32];
    cplx hst[2];
    const uint32_t hst_addr = sb + OFF_X + (lane & 8) * 1024 + (warp * 8 + (lane & 7)) * 128 + (((lane >> 4) ^ (lane & 7)) << 4);
    const uint32_t him = (2 - rank) * 16384;
    uint32_t peer;
    asm volatile("mapa.shared::cluster.u32 %0, %1, %2;" : "=r"(peer) : "r"(sb), "r"(rank ^ 1));
    auto credit = [&]() { if (lane == 0) mbar_arrive_cl(peer + OFF_KBAR + wg * 8); };
    uint4 g2;
#pragma unroll
    for (int kb = 0; kb < 8; kb++) {
      const int u = 16 + kb, slot = u % NSLOT;
      mbar_wait(fullb + 8 * slot, full_par(u));
      wg_fence();
#pragma unroll
      for (int kk = 0; kk < 4; kk++)
        wgmma_n128_ss<0, 1, DH128, DH128>(ab, dxw, kb * 16384 + kk * 32, dring, slot * 16384 + kk * 2048 + lbo(8192), 1);
      wg_commit();
      if (kb == 0) scale_u(3);
      if (kb == 4) {
        mbar_wait(sb + OFF_CBAR, 0);
        const float2 c = lds_f2(sb + OFF_CARRY + (warp * 8 + gr) * 8);
        mbar_wait(sb + OFF_EMPTY, 1);
        hst[0] = cfma(lq, cplx{c.x, c.y}, pre);
        hst[1] = cfma(l16, hst[0], e[0]);
      }
      if (kb >= 4) g2 = lds_u4(sb + OFF_GT + (kb - 4) * 64 + q * 16);
      wg_wait<1>(); release((u - 1) % NSLOT);
      if (kb) sched_fence(ck);
      if (kb < 4) {
#pragma unroll
        for (int i = kb * 6; i < kb * 6 + 6; i++) {
          pin(aa[2 * i]); pin(aa[2 * i + 1]);
          H[i] = gelu2_pair(aa[2 * i], aa[2 * i + 1]);
          pin(H[i]);
        }
      } else {
        const int j0 = (kb - 4) * 2;
        uint32_t rr[4], ri[4];
#pragma unroll
        for (int jj = 0; jj < 2; jj++) {
          const int j = j0 + jj;
#pragma unroll
          for (int h = 0; h < 2; h++) {
            const int i = 32 * h + 4 * j;
            const uint32_t g = jj ? (h ? g2.w : g2.z) : (h ? g2.y : g2.x);
            const cplx h0 = cfma(lam, hst[h], cplx{uu[i], uu[i + 2]});
            hst[h] = cfma(lam, h0, cplx{uu[i + 1], uu[i + 3]});
            rr[jj * 2 + h] = bf2_mul(pack_bf16(h0.re, hst[h].re), g);
            ri[jj * 2 + h] = bf2_mul(pack_bf16(h0.im, hst[h].im), g);
          }
        }
        const uint32_t a = hst_addr ^ (j0 << 4);
        asm volatile("stmatrix.sync.aligned.m8n8.x4.shared.b16 [%0], {%1,%2,%3,%4};" ::"r"(a), "r"(rr[0]), "r"(rr[1]), "r"(rr[2]), "r"(rr[3]) : "memory");
        asm volatile("stmatrix.sync.aligned.m8n8.x4.shared.b16 [%0], {%1,%2,%3,%4};" ::"r"(a + him), "r"(ri[0]), "r"(ri[1]), "r"(ri[2]), "r"(ri[3]) : "memory");
        if (kb == 7) { __syncwarp(); if (q == 3) mbar_arrive(sb + OFF_GBAR); }
      }
    }

    uint4* const psend = g_part + (size_t)(m * 8 + rank) * 3072 + warp * 128 + lane;
    const uint4* const precv = g_part + (size_t)(m * 8 + s) * 3072 + warp * 128 + lane;
    const uint32_t pbuf = OFF_X + warp * 2048 + lane * 16;
    float o[32], fin[32], fs[2];
    uint32_t r0[16], pt[16], sum[16], tag;
    auto recv_issue = [&](uint32_t (&r)[16], int k) {
#pragma unroll
      for (int i = 0; i < 4; i++) ld_b128(precv + k * 1024 + i * 32, r[4 * i], r[4 * i + 1], r[4 * i + 2], r[4 * i + 3]);
    };
    auto stale = [&](uint32_t (&r)[16]) {
      uint32_t r_;
#pragma unroll
      for (int i = 0; i < 16; i += 4) asm("lop3.b32 %0, %0, %1, 1, 0x78;" : "+r"(r[i]) : "r"(tag));
      asm volatile("{.reg .pred p; .reg .b32 t; lop3.b32 t, %1, %2, %3, 0xfe; lop3.b32 t, t, %4, 1, 0xa8; setp.ne.u32 p, t, 0; vote.sync.any.pred p, p, 0xffffffff; selp.u32 %0, 1, 0, p;}"
                   : "=r"(r_) : "r"(r[0]), "r"(r[4]), "r"(r[8]), "r"(r[12]));
      return r_ != 0;
    };
    auto recv_check = [&](uint32_t (&r)[16], int k) {
      if (__builtin_expect(stale(r), 0)) {
        int tries = 0;
#pragma unroll 1
        do { recv_issue(r, k); } while (stale(r) && ++tries < 200000);
      }
    };
    auto gelu_b = [&](int i0, int i1) {
#pragma unroll
      for (int i = i0; i < i1; i++) {
        pin(ab[2 * i]); pin(ab[2 * i + 1]);
        H[24 + i] = gelu2_pair(ab[2 * i], ab[2 * i + 1]);
        pin(H[24 + i]);
      }
    };
    auto mma = [&](float (&d)[32], int p, int k0, int k1, int acc) {
      const uint32_t wo = stage_off(p);
      wg_fence();
#pragma unroll
      for (int k = k0; k < k1; k++) {
        if (k >= 6 && k < 14) {
          const int kk = k - 6;
          if (kk < 4) wgmma_n64_rs<0, DH128, 1>(d, hf[4 * kk], hf[4 * kk + 1], hf[4 * kk + 2], hf[4 * kk + 3], dx0, wo + 14336 + kk * 32, 1);
          else wgmma_n64_rs<0, DH128, -1>(d, hf[4 * kk], hf[4 * kk + 1], hf[4 * kk + 2], hf[4 * kk + 3], dx0, wo + 22528 + (kk - 4) * 32, 1);
        } else {
          const int kk = k < 6 ? k : k - 8;
          wgmma_n64_rs<1, DH128>(d, H[4 * kk], H[4 * kk + 1], H[4 * kk + 2], H[4 * kk + 3], dx0, wo + (kk / 7) * 30720 + (kk % 7) * 2048, k != 0 || acc);
        }
      }
      wg_commit();
    };
    auto recv_peer = [&](int k) {
      mbar_wait(sb + OFF_RBAR + wg * 8, k & 1);
#pragma unroll
      for (int i = 0; i < 4; i++) { const uint4 v = lds_u4(sb + pbuf + i * 512); pt[4 * i] = v.x; pt[4 * i + 1] = v.y; pt[4 * i + 2] = v.z; pt[4 * i + 3] = v.w; }
    };
#pragma unroll
    for (int p = 0; p < 8; p++) {
      if (p == 0) {
        mbar_wait(fullb, full_par(24));
        mma(o, 0, 0, 4, 0);
        mbar_wait(sb + OFF_GBAR, 1);
        {
          const uint32_t ha = xw + ((lane >> 4) * 8 + (lane & 7)) * 128 + (((2 * w + ((lane >> 3) & 1)) ^ (lane & 7)) << 4);
#pragma unroll
          for (int kk = 0; kk < 8; kk++)
            asm volatile("ldmatrix.sync.aligned.m8n8.x4.trans.shared.b16 {%0,%1,%2,%3}, [%4];" : "=r"(hf[4 * kk]), "=r"(hf[4 * kk + 1]), "=r"(hf[4 * kk + 2]), "=r"(hf[4 * kk + 3])
                         : "r"(ha + (kk >> 2) * him + (kk & 3) * 2048) : "memory");
        }
        mbar_wait(fullb + 8, full_par(25));
        wg_wait<1>(); release(5);
        gelu_b(0, 6);
        mma(o, 0, 4, 8, 0);
        gelu_b(6, 12);
        mma(o, 0, 8, 12, 0);
        credit();
        gelu_b(12, 18);
        mbar_wait(fullb + 16, full_par(26));
        mma(o, 0, 12, 15, 0);
        gelu_b(18, 24);
        mma(o, 0, 15, 18, 0);
        gelu_b(24, 32);
        if (wg == 1) bar_sync(4, 256);
        mma(o, 0, 18, 22, 0);
      } else {
        bar_sync(3 + wg, 256);
        if (p < 7) mma(o, p, 0, 22, 0); else mma(fin, p, 0, 22, 1);
      }
      if (p < 7 || wg == 0) bar_arrive(4 - wg, 256);
      if (p < 7) mbar_wait(sb + OFF_XFULL + 8 * (p + 1), 1);
      if ((p & 1) == 0) {
        if (w == 0 && lane == 0) mbar_expect_tx(sb + OFF_RBAR + wg * 8, 8192);
        if (p == 6) {
          mbar_wait(sb + OFF_EMPTY + 32, 0);
          tag = lds_u(sb + OFF_EPOCH);
          recv_check(sum, 0); recv_check(r0, 1);
#pragma unroll
          for (int i = 0; i < 16; i++) sum[i] = bf2_add(sum[i], r0[i]);
        }
        mbar_wait(sb + OFF_KBAR + wg * 8, (p >> 1) & 1);
      } else {
        if (p == 1 || p == 7) tag = lds_u(sb + OFF_EPOCH);
        recv_peer(p >> 1);
        if (p == 7) {
          recv_check(r0, 2);
#pragma unroll
          for (int i = 0; i < 16; i++) { sum[i] = bf2_add(sum[i], bf2_add(r0[i], pt[i])); pin(sum[i]); }
          sched_fence(ck);
        }
      }
      if (p == 4) {
        mbar_wait(sb + OFF_LBAR, 1);
#pragma unroll
        for (int j = 0; j < 8; j++) {
          const uint4 v = lds_u4(sb + pbuf + 16384 + (j >> 2) * 16384 + (j & 3) * 512);
          fin[4 * j] = __uint_as_float(v.x); fin[4 * j + 1] = __uint_as_float(v.y); fin[4 * j + 2] = __uint_as_float(v.z); fin[4 * j + 3] = __uint_as_float(v.w);
        }
        recv_issue(sum, 0);
      }
      wg_wait<0>();
      if (p < 5) release(p);
      if (p < 7) reg_fence(o); else reg_fence(fin);
      if ((p & 1) == 0) {
        if (p == 6) recv_issue(r0, 2);
#pragma unroll
        for (int i = 0; i < 4; i++)
          asm volatile("st.async.shared::cluster.mbarrier::complete_tx::bytes.v4.b32 [%0], {%1,%2,%3,%4}, [%5];" ::"r"(peer + pbuf + i * 512),
                       "r"(pack_bf16(o[8 * i], o[8 * i + 1])), "r"(pack_bf16(o[8 * i + 2], o[8 * i + 3])), "r"(pack_bf16(o[8 * i + 4], o[8 * i + 5])),
                       "r"(pack_bf16(o[8 * i + 6], o[8 * i + 7])), "r"(peer + OFF_RBAR + wg * 8) : "memory");
      } else if (p < 7) {
        const int k = p >> 1;
#pragma unroll
        for (int i = 0; i < 4; i++) {
#pragma unroll
          for (int c = 4 * i; c < 4 * i + 4; c++) pt[c] = bf2_add(pt[c], pack_bf16(o[2 * c], o[2 * c + 1]));
          asm("lop3.b32 %0, %0, 1, %1, 0xb8;" : "+r"(pt[4 * i]) : "r"(tag));
          st_b128(psend + (((sp + 1 + k) & 3) * 6 + k) * 1024 + i * 32, pt[4 * i], pt[4 * i + 1], pt[4 * i + 2], pt[4 * i + 3]);
        }
        __syncwarp();
        credit();
        if (p == 5) recv_issue(r0, 1);
      }
      if (p == 2) {
#pragma unroll
        for (int h = 0; h < 2; h++) { fs[h] = __fdividef(2.f, 4.f + bf_lo(lds_h(sb + OFF_GS + (wg * 64 + w * 16 + gr + 8 * h) * 2))); pin(fs[h]); }
      }
    }
    {
      const uint32_t tb = sb + OFF_X + stage_off(0) + warp * 4096;
      const uint32_t ta = tb + gr * 256 + ((gr & 3) << 5) + q * 8;
      const uint32_t la = tb + (lane >> 3) * 256 + (((lane & 7) << 4) ^ ((lane >> 3) << 5));
      float* op = out + (size_t)(m * 128 + (lane >> 4) * 32 + warp * 4 + ((lane >> 3) & 1)) * DM + s * 64 + (lane & 7) * 4;
#pragma unroll
      for (int qt = 0; qt < 4; qt++) {
        const int h = qt & 1, ch = qt >> 1;
#pragma unroll
        for (int j = 0; j < 4; j++) {
          const int i = ch * 8 + j * 2 + h;
          sts_f2((ta ^ (j << 5)) + h * 2048 + ch * 128, (fin[2 * i] + bf_lo(sum[i])) * fs[h], (fin[2 * i + 1] + bf_hi(sum[i])) * fs[h]);
        }
        __syncwarp();
#pragma unroll
        for (int r = 0; r < 2; r++)
          *reinterpret_cast<uint4*>(op + (r * 64 + h * 2) * DM + ch * 32) = lds_u4(la + (h * 2 + r) * 1024 + ch * 128);
      }
      sts_u(sb + OFF_EPOCH + 4, ck);
      if (warp == 4 && lane == 0) g_epoch[b] = tag;
    }
  } else {
    const int lane = __shfl_sync(0xffffffffu, lane0, lane0);
    asm volatile("setmaxnreg.dec.sync.aligned.u32 56;");
    int wsel = warp;
    asm("" : "+r"(wsel));
    if (wsel > 8) {
      const uint4* gwp = reinterpret_cast<const uint4*>(gate_w) + (lane & 7);
      uint4 gw[4];
      if (warp != 11) {
        const int t = (warp - 9) * 32 + lane;
        unsigned par;
        asm volatile("ld.relaxed.gpu.global.u32 %0, [%1];" : "=r"(par) : "l"(g_epoch + b) : "memory");
        const float pr = bf_ld(lam_re + s * 64 + t), pi = sgn * bf_ld(lam_im + s * 64 + t), pd = bf_ld(log_dt + s * 64 + t);
#pragma unroll
        for (int i = 0; i < 4; i++) gw[i] = __ldg(gwp + i * 8);
        cluster_wait();
        par = __shfl_sync(0xffffffffu, (par + 1) & 1, 0);
        cplx l128 = make_lam(pr, pi, pd);
        {
          const float inv = __fdividef(sgn, fmaf(pr, pr, pi * pi));
          const cplx cf = cmul(cplx{l128.re - 1.f, l128.im}, cplx{pr * inv, -pi * inv});
          sts_f4(sb + OFF_LC + t * 16, l128.re, l128.im, cf.re, cf.im);
          mbar_arrive(sb + OFF_LBAR);
        }
#pragma unroll
        for (int i = 0; i < 7; i++) l128 = cmul(l128, l128);
        pin(l128.re); pin(l128.im);
        gate_rows<1>(sb, lane, xrot, s * 16 + (warp - 9) * 4, gw, gwp, g_gate + m * 128, par);
        uint32_t vr[15], vi[15];
#pragma unroll
        for (int i = 0; i < 15; i++) { vr[i] = par; vi[i] = 0; pin(vr[i]); pin(vi[i]); }
        mbar_wait(sb + OFF_GBAR, 0);
        float2* eb = g_end + s * 1024 + t;
        {
          const float2 e = lds_f2(sb + OFF_CARRY + t * 8);
          const unsigned long long v = ((unsigned long long)__float_as_uint(e.y) << 32) | ((__float_as_uint(e.x) & ~1u) | par);
          asm volatile("st.relaxed.gpu.global.b64 [%0], %1;" ::"l"(eb + m * 64), "l"(v) : "memory");
        }
        __nanosleep(400);
        const float2* e15 = eb + (m - 15) * 64;
        int tries = 0;
        bool bad;
#pragma unroll 1
        do {
#pragma unroll
          for (int i = 0; i < 15; i++)
            asm volatile("{.reg .pred p; .reg .b64 v; mov.b64 v, {%0,%1}; setp.ge.s32 p, %3, %4; @p ld.relaxed.gpu.global.b64 v, [%2]; mov.b64 {%0,%1}, v;}"
                         : "+r"(vr[i]), "+r"(vi[i]) : "l"(e15 + i * 64), "r"(m), "r"(15 - i) : "memory");
          uint32_t x = vr[0] ^ par;
#pragma unroll
          for (int i = 1; i < 15; i++) asm("lop3.b32 %0, %0, %1, %2, 0xf6;" : "+r"(x) : "r"(vr[i]), "r"(par));
          bad = __any_sync(0xffffffffu, x & 1);
        } while (bad && ++tries < 200000);
        cplx S = {__uint_as_float(vr[0] ^ par), __uint_as_float(vi[0])};
#pragma unroll
        for (int i = 1; i < 15; i++) S = cfma(l128, S, cplx{__uint_as_float(vr[i] ^ par), __uint_as_float(vi[i])});
        sts_f2(sb + OFF_CARRY + t * 8, S.re, S.im);
        mbar_arrive(sb + OFF_CBAR);
        mbar_wait(sb + OFF_CBAR, 0);
        const int gr = lane >> 2, q = lane & 3;
        float2 db[8];
#pragma unroll
        for (int j = 0; j < 8; j++) db[j] = lds_f2(sb + OFF_DB + j * 32 + q * 8);
        mbar_wait(sb + OFF_XFULL + 16, 1);
        mbar_wait(sb + OFF_EMPTY, 0);
#pragma unroll 1
        for (int cw = warp - 9; cw < 8; cw += 2) {
          const float r0 = 0.5f * bf_lo(lds_h(sb + OFF_GS + (cw * 16 + gr) * 2)), r1 = 0.5f * bf_lo(lds_h(sb + OFF_GS + (cw * 16 + gr) * 2 + 16));
          const uint32_t xa = sb + OFF_X + (1 + rank) * 16384 + (cw * 16 + (lane & 15)) * 128 + (((lane >> 4) ^ (lane & 7)) << 4);
          uint32_t xv[16];
#pragma unroll
          for (int i = 0; i < 4; i++)
            asm volatile("ldmatrix.sync.aligned.m8n8.x4.shared.b16 {%0,%1,%2,%3}, [%4];" : "=r"(xv[4 * i]), "=r"(xv[4 * i + 1]), "=r"(xv[4 * i + 2]), "=r"(xv[4 * i + 3])
                         : "r"(xa ^ (i << 5)) : "memory");
          __syncwarp();
#pragma unroll
          for (int j = 0; j < 8; j++) {
            const uint32_t x0 = bf2_mul(xv[2 * j], __float_as_uint(db[j].x)), x1 = bf2_mul(xv[2 * j + 1], __float_as_uint(db[j].x));
            pin(db[j].y);
            const float bl = bf_lo(__float_as_uint(db[j].y)), bh = bf_hi(__float_as_uint(db[j].y));
            sts_f4(sb + OFF_X + 16384 + (j >> 2) * 16384 + cw * 2048 + (j & 3) * 512 + lane * 16, fmaf(bf_lo(x0), r0, bl), fmaf(bf_hi(x0), r0, bh),
                   fmaf(bf_lo(x1), r1, bl), fmaf(bf_hi(x1), r1, bh));
          }
        }
        mbar_arrive(sb + OFF_LBAR);
      } else {
#pragma unroll
        for (int i = 0; i < 4; i++) gw[i] = __ldg(gwp + i * 8);
        unsigned par;
        asm volatile("ld.relaxed.gpu.global.u32 %0, [%1];" : "=r"(par) : "l"(g_epoch + b) : "memory");
        const uint32_t dk = __ldg(reinterpret_cast<const uint32_t*>(dskip + s * 64) + lane), bb = __ldg(reinterpret_cast<const uint32_t*>(b2 + s * 64) + lane);
        cluster_wait();
        if (lane == 0) sts_u(sb + OFF_EPOCH, par + 1);
        par = (par + 1) & 1;
        gate_rows<2>(sb, lane, xrot, s * 16 + 8, gw, gwp, g_gate + m * 128, par);
        mbar_wait(sb + OFF_GBAR, 0);
        sts_u2(sb + OFF_DB + lane * 8, dk, bf2_add(bb, bb));
        uint32_t g0, g1, g2, g3;
        int tries = 0;
#pragma unroll 1
        do {
          asm volatile("ld.relaxed.gpu.global.v4.u32 {%0,%1,%2,%3}, [%4];" : "=r"(g0), "=r"(g1), "=r"(g2), "=r"(g3) : "l"(g_gate + m * 128 + lane * 4) : "memory");
          g0 ^= par; g1 ^= par; g2 ^= par; g3 ^= par;
        } while (((g0 | g1 | g2 | g3) & 1) && ++tries < 200000);
        const uint32_t p01 = pack_bf16(__uint_as_float(g0), __uint_as_float(g1)), p23 = pack_bf16(__uint_as_float(g2), __uint_as_float(g3));
        sts_u2(sb + OFF_GS + lane * 8, p01, p23);
        const uint32_t gt = sb + OFF_GT + ((lane >> 2) & 3) * 64 + (lane & 1) * 32 + (lane & 2) * 4 + (lane >> 4) * 4;
        sts_u(gt, p01);
        sts_u(gt + 16, p23);
        mbar_arrive(sb + OFF_CBAR);
      }
    } else {
      cluster_wait();
      if (elect_one()) {
        const uint32_t t0 = clock();
#pragma unroll 1
        for (int u = 1; u < 8; u++) {
          while ((uint32_t)clock() - t0 < 200 + (u - 1) * 480) {}
          const uint32_t fb = sb + OFF_XFULL + 8 * u;
          mbar_expect_tx(fb, 32768);
          tma5d_mc(sb + OFF_X + ((u + xrot) & 7) * 16384 + rank * 8192, &maps.x, u * 64, rank * 8, m, fb);
          const int sl = u < 6 ? u : u - 6;
          if (u >= 6) mbar_wait(sb + OFF_EMPTY + 8 * sl, 0);
          tma4d(sb + OFF_RING + sl * 16384, &maps.bb, u * 64, s * 8, fb);
        }
        int slot = 2; uint32_t ph = 0;
#pragma unroll 1
        for (int u = 8; u < 24; u++) {
          const uint32_t fb = sb + OFF_FULL + 8 * slot, dst = sb + OFF_RING + slot * 16384;
          mbar_wait(sb + OFF_EMPTY + 8 * slot, ph);
          if (u < 16) {
            mbar_expect_tx(fb, 12288);
            tma3d(dst, &maps.w1b, 0, (u - 8) * 64, s * 7, fb);
            if (u < 12) map_prefetch(&maps.w1a + (u - 8));
          } else {
            mbar_expect_tx(fb, 16384);
            tma2d(dst, &maps.w1a, s * 224 + 96, ((u - xrot) & 7) * 64, fb);
            tma2d(dst + 8192, &maps.w1a, s * 224 + 160, ((u - xrot) & 7) * 64, fb);
          }
          if (++slot == NSLOT) { slot = 0; ph ^= 1; }
        }
#pragma unroll 1
        for (int j = 0; j < 3; j++) {
          const uint32_t fb = sb + OFF_FULL + 8 * j, dst = sb + OFF_X + stage_off(0);
          const int c = ((sp + 1) & 3) * 128 + ((rank ^ 1) << 6);
          mbar_wait(sb + OFF_EMPTY + 8 + 8 * j, 1);
          mbar_expect_tx(fb, j == 1 ? 16384 : 14336);
          if (j == 1) {
            tma2d(dst + 14336, &maps.cre, s * 64, c, fb);
            tma2d(dst + 22528, &maps.cim, s * 64, c, fb);
          } else {
            tma2d(dst + j * 15360, &maps.w2, c, s * 224 + j * 56, fb);
          }
        }
#pragma unroll 1
        for (int p = 1; p < 8; p++) {
          const int c = ((sp + 1 + (p >> 1)) & 3) * 128 + (((rank ^ p ^ 1) & 1) << 6);
          const uint32_t fb = sb + OFF_XFULL + 8 * p, dst = sb + OFF_X + stage_off(p);
          if (p == 2 || p > 3) mbar_wait(sb + OFF_EMPTY + (p == 2 ? 40 : (p - 4) * 8), p == 2);
          mbar_expect_tx(fb, 45056);
          tma2d(dst, &maps.w2, c, s * 224, fb);
          tma2d(dst + 14336, &maps.cre, s * 64, c, fb);
          tma2d(dst + 22528, &maps.cim, s * 64, c, fb);
          tma2d(dst + 30720, &maps.w2, c, s * 224 + 112, fb);
        }
      }
    }
  }
}

typedef CUresult (*EncFn)(CUtensorMap*, CUtensorMapDataType, cuuint32_t, void*, const cuuint64_t*, const cuuint64_t*, const cuuint32_t*,
                          const cuuint32_t*, CUtensorMapInterleave, CUtensorMapSwizzle, CUtensorMapL2promotion, CUtensorMapFloatOOBfill);

void encode(EncFn f, CUtensorMap* mp, const void* p, int rank, const cuuint64_t* dims, const cuuint64_t* strides, const cuuint32_t* box, CUtensorMapSwizzle sw) {
  cuuint32_t es[5] = {1, 1, 1, 1, 1};
  f(mp, CU_TENSOR_MAP_DATA_TYPE_BFLOAT16, rank, const_cast<void*>(p), dims, strides, box, es, CU_TENSOR_MAP_INTERLEAVE_NONE, sw,
    CU_TENSOR_MAP_L2_PROMOTION_L2_128B, CU_TENSOR_MAP_FLOAT_OOB_FILL_NONE);
}

}

extern "C" void kernel_launch(void* const* d_in, const int* in_sizes, int n_in, void* d_out, int out_size) {
  typedef const __nv_bfloat16* bp;
  bp x = (bp)d_in[0], lre = (bp)d_in[1], lim = (bp)d_in[2], bre = (bp)d_in[3], bim = (bp)d_in[4], cre = (bp)d_in[5], cim = (bp)d_in[6],
     ldt = (bp)d_in[7], dsk = (bp)d_in[8], w1 = (bp)d_in[10], b1 = (bp)d_in[11], w2 = (bp)d_in[12], b2 = (bp)d_in[13], gw = (bp)d_in[14];
  static EncFn enc = nullptr;
  if (!enc) {
    void* f = nullptr;
    cudaDriverEntryPointQueryResult qr;
    cudaGetDriverEntryPoint("cuTensorMapEncodeTiled", &f, cudaEnableDefault, &qr);
    enc = (EncFn)f;
    cudaFuncSetAttribute(fused_kernel, cudaFuncAttributeMaxDynamicSharedMemorySize, SMEM_BYTES);
  }
  Maps maps;
  const bool swap = bim < bre;
  {
    cuuint64_t d[5] = {DM, 2, 4, 16, SEQ / 128}, st[4] = {DM * 2, 32 * DM * 2, 2 * DM * 2, 128 * DM * 2};
    cuuint32_t bx[5] = {64, 2, 4, 8, 1};
    encode(enc, &maps.x, x, 5, d, st, bx, CU_TENSOR_MAP_SWIZZLE_128B);
  }
  {
    cuuint64_t d[2] = {DM, DM}, st[1] = {DM * 2};
    cuuint32_t bx[2] = {64, 64};
    encode(enc, &maps.cre, swap ? cim : cre, 2, d, st, bx, CU_TENSOR_MAP_SWIZZLE_128B);
    encode(enc, &maps.cim, swap ? cre : cim, 2, d, st, bx, CU_TENSOR_MAP_SWIZZLE_128B);
    cuuint64_t d4[4] = {DM, 8, 2, DM / 8}, st4[3] = {DM * 2, (cuuint64_t)(swap ? bre - bim : bim - bre) * 2, 8 * DM * 2};
    cuuint32_t bx4[4] = {64, 8, 2, 8};
    encode(enc, &maps.bb, swap ? bim : bre, 4, d4, st4, bx4, CU_TENSOR_MAP_SWIZZLE_128B);
  }
  {
    cuuint64_t d[2] = {FF, DM}, st[1] = {FF * 2};
    cuuint32_t bx[2] = {64, 64};
    encode(enc, &maps.w1a, w1, 2, d, st, bx, CU_TENSOR_MAP_SWIZZLE_128B);
    cuuint64_t d3[3] = {32, DM, FF / 32}, st3[2] = {FF * 2, 64};
    cuuint32_t bx3[3] = {32, 64, 3};
    encode(enc, &maps.w1b, w1, 3, d3, st3, bx3, CU_TENSOR_MAP_SWIZZLE_64B);
  }
  {
    cuuint64_t d[2] = {DM, FF}, st[1] = {DM * 2};
    cuuint32_t bx[2] = {64, 112};
    encode(enc, &maps.w2, w2, 2, d, st, bx, CU_TENSOR_MAP_SWIZZLE_128B);
  }
  fused_kernel<<<128, 384, SMEM_BYTES>>>(lre, lim, ldt, dsk, b1, b2, gw, (float*)d_out, swap ? -1.f : 1.f, maps);
}
```

```cpp
#include <cuda_runtime.h>
#include <cuda_bf16.h>
#include <cuda.h>
#include <stdint.h>

namespace {

constexpr int SEQ = 2048, DM = 512, FF = 1792;
constexpr int NSLOT = 6;
constexpr uint32_t OFF_X = 0, OFF_RING = 131072, OFF_MISC = 229376;
constexpr uint32_t OFF_XFULL = OFF_MISC, OFF_FULL = OFF_XFULL + 64, OFF_RBAR = OFF_FULL + 48, OFF_EMPTY = OFF_RBAR + 16, OFF_KBAR = OFF_EMPTY + 48,
                   OFF_GBAR = OFF_KBAR + 16, OFF_LBAR = OFF_GBAR + 8, OFF_CBAR = OFF_LBAR + 8, OFF_EPOCH = OFF_CBAR + 8;
constexpr uint32_t OFF_LC = OFF_MISC + 256;
constexpr uint32_t OFF_GS = OFF_LC;
constexpr uint32_t OFF_GT = OFF_LC + 256;
constexpr uint32_t OFF_DB = OFF_LC + 512;
constexpr uint32_t OFF_CARRY = OFF_LC + 1024;
constexpr uint32_t SMEM_BYTES = OFF_CARRY + 512;
static_assert(SMEM_BYTES <= 232448, "smem");

struct Maps { CUtensorMap x, bb, w1b, w1a, w2, cre, cim; };
__host__ __device__ constexpr uint32_t stage_off(int p) { return 49152 + 45056 * (((p >> 1) & 1) + 2 * (p & 1)); }
__host__ __device__ constexpr uint32_t full_par(int u) { return ((u - 8) / 6 + (u % 6 == 0)) & 1; }

__device__ uint4 g_part[16 * 8 * 3 * 1024];
__device__ float2 g_end[8 * 16 * 64];
__device__ unsigned g_gate[SEQ];
__device__ unsigned g_epoch[128];

__device__ __forceinline__ void mbar_init(uint32_t bar, uint32_t cnt) { asm volatile("mbarrier.init.shared::cta.b64 [%0], %1;" ::"r"(bar), "r"(cnt)); }
__device__ __forceinline__ void mbar_expect_tx(uint32_t bar, uint32_t bytes) { asm volatile("mbarrier.arrive.expect_tx.shared::cta.b64 _, [%0], %1;" ::"r"(bar), "r"(bytes) : "memory"); }
__device__ __forceinline__ void mbar_arrive(uint32_t bar) { asm volatile("mbarrier.arrive.shared::cta.b64 _, [%0];" ::"r"(bar) : "memory"); }
__device__ __forceinline__ void mbar_arrive_cl(uint32_t cbar) { asm volatile("mbarrier.arrive.shared::cluster.b64 _, [%0];" ::"r"(cbar) : "memory"); }
__device__ __forceinline__ void mbar_wait(uint32_t bar, uint32_t parity) {
  asm volatile(
      "{\n.reg .pred p;\n.reg .u32 c;\n"
      "mbarrier.try_wait.parity.shared::cta.b64 p, [%0], %1;\n"
      "@p bra.uni LAB_DONE;\n"
      "mov.u32 c, 0;\n"
      "LAB_WAIT:\n"
      "mbarrier.try_wait.parity.shared::cta.b64 p, [%0], %1;\n"
      "@p bra.uni LAB_DONE;\n"
      "add.u32 c, c, 1;\nsetp.lt.u32 p, c, 200000;\n@p bra.uni LAB_WAIT;\n"
      "LAB_DONE:\n}" ::"r"(bar), "r"(parity) : "memory");
}
__device__ __forceinline__ void tma2d(uint32_t dst, const CUtensorMap* m, int c0, int c1, uint32_t bar) {
  asm volatile("cp.async.bulk.tensor.2d.shared::cluster.global.mbarrier::complete_tx::bytes [%0], [%1, {%3,%4}], [%2];"
               ::"r"(dst), "l"(m), "r"(bar), "r"(c0), "r"(c1) : "memory");
}
__device__ __forceinline__ void tma3d(uint32_t dst, const CUtensorMap* m, int c0, int c1, int c2, uint32_t bar) {
  asm volatile("cp.async.bulk.tensor.3d.shared::cluster.global.mbarrier::complete_tx::bytes [%0], [%1, {%3,%4,%5}], [%2];"
               ::"r"(dst), "l"(m), "r"(bar), "r"(c0), "r"(c1), "r"(c2) : "memory");
}
__device__ __forceinline__ void tma4d(uint32_t dst, const CUtensorMap* m, int c0, int c3, uint32_t bar) {
  asm volatile("cp.async.bulk.tensor.4d.shared::cluster.global.mbarrier::complete_tx::bytes [%0], [%1, {%3,%5,%5,%4}], [%2];"
               ::"r"(dst), "l"(m), "r"(bar), "r"(c0), "r"(c3), "r"(0) : "memory");
}
__device__ __forceinline__ void tma5d(uint32_t dst, const CUtensorMap* m, int c0, int c3, int c4, uint32_t bar) {
  asm volatile("cp.async.bulk.tensor.5d.shared::cluster.global.mbarrier::complete_tx::bytes [%0], [%1, {%3,%6,%6,%4,%5}], [%2];"
               ::"r"(dst), "l"(m), "r"(bar), "r"(c0), "r"(c3), "r"(c4), "r"(0) : "memory");
}
__device__ __forceinline__ void tma5d_mc(uint32_t dst, const CUtensorMap* m, int c0, int c3, int c4, uint32_t bar) {
  asm volatile("cp.async.bulk.tensor.5d.shared::cluster.global.mbarrier::complete_tx::bytes.multicast::cluster [%0], [%1, {%3,%6,%6,%4,%5}], [%2], %7;"
               ::"r"(dst), "l"(m), "r"(bar), "r"(c0), "r"(c3), "r"(c4), "r"(0), "h"((uint16_t)3) : "memory");
}
__device__ __forceinline__ void map_prefetch(const CUtensorMap* m) { asm volatile("prefetch.tensormap [%0];" ::"l"(m) : "memory"); }
__device__ __forceinline__ bool elect_one() {
  uint32_t pred;
  asm volatile("{.reg .pred P; elect.sync _|P, 0xffffffff; selp.u32 %0, 1, 0, P;}" : "=r"(pred));
  return pred != 0;
}
__device__ __forceinline__ void cluster_wait() { asm volatile("barrier.cluster.wait.aligned;" ::: "memory"); }
__device__ __forceinline__ void wg_fence() { asm volatile("wgmma.fence.sync.aligned;" ::: "memory"); }
__device__ __forceinline__ void wg_commit() { asm volatile("wgmma.commit_group.sync.aligned;" ::: "memory"); }
template <int N> __device__ __forceinline__ void wg_wait() { asm volatile("wgmma.wait_group.sync.aligned %0;" ::"n"(N) : "memory"); }
__device__ __forceinline__ void pin(float& a) { asm volatile("" : "+f"(a)::"memory"); }
__device__ __forceinline__ void pin(uint32_t& a) { asm volatile("" : "+r"(a)::"memory"); }
template <int N> __device__ __forceinline__ void reg_fence(float (&d)[N]) {
#pragma unroll
  for (int i = 0; i < N; i++) pin(d[i]);
}
__device__ __forceinline__ void sched_fence(uint32_t& ck) { asm volatile("{.reg .b32 c; mov.u32 c, %%clock; xor.b32 %0, %0, c;}" : "+r"(ck)::"memory"); }
__device__ __forceinline__ void bar_sync(int id, int n) { asm volatile("bar.sync %0, %1;" ::"r"(id), "r"(n) : "memory"); }
__device__ __forceinline__ void bar_arrive(int id, int n) { asm volatile("bar.arrive %0, %1;" ::"r"(id), "r"(n) : "memory"); }
constexpr uint32_t DH128 = (1024 >> 4) | (1u << 30), DH64 = (512 >> 4) | (2u << 30);
__host__ __device__ constexpr uint32_t lbo(uint32_t bytes) { return (bytes >> 4) << 20; }
__device__ __forceinline__ uint32_t pack_bf16(float lo, float hi) { uint32_t r; asm("cvt.rn.bf16x2.f32 %0, %1, %2;" : "=r"(r) : "f"(hi), "f"(lo)); return r; }
__device__ __forceinline__ float bf_lo(uint32_t v) { return __uint_as_float(v << 16); }
__device__ __forceinline__ float bf_hi(uint32_t v) { return __uint_as_float(v & 0xffff0000u); }
__device__ __forceinline__ float bf_ld(const __nv_bfloat16* p) { return __bfloat162float(__ldg(p)); }
__device__ __forceinline__ uint32_t late16(uint32_t bar) {
  uint32_t r;
  asm volatile("{.reg .pred p; mbarrier.test_wait.parity.shared::cta.b64 p, [%1], 0; selp.u32 %0, 16, 0, p;}" : "=r"(r) : "r"(bar) : "memory");
  return r;
}
__device__ __forceinline__ float2 lds_f2(uint32_t a) { float2 v; asm volatile("ld.shared.v2.f32 {%0,%1}, [%2];" : "=f"(v.x), "=f"(v.y) : "r"(a)); return v; }
__device__ __forceinline__ uint32_t lds_h(uint32_t a) { uint32_t v; asm volatile("ld.shared.u16 %0, [%1];" : "=r"(v) : "r"(a)); return v; }
__device__ __forceinline__ uint32_t lds_u(uint32_t a) { uint32_t v; asm volatile("ld.shared.u32 %0, [%1];" : "=r"(v) : "r"(a)); return v; }
__device__ __forceinline__ uint4 lds_u4(uint32_t a) { uint4 v; asm volatile("ld.shared.v4.u32 {%0,%1,%2,%3}, [%4];" : "=r"(v.x), "=r"(v.y), "=r"(v.z), "=r"(v.w) : "r"(a)); return v; }
__device__ __forceinline__ void sts_u(uint32_t a, uint32_t v) { asm volatile("st.shared.u32 [%0], %1;" ::"r"(a), "r"(v) : "memory"); }
__device__ __forceinline__ void sts_u2(uint32_t a, uint32_t x, uint32_t y) { asm volatile("st.shared.v2.u32 [%0], {%1,%2};" ::"r"(a), "r"(x), "r"(y) : "memory"); }
__device__ __forceinline__ void sts_f2(uint32_t a, float x, float y) { asm volatile("st.shared.v2.f32 [%0], {%1,%2};" ::"r"(a), "f"(x), "f"(y) : "memory"); }
__device__ __forceinline__ void sts_f4(uint32_t a, float x, float y, float z, float w) {
  asm volatile("st.shared.v4.f32 [%0], {%1,%2,%3,%4};" ::"r"(a), "f"(x), "f"(y), "f"(z), "f"(w) : "memory");
}
__device__ __forceinline__ void st_b128(uint4* p, uint32_t a, uint32_t b, uint32_t c, uint32_t d) {
  asm volatile("st.relaxed.gpu.global.v4.b32 [%0], {%1,%2,%3,%4};" ::"l"(p), "r"(a), "r"(b), "r"(c), "r"(d) : "memory");
}
__device__ __forceinline__ void ld_b128(const uint4* p, uint32_t& a, uint32_t& b, uint32_t& c, uint32_t& d) {
  asm volatile("{.reg .b64 l, h; .reg .b128 v; ld.relaxed.gpu.global.b128 v, [%4]; mov.b128 {l,h}, v; mov.b64 {%0,%1}, l; mov.b64 {%2,%3}, h;}"
               : "=r"(a), "=r"(b), "=r"(c), "=r"(d) : "l"(p) : "memory");
}
__device__ __forceinline__ uint32_t bf2_mul(uint32_t a, uint32_t b) { uint32_t r; asm("mul.rn.bf16x2 %0, %1, %2;" : "=r"(r) : "r"(a), "r"(b)); return r; }
__device__ __forceinline__ uint32_t bf2_add(uint32_t a, uint32_t b) { uint32_t r; asm("add.rn.bf16x2 %0, %1, %2;" : "=r"(r) : "r"(a), "r"(b)); return r; }
__device__ __forceinline__ uint32_t bf2_fma(uint32_t a, uint32_t b, uint32_t c) { uint32_t r; asm("fma.rn.bf16x2 %0, %1, %2, %3;" : "=r"(r) : "r"(a), "r"(b), "r"(c)); return r; }
__device__ __forceinline__ uint32_t gelu2_pair(float a, float b) {
  const uint32_t v = pack_bf16(a, b);
  uint32_t t;
  asm("tanh.approx.bf16x2 %0, %1;" : "=r"(t) : "r"(bf2_fma(v, bf2_fma(bf2_mul(v, v), 0x3d123d12u, 0xbe4fbe4fu), v)));
  return bf2_fma(v, t, v);
}
struct cplx { float re, im; };
__device__ __forceinline__ cplx cmul(cplx a, cplx b) { return {fmaf(a.re, b.re, -a.im * b.im), fmaf(a.re, b.im, a.im * b.re)}; }
__device__ __forceinline__ cplx cfma(cplx a, cplx b, cplx c) {
  return {fmaf(a.re, b.re, fmaf(-a.im, b.im, c.re)), fmaf(a.re, b.im, fmaf(a.im, b.re, c.im))};
}
__device__ __forceinline__ cplx make_lam(float lre, float lim, float ldt) {
  float dt = __bfloat162float(__float2bfloat16_rn(expf(ldt)));
  float mag = expf(dt * lre), sn, cs;
  sincospif(dt * lim * 0.31830988618379067f, &sn, &cs);
  return {mag * cs, mag * sn};
}

__device__ __forceinline__ void gate_rows(uint32_t sb, int lane, int xrot, int row0, uint4 (&gw)[4], const uint4* gwp, unsigned* dst, unsigned par) {
  const int row = row0 + (lane >> 3);
  const uint32_t xr0 = sb + OFF_X + row * 128 + (((lane & 7) ^ (row & 7)) << 4), xr1 = (xr0 + 512) ^ 64;
  float z[2], y[2];
#pragma unroll
  for (int r = 0; r < 2; r++) z[r] = y[r] = 0.f;
#pragma unroll
  for (int kb = 0; kb < 8; kb++) {
    const uint4 w = gw[kb & 3];
    if (kb < 4) gw[kb] = __ldg(gwp + (kb + 4) * 8);
    mbar_wait(sb + OFF_XFULL + 8 * kb, 0);
#pragma unroll
    for (int r = 0; r < 2; r++) {
      const uint4 a = lds_u4((r ? xr1 : xr0) + ((kb + xrot) & 7) * 16384);
      const uint32_t p[4] = {bf2_mul(a.x, w.x), bf2_mul(a.y, w.y), bf2_mul(a.z, w.z), bf2_mul(a.w, w.w)};
#pragma unroll
      for (int c = 0; c < 4; c++) { z[r] += bf_lo(p[c]); y[r] += bf_hi(p[c]); }
    }
  }
  float zz = z[0] + y[0];
  const float z1 = z[1] + y[1];
  zz = ((lane & 4) ? z1 : zz) + __shfl_xor_sync(0xffffffffu, (lane & 4) ? zz : z1, 4);
  zz += __shfl_xor_sync(0xffffffffu, zz, 2);
  zz += __shfl_xor_sync(0xffffffffu, zz, 1);
  zz = bf_lo(pack_bf16(zz, 0.f));
  const float rho = 4.f * expf(zz > 40.f ? 40.f : zz);
  if ((lane & 3) == 0)
    asm volatile("st.relaxed.gpu.global.u32 [%0], %1;" ::"l"(dst + row + (lane & 4)), "r"((__float_as_uint(rho) & ~1u) | par) : "memory");
}

template<int TB,uint32_t BH,int SA=1> __device__ __forceinline__ void wgmma_n64_rs(float (&d)[32], uint32_t a0,uint32_t a1,uint32_t a2,uint32_t a3, uint32_t bl, uint32_t bo, int scale_d){
  asm volatile("{.reg .pred p; .reg .b32 t; .reg .b64 db; setp.ne.b32 p, %38, 0; add.u32 t, %36, %37; mov.b64 db, {t, %40};\n"
   "wgmma.mma_async.sync.aligned.m64n64k16.f32.bf16.bf16 {%0,%1,%2,%3,%4,%5,%6,%7,%8,%9,%10,%11,%12,%13,%14,%15,%16,%17,%18,%19,%20,%21,%22,%23,%24,%25,%26,%27,%28,%29,%30,%31}, {%32,%33,%34,%35}, db, p, %41, 1, %39;}"
   : "+f"(d[0]),"+f"(d[1]),"+f"(d[2]),"+f"(d[3]),"+f"(d[4]),"+f"(d[5]),"+f"(d[6]),"+f"(d[7]),"+f"(d[8]),"+f"(d[9]),"+f"(d[10]),"+f"(d[11]),"+f"(d[12]),"+f"(d[13]),"+f"(d[14]),"+f"(d[15]),"+f"(d[16]),"+f"(d[17]),"+f"(d[18]),"+f"(d[19]),"+f"(d[20]),"+f"(d[21]),"+f"(d[22]),"+f"(d[23]),"+f"(d[24]),"+f"(d[25]),"+f"(d[26]),"+f"(d[27]),"+f"(d[28]),"+f"(d[29]),"+f"(d[30]),"+f"(d[31])
   : "r"(a0),"r"(a1),"r"(a2),"r"(a3),"r"(bl),"r"(bo >> 4),"r"(scale_d),"n"(TB),"n"(BH),"n"(SA));
}
template<int TA,int TB,uint32_t AH,uint32_t BH> __device__ __forceinline__ void wgmma_n96_ss(float (&d)[48], uint32_t al, uint32_t ao, uint32_t bl, uint32_t bo, int scale_d){
  asm volatile("{.reg .pred p; .reg .b32 t, v; .reg .b64 da, db; setp.ne.b32 p, %52, 0; add.u32 t, %48, %49; mov.b64 da, {t, %55}; add.u32 v, %50, %51; mov.b64 db, {v, %56};\n"
   "wgmma.mma_async.sync.aligned.m64n96k16.f32.bf16.bf16 {%0,%1,%2,%3,%4,%5,%6,%7,%8,%9,%10,%11,%12,%13,%14,%15,%16,%17,%18,%19,%20,%21,%22,%23,%24,%25,%26,%27,%28,%29,%30,%31,%32,%33,%34,%35,%36,%37,%38,%39,%40,%41,%42,%43,%44,%45,%46,%47}, da, db, p, 1, 1, %53, %54;}"
   : "+f"(d[0]),"+f"(d[1]),"+f"(d[2]),"+f"(d[3]),"+f"(d[4]),"+f"(d[5]),"+f"(d[6]),"+f"(d[7]),"+f"(d[8]),"+f"(d[9]),"+f"(d[10]),"+f"(d[11]),"+f"(d[12]),"+f"(d[13]),"+f"(d[14]),"+f"(d[15]),"+f"(d[16]),"+f"(d[17]),"+f"(d[18]),"+f"(d[19]),"+f"(d[20]),"+f"(d[21]),"+f"(d[22]),"+f"(d[23]),"+f"(d[24]),"+f"(d[25]),"+f"(d[26]),"+f"(d[27]),"+f"(d[28]),"+f"(d[29]),"+f"(d[30]),"+f"(d[31]),"+f"(d[32]),"+f"(d[33]),"+f"(d[34]),"+f"(d[35]),"+f"(d[36]),"+f"(d[37]),"+f"(d[38]),"+f"(d[39]),"+f"(d[40]),"+f"(d[41]),"+f"(d[42]),"+f"(d[43]),"+f"(d[44]),"+f"(d[45]),"+f"(d[46]),"+f"(d[47])
   : "r"(al),"r"(ao >> 4),"r"(bl),"r"(bo >> 4),"r"(scale_d),"n"(TA),"n"(TB),"n"(AH),"n"(BH));
}
template<int TA,int TB,uint32_t AH,uint32_t BH> __device__ __forceinline__ void wgmma_n128_ss(float (&d)[64], uint32_t al, uint32_t ao, uint32_t bl, uint32_t bo, int scale_d){
  asm volatile("{.reg .pred p; .reg .b32 t, v; .reg .b64 da, db; setp.ne.b32 p, %68, 0; add.u32 t, %64, %65; mov.b64 da, {t, %71}; add.u32 v, %66, %67; mov.b64 db, {v, %72};\n"
   "wgmma.mma_async.sync.aligned.m64n128k16.f32.bf16.bf16 {%0,%1,%2,%3,%4,%5,%6,%7,%8,%9,%10,%11,%12,%13,%14,%15,%16,%17,%18,%19,%20,%21,%22,%23,%24,%25,%26,%27,%28,%29,%30,%31,%32,%33,%34,%35,%36,%37,%38,%39,%40,%41,%42,%43,%44,%45,%46,%47,%48,%49,%50,%51,%52,%53,%54,%55,%56,%57,%58,%59,%60,%61,%62,%63}, da, db, p, 1, 1, %69, %70;}"
   : "+f"(d[0]),"+f"(d[1]),"+f"(d[2]),"+f"(d[3]),"+f"(d[4]),"+f"(d[5]),"+f"(d[6]),"+f"(d[7]),"+f"(d[8]),"+f"(d[9]),"+f"(d[10]),"+f"(d[11]),"+f"(d[12]),"+f"(d[13]),"+f"(d[14]),"+f"(d[15]),"+f"(d[16]),"+f"(d[17]),"+f"(d[18]),"+f"(d[19]),"+f"(d[20]),"+f"(d[21]),"+f"(d[22]),"+f"(d[23]),"+f"(d[24]),"+f"(d[25]),"+f"(d[26]),"+f"(d[27]),"+f"(d[28]),"+f"(d[29]),"+f"(d[30]),"+f"(d[31]),"+f"(d[32]),"+f"(d[33]),"+f"(d[34]),"+f"(d[35]),"+f"(d[36]),"+f"(d[37]),"+f"(d[38]),"+f"(d[39]),"+f"(d[40]),"+f"(d[41]),"+f"(d[42]),"+f"(d[43]),"+f"(d[44]),"+f"(d[45]),"+f"(d[46]),"+f"(d[47]),"+f"(d[48]),"+f"(d[49]),"+f"(d[50]),"+f"(d[51]),"+f"(d[52]),"+f"(d[53]),"+f"(d[54]),"+f"(d[55]),"+f"(d[56]),"+f"(d[57]),"+f"(d[58]),"+f"(d[59]),"+f"(d[60]),"+f"(d[61]),"+f"(d[62]),"+f"(d[63])
   : "r"(al),"r"(ao >> 4),"r"(bl),"r"(bo >> 4),"r"(scale_d),"n"(TA),"n"(TB),"n"(AH),"n"(BH));
}

__global__ void __cluster_dims__(2, 1, 1) __launch_bounds__(384, 1)
fused_kernel(const __nv_bfloat16* __restrict__ lam_re, const __nv_bfloat16* __restrict__ lam_im, const __nv_bfloat16* __restrict__ log_dt,
             const __nv_bfloat16* __restrict__ dskip, const __nv_bfloat16* __restrict__ b1, const __nv_bfloat16* __restrict__ b2,
             const __nv_bfloat16* __restrict__ gate_w, float* __restrict__ out, float sgn, const __grid_constant__ Maps maps) {
  extern __shared__ __align__(1024) unsigned char smem_raw[];
  const uint32_t sb = (uint32_t)__cvta_generic_to_shared(smem_raw);
  const int b = blockIdx.x;
  const int rank = b & 1, cl = b >> 1;
  const int sp = (cl & 1) | ((cl >> 2) & 2), m = ((cl >> 1) & 3) | ((cl >> 4) << 2);
  const int s = sp * 2 + rank;
  const int xrot = 9 - 2 * sp;
  if (threadIdx.x == 0) {
    mbar_init(sb + OFF_XFULL, 1);
    mbar_expect_tx(sb + OFF_XFULL, 16384);
    tma5d(sb + OFF_X + (xrot & 7) * 16384, &maps.x, 0, 0, m, sb + OFF_XFULL);
    tma5d(sb + OFF_X + (xrot & 7) * 16384 + 8192, &maps.x, 0, 8, m, sb + OFF_XFULL);
  }
  if (threadIdx.x == 128) {
    mbar_init(sb + OFF_FULL, 1);
    mbar_expect_tx(sb + OFF_FULL, 16384);
    tma4d(sb + OFF_RING, &maps.bb, 0, s * 8, sb + OFF_FULL);
  }
  const int warp = __shfl_sync(0xffffffffu, (int)(threadIdx.x >> 5), 0);
  const int lane0 = threadIdx.x & 31;

  if (elect_one()) {
    if (warp > 8) {
      map_prefetch(&maps.x + (warp - 9));
      mbar_init(sb + OFF_GBAR + 8 * (warp - 9), warp < 11 ? 64 : 96);
    }
    const uint32_t c = warp < 8 ? 1 : warp < 11 ? 8 : 4, bar = sb + OFF_XFULL + 16 * warp;
    if ((warp & 11) != 0) mbar_init(bar, c);
    mbar_init(bar + 8, c);
    asm volatile("fence.mbarrier_init.release.cluster;" ::: "memory");
  }
  __syncwarp();
  asm volatile("barrier.cluster.arrive.relaxed.aligned;" ::: "memory");

  if (warp < 8) {
    const int lane = __shfl_sync(0xffffffffu, lane0, lane0);
    const int wg = warp >> 2, w = warp & 3, q = lane & 3, gr = lane >> 2;
    uint32_t bv[28];
#pragma unroll
    for (int j = 0; j < 28; j++) bv[j] = __ldg(reinterpret_cast<const uint32_t*>(b1 + s * 224 + j * 8) + q);
    asm volatile("setmaxnreg.inc.sync.aligned.u32 224;");
    cluster_wait();
    auto release = [&](int slot) { if (lane == 0) mbar_arrive(sb + OFF_EMPTY + 8 * slot); };
    const uint32_t xw = sb + OFF_X + wg * 8192, fullb = sb + OFF_FULL;
    const uint32_t dxw = (xw & 0x3FFFF) >> 4, dring = ((sb + OFF_RING) & 0x3FFFF) >> 4;

    float uu[64], aa[48], ab[64];
    cplx lam, coef, l16, l32, l64, lq, pre, e[2];
    uint32_t sh16, mhi, ck = 0;
    const uint32_t dx0 = ((sb + OFF_X) & 0x3FFFF) >> 4;

    auto bias = [&](int c) {
#pragma unroll
      for (int j = c * 7; j < c * 7 + 7; j++) {
        pin(bv[j]);
        float* d = j < 12 ? aa + 4 * j : ab + 4 * (j - 12);
        d[0] = d[2] = __uint_as_float(bv[j] << sh16); d[1] = d[3] = __uint_as_float(bv[j] & mhi);
        pin(d[0]); pin(d[1]); pin(d[2]); pin(d[3]);
      }
    };
#pragma unroll
    for (int kb = 0; kb < 8; kb++) {
      const int slot = kb % NSLOT;
      mbar_wait(sb + OFF_XFULL + 8 * kb, 0);
      if (kb == 0) mbar_wait(fullb, 0);
      if (kb == 2) { sh16 = late16(sb + OFF_XFULL); mhi = 0xffffffffu << sh16; }
      if (kb == 4) {
        mbar_wait(sb + OFF_LBAR, 0);
        const uint4 v = lds_u4(sb + OFF_LC + (warp * 8 + gr) * 16);
        lam = cplx{__uint_as_float(v.x), __uint_as_float(v.y)};
        coef = cplx{__uint_as_float(v.z), __uint_as_float(v.w)};
      }
      wg_fence();
      const uint32_t dxa = dx0 + ((kb + xrot) & 7) * 1024;
#pragma unroll
      for (int kk = 0; kk < 4; kk++)
        wgmma_n128_ss<0, 0, DH128, DH128>(uu, dring + wg * 512, slot * 16384 + kk * 32, dxa, kk * 32, (kb | kk) != 0);
      wg_commit();
      if (kb > 0) { wg_wait<1>(); release((kb - 1) % NSLOT); }
      if (kb >= 2 && kb < 6) bias(kb - 2);
      if (kb == 6) {
        pin(lam.re); pin(lam.im);
        cplx t = cmul(lam, lam); t = cmul(t, t); t = cmul(t, t);
        l16 = cmul(t, t); l32 = cmul(l16, l16); l64 = cmul(l32, l32);
        const cplx a = (q & 1) ? l32 : cplx{1.f, 0.f}, c = (q & 2) ? l64 : cplx{1.f, 0.f};
        lq = cmul(cmul(a, c), coef);
        pin(lq.re); pin(lq.im);
      }
    }
    auto scale_u = [&](int c) {
#pragma unroll
      for (int n = 0; n < 8; n++) {
        const int i = (n >> 2) * 32 + c * 8 + (n & 2) * 2 + (n & 1);
        pin(uu[i]); pin(uu[i + 2]);
        const cplx v = cmul(coef, cplx{uu[i], uu[i + 2]});
        uu[i] = v.re; uu[i + 2] = v.im;
        pin(uu[i]); pin(uu[i + 2]);
      }
    };
#pragma unroll
    for (int kb = 0; kb < 8; kb++) {
      const int u = 8 + kb, slot = u % NSLOT;
      mbar_wait(fullb + 8 * slot, full_par(u));
      wg_fence();
      const uint32_t dxa = dxw + ((kb + xrot) & 7) * 1024;
#pragma unroll
      for (int kk = 0; kk < 4; kk++)
        wgmma_n96_ss<0, 1, DH128, DH64>(aa, dxa, kk * 32, dring, slot * 16384 + kk * 1024 + lbo(4096), 1);
      wg_commit();
      if (kb != 4) { wg_wait<1>(); release((u - 1) % NSLOT); }
      if (kb == 0) {
        reg_fence(uu);
#pragma unroll
        for (int h = 0; h < 2; h++) e[h] = cplx{uu[32 * h], uu[32 * h + 2]};
      }
      if (kb == 0 || kb == 2 || kb == 3) {
        const int t0 = kb ? 5 * kb - 4 : 1;
#pragma unroll
        for (int t = t0; t < t0 + 5; t++) {
#pragma unroll
          for (int h = 0; h < 2; h++) { const int i = 32 * h + 4 * (t >> 1) + (t & 1); e[h] = cfma(lam, e[h], cplx{uu[i], uu[i + 2]}); }
        }
#pragma unroll
        for (int h = 0; h < 2; h++) { pin(e[h].re); pin(e[h].im); }
      }
      if (kb == 4) {
        sched_fence(ck);
        e[1] = cfma(l16, e[0], e[1]);
        cplx y = {__shfl_up_sync(0xffffffffu, e[1].re, 1, 4), __shfl_up_sync(0xffffffffu, e[1].im, 1, 4)};
        if (q >= 1) e[1] = cfma(l32, y, e[1]);
        y = cplx{__shfl_up_sync(0xffffffffu, e[1].re, 2, 4), __shfl_up_sync(0xffffffffu, e[1].im, 2, 4)};
        if (q >= 2) e[1] = cfma(l64, y, e[1]);
        if (q == 3) {
          sts_f2(sb + OFF_CARRY + (warp * 8 + gr) * 8, e[1].re, e[1].im);
          mbar_arrive(sb + OFF_GBAR);
        }
        e[1] = cplx{__shfl_up_sync(0xffffffffu, e[1].re, 1, 4), __shfl_up_sync(0xffffffffu, e[1].im, 1, 4)};
        wg_wait<1>(); release((u - 1) % NSLOT);
      }
      if (kb == 5) {
        pre = (q >= 1) ? cmul(coef, e[1]) : cplx{0.f, 0.f};
        e[0] = cmul(coef, e[0]);
        pin(pre.re); pin(pre.im); pin(e[0].re); pin(e[0].im);
      }
      if (kb > 4) scale_u(kb - 5);
    }
    uint32_t H[56], hf[32];
    cplx hst[2];
    const uint32_t hst_addr = sb + OFF_X + (lane & 8) * 1024 + (warp * 8 + (lane & 7)) * 128 + (((lane >> 4) ^ (lane & 7)) << 4);
    const uint32_t him = (2 - rank) * 16384;
    uint32_t peer;
    asm volatile("mapa.shared::cluster.u32 %0, %1, %2;" : "=r"(peer) : "r"(sb), "r"(rank ^ 1));
    auto credit = [&]() { if (lane == 0) mbar_arrive_cl(peer + OFF_KBAR + wg * 8); };
    uint4 g2;
#pragma unroll
    for (int kb = 0; kb < 8; kb++) {
      const int u = 16 + kb, slot = u % NSLOT;
      mbar_wait(fullb + 8 * slot, full_par(u));
      wg_fence();
#pragma unroll
      for (int kk = 0; kk < 4; kk++)
        wgmma_n128_ss<0, 1, DH128, DH128>(ab, dxw, kb * 16384 + kk * 32, dring, slot * 16384 + kk * 2048 + lbo(8192), 1);
      wg_commit();
      if (kb == 0) scale_u(3);
      if (kb == 4) {
        mbar_wait(sb + OFF_CBAR, 0);
        const float2 c = lds_f2(sb + OFF_CARRY + (warp * 8 + gr) * 8);
        mbar_wait(sb + OFF_EMPTY, 1);
        hst[0] = cfma(lq, cplx{c.x, c.y}, pre);
        hst[1] = cfma(l16, hst[0], e[0]);
      }
      if (kb >= 4) g2 = lds_u4(sb + OFF_GT + (kb - 4) * 64 + q * 16);
      wg_wait<1>(); release((u - 1) % NSLOT);
      if (kb) sched_fence(ck);
      if (kb < 4) {
#pragma unroll
        for (int i = kb * 6; i < kb * 6 + 6; i++) {
          pin(aa[2 * i]); pin(aa[2 * i + 1]);
          H[i] = gelu2_pair(aa[2 * i], aa[2 * i + 1]);
          pin(H[i]);
        }
      } else {
        const int j0 = (kb - 4) * 2;
        uint32_t rr[4], ri[4];
#pragma unroll
        for (int jj = 0; jj < 2; jj++) {
          const int j = j0 + jj;
#pragma unroll
          for (int h = 0; h < 2; h++) {
            const int i = 32 * h + 4 * j;
            const uint32_t g = jj ? (h ? g2.w : g2.z) : (h ? g2.y : g2.x);
            const cplx h0 = cfma(lam, hst[h], cplx{uu[i], uu[i + 2]});
            hst[h] = cfma(lam, h0, cplx{uu[i + 1], uu[i + 3]});
            rr[jj * 2 + h] = bf2_mul(pack_bf16(h0.re, hst[h].re), g);
            ri[jj * 2 + h] = bf2_mul(pack_bf16(h0.im, hst[h].im), g);
          }
        }
        const uint32_t a = hst_addr ^ (j0 << 4);
        asm volatile("stmatrix.sync.aligned.m8n8.x4.shared.b16 [%0], {%1,%2,%3,%4};" ::"r"(a), "r"(rr[0]), "r"(rr[1]), "r"(rr[2]), "r"(rr[3]) : "memory");
        asm volatile("stmatrix.sync.aligned.m8n8.x4.shared.b16 [%0], {%1,%2,%3,%4};" ::"r"(a + him), "r"(ri[0]), "r"(ri[1]), "r"(ri[2]), "r"(ri[3]) : "memory");
        if (kb == 7) { __syncwarp(); if (q == 3) mbar_arrive(sb + OFF_GBAR); }
      }
    }

    uint4* const psend = g_part + (size_t)(m * 8 + rank) * 3072 + warp * 128 + lane;
    const uint4* const precv = g_part + (size_t)(m * 8 + s) * 3072 + warp * 128 + lane;
    const uint32_t pbuf = OFF_X + warp * 2048 + lane * 16;
    float o[32], fin[32], fs[2];
    uint32_t r0[16], pt[16], sum[16], tag;
    auto recv_issue = [&](uint32_t (&r)[16], int k) {
#pragma unroll
      for (int i = 0; i < 4; i++) ld_b128(precv + k * 1024 + i * 32, r[4 * i], r[4 * i + 1], r[4 * i + 2], r[4 * i + 3]);
    };
    auto stale = [&](uint32_t (&r)[16]) {
      uint32_t r_;
#pragma unroll
      for (int i = 0; i < 16; i += 4) asm("lop3.b32 %0, %0, %1, 1, 0x78;" : "+r"(r[i]) : "r"(tag));
      asm volatile("{.reg .pred p; .reg .b32 t; lop3.b32 t, %1, %2, %3, 0xfe; lop3.b32 t, t, %4, 1, 0xa8; setp.ne.u32 p, t, 0; vote.sync.any.pred p, p, 0xffffffff; selp.u32 %0, 1, 0, p;}"
                   : "=r"(r_) : "r"(r[0]), "r"(r[4]), "r"(r[8]), "r"(r[12]));
      return r_ != 0;
    };
    auto recv_check = [&](uint32_t (&r)[16], int k) {
      if (__builtin_expect(stale(r), 0)) {
        int tries = 0;
#pragma unroll 1
        do { recv_issue(r, k); } while (stale(r) && ++tries < 200000);
      }
    };
    auto gelu_b = [&](int i0, int i1) {
#pragma unroll
      for (int i = i0; i < i1; i++) {
        pin(ab[2 * i]); pin(ab[2 * i + 1]);
        H[24 + i] = gelu2_pair(ab[2 * i], ab[2 * i + 1]);
        pin(H[24 + i]);
      }
    };
    auto mma = [&](float (&d)[32], int p, int k0, int k1, int acc) {
      const uint32_t wo = stage_off(p);
      wg_fence();
#pragma unroll
      for (int k = k0; k < k1; k++) {
        if (k >= 6 && k < 14) {
          const int kk = k - 6;
          if (kk < 4) wgmma_n64_rs<0, DH128, 1>(d, hf[4 * kk], hf[4 * kk + 1], hf[4 * kk + 2], hf[4 * kk + 3], dx0, wo + 14336 + kk * 32, 1);
          else wgmma_n64_rs<0, DH128, -1>(d, hf[4 * kk], hf[4 * kk + 1], hf[4 * kk + 2], hf[4 * kk + 3], dx0, wo + 22528 + (kk - 4) * 32, 1);
        } else {
          const int kk = k < 6 ? k : k - 8;
          wgmma_n64_rs<1, DH128>(d, H[4 * kk], H[4 * kk + 1], H[4 * kk + 2], H[4 * kk + 3], dx0, wo + (kk / 7) * 30720 + (kk % 7) * 2048, k != 0 || acc);
        }
      }
      wg_commit();
    };
    auto recv_peer = [&](int k) {
      mbar_wait(sb + OFF_RBAR + wg * 8, k & 1);
#pragma unroll
      for (int i = 0; i < 4; i++) { const uint4 v = lds_u4(sb + pbuf + i * 512); pt[4 * i] = v.x; pt[4 * i + 1] = v.y; pt[4 * i + 2] = v.z; pt[4 * i + 3] = v.w; }
    };
#pragma unroll
    for (int p = 0; p < 8; p++) {
      if (p == 0) {
        mbar_wait(fullb, full_par(24));
        mma(o, 0, 0, 4, 0);
        mbar_wait(fullb + 8, full_par(25));
        wg_wait<1>(); release(5);
        mbar_wait(sb + OFF_GBAR, 1);
        {
          const uint32_t ha = xw + ((lane >> 4) * 8 + (lane & 7)) * 128 + (((2 * w + ((lane >> 3) & 1)) ^ (lane & 7)) << 4);
#pragma unroll
          for (int kk = 0; kk < 8; kk++)
            asm volatile("ldmatrix.sync.aligned.m8n8.x4.trans.shared.b16 {%0,%1,%2,%3}, [%4];" : "=r"(hf[4 * kk]), "=r"(hf[4 * kk + 1]), "=r"(hf[4 * kk + 2]), "=r"(hf[4 * kk + 3])
                         : "r"(ha + (kk >> 2) * him + (kk & 3) * 2048) : "memory");
        }
        gelu_b(0, 6);
        mma(o, 0, 4, 8, 0);
        gelu_b(6, 12);
        mma(o, 0, 8, 12, 0);
        credit();
        gelu_b(12, 18);
        mbar_wait(fullb + 16, full_par(26));
        mma(o, 0, 12, 15, 0);
        gelu_b(18, 24);
        mma(o, 0, 15, 18, 0);
        gelu_b(24, 32);
        if (wg == 1) bar_sync(4, 256);
        mma(o, 0, 18, 22, 0);
      } else {
        bar_sync(3 + wg, 256);
        if (p < 7) mma(o, p, 0, 22, 0); else mma(fin, p, 0, 22, 1);
      }
      if (p < 7 || wg == 0) bar_arrive(4 - wg, 256);
      if (p < 7) mbar_wait(sb + OFF_XFULL + 8 * (p + 1), 1);
      if ((p & 1) == 0) {
        if (w == 0 && lane == 0) mbar_expect_tx(sb + OFF_RBAR + wg * 8, 8192);
        if (p == 6) {
          mbar_wait(sb + OFF_EMPTY + 32, 0);
          tag = lds_u(sb + OFF_EPOCH);
          recv_check(sum, 0); recv_check(r0, 1);
#pragma unroll
          for (int i = 0; i < 16; i++) sum[i] = bf2_add(sum[i], r0[i]);
        }
        mbar_wait(sb + OFF_KBAR + wg * 8, (p >> 1) & 1);
      } else {
        if (p == 1 || p == 7) tag = lds_u(sb + OFF_EPOCH);
        recv_peer(p >> 1);
        if (p == 7) {
          recv_check(r0, 2);
#pragma unroll
          for (int i = 0; i < 16; i++) { sum[i] = bf2_add(sum[i], bf2_add(r0[i], pt[i])); pin(sum[i]); }
          sched_fence(ck);
        }
      }
      if (p == 4) {
        mbar_wait(sb + OFF_LBAR, 1);
#pragma unroll
        for (int j = 0; j < 8; j++) {
          const uint4 v = lds_u4(sb + pbuf + 16384 + (j >> 2) * 16384 + (j & 3) * 512);
          fin[4 * j] = __uint_as_float(v.x); fin[4 * j + 1] = __uint_as_float(v.y); fin[4 * j + 2] = __uint_as_float(v.z); fin[4 * j + 3] = __uint_as_float(v.w);
        }
        recv_issue(sum, 0);
      }
      wg_wait<0>();
      if (p < 5) release(p);
      if (p < 7) reg_fence(o); else reg_fence(fin);
      if ((p & 1) == 0) {
        if (p == 6) recv_issue(r0, 2);
#pragma unroll
        for (int i = 0; i < 4; i++)
          asm volatile("st.async.shared::cluster.mbarrier::complete_tx::bytes.v4.b32 [%0], {%1,%2,%3,%4}, [%5];" ::"r"(peer + pbuf + i * 512),
                       "r"(pack_bf16(o[8 * i], o[8 * i + 1])), "r"(pack_bf16(o[8 * i + 2], o[8 * i + 3])), "r"(pack_bf16(o[8 * i + 4], o[8 * i + 5])),
                       "r"(pack_bf16(o[8 * i + 6], o[8 * i + 7])), "r"(peer + OFF_RBAR + wg * 8) : "memory");
      } else if (p < 7) {
        const int k = p >> 1;
#pragma unroll
        for (int i = 0; i < 4; i++) {
#pragma unroll
          for (int c = 4 * i; c < 4 * i + 4; c++) pt[c] = bf2_add(pt[c], pack_bf16(o[2 * c], o[2 * c + 1]));
          asm("lop3.b32 %0, %0, 1, %1, 0xb8;" : "+r"(pt[4 * i]) : "r"(tag));
          st_b128(psend + (((sp + 1 + k) & 3) * 6 + k) * 1024 + i * 32, pt[4 * i], pt[4 * i + 1], pt[4 * i + 2], pt[4 * i + 3]);
        }
        __syncwarp();
        credit();
        if (p == 5) recv_issue(r0, 1);
      }
      if (p == 2) {
#pragma unroll
        for (int h = 0; h < 2; h++) { fs[h] = __fdividef(2.f, 4.f + bf_lo(lds_h(sb + OFF_GS + (wg * 64 + w * 16 + gr + 8 * h) * 2))); pin(fs[h]); }
      }
    }
    {
      const uint32_t tb = sb + OFF_X + stage_off(0) + warp * 4096;
      const uint32_t ta = tb + gr * 256 + ((gr & 3) << 5) + q * 8;
      const uint32_t la = tb + (lane >> 3) * 256 + (((lane & 7) << 4) ^ ((lane >> 3) << 5));
      float* op = out + (size_t)(m * 128 + (lane >> 4) * 32 + warp * 4 + ((lane >> 3) & 1)) * DM + s * 64 + (lane & 7) * 4;
#pragma unroll
      for (int qt = 0; qt < 4; qt++) {
        const int h = qt & 1, ch = qt >> 1;
#pragma unroll
        for (int j = 0; j < 4; j++) {
          const int i = ch * 8 + j * 2 + h;
          sts_f2((ta ^ (j << 5)) + h * 2048 + ch * 128, (fin[2 * i] + bf_lo(sum[i])) * fs[h], (fin[2 * i + 1] + bf_hi(sum[i])) * fs[h]);
        }
        __syncwarp();
#pragma unroll
        for (int r = 0; r < 2; r++)
          *reinterpret_cast<uint4*>(op + (r * 64 + h * 2) * DM + ch * 32) = lds_u4(la + (h * 2 + r) * 1024 + ch * 128);
      }
      sts_u(sb + OFF_EPOCH + 4, ck);
      if (warp == 4 && lane == 0) g_epoch[b] = tag;
    }
  } else {
    const int lane = __shfl_sync(0xffffffffu, lane0, lane0);
    asm volatile("setmaxnreg.dec.sync.aligned.u32 56;");
    int wsel = warp;
    asm("" : "+r"(wsel));
    if (wsel > 8) {
      if (warp != 11) {
        const uint4* gwp = reinterpret_cast<const uint4*>(gate_w) + (lane & 7);
        uint4 gw[4];
        const int t = (warp - 9) * 32 + lane;
        unsigned par;
        asm volatile("ld.relaxed.gpu.global.u32 %0, [%1];" : "=r"(par) : "l"(g_epoch + b) : "memory");
        const float pr = bf_ld(lam_re + s * 64 + t), pi = sgn * bf_ld(lam_im + s * 64 + t), pd = bf_ld(log_dt + s * 64 + t);
#pragma unroll
        for (int i = 0; i < 4; i++) gw[i] = __ldg(gwp + i * 8);
        cluster_wait();
        par = __shfl_sync(0xffffffffu, (par + 1) & 1, 0);
        cplx l128 = make_lam(pr, pi, pd);
        {
          const float inv = __fdividef(sgn, fmaf(pr, pr, pi * pi));
          const cplx cf = cmul(cplx{l128.re - 1.f, l128.im}, cplx{pr * inv, -pi * inv});
          sts_f4(sb + OFF_LC + t * 16, l128.re, l128.im, cf.re, cf.im);
          mbar_arrive(sb + OFF_LBAR);
        }
#pragma unroll
        for (int i = 0; i < 7; i++) l128 = cmul(l128, l128);
        pin(l128.re); pin(l128.im);
        gate_rows(sb, lane, xrot, s * 16 + (warp - 9) * 8, gw, gwp, g_gate + m * 128, par);
        uint32_t vr[15], vi[15];
#pragma unroll
        for (int i = 0; i < 15; i++) { vr[i] = par; vi[i] = 0; pin(vr[i]); pin(vi[i]); }
        mbar_wait(sb + OFF_GBAR, 0);
        float2* eb = g_end + s * 1024 + t;
        {
          const float2 e = lds_f2(sb + OFF_CARRY + t * 8);
          const unsigned long long v = ((unsigned long long)__float_as_uint(e.y) << 32) | ((__float_as_uint(e.x) & ~1u) | par);
          asm volatile("st.relaxed.gpu.global.b64 [%0], %1;" ::"l"(eb + m * 64), "l"(v) : "memory");
        }
        __nanosleep(400);
        const float2* e15 = eb + (m - 15) * 64;
        int tries = 0;
        bool bad;
#pragma unroll 1
        do {
#pragma unroll
          for (int i = 0; i < 15; i++)
            asm volatile("{.reg .pred p; .reg .b64 v; mov.b64 v, {%0,%1}; setp.ge.s32 p, %3, %4; @p ld.relaxed.gpu.global.b64 v, [%2]; mov.b64 {%0,%1}, v;}"
                         : "+r"(vr[i]), "+r"(vi[i]) : "l"(e15 + i * 64), "r"(m), "r"(15 - i) : "memory");
          uint32_t x = vr[0] ^ par;
#pragma unroll
          for (int i = 1; i < 15; i++) asm("lop3.b32 %0, %0, %1, %2, 0xf6;" : "+r"(x) : "r"(vr[i]), "r"(par));
          bad = __any_sync(0xffffffffu, x & 1);
        } while (bad && ++tries < 200000);
        cplx S = {__uint_as_float(vr[0] ^ par), __uint_as_float(vi[0])};
#pragma unroll
        for (int i = 1; i < 15; i++) S = cfma(l128, S, cplx{__uint_as_float(vr[i] ^ par), __uint_as_float(vi[i])});
        sts_f2(sb + OFF_CARRY + t * 8, S.re, S.im);
        mbar_arrive(sb + OFF_CBAR);
        mbar_wait(sb + OFF_CBAR, 0);
        const int gr = lane >> 2, q = lane & 3;
        float2 db[8];
#pragma unroll
        for (int j = 0; j < 8; j++) db[j] = lds_f2(sb + OFF_DB + j * 32 + q * 8);
        mbar_wait(sb + OFF_XFULL + 16, 1);
        mbar_wait(sb + OFF_EMPTY, 0);
#pragma unroll 1
        for (int cw = warp - 9; cw < 8; cw += 2) {
          const float r0 = 0.5f * bf_lo(lds_h(sb + OFF_GS + (cw * 16 + gr) * 2)), r1 = 0.5f * bf_lo(lds_h(sb + OFF_GS + (cw * 16 + gr) * 2 + 16));
          const uint32_t xa = sb + OFF_X + (1 + rank) * 16384 + (cw * 16 + (lane & 15)) * 128 + (((lane >> 4) ^ (lane & 7)) << 4);
          uint32_t xv[16];
#pragma unroll
          for (int i = 0; i < 4; i++)
            asm volatile("ldmatrix.sync.aligned.m8n8.x4.shared.b16 {%0,%1,%2,%3}, [%4];" : "=r"(xv[4 * i]), "=r"(xv[4 * i + 1]), "=r"(xv[4 * i + 2]), "=r"(xv[4 * i + 3])
                         : "r"(xa ^ (i << 5)) : "memory");
          __syncwarp();
#pragma unroll
          for (int j = 0; j < 8; j++) {
            const uint32_t x0 = bf2_mul(xv[2 * j], __float_as_uint(db[j].x)), x1 = bf2_mul(xv[2 * j + 1], __float_as_uint(db[j].x));
            pin(db[j].y);
            const float bl = bf_lo(__float_as_uint(db[j].y)), bh = bf_hi(__float_as_uint(db[j].y));
            sts_f4(sb + OFF_X + 16384 + (j >> 2) * 16384 + cw * 2048 + (j & 3) * 512 + lane * 16, fmaf(bf_lo(x0), r0, bl), fmaf(bf_hi(x0), r0, bh),
                   fmaf(bf_lo(x1), r1, bl), fmaf(bf_hi(x1), r1, bh));
          }
        }
        mbar_arrive(sb + OFF_LBAR);
      } else {
        unsigned par;
        asm volatile("ld.relaxed.gpu.global.u32 %0, [%1];" : "=r"(par) : "l"(g_epoch + b) : "memory");
        const uint32_t dk = __ldg(reinterpret_cast<const uint32_t*>(dskip + s * 64) + lane), bb = __ldg(reinterpret_cast<const uint32_t*>(b2 + s * 64) + lane);
        cluster_wait();
        if (lane == 0) sts_u(sb + OFF_EPOCH, par + 1);
        par = (par + 1) & 1;
        mbar_wait(sb + OFF_GBAR, 0);
        sts_u2(sb + OFF_DB + lane * 8, dk, bf2_add(bb, bb));
        uint32_t g0, g1, g2, g3;
        int tries = 0;
#pragma unroll 1
        do {
          asm volatile("ld.relaxed.gpu.global.v4.u32 {%0,%1,%2,%3}, [%4];" : "=r"(g0), "=r"(g1), "=r"(g2), "=r"(g3) : "l"(g_gate + m * 128 + lane * 4) : "memory");
          g0 ^= par; g1 ^= par; g2 ^= par; g3 ^= par;
        } while (((g0 | g1 | g2 | g3) & 1) && ++tries < 200000);
        const uint32_t p01 = pack_bf16(__uint_as_float(g0), __uint_as_float(g1)), p23 = pack_bf16(__uint_as_float(g2), __uint_as_float(g3));
        sts_u2(sb + OFF_GS + lane * 8, p01, p23);
        const uint32_t gt = sb + OFF_GT + ((lane >> 2) & 3) * 64 + (lane & 1) * 32 + (lane & 2) * 4 + (lane >> 4) * 4;
        sts_u(gt, p01);
        sts_u(gt + 16, p23);
        mbar_arrive(sb + OFF_CBAR);
      }
    } else {
      cluster_wait();
      if (elect_one()) {
        const uint32_t t0 = clock();
#pragma unroll 1
        for (int u = 1; u < 8; u++) {
          while ((uint32_t)clock() - t0 < 200 + (u - 1) * 480) {}
          const uint32_t fb = sb + OFF_XFULL + 8 * u;
          mbar_expect_tx(fb, 32768);
          tma5d_mc(sb + OFF_X + ((u + xrot) & 7) * 16384 + rank * 8192, &maps.x, u * 64, rank * 8, m, fb);
          const int sl = u < 6 ? u : u - 6;
          if (u >= 6) mbar_wait(sb + OFF_EMPTY + 8 * sl, 0);
          tma4d(sb + OFF_RING + sl * 16384, &maps.bb, u * 64, s * 8, fb);
        }
        int slot = 2; uint32_t ph = 0;
#pragma unroll 1
        for (int u = 8; u < 24; u++) {
          const uint32_t fb = sb + OFF_FULL + 8 * slot, dst = sb + OFF_RING + slot * 16384;
          mbar_wait(sb + OFF_EMPTY + 8 * slot, ph);
          if (u < 16) {
            mbar_expect_tx(fb, 12288);
            tma3d(dst, &maps.w1b, 0, (u - 8) * 64, s * 7, fb);
            if (u < 12) map_prefetch(&maps.w1a + (u - 8));
          } else {
            mbar_expect_tx(fb, 16384);
            tma2d(dst, &maps.w1a, s * 224 + 96, ((u - xrot) & 7) * 64, fb);
            tma2d(dst + 8192, &maps.w1a, s * 224 + 160, ((u - xrot) & 7) * 64, fb);
          }
          if (++slot == NSLOT) { slot = 0; ph ^= 1; }
        }
#pragma unroll 1
        for (int j = 0; j < 3; j++) {
          const uint32_t fb = sb + OFF_FULL + 8 * j, dst = sb + OFF_X + stage_off(0);
          const int c = ((sp + 1) & 3) * 128 + ((rank ^ 1) << 6);
          mbar_wait(sb + OFF_EMPTY + 8 + 8 * j, 1);
          mbar_expect_tx(fb, j == 1 ? 16384 : 14336);
          if (j == 1) {
            tma2d(dst + 14336, &maps.cre, s * 64, c, fb);
            tma2d(dst + 22528, &maps.cim, s * 64, c, fb);
          } else {
            tma2d(dst + j * 15360, &maps.w2, c, s * 224 + j * 56, fb);
          }
        }
#pragma unroll 1
        for (int p = 1; p < 8; p++) {
          const int c = ((sp + 1 + (p >> 1)) & 3) * 128 + (((rank ^ p ^ 1) & 1) << 6);
          const uint32_t fb = sb + OFF_XFULL + 8 * p, dst = sb + OFF_X + stage_off(p);
          if (p == 2 || p > 3) mbar_wait(sb + OFF_EMPTY + (p == 2 ? 40 : (p - 4) * 8), p == 2);
          mbar_expect_tx(fb, 45056);
          tma2d(dst, &maps.w2, c, s * 224, fb);
          tma2d(dst + 14336, &maps.cre, s * 64, c, fb);
          tma2d(dst + 22528, &maps.cim, s * 64, c, fb);
          tma2d(dst + 30720, &maps.w2, c, s * 224 + 112, fb);
        }
      }
    }
  }
}

typedef CUresult (*EncFn)(CUtensorMap*, CUtensorMapDataType, cuuint32_t, void*, const cuuint64_t*, const cuuint64_t*, const cuuint32_t*,
                          const cuuint32_t*, CUtensorMapInterleave, CUtensorMapSwizzle, CUtensorMapL2promotion, CUtensorMapFloatOOBfill);

void encode(EncFn f, CUtensorMap* mp, const void* p, int rank, const cuuint64_t* dims, const cuuint64_t* strides, const cuuint32_t* box, CUtensorMapSwizzle sw) {
  cuuint32_t es[5] = {1, 1, 1, 1, 1};
  f(mp, CU_TENSOR_MAP_DATA_TYPE_BFLOAT16, rank, const_cast<void*>(p), dims, strides, box, es, CU_TENSOR_MAP_INTERLEAVE_NONE, sw,
    CU_TENSOR_MAP_L2_PROMOTION_L2_128B, CU_TENSOR_MAP_FLOAT_OOB_FILL_NONE);
}

}

extern "C" void kernel_launch(void* const* d_in, const int* in_sizes, int n_in, void* d_out, int out_size) {
  typedef const __nv_bfloat16* bp;
  bp x = (bp)d_in[0], lre = (bp)d_in[1], lim = (bp)d_in[2], bre = (bp)d_in[3], bim = (bp)d_in[4], cre = (bp)d_in[5], cim = (bp)d_in[6],
     ldt = (bp)d_in[7], dsk = (bp)d_in[8], w1 = (bp)d_in[10], b1 = (bp)d_in[11], w2 = (bp)d_in[12], b2 = (bp)d_in[13], gw = (bp)d_in[14];
  static EncFn enc = nullptr;
  if (!enc) {
    void* f = nullptr;
    cudaDriverEntryPointQueryResult qr;
    cudaGetDriverEntryPoint("cuTensorMapEncodeTiled", &f, cudaEnableDefault, &qr);
    enc = (EncFn)f;
    cudaFuncSetAttribute(fused_kernel, cudaFuncAttributeMaxDynamicSharedMemorySize, SMEM_BYTES);
  }
  Maps maps;
  const bool swap = bim < bre;
  {
    cuuint64_t d[5] = {DM, 2, 4, 16, SEQ / 128}, st[4] = {DM * 2, 32 * DM * 2, 2 * DM * 2, 128 * DM * 2};
    cuuint32_t bx[5] = {64, 2, 4, 8, 1};
    encode(enc, &maps.x, x, 5, d, st, bx, CU_TENSOR_MAP_SWIZZLE_128B);
  }
  {
    cuuint64_t d[2] = {DM, DM}, st[1] = {DM * 2};
    cuuint32_t bx[2] = {64, 64};
    encode(enc, &maps.cre, swap ? cim : cre, 2, d, st, bx, CU_TENSOR_MAP_SWIZZLE_128B);
    encode(enc, &maps.cim, swap ? cre : cim, 2, d, st, bx, CU_TENSOR_MAP_SWIZZLE_128B);
    cuuint64_t d4[4] = {DM, 8, 2, DM / 8}, st4[3] = {DM * 2, (cuuint64_t)(swap ? bre - bim : bim - bre) * 2, 8 * DM * 2};
    cuuint32_t bx4[4] = {64, 8, 2, 8};
    encode(enc, &maps.bb, swap ? bim : bre, 4, d4, st4, bx4, CU_TENSOR_MAP_SWIZZLE_128B);
  }
  {
    cuuint64_t d[2] = {FF, DM}, st[1] = {FF * 2};
    cuuint32_t bx[2] = {64, 64};
    encode(enc, &maps.w1a, w1, 2, d, st, bx, CU_TENSOR_MAP_SWIZZLE_128B);
    cuuint64_t d3[3] = {32, DM, FF / 32}, st3[2] = {FF * 2, 64};
    cuuint32_t bx3[3] = {32, 64, 3};
    encode(enc, &maps.w1b, w1, 3, d3, st3, bx3, CU_TENSOR_MAP_SWIZZLE_64B);
  }
  {
    cuuint64_t d[2] = {DM, FF}, st[1] = {DM * 2};
    cuuint32_t bx[2] = {64, 112};
    encode(enc, &maps.w2, w2, 2, d, st, bx, CU_TENSOR_MAP_SWIZZLE_128B);
  }
  fused_kernel<<<128, 384, SMEM_BYTES>>>(lre, lim, ldt, dsk, b1, b2, gw, (float*)d_out, swap ? -1.f : 1.f, maps);
}
```

```cpp
#include <cuda_runtime.h>
#include <cuda_bf16.h>
#include <cuda.h>
#include <stdint.h>

namespace {

constexpr int SEQ = 2048, DM = 512, FF = 1792;
constexpr int NSLOT = 6;
constexpr uint32_t OFF_X = 0, OFF_RING = 131072, OFF_MISC = 229376;
constexpr uint32_t OFF_XFULL = OFF_MISC, OFF_FULL = OFF_XFULL + 64, OFF_RBAR = OFF_FULL + 48, OFF_EMPTY = OFF_RBAR + 16, OFF_KBAR = OFF_EMPTY + 48,
                   OFF_GBAR = OFF_KBAR + 16, OFF_LBAR = OFF_GBAR + 8, OFF_CBAR = OFF_LBAR + 8, OFF_EPOCH = OFF_CBAR + 8;
constexpr uint32_t OFF_LC = OFF_MISC + 256;
constexpr uint32_t OFF_GS = OFF_LC;
constexpr uint32_t OFF_GT = OFF_LC + 256;
constexpr uint32_t OFF_DB = OFF_LC + 512;
constexpr uint32_t OFF_CARRY = OFF_LC + 1024;
constexpr uint32_t SMEM_BYTES = OFF_CARRY + 512;
static_assert(SMEM_BYTES <= 232448, "smem");

struct Maps { CUtensorMap x, bb, w1b, w1a, w2, cre, cim; };
__host__ __device__ constexpr uint32_t stage_off(int p) { return 49152 + 45056 * (((p >> 1) & 1) + 2 * (p & 1)); }
__host__ __device__ constexpr uint32_t full_par(int u) { return ((u - 8) / 6 + (u % 6 == 0)) & 1; }

__device__ uint4 g_part[16 * 8 * 3 * 1024];
__device__ float2 g_end[8 * 16 * 64];
__device__ unsigned g_gate[SEQ];
__device__ unsigned g_epoch[128];

__device__ __forceinline__ void mbar_init(uint32_t bar, uint32_t cnt) { asm volatile("mbarrier.init.shared::cta.b64 [%0], %1;" ::"r"(bar), "r"(cnt)); }
__device__ __forceinline__ void mbar_expect_tx(uint32_t bar, uint32_t bytes) { asm volatile("mbarrier.arrive.expect_tx.shared::cta.b64 _, [%0], %1;" ::"r"(bar), "r"(bytes) : "memory"); }
__device__ __forceinline__ void mbar_arrive(uint32_t bar) { asm volatile("mbarrier.arrive.shared::cta.b64 _, [%0];" ::"r"(bar) : "memory"); }
__device__ __forceinline__ void mbar_arrive_cl(uint32_t cbar) { asm volatile("mbarrier.arrive.shared::cluster.b64 _, [%0];" ::"r"(cbar) : "memory"); }
__device__ __forceinline__ void mbar_wait(uint32_t bar, uint32_t parity) {
  asm volatile(
      "{\n.reg .pred p;\n.reg .u32 c;\n"
      "mbarrier.try_wait.parity.shared::cta.b64 p, [%0], %1;\n"
      "@p bra.uni LAB_DONE;\n"
      "mov.u32 c, 0;\n"
      "LAB_WAIT:\n"
      "mbarrier.try_wait.parity.shared::cta.b64 p, [%0], %1;\n"
      "@p bra.uni LAB_DONE;\n"
      "add.u32 c, c, 1;\nsetp.lt.u32 p, c, 200000;\n@p bra.uni LAB_WAIT;\n"
      "LAB_DONE:\n}" ::"r"(bar), "r"(parity) : "memory");
}
__device__ __forceinline__ void tma2d(uint32_t dst, const CUtensorMap* m, int c0, int c1, uint32_t bar) {
  asm volatile("cp.async.bulk.tensor.2d.shared::cluster.global.mbarrier::complete_tx::bytes [%0], [%1, {%3,%4}], [%2];"
               ::"r"(dst), "l"(m), "r"(bar), "r"(c0), "r"(c1) : "memory");
}
__device__ __forceinline__ void tma3d(uint32_t dst, const CUtensorMap* m, int c0, int c1, int c2, uint32_t bar) {
  asm volatile("cp.async.bulk.tensor.3d.shared::cluster.global.mbarrier::complete_tx::bytes [%0], [%1, {%3,%4,%5}], [%2];"
               ::"r"(dst), "l"(m), "r"(bar), "r"(c0), "r"(c1), "r"(c2) : "memory");
}
__device__ __forceinline__ void tma4d(uint32_t dst, const CUtensorMap* m, int c0, int c3, uint32_t bar) {
  asm volatile("cp.async.bulk.tensor.4d.shared::cluster.global.mbarrier::complete_tx::bytes [%0], [%1, {%3,%5,%5,%4}], [%2];"
               ::"r"(dst), "l"(m), "r"(bar), "r"(c0), "r"(c3), "r"(0) : "memory");
}
__device__ __forceinline__ void tma5d(uint32_t dst, const CUtensorMap* m, int c0, int c3, int c4, uint32_t bar) {
  asm volatile("cp.async.bulk.tensor.5d.shared::cluster.global.mbarrier::complete_tx::bytes [%0], [%1, {%3,%6,%6,%4,%5}], [%2];"
               ::"r"(dst), "l"(m), "r"(bar), "r"(c0), "r"(c3), "r"(c4), "r"(0) : "memory");
}
__device__ __forceinline__ void tma5d_mc(uint32_t dst, const CUtensorMap* m, int c0, int c3, int c4, uint32_t bar) {
  asm volatile("cp.async.bulk.tensor.5d.shared::cluster.global.mbarrier::complete_tx::bytes.multicast::cluster [%0], [%1, {%3,%6,%6,%4,%5}], [%2], %7;"
               ::"r"(dst), "l"(m), "r"(bar), "r"(c0), "r"(c3), "r"(c4), "r"(0), "h"((uint16_t)3) : "memory");
}
__device__ __forceinline__ void map_prefetch(const CUtensorMap* m) { asm volatile("prefetch.tensormap [%0];" ::"l"(m) : "memory"); }
__device__ __forceinline__ bool elect_one() {
  uint32_t pred;
  asm volatile("{.reg .pred P; elect.sync _|P, 0xffffffff; selp.u32 %0, 1, 0, P;}" : "=r"(pred));
  return pred != 0;
}
__device__ __forceinline__ void cluster_wait() { asm volatile("barrier.cluster.wait.aligned;" ::: "memory"); }
__device__ __forceinline__ void wg_fence() { asm volatile("wgmma.fence.sync.aligned;" ::: "memory"); }
__device__ __forceinline__ void wg_commit() { asm volatile("wgmma.commit_group.sync.aligned;" ::: "memory"); }
template <int N> __device__ __forceinline__ void wg_wait() { asm volatile("wgmma.wait_group.sync.aligned %0;" ::"n"(N) : "memory"); }
__device__ __forceinline__ void pin(float& a) { asm volatile("" : "+f"(a)::"memory"); }
__device__ __forceinline__ void pin(uint32_t& a) { asm volatile("" : "+r"(a)::"memory"); }
template <int N> __device__ __forceinline__ void reg_fence(float (&d)[N]) {
#pragma unroll
  for (int i = 0; i < N; i++) pin(d[i]);
}
__device__ __forceinline__ void sched_fence(uint32_t& ck) { asm volatile("{.reg .b32 c; mov.u32 c, %%clock; xor.b32 %0, %0, c;}" : "+r"(ck)::"memory"); }
__device__ __forceinline__ void bar_sync(int id, int n) { asm volatile("bar.sync %0, %1;" ::"r"(id), "r"(n) : "memory"); }
__device__ __forceinline__ void bar_arrive(int id, int n) { asm volatile("bar.arrive %0, %1;" ::"r"(id), "r"(n) : "memory"); }
constexpr uint32_t DH128 = (1024 >> 4) | (1u << 30), DH64 = (512 >> 4) | (2u << 30);
__host__ __device__ constexpr uint32_t lbo(uint32_t bytes) { return (bytes >> 4) << 20; }
__device__ __forceinline__ uint32_t pack_bf16(float lo, float hi) { uint32_t r; asm("cvt.rn.bf16x2.f32 %0, %1, %2;" : "=r"(r) : "f"(hi), "f"(lo)); return r; }
__device__ __forceinline__ float bf_lo(uint32_t v) { return __uint_as_float(v << 16); }
__device__ __forceinline__ float bf_hi(uint32_t v) { return __uint_as_float(v & 0xffff0000u); }
__device__ __forceinline__ float bf_ld(const __nv_bfloat16* p) { return __bfloat162float(__ldg(p)); }
__device__ __forceinline__ uint32_t late16(uint32_t bar) {
  uint32_t r;
  asm volatile("{.reg .pred p; mbarrier.test_wait.parity.shared::cta.b64 p, [%1], 0; selp.u32 %0, 16, 0, p;}" : "=r"(r) : "r"(bar) : "memory");
  return r;
}
__device__ __forceinline__ float2 lds_f2(uint32_t a) { float2 v; asm volatile("ld.shared.v2.f32 {%0,%1}, [%2];" : "=f"(v.x), "=f"(v.y) : "r"(a)); return v; }
__device__ __forceinline__ uint32_t lds_h(uint32_t a) { uint32_t v; asm volatile("ld.shared.u16 %0, [%1];" : "=r"(v) : "r"(a)); return v; }
__device__ __forceinline__ uint32_t lds_u(uint32_t a) { uint32_t v; asm volatile("ld.shared.u32 %0, [%1];" : "=r"(v) : "r"(a)); return v; }
__device__ __forceinline__ uint4 lds_u4(uint32_t a) { uint4 v; asm volatile("ld.shared.v4.u32 {%0,%1,%2,%3}, [%4];" : "=r"(v.x), "=r"(v.y), "=r"(v.z), "=r"(v.w) : "r"(a)); return v; }
__device__ __forceinline__ void sts_u(uint32_t a, uint32_t v) { asm volatile("st.shared.u32 [%0], %1;" ::"r"(a), "r"(v) : "memory"); }
__device__ __forceinline__ void sts_u2(uint32_t a, uint32_t x, uint32_t y) { asm volatile("st.shared.v2.u32 [%0], {%1,%2};" ::"r"(a), "r"(x), "r"(y) : "memory"); }
__device__ __forceinline__ void sts_f2(uint32_t a, float x, float y) { asm volatile("st.shared.v2.f32 [%0], {%1,%2};" ::"r"(a), "f"(x), "f"(y) : "memory"); }
__device__ __forceinline__ void sts_f4(uint32_t a, float x, float y, float z, float w) {
  asm volatile("st.shared.v4.f32 [%0], {%1,%2,%3,%4};" ::"r"(a), "f"(x), "f"(y), "f"(z), "f"(w) : "memory");
}
__device__ __forceinline__ void st_b128(uint4* p, uint32_t a, uint32_t b, uint32_t c, uint32_t d) {
  asm volatile("st.relaxed.gpu.global.v4.b32 [%0], {%1,%2,%3,%4};" ::"l"(p), "r"(a), "r"(b), "r"(c), "r"(d) : "memory");
}
__device__ __forceinline__ void ld_b128(const uint4* p, uint32_t& a, uint32_t& b, uint32_t& c, uint32_t& d) {
  asm volatile("{.reg .b64 l, h; .reg .b128 v; ld.relaxed.gpu.global.b128 v, [%4]; mov.b128 {l,h}, v; mov.b64 {%0,%1}, l; mov.b64 {%2,%3}, h;}"
               : "=r"(a), "=r"(b), "=r"(c), "=r"(d) : "l"(p) : "memory");
}
__device__ __forceinline__ uint32_t bf2_mul(uint32_t a, uint32_t b) { uint32_t r; asm("mul.rn.bf16x2 %0, %1, %2;" : "=r"(r) : "r"(a), "r"(b)); return r; }
__device__ __forceinline__ uint32_t bf2_add(uint32_t a, uint32_t b) { uint32_t r; asm("add.rn.bf16x2 %0, %1, %2;" : "=r"(r) : "r"(a), "r"(b)); return r; }
__device__ __forceinline__ uint32_t bf2_fma(uint32_t a, uint32_t b, uint32_t c) { uint32_t r; asm("fma.rn.bf16x2 %0, %1, %2, %3;" : "=r"(r) : "r"(a), "r"(b), "r"(c)); return r; }
__device__ __forceinline__ uint32_t gelu2_pair(float a, float b) {
  const uint32_t v = pack_bf16(a, b);
  uint32_t t;
  asm("tanh.approx.bf16x2 %0, %1;" : "=r"(t) : "r"(bf2_fma(v, bf2_fma(bf2_mul(v, v), 0x3d123d12u, 0xbe4fbe4fu), v)));
  return bf2_fma(v, t, v);
}
struct cplx { float re, im; };
__device__ __forceinline__ cplx cmul(cplx a, cplx b) { return {fmaf(a.re, b.re, -a.im * b.im), fmaf(a.re, b.im, a.im * b.re)}; }
__device__ __forceinline__ cplx cfma(cplx a, cplx b, cplx c) {
  return {fmaf(a.re, b.re, fmaf(-a.im, b.im, c.re)), fmaf(a.re, b.im, fmaf(a.im, b.re, c.im))};
}
__device__ __forceinline__ cplx make_lam(float lre, float lim, float ldt) {
  float dt = __bfloat162float(__float2bfloat16_rn(expf(ldt)));
  float mag = expf(dt * lre), sn, cs;
  sincospif(dt * lim * 0.31830988618379067f, &sn, &cs);
  return {mag * cs, mag * sn};
}

__device__ __forceinline__ void gate_rows(uint32_t sb, int lane, int xrot, int row0, uint4 (&gw)[4], const uint4* gwp, unsigned* dst, unsigned par) {
  const int row = row0 + (lane >> 3);
  const uint32_t xr0 = sb + OFF_X + row * 128 + (((lane & 7) ^ (row & 7)) << 4), xr1 = (xr0 + 512) ^ 64;
  float z[2], y[2];
#pragma unroll
  for (int r = 0; r < 2; r++) z[r] = y[r] = 0.f;
#pragma unroll
  for (int kb = 0; kb < 8; kb++) {
    const uint4 w = gw[kb & 3];
    if (kb < 4) gw[kb] = __ldg(gwp + (kb + 4) * 8);
    mbar_wait(sb + OFF_XFULL + 8 * kb, 0);
#pragma unroll
    for (int r = 0; r < 2; r++) {
      const uint4 a = lds_u4((r ? xr1 : xr0) + ((kb + xrot) & 7) * 16384);
      const uint32_t p[4] = {bf2_mul(a.x, w.x), bf2_mul(a.y, w.y), bf2_mul(a.z, w.z), bf2_mul(a.w, w.w)};
#pragma unroll
      for (int c = 0; c < 4; c++) { z[r] += bf_lo(p[c]); y[r] += bf_hi(p[c]); }
    }
  }
  float zz = z[0] + y[0];
  const float z1 = z[1] + y[1];
  zz = ((lane & 4) ? z1 : zz) + __shfl_xor_sync(0xffffffffu, (lane & 4) ? zz : z1, 4);
  zz += __shfl_xor_sync(0xffffffffu, zz, 2);
  zz += __shfl_xor_sync(0xffffffffu, zz, 1);
  zz = bf_lo(pack_bf16(zz, 0.f));
  const float rho = 4.f * expf(zz > 40.f ? 40.f : zz);
  if ((lane & 3) == 0)
    asm volatile("st.relaxed.gpu.global.u32 [%0], %1;" ::"l"(dst + row + (lane & 4)), "r"((__float_as_uint(rho) & ~1u) | par) : "memory");
}

template<int TB,uint32_t BH,int SA=1> __device__ __forceinline__ void wgmma_n64_rs(float (&d)[32], uint32_t a0,uint32_t a1,uint32_t a2,uint32_t a3, uint32_t bl, uint32_t bo, int scale_d){
  asm volatile("{.reg .pred p; .reg .b32 t; .reg .b64 db; setp.ne.b32 p, %38, 0; add.u32 t, %36, %37; mov.b64 db, {t, %40};\n"
   "wgmma.mma_async.sync.aligned.m64n64k16.f32.bf16.bf16 {%0,%1,%2,%3,%4,%5,%6,%7,%8,%9,%10,%11,%12,%13,%14,%15,%16,%17,%18,%19,%20,%21,%22,%23,%24,%25,%26,%27,%28,%29,%30,%31}, {%32,%33,%34,%35}, db, p, %41, 1, %39;}"
   : "+f"(d[0]),"+f"(d[1]),"+f"(d[2]),"+f"(d[3]),"+f"(d[4]),"+f"(d[5]),"+f"(d[6]),"+f"(d[7]),"+f"(d[8]),"+f"(d[9]),"+f"(d[10]),"+f"(d[11]),"+f"(d[12]),"+f"(d[13]),"+f"(d[14]),"+f"(d[15]),"+f"(d[16]),"+f"(d[17]),"+f"(d[18]),"+f"(d[19]),"+f"(d[20]),"+f"(d[21]),"+f"(d[22]),"+f"(d[23]),"+f"(d[24]),"+f"(d[25]),"+f"(d[26]),"+f"(d[27]),"+f"(d[28]),"+f"(d[29]),"+f"(d[30]),"+f"(d[31])
   : "r"(a0),"r"(a1),"r"(a2),"r"(a3),"r"(bl),"r"(bo >> 4),"r"(scale_d),"n"(TB),"n"(BH),"n"(SA));
}
template<int TA,int TB,uint32_t AH,uint32_t BH> __device__ __forceinline__ void wgmma_n96_ss(float (&d)[48], uint32_t al, uint32_t ao, uint32_t bl, uint32_t bo, int scale_d){
  asm volatile("{.reg .pred p; .reg .b32 t, v; .reg .b64 da, db; setp.ne.b32 p, %52, 0; add.u32 t, %48, %49; mov.b64 da, {t, %55}; add.u32 v, %50, %51; mov.b64 db, {v, %56};\n"
   "wgmma.mma_async.sync.aligned.m64n96k16.f32.bf16.bf16 {%0,%1,%2,%3,%4,%5,%6,%7,%8,%9,%10,%11,%12,%13,%14,%15,%16,%17,%18,%19,%20,%21,%22,%23,%24,%25,%26,%27,%28,%29,%30,%31,%32,%33,%34,%35,%36,%37,%38,%39,%40,%41,%42,%43,%44,%45,%46,%47}, da, db, p, 1, 1, %53, %54;}"
   : "+f"(d[0]),"+f"(d[1]),"+f"(d[2]),"+f"(d[3]),"+f"(d[4]),"+f"(d[5]),"+f"(d[6]),"+f"(d[7]),"+f"(d[8]),"+f"(d[9]),"+f"(d[10]),"+f"(d[11]),"+f"(d[12]),"+f"(d[13]),"+f"(d[14]),"+f"(d[15]),"+f"(d[16]),"+f"(d[17]),"+f"(d[18]),"+f"(d[19]),"+f"(d[20]),"+f"(d[21]),"+f"(d[22]),"+f"(d[23]),"+f"(d[24]),"+f"(d[25]),"+f"(d[26]),"+f"(d[27]),"+f"(d[28]),"+f"(d[29]),"+f"(d[30]),"+f"(d[31]),"+f"(d[32]),"+f"(d[33]),"+f"(d[34]),"+f"(d[35]),"+f"(d[36]),"+f"(d[37]),"+f"(d[38]),"+f"(d[39]),"+f"(d[40]),"+f"(d[41]),"+f"(d[42]),"+f"(d[43]),"+f"(d[44]),"+f"(d[45]),"+f"(d[46]),"+f"(d[47])
   : "r"(al),"r"(ao >> 4),"r"(bl),"r"(bo >> 4),"r"(scale_d),"n"(TA),"n"(TB),"n"(AH),"n"(BH));
}
template<int TA,int TB,uint32_t AH,uint32_t BH> __device__ __forceinline__ void wgmma_n128_ss(float (&d)[64], uint32_t al, uint32_t ao, uint32_t bl, uint32_t bo, int scale_d){
  asm volatile("{.reg .pred p; .reg .b32 t, v; .reg .b64 da, db; setp.ne.b32 p, %68, 0; add.u32 t, %64, %65; mov.b64 da, {t, %71}; add.u32 v, %66, %67; mov.b64 db, {v, %72};\n"
   "wgmma.mma_async.sync.aligned.m64n128k16.f32.bf16.bf16 {%0,%1,%2,%3,%4,%5,%6,%7,%8,%9,%10,%11,%12,%13,%14,%15,%16,%17,%18,%19,%20,%21,%22,%23,%24,%25,%26,%27,%28,%29,%30,%31,%32,%33,%34,%35,%36,%37,%38,%39,%40,%41,%42,%43,%44,%45,%46,%47,%48,%49,%50,%51,%52,%53,%54,%55,%56,%57,%58,%59,%60,%61,%62,%63}, da, db, p, 1, 1, %69, %70;}"
   : "+f"(d[0]),"+f"(d[1]),"+f"(d[2]),"+f"(d[3]),"+f"(d[4]),"+f"(d[5]),"+f"(d[6]),"+f"(d[7]),"+f"(d[8]),"+f"(d[9]),"+f"(d[10]),"+f"(d[11]),"+f"(d[12]),"+f"(d[13]),"+f"(d[14]),"+f"(d[15]),"+f"(d[16]),"+f"(d[17]),"+f"(d[18]),"+f"(d[19]),"+f"(d[20]),"+f"(d[21]),"+f"(d[22]),"+f"(d[23]),"+f"(d[24]),"+f"(d[25]),"+f"(d[26]),"+f"(d[27]),"+f"(d[28]),"+f"(d[29]),"+f"(d[30]),"+f"(d[31]),"+f"(d[32]),"+f"(d[33]),"+f"(d[34]),"+f"(d[35]),"+f"(d[36]),"+f"(d[37]),"+f"(d[38]),"+f"(d[39]),"+f"(d[40]),"+f"(d[41]),"+f"(d[42]),"+f"(d[43]),"+f"(d[44]),"+f"(d[45]),"+f"(d[46]),"+f"(d[47]),"+f"(d[48]),"+f"(d[49]),"+f"(d[50]),"+f"(d[51]),"+f"(d[52]),"+f"(d[53]),"+f"(d[54]),"+f"(d[55]),"+f"(d[56]),"+f"(d[57]),"+f"(d[58]),"+f"(d[59]),"+f"(d[60]),"+f"(d[61]),"+f"(d[62]),"+f"(d[63])
   : "r"(al),"r"(ao >> 4),"r"(bl),"r"(bo >> 4),"r"(scale_d),"n"(TA),"n"(TB),"n"(AH),"n"(BH));
}

__global__ void __cluster_dims__(2, 1, 1) __launch_bounds__(384, 1)
fused_kernel(const __nv_bfloat16* __restrict__ lam_re, const __nv_bfloat16* __restrict__ lam_im, const __nv_bfloat16* __restrict__ log_dt,
             const __nv_bfloat16* __restrict__ dskip, const __nv_bfloat16* __restrict__ b1, const __nv_bfloat16* __restrict__ b2,
             const __nv_bfloat16* __restrict__ gate_w, float* __restrict__ out, float sgn, const __grid_constant__ Maps maps) {
  extern __shared__ __align__(1024) unsigned char smem_raw[];
  const uint32_t sb = (uint32_t)__cvta_generic_to_shared(smem_raw);
  const int b = blockIdx.x;
  const int rank = b & 1, cl = b >> 1;
  const int sp = (cl & 1) | ((cl >> 2) & 2), m = ((cl >> 1) & 3) | ((cl >> 4) << 2);
  const int s = sp * 2 + rank;
  const int xrot = 9 - 2 * sp;
  if (threadIdx.x == 0) {
    mbar_init(sb + OFF_XFULL, 1);
    mbar_expect_tx(sb + OFF_XFULL, 16384);
    tma5d(sb + OFF_X + (xrot & 7) * 16384, &maps.x, 0, 0, m, sb + OFF_XFULL);
    tma5d(sb + OFF_X + (xrot & 7) * 16384 + 8192, &maps.x, 0, 8, m, sb + OFF_XFULL);
  }
  if (threadIdx.x == 128) {
    mbar_init(sb + OFF_FULL, 1);
    mbar_expect_tx(sb + OFF_FULL, 16384);
    tma4d(sb + OFF_RING, &maps.bb, 0, s * 8, sb + OFF_FULL);
  }
  const int warp = __shfl_sync(0xffffffffu, (int)(threadIdx.x >> 5), 0);
  const int lane0 = threadIdx.x & 31;

  if (elect_one()) {
    if (warp > 8) {
      map_prefetch(&maps.x + (warp - 9));
      mbar_init(sb + OFF_GBAR + 8 * (warp - 9), warp < 11 ? 64 : 96);
    }
    const uint32_t c = warp < 8 ? 1 : warp < 11 ? 8 : 4, bar = sb + OFF_XFULL + 16 * warp;
    if ((warp & 11) != 0) mbar_init(bar, c);
    mbar_init(bar + 8, c);
    asm volatile("fence.mbarrier_init.release.cluster;" ::: "memory");
  }
  __syncwarp();
  asm volatile("barrier.cluster.arrive.relaxed.aligned;" ::: "memory");

  if (warp < 8) {
    const int lane = __shfl_sync(0xffffffffu, lane0, lane0);
    const int wg = warp >> 2, w = warp & 3, q = lane & 3, gr = lane >> 2;
    uint32_t bv[28];
#pragma unroll
    for (int j = 0; j < 28; j++) bv[j] = __ldg(reinterpret_cast<const uint32_t*>(b1 + s * 224 + j * 8) + q);
    asm volatile("setmaxnreg.inc.sync.aligned.u32 224;");
    cluster_wait();
    auto release = [&](int slot) { if (lane == 0) mbar_arrive(sb + OFF_EMPTY + 8 * slot); };
    const uint32_t xw = sb + OFF_X + wg * 8192, fullb = sb + OFF_FULL;
    const uint32_t dxw = (xw & 0x3FFFF) >> 4, dring = ((sb + OFF_RING) & 0x3FFFF) >> 4;

    float uu[64], aa[48], ab[64];
    cplx lam, coef, l16, l32, l64, lq, pre, e[2];
    uint32_t sh16, mhi, ck = 0;
    const uint32_t dx0 = ((sb + OFF_X) & 0x3FFFF) >> 4;

    auto bias = [&](int c) {
#pragma unroll
      for (int j = c * 7; j < c * 7 + 7; j++) {
        pin(bv[j]);
        float* d = j < 12 ? aa + 4 * j : ab + 4 * (j - 12);
        d[0] = d[2] = __uint_as_float(bv[j] << sh16); d[1] = d[3] = __uint_as_float(bv[j] & mhi);
        pin(d[0]); pin(d[1]); pin(d[2]); pin(d[3]);
      }
    };
#pragma unroll
    for (int kb = 0; kb < 8; kb++) {
      const int slot = kb % NSLOT;
      mbar_wait(sb + OFF_XFULL + 8 * kb, 0);
      if (kb == 0) mbar_wait(fullb, 0);
      if (kb == 2) { sh16 = late16(sb + OFF_XFULL); mhi = 0xffffffffu << sh16; }
      if (kb == 4) {
        mbar_wait(sb + OFF_LBAR, 0);
        const uint4 v = lds_u4(sb + OFF_LC + (warp * 8 + gr) * 16);
        lam = cplx{__uint_as_float(v.x), __uint_as_float(v.y)};
        coef = cplx{__uint_as_float(v.z), __uint_as_float(v.w)};
      }
      wg_fence();
      const uint32_t dxa = dx0 + ((kb + xrot) & 7) * 1024;
#pragma unroll
      for (int kk = 0; kk < 4; kk++)
        wgmma_n128_ss<0, 0, DH128, DH128>(uu, dring + wg * 512, slot * 16384 + kk * 32, dxa, kk * 32, (kb | kk) != 0);
      wg_commit();
      if (kb > 0) { wg_wait<1>(); release((kb - 1) % NSLOT); }
      if (kb >= 2 && kb < 6) bias(kb - 2);
      if (kb == 6) {
        pin(lam.re); pin(lam.im);
        cplx t = cmul(lam, lam); t = cmul(t, t); t = cmul(t, t);
        l16 = cmul(t, t); l32 = cmul(l16, l16); l64 = cmul(l32, l32);
        const cplx a = (q & 1) ? l32 : cplx{1.f, 0.f}, c = (q & 2) ? l64 : cplx{1.f, 0.f};
        lq = cmul(cmul(a, c), coef);
        pin(lq.re); pin(lq.im);
      }
    }
    auto scale_u = [&](int c) {
#pragma unroll
      for (int n = 0; n < 8; n++) {
        const int i = (n >> 2) * 32 + c * 8 + (n & 2) * 2 + (n & 1);
        pin(uu[i]); pin(uu[i + 2]);
        const cplx v = cmul(coef, cplx{uu[i], uu[i + 2]});
        uu[i] = v.re; uu[i + 2] = v.im;
        pin(uu[i]); pin(uu[i + 2]);
      }
    };
#pragma unroll
    for (int kb = 0; kb < 8; kb++) {
      const int u = 8 + kb, slot = u % NSLOT;
      mbar_wait(fullb + 8 * slot, full_par(u));
      wg_fence();
      const uint32_t dxa = dxw + ((kb + xrot) & 7) * 1024;
#pragma unroll
      for (int kk = 0; kk < 4; kk++)
        wgmma_n96_ss<0, 1, DH128, DH64>(aa, dxa, kk * 32, dring, slot * 16384 + kk * 1024 + lbo(4096), 1);
      wg_commit();
      if (kb != 4) { wg_wait<1>(); release((u - 1) % NSLOT); }
      if (kb == 0) {
        reg_fence(uu);
#pragma unroll
        for (int h = 0; h < 2; h++) e[h] = cplx{uu[32 * h], uu[32 * h + 2]};
      }
      if (kb == 0 || kb == 2 || kb == 3) {
        const int t0 = kb ? 5 * kb - 4 : 1;
#pragma unroll
        for (int t = t0; t < t0 + 5; t++) {
#pragma unroll
          for (int h = 0; h < 2; h++) { const int i = 32 * h + 4 * (t >> 1) + (t & 1); e[h] = cfma(lam, e[h], cplx{uu[i], uu[i + 2]}); }
        }
#pragma unroll
        for (int h = 0; h < 2; h++) { pin(e[h].re); pin(e[h].im); }
      }
      if (kb == 4) {
        sched_fence(ck);
        e[1] = cfma(l16, e[0], e[1]);
        cplx y = {__shfl_up_sync(0xffffffffu, e[1].re, 1, 4), __shfl_up_sync(0xffffffffu, e[1].im, 1, 4)};
        if (q >= 1) e[1] = cfma(l32, y, e[1]);
        y = cplx{__shfl_up_sync(0xffffffffu, e[1].re, 2, 4), __shfl_up_sync(0xffffffffu, e[1].im, 2, 4)};
        if (q >= 2) e[1] = cfma(l64, y, e[1]);
        if (q == 3) {
          sts_f2(sb + OFF_CARRY + (warp * 8 + gr) * 8, e[1].re, e[1].im);
          mbar_arrive(sb + OFF_GBAR);
        }
        e[1] = cplx{__shfl_up_sync(0xffffffffu, e[1].re, 1, 4), __shfl_up_sync(0xffffffffu, e[1].im, 1, 4)};
        wg_wait<1>(); release((u - 1) % NSLOT);
      }
      if (kb == 5) {
        pre = (q >= 1) ? cmul(coef, e[1]) : cplx{0.f, 0.f};
        e[0] = cmul(coef, e[0]);
        pin(pre.re); pin(pre.im); pin(e[0].re); pin(e[0].im);
      }
      if (kb > 4) scale_u(kb - 5);
    }
    uint32_t H[56], hf[32];
    cplx hst[2];
    const uint32_t hst_addr = sb + OFF_X + (lane & 8) * 1024 + (warp * 8 + (lane & 7)) * 128 + (((lane >> 4) ^ (lane & 7)) << 4);
    const uint32_t him = (2 - rank) * 16384;
    uint32_t peer;
    asm volatile("mapa.shared::cluster.u32 %0, %1, %2;" : "=r"(peer) : "r"(sb), "r"(rank ^ 1));
    auto credit = [&]() { if (lane == 0) mbar_arrive_cl(peer + OFF_KBAR + wg * 8); };
    uint4 g2;
#pragma unroll
    for (int kb = 0; kb < 8; kb++) {
      const int u = 16 + kb, slot = u % NSLOT;
      mbar_wait(fullb + 8 * slot, full_par(u));
      wg_fence();
#pragma unroll
      for (int kk = 0; kk < 4; kk++)
        wgmma_n128_ss<0, 1, DH128, DH128>(ab, dxw, kb * 16384 + kk * 32, dring, slot * 16384 + kk * 2048 + lbo(8192), 1);
      wg_commit();
      if (kb == 0) scale_u(3);
      if (kb == 4) {
        mbar_wait(sb + OFF_CBAR, 0);
        const float2 c = lds_f2(sb + OFF_CARRY + (warp * 8 + gr) * 8);
        mbar_wait(sb + OFF_EMPTY, 1);
        hst[0] = cfma(lq, cplx{c.x, c.y}, pre);
        hst[1] = cfma(l16, hst[0], e[0]);
      }
      if (kb >= 4) g2 = lds_u4(sb + OFF_GT + (kb - 4) * 64 + q * 16);
      wg_wait<1>(); release((u - 1) % NSLOT);
      if (kb) sched_fence(ck);
      if (kb < 4) {
#pragma unroll
        for (int i = kb * 6; i < kb * 6 + 6; i++) {
          pin(aa[2 * i]); pin(aa[2 * i + 1]);
          H[i] = gelu2_pair(aa[2 * i], aa[2 * i + 1]);
          pin(H[i]);
        }
      } else {
        const int j0 = (kb - 4) * 2;
        uint32_t rr[4], ri[4];
#pragma unroll
        for (int jj = 0; jj < 2; jj++) {
          const int j = j0 + jj;
#pragma unroll
          for (int h = 0; h < 2; h++) {
            const int i = 32 * h + 4 * j;
            const uint32_t g = jj ? (h ? g2.w : g2.z) : (h ? g2.y : g2.x);
            const cplx h0 = cfma(lam, hst[h], cplx{uu[i], uu[i + 2]});
            hst[h] = cfma(lam, h0, cplx{uu[i + 1], uu[i + 3]});
            rr[jj * 2 + h] = bf2_mul(pack_bf16(h0.re, hst[h].re), g);
            ri[jj * 2 + h] = bf2_mul(pack_bf16(h0.im, hst[h].im), g);
          }
        }
        const uint32_t a = hst_addr ^ (j0 << 4);
        asm volatile("stmatrix.sync.aligned.m8n8.x4.shared.b16 [%0], {%1,%2,%3,%4};" ::"r"(a), "r"(rr[0]), "r"(rr[1]), "r"(rr[2]), "r"(rr[3]) : "memory");
        asm volatile("stmatrix.sync.aligned.m8n8.x4.shared.b16 [%0], {%1,%2,%3,%4};" ::"r"(a + him), "r"(ri[0]), "r"(ri[1]), "r"(ri[2]), "r"(ri[3]) : "memory");
        if (kb == 7) { __syncwarp(); if (q == 3) mbar_arrive(sb + OFF_GBAR); }
      }
    }

    uint4* const psend = g_part + (size_t)(m * 8 + rank) * 3072 + warp * 128 + lane;
    const uint4* const precv = g_part + (size_t)(m * 8 + s) * 3072 + warp * 128 + lane;
    const uint32_t pbuf = OFF_X + warp * 2048 + lane * 16;
    float o[32], fin[32], fs[2];
    uint32_t r0[16], pt[16], sum[16], tag;
    auto recv_issue = [&](uint32_t (&r)[16], int k) {
#pragma unroll
      for (int i = 0; i < 4; i++) ld_b128(precv + k * 1024 + i * 32, r[4 * i], r[4 * i + 1], r[4 * i + 2], r[4 * i + 3]);
    };
    auto stale = [&](uint32_t (&r)[16]) {
      uint32_t r_;
#pragma unroll
      for (int i = 0; i < 16; i += 4) asm("lop3.b32 %0, %0, %1, 1, 0x78;" : "+r"(r[i]) : "r"(tag));
      asm volatile("{.reg .pred p; .reg .b32 t; lop3.b32 t, %1, %2, %3, 0xfe; lop3.b32 t, t, %4, 1, 0xa8; setp.ne.u32 p, t, 0; vote.sync.any.pred p, p, 0xffffffff; selp.u32 %0, 1, 0, p;}"
                   : "=r"(r_) : "r"(r[0]), "r"(r[4]), "r"(r[8]), "r"(r[12]));
      return r_ != 0;
    };
    auto recv_check = [&](uint32_t (&r)[16], int k) {
      if (__builtin_expect(stale(r), 0)) {
        int tries = 0;
#pragma unroll 1
        do { recv_issue(r, k); } while (stale(r) && ++tries < 200000);
      }
    };
    auto gelu_b = [&](int i0, int i1) {
#pragma unroll
      for (int i = i0; i < i1; i++) {
        pin(ab[2 * i]); pin(ab[2 * i + 1]);
        H[24 + i] = gelu2_pair(ab[2 * i], ab[2 * i + 1]);
        pin(H[24 + i]);
      }
    };
    auto mma = [&](float (&d)[32], int p, int k0, int k1, int acc) {
      const uint32_t wo = stage_off(p);
      wg_fence();
#pragma unroll
      for (int k = k0; k < k1; k++) {
        if (k >= 6 && k < 14) {
          const int kk = k - 6;
          if (kk < 4) wgmma_n64_rs<0, DH128, 1>(d, hf[4 * kk], hf[4 * kk + 1], hf[4 * kk + 2], hf[4 * kk + 3], dx0, wo + 14336 + kk * 32, 1);
          else wgmma_n64_rs<0, DH128, -1>(d, hf[4 * kk], hf[4 * kk + 1], hf[4 * kk + 2], hf[4 * kk + 3], dx0, wo + 22528 + (kk - 4) * 32, 1);
        } else {
          const int kk = k < 6 ? k : k - 8;
          wgmma_n64_rs<1, DH128>(d, H[4 * kk], H[4 * kk + 1], H[4 * kk + 2], H[4 * kk + 3], dx0, wo + (kk / 7) * 30720 + (kk % 7) * 2048, k != 0 || acc);
        }
      }
      wg_commit();
    };
    auto recv_peer = [&](int k) {
      mbar_wait(sb + OFF_RBAR + wg * 8, k & 1);
#pragma unroll
      for (int i = 0; i < 4; i++) { const uint4 v = lds_u4(sb + pbuf + i * 512); pt[4 * i] = v.x; pt[4 * i + 1] = v.y; pt[4 * i + 2] = v.z; pt[4 * i + 3] = v.w; }
    };
#pragma unroll
    for (int p = 0; p < 8; p++) {
      if (p == 0) {
        mbar_wait(fullb, full_par(24));
        mma(o, 0, 0, 4, 0);
        mbar_wait(fullb + 8, full_par(25));
        wg_wait<1>(); release(5);
        gelu_b(0, 8);
        mma(o, 0, 4, 6, 0);
        mbar_wait(sb + OFF_GBAR, 1);
        {
          const uint32_t ha = xw + ((lane >> 4) * 8 + (lane & 7)) * 128 + (((2 * w + ((lane >> 3) & 1)) ^ (lane & 7)) << 4);
#pragma unroll
          for (int kk = 0; kk < 8; kk++)
            asm volatile("ldmatrix.sync.aligned.m8n8.x4.trans.shared.b16 {%0,%1,%2,%3}, [%4];" : "=r"(hf[4 * kk]), "=r"(hf[4 * kk + 1]), "=r"(hf[4 * kk + 2]), "=r"(hf[4 * kk + 3])
                         : "r"(ha + (kk >> 2) * him + (kk & 3) * 2048) : "memory");
        }
        gelu_b(8, 12);
        mma(o, 0, 6, 10, 0);
        credit();
        gelu_b(12, 19);
        mbar_wait(fullb + 16, full_par(26));
        mma(o, 0, 10, 14, 0);
        gelu_b(19, 26);
        mma(o, 0, 14, 17, 0);
        gelu_b(26, 32);
        if (wg == 1) bar_sync(4, 256);
        mma(o, 0, 17, 22, 0);
      } else {
        bar_sync(3 + wg, 256);
        if (p < 7) mma(o, p, 0, 22, 0); else mma(fin, p, 0, 22, 1);
      }
      if (p < 7 || wg == 0) bar_arrive(4 - wg, 256);
      if (p < 7) mbar_wait(sb + OFF_XFULL + 8 * (p + 1), 1);
      if ((p & 1) == 0) {
        if (w == 0 && lane == 0) mbar_expect_tx(sb + OFF_RBAR + wg * 8, 8192);
        if (p == 6) {
          mbar_wait(sb + OFF_EMPTY + 32, 0);
          tag = lds_u(sb + OFF_EPOCH);
          recv_check(sum, 0); recv_check(r0, 1);
#pragma unroll
          for (int i = 0; i < 16; i++) sum[i] = bf2_add(sum[i], r0[i]);
        }
        mbar_wait(sb + OFF_KBAR + wg * 8, (p >> 1) & 1);
      } else {
        if (p == 1 || p == 7) tag = lds_u(sb + OFF_EPOCH);
        recv_peer(p >> 1);
        if (p == 7) {
          recv_check(r0, 2);
#pragma unroll
          for (int i = 0; i < 16; i++) { sum[i] = bf2_add(sum[i], bf2_add(r0[i], pt[i])); pin(sum[i]); }
          sched_fence(ck);
        }
      }
      if (p == 4) {
        mbar_wait(sb + OFF_LBAR, 1);
#pragma unroll
        for (int j = 0; j < 8; j++) {
          const uint4 v = lds_u4(sb + pbuf + 16384 + (j >> 2) * 16384 + (j & 3) * 512);
          fin[4 * j] = __uint_as_float(v.x); fin[4 * j + 1] = __uint_as_float(v.y); fin[4 * j + 2] = __uint_as_float(v.z); fin[4 * j + 3] = __uint_as_float(v.w);
        }
        recv_issue(sum, 0);
      }
      wg_wait<0>();
      if (p < 5) release(p);
      if (p < 7) reg_fence(o); else reg_fence(fin);
      if ((p & 1) == 0) {
        if (p == 6) recv_issue(r0, 2);
#pragma unroll
        for (int i = 0; i < 4; i++)
          asm volatile("st.async.shared::cluster.mbarrier::complete_tx::bytes.v4.b32 [%0], {%1,%2,%3,%4}, [%5];" ::"r"(peer + pbuf + i * 512),
                       "r"(pack_bf16(o[8 * i], o[8 * i + 1])), "r"(pack_bf16(o[8 * i + 2], o[8 * i + 3])), "r"(pack_bf16(o[8 * i + 4], o[8 * i + 5])),
                       "r"(pack_bf16(o[8 * i + 6], o[8 * i + 7])), "r"(peer + OFF_RBAR + wg * 8) : "memory");
      } else if (p < 7) {
        const int k = p >> 1;
#pragma unroll
        for (int i = 0; i < 4; i++) {
#pragma unroll
          for (int c = 4 * i; c < 4 * i + 4; c++) pt[c] = bf2_add(pt[c], pack_bf16(o[2 * c], o[2 * c + 1]));
          asm("lop3.b32 %0, %0, 1, %1, 0xb8;" : "+r"(pt[4 * i]) : "r"(tag));
          st_b128(psend + (((sp + 1 + k) & 3) * 6 + k) * 1024 + i * 32, pt[4 * i], pt[4 * i + 1], pt[4 * i + 2], pt[4 * i + 3]);
        }
        __syncwarp();
        credit();
        if (p == 5) recv_issue(r0, 1);
      }
      if (p == 2) {
#pragma unroll
        for (int h = 0; h < 2; h++) { fs[h] = __fdividef(2.f, 4.f + bf_lo(lds_h(sb + OFF_GS + (wg * 64 + w * 16 + gr + 8 * h) * 2))); pin(fs[h]); }
      }
    }
    {
      const uint32_t tb = sb + OFF_X + stage_off(0) + warp * 4096;
      const uint32_t ta = tb + gr * 256 + ((gr & 3) << 5) + q * 8;
      const uint32_t la = tb + (lane >> 3) * 256 + (((lane & 7) << 4) ^ ((lane >> 3) << 5));
      float* op = out + (size_t)(m * 128 + (lane >> 4) * 32 + warp * 4 + ((lane >> 3) & 1)) * DM + s * 64 + (lane & 7) * 4;
#pragma unroll
      for (int qt = 0; qt < 4; qt++) {
        const int h = qt & 1, ch = qt >> 1;
#pragma unroll
        for (int j = 0; j < 4; j++) {
          const int i = ch * 8 + j * 2 + h;
          sts_f2((ta ^ (j << 5)) + h * 2048 + ch * 128, (fin[2 * i] + bf_lo(sum[i])) * fs[h], (fin[2 * i + 1] + bf_hi(sum[i])) * fs[h]);
        }
        __syncwarp();
#pragma unroll
        for (int r = 0; r < 2; r++)
          *reinterpret_cast<uint4*>(op + (r * 64 + h * 2) * DM + ch * 32) = lds_u4(la + (h * 2 + r) * 1024 + ch * 128);
      }
      sts_u(sb + OFF_EPOCH + 4, ck);
      if (warp == 4 && lane == 0) g_epoch[b] = tag;
    }
  } else {
    const int lane = __shfl_sync(0xffffffffu, lane0, lane0);
    asm volatile("setmaxnreg.dec.sync.aligned.u32 56;");
    int wsel = warp;
    asm("" : "+r"(wsel));
    if (wsel > 8) {
      if (warp != 11) {
        const uint4* gwp = reinterpret_cast<const uint4*>(gate_w) + (lane & 7);
        uint4 gw[4];
        const int t = (warp - 9) * 32 + lane;
        unsigned par;
        asm volatile("ld.relaxed.gpu.global.u32 %0, [%1];" : "=r"(par) : "l"(g_epoch + b) : "memory");
        const float pr = bf_ld(lam_re + s * 64 + t), pi = sgn * bf_ld(lam_im + s * 64 + t), pd = bf_ld(log_dt + s * 64 + t);
#pragma unroll
        for (int i = 0; i < 4; i++) gw[i] = __ldg(gwp + i * 8);
        cluster_wait();
        par = __shfl_sync(0xffffffffu, (par + 1) & 1, 0);
        cplx l128 = make_lam(pr, pi, pd);
        {
          const float inv = __fdividef(sgn, fmaf(pr, pr, pi * pi));
          const cplx cf = cmul(cplx{l128.re - 1.f, l128.im}, cplx{pr * inv, -pi * inv});
          sts_f4(sb + OFF_LC + t * 16, l128.re, l128.im, cf.re, cf.im);
          mbar_arrive(sb + OFF_LBAR);
        }
#pragma unroll
        for (int i = 0; i < 7; i++) l128 = cmul(l128, l128);
        pin(l128.re); pin(l128.im);
        gate_rows(sb, lane, xrot, s * 16 + (warp - 9) * 8, gw, gwp, g_gate + m * 128, par);
        uint32_t vr[15], vi[15];
#pragma unroll
        for (int i = 0; i < 15; i++) { vr[i] = par; vi[i] = 0; pin(vr[i]); pin(vi[i]); }
        mbar_wait(sb + OFF_GBAR, 0);
        float2* eb = g_end + s * 1024 + t;
        {
          const float2 e = lds_f2(sb + OFF_CARRY + t * 8);
          const unsigned long long v = ((unsigned long long)__float_as_uint(e.y) << 32) | ((__float_as_uint(e.x) & ~1u) | par);
          asm volatile("st.relaxed.gpu.global.b64 [%0], %1;" ::"l"(eb + m * 64), "l"(v) : "memory");
        }
        __nanosleep(400);
        const float2* e15 = eb + (m - 15) * 64;
        int tries = 0;
        bool bad;
#pragma unroll 1
        do {
#pragma unroll
          for (int i = 0; i < 15; i++)
            asm volatile("{.reg .pred p; .reg .b64 v; mov.b64 v, {%0,%1}; setp.ge.s32 p, %3, %4; @p ld.relaxed.gpu.global.b64 v, [%2]; mov.b64 {%0,%1}, v;}"
                         : "+r"(vr[i]), "+r"(vi[i]) : "l"(e15 + i * 64), "r"(m), "r"(15 - i) : "memory");
          uint32_t x = vr[0] ^ par;
#pragma unroll
          for (int i = 1; i < 15; i++) asm("lop3.b32 %0, %0, %1, %2, 0xf6;" : "+r"(x) : "r"(vr[i]), "r"(par));
          bad = __any_sync(0xffffffffu, x & 1);
        } while (bad && ++tries < 200000);
        cplx S = {__uint_as_float(vr[0] ^ par), __uint_as_float(vi[0])};
#pragma unroll
        for (int i = 1; i < 15; i++) S = cfma(l128, S, cplx{__uint_as_float(vr[i] ^ par), __uint_as_float(vi[i])});
        sts_f2(sb + OFF_CARRY + t * 8, S.re, S.im);
        mbar_arrive(sb + OFF_CBAR);
        mbar_wait(sb + OFF_CBAR, 0);
        const int gr = lane >> 2, q = lane & 3;
        float2 db[8];
#pragma unroll
        for (int j = 0; j < 8; j++) db[j] = lds_f2(sb + OFF_DB + j * 32 + q * 8);
        mbar_wait(sb + OFF_XFULL + 16, 1);
        mbar_wait(sb + OFF_EMPTY, 0);
#pragma unroll 1
        for (int cw = warp - 9; cw < 8; cw += 2) {
          const float r0 = 0.5f * bf_lo(lds_h(sb + OFF_GS + (cw * 16 + gr) * 2)), r1 = 0.5f * bf_lo(lds_h(sb + OFF_GS + (cw * 16 + gr) * 2 + 16));
          const uint32_t xa = sb + OFF_X + (1 + rank) * 16384 + (cw * 16 + (lane & 15)) * 128 + (((lane >> 4) ^ (lane & 7)) << 4);
          uint32_t xv[16];
#pragma unroll
          for (int i = 0; i < 4; i++)
            asm volatile("ldmatrix.sync.aligned.m8n8.x4.shared.b16 {%0,%1,%2,%3}, [%4];" : "=r"(xv[4 * i]), "=r"(xv[4 * i + 1]), "=r"(xv[4 * i + 2]), "=r"(xv[4 * i + 3])
                         : "r"(xa ^ (i << 5)) : "memory");
          __syncwarp();
#pragma unroll
          for (int j = 0; j < 8; j++) {
            const uint32_t x0 = bf2_mul(xv[2 * j], __float_as_uint(db[j].x)), x1 = bf2_mul(xv[2 * j + 1], __float_as_uint(db[j].x));
            pin(db[j].y);
            const float bl = bf_lo(__float_as_uint(db[j].y)), bh = bf_hi(__float_as_uint(db[j].y));
            sts_f4(sb + OFF_X + 16384 + (j >> 2) * 16384 + cw * 2048 + (j & 3) * 512 + lane * 16, fmaf(bf_lo(x0), r0, bl), fmaf(bf_hi(x0), r0, bh),
                   fmaf(bf_lo(x1), r1, bl), fmaf(bf_hi(x1), r1, bh));
          }
        }
        mbar_arrive(sb + OFF_LBAR);
      } else {
        unsigned par;
        asm volatile("ld.relaxed.gpu.global.u32 %0, [%1];" : "=r"(par) : "l"(g_epoch + b) : "memory");
        const uint32_t dk = __ldg(reinterpret_cast<const uint32_t*>(dskip + s * 64) + lane), bb = __ldg(reinterpret_cast<const uint32_t*>(b2 + s * 64) + lane);
        cluster_wait();
        if (lane == 0) sts_u(sb + OFF_EPOCH, par + 1);
        par = (par + 1) & 1;
        mbar_wait(sb + OFF_GBAR, 0);
        sts_u2(sb + OFF_DB + lane * 8, dk, bf2_add(bb, bb));
        uint32_t g0, g1, g2, g3;
        int tries = 0;
#pragma unroll 1
        do {
          asm volatile("ld.relaxed.gpu.global.v4.u32 {%0,%1,%2,%3}, [%4];" : "=r"(g0), "=r"(g1), "=r"(g2), "=r"(g3) : "l"(g_gate + m * 128 + lane * 4) : "memory");
          g0 ^= par; g1 ^= par; g2 ^= par; g3 ^= par;
        } while (((g0 | g1 | g2 | g3) & 1) && ++tries < 200000);
        const uint32_t p01 = pack_bf16(__uint_as_float(g0), __uint_as_float(g1)), p23 = pack_bf16(__uint_as_float(g2), __uint_as_float(g3));
        sts_u2(sb + OFF_GS + lane * 8, p01, p23);
        const uint32_t gt = sb + OFF_GT + ((lane >> 2) & 3) * 64 + (lane & 1) * 32 + (lane & 2) * 4 + (lane >> 4) * 4;
        sts_u(gt, p01);
        sts_u(gt + 16, p23);
        mbar_arrive(sb + OFF_CBAR);
      }
    } else {
      cluster_wait();
      if (elect_one()) {
        const uint32_t t0 = clock();
#pragma unroll 1
        for (int u = 1; u < 8; u++) {
          while ((uint32_t)clock() - t0 < 200 + (u - 1) * 480) {}
          const uint32_t fb = sb + OFF_XFULL + 8 * u;
          mbar_expect_tx(fb, 32768);
          tma5d_mc(sb + OFF_X + ((u + xrot) & 7) * 16384 + rank * 8192, &maps.x, u * 64, rank * 8, m, fb);
          const int sl = u < 6 ? u : u - 6;
          if (u >= 6) mbar_wait(sb + OFF_EMPTY + 8 * sl, 0);
          tma4d(sb + OFF_RING + sl * 16384, &maps.bb, u * 64, s * 8, fb);
        }
        int slot = 2; uint32_t ph = 0;
#pragma unroll 1
        for (int u = 8; u < 24; u++) {
          const uint32_t fb = sb + OFF_FULL + 8 * slot, dst = sb + OFF_RING + slot * 16384;
          mbar_wait(sb + OFF_EMPTY + 8 * slot, ph);
          if (u < 16) {
            mbar_expect_tx(fb, 12288);
            tma3d(dst, &maps.w1b, 0, (u - 8) * 64, s * 7, fb);
            if (u < 12) map_prefetch(&maps.w1a + (u - 8));
          } else {
            mbar_expect_tx(fb, 16384);
            tma2d(dst, &maps.w1a, s * 224 + 96, ((u - xrot) & 7) * 64, fb);
            tma2d(dst + 8192, &maps.w1a, s * 224 + 160, ((u - xrot) & 7) * 64, fb);
          }
          if (++slot == NSLOT) { slot = 0; ph ^= 1; }
        }
#pragma unroll 1
        for (int j = 0; j < 3; j++) {
          const uint32_t fb = sb + OFF_FULL + 8 * j, dst = sb + OFF_X + stage_off(0);
          const int c = ((sp + 1) & 3) * 128 + ((rank ^ 1) << 6);
          mbar_wait(sb + OFF_EMPTY + 8 + 8 * j, 1);
          mbar_expect_tx(fb, j == 1 ? 16384 : 14336);
          if (j == 1) {
            tma2d(dst + 14336, &maps.cre, s * 64, c, fb);
            tma2d(dst + 22528, &maps.cim, s * 64, c, fb);
          } else {
            tma2d(dst + j * 15360, &maps.w2, c, s * 224 + j * 56, fb);
          }
        }
#pragma unroll 1
        for (int p = 1; p < 8; p++) {
          const int c = ((sp + 1 + (p >> 1)) & 3) * 128 + (((rank ^ p ^ 1) & 1) << 6);
          const uint32_t fb = sb + OFF_XFULL + 8 * p, dst = sb + OFF_X + stage_off(p);
          if (p == 2 || p > 3) mbar_wait(sb + OFF_EMPTY + (p == 2 ? 40 : (p - 4) * 8), p == 2);
          mbar_expect_tx(fb, 45056);
          tma2d(dst, &maps.w2, c, s * 224, fb);
          tma2d(dst + 14336, &maps.cre, s * 64, c, fb);
          tma2d(dst + 22528, &maps.cim, s * 64, c, fb);
          tma2d(dst + 30720, &maps.w2, c, s * 224 + 112, fb);
        }
      }
    }
  }
}

typedef CUresult (*EncFn)(CUtensorMap*, CUtensorMapDataType, cuuint32_t, void*, const cuuint64_t*, const cuuint64_t*, const cuuint32_t*,
                          const cuuint32_t*, CUtensorMapInterleave, CUtensorMapSwizzle, CUtensorMapL2promotion, CUtensorMapFloatOOBfill);

void encode(EncFn f, CUtensorMap* mp, const void* p, int rank, const cuuint64_t* dims, const cuuint64_t* strides, const cuuint32_t* box, CUtensorMapSwizzle sw) {
  cuuint32_t es[5] = {1, 1, 1, 1, 1};
  f(mp, CU_TENSOR_MAP_DATA_TYPE_BFLOAT16, rank, const_cast<void*>(p), dims, strides, box, es, CU_TENSOR_MAP_INTERLEAVE_NONE, sw,
    CU_TENSOR_MAP_L2_PROMOTION_L2_128B, CU_TENSOR_MAP_FLOAT_OOB_FILL_NONE);
}

}

extern "C" void kernel_launch(void* const* d_in, const int* in_sizes, int n_in, void* d_out, int out_size) {
  typedef const __nv_bfloat16* bp;
  bp x = (bp)d_in[0], lre = (bp)d_in[1], lim = (bp)d_in[2], bre = (bp)d_in[3], bim = (bp)d_in[4], cre = (bp)d_in[5], cim = (bp)d_in[6],
     ldt = (bp)d_in[7], dsk = (bp)d_in[8], w1 = (bp)d_in[10], b1 = (bp)d_in[11], w2 = (bp)d_in[12], b2 = (bp)d_in[13], gw = (bp)d_in[14];
  static EncFn enc = nullptr;
  if (!enc) {
    void* f = nullptr;
    cudaDriverEntryPointQueryResult qr;
    cudaGetDriverEntryPoint("cuTensorMapEncodeTiled", &f, cudaEnableDefault, &qr);
    enc = (EncFn)f;
    cudaFuncSetAttribute(fused_kernel, cudaFuncAttributeMaxDynamicSharedMemorySize, SMEM_BYTES);
  }
  Maps maps;
  const bool swap = bim < bre;
  {
    cuuint64_t d[5] = {DM, 2, 4, 16, SEQ / 128}, st[4] = {DM * 2, 32 * DM * 2, 2 * DM * 2, 128 * DM * 2};
    cuuint32_t bx[5] = {64, 2, 4, 8, 1};
    encode(enc, &maps.x, x, 5, d, st, bx, CU_TENSOR_MAP_SWIZZLE_128B);
  }
  {
    cuuint64_t d[2] = {DM, DM}, st[1] = {DM * 2};
    cuuint32_t bx[2] = {64, 64};
    encode(enc, &maps.cre, swap ? cim : cre, 2, d, st, bx, CU_TENSOR_MAP_SWIZZLE_128B);
    encode(enc, &maps.cim, swap ? cre : cim, 2, d, st, bx, CU_TENSOR_MAP_SWIZZLE_128B);
    cuuint64_t d4[4] = {DM, 8, 2, DM / 8}, st4[3] = {DM * 2, (cuuint64_t)(swap ? bre - bim : bim - bre) * 2, 8 * DM * 2};
    cuuint32_t bx4[4] = {64, 8, 2, 8};
    encode(enc, &maps.bb, swap ? bim : bre, 4, d4, st4, bx4, CU_TENSOR_MAP_SWIZZLE_128B);
  }
  {
    cuuint64_t d[2] = {FF, DM}, st[1] = {FF * 2};
    cuuint32_t bx[2] = {64, 64};
    encode(enc, &maps.w1a, w1, 2, d, st, bx, CU_TENSOR_MAP_SWIZZLE_128B);
    cuuint64_t d3[3] = {32, DM, FF / 32}, st3[2] = {FF * 2, 64};
    cuuint32_t bx3[3] = {32, 64, 3};
    encode(enc, &maps.w1b, w1, 3, d3, st3, bx3, CU_TENSOR_MAP_SWIZZLE_64B);
  }
  {
    cuuint64_t d[2] = {DM, FF}, st[1] = {DM * 2};
    cuuint32_t bx[2] = {64, 112};
    encode(enc, &maps.w2, w2, 2, d, st, bx, CU_TENSOR_MAP_SWIZZLE_128B);
  }
  fused_kernel<<<128, 384, SMEM_BYTES>>>(lre, lim, ldt, dsk, b1, b2, gw, (float*)d_out, swap ? -1.f : 1.f, maps);
}
```

```cpp
#include <cuda_runtime.h>
#include <cuda_bf16.h>
#include <cuda.h>
#include <stdint.h>

namespace {

constexpr int SEQ = 2048, DM = 512, FF = 1792;
constexpr int NSLOT = 6;
constexpr uint32_t OFF_X = 0, OFF_RING = 131072, OFF_MISC = 229376;
constexpr uint32_t OFF_XFULL = OFF_MISC, OFF_FULL = OFF_XFULL + 64, OFF_RBAR = OFF_FULL + 48, OFF_EMPTY = OFF_RBAR + 16, OFF_KBAR = OFF_EMPTY + 48,
                   OFF_GBAR = OFF_KBAR + 16, OFF_LBAR = OFF_GBAR + 8, OFF_CBAR = OFF_LBAR + 8, OFF_EPOCH = OFF_CBAR + 8;
constexpr uint32_t OFF_LC = OFF_MISC + 256;
constexpr uint32_t OFF_GS = OFF_LC;
constexpr uint32_t OFF_GT = OFF_LC + 256;
constexpr uint32_t OFF_DB = OFF_LC + 512;
constexpr uint32_t OFF_CARRY = OFF_LC + 1024;
constexpr uint32_t SMEM_BYTES = OFF_CARRY + 512;
static_assert(SMEM_BYTES <= 232448, "smem");

struct Maps { CUtensorMap x, bb, w1b, w1a, w2, cre, cim; };
__host__ __device__ constexpr uint32_t stage_off(int p) { return 49152 + 45056 * (((p >> 1) & 1) + 2 * (p & 1)); }
__host__ __device__ constexpr uint32_t full_par(int u) { return ((u - 8) / 6 + (u % 6 == 0)) & 1; }

__device__ __align__(128) uint4 g_part[16 * 8 * 3 * 1024];
__device__ __align__(128) float2 g_end[8 * 16 * 64];
__device__ __align__(128) unsigned g_gate[SEQ];
__device__ __align__(128) unsigned g_epoch[128];
__device__ __align__(128) __nv_bfloat16 g_bcopy[2 * DM * DM];

__device__ __forceinline__ void mbar_init(uint32_t bar, uint32_t cnt) { asm volatile("mbarrier.init.shared::cta.b64 [%0], %1;" ::"r"(bar), "r"(cnt)); }
__device__ __forceinline__ void mbar_expect_tx(uint32_t bar, uint32_t bytes) { asm volatile("mbarrier.arrive.expect_tx.shared::cta.b64 _, [%0], %1;" ::"r"(bar), "r"(bytes) : "memory"); }
__device__ __forceinline__ void mbar_arrive(uint32_t bar) { asm volatile("mbarrier.arrive.shared::cta.b64 _, [%0];" ::"r"(bar) : "memory"); }
__device__ __forceinline__ void mbar_arrive_cl(uint32_t cbar) { asm volatile("mbarrier.arrive.shared::cluster.b64 _, [%0];" ::"r"(cbar) : "memory"); }
__device__ __forceinline__ void mbar_wait(uint32_t bar, uint32_t parity) {
  asm volatile(
      "{\n.reg .pred p;\n.reg .u32 c;\n"
      "mbarrier.try_wait.parity.shared::cta.b64 p, [%0], %1;\n"
      "@p bra.uni LAB_DONE;\n"
      "mov.u32 c, 0;\n"
      "LAB_WAIT:\n"
      "mbarrier.try_wait.parity.shared::cta.b64 p, [%0], %1;\n"
      "@p bra.uni LAB_DONE;\n"
      "add.u32 c, c, 1;\nsetp.lt.u32 p, c, 200000;\n@p bra.uni LAB_WAIT;\n"
      "LAB_DONE:\n}" ::"r"(bar), "r"(parity) : "memory");
}
__device__ __forceinline__ void tma2d(uint32_t dst, const CUtensorMap* m, int c0, int c1, uint32_t bar) {
  asm volatile("cp.async.bulk.tensor.2d.shared::cluster.global.mbarrier::complete_tx::bytes [%0], [%1, {%3,%4}], [%2];"
               ::"r"(dst), "l"(m), "r"(bar), "r"(c0), "r"(c1) : "memory");
}
__device__ __forceinline__ void tma3d(uint32_t dst, const CUtensorMap* m, int c0, int c1, int c2, uint32_t bar) {
  asm volatile("cp.async.bulk.tensor.3d.shared::cluster.global.mbarrier::complete_tx::bytes [%0], [%1, {%3,%4,%5}], [%2];"
               ::"r"(dst), "l"(m), "r"(bar), "r"(c0), "r"(c1), "r"(c2) : "memory");
}
__device__ __forceinline__ void tma4d(uint32_t dst, const CUtensorMap* m, int c0, int c3, uint32_t bar) {
  asm volatile("cp.async.bulk.tensor.4d.shared::cluster.global.mbarrier::complete_tx::bytes [%0], [%1, {%3,%5,%5,%4}], [%2];"
               ::"r"(dst), "l"(m), "r"(bar), "r"(c0), "r"(c3), "r"(0) : "memory");
}
__device__ __forceinline__ void tma5d(uint32_t dst, const CUtensorMap* m, int c0, int c3, int c4, uint32_t bar) {
  asm volatile("cp.async.bulk.tensor.5d.shared::cluster.global.mbarrier::complete_tx::bytes [%0], [%1, {%3,%6,%6,%4,%5}], [%2];"
               ::"r"(dst), "l"(m), "r"(bar), "r"(c0), "r"(c3), "r"(c4), "r"(0) : "memory");
}
__device__ __forceinline__ void tma5d_mc(uint32_t dst, const CUtensorMap* m, int c0, int c3, int c4, uint32_t bar) {
  asm volatile("cp.async.bulk.tensor.5d.shared::cluster.global.mbarrier::complete_tx::bytes.multicast::cluster [%0], [%1, {%3,%6,%6,%4,%5}], [%2], %7;"
               ::"r"(dst), "l"(m), "r"(bar), "r"(c0), "r"(c3), "r"(c4), "r"(0), "h"((uint16_t)3) : "memory");
}
__device__ __forceinline__ void map_prefetch(const CUtensorMap* m) { asm volatile("prefetch.tensormap [%0];" ::"l"(m) : "memory"); }
__device__ __forceinline__ bool elect_one() {
  uint32_t pred;
  asm volatile("{.reg .pred P; elect.sync _|P, 0xffffffff; selp.u32 %0, 1, 0, P;}" : "=r"(pred));
  return pred != 0;
}
__device__ __forceinline__ void cluster_wait() { asm volatile("barrier.cluster.wait.aligned;" ::: "memory"); }
__device__ __forceinline__ void wg_fence() { asm volatile("wgmma.fence.sync.aligned;" ::: "memory"); }
__device__ __forceinline__ void wg_commit() { asm volatile("wgmma.commit_group.sync.aligned;" ::: "memory"); }
template <int N> __device__ __forceinline__ void wg_wait() { asm volatile("wgmma.wait_group.sync.aligned %0;" ::"n"(N) : "memory"); }
__device__ __forceinline__ void pin(float& a) { asm volatile("" : "+f"(a)::"memory"); }
__device__ __forceinline__ void pin(uint32_t& a) { asm volatile("" : "+r"(a)::"memory"); }
template <int N> __device__ __forceinline__ void reg_fence(float (&d)[N]) {
#pragma unroll
  for (int i = 0; i < N; i++) pin(d[i]);
}
__device__ __forceinline__ void sched_fence(uint32_t& ck) { asm volatile("{.reg .b32 c; mov.u32 c, %%clock; xor.b32 %0, %0, c;}" : "+r"(ck)::"memory"); }
__device__ __forceinline__ void bar_sync(int id, int n) { asm volatile("bar.sync %0, %1;" ::"r"(id), "r"(n) : "memory"); }
__device__ __forceinline__ void bar_arrive(int id, int n) { asm volatile("bar.arrive %0, %1;" ::"r"(id), "r"(n) : "memory"); }
constexpr uint32_t DH128 = (1024 >> 4) | (1u << 30), DH64 = (512 >> 4) | (2u << 30);
__host__ __device__ constexpr uint32_t lbo(uint32_t bytes) { return (bytes >> 4) << 20; }
__device__ __forceinline__ uint32_t pack_bf16(float lo, float hi) { uint32_t r; asm("cvt.rn.bf16x2.f32 %0, %1, %2;" : "=r"(r) : "f"(hi), "f"(lo)); return r; }
__device__ __forceinline__ float bf_lo(uint32_t v) { return __uint_as_float(v << 16); }
__device__ __forceinline__ float bf_hi(uint32_t v) { return __uint_as_float(v & 0xffff0000u); }
__device__ __forceinline__ float bf_ld(const __nv_bfloat16* p) { return __bfloat162float(__ldg(p)); }
__device__ __forceinline__ uint32_t late16(uint32_t bar) {
  uint32_t r;
  asm volatile("{.reg .pred p; mbarrier.test_wait.parity.shared::cta.b64 p, [%1], 0; selp.u32 %0, 16, 0, p;}" : "=r"(r) : "r"(bar) : "memory");
  return r;
}
__device__ __forceinline__ float2 lds_f2(uint32_t a) { float2 v; asm volatile("ld.shared.v2.f32 {%0,%1}, [%2];" : "=f"(v.x), "=f"(v.y) : "r"(a)); return v; }
__device__ __forceinline__ uint32_t lds_h(uint32_t a) { uint32_t v; asm volatile("ld.shared.u16 %0, [%1];" : "=r"(v) : "r"(a)); return v; }
__device__ __forceinline__ uint32_t lds_u(uint32_t a) { uint32_t v; asm volatile("ld.shared.u32 %0, [%1];" : "=r"(v) : "r"(a)); return v; }
__device__ __forceinline__ uint4 lds_u4(uint32_t a) { uint4 v; asm volatile("ld.shared.v4.u32 {%0,%1,%2,%3}, [%4];" : "=r"(v.x), "=r"(v.y), "=r"(v.z), "=r"(v.w) : "r"(a)); return v; }
__device__ __forceinline__ void sts_u(uint32_t a, uint32_t v) { asm volatile("st.shared.u32 [%0], %1;" ::"r"(a), "r"(v) : "memory"); }
__device__ __forceinline__ void sts_u2(uint32_t a, uint32_t x, uint32_t y) { asm volatile("st.shared.v2.u32 [%0], {%1,%2};" ::"r"(a), "r"(x), "r"(y) : "memory"); }
__device__ __forceinline__ void sts_f2(uint32_t a, float x, float y) { asm volatile("st.shared.v2.f32 [%0], {%1,%2};" ::"r"(a), "f"(x), "f"(y) : "memory"); }
__device__ __forceinline__ void sts_f4(uint32_t a, float x, float y, float z, float w) {
  asm volatile("st.shared.v4.f32 [%0], {%1,%2,%3,%4};" ::"r"(a), "f"(x), "f"(y), "f"(z), "f"(w) : "memory");
}
__device__ __forceinline__ void st_b128(uint4* p, uint32_t a, uint32_t b, uint32_t c, uint32_t d) {
  asm volatile("st.relaxed.gpu.global.v4.b32 [%0], {%1,%2,%3,%4};" ::"l"(p), "r"(a), "r"(b), "r"(c), "r"(d) : "memory");
}
__device__ __forceinline__ void ld_b128(const uint4* p, uint32_t& a, uint32_t& b, uint32_t& c, uint32_t& d) {
  asm volatile("{.reg .b64 l, h; .reg .b128 v; ld.relaxed.gpu.global.b128 v, [%4]; mov.b128 {l,h}, v; mov.b64 {%0,%1}, l; mov.b64 {%2,%3}, h;}"
               : "=r"(a), "=r"(b), "=r"(c), "=r"(d) : "l"(p) : "memory");
}
__device__ __forceinline__ uint32_t bf2_mul(uint32_t a, uint32_t b) { uint32_t r; asm("mul.rn.bf16x2 %0, %1, %2;" : "=r"(r) : "r"(a), "r"(b)); return r; }
__device__ __forceinline__ uint32_t bf2_add(uint32_t a, uint32_t b) { uint32_t r; asm("add.rn.bf16x2 %0, %1, %2;" : "=r"(r) : "r"(a), "r"(b)); return r; }
__device__ __forceinline__ uint32_t bf2_fma(uint32_t a, uint32_t b, uint32_t c) { uint32_t r; asm("fma.rn.bf16x2 %0, %1, %2, %3;" : "=r"(r) : "r"(a), "r"(b), "r"(c)); return r; }
__device__ __forceinline__ uint32_t gelu2_pair(float a, float b) {
  const uint32_t v = pack_bf16(a, b);
  uint32_t t;
  asm("tanh.approx.bf16x2 %0, %1;" : "=r"(t) : "r"(bf2_fma(v, bf2_fma(bf2_mul(v, v), 0x3d123d12u, 0xbe4fbe4fu), v)));
  return bf2_fma(v, t, v);
}
struct cplx { float re, im; };
__device__ __forceinline__ cplx cmul(cplx a, cplx b) { return {fmaf(a.re, b.re, -a.im * b.im), fmaf(a.re, b.im, a.im * b.re)}; }
__device__ __forceinline__ cplx cfma(cplx a, cplx b, cplx c) {
  return {fmaf(a.re, b.re, fmaf(-a.im, b.im, c.re)), fmaf(a.re, b.im, fmaf(a.im, b.re, c.im))};
}
__device__ __forceinline__ cplx make_lam(float lre, float lim, float ldt) {
  float dt = __bfloat162float(__float2bfloat16_rn(expf(ldt)));
  float mag = expf(dt * lre), sn, cs;
  sincospif(dt * lim * 0.31830988618379067f, &sn, &cs);
  return {mag * cs, mag * sn};
}

__device__ __forceinline__ void gate_rows(uint32_t sb, int lane, int xrot, int row0, uint4 (&gw)[4], const uint4* gwp, unsigned* dst, unsigned par) {
  const int row = row0 + (lane >> 3);
  const uint32_t xr0 = sb + OFF_X + row * 128 + (((lane & 7) ^ (row & 7)) << 4), xr1 = (xr0 + 512) ^ 64;
  float z[2], y[2];
#pragma unroll
  for (int r = 0; r < 2; r++) z[r] = y[r] = 0.f;
#pragma unroll
  for (int kb = 0; kb < 8; kb++) {
    const uint4 w = gw[kb & 3];
    if (kb < 4) gw[kb] = __ldg(gwp + (kb + 4) * 8);
    mbar_wait(sb + OFF_XFULL + 8 * kb, 0);
#pragma unroll
    for (int r = 0; r < 2; r++) {
      const uint4 a = lds_u4((r ? xr1 : xr0) + ((kb + xrot) & 7) * 16384);
      const uint32_t p[4] = {bf2_mul(a.x, w.x), bf2_mul(a.y, w.y), bf2_mul(a.z, w.z), bf2_mul(a.w, w.w)};
#pragma unroll
      for (int c = 0; c < 4; c++) { z[r] += bf_lo(p[c]); y[r] += bf_hi(p[c]); }
    }
  }
  float zz = z[0] + y[0];
  const float z1 = z[1] + y[1];
  zz = ((lane & 4) ? z1 : zz) + __shfl_xor_sync(0xffffffffu, (lane & 4) ? zz : z1, 4);
  zz += __shfl_xor_sync(0xffffffffu, zz, 2);
  zz += __shfl_xor_sync(0xffffffffu, zz, 1);
  zz = bf_lo(pack_bf16(zz, 0.f));
  const float rho = 4.f * expf(zz > 40.f ? 40.f : zz);
  if ((lane & 3) == 0)
    asm volatile("st.relaxed.gpu.global.u32 [%0], %1;" ::"l"(dst + row + (lane & 4)), "r"((__float_as_uint(rho) & ~1u) | par) : "memory");
}

template<int TB,uint32_t BH,int SA=1> __device__ __forceinline__ void wgmma_n64_rs(float (&d)[32], uint32_t a0,uint32_t a1,uint32_t a2,uint32_t a3, uint32_t bl, uint32_t bo, int scale_d){
  asm volatile("{.reg .pred p; .reg .b32 t; .reg .b64 db; setp.ne.b32 p, %38, 0; add.u32 t, %36, %37; mov.b64 db, {t, %40};\n"
   "wgmma.mma_async.sync.aligned.m64n64k16.f32.bf16.bf16 {%0,%1,%2,%3,%4,%5,%6,%7,%8,%9,%10,%11,%12,%13,%14,%15,%16,%17,%18,%19,%20,%21,%22,%23,%24,%25,%26,%27,%28,%29,%30,%31}, {%32,%33,%34,%35}, db, p, %41, 1, %39;}"
   : "+f"(d[0]),"+f"(d[1]),"+f"(d[2]),"+f"(d[3]),"+f"(d[4]),"+f"(d[5]),"+f"(d[6]),"+f"(d[7]),"+f"(d[8]),"+f"(d[9]),"+f"(d[10]),"+f"(d[11]),"+f"(d[12]),"+f"(d[13]),"+f"(d[14]),"+f"(d[15]),"+f"(d[16]),"+f"(d[17]),"+f"(d[18]),"+f"(d[19]),"+f"(d[20]),"+f"(d[21]),"+f"(d[22]),"+f"(d[23]),"+f"(d[24]),"+f"(d[25]),"+f"(d[26]),"+f"(d[27]),"+f"(d[28]),"+f"(d[29]),"+f"(d[30]),"+f"(d[31])
   : "r"(a0),"r"(a1),"r"(a2),"r"(a3),"r"(bl),"r"(bo >> 4),"r"(scale_d),"n"(TB),"n"(BH),"n"(SA));
}
template<int TA,int TB,uint32_t AH,uint32_t BH> __device__ __forceinline__ void wgmma_n96_ss(float (&d)[48], uint32_t al, uint32_t ao, uint32_t bl, uint32_t bo, int scale_d){
  asm volatile("{.reg .pred p; .reg .b32 t, v; .reg .b64 da, db; setp.ne.b32 p, %52, 0; add.u32 t, %48, %49; mov.b64 da, {t, %55}; add.u32 v, %50, %51; mov.b64 db, {v, %56};\n"
   "wgmma.mma_async.sync.aligned.m64n96k16.f32.bf16.bf16 {%0,%1,%2,%3,%4,%5,%6,%7,%8,%9,%10,%11,%12,%13,%14,%15,%16,%17,%18,%19,%20,%21,%22,%23,%24,%25,%26,%27,%28,%29,%30,%31,%32,%33,%34,%35,%36,%37,%38,%39,%40,%41,%42,%43,%44,%45,%46,%47}, da, db, p, 1, 1, %53, %54;}"
   : "+f"(d[0]),"+f"(d[1]),"+f"(d[2]),"+f"(d[3]),"+f"(d[4]),"+f"(d[5]),"+f"(d[6]),"+f"(d[7]),"+f"(d[8]),"+f"(d[9]),"+f"(d[10]),"+f"(d[11]),"+f"(d[12]),"+f"(d[13]),"+f"(d[14]),"+f"(d[15]),"+f"(d[16]),"+f"(d[17]),"+f"(d[18]),"+f"(d[19]),"+f"(d[20]),"+f"(d[21]),"+f"(d[22]),"+f"(d[23]),"+f"(d[24]),"+f"(d[25]),"+f"(d[26]),"+f"(d[27]),"+f"(d[28]),"+f"(d[29]),"+f"(d[30]),"+f"(d[31]),"+f"(d[32]),"+f"(d[33]),"+f"(d[34]),"+f"(d[35]),"+f"(d[36]),"+f"(d[37]),"+f"(d[38]),"+f"(d[39]),"+f"(d[40]),"+f"(d[41]),"+f"(d[42]),"+f"(d[43]),"+f"(d[44]),"+f"(d[45]),"+f"(d[46]),"+f"(d[47])
   : "r"(al),"r"(ao >> 4),"r"(bl),"r"(bo >> 4),"r"(scale_d),"n"(TA),"n"(TB),"n"(AH),"n"(BH));
}
template<int TA,int TB,uint32_t AH,uint32_t BH> __device__ __forceinline__ void wgmma_n128_ss(float (&d)[64], uint32_t al, uint32_t ao, uint32_t bl, uint32_t bo, int scale_d){
  asm volatile("{.reg .pred p; .reg .b32 t, v; .reg .b64 da, db; setp.ne.b32 p, %68, 0; add.u32 t, %64, %65; mov.b64 da, {t, %71}; add.u32 v, %66, %67; mov.b64 db, {v, %72};\n"
   "wgmma.mma_async.sync.aligned.m64n128k16.f32.bf16.bf16 {%0,%1,%2,%3,%4,%5,%6,%7,%8,%9,%10,%11,%12,%13,%14,%15,%16,%17,%18,%19,%20,%21,%22,%23,%24,%25,%26,%27,%28,%29,%30,%31,%32,%33,%34,%35,%36,%37,%38,%39,%40,%41,%42,%43,%44,%45,%46,%47,%48,%49,%50,%51,%52,%53,%54,%55,%56,%57,%58,%59,%60,%61,%62,%63}, da, db, p, 1, 1, %69, %70;}"
   : "+f"(d[0]),"+f"(d[1]),"+f"(d[2]),"+f"(d[3]),"+f"(d[4]),"+f"(d[5]),"+f"(d[6]),"+f"(d[7]),"+f"(d[8]),"+f"(d[9]),"+f"(d[10]),"+f"(d[11]),"+f"(d[12]),"+f"(d[13]),"+f"(d[14]),"+f"(d[15]),"+f"(d[16]),"+f"(d[17]),"+f"(d[18]),"+f"(d[19]),"+f"(d[20]),"+f"(d[21]),"+f"(d[22]),"+f"(d[23]),"+f"(d[24]),"+f"(d[25]),"+f"(d[26]),"+f"(d[27]),"+f"(d[28]),"+f"(d[29]),"+f"(d[30]),"+f"(d[31]),"+f"(d[32]),"+f"(d[33]),"+f"(d[34]),"+f"(d[35]),"+f"(d[36]),"+f"(d[37]),"+f"(d[38]),"+f"(d[39]),"+f"(d[40]),"+f"(d[41]),"+f"(d[42]),"+f"(d[43]),"+f"(d[44]),"+f"(d[45]),"+f"(d[46]),"+f"(d[47]),"+f"(d[48]),"+f"(d[49]),"+f"(d[50]),"+f"(d[51]),"+f"(d[52]),"+f"(d[53]),"+f"(d[54]),"+f"(d[55]),"+f"(d[56]),"+f"(d[57]),"+f"(d[58]),"+f"(d[59]),"+f"(d[60]),"+f"(d[61]),"+f"(d[62]),"+f"(d[63])
   : "r"(al),"r"(ao >> 4),"r"(bl),"r"(bo >> 4),"r"(scale_d),"n"(TA),"n"(TB),"n"(AH),"n"(BH));
}

__global__ void __cluster_dims__(2, 1, 1) __launch_bounds__(384, 1)
fused_kernel(const __nv_bfloat16* __restrict__ lam_re, const __nv_bfloat16* __restrict__ lam_im, const __nv_bfloat16* __restrict__ log_dt,
             const __nv_bfloat16* __restrict__ dskip, const __nv_bfloat16* __restrict__ b1, const __nv_bfloat16* __restrict__ b2,
             const __nv_bfloat16* __restrict__ gate_w, float* __restrict__ out, float sgn, const __grid_constant__ Maps maps) {
  extern __shared__ __align__(1024) unsigned char smem_raw[];
  const uint32_t sb = (uint32_t)__cvta_generic_to_shared(smem_raw);
  const int b = blockIdx.x;
  const int rank = b & 1, cl = b >> 1;
  const int sp = (cl & 1) | ((cl >> 2) & 2), m = ((cl >> 1) & 3) | ((cl >> 4) << 2);
  const int s = sp * 2 + rank;
  const int xrot = 9 - 2 * sp;
  if (threadIdx.x == 0) {
    mbar_init(sb + OFF_XFULL, 1);
    mbar_expect_tx(sb + OFF_XFULL, 16384);
    tma5d(sb + OFF_X + (xrot & 7) * 16384, &maps.x, 0, 0, m, sb + OFF_XFULL);
    tma5d(sb + OFF_X + (xrot & 7) * 16384 + 8192, &maps.x, 0, 8, m, sb + OFF_XFULL);
  }
  if (threadIdx.x == 128) {
    mbar_init(sb + OFF_FULL, 1);
    mbar_expect_tx(sb + OFF_FULL, 16384);
    tma4d(sb + OFF_RING, &maps.bb, 0, s * 8, sb + OFF_FULL);
  }
  const int warp = __shfl_sync(0xffffffffu, (int)(threadIdx.x >> 5), 0);
  const int lane0 = threadIdx.x & 31;

  if (elect_one()) {
    if (warp > 8) {
      map_prefetch(&maps.x + (warp - 9));
      mbar_init(sb + OFF_GBAR + 8 * (warp - 9), warp < 11 ? 64 : 96);
    }
    const uint32_t c = warp < 8 ? 1 : warp < 11 ? 8 : 4, bar = sb + OFF_XFULL + 16 * warp;
    if ((warp & 11) != 0) mbar_init(bar, c);
    mbar_init(bar + 8, c);
    asm volatile("fence.mbarrier_init.release.cluster;" ::: "memory");
  }
  __syncwarp();
  asm volatile("barrier.cluster.arrive.relaxed.aligned;" ::: "memory");

  if (warp < 8) {
    const int lane = __shfl_sync(0xffffffffu, lane0, lane0);
    const int wg = warp >> 2, w = warp & 3, q = lane & 3, gr = lane >> 2;
    uint32_t bv[28];
#pragma unroll
    for (int j = 0; j < 28; j++) bv[j] = __ldg(reinterpret_cast<const uint32_t*>(b1 + s * 224 + j * 8) + q);
    asm volatile("setmaxnreg.inc.sync.aligned.u32 224;");
    cluster_wait();
    auto release = [&](int slot) { if (lane == 0) mbar_arrive(sb + OFF_EMPTY + 8 * slot); };
    const uint32_t xw = sb + OFF_X + wg * 8192, fullb = sb + OFF_FULL;
    const uint32_t dxw = (xw & 0x3FFFF) >> 4, dring = ((sb + OFF_RING) & 0x3FFFF) >> 4;

    float uu[64], aa[48], ab[64];
    cplx lam, coef, l16, l32, l64, lq, pre, e[2];
    uint32_t sh16, mhi, ck = 0;
    const uint32_t dx0 = ((sb + OFF_X) & 0x3FFFF) >> 4;

    auto bias = [&](int c) {
#pragma unroll
      for (int j = c * 7; j < c * 7 + 7; j++) {
        pin(bv[j]);
        float* d = j < 12 ? aa + 4 * j : ab + 4 * (j - 12);
        d[0] = d[2] = __uint_as_float(bv[j] << sh16); d[1] = d[3] = __uint_as_float(bv[j] & mhi);
        pin(d[0]); pin(d[1]); pin(d[2]); pin(d[3]);
      }
    };
#pragma unroll
    for (int kb = 0; kb < 8; kb++) {
      const int slot = kb % NSLOT;
      mbar_wait(sb + OFF_XFULL + 8 * kb, 0);
      if (kb == 0) mbar_wait(fullb, 0);
      if (kb == 2) { sh16 = late16(sb + OFF_XFULL); mhi = 0xffffffffu << sh16; }
      if (kb == 4) {
        mbar_wait(sb + OFF_LBAR, 0);
        const uint4 v = lds_u4(sb + OFF_LC + (warp * 8 + gr) * 16);
        lam = cplx{__uint_as_float(v.x), __uint_as_float(v.y)};
        coef = cplx{__uint_as_float(v.z), __uint_as_float(v.w)};
      }
      wg_fence();
      const uint32_t dxa = dx0 + ((kb + xrot) & 7) * 1024;
#pragma unroll
      for (int kk = 0; kk < 4; kk++)
        wgmma_n128_ss<0, 0, DH128, DH128>(uu, dring + wg * 512, slot * 16384 + kk * 32, dxa, kk * 32, (kb | kk) != 0);
      wg_commit();
      if (kb > 0) { wg_wait<1>(); release((kb - 1) % NSLOT); }
      if (kb >= 2 && kb < 6) bias(kb - 2);
      if (kb == 6) {
        pin(lam.re); pin(lam.im);
        cplx t = cmul(lam, lam); t = cmul(t, t); t = cmul(t, t);
        l16 = cmul(t, t); l32 = cmul(l16, l16); l64 = cmul(l32, l32);
        const cplx a = (q & 1) ? l32 : cplx{1.f, 0.f}, c = (q & 2) ? l64 : cplx{1.f, 0.f};
        lq = cmul(cmul(a, c), coef);
        pin(lq.re); pin(lq.im);
      }
    }
    auto scale_u = [&](int c) {
#pragma unroll
      for (int n = 0; n < 8; n++) {
        const int i = (n >> 2) * 32 + c * 8 + (n & 2) * 2 + (n & 1);
        pin(uu[i]); pin(uu[i + 2]);
        const cplx v = cmul(coef, cplx{uu[i], uu[i + 2]});
        uu[i] = v.re; uu[i + 2] = v.im;
        pin(uu[i]); pin(uu[i + 2]);
      }
    };
#pragma unroll
    for (int kb = 0; kb < 8; kb++) {
      const int u = 8 + kb, slot = u % NSLOT;
      mbar_wait(fullb + 8 * slot, full_par(u));
      wg_fence();
      const uint32_t dxa = dxw + ((kb + xrot) & 7) * 1024;
#pragma unroll
      for (int kk = 0; kk < 4; kk++)
        wgmma_n96_ss<0, 1, DH128, DH64>(aa, dxa, kk * 32, dring, slot * 16384 + kk * 1024 + lbo(4096), 1);
      wg_commit();
      if (kb != 4) { wg_wait<1>(); release((u - 1) % NSLOT); }
      if (kb == 0) {
        reg_fence(uu);
#pragma unroll
        for (int h = 0; h < 2; h++) e[h] = cplx{uu[32 * h], uu[32 * h + 2]};
      }
      if (kb == 0 || kb == 2 || kb == 3) {
        const int t0 = kb ? 5 * kb - 4 : 1;
#pragma unroll
        for (int t = t0; t < t0 + 5; t++) {
#pragma unroll
          for (int h = 0; h < 2; h++) { const int i = 32 * h + 4 * (t >> 1) + (t & 1); e[h] = cfma(lam, e[h], cplx{uu[i], uu[i + 2]}); }
        }
#pragma unroll
        for (int h = 0; h < 2; h++) { pin(e[h].re); pin(e[h].im); }
      }
      if (kb == 4) {
        sched_fence(ck);
        e[1] = cfma(l16, e[0], e[1]);
        cplx y = {__shfl_up_sync(0xffffffffu, e[1].re, 1, 4), __shfl_up_sync(0xffffffffu, e[1].im, 1, 4)};
        if (q >= 1) e[1] = cfma(l32, y, e[1]);
        y = cplx{__shfl_up_sync(0xffffffffu, e[1].re, 2, 4), __shfl_up_sync(0xffffffffu, e[1].im, 2, 4)};
        if (q >= 2) e[1] = cfma(l64, y, e[1]);
        if (q == 3) {
          sts_f2(sb + OFF_CARRY + (warp * 8 + gr) * 8, e[1].re, e[1].im);
          mbar_arrive(sb + OFF_GBAR);
        }
        e[1] = cplx{__shfl_up_sync(0xffffffffu, e[1].re, 1, 4), __shfl_up_sync(0xffffffffu, e[1].im, 1, 4)};
        wg_wait<1>(); release((u - 1) % NSLOT);
      }
      if (kb == 5) {
        pre = (q >= 1) ? cmul(coef, e[1]) : cplx{0.f, 0.f};
        e[0] = cmul(coef, e[0]);
        pin(pre.re); pin(pre.im); pin(e[0].re); pin(e[0].im);
      }
      if (kb > 4) scale_u(kb - 5);
    }
    uint32_t H[56], hf[32];
    cplx hst[2];
    const uint32_t hst_addr = sb + OFF_X + (lane & 8) * 1024 + (warp * 8 + (lane & 7)) * 128 + (((lane >> 4) ^ (lane & 7)) << 4);
    const uint32_t him = (2 - rank) * 16384;
    uint32_t peer;
    asm volatile("mapa.shared::cluster.u32 %0, %1, %2;" : "=r"(peer) : "r"(sb), "r"(rank ^ 1));
    auto credit = [&]() { if (lane == 0) mbar_arrive_cl(peer + OFF_KBAR + wg * 8); };
    uint4 g2;
#pragma unroll
    for (int kb = 0; kb < 8; kb++) {
      const int u = 16 + kb, slot = u % NSLOT;
      mbar_wait(fullb + 8 * slot, full_par(u));
      wg_fence();
#pragma unroll
      for (int kk = 0; kk < 4; kk++)
        wgmma_n128_ss<0, 1, DH128, DH128>(ab, dxw, kb * 16384 + kk * 32, dring, slot * 16384 + kk * 2048 + lbo(8192), 1);
      wg_commit();
      if (kb == 0) scale_u(3);
      if (kb == 4) {
        mbar_wait(sb + OFF_CBAR, 0);
        const float2 c = lds_f2(sb + OFF_CARRY + (warp * 8 + gr) * 8);
        mbar_wait(sb + OFF_EMPTY, 1);
        hst[0] = cfma(lq, cplx{c.x, c.y}, pre);
        hst[1] = cfma(l16, hst[0], e[0]);
      }
      if (kb >= 4) g2 = lds_u4(sb + OFF_GT + (kb - 4) * 64 + q * 16);
      wg_wait<1>(); release((u - 1) % NSLOT);
      if (kb) sched_fence(ck);
      if (kb < 4) {
#pragma unroll
        for (int i = kb * 6; i < kb * 6 + 6; i++) {
          pin(aa[2 * i]); pin(aa[2 * i + 1]);
          H[i] = gelu2_pair(aa[2 * i], aa[2 * i + 1]);
          pin(H[i]);
        }
      } else {
        const int j0 = (kb - 4) * 2;
        uint32_t rr[4], ri[4];
#pragma unroll
        for (int jj = 0; jj < 2; jj++) {
          const int j = j0 + jj;
#pragma unroll
          for (int h = 0; h < 2; h++) {
            const int i = 32 * h + 4 * j;
            const uint32_t g = jj ? (h ? g2.w : g2.z) : (h ? g2.y : g2.x);
            const cplx h0 = cfma(lam, hst[h], cplx{uu[i], uu[i + 2]});
            hst[h] = cfma(lam, h0, cplx{uu[i + 1], uu[i + 3]});
            rr[jj * 2 + h] = bf2_mul(pack_bf16(h0.re, hst[h].re), g);
            ri[jj * 2 + h] = bf2_mul(pack_bf16(h0.im, hst[h].im), g);
          }
        }
        const uint32_t a = hst_addr ^ (j0 << 4);
        asm volatile("stmatrix.sync.aligned.m8n8.x4.shared.b16 [%0], {%1,%2,%3,%4};" ::"r"(a), "r"(rr[0]), "r"(rr[1]), "r"(rr[2]), "r"(rr[3]) : "memory");
        asm volatile("stmatrix.sync.aligned.m8n8.x4.shared.b16 [%0], {%1,%2,%3,%4};" ::"r"(a + him), "r"(ri[0]), "r"(ri[1]), "r"(ri[2]), "r"(ri[3]) : "memory");
        if (kb == 7) { __syncwarp(); if (q == 3) mbar_arrive(sb + OFF_GBAR); }
      }
    }

    uint4* const psend = g_part + (size_t)(m * 8 + rank) * 3072 + warp * 128 + lane;
    const uint4* const precv = g_part + (size_t)(m * 8 + s) * 3072 + warp * 128 + lane;
    const uint32_t pbuf = OFF_X + warp * 2048 + lane * 16;
    float o[32], fin[32], fs[2];
    uint32_t r0[16], pt[16], sum[16], tag;
    auto recv_issue = [&](uint32_t (&r)[16], int k) {
#pragma unroll
      for (int i = 0; i < 4; i++) ld_b128(precv + k * 1024 + i * 32, r[4 * i], r[4 * i + 1], r[4 * i + 2], r[4 * i + 3]);
    };
    auto stale = [&](uint32_t (&r)[16]) {
      uint32_t r_;
#pragma unroll
      for (int i = 0; i < 16; i += 4) asm("lop3.b32 %0, %0, %1, 1, 0x78;" : "+r"(r[i]) : "r"(tag));
      asm volatile("{.reg .pred p; .reg .b32 t; lop3.b32 t, %1, %2, %3, 0xfe; lop3.b32 t, t, %4, 1, 0xa8; setp.ne.u32 p, t, 0; vote.sync.any.pred p, p, 0xffffffff; selp.u32 %0, 1, 0, p;}"
                   : "=r"(r_) : "r"(r[0]), "r"(r[4]), "r"(r[8]), "r"(r[12]));
      return r_ != 0;
    };
    auto recv_check = [&](uint32_t (&r)[16], int k) {
      if (__builtin_expect(stale(r), 0)) {
        int tries = 0;
#pragma unroll 1
        do { recv_issue(r, k); } while (stale(r) && ++tries < 200000);
      }
    };
    auto gelu_b = [&](int i0, int i1) {
#pragma unroll
      for (int i = i0; i < i1; i++) {
        pin(ab[2 * i]); pin(ab[2 * i + 1]);
        H[24 + i] = gelu2_pair(ab[2 * i], ab[2 * i + 1]);
        pin(H[24 + i]);
      }
    };
    auto mma = [&](float (&d)[32], int p, int k0, int k1, int acc) {
      const uint32_t wo = stage_off(p);
      wg_fence();
#pragma unroll
      for (int k = k0; k < k1; k++) {
        if (k >= 6 && k < 14) {
          const int kk = k - 6;
          if (kk < 4) wgmma_n64_rs<0, DH128, 1>(d, hf[4 * kk], hf[4 * kk + 1], hf[4 * kk + 2], hf[4 * kk + 3], dx0, wo + 14336 + kk * 32, 1);
          else wgmma_n64_rs<0, DH128, -1>(d, hf[4 * kk], hf[4 * kk + 1], hf[4 * kk + 2], hf[4 * kk + 3], dx0, wo + 22528 + (kk - 4) * 32, 1);
        } else {
          const int kk = k < 6 ? k : k - 8;
          wgmma_n64_rs<1, DH128>(d, H[4 * kk], H[4 * kk + 1], H[4 * kk + 2], H[4 * kk + 3], dx0, wo + (kk / 7) * 30720 + (kk % 7) * 2048, k != 0 || acc);
        }
      }
      wg_commit();
    };
    auto recv_peer = [&](int k) {
      mbar_wait(sb + OFF_RBAR + wg * 8, k & 1);
#pragma unroll
      for (int i = 0; i < 4; i++) { const uint4 v = lds_u4(sb + pbuf + i * 512); pt[4 * i] = v.x; pt[4 * i + 1] = v.y; pt[4 * i + 2] = v.z; pt[4 * i + 3] = v.w; }
    };
#pragma unroll
    for (int p = 0; p < 8; p++) {
      if (p == 0) {
        mbar_wait(fullb, full_par(24));
        mma(o, 0, 0, 4, 0);
        mbar_wait(fullb + 8, full_par(25));
        wg_wait<1>(); release(5);
        gelu_b(0, 8);
        mma(o, 0, 4, 6, 0);
        mbar_wait(sb + OFF_GBAR, 1);
        {
          const uint32_t ha = xw + ((lane >> 4) * 8 + (lane & 7)) * 128 + (((2 * w + ((lane >> 3) & 1)) ^ (lane & 7)) << 4);
#pragma unroll
          for (int kk = 0; kk < 8; kk++)
            asm volatile("ldmatrix.sync.aligned.m8n8.x4.trans.shared.b16 {%0,%1,%2,%3}, [%4];" : "=r"(hf[4 * kk]), "=r"(hf[4 * kk + 1]), "=r"(hf[4 * kk + 2]), "=r"(hf[4 * kk + 3])
                         : "r"(ha + (kk >> 2) * him + (kk & 3) * 2048) : "memory");
        }
        gelu_b(8, 12);
        mma(o, 0, 6, 10, 0);
        credit();
        gelu_b(12, 19);
        mbar_wait(fullb + 16, full_par(26));
        mma(o, 0, 10, 14, 0);
        gelu_b(19, 26);
        mma(o, 0, 14, 17, 0);
        gelu_b(26, 32);
        if (wg == 1) bar_sync(4, 256);
        mma(o, 0, 17, 22, 0);
      } else {
        bar_sync(3 + wg, 256);
        if (p < 7) mma(o, p, 0, 22, 0); else mma(fin, p, 0, 22, 1);
      }
      if (p < 7 || wg == 0) bar_arrive(4 - wg, 256);
      if (p < 7) mbar_wait(sb + OFF_XFULL + 8 * (p + 1), 1);
      if ((p & 1) == 0) {
        if (w == 0 && lane == 0) mbar_expect_tx(sb + OFF_RBAR + wg * 8, 8192);
        if (p == 6) {
          mbar_wait(sb + OFF_EMPTY + 32, 0);
          tag = lds_u(sb + OFF_EPOCH);
          recv_check(sum, 0); recv_check(r0, 1);
#pragma unroll
          for (int i = 0; i < 16; i++) sum[i] = bf2_add(sum[i], r0[i]);
        }
        mbar_wait(sb + OFF_KBAR + wg * 8, (p >> 1) & 1);
      } else {
        if (p == 1 || p == 7) tag = lds_u(sb + OFF_EPOCH);
        recv_peer(p >> 1);
        if (p == 7) {
          recv_check(r0, 2);
#pragma unroll
          for (int i = 0; i < 16; i++) { sum[i] = bf2_add(sum[i], bf2_add(r0[i], pt[i])); pin(sum[i]); }
          sched_fence(ck);
        }
      }
      if (p == 4) {
        mbar_wait(sb + OFF_LBAR, 1);
#pragma unroll
        for (int j = 0; j < 8; j++) {
          const uint4 v = lds_u4(sb + pbuf + 16384 + (j >> 2) * 16384 + (j & 3) * 512);
          fin[4 * j] = __uint_as_float(v.x); fin[4 * j + 1] = __uint_as_float(v.y); fin[4 * j + 2] = __uint_as_float(v.z); fin[4 * j + 3] = __uint_as_float(v.w);
        }
        recv_issue(sum, 0);
      }
      wg_wait<0>();
      if (p < 5) release(p);
      if (p < 7) reg_fence(o); else reg_fence(fin);
      if ((p & 1) == 0) {
        if (p == 6) recv_issue(r0, 2);
#pragma unroll
        for (int i = 0; i < 4; i++)
          asm volatile("st.async.shared::cluster.mbarrier::complete_tx::bytes.v4.b32 [%0], {%1,%2,%3,%4}, [%5];" ::"r"(peer + pbuf + i * 512),
                       "r"(pack_bf16(o[8 * i], o[8 * i + 1])), "r"(pack_bf16(o[8 * i + 2], o[8 * i + 3])), "r"(pack_bf16(o[8 * i + 4], o[8 * i + 5])),
                       "r"(pack_bf16(o[8 * i + 6], o[8 * i + 7])), "r"(peer + OFF_RBAR + wg * 8) : "memory");
      } else if (p < 7) {
        const int k = p >> 1;
#pragma unroll
        for (int i = 0; i < 4; i++) {
#pragma unroll
          for (int c = 4 * i; c < 4 * i + 4; c++) pt[c] = bf2_add(pt[c], pack_bf16(o[2 * c], o[2 * c + 1]));
          asm("lop3.b32 %0, %0, 1, %1, 0xb8;" : "+r"(pt[4 * i]) : "r"(tag));
          st_b128(psend + (((sp + 1 + k) & 3) * 6 + k) * 1024 + i * 32, pt[4 * i], pt[4 * i + 1], pt[4 * i + 2], pt[4 * i + 3]);
        }
        __syncwarp();
        credit();
        if (p == 5) recv_issue(r0, 1);
      }
      if (p == 2) {
#pragma unroll
        for (int h = 0; h < 2; h++) { fs[h] = __fdividef(2.f, 4.f + bf_lo(lds_h(sb + OFF_GS + (wg * 64 + w * 16 + gr + 8 * h) * 2))); pin(fs[h]); }
      }
    }
    {
      const uint32_t tb = sb + OFF_X + stage_off(0) + warp * 4096;
      const uint32_t ta = tb + gr * 256 + ((gr & 3) << 5) + q * 8;
      const uint32_t la = tb + (lane >> 3) * 256 + (((lane & 7) << 4) ^ ((lane >> 3) << 5));
      float* op = out + (size_t)(m * 128 + (lane >> 4) * 32 + warp * 4 + ((lane >> 3) & 1)) * DM + s * 64 + (lane & 7) * 4;
#pragma unroll
      for (int qt = 0; qt < 4; qt++) {
        const int h = qt & 1, ch = qt >> 1;
#pragma unroll
        for (int j = 0; j < 4; j++) {
          const int i = ch * 8 + j * 2 + h;
          sts_f2((ta ^ (j << 5)) + h * 2048 + ch * 128, (fin[2 * i] + bf_lo(sum[i])) * fs[h], (fin[2 * i + 1] + bf_hi(sum[i])) * fs[h]);
        }
        __syncwarp();
#pragma unroll
        for (int r = 0; r < 2; r++)
          *reinterpret_cast<uint4*>(op + (r * 64 + h * 2) * DM + ch * 32) = lds_u4(la + (h * 2 + r) * 1024 + ch * 128);
      }
      sts_u(sb + OFF_EPOCH + 4, ck);
      if (warp == 4 && lane == 0) g_epoch[b] = tag;
    }
  } else {
    const int lane = __shfl_sync(0xffffffffu, lane0, lane0);
    asm volatile("setmaxnreg.dec.sync.aligned.u32 56;");
    int wsel = warp;
    asm("" : "+r"(wsel));
    if (wsel > 8) {
      if (warp != 11) {
        const uint4* gwp = reinterpret_cast<const uint4*>(gate_w) + (lane & 7);
        uint4 gw[4];
        const int t = (warp - 9) * 32 + lane;
        unsigned par;
        asm volatile("ld.relaxed.gpu.global.u32 %0, [%1];" : "=r"(par) : "l"(g_epoch + b) : "memory");
        const float pr = bf_ld(lam_re + s * 64 + t), pi = sgn * bf_ld(lam_im + s * 64 + t), pd = bf_ld(log_dt + s * 64 + t);
#pragma unroll
        for (int i = 0; i < 4; i++) gw[i] = __ldg(gwp + i * 8);
        cluster_wait();
        par = __shfl_sync(0xffffffffu, (par + 1) & 1, 0);
        cplx l128 = make_lam(pr, pi, pd);
        {
          const float inv = __fdividef(sgn, fmaf(pr, pr, pi * pi));
          const cplx cf = cmul(cplx{l128.re - 1.f, l128.im}, cplx{pr * inv, -pi * inv});
          sts_f4(sb + OFF_LC + t * 16, l128.re, l128.im, cf.re, cf.im);
          mbar_arrive(sb + OFF_LBAR);
        }
#pragma unroll
        for (int i = 0; i < 7; i++) l128 = cmul(l128, l128);
        pin(l128.re); pin(l128.im);
        gate_rows(sb, lane, xrot, s * 16 + (warp - 9) * 8, gw, gwp, g_gate + m * 128, par);
        uint32_t vr[15], vi[15];
#pragma unroll
        for (int i = 0; i < 15; i++) { vr[i] = par; vi[i] = 0; pin(vr[i]); pin(vi[i]); }
        mbar_wait(sb + OFF_GBAR, 0);
        float2* eb = g_end + s * 1024 + t;
        {
          const float2 e = lds_f2(sb + OFF_CARRY + t * 8);
          const unsigned long long v = ((unsigned long long)__float_as_uint(e.y) << 32) | ((__float_as_uint(e.x) & ~1u) | par);
          asm volatile("st.relaxed.gpu.global.b64 [%0], %1;" ::"l"(eb + m * 64), "l"(v) : "memory");
        }
        __nanosleep(400);
        const float2* e15 = eb + (m - 15) * 64;
        int tries = 0;
        bool bad;
#pragma unroll 1
        do {
#pragma unroll
          for (int i = 0; i < 15; i++)
            asm volatile("{.reg .pred p; .reg .b64 v; mov.b64 v, {%0,%1}; setp.ge.s32 p, %3, %4; @p ld.relaxed.gpu.global.b64 v, [%2]; mov.b64 {%0,%1}, v;}"
                         : "+r"(vr[i]), "+r"(vi[i]) : "l"(e15 + i * 64), "r"(m), "r"(15 - i) : "memory");
          uint32_t x = vr[0] ^ par;
#pragma unroll
          for (int i = 1; i < 15; i++) asm("lop3.b32 %0, %0, %1, %2, 0xf6;" : "+r"(x) : "r"(vr[i]), "r"(par));
          bad = __any_sync(0xffffffffu, x & 1);
        } while (bad && ++tries < 200000);
        cplx S = {__uint_as_float(vr[0] ^ par), __uint_as_float(vi[0])};
#pragma unroll
        for (int i = 1; i < 15; i++) S = cfma(l128, S, cplx{__uint_as_float(vr[i] ^ par), __uint_as_float(vi[i])});
        sts_f2(sb + OFF_CARRY + t * 8, S.re, S.im);
        mbar_arrive(sb + OFF_CBAR);
        mbar_wait(sb + OFF_CBAR, 0);
        const int gr = lane >> 2, q = lane & 3;
        float2 db[8];
#pragma unroll
        for (int j = 0; j < 8; j++) db[j] = lds_f2(sb + OFF_DB + j * 32 + q * 8);
        mbar_wait(sb + OFF_XFULL + 16, 1);
        mbar_wait(sb + OFF_EMPTY, 0);
#pragma unroll 1
        for (int cw = warp - 9; cw < 8; cw += 2) {
          const float r0 = 0.5f * bf_lo(lds_h(sb + OFF_GS + (cw * 16 + gr) * 2)), r1 = 0.5f * bf_lo(lds_h(sb + OFF_GS + (cw * 16 + gr) * 2 + 16));
          const uint32_t xa = sb + OFF_X + (1 + rank) * 16384 + (cw * 16 + (lane & 15)) * 128 + (((lane >> 4) ^ (lane & 7)) << 4);
          uint32_t xv[16];
#pragma unroll
          for (int i = 0; i < 4; i++)
            asm volatile("ldmatrix.sync.aligned.m8n8.x4.shared.b16 {%0,%1,%2,%3}, [%4];" : "=r"(xv[4 * i]), "=r"(xv[4 * i + 1]), "=r"(xv[4 * i + 2]), "=r"(xv[4 * i + 3])
                         : "r"(xa ^ (i << 5)) : "memory");
          __syncwarp();
#pragma unroll
          for (int j = 0; j < 8; j++) {
            const uint32_t x0 = bf2_mul(xv[2 * j], __float_as_uint(db[j].x)), x1 = bf2_mul(xv[2 * j + 1], __float_as_uint(db[j].x));
            pin(db[j].y);
            const float bl = bf_lo(__float_as_uint(db[j].y)), bh = bf_hi(__float_as_uint(db[j].y));
            sts_f4(sb + OFF_X + 16384 + (j >> 2) * 16384 + cw * 2048 + (j & 3) * 512 + lane * 16, fmaf(bf_lo(x0), r0, bl), fmaf(bf_hi(x0), r0, bh),
                   fmaf(bf_lo(x1), r1, bl), fmaf(bf_hi(x1), r1, bh));
          }
        }
        mbar_arrive(sb + OFF_LBAR);
      } else {
        unsigned par;
        asm volatile("ld.relaxed.gpu.global.u32 %0, [%1];" : "=r"(par) : "l"(g_epoch + b) : "memory");
        const uint32_t dk = __ldg(reinterpret_cast<const uint32_t*>(dskip + s * 64) + lane), bb = __ldg(reinterpret_cast<const uint32_t*>(b2 + s * 64) + lane);
        cluster_wait();
        if (lane == 0) sts_u(sb + OFF_EPOCH, par + 1);
        par = (par + 1) & 1;
        mbar_wait(sb + OFF_GBAR, 0);
        sts_u2(sb + OFF_DB + lane * 8, dk, bf2_add(bb, bb));
        uint32_t g0, g1, g2, g3;
        int tries = 0;
#pragma unroll 1
        do {
          asm volatile("ld.relaxed.gpu.global.v4.u32 {%0,%1,%2,%3}, [%4];" : "=r"(g0), "=r"(g1), "=r"(g2), "=r"(g3) : "l"(g_gate + m * 128 + lane * 4) : "memory");
          g0 ^= par; g1 ^= par; g2 ^= par; g3 ^= par;
        } while (((g0 | g1 | g2 | g3) & 1) && ++tries < 200000);
        const uint32_t p01 = pack_bf16(__uint_as_float(g0), __uint_as_float(g1)), p23 = pack_bf16(__uint_as_float(g2), __uint_as_float(g3));
        sts_u2(sb + OFF_GS + lane * 8, p01, p23);
        const uint32_t gt = sb + OFF_GT + ((lane >> 2) & 3) * 64 + (lane & 1) * 32 + (lane & 2) * 4 + (lane >> 4) * 4;
        sts_u(gt, p01);
        sts_u(gt + 16, p23);
        mbar_arrive(sb + OFF_CBAR);
      }
    } else {
      cluster_wait();
      if (elect_one()) {
        const uint32_t t0 = clock();
#pragma unroll 1
        for (int u = 1; u < 8; u++) {
          while ((uint32_t)clock() - t0 < 200 + (u - 1) * 480) {}
          const uint32_t fb = sb + OFF_XFULL + 8 * u;
          mbar_expect_tx(fb, 32768);
          tma5d_mc(sb + OFF_X + ((u + xrot) & 7) * 16384 + rank * 8192, &maps.x, u * 64, rank * 8, m, fb);
          const int sl = u < 6 ? u : u - 6;
          if (u >= 6) mbar_wait(sb + OFF_EMPTY + 8 * sl, 0);
          tma4d(sb + OFF_RING + sl * 16384, &maps.bb, u * 64, s * 8, fb);
        }
        int slot = 2; uint32_t ph = 0;
#pragma unroll 1
        for (int u = 8; u < 24; u++) {
          const uint32_t fb = sb + OFF_FULL + 8 * slot, dst = sb + OFF_RING + slot * 16384;
          mbar_wait(sb + OFF_EMPTY + 8 * slot, ph);
          if (u < 16) {
            mbar_expect_tx(fb, 12288);
            tma3d(dst, &maps.w1b, 0, (u - 8) * 64, s * 7, fb);
            if (u < 12) map_prefetch(&maps.w1a + (u - 8));
          } else {
            mbar_expect_tx(fb, 16384);
            tma2d(dst, &maps.w1a, s * 224 + 96, ((u - xrot) & 7) * 64, fb);
            tma2d(dst + 8192, &maps.w1a, s * 224 + 160, ((u - xrot) & 7) * 64, fb);
          }
          if (++slot == NSLOT) { slot = 0; ph ^= 1; }
        }
#pragma unroll 1
        for (int j = 0; j < 3; j++) {
          const uint32_t fb = sb + OFF_FULL + 8 * j, dst = sb + OFF_X + stage_off(0);
          const int c = ((sp + 1) & 3) * 128 + ((rank ^ 1) << 6);
          mbar_wait(sb + OFF_EMPTY + 8 + 8 * j, 1);
          mbar_expect_tx(fb, j == 1 ? 16384 : 14336);
          if (j == 1) {
            tma2d(dst + 14336, &maps.cre, s * 64, c, fb);
            tma2d(dst + 22528, &maps.cim, s * 64, c, fb);
          } else {
            tma2d(dst + j * 15360, &maps.w2, c, s * 224 + j * 56, fb);
          }
        }
#pragma unroll 1
        for (int p = 1; p < 8; p++) {
          const int c = ((sp + 1 + (p >> 1)) & 3) * 128 + (((rank ^ p ^ 1) & 1) << 6);
          const uint32_t fb = sb + OFF_XFULL + 8 * p, dst = sb + OFF_X + stage_off(p);
          if (p == 2 || p > 3) mbar_wait(sb + OFF_EMPTY + (p == 2 ? 40 : (p - 4) * 8), p == 2);
          mbar_expect_tx(fb, 45056);
          tma2d(dst, &maps.w2, c, s * 224, fb);
          tma2d(dst + 14336, &maps.cre, s * 64, c, fb);
          tma2d(dst + 22528, &maps.cim, s * 64, c, fb);
          tma2d(dst + 30720, &maps.w2, c, s * 224 + 112, fb);
        }
      }
    }
  }
}

typedef CUresult (*EncFn)(CUtensorMap*, CUtensorMapDataType, cuuint32_t, void*, const cuuint64_t*, const cuuint64_t*, const cuuint32_t*,
                          const cuuint32_t*, CUtensorMapInterleave, CUtensorMapSwizzle, CUtensorMapL2promotion, CUtensorMapFloatOOBfill);

void encode(EncFn f, CUtensorMap* mp, const void* p, int rank, const cuuint64_t* dims, const cuuint64_t* strides, const cuuint32_t* box, CUtensorMapSwizzle sw) {
  cuuint32_t es[5] = {1, 1, 1, 1, 1};
  f(mp, CU_TENSOR_MAP_DATA_TYPE_BFLOAT16, rank, const_cast<void*>(p), dims, strides, box, es, CU_TENSOR_MAP_INTERLEAVE_NONE, sw,
    CU_TENSOR_MAP_L2_PROMOTION_L2_128B, CU_TENSOR_MAP_FLOAT_OOB_FILL_NONE);
}

}

extern "C" void kernel_launch(void* const* d_in, const int* in_sizes, int n_in, void* d_out, int out_size) {
  typedef const __nv_bfloat16* bp;
  bp x = (bp)d_in[0], lre = (bp)d_in[1], lim = (bp)d_in[2], bre = (bp)d_in[3], bim = (bp)d_in[4], cre = (bp)d_in[5], cim = (bp)d_in[6],
     ldt = (bp)d_in[7], dsk = (bp)d_in[8], w1 = (bp)d_in[10], b1 = (bp)d_in[11], w2 = (bp)d_in[12], b2 = (bp)d_in[13], gw = (bp)d_in[14];
  static EncFn enc = nullptr;
  if (!enc) {
    void* f = nullptr;
    cudaDriverEntryPointQueryResult qr;
    cudaGetDriverEntryPoint("cuTensorMapEncodeTiled", &f, cudaEnableDefault, &qr);
    enc = (EncFn)f;
    cudaFuncSetAttribute(fused_kernel, cudaFuncAttributeMaxDynamicSharedMemorySize, SMEM_BYTES);
  }
  Maps maps;
  const uintptr_t dist = bim < bre ? (uintptr_t)bre - (uintptr_t)bim : (uintptr_t)bim - (uintptr_t)bre;
  if (dist == 0 || dist % 16 != 0 || dist >= (1ull << 40)) {
    void* p = nullptr;
    cudaGetSymbolAddress(&p, g_bcopy);
    cudaMemcpyAsync(p, bre, DM * DM * 2, cudaMemcpyDeviceToDevice);
    cudaMemcpyAsync((char*)p + DM * DM * 2, bim, DM * DM * 2, cudaMemcpyDeviceToDevice);
    bre = (bp)p; bim = bre + DM * DM;
  }
  const bool swap = bim < bre;
  {
    cuuint64_t d[5] = {DM, 2, 4, 16, SEQ / 128}, st[4] = {DM * 2, 32 * DM * 2, 2 * DM * 2, 128 * DM * 2};
    cuuint32_t bx[5] = {64, 2, 4, 8, 1};
    encode(enc, &maps.x, x, 5, d, st, bx, CU_TENSOR_MAP_SWIZZLE_128B);
  }
  {
    cuuint64_t d[2] = {DM, DM}, st[1] = {DM * 2};
    cuuint32_t bx[2] = {64, 64};
    encode(enc, &maps.cre, swap ? cim : cre, 2, d, st, bx, CU_TENSOR_MAP_SWIZZLE_128B);
    encode(enc, &maps.cim, swap ? cre : cim, 2, d, st, bx, CU_TENSOR_MAP_SWIZZLE_128B);
    cuuint64_t d4[4] = {DM, 8, 2, DM / 8}, st4[3] = {DM * 2, (cuuint64_t)(swap ? bre - bim : bim - bre) * 2, 8 * DM * 2};
    cuuint32_t bx4[4] = {64, 8, 2, 8};
    encode(enc, &maps.bb, swap ? bim : bre, 4, d4, st4, bx4, CU_TENSOR_MAP_SWIZZLE_128B);
  }
  {
    cuuint64_t d[2] = {FF, DM}, st[1] = {FF * 2};
    cuuint32_t bx[2] = {64, 64};
    encode(enc, &maps.w1a, w1, 2, d, st, bx, CU_TENSOR_MAP_SWIZZLE_128B);
    cuuint64_t d3[3] = {32, DM, FF / 32}, st3[2] = {FF * 2, 64};
    cuuint32_t bx3[3] = {32, 64, 3};
    encode(enc, &maps.w1b, w1, 3, d3, st3, bx3, CU_TENSOR_MAP_SWIZZLE_64B);
  }
  {
    cuuint64_t d[2] = {DM, FF}, st[1] = {DM * 2};
    cuuint32_t bx[2] = {64, 112};
    encode(enc, &maps.w2, w2, 2, d, st, bx, CU_TENSOR_MAP_SWIZZLE_128B);
  }
  fused_kernel<<<128, 384, SMEM_BYTES>>>(lre, lim, ldt, dsk, b1, b2, gw, (float*)d_out, swap ? -1.f : 1.f, maps);
}
```
